```python
import torch

def _softmax(x, axis=-1):
    return torch.softmax(x, dim=axis)
def _gelu(x):
    return torch.nn.functional.gelu(x, approximate="tanh")
def _silu(x):
    return torch.nn.functional.silu(x)
def _sigmoid(x):
    return torch.sigmoid(x)
def _layernorm(x, axis=-1, eps=1e-5):
    m = x.mean(dim=axis, keepdim=True)
    v = x.var(dim=axis, keepdim=True, unbiased=False)
    return (x - m) / torch.sqrt(v + eps)
def _scatter_add(tgt, idx, src, axis=0):
    return tgt.clone().index_add_(axis, idx, src)
def _segment_sum(src, seg, n):
    out = torch.zeros((n,) + src.shape[1:], dtype=src.dtype)
    return out.index_add_(0, seg, src)
def _pad(x, pw):
    flat = tuple(v for pair in reversed(pw) for v in pair)
    return torch.nn.functional.pad(x, flat)

kernel_name = 'recurrent_scan__ssm_conv_s4d__swiglu_ffn__prompt'

def setup_inputs():

    _w = (lambda a: (lambda t: t.to(torch.bfloat16) if t.is_floating_point() else t)(torch.as_tensor(a)))
    def _A_setup():
        Bsz, L, D, N = 1, 2048, 512, 128
        return {
            "u": _w((lambda *s: torch.randn(*s, dtype=torch.bfloat16) * 0.05)(Bsz, L, D)),
            "log_A_real": _w((lambda *s: torch.randn(*s, dtype=torch.bfloat16) * 6.4)(D, N) * 0.5),
            "A_imag": _w((lambda *s: torch.randn(*s, dtype=torch.bfloat16) * 0.05)(D, N) * 3.14),
            "C_real": _w((lambda *s: torch.randn(*s, dtype=torch.bfloat16) * 0.05)(D, N) / N ** 0.5),
            "C_imag": _w((lambda *s: torch.randn(*s, dtype=torch.bfloat16) * 0.05)(D, N) / N ** 0.5),
            "log_dt": _w((lambda *s: torch.randn(*s, dtype=torch.bfloat16) * 0.05)(D) * 0.5 - 4.0),
            "D_skip": _w((lambda *s: torch.randn(*s, dtype=torch.bfloat16) * 0.05)(D)),
        }
    _A_in = _A_setup()

    def _B_setup():
        B, S, D, F = 1, 2048, 512, 1376
        return {
            "x": _w((lambda *s: torch.randn(*s, dtype=torch.bfloat16) * 0.05)(B, S, D)),
            "w_gate": _w((lambda *s: torch.randn(*s, dtype=torch.bfloat16) * 0.05)(D, F)),
            "w_up": _w((lambda *s: torch.randn(*s, dtype=torch.bfloat16) * 0.05)(D, F)),
            "w_down": _w((lambda *s: torch.randn(*s, dtype=torch.bfloat16) * 0.05)(F, D)),
        }
    _B_in = _B_setup()

    return {
        "A_u": _A_in["u"],
        "A_log_A_real": _A_in["log_A_real"],
        "A_A_imag": _A_in["A_imag"],
        "A_C_real": _A_in["C_real"],
        "A_C_imag": _A_in["C_imag"],
        "A_log_dt": _A_in["log_dt"],
        "A_D_skip": _A_in["D_skip"],
        "B_x": _B_in["x"],
        "B_w_gate": _B_in["w_gate"],
        "B_w_up": _B_in["w_up"],
        "B_w_down": _B_in["w_down"],
    }

def reference(A_u, A_log_A_real, A_A_imag, A_C_real, A_C_imag, A_log_dt, A_D_skip, B_x, B_w_gate, B_w_up, B_w_down):
    def _A_ref(u, log_A_real, A_imag, C_real, C_imag, log_dt, D_skip):
        L = u.shape[1]
        dt = torch.exp(log_dt)
        A = -torch.exp(log_A_real) + 1j * A_imag
        C = (C_real + 1j * C_imag) * dt[:, None]
        pos = (lambda x, dt: x.to(dt))(torch.arange(L), log_dt.dtype)
        P = torch.exp((A * dt[:, None])[:, :, None] * pos[None, None, :])
        K = 2.0 * torch.einsum("dn,dnl->dl", C, P).real
        L2 = 2 * L
        u_t = (lambda x, *d: x.permute(*d))(u, 0, 2, 1)
        Kf = (lambda x, *a, **k: torch.fft.rfft(x.float(), *a, **k))(K, L2)
        Uf = (lambda x, *a, **k: torch.fft.rfft(x.float(), *a, **k))(u_t, L2)
        y = (lambda x, *a, **k: torch.fft.irfft(x, *a, **k).to(torch.bfloat16))(Uf * Kf[None, :, :], L2)[:, :, :L]
        y = (lambda x, *d: x.permute(*d))(y, 0, 2, 1)
        return y + u * D_skip[None, None, :]

    def _B_ref(x, w_gate, w_up, w_down):
        g = _silu(x @ w_gate)
        u = x @ w_up
        return (g * u) @ w_down

    x = A_u
    xn = _layernorm(x, axis=-1)
    s = _A_ref(xn, A_log_A_real, A_A_imag, A_C_real, A_C_imag, A_log_dt, A_D_skip)
    g = _silu(_B_ref(xn, B_w_gate, B_w_up, B_w_down))
    return x + s * g
```

```cpp
#include <cuda_runtime.h>
#include <cuda_bf16.h>
#include <cuda.h>
#include <stdint.h>

#define PROF 0

namespace {

constexpr int SEQ = 2048, DM = 512, FF = 1376;
constexpr int NCTA = 132;
constexpr int TOKG = 344;

constexpr uint32_t OFF_W = 0;
constexpr uint32_t OFF_X0 = 65536;
constexpr uint32_t OFF_X1 = 110592;
constexpr uint32_t OFF_CONV = 153600;
constexpr uint32_t CH_STRIDE = 17408;
constexpr uint32_t CH_T = 0;
constexpr uint32_t CH_A3 = 6272;
constexpr uint32_t CH_B3 = 10368;
constexpr uint32_t CH_U = 12416;
constexpr uint32_t CH_G = 16640;
constexpr uint32_t UPLANE = 2112;
constexpr uint32_t OFF_STATS = 223232;
constexpr uint32_t OFF_CSUM = 225984;
constexpr uint32_t OFF_RED = 226496;
constexpr uint32_t OFF_BAR = 228032;
constexpr uint32_t SMEM_BYTES = 228544 + 1024;

enum {
    B_FULLW = 0, B_EMPTYW = 4, B_FULLX = 8, B_EMPTYX = 12, B_FULLD = 16, B_EMPTYD = 22, B_FULLH = 28, B_EMPTYH = 33,
    B_STATS = 38, B_CONV = 39, B_U = 40, B_XO = 41, B_S = 42, B_GO = 43, B_CH0 = 44, B_LN = 45, B_EPI = 46, B_SIG = 48, B_COUNT = 50
};
enum { F_A = 0, F_H = 1, F_S = 13, F_EXIT = 17, F_COUNT = 18 };

__device__ uint4 g_xnT[DM * 256];
__device__ float2 g_stats[SEQ];
__device__ float g_csum[3 * 2 * 1408];
__device__ uint4 g_H[32 * 172 * 64];
__device__ uint2 g_S[256 * 1024];
__device__ unsigned g_flags[F_COUNT * 32];
#define STAMP(i) do {} while (0)

__device__ __forceinline__ uint32_t smem_u32(const void* p) { return (uint32_t)__cvta_generic_to_shared(p); }
__device__ __forceinline__ void mbar_init(uint32_t bar, uint32_t cnt) { asm volatile("mbarrier.init.shared::cta.b64 [%0], %1;" :: "r"(bar), "r"(cnt) : "memory"); }
__device__ __forceinline__ void mbar_expect(uint32_t bar, uint32_t bytes) { asm volatile("mbarrier.arrive.expect_tx.shared::cta.b64 _, [%0], %1;" :: "r"(bar), "r"(bytes) : "memory"); }
__device__ __forceinline__ void mbar_arrive(uint32_t bar) { asm volatile("mbarrier.arrive.shared::cta.b64 _, [%0];" :: "r"(bar) : "memory"); }
__device__ __forceinline__ void mbar_wait(uint32_t bar, uint32_t parity) {
    uint32_t ok, n = 0;
    do {
        asm volatile("{.reg .pred p; mbarrier.try_wait.parity.shared::cta.b64 p, [%1], %2; selp.u32 %0, 1, 0, p;}" : "=r"(ok) : "r"(bar), "r"(parity) : "memory");
        if (!ok && ++n > (1u << 22)) __trap();
    } while (!ok);
}
__device__ __forceinline__ void mbar_wait_c(uint32_t bar, uint32_t parity) {
    asm volatile("{.reg .pred p; .reg .u32 n; mov.u32 n, 0;\n"
                 "LAB_WAIT: mbarrier.try_wait.parity.shared::cta.b64 p, [%0], %1;\n"
                 "@p bra LAB_DONE; add.u32 n, n, 1; setp.lt.u32 p, n, 0x200000; @p bra LAB_WAIT;\n"
                 "LAB_DONE: }" :: "r"(bar), "r"(parity) : "memory");
}
__device__ __forceinline__ bool elect_one() { uint32_t p; asm volatile("{.reg .pred P; elect.sync _|P, 0xffffffff; selp.u32 %0, 1, 0, P;}" : "=r"(p)); return p; }
__device__ __forceinline__ void tma2d(uint32_t dst, const CUtensorMap* m, int c0, int c1, uint32_t bar) {
    asm volatile("cp.async.bulk.tensor.2d.shared::cluster.global.mbarrier::complete_tx::bytes [%0], [%1, {%3, %4}], [%2];"
        :: "r"(dst), "l"(m), "r"(bar), "r"(c0), "r"(c1) : "memory");
}
__device__ __forceinline__ void tma2d_store(const CUtensorMap* m, int c0, int c1, uint32_t src) {
    asm volatile("cp.async.bulk.tensor.2d.global.shared::cta.bulk_group [%0, {%2, %3}], [%1];" :: "l"(m), "r"(src), "r"(c0), "r"(c1) : "memory");
}
__device__ __forceinline__ void bulk_load(uint32_t dst, const void* src, uint32_t bytes, uint32_t bar) {
    asm volatile("cp.async.bulk.shared::cluster.global.mbarrier::complete_tx::bytes [%0], [%1], %2, [%3];" :: "r"(dst), "l"(src), "r"(bytes), "r"(bar) : "memory");
}
__device__ __forceinline__ void fence_async() { asm volatile("fence.proxy.async;" ::: "memory"); }
__device__ __forceinline__ void flag_wait(int f, unsigned target) {
    const unsigned* p = g_flags + f * 32; unsigned v, n = 0;
    while (true) {
        asm volatile("ld.acquire.gpu.global.u32 %0, [%1];" : "=r"(v) : "l"(p) : "memory");
        if (v >= target) break;
        if (++n > (1u << 22)) __trap();
        __nanosleep(20);
    }
}
__device__ __forceinline__ void flag_signal(int f) {
    asm volatile("fence.acq_rel.gpu;" ::: "memory");
    asm volatile("red.relaxed.gpu.global.add.u32 [%0], 1;" :: "l"(g_flags + f * 32) : "memory");
}
__device__ __forceinline__ void exit_count() {
    unsigned old = atomicAdd(g_flags + F_EXIT * 32, 1u);
    if (old == NCTA - 1) {
        #pragma unroll 1
        for (int i = 0; i < F_COUNT; i++) g_flags[i * 32] = 0;
    }
}
__device__ __forceinline__ void bar_sync(int id) { asm volatile("bar.sync %0, 128;" :: "r"(id) : "memory"); }
__device__ __forceinline__ uint64_t mkdesc(uint32_t addr, uint32_t lbo, uint32_t sbo, uint32_t swz) {
    return (uint64_t)((addr & 0x3FFFF) >> 4) | ((uint64_t)(lbo >> 4) << 16) | ((uint64_t)(sbo >> 4) << 32) | ((uint64_t)swz << 62);
}
#define WG_FENCE() asm volatile("wgmma.fence.sync.aligned;" ::: "memory")
#define WG_COMMIT() asm volatile("wgmma.commit_group.sync.aligned;" ::: "memory")
#define WG_WAIT(n) asm volatile("wgmma.wait_group.sync.aligned " #n ";" ::: "memory")
template <int N> __device__ __forceinline__ void fence_acc(float (&d)[N]) {
    #pragma unroll
    for (int i = 0; i < N; i++) asm volatile("" : "+f"(d[i]) :: "memory");
}
__device__ __forceinline__ uint32_t pack2(float lo, float hi) { uint32_t r; asm("cvt.rn.bf16x2.f32 %0, %1, %2;" : "=r"(r) : "f"(hi), "f"(lo)); return r; }
__device__ __forceinline__ float bf_lo(uint32_t v) { return __uint_as_float(v << 16); }
__device__ __forceinline__ float bf_hi(uint32_t v) { return __uint_as_float(v & 0xffff0000u); }
__device__ __forceinline__ float bf_round(float v) { return __bfloat162float(__float2bfloat16_rn(v)); }
__device__ __forceinline__ float tanh_fast(float v) { float r; asm("tanh.approx.f32 %0, %1;" : "=f"(r) : "f"(v)); return r; }
__device__ __forceinline__ uint4 lds128(uint32_t a) { uint4 v; asm volatile("ld.shared.v4.b32 {%0,%1,%2,%3}, [%4];" : "=r"(v.x), "=r"(v.y), "=r"(v.z), "=r"(v.w) : "r"(a)); return v; }
__device__ __forceinline__ uint2 lds64(uint32_t a) { uint2 v; asm volatile("ld.shared.v2.b32 {%0,%1}, [%2];" : "=r"(v.x), "=r"(v.y) : "r"(a)); return v; }
__device__ __forceinline__ float ldsf(uint32_t a) { float v; asm volatile("ld.shared.f32 %0, [%1];" : "=f"(v) : "r"(a)); return v; }
__device__ __forceinline__ void sts128(uint32_t a, uint32_t x, uint32_t y, uint32_t z, uint32_t w) { asm volatile("st.shared.v4.b32 [%0], {%1,%2,%3,%4};" :: "r"(a), "r"(x), "r"(y), "r"(z), "r"(w) : "memory"); }
__device__ __forceinline__ void sts64(uint32_t a, uint32_t x, uint32_t y) { asm volatile("st.shared.v2.b32 [%0], {%1,%2};" :: "r"(a), "r"(x), "r"(y) : "memory"); }
__device__ __forceinline__ void stsf(uint32_t a, float x) { asm volatile("st.shared.f32 [%0], %1;" :: "r"(a), "f"(x) : "memory"); }
__device__ __forceinline__ void sts16(uint32_t a, uint32_t x) { asm volatile("st.shared.b16 [%0], %1;" :: "r"(a), "h"((unsigned short)x) : "memory"); }
__device__ __forceinline__ uint4 ldg128(const void* p) { uint4 v; asm volatile("ld.global.nc.L1::no_allocate.v4.b32 {%0,%1,%2,%3}, [%4];" : "=r"(v.x), "=r"(v.y), "=r"(v.z), "=r"(v.w) : "l"(p)); return v; }

template<int N> __device__ __forceinline__ void wg_rs(float (&d)[64], uint32_t a0, uint32_t a1, uint32_t a2, uint32_t a3, uint64_t db, int sc);
template<> __device__ __forceinline__ void wg_rs<128>(float (&d)[64], uint32_t a0, uint32_t a1, uint32_t a2, uint32_t a3, uint64_t db, int sc) {
  asm volatile("{.reg .pred p; setp.ne.b32 p, %69, 0; wgmma.mma_async.sync.aligned.m64n128k16.f32.bf16.bf16 {%0,%1,%2,%3,%4,%5,%6,%7,%8,%9,%10,%11,%12,%13,%14,%15,%16,%17,%18,%19,%20,%21,%22,%23,%24,%25,%26,%27,%28,%29,%30,%31,%32,%33,%34,%35,%36,%37,%38,%39,%40,%41,%42,%43,%44,%45,%46,%47,%48,%49,%50,%51,%52,%53,%54,%55,%56,%57,%58,%59,%60,%61,%62,%63}, {%64,%65,%66,%67}, %68, p, 1, 1, 0;}"
    : "+f"(d[0]),"+f"(d[1]),"+f"(d[2]),"+f"(d[3]),"+f"(d[4]),"+f"(d[5]),"+f"(d[6]),"+f"(d[7]),"+f"(d[8]),"+f"(d[9]),"+f"(d[10]),"+f"(d[11]),"+f"(d[12]),"+f"(d[13]),"+f"(d[14]),"+f"(d[15]),"+f"(d[16]),"+f"(d[17]),"+f"(d[18]),"+f"(d[19]),"+f"(d[20]),"+f"(d[21]),"+f"(d[22]),"+f"(d[23]),"+f"(d[24]),"+f"(d[25]),"+f"(d[26]),"+f"(d[27]),"+f"(d[28]),"+f"(d[29]),"+f"(d[30]),"+f"(d[31]),"+f"(d[32]),"+f"(d[33]),"+f"(d[34]),"+f"(d[35]),"+f"(d[36]),"+f"(d[37]),"+f"(d[38]),"+f"(d[39]),"+f"(d[40]),"+f"(d[41]),"+f"(d[42]),"+f"(d[43]),"+f"(d[44]),"+f"(d[45]),"+f"(d[46]),"+f"(d[47]),"+f"(d[48]),"+f"(d[49]),"+f"(d[50]),"+f"(d[51]),"+f"(d[52]),"+f"(d[53]),"+f"(d[54]),"+f"(d[55]),"+f"(d[56]),"+f"(d[57]),"+f"(d[58]),"+f"(d[59]),"+f"(d[60]),"+f"(d[61]),"+f"(d[62]),"+f"(d[63]) : "r"(a0), "r"(a1), "r"(a2), "r"(a3), "l"(db), "r"(sc));
}
template<> __device__ __forceinline__ void wg_rs<120>(float (&d)[64], uint32_t a0, uint32_t a1, uint32_t a2, uint32_t a3, uint64_t db, int sc) {
  asm volatile("{.reg .pred p; setp.ne.b32 p, %65, 0; wgmma.mma_async.sync.aligned.m64n120k16.f32.bf16.bf16 {%0,%1,%2,%3,%4,%5,%6,%7,%8,%9,%10,%11,%12,%13,%14,%15,%16,%17,%18,%19,%20,%21,%22,%23,%24,%25,%26,%27,%28,%29,%30,%31,%32,%33,%34,%35,%36,%37,%38,%39,%40,%41,%42,%43,%44,%45,%46,%47,%48,%49,%50,%51,%52,%53,%54,%55,%56,%57,%58,%59}, {%60,%61,%62,%63}, %64, p, 1, 1, 0;}"
    : "+f"(d[0]),"+f"(d[1]),"+f"(d[2]),"+f"(d[3]),"+f"(d[4]),"+f"(d[5]),"+f"(d[6]),"+f"(d[7]),"+f"(d[8]),"+f"(d[9]),"+f"(d[10]),"+f"(d[11]),"+f"(d[12]),"+f"(d[13]),"+f"(d[14]),"+f"(d[15]),"+f"(d[16]),"+f"(d[17]),"+f"(d[18]),"+f"(d[19]),"+f"(d[20]),"+f"(d[21]),"+f"(d[22]),"+f"(d[23]),"+f"(d[24]),"+f"(d[25]),"+f"(d[26]),"+f"(d[27]),"+f"(d[28]),"+f"(d[29]),"+f"(d[30]),"+f"(d[31]),"+f"(d[32]),"+f"(d[33]),"+f"(d[34]),"+f"(d[35]),"+f"(d[36]),"+f"(d[37]),"+f"(d[38]),"+f"(d[39]),"+f"(d[40]),"+f"(d[41]),"+f"(d[42]),"+f"(d[43]),"+f"(d[44]),"+f"(d[45]),"+f"(d[46]),"+f"(d[47]),"+f"(d[48]),"+f"(d[49]),"+f"(d[50]),"+f"(d[51]),"+f"(d[52]),"+f"(d[53]),"+f"(d[54]),"+f"(d[55]),"+f"(d[56]),"+f"(d[57]),"+f"(d[58]),"+f"(d[59]) : "r"(a0), "r"(a1), "r"(a2), "r"(a3), "l"(db), "r"(sc));
}
template<> __device__ __forceinline__ void wg_rs<112>(float (&d)[64], uint32_t a0, uint32_t a1, uint32_t a2, uint32_t a3, uint64_t db, int sc) {
  asm volatile("{.reg .pred p; setp.ne.b32 p, %61, 0; wgmma.mma_async.sync.aligned.m64n112k16.f32.bf16.bf16 {%0,%1,%2,%3,%4,%5,%6,%7,%8,%9,%10,%11,%12,%13,%14,%15,%16,%17,%18,%19,%20,%21,%22,%23,%24,%25,%26,%27,%28,%29,%30,%31,%32,%33,%34,%35,%36,%37,%38,%39,%40,%41,%42,%43,%44,%45,%46,%47,%48,%49,%50,%51,%52,%53,%54,%55}, {%56,%57,%58,%59}, %60, p, 1, 1, 0;}"
    : "+f"(d[0]),"+f"(d[1]),"+f"(d[2]),"+f"(d[3]),"+f"(d[4]),"+f"(d[5]),"+f"(d[6]),"+f"(d[7]),"+f"(d[8]),"+f"(d[9]),"+f"(d[10]),"+f"(d[11]),"+f"(d[12]),"+f"(d[13]),"+f"(d[14]),"+f"(d[15]),"+f"(d[16]),"+f"(d[17]),"+f"(d[18]),"+f"(d[19]),"+f"(d[20]),"+f"(d[21]),"+f"(d[22]),"+f"(d[23]),"+f"(d[24]),"+f"(d[25]),"+f"(d[26]),"+f"(d[27]),"+f"(d[28]),"+f"(d[29]),"+f"(d[30]),"+f"(d[31]),"+f"(d[32]),"+f"(d[33]),"+f"(d[34]),"+f"(d[35]),"+f"(d[36]),"+f"(d[37]),"+f"(d[38]),"+f"(d[39]),"+f"(d[40]),"+f"(d[41]),"+f"(d[42]),"+f"(d[43]),"+f"(d[44]),"+f"(d[45]),"+f"(d[46]),"+f"(d[47]),"+f"(d[48]),"+f"(d[49]),"+f"(d[50]),"+f"(d[51]),"+f"(d[52]),"+f"(d[53]),"+f"(d[54]),"+f"(d[55]) : "r"(a0), "r"(a1), "r"(a2), "r"(a3), "l"(db), "r"(sc));
}
template<> __device__ __forceinline__ void wg_rs<104>(float (&d)[64], uint32_t a0, uint32_t a1, uint32_t a2, uint32_t a3, uint64_t db, int sc) {
  asm volatile("{.reg .pred p; setp.ne.b32 p, %57, 0; wgmma.mma_async.sync.aligned.m64n104k16.f32.bf16.bf16 {%0,%1,%2,%3,%4,%5,%6,%7,%8,%9,%10,%11,%12,%13,%14,%15,%16,%17,%18,%19,%20,%21,%22,%23,%24,%25,%26,%27,%28,%29,%30,%31,%32,%33,%34,%35,%36,%37,%38,%39,%40,%41,%42,%43,%44,%45,%46,%47,%48,%49,%50,%51}, {%52,%53,%54,%55}, %56, p, 1, 1, 0;}"
    : "+f"(d[0]),"+f"(d[1]),"+f"(d[2]),"+f"(d[3]),"+f"(d[4]),"+f"(d[5]),"+f"(d[6]),"+f"(d[7]),"+f"(d[8]),"+f"(d[9]),"+f"(d[10]),"+f"(d[11]),"+f"(d[12]),"+f"(d[13]),"+f"(d[14]),"+f"(d[15]),"+f"(d[16]),"+f"(d[17]),"+f"(d[18]),"+f"(d[19]),"+f"(d[20]),"+f"(d[21]),"+f"(d[22]),"+f"(d[23]),"+f"(d[24]),"+f"(d[25]),"+f"(d[26]),"+f"(d[27]),"+f"(d[28]),"+f"(d[29]),"+f"(d[30]),"+f"(d[31]),"+f"(d[32]),"+f"(d[33]),"+f"(d[34]),"+f"(d[35]),"+f"(d[36]),"+f"(d[37]),"+f"(d[38]),"+f"(d[39]),"+f"(d[40]),"+f"(d[41]),"+f"(d[42]),"+f"(d[43]),"+f"(d[44]),"+f"(d[45]),"+f"(d[46]),"+f"(d[47]),"+f"(d[48]),"+f"(d[49]),"+f"(d[50]),"+f"(d[51]) : "r"(a0), "r"(a1), "r"(a2), "r"(a3), "l"(db), "r"(sc));
}
template<> __device__ __forceinline__ void wg_rs<96>(float (&d)[64], uint32_t a0, uint32_t a1, uint32_t a2, uint32_t a3, uint64_t db, int sc) {
  asm volatile("{.reg .pred p; setp.ne.b32 p, %53, 0; wgmma.mma_async.sync.aligned.m64n96k16.f32.bf16.bf16 {%0,%1,%2,%3,%4,%5,%6,%7,%8,%9,%10,%11,%12,%13,%14,%15,%16,%17,%18,%19,%20,%21,%22,%23,%24,%25,%26,%27,%28,%29,%30,%31,%32,%33,%34,%35,%36,%37,%38,%39,%40,%41,%42,%43,%44,%45,%46,%47}, {%48,%49,%50,%51}, %52, p, 1, 1, 0;}"
    : "+f"(d[0]),"+f"(d[1]),"+f"(d[2]),"+f"(d[3]),"+f"(d[4]),"+f"(d[5]),"+f"(d[6]),"+f"(d[7]),"+f"(d[8]),"+f"(d[9]),"+f"(d[10]),"+f"(d[11]),"+f"(d[12]),"+f"(d[13]),"+f"(d[14]),"+f"(d[15]),"+f"(d[16]),"+f"(d[17]),"+f"(d[18]),"+f"(d[19]),"+f"(d[20]),"+f"(d[21]),"+f"(d[22]),"+f"(d[23]),"+f"(d[24]),"+f"(d[25]),"+f"(d[26]),"+f"(d[27]),"+f"(d[28]),"+f"(d[29]),"+f"(d[30]),"+f"(d[31]),"+f"(d[32]),"+f"(d[33]),"+f"(d[34]),"+f"(d[35]),"+f"(d[36]),"+f"(d[37]),"+f"(d[38]),"+f"(d[39]),"+f"(d[40]),"+f"(d[41]),"+f"(d[42]),"+f"(d[43]),"+f"(d[44]),"+f"(d[45]),"+f"(d[46]),"+f"(d[47]) : "r"(a0), "r"(a1), "r"(a2), "r"(a3), "l"(db), "r"(sc));
}
template<> __device__ __forceinline__ void wg_rs<88>(float (&d)[64], uint32_t a0, uint32_t a1, uint32_t a2, uint32_t a3, uint64_t db, int sc) {
  asm volatile("{.reg .pred p; setp.ne.b32 p, %49, 0; wgmma.mma_async.sync.aligned.m64n88k16.f32.bf16.bf16 {%0,%1,%2,%3,%4,%5,%6,%7,%8,%9,%10,%11,%12,%13,%14,%15,%16,%17,%18,%19,%20,%21,%22,%23,%24,%25,%26,%27,%28,%29,%30,%31,%32,%33,%34,%35,%36,%37,%38,%39,%40,%41,%42,%43}, {%44,%45,%46,%47}, %48, p, 1, 1, 0;}"
    : "+f"(d[0]),"+f"(d[1]),"+f"(d[2]),"+f"(d[3]),"+f"(d[4]),"+f"(d[5]),"+f"(d[6]),"+f"(d[7]),"+f"(d[8]),"+f"(d[9]),"+f"(d[10]),"+f"(d[11]),"+f"(d[12]),"+f"(d[13]),"+f"(d[14]),"+f"(d[15]),"+f"(d[16]),"+f"(d[17]),"+f"(d[18]),"+f"(d[19]),"+f"(d[20]),"+f"(d[21]),"+f"(d[22]),"+f"(d[23]),"+f"(d[24]),"+f"(d[25]),"+f"(d[26]),"+f"(d[27]),"+f"(d[28]),"+f"(d[29]),"+f"(d[30]),"+f"(d[31]),"+f"(d[32]),"+f"(d[33]),"+f"(d[34]),"+f"(d[35]),"+f"(d[36]),"+f"(d[37]),"+f"(d[38]),"+f"(d[39]),"+f"(d[40]),"+f"(d[41]),"+f"(d[42]),"+f"(d[43]) : "r"(a0), "r"(a1), "r"(a2), "r"(a3), "l"(db), "r"(sc));
}
template<> __device__ __forceinline__ void wg_rs<80>(float (&d)[64], uint32_t a0, uint32_t a1, uint32_t a2, uint32_t a3, uint64_t db, int sc) {
  asm volatile("{.reg .pred p; setp.ne.b32 p, %45, 0; wgmma.mma_async.sync.aligned.m64n80k16.f32.bf16.bf16 {%0,%1,%2,%3,%4,%5,%6,%7,%8,%9,%10,%11,%12,%13,%14,%15,%16,%17,%18,%19,%20,%21,%22,%23,%24,%25,%26,%27,%28,%29,%30,%31,%32,%33,%34,%35,%36,%37,%38,%39}, {%40,%41,%42,%43}, %44, p, 1, 1, 0;}"
    : "+f"(d[0]),"+f"(d[1]),"+f"(d[2]),"+f"(d[3]),"+f"(d[4]),"+f"(d[5]),"+f"(d[6]),"+f"(d[7]),"+f"(d[8]),"+f"(d[9]),"+f"(d[10]),"+f"(d[11]),"+f"(d[12]),"+f"(d[13]),"+f"(d[14]),"+f"(d[15]),"+f"(d[16]),"+f"(d[17]),"+f"(d[18]),"+f"(d[19]),"+f"(d[20]),"+f"(d[21]),"+f"(d[22]),"+f"(d[23]),"+f"(d[24]),"+f"(d[25]),"+f"(d[26]),"+f"(d[27]),"+f"(d[28]),"+f"(d[29]),"+f"(d[30]),"+f"(d[31]),"+f"(d[32]),"+f"(d[33]),"+f"(d[34]),"+f"(d[35]),"+f"(d[36]),"+f"(d[37]),"+f"(d[38]),"+f"(d[39]) : "r"(a0), "r"(a1), "r"(a2), "r"(a3), "l"(db), "r"(sc));
}
template<> __device__ __forceinline__ void wg_rs<72>(float (&d)[64], uint32_t a0, uint32_t a1, uint32_t a2, uint32_t a3, uint64_t db, int sc) {
  asm volatile("{.reg .pred p; setp.ne.b32 p, %41, 0; wgmma.mma_async.sync.aligned.m64n72k16.f32.bf16.bf16 {%0,%1,%2,%3,%4,%5,%6,%7,%8,%9,%10,%11,%12,%13,%14,%15,%16,%17,%18,%19,%20,%21,%22,%23,%24,%25,%26,%27,%28,%29,%30,%31,%32,%33,%34,%35}, {%36,%37,%38,%39}, %40, p, 1, 1, 0;}"
    : "+f"(d[0]),"+f"(d[1]),"+f"(d[2]),"+f"(d[3]),"+f"(d[4]),"+f"(d[5]),"+f"(d[6]),"+f"(d[7]),"+f"(d[8]),"+f"(d[9]),"+f"(d[10]),"+f"(d[11]),"+f"(d[12]),"+f"(d[13]),"+f"(d[14]),"+f"(d[15]),"+f"(d[16]),"+f"(d[17]),"+f"(d[18]),"+f"(d[19]),"+f"(d[20]),"+f"(d[21]),"+f"(d[22]),"+f"(d[23]),"+f"(d[24]),"+f"(d[25]),"+f"(d[26]),"+f"(d[27]),"+f"(d[28]),"+f"(d[29]),"+f"(d[30]),"+f"(d[31]),"+f"(d[32]),"+f"(d[33]),"+f"(d[34]),"+f"(d[35]) : "r"(a0), "r"(a1), "r"(a2), "r"(a3), "l"(db), "r"(sc));
}
template<> __device__ __forceinline__ void wg_rs<64>(float (&d)[64], uint32_t a0, uint32_t a1, uint32_t a2, uint32_t a3, uint64_t db, int sc) {
  asm volatile("{.reg .pred p; setp.ne.b32 p, %37, 0; wgmma.mma_async.sync.aligned.m64n64k16.f32.bf16.bf16 {%0,%1,%2,%3,%4,%5,%6,%7,%8,%9,%10,%11,%12,%13,%14,%15,%16,%17,%18,%19,%20,%21,%22,%23,%24,%25,%26,%27,%28,%29,%30,%31}, {%32,%33,%34,%35}, %36, p, 1, 1, 0;}"
    : "+f"(d[0]),"+f"(d[1]),"+f"(d[2]),"+f"(d[3]),"+f"(d[4]),"+f"(d[5]),"+f"(d[6]),"+f"(d[7]),"+f"(d[8]),"+f"(d[9]),"+f"(d[10]),"+f"(d[11]),"+f"(d[12]),"+f"(d[13]),"+f"(d[14]),"+f"(d[15]),"+f"(d[16]),"+f"(d[17]),"+f"(d[18]),"+f"(d[19]),"+f"(d[20]),"+f"(d[21]),"+f"(d[22]),"+f"(d[23]),"+f"(d[24]),"+f"(d[25]),"+f"(d[26]),"+f"(d[27]),"+f"(d[28]),"+f"(d[29]),"+f"(d[30]),"+f"(d[31]) : "r"(a0), "r"(a1), "r"(a2), "r"(a3), "l"(db), "r"(sc));
}
__device__ __forceinline__ void wg_tt128(float (&d)[64], uint64_t da, uint64_t db, int sc) {
  asm volatile("{.reg .pred p; setp.ne.b32 p, %66, 0; wgmma.mma_async.sync.aligned.m64n128k16.f32.bf16.bf16 {%0,%1,%2,%3,%4,%5,%6,%7,%8,%9,%10,%11,%12,%13,%14,%15,%16,%17,%18,%19,%20,%21,%22,%23,%24,%25,%26,%27,%28,%29,%30,%31,%32,%33,%34,%35,%36,%37,%38,%39,%40,%41,%42,%43,%44,%45,%46,%47,%48,%49,%50,%51,%52,%53,%54,%55,%56,%57,%58,%59,%60,%61,%62,%63}, %64, %65, p, 1, 1, 1, 1;}"
    : "+f"(d[0]),"+f"(d[1]),"+f"(d[2]),"+f"(d[3]),"+f"(d[4]),"+f"(d[5]),"+f"(d[6]),"+f"(d[7]),"+f"(d[8]),"+f"(d[9]),"+f"(d[10]),"+f"(d[11]),"+f"(d[12]),"+f"(d[13]),"+f"(d[14]),"+f"(d[15]),"+f"(d[16]),"+f"(d[17]),"+f"(d[18]),"+f"(d[19]),"+f"(d[20]),"+f"(d[21]),"+f"(d[22]),"+f"(d[23]),"+f"(d[24]),"+f"(d[25]),"+f"(d[26]),"+f"(d[27]),"+f"(d[28]),"+f"(d[29]),"+f"(d[30]),"+f"(d[31]),"+f"(d[32]),"+f"(d[33]),"+f"(d[34]),"+f"(d[35]),"+f"(d[36]),"+f"(d[37]),"+f"(d[38]),"+f"(d[39]),"+f"(d[40]),"+f"(d[41]),"+f"(d[42]),"+f"(d[43]),"+f"(d[44]),"+f"(d[45]),"+f"(d[46]),"+f"(d[47]),"+f"(d[48]),"+f"(d[49]),"+f"(d[50]),"+f"(d[51]),"+f"(d[52]),"+f"(d[53]),"+f"(d[54]),"+f"(d[55]),"+f"(d[56]),"+f"(d[57]),"+f"(d[58]),"+f"(d[59]),"+f"(d[60]),"+f"(d[61]),"+f"(d[62]),"+f"(d[63]) : "l"(da), "l"(db), "r"(sc));
}
__device__ __forceinline__ void wg_tt64(float (&d)[64], uint64_t da, uint64_t db, int sc) {
  asm volatile("{.reg .pred p; setp.ne.b32 p, %34, 0; wgmma.mma_async.sync.aligned.m64n64k16.f32.bf16.bf16 {%0,%1,%2,%3,%4,%5,%6,%7,%8,%9,%10,%11,%12,%13,%14,%15,%16,%17,%18,%19,%20,%21,%22,%23,%24,%25,%26,%27,%28,%29,%30,%31}, %32, %33, p, 1, 1, 1, 1;}"
    : "+f"(d[0]),"+f"(d[1]),"+f"(d[2]),"+f"(d[3]),"+f"(d[4]),"+f"(d[5]),"+f"(d[6]),"+f"(d[7]),"+f"(d[8]),"+f"(d[9]),"+f"(d[10]),"+f"(d[11]),"+f"(d[12]),"+f"(d[13]),"+f"(d[14]),"+f"(d[15]),"+f"(d[16]),"+f"(d[17]),"+f"(d[18]),"+f"(d[19]),"+f"(d[20]),"+f"(d[21]),"+f"(d[22]),"+f"(d[23]),"+f"(d[24]),"+f"(d[25]),"+f"(d[26]),"+f"(d[27]),"+f"(d[28]),"+f"(d[29]),"+f"(d[30]),"+f"(d[31]) : "l"(da), "l"(db), "r"(sc));
}
__device__ __forceinline__ void wg_tt32(float (&d)[64], uint64_t da, uint64_t db, int sc) {
  asm volatile("{.reg .pred p; setp.ne.b32 p, %18, 0; wgmma.mma_async.sync.aligned.m64n32k16.f32.bf16.bf16 {%0,%1,%2,%3,%4,%5,%6,%7,%8,%9,%10,%11,%12,%13,%14,%15}, %16, %17, p, 1, 1, 1, 1;}"
    : "+f"(d[0]),"+f"(d[1]),"+f"(d[2]),"+f"(d[3]),"+f"(d[4]),"+f"(d[5]),"+f"(d[6]),"+f"(d[7]),"+f"(d[8]),"+f"(d[9]),"+f"(d[10]),"+f"(d[11]),"+f"(d[12]),"+f"(d[13]),"+f"(d[14]),"+f"(d[15]) : "l"(da), "l"(db), "r"(sc));
}
__device__ __forceinline__ void wg_g1(float (&d)[88], uint64_t da, uint64_t db, int sc) {
  asm volatile("{.reg .pred p; setp.ne.b32 p, %90, 0; wgmma.mma_async.sync.aligned.m64n176k16.f32.bf16.bf16 {%0,%1,%2,%3,%4,%5,%6,%7,%8,%9,%10,%11,%12,%13,%14,%15,%16,%17,%18,%19,%20,%21,%22,%23,%24,%25,%26,%27,%28,%29,%30,%31,%32,%33,%34,%35,%36,%37,%38,%39,%40,%41,%42,%43,%44,%45,%46,%47,%48,%49,%50,%51,%52,%53,%54,%55,%56,%57,%58,%59,%60,%61,%62,%63,%64,%65,%66,%67,%68,%69,%70,%71,%72,%73,%74,%75,%76,%77,%78,%79,%80,%81,%82,%83,%84,%85,%86,%87}, %88, %89, p, 1, 1, 1, 0;}"
    : "+f"(d[0]),"+f"(d[1]),"+f"(d[2]),"+f"(d[3]),"+f"(d[4]),"+f"(d[5]),"+f"(d[6]),"+f"(d[7]),"+f"(d[8]),"+f"(d[9]),"+f"(d[10]),"+f"(d[11]),"+f"(d[12]),"+f"(d[13]),"+f"(d[14]),"+f"(d[15]),"+f"(d[16]),"+f"(d[17]),"+f"(d[18]),"+f"(d[19]),"+f"(d[20]),"+f"(d[21]),"+f"(d[22]),"+f"(d[23]),"+f"(d[24]),"+f"(d[25]),"+f"(d[26]),"+f"(d[27]),"+f"(d[28]),"+f"(d[29]),"+f"(d[30]),"+f"(d[31]),"+f"(d[32]),"+f"(d[33]),"+f"(d[34]),"+f"(d[35]),"+f"(d[36]),"+f"(d[37]),"+f"(d[38]),"+f"(d[39]),"+f"(d[40]),"+f"(d[41]),"+f"(d[42]),"+f"(d[43]),"+f"(d[44]),"+f"(d[45]),"+f"(d[46]),"+f"(d[47]),"+f"(d[48]),"+f"(d[49]),"+f"(d[50]),"+f"(d[51]),"+f"(d[52]),"+f"(d[53]),"+f"(d[54]),"+f"(d[55]),"+f"(d[56]),"+f"(d[57]),"+f"(d[58]),"+f"(d[59]),"+f"(d[60]),"+f"(d[61]),"+f"(d[62]),"+f"(d[63]),"+f"(d[64]),"+f"(d[65]),"+f"(d[66]),"+f"(d[67]),"+f"(d[68]),"+f"(d[69]),"+f"(d[70]),"+f"(d[71]),"+f"(d[72]),"+f"(d[73]),"+f"(d[74]),"+f"(d[75]),"+f"(d[76]),"+f"(d[77]),"+f"(d[78]),"+f"(d[79]),"+f"(d[80]),"+f"(d[81]),"+f"(d[82]),"+f"(d[83]),"+f"(d[84]),"+f"(d[85]),"+f"(d[86]),"+f"(d[87]) : "l"(da), "l"(db), "r"(sc));
}
__device__ __forceinline__ void wg_g1(float (&d)[84], uint64_t da, uint64_t db, int sc) {
  asm volatile("{.reg .pred p; setp.ne.b32 p, %86, 0; wgmma.mma_async.sync.aligned.m64n168k16.f32.bf16.bf16 {%0,%1,%2,%3,%4,%5,%6,%7,%8,%9,%10,%11,%12,%13,%14,%15,%16,%17,%18,%19,%20,%21,%22,%23,%24,%25,%26,%27,%28,%29,%30,%31,%32,%33,%34,%35,%36,%37,%38,%39,%40,%41,%42,%43,%44,%45,%46,%47,%48,%49,%50,%51,%52,%53,%54,%55,%56,%57,%58,%59,%60,%61,%62,%63,%64,%65,%66,%67,%68,%69,%70,%71,%72,%73,%74,%75,%76,%77,%78,%79,%80,%81,%82,%83}, %84, %85, p, 1, 1, 1, 0;}"
    : "+f"(d[0]),"+f"(d[1]),"+f"(d[2]),"+f"(d[3]),"+f"(d[4]),"+f"(d[5]),"+f"(d[6]),"+f"(d[7]),"+f"(d[8]),"+f"(d[9]),"+f"(d[10]),"+f"(d[11]),"+f"(d[12]),"+f"(d[13]),"+f"(d[14]),"+f"(d[15]),"+f"(d[16]),"+f"(d[17]),"+f"(d[18]),"+f"(d[19]),"+f"(d[20]),"+f"(d[21]),"+f"(d[22]),"+f"(d[23]),"+f"(d[24]),"+f"(d[25]),"+f"(d[26]),"+f"(d[27]),"+f"(d[28]),"+f"(d[29]),"+f"(d[30]),"+f"(d[31]),"+f"(d[32]),"+f"(d[33]),"+f"(d[34]),"+f"(d[35]),"+f"(d[36]),"+f"(d[37]),"+f"(d[38]),"+f"(d[39]),"+f"(d[40]),"+f"(d[41]),"+f"(d[42]),"+f"(d[43]),"+f"(d[44]),"+f"(d[45]),"+f"(d[46]),"+f"(d[47]),"+f"(d[48]),"+f"(d[49]),"+f"(d[50]),"+f"(d[51]),"+f"(d[52]),"+f"(d[53]),"+f"(d[54]),"+f"(d[55]),"+f"(d[56]),"+f"(d[57]),"+f"(d[58]),"+f"(d[59]),"+f"(d[60]),"+f"(d[61]),"+f"(d[62]),"+f"(d[63]),"+f"(d[64]),"+f"(d[65]),"+f"(d[66]),"+f"(d[67]),"+f"(d[68]),"+f"(d[69]),"+f"(d[70]),"+f"(d[71]),"+f"(d[72]),"+f"(d[73]),"+f"(d[74]),"+f"(d[75]),"+f"(d[76]),"+f"(d[77]),"+f"(d[78]),"+f"(d[79]),"+f"(d[80]),"+f"(d[81]),"+f"(d[82]),"+f"(d[83]) : "l"(da), "l"(db), "r"(sc));
}
__device__ __forceinline__ void wg_rs_first(float (&d)[64], uint32_t a0, uint32_t a1, uint32_t a2, uint32_t a3, uint64_t db) {
  asm volatile("{.reg .pred p; setp.ne.b32 p, 0, 0; wgmma.mma_async.sync.aligned.m64n128k16.f32.bf16.bf16 {%0,%1,%2,%3,%4,%5,%6,%7,%8,%9,%10,%11,%12,%13,%14,%15,%16,%17,%18,%19,%20,%21,%22,%23,%24,%25,%26,%27,%28,%29,%30,%31,%32,%33,%34,%35,%36,%37,%38,%39,%40,%41,%42,%43,%44,%45,%46,%47,%48,%49,%50,%51,%52,%53,%54,%55,%56,%57,%58,%59,%60,%61,%62,%63}, {%64,%65,%66,%67}, %68, p, 1, 1, 0;}"
    : "=f"(d[0]),"=f"(d[1]),"=f"(d[2]),"=f"(d[3]),"=f"(d[4]),"=f"(d[5]),"=f"(d[6]),"=f"(d[7]),"=f"(d[8]),"=f"(d[9]),"=f"(d[10]),"=f"(d[11]),"=f"(d[12]),"=f"(d[13]),"=f"(d[14]),"=f"(d[15]),"=f"(d[16]),"=f"(d[17]),"=f"(d[18]),"=f"(d[19]),"=f"(d[20]),"=f"(d[21]),"=f"(d[22]),"=f"(d[23]),"=f"(d[24]),"=f"(d[25]),"=f"(d[26]),"=f"(d[27]),"=f"(d[28]),"=f"(d[29]),"=f"(d[30]),"=f"(d[31]),"=f"(d[32]),"=f"(d[33]),"=f"(d[34]),"=f"(d[35]),"=f"(d[36]),"=f"(d[37]),"=f"(d[38]),"=f"(d[39]),"=f"(d[40]),"=f"(d[41]),"=f"(d[42]),"=f"(d[43]),"=f"(d[44]),"=f"(d[45]),"=f"(d[46]),"=f"(d[47]),"=f"(d[48]),"=f"(d[49]),"=f"(d[50]),"=f"(d[51]),"=f"(d[52]),"=f"(d[53]),"=f"(d[54]),"=f"(d[55]),"=f"(d[56]),"=f"(d[57]),"=f"(d[58]),"=f"(d[59]),"=f"(d[60]),"=f"(d[61]),"=f"(d[62]),"=f"(d[63]) : "r"(a0), "r"(a1), "r"(a2), "r"(a3), "l"(db));
}
__device__ __forceinline__ void wg_g1_first(float (&d)[88], uint64_t da, uint64_t db) {
  asm volatile("{.reg .pred p; setp.ne.b32 p, 0, 0; wgmma.mma_async.sync.aligned.m64n176k16.f32.bf16.bf16 {%0,%1,%2,%3,%4,%5,%6,%7,%8,%9,%10,%11,%12,%13,%14,%15,%16,%17,%18,%19,%20,%21,%22,%23,%24,%25,%26,%27,%28,%29,%30,%31,%32,%33,%34,%35,%36,%37,%38,%39,%40,%41,%42,%43,%44,%45,%46,%47,%48,%49,%50,%51,%52,%53,%54,%55,%56,%57,%58,%59,%60,%61,%62,%63,%64,%65,%66,%67,%68,%69,%70,%71,%72,%73,%74,%75,%76,%77,%78,%79,%80,%81,%82,%83,%84,%85,%86,%87}, %88, %89, p, 1, 1, 1, 0;}"
    : "=f"(d[0]),"=f"(d[1]),"=f"(d[2]),"=f"(d[3]),"=f"(d[4]),"=f"(d[5]),"=f"(d[6]),"=f"(d[7]),"=f"(d[8]),"=f"(d[9]),"=f"(d[10]),"=f"(d[11]),"=f"(d[12]),"=f"(d[13]),"=f"(d[14]),"=f"(d[15]),"=f"(d[16]),"=f"(d[17]),"=f"(d[18]),"=f"(d[19]),"=f"(d[20]),"=f"(d[21]),"=f"(d[22]),"=f"(d[23]),"=f"(d[24]),"=f"(d[25]),"=f"(d[26]),"=f"(d[27]),"=f"(d[28]),"=f"(d[29]),"=f"(d[30]),"=f"(d[31]),"=f"(d[32]),"=f"(d[33]),"=f"(d[34]),"=f"(d[35]),"=f"(d[36]),"=f"(d[37]),"=f"(d[38]),"=f"(d[39]),"=f"(d[40]),"=f"(d[41]),"=f"(d[42]),"=f"(d[43]),"=f"(d[44]),"=f"(d[45]),"=f"(d[46]),"=f"(d[47]),"=f"(d[48]),"=f"(d[49]),"=f"(d[50]),"=f"(d[51]),"=f"(d[52]),"=f"(d[53]),"=f"(d[54]),"=f"(d[55]),"=f"(d[56]),"=f"(d[57]),"=f"(d[58]),"=f"(d[59]),"=f"(d[60]),"=f"(d[61]),"=f"(d[62]),"=f"(d[63]),"=f"(d[64]),"=f"(d[65]),"=f"(d[66]),"=f"(d[67]),"=f"(d[68]),"=f"(d[69]),"=f"(d[70]),"=f"(d[71]),"=f"(d[72]),"=f"(d[73]),"=f"(d[74]),"=f"(d[75]),"=f"(d[76]),"=f"(d[77]),"=f"(d[78]),"=f"(d[79]),"=f"(d[80]),"=f"(d[81]),"=f"(d[82]),"=f"(d[83]),"=f"(d[84]),"=f"(d[85]),"=f"(d[86]),"=f"(d[87]) : "l"(da), "l"(db));
}
__device__ __forceinline__ void wg_g1_first(float (&d)[84], uint64_t da, uint64_t db) {
  asm volatile("{.reg .pred p; setp.ne.b32 p, 0, 0; wgmma.mma_async.sync.aligned.m64n168k16.f32.bf16.bf16 {%0,%1,%2,%3,%4,%5,%6,%7,%8,%9,%10,%11,%12,%13,%14,%15,%16,%17,%18,%19,%20,%21,%22,%23,%24,%25,%26,%27,%28,%29,%30,%31,%32,%33,%34,%35,%36,%37,%38,%39,%40,%41,%42,%43,%44,%45,%46,%47,%48,%49,%50,%51,%52,%53,%54,%55,%56,%57,%58,%59,%60,%61,%62,%63,%64,%65,%66,%67,%68,%69,%70,%71,%72,%73,%74,%75,%76,%77,%78,%79,%80,%81,%82,%83}, %84, %85, p, 1, 1, 1, 0;}"
    : "=f"(d[0]),"=f"(d[1]),"=f"(d[2]),"=f"(d[3]),"=f"(d[4]),"=f"(d[5]),"=f"(d[6]),"=f"(d[7]),"=f"(d[8]),"=f"(d[9]),"=f"(d[10]),"=f"(d[11]),"=f"(d[12]),"=f"(d[13]),"=f"(d[14]),"=f"(d[15]),"=f"(d[16]),"=f"(d[17]),"=f"(d[18]),"=f"(d[19]),"=f"(d[20]),"=f"(d[21]),"=f"(d[22]),"=f"(d[23]),"=f"(d[24]),"=f"(d[25]),"=f"(d[26]),"=f"(d[27]),"=f"(d[28]),"=f"(d[29]),"=f"(d[30]),"=f"(d[31]),"=f"(d[32]),"=f"(d[33]),"=f"(d[34]),"=f"(d[35]),"=f"(d[36]),"=f"(d[37]),"=f"(d[38]),"=f"(d[39]),"=f"(d[40]),"=f"(d[41]),"=f"(d[42]),"=f"(d[43]),"=f"(d[44]),"=f"(d[45]),"=f"(d[46]),"=f"(d[47]),"=f"(d[48]),"=f"(d[49]),"=f"(d[50]),"=f"(d[51]),"=f"(d[52]),"=f"(d[53]),"=f"(d[54]),"=f"(d[55]),"=f"(d[56]),"=f"(d[57]),"=f"(d[58]),"=f"(d[59]),"=f"(d[60]),"=f"(d[61]),"=f"(d[62]),"=f"(d[63]),"=f"(d[64]),"=f"(d[65]),"=f"(d[66]),"=f"(d[67]),"=f"(d[68]),"=f"(d[69]),"=f"(d[70]),"=f"(d[71]),"=f"(d[72]),"=f"(d[73]),"=f"(d[74]),"=f"(d[75]),"=f"(d[76]),"=f"(d[77]),"=f"(d[78]),"=f"(d[79]),"=f"(d[80]),"=f"(d[81]),"=f"(d[82]),"=f"(d[83]) : "l"(da), "l"(db));
}
__device__ __forceinline__ void wg_tt128_first(float (&d)[64], uint64_t da, uint64_t db) {
  asm volatile("{.reg .pred p; setp.ne.b32 p, 0, 0; wgmma.mma_async.sync.aligned.m64n128k16.f32.bf16.bf16 {%0,%1,%2,%3,%4,%5,%6,%7,%8,%9,%10,%11,%12,%13,%14,%15,%16,%17,%18,%19,%20,%21,%22,%23,%24,%25,%26,%27,%28,%29,%30,%31,%32,%33,%34,%35,%36,%37,%38,%39,%40,%41,%42,%43,%44,%45,%46,%47,%48,%49,%50,%51,%52,%53,%54,%55,%56,%57,%58,%59,%60,%61,%62,%63}, %64, %65, p, 1, 1, 1, 1;}"
    : "=f"(d[0]),"=f"(d[1]),"=f"(d[2]),"=f"(d[3]),"=f"(d[4]),"=f"(d[5]),"=f"(d[6]),"=f"(d[7]),"=f"(d[8]),"=f"(d[9]),"=f"(d[10]),"=f"(d[11]),"=f"(d[12]),"=f"(d[13]),"=f"(d[14]),"=f"(d[15]),"=f"(d[16]),"=f"(d[17]),"=f"(d[18]),"=f"(d[19]),"=f"(d[20]),"=f"(d[21]),"=f"(d[22]),"=f"(d[23]),"=f"(d[24]),"=f"(d[25]),"=f"(d[26]),"=f"(d[27]),"=f"(d[28]),"=f"(d[29]),"=f"(d[30]),"=f"(d[31]),"=f"(d[32]),"=f"(d[33]),"=f"(d[34]),"=f"(d[35]),"=f"(d[36]),"=f"(d[37]),"=f"(d[38]),"=f"(d[39]),"=f"(d[40]),"=f"(d[41]),"=f"(d[42]),"=f"(d[43]),"=f"(d[44]),"=f"(d[45]),"=f"(d[46]),"=f"(d[47]),"=f"(d[48]),"=f"(d[49]),"=f"(d[50]),"=f"(d[51]),"=f"(d[52]),"=f"(d[53]),"=f"(d[54]),"=f"(d[55]),"=f"(d[56]),"=f"(d[57]),"=f"(d[58]),"=f"(d[59]),"=f"(d[60]),"=f"(d[61]),"=f"(d[62]),"=f"(d[63]) : "l"(da), "l"(db));
}

struct Params {
    const __nv_bfloat16 *x, *logA, *Aim, *Cr, *Ci, *logdt, *Dskip, *Wg, *Wu;
};

__device__ __forceinline__ void conv_channel(uint32_t cb, int w, int lane, uint32_t (&res)[8], uint32_t bar_free) {
    const int q = lane & 3, g = lane >> 2, gam = g >> 2;
    float acc[64];
    uint4 a[5][4];
    {
        const uint32_t t0 = cb + CH_T + (uint32_t)(14 + 4 * w + (g & 3) + 32 * gam - 2 * q) * 80u;
        #pragma unroll
        for (int s4 = 0; s4 < 5; s4++) {
            a[s4][0] = lds128(t0 + s4 * 16);
            a[s4][1] = lds128(t0 + 16 * 80 + s4 * 16);
            a[s4][2] = lds128(t0 - 8 * 80 + s4 * 16);
            a[s4][3] = lds128(t0 + 8 * 80 + s4 * 16);
        }
    }
    const uint64_t dU = mkdesc(cb + CH_U, UPLANE, 128, 0);
    WG_FENCE();
#define CT(N, s, c) wg_rs<N>(acc, a[(s) >> 2][0].c, a[(s) >> 2][1].c, a[(s) >> 2][2].c, a[(s) >> 2][3].c, dU + 4 * (s), 1)
    wg_rs_first(acc, a[0][0].x, a[0][1].x, a[0][2].x, a[0][3].x, dU); CT(128, 1, y); CT(120, 2, z); CT(120, 3, w);
    CT(112, 4, x); CT(112, 5, y); CT(104, 6, z); CT(104, 7, w);
    CT(96, 8, x);  CT(96, 9, y);  CT(88, 10, z); CT(88, 11, w);
    CT(80, 12, x); CT(80, 13, y); CT(72, 14, z); CT(72, 15, w);
    CT(64, 16, x);
#undef CT
    wg_tt64(acc, mkdesc(cb + CH_A3, 128, 512, 0), mkdesc(cb + CH_B3, 128, 256, 0), 1);
    wg_tt32(acc, mkdesc(cb + CH_A3 + 256, 128, 512, 0), mkdesc(cb + CH_B3 + 1024, 128, 256, 0), 1);
    WG_COMMIT();
    WG_WAIT(0);
    fence_acc(acc);
    if (bar_free && lane == 0) mbar_arrive(bar_free);
    const int src1 = (lane & ~3) | ((q + 1) & 3);
    float E[16][2];
    #pragma unroll
    for (int j = 0; j < 16; j++) {
        const float nxt = (j < 15) ? acc[4 * (j + 1) + 2] : 0.f;
        const float sup = (q == 0) ? nxt : acc[4 * j + 2];
        const float v = __shfl_sync(0xffffffffu, sup, src1);
        E[j][0] = acc[4 * j] + acc[4 * j + 3];
        E[j][1] = acc[4 * j + 1] + v;
    }
    const int src2 = gam ? ((lane & 12) | ((q + 3) & 3)) : (16 | (lane & 12) | ((q + 1) & 3));
    const bool c1 = gam && q != 0, c2 = gam && q == 0;
    #pragma unroll
    for (int a2 = 0; a2 < 8; a2++) {
        float y[2];
        #pragma unroll
        for (int e = 0; e < 2; e++) {
            const float sup = c1 ? E[2 * a2][e] : E[2 * a2 + 1][e];
            const float nxt = (a2 < 7) ? E[2 * a2 + 2][e] : 0.f;
            const float keep = c2 ? nxt : (c1 ? E[2 * a2 + 1][e] : E[2 * a2][e]);
            y[e] = keep + __shfl_sync(0xffffffffu, sup, src2);
        }
        res[a2] = pack2(y[1], y[0]);
    }
}

template <int N, int V>
__device__ __forceinline__ void consumer(uint32_t sb, const CUtensorMap* tmOut) {
    const int tid = threadIdx.x & 127, w = tid >> 5, lane = tid & 31, q = lane & 3, g = lane >> 2;
    const int c = blockIdx.x, fb = c % 22, tg = c / 22;
    const uint32_t bars = sb + OFF_BAR;
    {
        float ag[N / 2], au[N / 2];
        const uint32_t xb = sb + (V ? OFF_X1 : OFF_X0);
        if (V == 1) mbar_wait_c(bars + 8 * B_GO, 0);
        #pragma unroll
        for (int st = 0; st < 8; st++) {
            mbar_wait_c(bars + 8 * (B_FULLW + (st & 3)), (st >> 2) & 1);
            mbar_wait_c(bars + 8 * (B_FULLX + 2 * V + (st & 1)), (st >> 1) & 1);
            if (st == 0) STAMP(8 * V + 0);
            const uint64_t dG = mkdesc(sb + OFF_W + (st & 3) * 16384, 0, 1024, 1);
            const uint64_t dX = mkdesc(xb + (st & 1) * (N * 128), 16, 1024, 1);
            WG_FENCE();
            #pragma unroll
            for (int k = 0; k < 4; k++) {
                if ((st | k) == 0) { wg_g1_first(ag, dG, dX); wg_g1_first(au, dG + 512, dX); }
                else { wg_g1(ag, dG + k * 128, dX + k * 2, 1); wg_g1(au, dG + 512 + k * 128, dX + k * 2, 1); }
            }
            WG_COMMIT();
            if (st > 0) {
                WG_WAIT(1);
                if (lane == 0) {
                    mbar_arrive(bars + 8 * (B_EMPTYW + ((st - 1) & 3)));
                    mbar_arrive(bars + 8 * (B_EMPTYX + 2 * V + ((st - 1) & 1)));
                    if (V == 0 && st == 1) mbar_arrive(bars + 8 * B_GO);
                }
            }
        }
        WG_WAIT(0);
        fence_acc(ag); fence_acc(au);
        if (lane == 0) { mbar_arrive(bars + 8 * (B_EMPTYW + 3)); mbar_arrive(bars + 8 * (B_EMPTYX + 2 * V + 1)); }
        STAMP(8 * V + 1);
        mbar_wait_c(bars + 8 * B_STATS, 0);
        const float cg0 = ldsf(sb + OFF_CSUM + (16 * w + g) * 4), cg1 = ldsf(sb + OFF_CSUM + (16 * w + g + 8) * 4);
        const float cu0 = ldsf(sb + OFF_CSUM + (64 + 16 * w + g) * 4), cu1 = ldsf(sb + OFF_CSUM + (64 + 16 * w + g + 8) * 4);
        const int fch = 8 * fb + 2 * w;
        char* hp = (char*)g_H + fch * 1024 + lane * 4;
        const int o0 = 43 * tg + 22 * V;
        const bool rows_ok = fch < 172;
        #pragma unroll
        for (int j = 0; j < N / 8; j++) {
            const uint4 sv = lds128(sb + OFF_STATS + (176 * V + 8 * j + 2 * q) * 8);
            const float m0 = __uint_as_float(sv.x), r0 = __uint_as_float(sv.y), m1 = __uint_as_float(sv.z), r1 = __uint_as_float(sv.w);
            const float h0 = 0.5f * r0, h1 = 0.5f * r1;
            float hv[4];
            #pragma unroll
            for (int i = 0; i < 4; i++) {
                const float m = (i & 1) ? m1 : m0, r = (i & 1) ? r1 : r0, hr = (i & 1) ? h1 : h0;
                const float gh = fmaf(-m, (i & 2) ? cg1 : cg0, ag[4 * j + i]) * hr;
                const float uu = fmaf(-m, (i & 2) ? cu1 : cu0, au[4 * j + i]) * r;
                const float p = gh * uu;
                hv[i] = fmaf(p, tanh_fast(gh), p);
            }
            const int o = o0 + j;
            const int off = (o >> 3) * (172 * 1024) + (((o & 1) << 1) | (o & 4) | ((o >> 1) & 1)) * 128;
            if (rows_ok && o < 256) {
                *(uint32_t*)(hp + off) = pack2(hv[0], hv[1]);
                *(uint32_t*)(hp + off + 1024) = pack2(hv[2], hv[3]);
            }
        }
        mbar_arrive(bars + 8 * (B_EPI + V));
        STAMP(8 * V + 2);
    }
    if (c >= 128) return;
    {
        mbar_wait_c(bars + 8 * B_CONV, 0);
        uint32_t r0[8], r1[8];
        #pragma unroll
        for (int i = 0; i < 8; i++) r1[i] = 0;
        #pragma unroll 1
        for (int e = 0; e < 2; e++) {
            #pragma unroll
            for (int i = 0; i < 8; i++) r0[i] = r1[i];
            conv_channel(sb + OFF_CONV + (2 * V + e) * CH_STRIDE, w, lane, r1, (V == 0 && e == 0) ? bars + 8 * B_CH0 : 0);
            if (e == 0) STAMP(8 * V + 3);
        }
        const int gam = g >> 2, qq = gam ? ((q + 3) & 3) : q;
        uint2* sp = g_S + (2 * c + V) * 1024 + (63 - 4 * gam - qq) * 16 + 4 * w + (g & 3);
        #pragma unroll
        for (int a2 = 0; a2 < 8; a2++) sp[-a2 * 128] = make_uint2(r0[a2], r1[a2]);
        mbar_arrive(bars + 8 * (B_SIG + V));
        STAMP(8 * V + 4);
    }
    if (V == 1) return;
    {
        const int tau = c >> 2, dg = c & 3;
        float acc[64];
        #pragma unroll
        for (int i = 0; i < 64; i++) acc[i] = 0.f;
        uint2 sv[16];
        #pragma unroll
        for (int i = 0; i < 16; i++) sv[i] = make_uint2(0, 0);
        int sd = 0, sh = 0; uint32_t pd = 0, ph = 0;
        int psd = 0, psh = 0;
        #pragma unroll 1
        for (int st = 0; st < 22; st++) {
            mbar_wait_c(bars + 8 * (B_FULLD + sd), pd);
            mbar_wait_c(bars + 8 * (B_FULLH + sh), ph);
            if (st == 0) STAMP(5);
            const uint32_t da = (sd == 2) ? OFF_X0 : (sd == 4) ? OFF_X0 + 22528 : OFF_W + ((sd + 1) >> 1) * 16384;
            const uint64_t dB = mkdesc(sb + da, 8192, 1024, 1);
            const uint64_t dA = mkdesc(sb + OFF_X1 + sh * 8192, 1024, 128, 0);
            WG_FENCE();
            wg_tt128(acc, dA, dB, 1);
            wg_tt128(acc, dA + 128, dB + 128, 1);
            if (st < 21) {
                wg_tt128(acc, dA + 256, dB + 256, 1);
                wg_tt128(acc, dA + 384, dB + 384, 1);
            }
            WG_COMMIT();
            if (st > 0) {
                WG_WAIT(1);
                if (lane == 0) { mbar_arrive(bars + 8 * (B_EMPTYD + psd)); mbar_arrive(bars + 8 * (B_EMPTYH + psh)); }
            }
            psd = sd; psh = sh;
            if (++sd == 6) { sd = 0; pd ^= 1; }
            if (++sh == 5) { sh = 0; ph ^= 1; }
            if (st == 14) {
                mbar_wait_c(bars + 8 * B_S, 0);
                const uint2* sp = g_S + (dg * 64 + q) * 1024 + (2 * tau + (w >> 1)) * 16 + 8 * (w & 1) + g;
                #pragma unroll
                for (int j = 0; j < 16; j++)
                    asm volatile("ld.global.cg.v2.b32 {%0,%1}, [%2];" : "=r"(sv[j].x), "=r"(sv[j].y) : "l"(sp + j * 4096));
            }
        }
        WG_WAIT(0);
        fence_acc(acc);
        STAMP(6);
        mbar_wait_c(bars + 8 * B_XO, 0);
        const uint32_t row = 8 * (w & 1) + 32 * (w >> 1) + (lane & 7) + 16 * ((lane >> 3) & 1);
        const uint32_t xo = sb + OFF_CONV + row * 128;
        #pragma unroll
        for (int j = 0; j < 16; j += 2) {
            const uint32_t ad = xo + (j >> 3) * 8192 + ((((j & 7) + (lane >> 4)) ^ (lane & 7)) << 4);
            uint32_t xr[4];
            asm volatile("ldmatrix.sync.aligned.m8n8.x4.shared.b16 {%0,%1,%2,%3}, [%4];" : "=r"(xr[0]), "=r"(xr[1]), "=r"(xr[2]), "=r"(xr[3]) : "r"(ad));
            #pragma unroll
            for (int i = 0; i < 4; i++) {
                const int jj = j + (i >> 1), hh = i & 1;
                const float f0 = 0.5f * acc[4 * jj + 2 * hh], f1 = 0.5f * acc[4 * jj + 2 * hh + 1];
                const float G0 = fmaf(f0, tanh_fast(f0), f0), G1 = fmaf(f1, tanh_fast(f1), f1);
                const float s0 = hh ? bf_hi(sv[jj].x) : bf_lo(sv[jj].x), s1 = hh ? bf_hi(sv[jj].y) : bf_lo(sv[jj].y);
                xr[i] = pack2(fmaf(s0, G0, bf_lo(xr[i])), fmaf(s1, G1, bf_hi(xr[i])));
            }
            asm volatile("stmatrix.sync.aligned.m8n8.x4.shared.b16 [%0], {%1,%2,%3,%4};" :: "r"(ad), "r"(xr[0]), "r"(xr[1]), "r"(xr[2]), "r"(xr[3]) : "memory");
        }
        fence_async();
        bar_sync(1);
        if (w == 0 && elect_one()) {
            tma2d_store(tmOut, dg * 128, tau * 64, sb + OFF_CONV);
            tma2d_store(tmOut, dg * 128 + 64, tau * 64, sb + OFF_CONV + 8192);
            asm volatile("cp.async.bulk.commit_group;" ::: "memory");
            asm volatile("cp.async.bulk.wait_group.read 0;" ::: "memory");
        }
        STAMP(7);
    }
}

__device__ __forceinline__ float2 cexp_p(float re2, float om, float p) {
    float mag, sn, cs;
    asm("ex2.approx.ftz.f32 %0, %1;" : "=f"(mag) : "f"(re2 * p));
    const float k = fmaf(om, p, 12582912.f) - 12582912.f;
    const float th = fmaf(om, p, -k) * 6.283185307179586f;
    asm("sin.approx.ftz.f32 %0, %1;" : "=f"(sn) : "f"(th));
    asm("cos.approx.ftz.f32 %0, %1;" : "=f"(cs) : "f"(th));
    return make_float2(mag * cs, mag * sn);
}
__device__ __forceinline__ float2 cmul(float2 a, float2 b) { return make_float2(fmaf(a.x, b.x, -a.y * b.y), fmaf(a.x, b.y, a.y * b.x)); }
__device__ __forceinline__ float2 csqr(float2 a) { const float t = a.x * a.y; return make_float2(fmaf(a.x, a.x, -a.y * a.y), t + t); }
__device__ __forceinline__ void mma16816(float (&d)[4], const uint32_t (&a)[4], uint32_t b0, uint32_t b1) {
    asm volatile("mma.sync.aligned.m16n8k16.row.col.f32.bf16.bf16.f32 {%0,%1,%2,%3}, {%4,%5,%6,%7}, {%8,%9}, {%0,%1,%2,%3};"
        : "+f"(d[0]), "+f"(d[1]), "+f"(d[2]), "+f"(d[3]) : "r"(a[0]), "r"(a[1]), "r"(a[2]), "r"(a[3]), "r"(b0), "r"(b1));
}
__device__ __forceinline__ void ln_reduce(float (&s)[8], uint32_t red, int w, int lane) {
    const bool b4 = lane & 16, b3 = lane & 8, b2 = lane & 4;
    float t[4], u[2], v;
    #pragma unroll
    for (int k = 0; k < 4; k++) t[k] = (b4 ? s[4 + k] : s[k]) + __shfl_xor_sync(0xffffffffu, b4 ? s[k] : s[4 + k], 16);
    #pragma unroll
    for (int k = 0; k < 2; k++) u[k] = (b3 ? t[2 + k] : t[k]) + __shfl_xor_sync(0xffffffffu, b3 ? t[k] : t[2 + k], 8);
    v = (b2 ? u[1] : u[0]) + __shfl_xor_sync(0xffffffffu, b2 ? u[0] : u[1], 4);
    v += __shfl_xor_sync(0xffffffffu, v, 2);
    if (!(lane & 2)) stsf(red + (w * 16 + (lane & 1) * 8 + (lane >> 2)) * 4, v);
    bar_sync(2);
    #pragma unroll
    for (int k = 0; k < 8; k++) s[k] = 0.f;
    #pragma unroll
    for (int ww = 0; ww < 4; ww++) {
        const uint4 a = lds128(red + (ww * 16 + (lane & 1) * 8) * 4), b = lds128(red + (ww * 16 + (lane & 1) * 8 + 4) * 4);
        s[0] += __uint_as_float(a.x); s[1] += __uint_as_float(a.y); s[2] += __uint_as_float(a.z); s[3] += __uint_as_float(a.w);
        s[4] += __uint_as_float(b.x); s[5] += __uint_as_float(b.y); s[6] += __uint_as_float(b.z); s[7] += __uint_as_float(b.w);
    }
}

__device__ __forceinline__ void aux_role(uint32_t sb, const Params& P) {
    const int tid = threadIdx.x & 127, w = tid >> 5, lane = tid & 31, q = lane & 3, g = lane >> 2;
    const int c = blockIdx.x, fb = c % 22, tg = c / 22;
    const uint32_t bars = sb + OFF_BAR;
    const uint32_t cb = sb + OFF_CONV + w * CH_STRIDE;
    const uint32_t sF = cb + CH_A3, sP = cb + CH_A3 + 2064;
    float dsk = 0.f;
    if (c < 128) {
        const int eta = lane & 1, del = w * 16 + (lane >> 1);
        const int tok0 = 32 * (c >> 1) + 16 * eta + 8 * (c & 1);
        uint4 xr[8];
        #pragma unroll
        for (int r = 0; r < 8; r++) xr[r] = ldg128(P.x + (tok0 + r) * DM + 8 * del);
        {
            const int d = 4 * c + w;
            const uint2 la = *(const uint2*)(P.logA + d * 128 + 4 * lane), ai = *(const uint2*)(P.Aim + d * 128 + 4 * lane);
            const uint2 cr = *(const uint2*)(P.Cr + d * 128 + 4 * lane), ci = *(const uint2*)(P.Ci + d * 128 + 4 * lane);
            const float dt = bf_round(expf(__bfloat162float(P.logdt[d])));
            dsk = __bfloat162float(P.Dskip[d]);
            #pragma unroll
            for (int i = 0; i < 4; i++) {
                const uint32_t l2 = (i & 2) ? la.y : la.x, a2 = (i & 2) ? ai.y : ai.x, r2 = (i & 2) ? cr.y : cr.x, i2 = (i & 2) ? ci.y : ci.x;
                const float re = -bf_round(expf((i & 1) ? bf_hi(l2) : bf_lo(l2))) * dt;
                const float im = ((i & 1) ? bf_hi(a2) : bf_lo(a2)) * dt;
                sts128(sP + (4 * lane + i) * 16, __float_as_uint(re * 1.4426950408889634f), __float_as_uint(im * 0.15915494309189535f),
                       __float_as_uint(((i & 1) ? bf_hi(r2) : bf_lo(r2)) * dt * 2.f), __float_as_uint(((i & 1) ? bf_hi(i2) : bf_lo(i2)) * dt * 2.f));
            }
        }
        float s[8];
        #pragma unroll
        for (int r = 0; r < 8; r++)
            s[r] = ((bf_lo(xr[r].x) + bf_hi(xr[r].x)) + (bf_lo(xr[r].y) + bf_hi(xr[r].y))) + ((bf_lo(xr[r].z) + bf_hi(xr[r].z)) + (bf_lo(xr[r].w) + bf_hi(xr[r].w)));
        ln_reduce(s, sb + OFF_RED, w, lane);
        float mean[8];
        #pragma unroll
        for (int r = 0; r < 8; r++) {
            const float m = s[r] * (1.f / DM); mean[r] = m;
            float a = 0.f, t;
            t = bf_lo(xr[r].x) - m; a = fmaf(t, t, a); t = bf_hi(xr[r].x) - m; a = fmaf(t, t, a);
            t = bf_lo(xr[r].y) - m; a = fmaf(t, t, a); t = bf_hi(xr[r].y) - m; a = fmaf(t, t, a);
            t = bf_lo(xr[r].z) - m; a = fmaf(t, t, a); t = bf_hi(xr[r].z) - m; a = fmaf(t, t, a);
            t = bf_lo(xr[r].w) - m; a = fmaf(t, t, a); t = bf_hi(xr[r].w) - m; a = fmaf(t, t, a);
            s[r] = a;
        }
        ln_reduce(s, sb + OFF_RED + 256, w, lane);
        #pragma unroll
        for (int r = 0; r < 8; r++) {
            const float mb = bf_round(mean[r]);
            const float sd = bf_round(sqrtf(bf_round(bf_round(s[r] * (1.f / DM)) + 1e-5f)));
            const float ri = 1.f / sd;
            s[r] = ri;
            if (del == r) g_stats[tok0 + r] = make_float2(mb, ri);
            const __nv_bfloat162 m2 = __float2bfloat162_rn(mb);
            uint32_t* xp = &xr[r].x;
            #pragma unroll
            for (int k = 0; k < 4; k++) { const __nv_bfloat162 dv = __hsub2(*(__nv_bfloat162*)&xp[k], m2); xp[k] = *(const uint32_t*)&dv; }
        }
        uint4* dst = g_xnT + (8 * del) * 256 + (c & 1) * 128 + (127 - 2 * (c >> 1) - eta);
        #pragma unroll
        for (int k = 0; k < 8; k++) {
            uint32_t o[4];
            #pragma unroll
            for (int r = 0; r < 8; r += 2) {
                const uint32_t w0 = (&xr[r].x)[k >> 1], w1 = (&xr[r + 1].x)[k >> 1];
                o[r >> 1] = pack2(((k & 1) ? bf_hi(w0) : bf_lo(w0)) * s[r], ((k & 1) ? bf_hi(w1) : bf_lo(w1)) * s[r + 1]);
            }
            dst[k * 256] = make_uint4(o[0], o[1], o[2], o[3]);
        }
    }
    STAMP(16);
    {
        const int mat = c / 66, rem = c % 66, cg = rem / 3, third = rem % 3;
        const int r0 = 171 * third, r1 = min(r0 + 171, DM), col = 64 * cg + 8 * (lane & 7);
        const __nv_bfloat16* W = (mat ? P.Wu : P.Wg) + col;
        float a[8];
        #pragma unroll
        for (int k = 0; k < 8; k++) a[k] = 0.f;
        #pragma unroll
        for (int it = 0; it < 11; it++) {
            const int row = r0 + 16 * it + 4 * w + (lane >> 3);
            uint4 v = make_uint4(0, 0, 0, 0);
            if (row < r1 && col < FF) v = ldg128(W + row * FF);
            a[0] += bf_lo(v.x); a[1] += bf_hi(v.x); a[2] += bf_lo(v.y); a[3] += bf_hi(v.y);
            a[4] += bf_lo(v.z); a[5] += bf_hi(v.z); a[6] += bf_lo(v.w); a[7] += bf_hi(v.w);
        }
        #pragma unroll
        for (int k = 0; k < 8; k++) { a[k] += __shfl_xor_sync(0xffffffffu, a[k], 8); a[k] += __shfl_xor_sync(0xffffffffu, a[k], 16); }
        const uint32_t red = sb + OFF_RED + 512;
        if (lane < 8) {
            sts128(red + (w * 64 + lane * 8) * 4, __float_as_uint(a[0]), __float_as_uint(a[1]), __float_as_uint(a[2]), __float_as_uint(a[3]));
            sts128(red + (w * 64 + lane * 8 + 4) * 4, __float_as_uint(a[4]), __float_as_uint(a[5]), __float_as_uint(a[6]), __float_as_uint(a[7]));
        }
        bar_sync(2);
        if (tid < 64) g_csum[(third * 2 + mat) * 1408 + 64 * cg + tid] = (ldsf(red + tid * 4) + ldsf(red + (64 + tid) * 4)) + (ldsf(red + (128 + tid) * 4) + ldsf(red + (192 + tid) * 4));
        mbar_arrive(bars + 8 * B_LN);
    }
    STAMP(17);
    if (c < 128) {
        float dacc[2][3][4];
        #pragma unroll
        for (int i = 0; i < 24; i++) (&dacc[0][0][0])[i] = 0.f;
        const float p0 = (float)g, p8 = (float)(8 * g);
        const float p1 = (g < 4) ? (float)(256 + 2 * g) : (float)(512 + 4 * (g & 1) + 256 * ((g >> 1) & 1));
        const float p2 = (g < 4) ? (float)(1032 + 256 * g) : 1024.f;
        #pragma unroll 1
        for (int ks = 0; ks < 16; ks++) {
            uint32_t a0[4], a1[4], b[3][2];
            #pragma unroll
            for (int mh = 0; mh < 2; mh++) {
                const uint4 pv = lds128(sP + (8 * ks + q + 4 * mh) * 16);
                const float re2 = __uint_as_float(pv.x), om = __uint_as_float(pv.y);
                const float2 C = make_float2(__uint_as_float(pv.z), __uint_as_float(pv.w));
                const float2 R0 = cexp_p(re2, om, p8);
                float2 z32; z32.x = __shfl_sync(0xffffffffu, R0.x, 16 + q); z32.y = __shfl_sync(0xffffffffu, R0.y, 16 + q);
                const float2 z64 = csqr(z32), z128 = csqr(z64);
                const float2 R1 = cmul(R0, z64), R2 = cmul(R0, z128), R3 = cmul(R1, z128);
                const float2 L0 = cmul(C, cexp_p(re2, om, p0)), L1 = cmul(C, cexp_p(re2, om, p1)), L2 = cmul(C, cexp_p(re2, om, p2));
                a0[2 * mh] = pack2(R0.x, R0.y); a0[2 * mh + 1] = pack2(R1.x, R1.y);
                a1[2 * mh] = pack2(R2.x, R2.y); a1[2 * mh + 1] = pack2(R3.x, R3.y);
                b[0][mh] = pack2(L0.x, -L0.y); b[1][mh] = pack2(L1.x, -L1.y); b[2][mh] = pack2(L2.x, -L2.y);
            }
            #pragma unroll
            for (int t = 0; t < 3; t++) { mma16816(dacc[0][t], a0, b[t][0], b[t][1]); mma16816(dacc[1][t], a1, b[t][0], b[t][1]); }
        }
        STAMP(18);
        const uint32_t sG = cb + CH_G;
        if (lane < 8) sts128(sG + (lane >> 2) * 192 + 128 + (lane & 3) * 16, 0, 0, 0, 0);
        #pragma unroll
        for (int mu = 0; mu < 2; mu++)
            #pragma unroll
            for (int hh = 0; hh < 2; hh++) {
                const int m = 16 * mu + 8 * hh + g;
                sts64(sF + (8 * m + 2 * q) * 4, __float_as_uint(dacc[mu][0][2 * hh]), __float_as_uint(dacc[mu][0][2 * hh + 1]));
                const int i1 = (q < 2) ? 256 + 4 * m + 2 * q : 384 + 2 * m + 64 * (q - 2);
                sts64(sF + i1 * 4, __float_as_uint(dacc[mu][1][2 * hh]), __float_as_uint(dacc[mu][1][2 * hh + 1]));
                if (q < 2) {
                    const uint32_t pk = pack2(dacc[mu][2][2 * hh], dacc[mu][2][2 * hh + 1]);
                    const uint32_t ga = sG + ((m & 1) ? 0 : 192) + (63 - (m >> 1) - 32 * q) * 2;
                    sts16(ga, pk & 0xffff); sts16(ga - 32, pk >> 16);
                } else if (q == 2 && m == 0) stsf(sF + 512 * 4, dacc[mu][2][2 * hh]);
            }
        __syncwarp();
        #pragma unroll 1
        for (int pass = 0; pass < 3; pass++) {
            const int row = min(pass * 32 + lane, 77), v = row - 14;
            uint32_t o[20];
            float kv[2][17];
            #pragma unroll
            for (int z = 0; z < 2; z++) {
                const int u = v - z;
                const uint32_t f0 = sF + u * 4, f1 = sF + (128 + ((u + ((u >> 1) & 1)) >> 1)) * 4, f2 = sF + (256 + ((u + 1 + ((u >> 2) & 1)) >> 2)) * 4;
                kv[z][0] = ldsf(u < 0 ? sF : f0); if (u < 0) kv[z][0] = 0.f; if (u == 0) kv[z][0] += dsk;
                #pragma unroll
                for (int s = 1; s < 4; s++) kv[z][s] = ldsf(f0 + s * 256);
                kv[z][4] = ldsf(u < 0 ? f0 + 1024 : f1 + 512);
                #pragma unroll
                for (int s = 5; s < 8; s++) kv[z][s] = ldsf(f1 + s * 128);
                kv[z][8] = ldsf(u < 0 ? f1 + 1024 : f2 + 512);
                #pragma unroll
                for (int s = 9; s < 16; s++) kv[z][s] = ldsf(f2 + s * 64);
                kv[z][16] = ldsf(u < 0 ? f2 + 1024 : sF + 2048); if (u > 4) kv[z][16] = 0.f;
            }
            #pragma unroll
            for (int s = 0; s < 17; s++) o[s] = pack2(kv[0][s], kv[1][s]);
            o[17] = o[18] = o[19] = 0;
            #pragma unroll
            for (int s4 = 0; s4 < 5; s4++) sts128(cb + CH_T + row * 80 + s4 * 16, o[4 * s4], o[4 * s4 + 1], o[4 * s4 + 2], o[4 * s4 + 3]);
        }
        __syncwarp();
        #pragma unroll
        for (int i = 0; i < 4; i++) {
            const int un = i * 32 + lane, ch = un >> 4, sig = (un >> 3) & 1, kp = un & 7;
            const uint2 x0 = lds64(sG + sig * 192 + (8 * ch + 4 * kp) * 2), x1 = lds64(sG + sig * 192 + (8 * ch + 4 * kp + 4) * 2);
            sts128(cb + CH_B3 + un * 16, x0.x, x0.y, x1.x, x1.y);
        }
        if (lane < 8) sts128(cb + CH_U + (lane >> 2) * UPLANE + 2048 + (lane & 3) * 16, 0, 0, 0, 0);
    }
    STAMP(19);
    if (tid == 0) {
        flag_wait(F_A, NCTA);
        if (c < 128) {
            fence_async();
            mbar_expect(bars + 8 * B_U, 8 * 2048);
            #pragma unroll 1
            for (int i = 0; i < 8; i++)
                bulk_load(sb + OFF_CONV + (i >> 1) * CH_STRIDE + CH_U + (i & 1) * UPLANE, g_xnT + (4 * c + (i >> 1)) * 256 + (i & 1) * 128, 2048, bars + 8 * B_U);
        } else exit_count();
    }
    bar_sync(2);
    {
        const float* cs = g_csum + (tid >> 6) * 1408 + 64 * fb + (tid & 63);
        stsf(sb + OFF_CSUM + tid * 4, __ldcg(cs) + __ldcg(cs + 2816) + __ldcg(cs + 5632));
        #pragma unroll
        for (int i = 0; i < 3; i++) {
            const int t = tid + 128 * i;
            if (t < TOKG) {
                const float2 sv = __ldcg(g_stats + min(TOKG * tg + t, SEQ - 1));
                sts64(sb + OFF_STATS + t * 8, __float_as_uint(sv.x), __float_as_uint(sv.y));
            }
        }
        mbar_arrive(bars + 8 * B_STATS);
    }
    STAMP(20);
    if (c >= 128) return;
    mbar_wait(bars + 8 * B_U, 0);
    {
        const int kap = (lane >> 4) * 8 + ((lane >> 1) & 7), gam = lane & 1, hh = w >> 1, wp = w & 1;
        const int a = 8 * kap + 4 * gam + 2 * hh + wp;
        #pragma unroll 1
        for (int ch = 0; ch < 4; ch++) {
            const uint32_t cc = sb + OFF_CONV + ch * CH_STRIDE;
            float p[24];
            uint4 r[4];
            #pragma unroll
            for (int i = 0; i < 4; i++) { const int rr = a - 3 + i; r[i] = lds128(cc + CH_U + (rr & 1) * UPLANE + (127 - (rr >> 1)) * 16); }
            p[0] = 0.f;
            p[1] = bf_lo(r[0].z); p[2] = p[1] + bf_hi(r[0].z); p[3] = p[2] + bf_lo(r[0].w); p[4] = p[3] + bf_hi(r[0].w);
            #pragma unroll
            for (int i = 0; i < 8; i++) {
                const uint32_t wv = (&r[1 + (i >> 2)].x)[i & 3];
                p[5 + 2 * i] = p[4 + 2 * i] + bf_lo(wv); p[6 + 2 * i] = p[5 + 2 * i] + bf_hi(wv);
            }
            p[21] = p[20] + bf_lo(r[3].x); p[22] = p[21] + bf_hi(r[3].x); p[23] = p[22] + bf_lo(r[3].y);
            #pragma unroll
            for (int hf = 0; hf < 2; hf++) {
                const uint32_t ad = cc + CH_A3 + (2 * (2 * wp + hf) + hh) * 512 + (kap >> 3) * 256 + (kap & 7) * 16 + gam * 8;
                const int i = 4 * hf;
                sts64(ad, pack2(p[i + 9] - p[i], p[i + 10] - p[i + 1]), pack2(p[i + 11] - p[i + 2], p[i + 12] - p[i + 3]));
                sts64(ad + 128, pack2(p[i + 16] - p[i + 9], p[i + 17] - p[i + 10]), pack2(p[i + 18] - p[i + 11], p[i + 19] - p[i + 12]));
            }
        }
    }
    fence_async();
    mbar_arrive(bars + 8 * B_CONV);
    STAMP(21);
}

__global__ void __launch_bounds__(512, 1)
fused_kernel(const __grid_constant__ CUtensorMap tmX0, const __grid_constant__ CUtensorMap tmX1, const __grid_constant__ CUtensorMap tmXO,
             const __grid_constant__ CUtensorMap tmOut, const __grid_constant__ CUtensorMap tmWg, const __grid_constant__ CUtensorMap tmWu,
             const __grid_constant__ CUtensorMap tmWd, const __grid_constant__ Params P) {
    extern __shared__ uint8_t smem_raw[];
    const uint32_t sb = (smem_u32(smem_raw) + 1023) & ~1023u;
    const uint32_t bars = sb + OFF_BAR;
    const int warp = __shfl_sync(0xffffffffu, threadIdx.x >> 5, 0);
    if (warp == 12) {
        STAMP(24);
        const int lane = threadIdx.x & 31;
        for (int i = lane; i < B_COUNT; i += 32) {
            uint32_t cnt = 1;
            if (i >= B_EMPTYW && i < B_EMPTYW + 4) cnt = 8;
            else if ((i >= B_EMPTYX && i < B_EMPTYX + 4) || (i >= B_EMPTYD && i < B_EMPTYD + 6) || (i >= B_EMPTYH && i < B_EMPTYH + 5) || i == B_GO || i == B_CH0) cnt = 4;
            else if (i == B_STATS || i == B_CONV || i == B_LN || i >= B_EPI) cnt = 128;
            mbar_init(bars + 8 * i, cnt);
        }
        asm volatile("fence.mbarrier_init.release.cluster;" ::: "memory");
        fence_async();
    }
    __syncthreads();
    const int c = blockIdx.x, fb = c % 22, tg = c / 22, tau = c >> 2, dg = c & 3;
    if (warp >= 12) {
        asm volatile("setmaxnreg.dec.sync.aligned.u32 24;");
        if (warp == 12) {
            if (elect_one()) {
                #pragma unroll 1
                for (int st = 0; st < 8; st++) {
                    const int s = st & 3;
                    if (st >= 4) mbar_wait(bars + 8 * (B_EMPTYW + s), 0);
                    mbar_expect(bars + 8 * (B_FULLW + s), 16384);
                    tma2d(sb + OFF_W + s * 16384, &tmWg, 64 * fb, 64 * st, bars + 8 * (B_FULLW + s));
                    tma2d(sb + OFF_W + s * 16384 + 8192, &tmWu, 64 * fb, 64 * st, bars + 8 * (B_FULLW + s));
                }
                if (c < 128) {
                    int sd = 0; uint32_t pe = 1;
                    #pragma unroll 1
                    for (int st = 0; st < 22; st++) {
                        const uint32_t da = (sd == 2) ? OFF_X0 : (sd == 4) ? OFF_X0 + 22528 : OFF_W + ((sd + 1) >> 1) * 16384;
                        if (st < 6) {
                            if (sd == 2 || sd == 4) mbar_wait(bars + 8 * (B_EMPTYX + (sd >> 2)), 1);
                            else mbar_wait(bars + 8 * (B_EMPTYW + ((sd + 1) >> 1)), 1);
                        } else mbar_wait(bars + 8 * (B_EMPTYD + sd), pe);
                        mbar_expect(bars + 8 * (B_FULLD + sd), 16384);
                        tma2d(sb + da, &tmWd, 128 * dg, 64 * st, bars + 8 * (B_FULLD + sd));
                        tma2d(sb + da + 8192, &tmWd, 128 * dg + 64, 64 * st, bars + 8 * (B_FULLD + sd));
                        if (++sd == 6) { sd = 0; pe ^= 1; }
                    }
                }
            }
        } else if (warp == 13) {
            if (elect_one()) {
                #pragma unroll 1
                for (int st = 0; st < 8; st++) {
                    const int s = st & 1;
                    if (st >= 2) mbar_wait(bars + 8 * (B_EMPTYX + s), ((st >> 1) & 1) ^ 1);
                    mbar_expect(bars + 8 * (B_FULLX + s), 176 * 128);
                    tma2d(sb + OFF_X0 + s * 22528, &tmX0, 64 * st, TOKG * tg, bars + 8 * (B_FULLX + s));
                }
                if (c < 128) {
                    mbar_wait(bars + 8 * (B_EPI + 1), 0);
                    const int oa = 8 * tau, ob = 8 * tau + 7;
                    flag_wait(F_H + 2 * (oa / 43) + ((oa % 43) >= 22), 22);
                    flag_wait(F_H + 2 * (ob / 43) + ((ob % 43) >= 22), 22);
                    fence_async();
                    STAMP(25);
                    const char* hsrc = (const char*)g_H + tau * (172 * 1024);
                    int sh = 0; uint32_t pe = 1;
                    #pragma unroll 1
                    for (int st = 0; st < 22; st++) {
                        if (st >= 5) mbar_wait(bars + 8 * (B_EMPTYH + sh), pe);
                        const uint32_t nb = st < 21 ? 8192 : 4096;
                        mbar_expect(bars + 8 * (B_FULLH + sh), nb);
                        bulk_load(sb + OFF_X1 + sh * 8192, hsrc + st * 8192, nb, bars + 8 * (B_FULLH + sh));
                        if (++sh == 5) { sh = 0; pe ^= 1; }
                    }
                }
            }
        } else if (warp == 14) {
            if (elect_one()) {
                #pragma unroll 1
                for (int st = 0; st < 8; st++) {
                    const int s = st & 1;
                    if (st >= 2) mbar_wait(bars + 8 * (B_EMPTYX + 2 + s), ((st >> 1) & 1) ^ 1);
                    mbar_expect(bars + 8 * (B_FULLX + 2 + s), 168 * 128);
                    tma2d(sb + OFF_X1 + s * 21504, &tmX1, 64 * st, TOKG * tg + 176, bars + 8 * (B_FULLX + 2 + s));
                }
                if (c < 128) {
                    mbar_wait(bars + 8 * B_CH0, 0);
                    mbar_expect(bars + 8 * B_XO, 16384);
                    tma2d(sb + OFF_CONV, &tmXO, 128 * dg, 64 * tau, bars + 8 * B_XO);
                    tma2d(sb + OFF_CONV + 8192, &tmXO, 128 * dg + 64, 64 * tau, bars + 8 * B_XO);
                    flag_wait(F_S + dg, 64);
                    STAMP(26);
                    mbar_arrive(bars + 8 * B_S);
                    mbar_wait(bars + 8 * B_FULLH, 0);
                    exit_count();
                }
            }
        } else {
            if (elect_one()) {
                mbar_wait(bars + 8 * B_LN, 0);
                flag_signal(F_A);
                mbar_wait(bars + 8 * B_EPI, 0);
                flag_signal(F_H + 2 * tg);
                mbar_wait(bars + 8 * (B_EPI + 1), 0);
                flag_signal(F_H + 2 * tg + 1);
                if (c < 128) {
                    mbar_wait(bars + 8 * B_SIG, 0);
                    flag_signal(F_S + (c >> 5));
                    mbar_wait(bars + 8 * (B_SIG + 1), 0);
                    flag_signal(F_S + (c >> 5));
                }
            }
        }
    } else if (warp >= 8) {
        asm volatile("setmaxnreg.dec.sync.aligned.u32 80;");
        aux_role(sb, P);
    } else if (warp >= 4) {
        asm volatile("setmaxnreg.inc.sync.aligned.u32 200;");
        consumer<168, 1>(sb, &tmOut);
    } else {
        asm volatile("setmaxnreg.inc.sync.aligned.u32 208;");
        consumer<176, 0>(sb, &tmOut);
    }
}

typedef CUresult (*EncodeFn)(CUtensorMap*, CUtensorMapDataType, cuuint32_t, void*, const cuuint64_t*, const cuuint64_t*, const cuuint32_t*,
                             const cuuint32_t*, CUtensorMapInterleave, CUtensorMapSwizzle, CUtensorMapL2promotion, CUtensorMapFloatOOBfill);

CUtensorMap make_map(EncodeFn enc, const void* ptr, uint64_t inner, uint64_t outer, uint32_t box_outer) {
    CUtensorMap m;
    cuuint64_t dims[2] = {inner, outer}, strides[1] = {inner * 2};
    cuuint32_t box[2] = {64, box_outer}, es[2] = {1, 1};
    enc(&m, CU_TENSOR_MAP_DATA_TYPE_BFLOAT16, 2, (void*)ptr, dims, strides, box, es, CU_TENSOR_MAP_INTERLEAVE_NONE,
        CU_TENSOR_MAP_SWIZZLE_128B, CU_TENSOR_MAP_L2_PROMOTION_L2_128B, CU_TENSOR_MAP_FLOAT_OOB_FILL_NONE);
    return m;
}

}

extern "C" void kernel_launch(void* const* d_in, const int* in_sizes, int n_in, void* d_out, int out_size) {
    (void)in_sizes; (void)n_in; (void)out_size;
    static EncodeFn enc = nullptr;
    if (!enc) {
        cudaDriverEntryPointQueryResult qr;
        cudaGetDriverEntryPoint("cuTensorMapEncodeTiled", (void**)&enc, cudaEnableDefault, &qr);
        cudaFuncSetAttribute(fused_kernel, cudaFuncAttributeMaxDynamicSharedMemorySize, SMEM_BYTES);
    }
    const __nv_bfloat16* x = (const __nv_bfloat16*)d_in[0];
    Params P;
    P.x = x; P.logA = (const __nv_bfloat16*)d_in[1]; P.Aim = (const __nv_bfloat16*)d_in[2]; P.Cr = (const __nv_bfloat16*)d_in[3];
    P.Ci = (const __nv_bfloat16*)d_in[4]; P.logdt = (const __nv_bfloat16*)d_in[5]; P.Dskip = (const __nv_bfloat16*)d_in[6];
    P.Wg = (const __nv_bfloat16*)d_in[8]; P.Wu = (const __nv_bfloat16*)d_in[9];
    const CUtensorMap tmX0 = make_map(enc, x, DM, SEQ, 176), tmX1 = make_map(enc, x, DM, SEQ, 168), tmXO = make_map(enc, x, DM, SEQ, 64);
    const CUtensorMap tmOut = make_map(enc, d_out, DM, SEQ, 64);
    const CUtensorMap tmWg = make_map(enc, d_in[8], FF, DM, 64), tmWu = make_map(enc, d_in[9], FF, DM, 64), tmWd = make_map(enc, d_in[10], DM, FF, 64);
    fused_kernel<<<NCTA, 512, SMEM_BYTES>>>(tmX0, tmX1, tmXO, tmOut, tmWg, tmWu, tmWd, P);
}
```

```cpp
#include <cuda_runtime.h>
#include <cuda_bf16.h>
#include <cuda.h>
#include <stdint.h>

#define PROF 0

namespace {

constexpr int SEQ = 2048, DM = 512, FF = 1376;
constexpr int NCTA = 132;
constexpr int TOKG = 344;

constexpr uint32_t OFF_W = 0;
constexpr uint32_t OFF_X0 = 65536;
constexpr uint32_t OFF_X1 = 110592;
constexpr uint32_t OFF_CONV = 153600;
constexpr uint32_t CH_STRIDE = 17408;
constexpr uint32_t CH_T = 0;
constexpr uint32_t CH_A3 = 6272;
constexpr uint32_t CH_B3 = 10368;
constexpr uint32_t CH_U = 12416;
constexpr uint32_t CH_G = 16640;
constexpr uint32_t UPLANE = 2112;
constexpr uint32_t OFF_STATS = 223232;
constexpr uint32_t OFF_CSUM = 225984;
constexpr uint32_t OFF_RED = 226496;
constexpr uint32_t OFF_BAR = 228032;
constexpr uint32_t SMEM_BYTES = 228544 + 1024;

enum {
    B_FULLW = 0, B_EMPTYW = 4, B_FULLX = 8, B_EMPTYX = 12, B_FULLD = 16, B_EMPTYD = 22, B_FULLH = 28, B_EMPTYH = 33,
    B_STATS = 38, B_CONV = 39, B_U = 40, B_XO = 41, B_S = 42, B_GO = 43, B_CH0 = 44, B_LN = 45, B_EPI = 46, B_SIG = 48, B_COUNT = 50
};
enum { F_A = 0, F_H = 1, F_S = 13, F_EXIT = 17, F_COUNT = 18 };

__device__ uint4 g_xnT[DM * 256];
__device__ float2 g_stats[SEQ];
__device__ float g_csum[3 * 2 * 1408];
__device__ uint4 g_H[32 * 172 * 64];
__device__ uint2 g_S[256 * 1024];
__device__ unsigned g_flags[F_COUNT * 32];
#define STAMP(i) do {} while (0)

__device__ __forceinline__ uint32_t smem_u32(const void* p) { return (uint32_t)__cvta_generic_to_shared(p); }
__device__ __forceinline__ void mbar_init(uint32_t bar, uint32_t cnt) { asm volatile("mbarrier.init.shared::cta.b64 [%0], %1;" :: "r"(bar), "r"(cnt) : "memory"); }
__device__ __forceinline__ void mbar_expect(uint32_t bar, uint32_t bytes) { asm volatile("mbarrier.arrive.expect_tx.shared::cta.b64 _, [%0], %1;" :: "r"(bar), "r"(bytes) : "memory"); }
__device__ __forceinline__ void mbar_arrive(uint32_t bar) { asm volatile("mbarrier.arrive.shared::cta.b64 _, [%0];" :: "r"(bar) : "memory"); }
__device__ __forceinline__ void mbar_wait(uint32_t bar, uint32_t parity) {
    uint32_t ok, n = 0;
    do {
        asm volatile("{.reg .pred p; mbarrier.try_wait.parity.shared::cta.b64 p, [%1], %2; selp.u32 %0, 1, 0, p;}" : "=r"(ok) : "r"(bar), "r"(parity) : "memory");
        if (!ok && ++n > (1u << 22)) __trap();
    } while (!ok);
}
__device__ __forceinline__ void mbar_wait_c(uint32_t bar, uint32_t parity) {
    asm volatile("{.reg .pred p; .reg .u32 n; mov.u32 n, 0;\n"
                 "LAB_WAIT: mbarrier.try_wait.parity.shared::cta.b64 p, [%0], %1;\n"
                 "@p bra LAB_DONE; add.u32 n, n, 1; setp.lt.u32 p, n, 0x200000; @p bra LAB_WAIT;\n"
                 "LAB_DONE: }" :: "r"(bar), "r"(parity) : "memory");
}
__device__ __forceinline__ bool elect_one() { uint32_t p; asm volatile("{.reg .pred P; elect.sync _|P, 0xffffffff; selp.u32 %0, 1, 0, P;}" : "=r"(p)); return p; }
__device__ __forceinline__ void tma2d(uint32_t dst, const CUtensorMap* m, int c0, int c1, uint32_t bar) {
    asm volatile("cp.async.bulk.tensor.2d.shared::cluster.global.mbarrier::complete_tx::bytes [%0], [%1, {%3, %4}], [%2];"
        :: "r"(dst), "l"(m), "r"(bar), "r"(c0), "r"(c1) : "memory");
}
__device__ __forceinline__ void tma2d_store(const CUtensorMap* m, int c0, int c1, uint32_t src) {
    asm volatile("cp.async.bulk.tensor.2d.global.shared::cta.bulk_group [%0, {%2, %3}], [%1];" :: "l"(m), "r"(src), "r"(c0), "r"(c1) : "memory");
}
__device__ __forceinline__ void bulk_load(uint32_t dst, const void* src, uint32_t bytes, uint32_t bar) {
    asm volatile("cp.async.bulk.shared::cluster.global.mbarrier::complete_tx::bytes [%0], [%1], %2, [%3];" :: "r"(dst), "l"(src), "r"(bytes), "r"(bar) : "memory");
}
__device__ __forceinline__ void fence_async() { asm volatile("fence.proxy.async;" ::: "memory"); }
__device__ __forceinline__ void flag_wait(int f, unsigned target) {
    const unsigned* p = g_flags + f * 32; unsigned v, n = 0;
    while (true) {
        asm volatile("ld.acquire.gpu.global.u32 %0, [%1];" : "=r"(v) : "l"(p) : "memory");
        if (v >= target) break;
        if (++n > (1u << 22)) __trap();
        __nanosleep(20);
    }
}
__device__ __forceinline__ void flag_signal(int f) {
    asm volatile("fence.acq_rel.gpu;" ::: "memory");
    asm volatile("red.relaxed.gpu.global.add.u32 [%0], 1;" :: "l"(g_flags + f * 32) : "memory");
}
__device__ __forceinline__ void exit_count() {
    unsigned old = atomicAdd(g_flags + F_EXIT * 32, 1u);
    if (old == NCTA - 1) {
        #pragma unroll 1
        for (int i = 0; i < F_COUNT; i++) g_flags[i * 32] = 0;
    }
}
__device__ __forceinline__ void bar_sync(int id) { asm volatile("bar.sync %0, 128;" :: "r"(id) : "memory"); }
__device__ __forceinline__ uint64_t mkdesc(uint32_t addr, uint32_t lbo, uint32_t sbo, uint32_t swz) {
    return (uint64_t)((addr & 0x3FFFF) >> 4) | ((uint64_t)(lbo >> 4) << 16) | ((uint64_t)(sbo >> 4) << 32) | ((uint64_t)swz << 62);
}
#define WG_FENCE() asm volatile("wgmma.fence.sync.aligned;" ::: "memory")
#define WG_COMMIT() asm volatile("wgmma.commit_group.sync.aligned;" ::: "memory")
#define WG_WAIT(n) asm volatile("wgmma.wait_group.sync.aligned " #n ";" ::: "memory")
template <int N> __device__ __forceinline__ void fence_acc(float (&d)[N]) {
    #pragma unroll
    for (int i = 0; i < N; i++) asm volatile("" : "+f"(d[i]) :: "memory");
}
__device__ __forceinline__ uint32_t pack2(float lo, float hi) { uint32_t r; asm("cvt.rn.bf16x2.f32 %0, %1, %2;" : "=r"(r) : "f"(hi), "f"(lo)); return r; }
__device__ __forceinline__ float bf_lo(uint32_t v) { return __uint_as_float(v << 16); }
__device__ __forceinline__ float bf_hi(uint32_t v) { return __uint_as_float(v & 0xffff0000u); }
__device__ __forceinline__ float bf_round(float v) { return __bfloat162float(__float2bfloat16_rn(v)); }
__device__ __forceinline__ float tanh_fast(float v) { float r; asm("tanh.approx.f32 %0, %1;" : "=f"(r) : "f"(v)); return r; }
__device__ __forceinline__ uint4 lds128(uint32_t a) { uint4 v; asm volatile("ld.shared.v4.b32 {%0,%1,%2,%3}, [%4];" : "=r"(v.x), "=r"(v.y), "=r"(v.z), "=r"(v.w) : "r"(a)); return v; }
__device__ __forceinline__ uint2 lds64(uint32_t a) { uint2 v; asm volatile("ld.shared.v2.b32 {%0,%1}, [%2];" : "=r"(v.x), "=r"(v.y) : "r"(a)); return v; }
__device__ __forceinline__ float ldsf(uint32_t a) { float v; asm volatile("ld.shared.f32 %0, [%1];" : "=f"(v) : "r"(a)); return v; }
__device__ __forceinline__ void sts128(uint32_t a, uint32_t x, uint32_t y, uint32_t z, uint32_t w) { asm volatile("st.shared.v4.b32 [%0], {%1,%2,%3,%4};" :: "r"(a), "r"(x), "r"(y), "r"(z), "r"(w) : "memory"); }
__device__ __forceinline__ void sts64(uint32_t a, uint32_t x, uint32_t y) { asm volatile("st.shared.v2.b32 [%0], {%1,%2};" :: "r"(a), "r"(x), "r"(y) : "memory"); }
__device__ __forceinline__ void stsf(uint32_t a, float x) { asm volatile("st.shared.f32 [%0], %1;" :: "r"(a), "f"(x) : "memory"); }
__device__ __forceinline__ void sts16(uint32_t a, uint32_t x) { asm volatile("st.shared.b16 [%0], %1;" :: "r"(a), "h"((unsigned short)x) : "memory"); }
__device__ __forceinline__ uint4 ldg128(const void* p) { uint4 v; asm volatile("ld.global.nc.L1::no_allocate.v4.b32 {%0,%1,%2,%3}, [%4];" : "=r"(v.x), "=r"(v.y), "=r"(v.z), "=r"(v.w) : "l"(p)); return v; }

template<int N> __device__ __forceinline__ void wg_rs(float (&d)[64], uint32_t a0, uint32_t a1, uint32_t a2, uint32_t a3, uint64_t db, int sc);
template<> __device__ __forceinline__ void wg_rs<128>(float (&d)[64], uint32_t a0, uint32_t a1, uint32_t a2, uint32_t a3, uint64_t db, int sc) {
  asm volatile("{.reg .pred p; setp.ne.b32 p, %69, 0; wgmma.mma_async.sync.aligned.m64n128k16.f32.bf16.bf16 {%0,%1,%2,%3,%4,%5,%6,%7,%8,%9,%10,%11,%12,%13,%14,%15,%16,%17,%18,%19,%20,%21,%22,%23,%24,%25,%26,%27,%28,%29,%30,%31,%32,%33,%34,%35,%36,%37,%38,%39,%40,%41,%42,%43,%44,%45,%46,%47,%48,%49,%50,%51,%52,%53,%54,%55,%56,%57,%58,%59,%60,%61,%62,%63}, {%64,%65,%66,%67}, %68, p, 1, 1, 0;}"
    : "+f"(d[0]),"+f"(d[1]),"+f"(d[2]),"+f"(d[3]),"+f"(d[4]),"+f"(d[5]),"+f"(d[6]),"+f"(d[7]),"+f"(d[8]),"+f"(d[9]),"+f"(d[10]),"+f"(d[11]),"+f"(d[12]),"+f"(d[13]),"+f"(d[14]),"+f"(d[15]),"+f"(d[16]),"+f"(d[17]),"+f"(d[18]),"+f"(d[19]),"+f"(d[20]),"+f"(d[21]),"+f"(d[22]),"+f"(d[23]),"+f"(d[24]),"+f"(d[25]),"+f"(d[26]),"+f"(d[27]),"+f"(d[28]),"+f"(d[29]),"+f"(d[30]),"+f"(d[31]),"+f"(d[32]),"+f"(d[33]),"+f"(d[34]),"+f"(d[35]),"+f"(d[36]),"+f"(d[37]),"+f"(d[38]),"+f"(d[39]),"+f"(d[40]),"+f"(d[41]),"+f"(d[42]),"+f"(d[43]),"+f"(d[44]),"+f"(d[45]),"+f"(d[46]),"+f"(d[47]),"+f"(d[48]),"+f"(d[49]),"+f"(d[50]),"+f"(d[51]),"+f"(d[52]),"+f"(d[53]),"+f"(d[54]),"+f"(d[55]),"+f"(d[56]),"+f"(d[57]),"+f"(d[58]),"+f"(d[59]),"+f"(d[60]),"+f"(d[61]),"+f"(d[62]),"+f"(d[63]) : "r"(a0), "r"(a1), "r"(a2), "r"(a3), "l"(db), "r"(sc));
}
template<> __device__ __forceinline__ void wg_rs<120>(float (&d)[64], uint32_t a0, uint32_t a1, uint32_t a2, uint32_t a3, uint64_t db, int sc) {
  asm volatile("{.reg .pred p; setp.ne.b32 p, %65, 0; wgmma.mma_async.sync.aligned.m64n120k16.f32.bf16.bf16 {%0,%1,%2,%3,%4,%5,%6,%7,%8,%9,%10,%11,%12,%13,%14,%15,%16,%17,%18,%19,%20,%21,%22,%23,%24,%25,%26,%27,%28,%29,%30,%31,%32,%33,%34,%35,%36,%37,%38,%39,%40,%41,%42,%43,%44,%45,%46,%47,%48,%49,%50,%51,%52,%53,%54,%55,%56,%57,%58,%59}, {%60,%61,%62,%63}, %64, p, 1, 1, 0;}"
    : "+f"(d[0]),"+f"(d[1]),"+f"(d[2]),"+f"(d[3]),"+f"(d[4]),"+f"(d[5]),"+f"(d[6]),"+f"(d[7]),"+f"(d[8]),"+f"(d[9]),"+f"(d[10]),"+f"(d[11]),"+f"(d[12]),"+f"(d[13]),"+f"(d[14]),"+f"(d[15]),"+f"(d[16]),"+f"(d[17]),"+f"(d[18]),"+f"(d[19]),"+f"(d[20]),"+f"(d[21]),"+f"(d[22]),"+f"(d[23]),"+f"(d[24]),"+f"(d[25]),"+f"(d[26]),"+f"(d[27]),"+f"(d[28]),"+f"(d[29]),"+f"(d[30]),"+f"(d[31]),"+f"(d[32]),"+f"(d[33]),"+f"(d[34]),"+f"(d[35]),"+f"(d[36]),"+f"(d[37]),"+f"(d[38]),"+f"(d[39]),"+f"(d[40]),"+f"(d[41]),"+f"(d[42]),"+f"(d[43]),"+f"(d[44]),"+f"(d[45]),"+f"(d[46]),"+f"(d[47]),"+f"(d[48]),"+f"(d[49]),"+f"(d[50]),"+f"(d[51]),"+f"(d[52]),"+f"(d[53]),"+f"(d[54]),"+f"(d[55]),"+f"(d[56]),"+f"(d[57]),"+f"(d[58]),"+f"(d[59]) : "r"(a0), "r"(a1), "r"(a2), "r"(a3), "l"(db), "r"(sc));
}
template<> __device__ __forceinline__ void wg_rs<112>(float (&d)[64], uint32_t a0, uint32_t a1, uint32_t a2, uint32_t a3, uint64_t db, int sc) {
  asm volatile("{.reg .pred p; setp.ne.b32 p, %61, 0; wgmma.mma_async.sync.aligned.m64n112k16.f32.bf16.bf16 {%0,%1,%2,%3,%4,%5,%6,%7,%8,%9,%10,%11,%12,%13,%14,%15,%16,%17,%18,%19,%20,%21,%22,%23,%24,%25,%26,%27,%28,%29,%30,%31,%32,%33,%34,%35,%36,%37,%38,%39,%40,%41,%42,%43,%44,%45,%46,%47,%48,%49,%50,%51,%52,%53,%54,%55}, {%56,%57,%58,%59}, %60, p, 1, 1, 0;}"
    : "+f"(d[0]),"+f"(d[1]),"+f"(d[2]),"+f"(d[3]),"+f"(d[4]),"+f"(d[5]),"+f"(d[6]),"+f"(d[7]),"+f"(d[8]),"+f"(d[9]),"+f"(d[10]),"+f"(d[11]),"+f"(d[12]),"+f"(d[13]),"+f"(d[14]),"+f"(d[15]),"+f"(d[16]),"+f"(d[17]),"+f"(d[18]),"+f"(d[19]),"+f"(d[20]),"+f"(d[21]),"+f"(d[22]),"+f"(d[23]),"+f"(d[24]),"+f"(d[25]),"+f"(d[26]),"+f"(d[27]),"+f"(d[28]),"+f"(d[29]),"+f"(d[30]),"+f"(d[31]),"+f"(d[32]),"+f"(d[33]),"+f"(d[34]),"+f"(d[35]),"+f"(d[36]),"+f"(d[37]),"+f"(d[38]),"+f"(d[39]),"+f"(d[40]),"+f"(d[41]),"+f"(d[42]),"+f"(d[43]),"+f"(d[44]),"+f"(d[45]),"+f"(d[46]),"+f"(d[47]),"+f"(d[48]),"+f"(d[49]),"+f"(d[50]),"+f"(d[51]),"+f"(d[52]),"+f"(d[53]),"+f"(d[54]),"+f"(d[55]) : "r"(a0), "r"(a1), "r"(a2), "r"(a3), "l"(db), "r"(sc));
}
template<> __device__ __forceinline__ void wg_rs<104>(float (&d)[64], uint32_t a0, uint32_t a1, uint32_t a2, uint32_t a3, uint64_t db, int sc) {
  asm volatile("{.reg .pred p; setp.ne.b32 p, %57, 0; wgmma.mma_async.sync.aligned.m64n104k16.f32.bf16.bf16 {%0,%1,%2,%3,%4,%5,%6,%7,%8,%9,%10,%11,%12,%13,%14,%15,%16,%17,%18,%19,%20,%21,%22,%23,%24,%25,%26,%27,%28,%29,%30,%31,%32,%33,%34,%35,%36,%37,%38,%39,%40,%41,%42,%43,%44,%45,%46,%47,%48,%49,%50,%51}, {%52,%53,%54,%55}, %56, p, 1, 1, 0;}"
    : "+f"(d[0]),"+f"(d[1]),"+f"(d[2]),"+f"(d[3]),"+f"(d[4]),"+f"(d[5]),"+f"(d[6]),"+f"(d[7]),"+f"(d[8]),"+f"(d[9]),"+f"(d[10]),"+f"(d[11]),"+f"(d[12]),"+f"(d[13]),"+f"(d[14]),"+f"(d[15]),"+f"(d[16]),"+f"(d[17]),"+f"(d[18]),"+f"(d[19]),"+f"(d[20]),"+f"(d[21]),"+f"(d[22]),"+f"(d[23]),"+f"(d[24]),"+f"(d[25]),"+f"(d[26]),"+f"(d[27]),"+f"(d[28]),"+f"(d[29]),"+f"(d[30]),"+f"(d[31]),"+f"(d[32]),"+f"(d[33]),"+f"(d[34]),"+f"(d[35]),"+f"(d[36]),"+f"(d[37]),"+f"(d[38]),"+f"(d[39]),"+f"(d[40]),"+f"(d[41]),"+f"(d[42]),"+f"(d[43]),"+f"(d[44]),"+f"(d[45]),"+f"(d[46]),"+f"(d[47]),"+f"(d[48]),"+f"(d[49]),"+f"(d[50]),"+f"(d[51]) : "r"(a0), "r"(a1), "r"(a2), "r"(a3), "l"(db), "r"(sc));
}
template<> __device__ __forceinline__ void wg_rs<96>(float (&d)[64], uint32_t a0, uint32_t a1, uint32_t a2, uint32_t a3, uint64_t db, int sc) {
  asm volatile("{.reg .pred p; setp.ne.b32 p, %53, 0; wgmma.mma_async.sync.aligned.m64n96k16.f32.bf16.bf16 {%0,%1,%2,%3,%4,%5,%6,%7,%8,%9,%10,%11,%12,%13,%14,%15,%16,%17,%18,%19,%20,%21,%22,%23,%24,%25,%26,%27,%28,%29,%30,%31,%32,%33,%34,%35,%36,%37,%38,%39,%40,%41,%42,%43,%44,%45,%46,%47}, {%48,%49,%50,%51}, %52, p, 1, 1, 0;}"
    : "+f"(d[0]),"+f"(d[1]),"+f"(d[2]),"+f"(d[3]),"+f"(d[4]),"+f"(d[5]),"+f"(d[6]),"+f"(d[7]),"+f"(d[8]),"+f"(d[9]),"+f"(d[10]),"+f"(d[11]),"+f"(d[12]),"+f"(d[13]),"+f"(d[14]),"+f"(d[15]),"+f"(d[16]),"+f"(d[17]),"+f"(d[18]),"+f"(d[19]),"+f"(d[20]),"+f"(d[21]),"+f"(d[22]),"+f"(d[23]),"+f"(d[24]),"+f"(d[25]),"+f"(d[26]),"+f"(d[27]),"+f"(d[28]),"+f"(d[29]),"+f"(d[30]),"+f"(d[31]),"+f"(d[32]),"+f"(d[33]),"+f"(d[34]),"+f"(d[35]),"+f"(d[36]),"+f"(d[37]),"+f"(d[38]),"+f"(d[39]),"+f"(d[40]),"+f"(d[41]),"+f"(d[42]),"+f"(d[43]),"+f"(d[44]),"+f"(d[45]),"+f"(d[46]),"+f"(d[47]) : "r"(a0), "r"(a1), "r"(a2), "r"(a3), "l"(db), "r"(sc));
}
template<> __device__ __forceinline__ void wg_rs<88>(float (&d)[64], uint32_t a0, uint32_t a1, uint32_t a2, uint32_t a3, uint64_t db, int sc) {
  asm volatile("{.reg .pred p; setp.ne.b32 p, %49, 0; wgmma.mma_async.sync.aligned.m64n88k16.f32.bf16.bf16 {%0,%1,%2,%3,%4,%5,%6,%7,%8,%9,%10,%11,%12,%13,%14,%15,%16,%17,%18,%19,%20,%21,%22,%23,%24,%25,%26,%27,%28,%29,%30,%31,%32,%33,%34,%35,%36,%37,%38,%39,%40,%41,%42,%43}, {%44,%45,%46,%47}, %48, p, 1, 1, 0;}"
    : "+f"(d[0]),"+f"(d[1]),"+f"(d[2]),"+f"(d[3]),"+f"(d[4]),"+f"(d[5]),"+f"(d[6]),"+f"(d[7]),"+f"(d[8]),"+f"(d[9]),"+f"(d[10]),"+f"(d[11]),"+f"(d[12]),"+f"(d[13]),"+f"(d[14]),"+f"(d[15]),"+f"(d[16]),"+f"(d[17]),"+f"(d[18]),"+f"(d[19]),"+f"(d[20]),"+f"(d[21]),"+f"(d[22]),"+f"(d[23]),"+f"(d[24]),"+f"(d[25]),"+f"(d[26]),"+f"(d[27]),"+f"(d[28]),"+f"(d[29]),"+f"(d[30]),"+f"(d[31]),"+f"(d[32]),"+f"(d[33]),"+f"(d[34]),"+f"(d[35]),"+f"(d[36]),"+f"(d[37]),"+f"(d[38]),"+f"(d[39]),"+f"(d[40]),"+f"(d[41]),"+f"(d[42]),"+f"(d[43]) : "r"(a0), "r"(a1), "r"(a2), "r"(a3), "l"(db), "r"(sc));
}
template<> __device__ __forceinline__ void wg_rs<80>(float (&d)[64], uint32_t a0, uint32_t a1, uint32_t a2, uint32_t a3, uint64_t db, int sc) {
  asm volatile("{.reg .pred p; setp.ne.b32 p, %45, 0; wgmma.mma_async.sync.aligned.m64n80k16.f32.bf16.bf16 {%0,%1,%2,%3,%4,%5,%6,%7,%8,%9,%10,%11,%12,%13,%14,%15,%16,%17,%18,%19,%20,%21,%22,%23,%24,%25,%26,%27,%28,%29,%30,%31,%32,%33,%34,%35,%36,%37,%38,%39}, {%40,%41,%42,%43}, %44, p, 1, 1, 0;}"
    : "+f"(d[0]),"+f"(d[1]),"+f"(d[2]),"+f"(d[3]),"+f"(d[4]),"+f"(d[5]),"+f"(d[6]),"+f"(d[7]),"+f"(d[8]),"+f"(d[9]),"+f"(d[10]),"+f"(d[11]),"+f"(d[12]),"+f"(d[13]),"+f"(d[14]),"+f"(d[15]),"+f"(d[16]),"+f"(d[17]),"+f"(d[18]),"+f"(d[19]),"+f"(d[20]),"+f"(d[21]),"+f"(d[22]),"+f"(d[23]),"+f"(d[24]),"+f"(d[25]),"+f"(d[26]),"+f"(d[27]),"+f"(d[28]),"+f"(d[29]),"+f"(d[30]),"+f"(d[31]),"+f"(d[32]),"+f"(d[33]),"+f"(d[34]),"+f"(d[35]),"+f"(d[36]),"+f"(d[37]),"+f"(d[38]),"+f"(d[39]) : "r"(a0), "r"(a1), "r"(a2), "r"(a3), "l"(db), "r"(sc));
}
template<> __device__ __forceinline__ void wg_rs<72>(float (&d)[64], uint32_t a0, uint32_t a1, uint32_t a2, uint32_t a3, uint64_t db, int sc) {
  asm volatile("{.reg .pred p; setp.ne.b32 p, %41, 0; wgmma.mma_async.sync.aligned.m64n72k16.f32.bf16.bf16 {%0,%1,%2,%3,%4,%5,%6,%7,%8,%9,%10,%11,%12,%13,%14,%15,%16,%17,%18,%19,%20,%21,%22,%23,%24,%25,%26,%27,%28,%29,%30,%31,%32,%33,%34,%35}, {%36,%37,%38,%39}, %40, p, 1, 1, 0;}"
    : "+f"(d[0]),"+f"(d[1]),"+f"(d[2]),"+f"(d[3]),"+f"(d[4]),"+f"(d[5]),"+f"(d[6]),"+f"(d[7]),"+f"(d[8]),"+f"(d[9]),"+f"(d[10]),"+f"(d[11]),"+f"(d[12]),"+f"(d[13]),"+f"(d[14]),"+f"(d[15]),"+f"(d[16]),"+f"(d[17]),"+f"(d[18]),"+f"(d[19]),"+f"(d[20]),"+f"(d[21]),"+f"(d[22]),"+f"(d[23]),"+f"(d[24]),"+f"(d[25]),"+f"(d[26]),"+f"(d[27]),"+f"(d[28]),"+f"(d[29]),"+f"(d[30]),"+f"(d[31]),"+f"(d[32]),"+f"(d[33]),"+f"(d[34]),"+f"(d[35]) : "r"(a0), "r"(a1), "r"(a2), "r"(a3), "l"(db), "r"(sc));
}
template<> __device__ __forceinline__ void wg_rs<64>(float (&d)[64], uint32_t a0, uint32_t a1, uint32_t a2, uint32_t a3, uint64_t db, int sc) {
  asm volatile("{.reg .pred p; setp.ne.b32 p, %37, 0; wgmma.mma_async.sync.aligned.m64n64k16.f32.bf16.bf16 {%0,%1,%2,%3,%4,%5,%6,%7,%8,%9,%10,%11,%12,%13,%14,%15,%16,%17,%18,%19,%20,%21,%22,%23,%24,%25,%26,%27,%28,%29,%30,%31}, {%32,%33,%34,%35}, %36, p, 1, 1, 0;}"
    : "+f"(d[0]),"+f"(d[1]),"+f"(d[2]),"+f"(d[3]),"+f"(d[4]),"+f"(d[5]),"+f"(d[6]),"+f"(d[7]),"+f"(d[8]),"+f"(d[9]),"+f"(d[10]),"+f"(d[11]),"+f"(d[12]),"+f"(d[13]),"+f"(d[14]),"+f"(d[15]),"+f"(d[16]),"+f"(d[17]),"+f"(d[18]),"+f"(d[19]),"+f"(d[20]),"+f"(d[21]),"+f"(d[22]),"+f"(d[23]),"+f"(d[24]),"+f"(d[25]),"+f"(d[26]),"+f"(d[27]),"+f"(d[28]),"+f"(d[29]),"+f"(d[30]),"+f"(d[31]) : "r"(a0), "r"(a1), "r"(a2), "r"(a3), "l"(db), "r"(sc));
}
__device__ __forceinline__ void wg_tt128(float (&d)[64], uint64_t da, uint64_t db, int sc) {
  asm volatile("{.reg .pred p; setp.ne.b32 p, %66, 0; wgmma.mma_async.sync.aligned.m64n128k16.f32.bf16.bf16 {%0,%1,%2,%3,%4,%5,%6,%7,%8,%9,%10,%11,%12,%13,%14,%15,%16,%17,%18,%19,%20,%21,%22,%23,%24,%25,%26,%27,%28,%29,%30,%31,%32,%33,%34,%35,%36,%37,%38,%39,%40,%41,%42,%43,%44,%45,%46,%47,%48,%49,%50,%51,%52,%53,%54,%55,%56,%57,%58,%59,%60,%61,%62,%63}, %64, %65, p, 1, 1, 1, 1;}"
    : "+f"(d[0]),"+f"(d[1]),"+f"(d[2]),"+f"(d[3]),"+f"(d[4]),"+f"(d[5]),"+f"(d[6]),"+f"(d[7]),"+f"(d[8]),"+f"(d[9]),"+f"(d[10]),"+f"(d[11]),"+f"(d[12]),"+f"(d[13]),"+f"(d[14]),"+f"(d[15]),"+f"(d[16]),"+f"(d[17]),"+f"(d[18]),"+f"(d[19]),"+f"(d[20]),"+f"(d[21]),"+f"(d[22]),"+f"(d[23]),"+f"(d[24]),"+f"(d[25]),"+f"(d[26]),"+f"(d[27]),"+f"(d[28]),"+f"(d[29]),"+f"(d[30]),"+f"(d[31]),"+f"(d[32]),"+f"(d[33]),"+f"(d[34]),"+f"(d[35]),"+f"(d[36]),"+f"(d[37]),"+f"(d[38]),"+f"(d[39]),"+f"(d[40]),"+f"(d[41]),"+f"(d[42]),"+f"(d[43]),"+f"(d[44]),"+f"(d[45]),"+f"(d[46]),"+f"(d[47]),"+f"(d[48]),"+f"(d[49]),"+f"(d[50]),"+f"(d[51]),"+f"(d[52]),"+f"(d[53]),"+f"(d[54]),"+f"(d[55]),"+f"(d[56]),"+f"(d[57]),"+f"(d[58]),"+f"(d[59]),"+f"(d[60]),"+f"(d[61]),"+f"(d[62]),"+f"(d[63]) : "l"(da), "l"(db), "r"(sc));
}
__device__ __forceinline__ void wg_tt64(float (&d)[64], uint64_t da, uint64_t db, int sc) {
  asm volatile("{.reg .pred p; setp.ne.b32 p, %34, 0; wgmma.mma_async.sync.aligned.m64n64k16.f32.bf16.bf16 {%0,%1,%2,%3,%4,%5,%6,%7,%8,%9,%10,%11,%12,%13,%14,%15,%16,%17,%18,%19,%20,%21,%22,%23,%24,%25,%26,%27,%28,%29,%30,%31}, %32, %33, p, 1, 1, 1, 1;}"
    : "+f"(d[0]),"+f"(d[1]),"+f"(d[2]),"+f"(d[3]),"+f"(d[4]),"+f"(d[5]),"+f"(d[6]),"+f"(d[7]),"+f"(d[8]),"+f"(d[9]),"+f"(d[10]),"+f"(d[11]),"+f"(d[12]),"+f"(d[13]),"+f"(d[14]),"+f"(d[15]),"+f"(d[16]),"+f"(d[17]),"+f"(d[18]),"+f"(d[19]),"+f"(d[20]),"+f"(d[21]),"+f"(d[22]),"+f"(d[23]),"+f"(d[24]),"+f"(d[25]),"+f"(d[26]),"+f"(d[27]),"+f"(d[28]),"+f"(d[29]),"+f"(d[30]),"+f"(d[31]) : "l"(da), "l"(db), "r"(sc));
}
__device__ __forceinline__ void wg_tt32(float (&d)[64], uint64_t da, uint64_t db, int sc) {
  asm volatile("{.reg .pred p; setp.ne.b32 p, %18, 0; wgmma.mma_async.sync.aligned.m64n32k16.f32.bf16.bf16 {%0,%1,%2,%3,%4,%5,%6,%7,%8,%9,%10,%11,%12,%13,%14,%15}, %16, %17, p, 1, 1, 1, 1;}"
    : "+f"(d[0]),"+f"(d[1]),"+f"(d[2]),"+f"(d[3]),"+f"(d[4]),"+f"(d[5]),"+f"(d[6]),"+f"(d[7]),"+f"(d[8]),"+f"(d[9]),"+f"(d[10]),"+f"(d[11]),"+f"(d[12]),"+f"(d[13]),"+f"(d[14]),"+f"(d[15]) : "l"(da), "l"(db), "r"(sc));
}
__device__ __forceinline__ void wg_g1(float (&d)[88], uint64_t da, uint64_t db, int sc) {
  asm volatile("{.reg .pred p; setp.ne.b32 p, %90, 0; wgmma.mma_async.sync.aligned.m64n176k16.f32.bf16.bf16 {%0,%1,%2,%3,%4,%5,%6,%7,%8,%9,%10,%11,%12,%13,%14,%15,%16,%17,%18,%19,%20,%21,%22,%23,%24,%25,%26,%27,%28,%29,%30,%31,%32,%33,%34,%35,%36,%37,%38,%39,%40,%41,%42,%43,%44,%45,%46,%47,%48,%49,%50,%51,%52,%53,%54,%55,%56,%57,%58,%59,%60,%61,%62,%63,%64,%65,%66,%67,%68,%69,%70,%71,%72,%73,%74,%75,%76,%77,%78,%79,%80,%81,%82,%83,%84,%85,%86,%87}, %88, %89, p, 1, 1, 1, 0;}"
    : "+f"(d[0]),"+f"(d[1]),"+f"(d[2]),"+f"(d[3]),"+f"(d[4]),"+f"(d[5]),"+f"(d[6]),"+f"(d[7]),"+f"(d[8]),"+f"(d[9]),"+f"(d[10]),"+f"(d[11]),"+f"(d[12]),"+f"(d[13]),"+f"(d[14]),"+f"(d[15]),"+f"(d[16]),"+f"(d[17]),"+f"(d[18]),"+f"(d[19]),"+f"(d[20]),"+f"(d[21]),"+f"(d[22]),"+f"(d[23]),"+f"(d[24]),"+f"(d[25]),"+f"(d[26]),"+f"(d[27]),"+f"(d[28]),"+f"(d[29]),"+f"(d[30]),"+f"(d[31]),"+f"(d[32]),"+f"(d[33]),"+f"(d[34]),"+f"(d[35]),"+f"(d[36]),"+f"(d[37]),"+f"(d[38]),"+f"(d[39]),"+f"(d[40]),"+f"(d[41]),"+f"(d[42]),"+f"(d[43]),"+f"(d[44]),"+f"(d[45]),"+f"(d[46]),"+f"(d[47]),"+f"(d[48]),"+f"(d[49]),"+f"(d[50]),"+f"(d[51]),"+f"(d[52]),"+f"(d[53]),"+f"(d[54]),"+f"(d[55]),"+f"(d[56]),"+f"(d[57]),"+f"(d[58]),"+f"(d[59]),"+f"(d[60]),"+f"(d[61]),"+f"(d[62]),"+f"(d[63]),"+f"(d[64]),"+f"(d[65]),"+f"(d[66]),"+f"(d[67]),"+f"(d[68]),"+f"(d[69]),"+f"(d[70]),"+f"(d[71]),"+f"(d[72]),"+f"(d[73]),"+f"(d[74]),"+f"(d[75]),"+f"(d[76]),"+f"(d[77]),"+f"(d[78]),"+f"(d[79]),"+f"(d[80]),"+f"(d[81]),"+f"(d[82]),"+f"(d[83]),"+f"(d[84]),"+f"(d[85]),"+f"(d[86]),"+f"(d[87]) : "l"(da), "l"(db), "r"(sc));
}
__device__ __forceinline__ void wg_g1(float (&d)[84], uint64_t da, uint64_t db, int sc) {
  asm volatile("{.reg .pred p; setp.ne.b32 p, %86, 0; wgmma.mma_async.sync.aligned.m64n168k16.f32.bf16.bf16 {%0,%1,%2,%3,%4,%5,%6,%7,%8,%9,%10,%11,%12,%13,%14,%15,%16,%17,%18,%19,%20,%21,%22,%23,%24,%25,%26,%27,%28,%29,%30,%31,%32,%33,%34,%35,%36,%37,%38,%39,%40,%41,%42,%43,%44,%45,%46,%47,%48,%49,%50,%51,%52,%53,%54,%55,%56,%57,%58,%59,%60,%61,%62,%63,%64,%65,%66,%67,%68,%69,%70,%71,%72,%73,%74,%75,%76,%77,%78,%79,%80,%81,%82,%83}, %84, %85, p, 1, 1, 1, 0;}"
    : "+f"(d[0]),"+f"(d[1]),"+f"(d[2]),"+f"(d[3]),"+f"(d[4]),"+f"(d[5]),"+f"(d[6]),"+f"(d[7]),"+f"(d[8]),"+f"(d[9]),"+f"(d[10]),"+f"(d[11]),"+f"(d[12]),"+f"(d[13]),"+f"(d[14]),"+f"(d[15]),"+f"(d[16]),"+f"(d[17]),"+f"(d[18]),"+f"(d[19]),"+f"(d[20]),"+f"(d[21]),"+f"(d[22]),"+f"(d[23]),"+f"(d[24]),"+f"(d[25]),"+f"(d[26]),"+f"(d[27]),"+f"(d[28]),"+f"(d[29]),"+f"(d[30]),"+f"(d[31]),"+f"(d[32]),"+f"(d[33]),"+f"(d[34]),"+f"(d[35]),"+f"(d[36]),"+f"(d[37]),"+f"(d[38]),"+f"(d[39]),"+f"(d[40]),"+f"(d[41]),"+f"(d[42]),"+f"(d[43]),"+f"(d[44]),"+f"(d[45]),"+f"(d[46]),"+f"(d[47]),"+f"(d[48]),"+f"(d[49]),"+f"(d[50]),"+f"(d[51]),"+f"(d[52]),"+f"(d[53]),"+f"(d[54]),"+f"(d[55]),"+f"(d[56]),"+f"(d[57]),"+f"(d[58]),"+f"(d[59]),"+f"(d[60]),"+f"(d[61]),"+f"(d[62]),"+f"(d[63]),"+f"(d[64]),"+f"(d[65]),"+f"(d[66]),"+f"(d[67]),"+f"(d[68]),"+f"(d[69]),"+f"(d[70]),"+f"(d[71]),"+f"(d[72]),"+f"(d[73]),"+f"(d[74]),"+f"(d[75]),"+f"(d[76]),"+f"(d[77]),"+f"(d[78]),"+f"(d[79]),"+f"(d[80]),"+f"(d[81]),"+f"(d[82]),"+f"(d[83]) : "l"(da), "l"(db), "r"(sc));
}
__device__ __forceinline__ void wg_rs_first(float (&d)[64], uint32_t a0, uint32_t a1, uint32_t a2, uint32_t a3, uint64_t db) {
  asm volatile("{.reg .pred p; setp.ne.b32 p, 0, 0; wgmma.mma_async.sync.aligned.m64n128k16.f32.bf16.bf16 {%0,%1,%2,%3,%4,%5,%6,%7,%8,%9,%10,%11,%12,%13,%14,%15,%16,%17,%18,%19,%20,%21,%22,%23,%24,%25,%26,%27,%28,%29,%30,%31,%32,%33,%34,%35,%36,%37,%38,%39,%40,%41,%42,%43,%44,%45,%46,%47,%48,%49,%50,%51,%52,%53,%54,%55,%56,%57,%58,%59,%60,%61,%62,%63}, {%64,%65,%66,%67}, %68, p, 1, 1, 0;}"
    : "=f"(d[0]),"=f"(d[1]),"=f"(d[2]),"=f"(d[3]),"=f"(d[4]),"=f"(d[5]),"=f"(d[6]),"=f"(d[7]),"=f"(d[8]),"=f"(d[9]),"=f"(d[10]),"=f"(d[11]),"=f"(d[12]),"=f"(d[13]),"=f"(d[14]),"=f"(d[15]),"=f"(d[16]),"=f"(d[17]),"=f"(d[18]),"=f"(d[19]),"=f"(d[20]),"=f"(d[21]),"=f"(d[22]),"=f"(d[23]),"=f"(d[24]),"=f"(d[25]),"=f"(d[26]),"=f"(d[27]),"=f"(d[28]),"=f"(d[29]),"=f"(d[30]),"=f"(d[31]),"=f"(d[32]),"=f"(d[33]),"=f"(d[34]),"=f"(d[35]),"=f"(d[36]),"=f"(d[37]),"=f"(d[38]),"=f"(d[39]),"=f"(d[40]),"=f"(d[41]),"=f"(d[42]),"=f"(d[43]),"=f"(d[44]),"=f"(d[45]),"=f"(d[46]),"=f"(d[47]),"=f"(d[48]),"=f"(d[49]),"=f"(d[50]),"=f"(d[51]),"=f"(d[52]),"=f"(d[53]),"=f"(d[54]),"=f"(d[55]),"=f"(d[56]),"=f"(d[57]),"=f"(d[58]),"=f"(d[59]),"=f"(d[60]),"=f"(d[61]),"=f"(d[62]),"=f"(d[63]) : "r"(a0), "r"(a1), "r"(a2), "r"(a3), "l"(db));
}
__device__ __forceinline__ void wg_g1_first(float (&d)[88], uint64_t da, uint64_t db) {
  asm volatile("{.reg .pred p; setp.ne.b32 p, 0, 0; wgmma.mma_async.sync.aligned.m64n176k16.f32.bf16.bf16 {%0,%1,%2,%3,%4,%5,%6,%7,%8,%9,%10,%11,%12,%13,%14,%15,%16,%17,%18,%19,%20,%21,%22,%23,%24,%25,%26,%27,%28,%29,%30,%31,%32,%33,%34,%35,%36,%37,%38,%39,%40,%41,%42,%43,%44,%45,%46,%47,%48,%49,%50,%51,%52,%53,%54,%55,%56,%57,%58,%59,%60,%61,%62,%63,%64,%65,%66,%67,%68,%69,%70,%71,%72,%73,%74,%75,%76,%77,%78,%79,%80,%81,%82,%83,%84,%85,%86,%87}, %88, %89, p, 1, 1, 1, 0;}"
    : "=f"(d[0]),"=f"(d[1]),"=f"(d[2]),"=f"(d[3]),"=f"(d[4]),"=f"(d[5]),"=f"(d[6]),"=f"(d[7]),"=f"(d[8]),"=f"(d[9]),"=f"(d[10]),"=f"(d[11]),"=f"(d[12]),"=f"(d[13]),"=f"(d[14]),"=f"(d[15]),"=f"(d[16]),"=f"(d[17]),"=f"(d[18]),"=f"(d[19]),"=f"(d[20]),"=f"(d[21]),"=f"(d[22]),"=f"(d[23]),"=f"(d[24]),"=f"(d[25]),"=f"(d[26]),"=f"(d[27]),"=f"(d[28]),"=f"(d[29]),"=f"(d[30]),"=f"(d[31]),"=f"(d[32]),"=f"(d[33]),"=f"(d[34]),"=f"(d[35]),"=f"(d[36]),"=f"(d[37]),"=f"(d[38]),"=f"(d[39]),"=f"(d[40]),"=f"(d[41]),"=f"(d[42]),"=f"(d[43]),"=f"(d[44]),"=f"(d[45]),"=f"(d[46]),"=f"(d[47]),"=f"(d[48]),"=f"(d[49]),"=f"(d[50]),"=f"(d[51]),"=f"(d[52]),"=f"(d[53]),"=f"(d[54]),"=f"(d[55]),"=f"(d[56]),"=f"(d[57]),"=f"(d[58]),"=f"(d[59]),"=f"(d[60]),"=f"(d[61]),"=f"(d[62]),"=f"(d[63]),"=f"(d[64]),"=f"(d[65]),"=f"(d[66]),"=f"(d[67]),"=f"(d[68]),"=f"(d[69]),"=f"(d[70]),"=f"(d[71]),"=f"(d[72]),"=f"(d[73]),"=f"(d[74]),"=f"(d[75]),"=f"(d[76]),"=f"(d[77]),"=f"(d[78]),"=f"(d[79]),"=f"(d[80]),"=f"(d[81]),"=f"(d[82]),"=f"(d[83]),"=f"(d[84]),"=f"(d[85]),"=f"(d[86]),"=f"(d[87]) : "l"(da), "l"(db));
}
__device__ __forceinline__ void wg_g1_first(float (&d)[84], uint64_t da, uint64_t db) {
  asm volatile("{.reg .pred p; setp.ne.b32 p, 0, 0; wgmma.mma_async.sync.aligned.m64n168k16.f32.bf16.bf16 {%0,%1,%2,%3,%4,%5,%6,%7,%8,%9,%10,%11,%12,%13,%14,%15,%16,%17,%18,%19,%20,%21,%22,%23,%24,%25,%26,%27,%28,%29,%30,%31,%32,%33,%34,%35,%36,%37,%38,%39,%40,%41,%42,%43,%44,%45,%46,%47,%48,%49,%50,%51,%52,%53,%54,%55,%56,%57,%58,%59,%60,%61,%62,%63,%64,%65,%66,%67,%68,%69,%70,%71,%72,%73,%74,%75,%76,%77,%78,%79,%80,%81,%82,%83}, %84, %85, p, 1, 1, 1, 0;}"
    : "=f"(d[0]),"=f"(d[1]),"=f"(d[2]),"=f"(d[3]),"=f"(d[4]),"=f"(d[5]),"=f"(d[6]),"=f"(d[7]),"=f"(d[8]),"=f"(d[9]),"=f"(d[10]),"=f"(d[11]),"=f"(d[12]),"=f"(d[13]),"=f"(d[14]),"=f"(d[15]),"=f"(d[16]),"=f"(d[17]),"=f"(d[18]),"=f"(d[19]),"=f"(d[20]),"=f"(d[21]),"=f"(d[22]),"=f"(d[23]),"=f"(d[24]),"=f"(d[25]),"=f"(d[26]),"=f"(d[27]),"=f"(d[28]),"=f"(d[29]),"=f"(d[30]),"=f"(d[31]),"=f"(d[32]),"=f"(d[33]),"=f"(d[34]),"=f"(d[35]),"=f"(d[36]),"=f"(d[37]),"=f"(d[38]),"=f"(d[39]),"=f"(d[40]),"=f"(d[41]),"=f"(d[42]),"=f"(d[43]),"=f"(d[44]),"=f"(d[45]),"=f"(d[46]),"=f"(d[47]),"=f"(d[48]),"=f"(d[49]),"=f"(d[50]),"=f"(d[51]),"=f"(d[52]),"=f"(d[53]),"=f"(d[54]),"=f"(d[55]),"=f"(d[56]),"=f"(d[57]),"=f"(d[58]),"=f"(d[59]),"=f"(d[60]),"=f"(d[61]),"=f"(d[62]),"=f"(d[63]),"=f"(d[64]),"=f"(d[65]),"=f"(d[66]),"=f"(d[67]),"=f"(d[68]),"=f"(d[69]),"=f"(d[70]),"=f"(d[71]),"=f"(d[72]),"=f"(d[73]),"=f"(d[74]),"=f"(d[75]),"=f"(d[76]),"=f"(d[77]),"=f"(d[78]),"=f"(d[79]),"=f"(d[80]),"=f"(d[81]),"=f"(d[82]),"=f"(d[83]) : "l"(da), "l"(db));
}
__device__ __forceinline__ void wg_tt128_first(float (&d)[64], uint64_t da, uint64_t db) {
  asm volatile("{.reg .pred p; setp.ne.b32 p, 0, 0; wgmma.mma_async.sync.aligned.m64n128k16.f32.bf16.bf16 {%0,%1,%2,%3,%4,%5,%6,%7,%8,%9,%10,%11,%12,%13,%14,%15,%16,%17,%18,%19,%20,%21,%22,%23,%24,%25,%26,%27,%28,%29,%30,%31,%32,%33,%34,%35,%36,%37,%38,%39,%40,%41,%42,%43,%44,%45,%46,%47,%48,%49,%50,%51,%52,%53,%54,%55,%56,%57,%58,%59,%60,%61,%62,%63}, %64, %65, p, 1, 1, 1, 1;}"
    : "=f"(d[0]),"=f"(d[1]),"=f"(d[2]),"=f"(d[3]),"=f"(d[4]),"=f"(d[5]),"=f"(d[6]),"=f"(d[7]),"=f"(d[8]),"=f"(d[9]),"=f"(d[10]),"=f"(d[11]),"=f"(d[12]),"=f"(d[13]),"=f"(d[14]),"=f"(d[15]),"=f"(d[16]),"=f"(d[17]),"=f"(d[18]),"=f"(d[19]),"=f"(d[20]),"=f"(d[21]),"=f"(d[22]),"=f"(d[23]),"=f"(d[24]),"=f"(d[25]),"=f"(d[26]),"=f"(d[27]),"=f"(d[28]),"=f"(d[29]),"=f"(d[30]),"=f"(d[31]),"=f"(d[32]),"=f"(d[33]),"=f"(d[34]),"=f"(d[35]),"=f"(d[36]),"=f"(d[37]),"=f"(d[38]),"=f"(d[39]),"=f"(d[40]),"=f"(d[41]),"=f"(d[42]),"=f"(d[43]),"=f"(d[44]),"=f"(d[45]),"=f"(d[46]),"=f"(d[47]),"=f"(d[48]),"=f"(d[49]),"=f"(d[50]),"=f"(d[51]),"=f"(d[52]),"=f"(d[53]),"=f"(d[54]),"=f"(d[55]),"=f"(d[56]),"=f"(d[57]),"=f"(d[58]),"=f"(d[59]),"=f"(d[60]),"=f"(d[61]),"=f"(d[62]),"=f"(d[63]) : "l"(da), "l"(db));
}

struct Params {
    const __nv_bfloat16 *x, *logA, *Aim, *Cr, *Ci, *logdt, *Dskip, *Wg, *Wu;
};

__device__ __forceinline__ void conv_channel(uint32_t cb, int w, int lane, uint32_t (&res)[8], uint32_t bar_free) {
    const int q = lane & 3, g = lane >> 2, gam = g >> 2;
    float acc[64];
    uint4 a[5][4];
    {
        const uint32_t t0 = cb + CH_T + (uint32_t)(14 + 4 * w + (g & 3) + 32 * gam - 2 * q) * 80u;
        #pragma unroll
        for (int s4 = 0; s4 < 5; s4++) {
            a[s4][0] = lds128(t0 + s4 * 16);
            a[s4][1] = lds128(t0 + 16 * 80 + s4 * 16);
            a[s4][2] = lds128(t0 - 8 * 80 + s4 * 16);
            a[s4][3] = lds128(t0 + 8 * 80 + s4 * 16);
        }
    }
    const uint64_t dU = mkdesc(cb + CH_U, UPLANE, 128, 0);
    WG_FENCE();
#define CT(N, s, c) wg_rs<N>(acc, a[(s) >> 2][0].c, a[(s) >> 2][1].c, a[(s) >> 2][2].c, a[(s) >> 2][3].c, dU + 4 * (s), 1)
    wg_rs_first(acc, a[0][0].x, a[0][1].x, a[0][2].x, a[0][3].x, dU); CT(128, 1, y); CT(120, 2, z); CT(120, 3, w);
    CT(112, 4, x); CT(112, 5, y); CT(104, 6, z); CT(104, 7, w);
    CT(96, 8, x);  CT(96, 9, y);  CT(88, 10, z); CT(88, 11, w);
    CT(80, 12, x); CT(80, 13, y); CT(72, 14, z); CT(72, 15, w);
    CT(64, 16, x);
#undef CT
    wg_tt64(acc, mkdesc(cb + CH_A3, 128, 512, 0), mkdesc(cb + CH_B3, 128, 256, 0), 1);
    wg_tt32(acc, mkdesc(cb + CH_A3 + 256, 128, 512, 0), mkdesc(cb + CH_B3 + 1024, 128, 256, 0), 1);
    WG_COMMIT();
    WG_WAIT(0);
    fence_acc(acc);
    if (bar_free && lane == 0) mbar_arrive(bar_free);
    const int src1 = (lane & ~3) | ((q + 1) & 3);
    float E[16][2];
    #pragma unroll
    for (int j = 0; j < 16; j++) {
        const float nxt = (j < 15) ? acc[4 * (j + 1) + 2] : 0.f;
        const float sup = (q == 0) ? nxt : acc[4 * j + 2];
        const float v = __shfl_sync(0xffffffffu, sup, src1);
        E[j][0] = acc[4 * j] + acc[4 * j + 3];
        E[j][1] = acc[4 * j + 1] + v;
    }
    const int src2 = gam ? ((lane & 12) | ((q + 3) & 3)) : (16 | (lane & 12) | ((q + 1) & 3));
    const bool c1 = gam && q != 0, c2 = gam && q == 0;
    #pragma unroll
    for (int a2 = 0; a2 < 8; a2++) {
        float y[2];
        #pragma unroll
        for (int e = 0; e < 2; e++) {
            const float sup = c1 ? E[2 * a2][e] : E[2 * a2 + 1][e];
            const float nxt = (a2 < 7) ? E[2 * a2 + 2][e] : 0.f;
            const float keep = c2 ? nxt : (c1 ? E[2 * a2 + 1][e] : E[2 * a2][e]);
            y[e] = keep + __shfl_sync(0xffffffffu, sup, src2);
        }
        res[a2] = pack2(y[1], y[0]);
    }
}

template <int N, int V>
__device__ __forceinline__ void consumer(uint32_t sb, const CUtensorMap* tmOut) {
    const int tid = threadIdx.x & 127, w = tid >> 5, lane = tid & 31, q = lane & 3, g = lane >> 2;
    const int c = blockIdx.x, fb = c % 22, tg = c / 22;
    const uint32_t bars = sb + OFF_BAR;
    {
        float ag[N / 2], au[N / 2];
        const uint32_t xb = sb + (V ? OFF_X1 : OFF_X0);
        if (V == 1) mbar_wait_c(bars + 8 * B_GO, 0);
        #pragma unroll
        for (int st = 0; st < 8; st++) {
            mbar_wait_c(bars + 8 * (B_FULLW + (st & 3)), (st >> 2) & 1);
            if (st == 0) STAMP(37 + V);
            mbar_wait_c(bars + 8 * (B_FULLX + 2 * V + (st & 1)), (st >> 1) & 1);
            if (V == 0) STAMP(40 + st); else STAMP(48 + st);
            if (st == 0) STAMP(8 * V + 0);
            const uint64_t dG = mkdesc(sb + OFF_W + (st & 3) * 16384, 0, 1024, 1);
            const uint64_t dX = mkdesc(xb + (st & 1) * (N * 128), 16, 1024, 1);
            WG_FENCE();
            #pragma unroll
            for (int k = 0; k < 4; k++) {
                if ((st | k) == 0) { wg_g1_first(ag, dG, dX); wg_g1_first(au, dG + 512, dX); }
                else { wg_g1(ag, dG + k * 128, dX + k * 2, 1); wg_g1(au, dG + 512 + k * 128, dX + k * 2, 1); }
            }
            WG_COMMIT();
            if (st > 0) {
                WG_WAIT(1);
                if (lane == 0) {
                    mbar_arrive(bars + 8 * (B_EMPTYW + ((st - 1) & 3)));
                    mbar_arrive(bars + 8 * (B_EMPTYX + 2 * V + ((st - 1) & 1)));
                    if (V == 0 && st == 1) mbar_arrive(bars + 8 * B_GO);
                }
            }
        }
        WG_WAIT(0);
        fence_acc(ag); fence_acc(au);
        if (lane == 0) { mbar_arrive(bars + 8 * (B_EMPTYW + 3)); mbar_arrive(bars + 8 * (B_EMPTYX + 2 * V + 1)); }
        STAMP(8 * V + 1);
        mbar_wait_c(bars + 8 * B_STATS, 0);
        const float cg0 = ldsf(sb + OFF_CSUM + (16 * w + g) * 4), cg1 = ldsf(sb + OFF_CSUM + (16 * w + g + 8) * 4);
        const float cu0 = ldsf(sb + OFF_CSUM + (64 + 16 * w + g) * 4), cu1 = ldsf(sb + OFF_CSUM + (64 + 16 * w + g + 8) * 4);
        const int fch = 8 * fb + 2 * w;
        char* hp = (char*)g_H + fch * 1024 + lane * 4;
        const int o0 = 43 * tg + 22 * V;
        const bool rows_ok = fch < 172;
        #pragma unroll
        for (int j = 0; j < N / 8; j++) {
            const uint4 sv = lds128(sb + OFF_STATS + (176 * V + 8 * j + 2 * q) * 8);
            const float m0 = __uint_as_float(sv.x), r0 = __uint_as_float(sv.y), m1 = __uint_as_float(sv.z), r1 = __uint_as_float(sv.w);
            const float h0 = 0.5f * r0, h1 = 0.5f * r1;
            float hv[4];
            #pragma unroll
            for (int i = 0; i < 4; i++) {
                const float m = (i & 1) ? m1 : m0, r = (i & 1) ? r1 : r0, hr = (i & 1) ? h1 : h0;
                const float gh = fmaf(-m, (i & 2) ? cg1 : cg0, ag[4 * j + i]) * hr;
                const float uu = fmaf(-m, (i & 2) ? cu1 : cu0, au[4 * j + i]) * r;
                const float p = gh * uu;
                hv[i] = fmaf(p, tanh_fast(gh), p);
            }
            const int o = o0 + j;
            const int off = (o >> 3) * (172 * 1024) + (((o & 1) << 1) | (o & 4) | ((o >> 1) & 1)) * 128;
            if (rows_ok && o < 256) {
                *(uint32_t*)(hp + off) = pack2(hv[0], hv[1]);
                *(uint32_t*)(hp + off + 1024) = pack2(hv[2], hv[3]);
            }
        }
        mbar_arrive(bars + 8 * (B_EPI + V));
        STAMP(8 * V + 2);
    }
    if (c >= 128) return;
    {
        mbar_wait_c(bars + 8 * B_CONV, 0);
        uint32_t r0[8], r1[8];
        #pragma unroll
        for (int i = 0; i < 8; i++) r1[i] = 0;
        #pragma unroll 1
        for (int e = 0; e < 2; e++) {
            #pragma unroll
            for (int i = 0; i < 8; i++) r0[i] = r1[i];
            conv_channel(sb + OFF_CONV + (2 * V + e) * CH_STRIDE, w, lane, r1, (V == 0 && e == 0) ? bars + 8 * B_CH0 : 0);
            if (e == 0) STAMP(8 * V + 3);
        }
        const int gam = g >> 2, qq = gam ? ((q + 3) & 3) : q;
        uint2* sp = g_S + (2 * c + V) * 1024 + (63 - 4 * gam - qq) * 16 + 4 * w + (g & 3);
        #pragma unroll
        for (int a2 = 0; a2 < 8; a2++) sp[-a2 * 128] = make_uint2(r0[a2], r1[a2]);
        mbar_arrive(bars + 8 * (B_SIG + V));
        STAMP(8 * V + 4);
    }
    if (V == 1) return;
    {
        const int tau = c >> 2, dg = c & 3;
        float acc[64];
        #pragma unroll
        for (int i = 0; i < 64; i++) acc[i] = 0.f;
        uint2 sv[16];
        #pragma unroll
        for (int i = 0; i < 16; i++) sv[i] = make_uint2(0, 0);
        int sd = 0, sh = 0; uint32_t pd = 0, ph = 0;
        int psd = 0, psh = 0;
        #pragma unroll 1
        for (int st = 0; st < 22; st++) {
            mbar_wait_c(bars + 8 * (B_FULLD + sd), pd);
            mbar_wait_c(bars + 8 * (B_FULLH + sh), ph);
            if (st == 0) STAMP(5);
            const uint32_t da = (sd == 2) ? OFF_X0 : (sd == 4) ? OFF_X0 + 22528 : OFF_W + ((sd + 1) >> 1) * 16384;
            const uint64_t dB = mkdesc(sb + da, 8192, 1024, 1);
            const uint64_t dA = mkdesc(sb + OFF_X1 + sh * 8192, 1024, 128, 0);
            WG_FENCE();
            wg_tt128(acc, dA, dB, 1);
            wg_tt128(acc, dA + 128, dB + 128, 1);
            if (st < 21) {
                wg_tt128(acc, dA + 256, dB + 256, 1);
                wg_tt128(acc, dA + 384, dB + 384, 1);
            }
            WG_COMMIT();
            if (st > 0) {
                WG_WAIT(1);
                if (lane == 0) { mbar_arrive(bars + 8 * (B_EMPTYD + psd)); mbar_arrive(bars + 8 * (B_EMPTYH + psh)); }
            }
            psd = sd; psh = sh;
            if (++sd == 6) { sd = 0; pd ^= 1; }
            if (++sh == 5) { sh = 0; ph ^= 1; }
            if (st == 14) {
                mbar_wait_c(bars + 8 * B_S, 0);
                const uint2* sp = g_S + (dg * 64 + q) * 1024 + (2 * tau + (w >> 1)) * 16 + 8 * (w & 1) + g;
                #pragma unroll
                for (int j = 0; j < 16; j++)
                    asm volatile("ld.global.cg.v2.b32 {%0,%1}, [%2];" : "=r"(sv[j].x), "=r"(sv[j].y) : "l"(sp + j * 4096));
            }
        }
        WG_WAIT(0);
        fence_acc(acc);
        STAMP(6);
        mbar_wait_c(bars + 8 * B_XO, 0);
        const uint32_t row = 8 * (w & 1) + 32 * (w >> 1) + (lane & 7) + 16 * ((lane >> 3) & 1);
        const uint32_t xo = sb + OFF_CONV + row * 128;
        #pragma unroll
        for (int j = 0; j < 16; j += 2) {
            const uint32_t ad = xo + (j >> 3) * 8192 + ((((j & 7) + (lane >> 4)) ^ (lane & 7)) << 4);
            uint32_t xr[4];
            asm volatile("ldmatrix.sync.aligned.m8n8.x4.shared.b16 {%0,%1,%2,%3}, [%4];" : "=r"(xr[0]), "=r"(xr[1]), "=r"(xr[2]), "=r"(xr[3]) : "r"(ad));
            #pragma unroll
            for (int i = 0; i < 4; i++) {
                const int jj = j + (i >> 1), hh = i & 1;
                const float f0 = 0.5f * acc[4 * jj + 2 * hh], f1 = 0.5f * acc[4 * jj + 2 * hh + 1];
                const float G0 = fmaf(f0, tanh_fast(f0), f0), G1 = fmaf(f1, tanh_fast(f1), f1);
                const float s0 = hh ? bf_hi(sv[jj].x) : bf_lo(sv[jj].x), s1 = hh ? bf_hi(sv[jj].y) : bf_lo(sv[jj].y);
                xr[i] = pack2(fmaf(s0, G0, bf_lo(xr[i])), fmaf(s1, G1, bf_hi(xr[i])));
            }
            asm volatile("stmatrix.sync.aligned.m8n8.x4.shared.b16 [%0], {%1,%2,%3,%4};" :: "r"(ad), "r"(xr[0]), "r"(xr[1]), "r"(xr[2]), "r"(xr[3]) : "memory");
        }
        fence_async();
        bar_sync(1);
        if (w == 0 && elect_one()) {
            tma2d_store(tmOut, dg * 128, tau * 64, sb + OFF_CONV);
            tma2d_store(tmOut, dg * 128 + 64, tau * 64, sb + OFF_CONV + 8192);
            asm volatile("cp.async.bulk.commit_group;" ::: "memory");
            asm volatile("cp.async.bulk.wait_group.read 0;" ::: "memory");
        }
        STAMP(7);
    }
}

__device__ __forceinline__ float2 cexp_p(float re2, float om, float p) {
    float mag, sn, cs;
    asm("ex2.approx.ftz.f32 %0, %1;" : "=f"(mag) : "f"(re2 * p));
    const float k = fmaf(om, p, 12582912.f) - 12582912.f;
    const float th = fmaf(om, p, -k) * 6.283185307179586f;
    asm("sin.approx.ftz.f32 %0, %1;" : "=f"(sn) : "f"(th));
    asm("cos.approx.ftz.f32 %0, %1;" : "=f"(cs) : "f"(th));
    return make_float2(mag * cs, mag * sn);
}
__device__ __forceinline__ float2 cmul(float2 a, float2 b) { return make_float2(fmaf(a.x, b.x, -a.y * b.y), fmaf(a.x, b.y, a.y * b.x)); }
__device__ __forceinline__ float2 csqr(float2 a) { const float t = a.x * a.y; return make_float2(fmaf(a.x, a.x, -a.y * a.y), t + t); }
__device__ __forceinline__ void mma16816(float (&d)[4], const uint32_t (&a)[4], uint32_t b0, uint32_t b1) {
    asm volatile("mma.sync.aligned.m16n8k16.row.col.f32.bf16.bf16.f32 {%0,%1,%2,%3}, {%4,%5,%6,%7}, {%8,%9}, {%0,%1,%2,%3};"
        : "+f"(d[0]), "+f"(d[1]), "+f"(d[2]), "+f"(d[3]) : "r"(a[0]), "r"(a[1]), "r"(a[2]), "r"(a[3]), "r"(b0), "r"(b1));
}
__device__ __forceinline__ void ln_reduce(float (&s)[8], uint32_t red, int w, int lane) {
    const bool b4 = lane & 16, b3 = lane & 8, b2 = lane & 4;
    float t[4], u[2], v;
    #pragma unroll
    for (int k = 0; k < 4; k++) t[k] = (b4 ? s[4 + k] : s[k]) + __shfl_xor_sync(0xffffffffu, b4 ? s[k] : s[4 + k], 16);
    #pragma unroll
    for (int k = 0; k < 2; k++) u[k] = (b3 ? t[2 + k] : t[k]) + __shfl_xor_sync(0xffffffffu, b3 ? t[k] : t[2 + k], 8);
    v = (b2 ? u[1] : u[0]) + __shfl_xor_sync(0xffffffffu, b2 ? u[0] : u[1], 4);
    v += __shfl_xor_sync(0xffffffffu, v, 2);
    if (!(lane & 2)) stsf(red + (w * 16 + (lane & 1) * 8 + (lane >> 2)) * 4, v);
    bar_sync(2);
    #pragma unroll
    for (int k = 0; k < 8; k++) s[k] = 0.f;
    #pragma unroll
    for (int ww = 0; ww < 4; ww++) {
        const uint4 a = lds128(red + (ww * 16 + (lane & 1) * 8) * 4), b = lds128(red + (ww * 16 + (lane & 1) * 8 + 4) * 4);
        s[0] += __uint_as_float(a.x); s[1] += __uint_as_float(a.y); s[2] += __uint_as_float(a.z); s[3] += __uint_as_float(a.w);
        s[4] += __uint_as_float(b.x); s[5] += __uint_as_float(b.y); s[6] += __uint_as_float(b.z); s[7] += __uint_as_float(b.w);
    }
}

__device__ __forceinline__ void aux_role(uint32_t sb, const Params& P) {
    const int tid = threadIdx.x & 127, w = tid >> 5, lane = tid & 31, q = lane & 3, g = lane >> 2;
    const int c = blockIdx.x, fb = c % 22, tg = c / 22;
    const uint32_t bars = sb + OFF_BAR;
    const uint32_t cb = sb + OFF_CONV + w * CH_STRIDE;
    const uint32_t sF = cb + CH_A3, sP = cb + CH_A3 + 2064;
    float dsk = 0.f;
    if (c < 128) {
        const int eta = lane & 1, del = w * 16 + (lane >> 1);
        const int tok0 = 32 * (c >> 1) + 16 * eta + 8 * (c & 1);
        uint4 xr[8];
        #pragma unroll
        for (int r = 0; r < 8; r++) xr[r] = ldg128(P.x + (tok0 + r) * DM + 8 * del);
        {
            const int d = 4 * c + w;
            const uint2 la = *(const uint2*)(P.logA + d * 128 + 4 * lane), ai = *(const uint2*)(P.Aim + d * 128 + 4 * lane);
            const uint2 cr = *(const uint2*)(P.Cr + d * 128 + 4 * lane), ci = *(const uint2*)(P.Ci + d * 128 + 4 * lane);
            const float dt = bf_round(expf(__bfloat162float(P.logdt[d])));
            dsk = __bfloat162float(P.Dskip[d]);
            #pragma unroll
            for (int i = 0; i < 4; i++) {
                const uint32_t l2 = (i & 2) ? la.y : la.x, a2 = (i & 2) ? ai.y : ai.x, r2 = (i & 2) ? cr.y : cr.x, i2 = (i & 2) ? ci.y : ci.x;
                const float re = -bf_round(expf((i & 1) ? bf_hi(l2) : bf_lo(l2))) * dt;
                const float im = ((i & 1) ? bf_hi(a2) : bf_lo(a2)) * dt;
                sts128(sP + (4 * lane + i) * 16, __float_as_uint(re * 1.4426950408889634f), __float_as_uint(im * 0.15915494309189535f),
                       __float_as_uint(((i & 1) ? bf_hi(r2) : bf_lo(r2)) * dt * 2.f), __float_as_uint(((i & 1) ? bf_hi(i2) : bf_lo(i2)) * dt * 2.f));
            }
        }
        STAMP(34);
        float s[8];
        #pragma unroll
        for (int r = 0; r < 8; r++)
            s[r] = ((bf_lo(xr[r].x) + bf_hi(xr[r].x)) + (bf_lo(xr[r].y) + bf_hi(xr[r].y))) + ((bf_lo(xr[r].z) + bf_hi(xr[r].z)) + (bf_lo(xr[r].w) + bf_hi(xr[r].w)));
        ln_reduce(s, sb + OFF_RED, w, lane);
        STAMP(35);
        float mean[8];
        #pragma unroll
        for (int r = 0; r < 8; r++) {
            const float m = s[r] * (1.f / DM); mean[r] = m;
            float a = 0.f, t;
            t = bf_lo(xr[r].x) - m; a = fmaf(t, t, a); t = bf_hi(xr[r].x) - m; a = fmaf(t, t, a);
            t = bf_lo(xr[r].y) - m; a = fmaf(t, t, a); t = bf_hi(xr[r].y) - m; a = fmaf(t, t, a);
            t = bf_lo(xr[r].z) - m; a = fmaf(t, t, a); t = bf_hi(xr[r].z) - m; a = fmaf(t, t, a);
            t = bf_lo(xr[r].w) - m; a = fmaf(t, t, a); t = bf_hi(xr[r].w) - m; a = fmaf(t, t, a);
            s[r] = a;
        }
        ln_reduce(s, sb + OFF_RED + 256, w, lane);
        #pragma unroll
        for (int r = 0; r < 8; r++) {
            const float mb = bf_round(mean[r]);
            const float sd = bf_round(sqrtf(bf_round(bf_round(s[r] * (1.f / DM)) + 1e-5f)));
            const float ri = 1.f / sd;
            s[r] = ri;
            if (del == r) g_stats[tok0 + r] = make_float2(mb, ri);
            const __nv_bfloat162 m2 = __float2bfloat162_rn(mb);
            uint32_t* xp = &xr[r].x;
            #pragma unroll
            for (int k = 0; k < 4; k++) { const __nv_bfloat162 dv = __hsub2(*(__nv_bfloat162*)&xp[k], m2); xp[k] = *(const uint32_t*)&dv; }
        }
        STAMP(36);
        uint4* dst = g_xnT + (8 * del) * 256 + (c & 1) * 128 + (127 - 2 * (c >> 1) - eta);
        #pragma unroll
        for (int k = 0; k < 8; k++) {
            uint32_t o[4];
            #pragma unroll
            for (int r = 0; r < 8; r += 2) {
                const uint32_t w0 = (&xr[r].x)[k >> 1], w1 = (&xr[r + 1].x)[k >> 1];
                o[r >> 1] = pack2(((k & 1) ? bf_hi(w0) : bf_lo(w0)) * s[r], ((k & 1) ? bf_hi(w1) : bf_lo(w1)) * s[r + 1]);
            }
            dst[k * 256] = make_uint4(o[0], o[1], o[2], o[3]);
        }
    }
    STAMP(16);
    {
        const int mat = c / 66, rem = c % 66, cg = rem / 3, third = rem % 3;
        const int r0 = 171 * third, r1 = min(r0 + 171, DM), col = 64 * cg + 8 * (lane & 7);
        const __nv_bfloat16* W = (mat ? P.Wu : P.Wg) + col;
        float a[8];
        #pragma unroll
        for (int k = 0; k < 8; k++) a[k] = 0.f;
        #pragma unroll
        for (int it = 0; it < 11; it++) {
            const int row = r0 + 16 * it + 4 * w + (lane >> 3);
            uint4 v = make_uint4(0, 0, 0, 0);
            if (row < r1 && col < FF) v = ldg128(W + row * FF);
            a[0] += bf_lo(v.x); a[1] += bf_hi(v.x); a[2] += bf_lo(v.y); a[3] += bf_hi(v.y);
            a[4] += bf_lo(v.z); a[5] += bf_hi(v.z); a[6] += bf_lo(v.w); a[7] += bf_hi(v.w);
        }
        #pragma unroll
        for (int k = 0; k < 8; k++) { a[k] += __shfl_xor_sync(0xffffffffu, a[k], 8); a[k] += __shfl_xor_sync(0xffffffffu, a[k], 16); }
        const uint32_t red = sb + OFF_RED + 512;
        if (lane < 8) {
            sts128(red + (w * 64 + lane * 8) * 4, __float_as_uint(a[0]), __float_as_uint(a[1]), __float_as_uint(a[2]), __float_as_uint(a[3]));
            sts128(red + (w * 64 + lane * 8 + 4) * 4, __float_as_uint(a[4]), __float_as_uint(a[5]), __float_as_uint(a[6]), __float_as_uint(a[7]));
        }
        bar_sync(2);
        if (tid < 64) g_csum[(third * 2 + mat) * 1408 + 64 * cg + tid] = (ldsf(red + tid * 4) + ldsf(red + (64 + tid) * 4)) + (ldsf(red + (128 + tid) * 4) + ldsf(red + (192 + tid) * 4));
        mbar_arrive(bars + 8 * B_LN);
    }
    STAMP(17);
    if (c < 128) {
        float dacc[2][3][4];
        #pragma unroll
        for (int i = 0; i < 24; i++) (&dacc[0][0][0])[i] = 0.f;
        const float p0 = (float)g, p8 = (float)(8 * g);
        const float p1 = (g < 4) ? (float)(256 + 2 * g) : (float)(512 + 4 * (g & 1) + 256 * ((g >> 1) & 1));
        const float p2 = (g < 4) ? (float)(1032 + 256 * g) : 1024.f;
        #pragma unroll 1
        for (int ks = 0; ks < 16; ks++) {
            uint32_t a0[4], a1[4], b[3][2];
            #pragma unroll
            for (int mh = 0; mh < 2; mh++) {
                const uint4 pv = lds128(sP + (8 * ks + q + 4 * mh) * 16);
                const float re2 = __uint_as_float(pv.x), om = __uint_as_float(pv.y);
                const float2 C = make_float2(__uint_as_float(pv.z), __uint_as_float(pv.w));
                const float2 R0 = cexp_p(re2, om, p8);
                float2 z32; z32.x = __shfl_sync(0xffffffffu, R0.x, 16 + q); z32.y = __shfl_sync(0xffffffffu, R0.y, 16 + q);
                const float2 z64 = csqr(z32), z128 = csqr(z64);
                const float2 R1 = cmul(R0, z64), R2 = cmul(R0, z128), R3 = cmul(R1, z128);
                const float2 L0 = cmul(C, cexp_p(re2, om, p0)), L1 = cmul(C, cexp_p(re2, om, p1)), L2 = cmul(C, cexp_p(re2, om, p2));
                a0[2 * mh] = pack2(R0.x, R0.y); a0[2 * mh + 1] = pack2(R1.x, R1.y);
                a1[2 * mh] = pack2(R2.x, R2.y); a1[2 * mh + 1] = pack2(R3.x, R3.y);
                b[0][mh] = pack2(L0.x, -L0.y); b[1][mh] = pack2(L1.x, -L1.y); b[2][mh] = pack2(L2.x, -L2.y);
            }
            #pragma unroll
            for (int t = 0; t < 3; t++) { mma16816(dacc[0][t], a0, b[t][0], b[t][1]); mma16816(dacc[1][t], a1, b[t][0], b[t][1]); }
        }
        STAMP(18);
        const uint32_t sG = cb + CH_G;
        if (lane < 8) sts128(sG + (lane >> 2) * 192 + 128 + (lane & 3) * 16, 0, 0, 0, 0);
        #pragma unroll
        for (int mu = 0; mu < 2; mu++)
            #pragma unroll
            for (int hh = 0; hh < 2; hh++) {
                const int m = 16 * mu + 8 * hh + g;
                sts64(sF + (8 * m + 2 * q) * 4, __float_as_uint(dacc[mu][0][2 * hh]), __float_as_uint(dacc[mu][0][2 * hh + 1]));
                const int i1 = (q < 2) ? 256 + 4 * m + 2 * q : 384 + 2 * m + 64 * (q - 2);
                sts64(sF + i1 * 4, __float_as_uint(dacc[mu][1][2 * hh]), __float_as_uint(dacc[mu][1][2 * hh + 1]));
                if (q < 2) {
                    const uint32_t pk = pack2(dacc[mu][2][2 * hh], dacc[mu][2][2 * hh + 1]);
                    const uint32_t ga = sG + ((m & 1) ? 0 : 192) + (63 - (m >> 1) - 32 * q) * 2;
                    sts16(ga, pk & 0xffff); sts16(ga - 32, pk >> 16);
                } else if (q == 2 && m == 0) stsf(sF + 512 * 4, dacc[mu][2][2 * hh]);
            }
        __syncwarp();
        #pragma unroll 1
        for (int pass = 0; pass < 3; pass++) {
            const int row = min(pass * 32 + lane, 77), v = row - 14;
            uint32_t o[20];
            float kv[2][17];
            #pragma unroll
            for (int z = 0; z < 2; z++) {
                const int u = v - z;
                const uint32_t f0 = sF + u * 4, f1 = sF + (128 + ((u + ((u >> 1) & 1)) >> 1)) * 4, f2 = sF + (256 + ((u + 1 + ((u >> 2) & 1)) >> 2)) * 4;
                kv[z][0] = ldsf(u < 0 ? sF : f0); if (u < 0) kv[z][0] = 0.f; if (u == 0) kv[z][0] += dsk;
                #pragma unroll
                for (int s = 1; s < 4; s++) kv[z][s] = ldsf(f0 + s * 256);
                kv[z][4] = ldsf(u < 0 ? f0 + 1024 : f1 + 512);
                #pragma unroll
                for (int s = 5; s < 8; s++) kv[z][s] = ldsf(f1 + s * 128);
                kv[z][8] = ldsf(u < 0 ? f1 + 1024 : f2 + 512);
                #pragma unroll
                for (int s = 9; s < 16; s++) kv[z][s] = ldsf(f2 + s * 64);
                kv[z][16] = ldsf(u < 0 ? f2 + 1024 : sF + 2048); if (u > 4) kv[z][16] = 0.f;
            }
            #pragma unroll
            for (int s = 0; s < 17; s++) o[s] = pack2(kv[0][s], kv[1][s]);
            o[17] = o[18] = o[19] = 0;
            #pragma unroll
            for (int s4 = 0; s4 < 5; s4++) sts128(cb + CH_T + row * 80 + s4 * 16, o[4 * s4], o[4 * s4 + 1], o[4 * s4 + 2], o[4 * s4 + 3]);
        }
        __syncwarp();
        #pragma unroll
        for (int i = 0; i < 4; i++) {
            const int un = i * 32 + lane, ch = un >> 4, sig = (un >> 3) & 1, kp = un & 7;
            const uint2 x0 = lds64(sG + sig * 192 + (8 * ch + 4 * kp) * 2), x1 = lds64(sG + sig * 192 + (8 * ch + 4 * kp + 4) * 2);
            sts128(cb + CH_B3 + un * 16, x0.x, x0.y, x1.x, x1.y);
        }
        if (lane < 8) sts128(cb + CH_U + (lane >> 2) * UPLANE + 2048 + (lane & 3) * 16, 0, 0, 0, 0);
    }
    STAMP(19);
    if (tid == 0) {
        flag_wait(F_A, NCTA);
        if (c < 128) {
            fence_async();
            mbar_expect(bars + 8 * B_U, 8 * 2048);
            #pragma unroll 1
            for (int i = 0; i < 8; i++)
                bulk_load(sb + OFF_CONV + (i >> 1) * CH_STRIDE + CH_U + (i & 1) * UPLANE, g_xnT + (4 * c + (i >> 1)) * 256 + (i & 1) * 128, 2048, bars + 8 * B_U);
        } else exit_count();
    }
    bar_sync(2);
    {
        const float* cs = g_csum + (tid >> 6) * 1408 + 64 * fb + (tid & 63);
        stsf(sb + OFF_CSUM + tid * 4, __ldcg(cs) + __ldcg(cs + 2816) + __ldcg(cs + 5632));
        #pragma unroll
        for (int i = 0; i < 3; i++) {
            const int t = tid + 128 * i;
            if (t < TOKG) {
                const float2 sv = __ldcg(g_stats + min(TOKG * tg + t, SEQ - 1));
                sts64(sb + OFF_STATS + t * 8, __float_as_uint(sv.x), __float_as_uint(sv.y));
            }
        }
        mbar_arrive(bars + 8 * B_STATS);
    }
    STAMP(20);
    if (c >= 128) return;
    mbar_wait(bars + 8 * B_U, 0);
    {
        const int kap = (lane >> 4) * 8 + ((lane >> 1) & 7), gam = lane & 1, hh = w >> 1, wp = w & 1;
        const int a = 8 * kap + 4 * gam + 2 * hh + wp;
        #pragma unroll 1
        for (int ch = 0; ch < 4; ch++) {
            const uint32_t cc = sb + OFF_CONV + ch * CH_STRIDE;
            float p[24];
            uint4 r[4];
            #pragma unroll
            for (int i = 0; i < 4; i++) { const int rr = a - 3 + i; r[i] = lds128(cc + CH_U + (rr & 1) * UPLANE + (127 - (rr >> 1)) * 16); }
            p[0] = 0.f;
            p[1] = bf_lo(r[0].z); p[2] = p[1] + bf_hi(r[0].z); p[3] = p[2] + bf_lo(r[0].w); p[4] = p[3] + bf_hi(r[0].w);
            #pragma unroll
            for (int i = 0; i < 8; i++) {
                const uint32_t wv = (&r[1 + (i >> 2)].x)[i & 3];
                p[5 + 2 * i] = p[4 + 2 * i] + bf_lo(wv); p[6 + 2 * i] = p[5 + 2 * i] + bf_hi(wv);
            }
            p[21] = p[20] + bf_lo(r[3].x); p[22] = p[21] + bf_hi(r[3].x); p[23] = p[22] + bf_lo(r[3].y);
            #pragma unroll
            for (int hf = 0; hf < 2; hf++) {
                const uint32_t ad = cc + CH_A3 + (2 * (2 * wp + hf) + hh) * 512 + (kap >> 3) * 256 + (kap & 7) * 16 + gam * 8;
                const int i = 4 * hf;
                sts64(ad, pack2(p[i + 9] - p[i], p[i + 10] - p[i + 1]), pack2(p[i + 11] - p[i + 2], p[i + 12] - p[i + 3]));
                sts64(ad + 128, pack2(p[i + 16] - p[i + 9], p[i + 17] - p[i + 10]), pack2(p[i + 18] - p[i + 11], p[i + 19] - p[i + 12]));
            }
        }
    }
    fence_async();
    mbar_arrive(bars + 8 * B_CONV);
    STAMP(21);
}

__global__ void __launch_bounds__(512, 1)
fused_kernel(const __grid_constant__ CUtensorMap tmX0, const __grid_constant__ CUtensorMap tmX1, const __grid_constant__ CUtensorMap tmXO,
             const __grid_constant__ CUtensorMap tmOut, const __grid_constant__ CUtensorMap tmWg, const __grid_constant__ CUtensorMap tmWu,
             const __grid_constant__ CUtensorMap tmWd, const __grid_constant__ Params P) {
    extern __shared__ uint8_t smem_raw[];
    const uint32_t sb = (smem_u32(smem_raw) + 1023) & ~1023u;
    const uint32_t bars = sb + OFF_BAR;
    const int warp = __shfl_sync(0xffffffffu, threadIdx.x >> 5, 0);
    if (warp == 12) {
        STAMP(24);
        const int lane = threadIdx.x & 31;
        for (int i = lane; i < B_COUNT; i += 32) {
            uint32_t cnt = 1;
            if (i >= B_EMPTYW && i < B_EMPTYW + 4) cnt = 8;
            else if ((i >= B_EMPTYX && i < B_EMPTYX + 4) || (i >= B_EMPTYD && i < B_EMPTYD + 6) || (i >= B_EMPTYH && i < B_EMPTYH + 5) || i == B_GO || i == B_CH0) cnt = 4;
            else if (i == B_STATS || i == B_CONV || i == B_LN || i >= B_EPI) cnt = 128;
            mbar_init(bars + 8 * i, cnt);
        }
        asm volatile("fence.mbarrier_init.release.cluster;" ::: "memory");
        fence_async();
    }
    __syncthreads();
    const int c = blockIdx.x, fb = c % 22, tg = c / 22, tau = c >> 2, dg = c & 3;
    if (warp >= 12) {
        asm volatile("setmaxnreg.dec.sync.aligned.u32 24;");
        STAMP(27 + warp - 12);
        if (warp == 12) {
            if (elect_one()) {
                #pragma unroll 1
                for (int st = 0; st < 8; st++) {
                    const int s = st & 3;
                    if (st >= 4) mbar_wait(bars + 8 * (B_EMPTYW + s), 0);
                    mbar_expect(bars + 8 * (B_FULLW + s), 16384);
                    tma2d(sb + OFF_W + s * 16384, &tmWg, 64 * fb, 64 * st, bars + 8 * (B_FULLW + s));
                    tma2d(sb + OFF_W + s * 16384 + 8192, &tmWu, 64 * fb, 64 * st, bars + 8 * (B_FULLW + s));
                    if (st == 0) STAMP(31);
                }
                if (c < 128) {
                    int sd = 0; uint32_t pe = 1;
                    #pragma unroll 1
                    for (int st = 0; st < 22; st++) {
                        const uint32_t da = (sd == 2) ? OFF_X0 : (sd == 4) ? OFF_X0 + 22528 : OFF_W + ((sd + 1) >> 1) * 16384;
                        if (st < 6) {
                            if (sd == 2 || sd == 4) mbar_wait(bars + 8 * (B_EMPTYX + (sd >> 2)), 1);
                            else mbar_wait(bars + 8 * (B_EMPTYW + ((sd + 1) >> 1)), 1);
                        } else mbar_wait(bars + 8 * (B_EMPTYD + sd), pe);
                        mbar_expect(bars + 8 * (B_FULLD + sd), 16384);
                        tma2d(sb + da, &tmWd, 128 * dg, 64 * st, bars + 8 * (B_FULLD + sd));
                        tma2d(sb + da + 8192, &tmWd, 128 * dg + 64, 64 * st, bars + 8 * (B_FULLD + sd));
                        if (++sd == 6) { sd = 0; pe ^= 1; }
                    }
                }
            }
        } else if (warp == 13) {
            if (elect_one()) {
                #pragma unroll 1
                for (int st = 0; st < 8; st++) {
                    const int s = st & 1;
                    if (st >= 2) mbar_wait(bars + 8 * (B_EMPTYX + s), ((st >> 1) & 1) ^ 1);
                    mbar_expect(bars + 8 * (B_FULLX + s), 176 * 128);
                    tma2d(sb + OFF_X0 + s * 22528, &tmX0, 64 * st, TOKG * tg, bars + 8 * (B_FULLX + s));
                }
                if (c < 128) {
                    mbar_wait(bars + 8 * (B_EPI + 1), 0);
                    const int oa = 8 * tau, ob = 8 * tau + 7;
                    flag_wait(F_H + 2 * (oa / 43) + ((oa % 43) >= 22), 22);
                    flag_wait(F_H + 2 * (ob / 43) + ((ob % 43) >= 22), 22);
                    fence_async();
                    STAMP(25);
                    const char* hsrc = (const char*)g_H + tau * (172 * 1024);
                    int sh = 0; uint32_t pe = 1;
                    #pragma unroll 1
                    for (int st = 0; st < 22; st++) {
                        if (st >= 5) mbar_wait(bars + 8 * (B_EMPTYH + sh), pe);
                        const uint32_t nb = st < 21 ? 8192 : 4096;
                        mbar_expect(bars + 8 * (B_FULLH + sh), nb);
                        bulk_load(sb + OFF_X1 + sh * 8192, hsrc + st * 8192, nb, bars + 8 * (B_FULLH + sh));
                        if (++sh == 5) { sh = 0; pe ^= 1; }
                    }
                }
            }
        } else if (warp == 14) {
            if (elect_one()) {
                #pragma unroll 1
                for (int st = 0; st < 8; st++) {
                    const int s = st & 1;
                    if (st >= 2) mbar_wait(bars + 8 * (B_EMPTYX + 2 + s), ((st >> 1) & 1) ^ 1);
                    mbar_expect(bars + 8 * (B_FULLX + 2 + s), 168 * 128);
                    tma2d(sb + OFF_X1 + s * 21504, &tmX1, 64 * st, TOKG * tg + 176, bars + 8 * (B_FULLX + 2 + s));
                }
                if (c < 128) {
                    mbar_wait(bars + 8 * B_CH0, 0);
                    mbar_expect(bars + 8 * B_XO, 16384);
                    tma2d(sb + OFF_CONV, &tmXO, 128 * dg, 64 * tau, bars + 8 * B_XO);
                    tma2d(sb + OFF_CONV + 8192, &tmXO, 128 * dg + 64, 64 * tau, bars + 8 * B_XO);
                    flag_wait(F_S + dg, 64);
                    STAMP(26);
                    mbar_arrive(bars + 8 * B_S);
                    mbar_wait(bars + 8 * B_FULLH, 0);
                    exit_count();
                }
            }
        } else {
            if (elect_one()) {
                mbar_wait(bars + 8 * B_LN, 0);
                flag_signal(F_A);
                mbar_wait(bars + 8 * B_EPI, 0);
                flag_signal(F_H + 2 * tg);
                mbar_wait(bars + 8 * (B_EPI + 1), 0);
                flag_signal(F_H + 2 * tg + 1);
                if (c < 128) {
                    mbar_wait(bars + 8 * B_SIG, 0);
                    flag_signal(F_S + (c >> 5));
                    mbar_wait(bars + 8 * (B_SIG + 1), 0);
                    flag_signal(F_S + (c >> 5));
                }
            }
        }
    } else if (warp >= 8) {
        asm volatile("setmaxnreg.dec.sync.aligned.u32 80;");
        STAMP(32);
        aux_role(sb, P);
    } else if (warp >= 4) {
        asm volatile("setmaxnreg.inc.sync.aligned.u32 200;");
        consumer<168, 1>(sb, &tmOut);
    } else {
        asm volatile("setmaxnreg.inc.sync.aligned.u32 208;");
        STAMP(33);
        consumer<176, 0>(sb, &tmOut);
    }
}

typedef CUresult (*EncodeFn)(CUtensorMap*, CUtensorMapDataType, cuuint32_t, void*, const cuuint64_t*, const cuuint64_t*, const cuuint32_t*,
                             const cuuint32_t*, CUtensorMapInterleave, CUtensorMapSwizzle, CUtensorMapL2promotion, CUtensorMapFloatOOBfill);

CUtensorMap make_map(EncodeFn enc, const void* ptr, uint64_t inner, uint64_t outer, uint32_t box_outer) {
    CUtensorMap m;
    cuuint64_t dims[2] = {inner, outer}, strides[1] = {inner * 2};
    cuuint32_t box[2] = {64, box_outer}, es[2] = {1, 1};
    enc(&m, CU_TENSOR_MAP_DATA_TYPE_BFLOAT16, 2, (void*)ptr, dims, strides, box, es, CU_TENSOR_MAP_INTERLEAVE_NONE,
        CU_TENSOR_MAP_SWIZZLE_128B, CU_TENSOR_MAP_L2_PROMOTION_L2_128B, CU_TENSOR_MAP_FLOAT_OOB_FILL_NONE);
    return m;
}

}

extern "C" void kernel_launch(void* const* d_in, const int* in_sizes, int n_in, void* d_out, int out_size) {
    (void)in_sizes; (void)n_in; (void)out_size;
    static EncodeFn enc = nullptr;
    if (!enc) {
        cudaDriverEntryPointQueryResult qr;
        cudaGetDriverEntryPoint("cuTensorMapEncodeTiled", (void**)&enc, cudaEnableDefault, &qr);
        cudaFuncSetAttribute(fused_kernel, cudaFuncAttributeMaxDynamicSharedMemorySize, SMEM_BYTES);
    }
    const __nv_bfloat16* x = (const __nv_bfloat16*)d_in[0];
    Params P;
    P.x = x; P.logA = (const __nv_bfloat16*)d_in[1]; P.Aim = (const __nv_bfloat16*)d_in[2]; P.Cr = (const __nv_bfloat16*)d_in[3];
    P.Ci = (const __nv_bfloat16*)d_in[4]; P.logdt = (const __nv_bfloat16*)d_in[5]; P.Dskip = (const __nv_bfloat16*)d_in[6];
    P.Wg = (const __nv_bfloat16*)d_in[8]; P.Wu = (const __nv_bfloat16*)d_in[9];
    const CUtensorMap tmX0 = make_map(enc, x, DM, SEQ, 176), tmX1 = make_map(enc, x, DM, SEQ, 168), tmXO = make_map(enc, x, DM, SEQ, 64);
    const CUtensorMap tmOut = make_map(enc, d_out, DM, SEQ, 64);
    const CUtensorMap tmWg = make_map(enc, d_in[8], FF, DM, 64), tmWu = make_map(enc, d_in[9], FF, DM, 64), tmWd = make_map(enc, d_in[10], DM, FF, 64);
    fused_kernel<<<NCTA, 512, SMEM_BYTES>>>(tmX0, tmX1, tmXO, tmOut, tmWg, tmWu, tmWd, P);
}
```

```cpp
#include <cuda_runtime.h>
#include <cuda_bf16.h>
#include <cuda.h>
#include <stdint.h>

#define PROF 0

namespace {

constexpr int SEQ = 2048, DM = 512, FF = 1376;
constexpr int NCTA = 132;
constexpr int TOKG = 344;

constexpr uint32_t OFF_W = 0;
constexpr uint32_t XBUF = 22528;
constexpr uint32_t OFF_X = 65536;
constexpr uint32_t OFF_CONV = 155648;
constexpr uint32_t CH_STRIDE = 16640;
constexpr uint32_t CH_T = 0;
constexpr uint32_t CH_A3 = 6272;
constexpr uint32_t CH_B3 = 10368;
constexpr uint32_t CH_U = 12416;
constexpr uint32_t CH_G = CH_A3 + 2064;
constexpr uint32_t UPLANE = 2112;
constexpr uint32_t LNROW = 1040;
constexpr uint32_t OFF_MB = 222208;
constexpr uint32_t OFF_HR = 227712;
constexpr uint32_t OFF_CSUM = 229120;
constexpr uint32_t OFF_BAR = 231168;
constexpr uint32_t SMEM_BYTES = 231680;

enum {
    B_FULLW = 0, B_EMPTYW = 4, B_FULLX = 8, B_EMPTYX = 12, B_FULLD = 16, B_EMPTYD = 22, B_FULLH = 28, B_EMPTYH = 33,
    B_U = 38, B_XO = 39, B_S = 40, B_LNX = 41, B_STG = 42,
    B_GO = 44, B_CH0 = 45,
    B_STATS = 46, B_CONV = 47, B_LN = 48, B_CS = 49, B_EPI = 50, B_SIG = 52,
    B_COUNT = 54
};
enum { F_A = 0, F_H = 1, F_S = 13, F_EXIT = 17, F_COUNT = 18 };

__device__ uint4 g_xnT[DM * 256];
__device__ float2 g_stats[SEQ];
__device__ uint4 g_H[172 * 256 * 8];
__device__ uint2 g_S[256 * 1024];
__device__ unsigned g_flags[F_COUNT * 32];
#define STAMP(i) do {} while (0)

__device__ __forceinline__ uint32_t smem_u32(const void* p) { return (uint32_t)__cvta_generic_to_shared(p); }
__device__ __forceinline__ void mbar_expect(uint32_t bar, uint32_t bytes) { asm volatile("mbarrier.arrive.expect_tx.shared::cta.b64 _, [%0], %1;" :: "r"(bar), "r"(bytes) : "memory"); }
__device__ __forceinline__ void mbar_arrive(uint32_t bar) { asm volatile("mbarrier.arrive.shared::cta.b64 _, [%0];" :: "r"(bar) : "memory"); }
__device__ __forceinline__ void mbar_wait(uint32_t bar, uint32_t parity) {
    asm volatile("{.reg .pred p; .reg .u32 n; mov.u32 n, 0x200000;\n"
                 "LW: mbarrier.try_wait.parity.shared::cta.b64 p, [%0], %1;\n"
                 "sub.u32 n, n, 1; setp.eq.or.u32 p, n, 0, p; @!p bra LW;}" :: "r"(bar), "r"(parity) : "memory");
}
__device__ __forceinline__ bool elect_one() { uint32_t p; asm volatile("{.reg .pred P; elect.sync _|P, 0xffffffff; selp.u32 %0, 1, 0, P;}" : "=r"(p)); return p; }
__device__ __forceinline__ void tma2d(uint32_t dst, const CUtensorMap* m, int c0, int c1, uint32_t bar) {
    asm volatile("cp.async.bulk.tensor.2d.shared::cluster.global.mbarrier::complete_tx::bytes [%0], [%1, {%3, %4}], [%2];"
        :: "r"(dst), "l"(m), "r"(bar), "r"(c0), "r"(c1) : "memory");
}
__device__ __forceinline__ void bulk_load(uint32_t dst, const void* src, uint32_t bytes, uint32_t bar) {
    asm volatile("cp.async.bulk.shared::cluster.global.mbarrier::complete_tx::bytes [%0], [%1], %2, [%3];" :: "r"(dst), "l"(src), "r"(bytes), "r"(bar) : "memory");
}
__device__ __forceinline__ void fence_async() { asm volatile("fence.proxy.async;" ::: "memory"); }
__device__ __forceinline__ void fence_async_smem() { asm volatile("fence.proxy.async.shared::cta;" ::: "memory"); }
__device__ __forceinline__ void flag_wait(int f, unsigned target) {
    asm volatile("{.reg .pred p; .reg .u32 n, v; mov.u32 n, 0x400000;\n"
                 "LF: ld.acquire.gpu.global.u32 v, [%0]; setp.ge.u32 p, v, %1; @p bra LD;\n"
                 "nanosleep.u32 20; sub.u32 n, n, 1; setp.ne.u32 p, n, 0; @p bra LF; trap;\nLD: }"
                 :: "l"(g_flags + f * 32), "r"(target) : "memory");
}
__device__ __forceinline__ void flag_signal(int f) {
    asm volatile("fence.acq_rel.gpu; red.relaxed.gpu.global.add.u32 [%0], 1;" :: "l"(g_flags + f * 32) : "memory");
}
__device__ __forceinline__ void exit_count() {
    if (atomicAdd(g_flags + F_EXIT * 32, 1u) == NCTA - 1) {
        #pragma unroll 1
        for (int i = 0; i < F_COUNT; i++) g_flags[i * 32] = 0;
    }
}
__device__ __forceinline__ void bar_sync(int id) { asm volatile("bar.sync %0, 128;" :: "r"(id) : "memory"); }
__device__ __forceinline__ uint64_t mkdesc(uint32_t addr, uint32_t lbo, uint32_t sbo, uint32_t swz) {
    return (uint64_t)((addr >> 4) | ((lbo >> 4) << 16)) | ((uint64_t)((sbo >> 4) | (swz << 30)) << 32);
}
#define WG_FENCE() asm volatile("wgmma.fence.sync.aligned;" ::: "memory")
#define WG_COMMIT() asm volatile("wgmma.commit_group.sync.aligned;" ::: "memory")
#define WG_WAIT(n) asm volatile("wgmma.wait_group.sync.aligned " #n ";" ::: "memory")
template <int N> __device__ __forceinline__ void fence_acc(float (&d)[N]) {
    #pragma unroll
    for (int i = 0; i < N; i++) asm volatile("" : "+f"(d[i]) :: "memory");
}
template <int N> __device__ __forceinline__ void define_acc(float (&d)[N]) {
    #pragma unroll
    for (int i = 0; i < N; i++) asm volatile("" : "=f"(d[i]));
}
__device__ __forceinline__ uint32_t pack2(float lo, float hi) { uint32_t r; asm("cvt.rn.bf16x2.f32 %0, %1, %2;" : "=r"(r) : "f"(hi), "f"(lo)); return r; }
__device__ __forceinline__ float bf_lo(uint32_t v) { return __uint_as_float(v << 16); }
__device__ __forceinline__ float bf_hi(uint32_t v) { return __uint_as_float(v & 0xffff0000u); }
__device__ __forceinline__ float bf_round(float v) { return bf_hi(pack2(0.f, v)); }
__device__ __forceinline__ float tanh_fast(float v) { float r; asm("tanh.approx.f32 %0, %1;" : "=f"(r) : "f"(v)); return r; }
__device__ __forceinline__ float ex2(float v) { float r; asm("ex2.approx.ftz.f32 %0, %1;" : "=f"(r) : "f"(v)); return r; }
__device__ __forceinline__ uint4 lds128(uint32_t a) { uint4 v; asm volatile("ld.shared.v4.b32 {%0,%1,%2,%3}, [%4];" : "=r"(v.x), "=r"(v.y), "=r"(v.z), "=r"(v.w) : "r"(a)); return v; }
__device__ __forceinline__ uint2 lds64(uint32_t a) { uint2 v; asm volatile("ld.shared.v2.b32 {%0,%1}, [%2];" : "=r"(v.x), "=r"(v.y) : "r"(a)); return v; }
__device__ __forceinline__ float ldsf(uint32_t a) { float v; asm volatile("ld.shared.f32 %0, [%1];" : "=f"(v) : "r"(a)); return v; }
__device__ __forceinline__ void sts128(uint32_t a, uint32_t x, uint32_t y, uint32_t z, uint32_t w) { asm volatile("st.shared.v4.b32 [%0], {%1,%2,%3,%4};" :: "r"(a), "r"(x), "r"(y), "r"(z), "r"(w) : "memory"); }
__device__ __forceinline__ void sts64(uint32_t a, uint32_t x, uint32_t y) { asm volatile("st.shared.v2.b32 [%0], {%1,%2};" :: "r"(a), "r"(x), "r"(y) : "memory"); }
__device__ __forceinline__ void stsf(uint32_t a, float x) { asm volatile("st.shared.f32 [%0], %1;" :: "r"(a), "f"(x) : "memory"); }
__device__ __forceinline__ void sts16(uint32_t a, uint32_t x) { asm volatile("st.shared.b16 [%0], %1;" :: "r"(a), "h"((unsigned short)x) : "memory"); }
__device__ __forceinline__ void stsm4(uint32_t a, uint32_t r0, uint32_t r1, uint32_t r2, uint32_t r3) {
    asm volatile("stmatrix.sync.aligned.m8n8.x4.shared.b16 [%0], {%1,%2,%3,%4};" :: "r"(a), "r"(r0), "r"(r1), "r"(r2), "r"(r3) : "memory");
}
#define FU(x) __float_as_uint(x)
#define UF(x) __uint_as_float(x)
__device__ __forceinline__ uint32_t wd_slot(int s) { return (uint32_t)((0x403056201000ull >> (8 * s)) & 0xff) << 10; }

template<int N> __device__ __forceinline__ void wg_rs(float (&d)[64], uint32_t a0, uint32_t a1, uint32_t a2, uint32_t a3, uint64_t db);
template<> __device__ __forceinline__ void wg_rs<128>(float (&d)[64], uint32_t a0, uint32_t a1, uint32_t a2, uint32_t a3, uint64_t db) {
  asm volatile("{.reg .pred p; setp.ne.b32 p, 1, 0; wgmma.mma_async.sync.aligned.m64n128k16.f32.bf16.bf16 {%0,%1,%2,%3,%4,%5,%6,%7,%8,%9,%10,%11,%12,%13,%14,%15,%16,%17,%18,%19,%20,%21,%22,%23,%24,%25,%26,%27,%28,%29,%30,%31,%32,%33,%34,%35,%36,%37,%38,%39,%40,%41,%42,%43,%44,%45,%46,%47,%48,%49,%50,%51,%52,%53,%54,%55,%56,%57,%58,%59,%60,%61,%62,%63}, {%64,%65,%66,%67}, %68, p, 1, 1, 0;}"
    : "+f"(d[0]),"+f"(d[1]),"+f"(d[2]),"+f"(d[3]),"+f"(d[4]),"+f"(d[5]),"+f"(d[6]),"+f"(d[7]),"+f"(d[8]),"+f"(d[9]),"+f"(d[10]),"+f"(d[11]),"+f"(d[12]),"+f"(d[13]),"+f"(d[14]),"+f"(d[15]),"+f"(d[16]),"+f"(d[17]),"+f"(d[18]),"+f"(d[19]),"+f"(d[20]),"+f"(d[21]),"+f"(d[22]),"+f"(d[23]),"+f"(d[24]),"+f"(d[25]),"+f"(d[26]),"+f"(d[27]),"+f"(d[28]),"+f"(d[29]),"+f"(d[30]),"+f"(d[31]),"+f"(d[32]),"+f"(d[33]),"+f"(d[34]),"+f"(d[35]),"+f"(d[36]),"+f"(d[37]),"+f"(d[38]),"+f"(d[39]),"+f"(d[40]),"+f"(d[41]),"+f"(d[42]),"+f"(d[43]),"+f"(d[44]),"+f"(d[45]),"+f"(d[46]),"+f"(d[47]),"+f"(d[48]),"+f"(d[49]),"+f"(d[50]),"+f"(d[51]),"+f"(d[52]),"+f"(d[53]),"+f"(d[54]),"+f"(d[55]),"+f"(d[56]),"+f"(d[57]),"+f"(d[58]),"+f"(d[59]),"+f"(d[60]),"+f"(d[61]),"+f"(d[62]),"+f"(d[63]) : "r"(a0), "r"(a1), "r"(a2), "r"(a3), "l"(db));
}
template<> __device__ __forceinline__ void wg_rs<120>(float (&d)[64], uint32_t a0, uint32_t a1, uint32_t a2, uint32_t a3, uint64_t db) {
  asm volatile("{.reg .pred p; setp.ne.b32 p, 1, 0; wgmma.mma_async.sync.aligned.m64n120k16.f32.bf16.bf16 {%0,%1,%2,%3,%4,%5,%6,%7,%8,%9,%10,%11,%12,%13,%14,%15,%16,%17,%18,%19,%20,%21,%22,%23,%24,%25,%26,%27,%28,%29,%30,%31,%32,%33,%34,%35,%36,%37,%38,%39,%40,%41,%42,%43,%44,%45,%46,%47,%48,%49,%50,%51,%52,%53,%54,%55,%56,%57,%58,%59}, {%60,%61,%62,%63}, %64, p, 1, 1, 0;}"
    : "+f"(d[0]),"+f"(d[1]),"+f"(d[2]),"+f"(d[3]),"+f"(d[4]),"+f"(d[5]),"+f"(d[6]),"+f"(d[7]),"+f"(d[8]),"+f"(d[9]),"+f"(d[10]),"+f"(d[11]),"+f"(d[12]),"+f"(d[13]),"+f"(d[14]),"+f"(d[15]),"+f"(d[16]),"+f"(d[17]),"+f"(d[18]),"+f"(d[19]),"+f"(d[20]),"+f"(d[21]),"+f"(d[22]),"+f"(d[23]),"+f"(d[24]),"+f"(d[25]),"+f"(d[26]),"+f"(d[27]),"+f"(d[28]),"+f"(d[29]),"+f"(d[30]),"+f"(d[31]),"+f"(d[32]),"+f"(d[33]),"+f"(d[34]),"+f"(d[35]),"+f"(d[36]),"+f"(d[37]),"+f"(d[38]),"+f"(d[39]),"+f"(d[40]),"+f"(d[41]),"+f"(d[42]),"+f"(d[43]),"+f"(d[44]),"+f"(d[45]),"+f"(d[46]),"+f"(d[47]),"+f"(d[48]),"+f"(d[49]),"+f"(d[50]),"+f"(d[51]),"+f"(d[52]),"+f"(d[53]),"+f"(d[54]),"+f"(d[55]),"+f"(d[56]),"+f"(d[57]),"+f"(d[58]),"+f"(d[59]) : "r"(a0), "r"(a1), "r"(a2), "r"(a3), "l"(db));
}
template<> __device__ __forceinline__ void wg_rs<112>(float (&d)[64], uint32_t a0, uint32_t a1, uint32_t a2, uint32_t a3, uint64_t db) {
  asm volatile("{.reg .pred p; setp.ne.b32 p, 1, 0; wgmma.mma_async.sync.aligned.m64n112k16.f32.bf16.bf16 {%0,%1,%2,%3,%4,%5,%6,%7,%8,%9,%10,%11,%12,%13,%14,%15,%16,%17,%18,%19,%20,%21,%22,%23,%24,%25,%26,%27,%28,%29,%30,%31,%32,%33,%34,%35,%36,%37,%38,%39,%40,%41,%42,%43,%44,%45,%46,%47,%48,%49,%50,%51,%52,%53,%54,%55}, {%56,%57,%58,%59}, %60, p, 1, 1, 0;}"
    : "+f"(d[0]),"+f"(d[1]),"+f"(d[2]),"+f"(d[3]),"+f"(d[4]),"+f"(d[5]),"+f"(d[6]),"+f"(d[7]),"+f"(d[8]),"+f"(d[9]),"+f"(d[10]),"+f"(d[11]),"+f"(d[12]),"+f"(d[13]),"+f"(d[14]),"+f"(d[15]),"+f"(d[16]),"+f"(d[17]),"+f"(d[18]),"+f"(d[19]),"+f"(d[20]),"+f"(d[21]),"+f"(d[22]),"+f"(d[23]),"+f"(d[24]),"+f"(d[25]),"+f"(d[26]),"+f"(d[27]),"+f"(d[28]),"+f"(d[29]),"+f"(d[30]),"+f"(d[31]),"+f"(d[32]),"+f"(d[33]),"+f"(d[34]),"+f"(d[35]),"+f"(d[36]),"+f"(d[37]),"+f"(d[38]),"+f"(d[39]),"+f"(d[40]),"+f"(d[41]),"+f"(d[42]),"+f"(d[43]),"+f"(d[44]),"+f"(d[45]),"+f"(d[46]),"+f"(d[47]),"+f"(d[48]),"+f"(d[49]),"+f"(d[50]),"+f"(d[51]),"+f"(d[52]),"+f"(d[53]),"+f"(d[54]),"+f"(d[55]) : "r"(a0), "r"(a1), "r"(a2), "r"(a3), "l"(db));
}
template<> __device__ __forceinline__ void wg_rs<104>(float (&d)[64], uint32_t a0, uint32_t a1, uint32_t a2, uint32_t a3, uint64_t db) {
  asm volatile("{.reg .pred p; setp.ne.b32 p, 1, 0; wgmma.mma_async.sync.aligned.m64n104k16.f32.bf16.bf16 {%0,%1,%2,%3,%4,%5,%6,%7,%8,%9,%10,%11,%12,%13,%14,%15,%16,%17,%18,%19,%20,%21,%22,%23,%24,%25,%26,%27,%28,%29,%30,%31,%32,%33,%34,%35,%36,%37,%38,%39,%40,%41,%42,%43,%44,%45,%46,%47,%48,%49,%50,%51}, {%52,%53,%54,%55}, %56, p, 1, 1, 0;}"
    : "+f"(d[0]),"+f"(d[1]),"+f"(d[2]),"+f"(d[3]),"+f"(d[4]),"+f"(d[5]),"+f"(d[6]),"+f"(d[7]),"+f"(d[8]),"+f"(d[9]),"+f"(d[10]),"+f"(d[11]),"+f"(d[12]),"+f"(d[13]),"+f"(d[14]),"+f"(d[15]),"+f"(d[16]),"+f"(d[17]),"+f"(d[18]),"+f"(d[19]),"+f"(d[20]),"+f"(d[21]),"+f"(d[22]),"+f"(d[23]),"+f"(d[24]),"+f"(d[25]),"+f"(d[26]),"+f"(d[27]),"+f"(d[28]),"+f"(d[29]),"+f"(d[30]),"+f"(d[31]),"+f"(d[32]),"+f"(d[33]),"+f"(d[34]),"+f"(d[35]),"+f"(d[36]),"+f"(d[37]),"+f"(d[38]),"+f"(d[39]),"+f"(d[40]),"+f"(d[41]),"+f"(d[42]),"+f"(d[43]),"+f"(d[44]),"+f"(d[45]),"+f"(d[46]),"+f"(d[47]),"+f"(d[48]),"+f"(d[49]),"+f"(d[50]),"+f"(d[51]) : "r"(a0), "r"(a1), "r"(a2), "r"(a3), "l"(db));
}
template<> __device__ __forceinline__ void wg_rs<96>(float (&d)[64], uint32_t a0, uint32_t a1, uint32_t a2, uint32_t a3, uint64_t db) {
  asm volatile("{.reg .pred p; setp.ne.b32 p, 1, 0; wgmma.mma_async.sync.aligned.m64n96k16.f32.bf16.bf16 {%0,%1,%2,%3,%4,%5,%6,%7,%8,%9,%10,%11,%12,%13,%14,%15,%16,%17,%18,%19,%20,%21,%22,%23,%24,%25,%26,%27,%28,%29,%30,%31,%32,%33,%34,%35,%36,%37,%38,%39,%40,%41,%42,%43,%44,%45,%46,%47}, {%48,%49,%50,%51}, %52, p, 1, 1, 0;}"
    : "+f"(d[0]),"+f"(d[1]),"+f"(d[2]),"+f"(d[3]),"+f"(d[4]),"+f"(d[5]),"+f"(d[6]),"+f"(d[7]),"+f"(d[8]),"+f"(d[9]),"+f"(d[10]),"+f"(d[11]),"+f"(d[12]),"+f"(d[13]),"+f"(d[14]),"+f"(d[15]),"+f"(d[16]),"+f"(d[17]),"+f"(d[18]),"+f"(d[19]),"+f"(d[20]),"+f"(d[21]),"+f"(d[22]),"+f"(d[23]),"+f"(d[24]),"+f"(d[25]),"+f"(d[26]),"+f"(d[27]),"+f"(d[28]),"+f"(d[29]),"+f"(d[30]),"+f"(d[31]),"+f"(d[32]),"+f"(d[33]),"+f"(d[34]),"+f"(d[35]),"+f"(d[36]),"+f"(d[37]),"+f"(d[38]),"+f"(d[39]),"+f"(d[40]),"+f"(d[41]),"+f"(d[42]),"+f"(d[43]),"+f"(d[44]),"+f"(d[45]),"+f"(d[46]),"+f"(d[47]) : "r"(a0), "r"(a1), "r"(a2), "r"(a3), "l"(db));
}
template<> __device__ __forceinline__ void wg_rs<88>(float (&d)[64], uint32_t a0, uint32_t a1, uint32_t a2, uint32_t a3, uint64_t db) {
  asm volatile("{.reg .pred p; setp.ne.b32 p, 1, 0; wgmma.mma_async.sync.aligned.m64n88k16.f32.bf16.bf16 {%0,%1,%2,%3,%4,%5,%6,%7,%8,%9,%10,%11,%12,%13,%14,%15,%16,%17,%18,%19,%20,%21,%22,%23,%24,%25,%26,%27,%28,%29,%30,%31,%32,%33,%34,%35,%36,%37,%38,%39,%40,%41,%42,%43}, {%44,%45,%46,%47}, %48, p, 1, 1, 0;}"
    : "+f"(d[0]),"+f"(d[1]),"+f"(d[2]),"+f"(d[3]),"+f"(d[4]),"+f"(d[5]),"+f"(d[6]),"+f"(d[7]),"+f"(d[8]),"+f"(d[9]),"+f"(d[10]),"+f"(d[11]),"+f"(d[12]),"+f"(d[13]),"+f"(d[14]),"+f"(d[15]),"+f"(d[16]),"+f"(d[17]),"+f"(d[18]),"+f"(d[19]),"+f"(d[20]),"+f"(d[21]),"+f"(d[22]),"+f"(d[23]),"+f"(d[24]),"+f"(d[25]),"+f"(d[26]),"+f"(d[27]),"+f"(d[28]),"+f"(d[29]),"+f"(d[30]),"+f"(d[31]),"+f"(d[32]),"+f"(d[33]),"+f"(d[34]),"+f"(d[35]),"+f"(d[36]),"+f"(d[37]),"+f"(d[38]),"+f"(d[39]),"+f"(d[40]),"+f"(d[41]),"+f"(d[42]),"+f"(d[43]) : "r"(a0), "r"(a1), "r"(a2), "r"(a3), "l"(db));
}
template<> __device__ __forceinline__ void wg_rs<80>(float (&d)[64], uint32_t a0, uint32_t a1, uint32_t a2, uint32_t a3, uint64_t db) {
  asm volatile("{.reg .pred p; setp.ne.b32 p, 1, 0; wgmma.mma_async.sync.aligned.m64n80k16.f32.bf16.bf16 {%0,%1,%2,%3,%4,%5,%6,%7,%8,%9,%10,%11,%12,%13,%14,%15,%16,%17,%18,%19,%20,%21,%22,%23,%24,%25,%26,%27,%28,%29,%30,%31,%32,%33,%34,%35,%36,%37,%38,%39}, {%40,%41,%42,%43}, %44, p, 1, 1, 0;}"
    : "+f"(d[0]),"+f"(d[1]),"+f"(d[2]),"+f"(d[3]),"+f"(d[4]),"+f"(d[5]),"+f"(d[6]),"+f"(d[7]),"+f"(d[8]),"+f"(d[9]),"+f"(d[10]),"+f"(d[11]),"+f"(d[12]),"+f"(d[13]),"+f"(d[14]),"+f"(d[15]),"+f"(d[16]),"+f"(d[17]),"+f"(d[18]),"+f"(d[19]),"+f"(d[20]),"+f"(d[21]),"+f"(d[22]),"+f"(d[23]),"+f"(d[24]),"+f"(d[25]),"+f"(d[26]),"+f"(d[27]),"+f"(d[28]),"+f"(d[29]),"+f"(d[30]),"+f"(d[31]),"+f"(d[32]),"+f"(d[33]),"+f"(d[34]),"+f"(d[35]),"+f"(d[36]),"+f"(d[37]),"+f"(d[38]),"+f"(d[39]) : "r"(a0), "r"(a1), "r"(a2), "r"(a3), "l"(db));
}
template<> __device__ __forceinline__ void wg_rs<72>(float (&d)[64], uint32_t a0, uint32_t a1, uint32_t a2, uint32_t a3, uint64_t db) {
  asm volatile("{.reg .pred p; setp.ne.b32 p, 1, 0; wgmma.mma_async.sync.aligned.m64n72k16.f32.bf16.bf16 {%0,%1,%2,%3,%4,%5,%6,%7,%8,%9,%10,%11,%12,%13,%14,%15,%16,%17,%18,%19,%20,%21,%22,%23,%24,%25,%26,%27,%28,%29,%30,%31,%32,%33,%34,%35}, {%36,%37,%38,%39}, %40, p, 1, 1, 0;}"
    : "+f"(d[0]),"+f"(d[1]),"+f"(d[2]),"+f"(d[3]),"+f"(d[4]),"+f"(d[5]),"+f"(d[6]),"+f"(d[7]),"+f"(d[8]),"+f"(d[9]),"+f"(d[10]),"+f"(d[11]),"+f"(d[12]),"+f"(d[13]),"+f"(d[14]),"+f"(d[15]),"+f"(d[16]),"+f"(d[17]),"+f"(d[18]),"+f"(d[19]),"+f"(d[20]),"+f"(d[21]),"+f"(d[22]),"+f"(d[23]),"+f"(d[24]),"+f"(d[25]),"+f"(d[26]),"+f"(d[27]),"+f"(d[28]),"+f"(d[29]),"+f"(d[30]),"+f"(d[31]),"+f"(d[32]),"+f"(d[33]),"+f"(d[34]),"+f"(d[35]) : "r"(a0), "r"(a1), "r"(a2), "r"(a3), "l"(db));
}
template<> __device__ __forceinline__ void wg_rs<64>(float (&d)[64], uint32_t a0, uint32_t a1, uint32_t a2, uint32_t a3, uint64_t db) {
  asm volatile("{.reg .pred p; setp.ne.b32 p, 1, 0; wgmma.mma_async.sync.aligned.m64n64k16.f32.bf16.bf16 {%0,%1,%2,%3,%4,%5,%6,%7,%8,%9,%10,%11,%12,%13,%14,%15,%16,%17,%18,%19,%20,%21,%22,%23,%24,%25,%26,%27,%28,%29,%30,%31}, {%32,%33,%34,%35}, %36, p, 1, 1, 0;}"
    : "+f"(d[0]),"+f"(d[1]),"+f"(d[2]),"+f"(d[3]),"+f"(d[4]),"+f"(d[5]),"+f"(d[6]),"+f"(d[7]),"+f"(d[8]),"+f"(d[9]),"+f"(d[10]),"+f"(d[11]),"+f"(d[12]),"+f"(d[13]),"+f"(d[14]),"+f"(d[15]),"+f"(d[16]),"+f"(d[17]),"+f"(d[18]),"+f"(d[19]),"+f"(d[20]),"+f"(d[21]),"+f"(d[22]),"+f"(d[23]),"+f"(d[24]),"+f"(d[25]),"+f"(d[26]),"+f"(d[27]),"+f"(d[28]),"+f"(d[29]),"+f"(d[30]),"+f"(d[31]) : "r"(a0), "r"(a1), "r"(a2), "r"(a3), "l"(db));
}
__device__ __forceinline__ void wg_rs_first(float (&d)[64], uint32_t a0, uint32_t a1, uint32_t a2, uint32_t a3, uint64_t db) {
  asm volatile("{.reg .pred p; setp.ne.b32 p, 0, 0; wgmma.mma_async.sync.aligned.m64n128k16.f32.bf16.bf16 {%0,%1,%2,%3,%4,%5,%6,%7,%8,%9,%10,%11,%12,%13,%14,%15,%16,%17,%18,%19,%20,%21,%22,%23,%24,%25,%26,%27,%28,%29,%30,%31,%32,%33,%34,%35,%36,%37,%38,%39,%40,%41,%42,%43,%44,%45,%46,%47,%48,%49,%50,%51,%52,%53,%54,%55,%56,%57,%58,%59,%60,%61,%62,%63}, {%64,%65,%66,%67}, %68, p, 1, 1, 0;}"
    : "=f"(d[0]),"=f"(d[1]),"=f"(d[2]),"=f"(d[3]),"=f"(d[4]),"=f"(d[5]),"=f"(d[6]),"=f"(d[7]),"=f"(d[8]),"=f"(d[9]),"=f"(d[10]),"=f"(d[11]),"=f"(d[12]),"=f"(d[13]),"=f"(d[14]),"=f"(d[15]),"=f"(d[16]),"=f"(d[17]),"=f"(d[18]),"=f"(d[19]),"=f"(d[20]),"=f"(d[21]),"=f"(d[22]),"=f"(d[23]),"=f"(d[24]),"=f"(d[25]),"=f"(d[26]),"=f"(d[27]),"=f"(d[28]),"=f"(d[29]),"=f"(d[30]),"=f"(d[31]),"=f"(d[32]),"=f"(d[33]),"=f"(d[34]),"=f"(d[35]),"=f"(d[36]),"=f"(d[37]),"=f"(d[38]),"=f"(d[39]),"=f"(d[40]),"=f"(d[41]),"=f"(d[42]),"=f"(d[43]),"=f"(d[44]),"=f"(d[45]),"=f"(d[46]),"=f"(d[47]),"=f"(d[48]),"=f"(d[49]),"=f"(d[50]),"=f"(d[51]),"=f"(d[52]),"=f"(d[53]),"=f"(d[54]),"=f"(d[55]),"=f"(d[56]),"=f"(d[57]),"=f"(d[58]),"=f"(d[59]),"=f"(d[60]),"=f"(d[61]),"=f"(d[62]),"=f"(d[63]) : "r"(a0), "r"(a1), "r"(a2), "r"(a3), "l"(db));
}
__device__ __forceinline__ void wg_kk176(float (&d)[88], uint64_t da, uint64_t db, int sc) {
  asm volatile("{.reg .pred p; setp.ne.b32 p, %90, 0; wgmma.mma_async.sync.aligned.m64n176k16.f32.bf16.bf16 {%0,%1,%2,%3,%4,%5,%6,%7,%8,%9,%10,%11,%12,%13,%14,%15,%16,%17,%18,%19,%20,%21,%22,%23,%24,%25,%26,%27,%28,%29,%30,%31,%32,%33,%34,%35,%36,%37,%38,%39,%40,%41,%42,%43,%44,%45,%46,%47,%48,%49,%50,%51,%52,%53,%54,%55,%56,%57,%58,%59,%60,%61,%62,%63,%64,%65,%66,%67,%68,%69,%70,%71,%72,%73,%74,%75,%76,%77,%78,%79,%80,%81,%82,%83,%84,%85,%86,%87}, %88, %89, p, 1, 1, 0, 0;}"
    : "+f"(d[0]),"+f"(d[1]),"+f"(d[2]),"+f"(d[3]),"+f"(d[4]),"+f"(d[5]),"+f"(d[6]),"+f"(d[7]),"+f"(d[8]),"+f"(d[9]),"+f"(d[10]),"+f"(d[11]),"+f"(d[12]),"+f"(d[13]),"+f"(d[14]),"+f"(d[15]),"+f"(d[16]),"+f"(d[17]),"+f"(d[18]),"+f"(d[19]),"+f"(d[20]),"+f"(d[21]),"+f"(d[22]),"+f"(d[23]),"+f"(d[24]),"+f"(d[25]),"+f"(d[26]),"+f"(d[27]),"+f"(d[28]),"+f"(d[29]),"+f"(d[30]),"+f"(d[31]),"+f"(d[32]),"+f"(d[33]),"+f"(d[34]),"+f"(d[35]),"+f"(d[36]),"+f"(d[37]),"+f"(d[38]),"+f"(d[39]),"+f"(d[40]),"+f"(d[41]),"+f"(d[42]),"+f"(d[43]),"+f"(d[44]),"+f"(d[45]),"+f"(d[46]),"+f"(d[47]),"+f"(d[48]),"+f"(d[49]),"+f"(d[50]),"+f"(d[51]),"+f"(d[52]),"+f"(d[53]),"+f"(d[54]),"+f"(d[55]),"+f"(d[56]),"+f"(d[57]),"+f"(d[58]),"+f"(d[59]),"+f"(d[60]),"+f"(d[61]),"+f"(d[62]),"+f"(d[63]),"+f"(d[64]),"+f"(d[65]),"+f"(d[66]),"+f"(d[67]),"+f"(d[68]),"+f"(d[69]),"+f"(d[70]),"+f"(d[71]),"+f"(d[72]),"+f"(d[73]),"+f"(d[74]),"+f"(d[75]),"+f"(d[76]),"+f"(d[77]),"+f"(d[78]),"+f"(d[79]),"+f"(d[80]),"+f"(d[81]),"+f"(d[82]),"+f"(d[83]),"+f"(d[84]),"+f"(d[85]),"+f"(d[86]),"+f"(d[87]) : "l"(da), "l"(db), "r"(sc));
}
__device__ __forceinline__ void wg_tt128(float (&d)[64], uint64_t da, uint64_t db, int sc) {
  asm volatile("{.reg .pred p; setp.ne.b32 p, %66, 0; wgmma.mma_async.sync.aligned.m64n128k16.f32.bf16.bf16 {%0,%1,%2,%3,%4,%5,%6,%7,%8,%9,%10,%11,%12,%13,%14,%15,%16,%17,%18,%19,%20,%21,%22,%23,%24,%25,%26,%27,%28,%29,%30,%31,%32,%33,%34,%35,%36,%37,%38,%39,%40,%41,%42,%43,%44,%45,%46,%47,%48,%49,%50,%51,%52,%53,%54,%55,%56,%57,%58,%59,%60,%61,%62,%63}, %64, %65, p, 1, 1, 1, 1;}"
    : "+f"(d[0]),"+f"(d[1]),"+f"(d[2]),"+f"(d[3]),"+f"(d[4]),"+f"(d[5]),"+f"(d[6]),"+f"(d[7]),"+f"(d[8]),"+f"(d[9]),"+f"(d[10]),"+f"(d[11]),"+f"(d[12]),"+f"(d[13]),"+f"(d[14]),"+f"(d[15]),"+f"(d[16]),"+f"(d[17]),"+f"(d[18]),"+f"(d[19]),"+f"(d[20]),"+f"(d[21]),"+f"(d[22]),"+f"(d[23]),"+f"(d[24]),"+f"(d[25]),"+f"(d[26]),"+f"(d[27]),"+f"(d[28]),"+f"(d[29]),"+f"(d[30]),"+f"(d[31]),"+f"(d[32]),"+f"(d[33]),"+f"(d[34]),"+f"(d[35]),"+f"(d[36]),"+f"(d[37]),"+f"(d[38]),"+f"(d[39]),"+f"(d[40]),"+f"(d[41]),"+f"(d[42]),"+f"(d[43]),"+f"(d[44]),"+f"(d[45]),"+f"(d[46]),"+f"(d[47]),"+f"(d[48]),"+f"(d[49]),"+f"(d[50]),"+f"(d[51]),"+f"(d[52]),"+f"(d[53]),"+f"(d[54]),"+f"(d[55]),"+f"(d[56]),"+f"(d[57]),"+f"(d[58]),"+f"(d[59]),"+f"(d[60]),"+f"(d[61]),"+f"(d[62]),"+f"(d[63]) : "l"(da), "l"(db), "r"(sc));
}
__device__ __forceinline__ void wg_tt64(float (&d)[64], uint64_t da, uint64_t db, int sc) {
  asm volatile("{.reg .pred p; setp.ne.b32 p, %34, 0; wgmma.mma_async.sync.aligned.m64n64k16.f32.bf16.bf16 {%0,%1,%2,%3,%4,%5,%6,%7,%8,%9,%10,%11,%12,%13,%14,%15,%16,%17,%18,%19,%20,%21,%22,%23,%24,%25,%26,%27,%28,%29,%30,%31}, %32, %33, p, 1, 1, 1, 1;}"
    : "+f"(d[0]),"+f"(d[1]),"+f"(d[2]),"+f"(d[3]),"+f"(d[4]),"+f"(d[5]),"+f"(d[6]),"+f"(d[7]),"+f"(d[8]),"+f"(d[9]),"+f"(d[10]),"+f"(d[11]),"+f"(d[12]),"+f"(d[13]),"+f"(d[14]),"+f"(d[15]),"+f"(d[16]),"+f"(d[17]),"+f"(d[18]),"+f"(d[19]),"+f"(d[20]),"+f"(d[21]),"+f"(d[22]),"+f"(d[23]),"+f"(d[24]),"+f"(d[25]),"+f"(d[26]),"+f"(d[27]),"+f"(d[28]),"+f"(d[29]),"+f"(d[30]),"+f"(d[31]) : "l"(da), "l"(db), "r"(sc));
}
__device__ __forceinline__ void wg_tt32(float (&d)[64], uint64_t da, uint64_t db, int sc) {
  asm volatile("{.reg .pred p; setp.ne.b32 p, %18, 0; wgmma.mma_async.sync.aligned.m64n32k16.f32.bf16.bf16 {%0,%1,%2,%3,%4,%5,%6,%7,%8,%9,%10,%11,%12,%13,%14,%15}, %16, %17, p, 1, 1, 1, 1;}"
    : "+f"(d[0]),"+f"(d[1]),"+f"(d[2]),"+f"(d[3]),"+f"(d[4]),"+f"(d[5]),"+f"(d[6]),"+f"(d[7]),"+f"(d[8]),"+f"(d[9]),"+f"(d[10]),"+f"(d[11]),"+f"(d[12]),"+f"(d[13]),"+f"(d[14]),"+f"(d[15]) : "l"(da), "l"(db), "r"(sc));
}
__device__ __forceinline__ void wg_g1(float (&d)[88], uint64_t da, uint64_t db, int sc) {
  asm volatile("{.reg .pred p; setp.ne.b32 p, %90, 0; wgmma.mma_async.sync.aligned.m64n176k16.f32.bf16.bf16 {%0,%1,%2,%3,%4,%5,%6,%7,%8,%9,%10,%11,%12,%13,%14,%15,%16,%17,%18,%19,%20,%21,%22,%23,%24,%25,%26,%27,%28,%29,%30,%31,%32,%33,%34,%35,%36,%37,%38,%39,%40,%41,%42,%43,%44,%45,%46,%47,%48,%49,%50,%51,%52,%53,%54,%55,%56,%57,%58,%59,%60,%61,%62,%63,%64,%65,%66,%67,%68,%69,%70,%71,%72,%73,%74,%75,%76,%77,%78,%79,%80,%81,%82,%83,%84,%85,%86,%87}, %88, %89, p, 1, 1, 1, 0;}"
    : "+f"(d[0]),"+f"(d[1]),"+f"(d[2]),"+f"(d[3]),"+f"(d[4]),"+f"(d[5]),"+f"(d[6]),"+f"(d[7]),"+f"(d[8]),"+f"(d[9]),"+f"(d[10]),"+f"(d[11]),"+f"(d[12]),"+f"(d[13]),"+f"(d[14]),"+f"(d[15]),"+f"(d[16]),"+f"(d[17]),"+f"(d[18]),"+f"(d[19]),"+f"(d[20]),"+f"(d[21]),"+f"(d[22]),"+f"(d[23]),"+f"(d[24]),"+f"(d[25]),"+f"(d[26]),"+f"(d[27]),"+f"(d[28]),"+f"(d[29]),"+f"(d[30]),"+f"(d[31]),"+f"(d[32]),"+f"(d[33]),"+f"(d[34]),"+f"(d[35]),"+f"(d[36]),"+f"(d[37]),"+f"(d[38]),"+f"(d[39]),"+f"(d[40]),"+f"(d[41]),"+f"(d[42]),"+f"(d[43]),"+f"(d[44]),"+f"(d[45]),"+f"(d[46]),"+f"(d[47]),"+f"(d[48]),"+f"(d[49]),"+f"(d[50]),"+f"(d[51]),"+f"(d[52]),"+f"(d[53]),"+f"(d[54]),"+f"(d[55]),"+f"(d[56]),"+f"(d[57]),"+f"(d[58]),"+f"(d[59]),"+f"(d[60]),"+f"(d[61]),"+f"(d[62]),"+f"(d[63]),"+f"(d[64]),"+f"(d[65]),"+f"(d[66]),"+f"(d[67]),"+f"(d[68]),"+f"(d[69]),"+f"(d[70]),"+f"(d[71]),"+f"(d[72]),"+f"(d[73]),"+f"(d[74]),"+f"(d[75]),"+f"(d[76]),"+f"(d[77]),"+f"(d[78]),"+f"(d[79]),"+f"(d[80]),"+f"(d[81]),"+f"(d[82]),"+f"(d[83]),"+f"(d[84]),"+f"(d[85]),"+f"(d[86]),"+f"(d[87]) : "l"(da), "l"(db), "r"(sc));
}

struct Params { const __nv_bfloat16 *x, *logA, *Aim, *Cr, *Ci, *logdt, *Dskip; };
struct Maps { CUtensorMap x[2], xo, out, wg, wu, wd, hst[2], hld; };

__device__ __forceinline__ void conv_channel(uint32_t cb, int w, int lane, uint32_t (&res)[8], uint32_t bar_free) {
    const int q = lane & 3, g = lane >> 2, gam = g >> 2;
    float acc[64];
    uint4 a[4][4];
    const uint32_t t0 = cb + CH_T + (uint32_t)(14 + 4 * w + (g & 3) + 32 * gam - 2 * q) * 80u;
    #pragma unroll
    for (int s4 = 0; s4 < 4; s4++) {
        a[s4][0] = lds128(t0 + s4 * 16);
        a[s4][1] = lds128(t0 + 16 * 80 + s4 * 16);
        a[s4][2] = lds128(t0 - 8 * 80 + s4 * 16);
        a[s4][3] = lds128(t0 + 8 * 80 + s4 * 16);
    }
    const uint32_t l0 = FU(ldsf(t0 + 64)), l1 = FU(ldsf(t0 + 16 * 80 + 64)), l2 = FU(ldsf(t0 - 8 * 80 + 64)), l3 = FU(ldsf(t0 + 8 * 80 + 64));
    const uint64_t dU = mkdesc(cb + CH_U, UPLANE, 128, 0);
    WG_FENCE();
#define CT(N, s, c) wg_rs<N>(acc, a[(s) >> 2][0].c, a[(s) >> 2][1].c, a[(s) >> 2][2].c, a[(s) >> 2][3].c, dU + 4 * (s))
    wg_rs_first(acc, a[0][0].x, a[0][1].x, a[0][2].x, a[0][3].x, dU);
    CT(128, 1, y); CT(120, 2, z); CT(120, 3, w);
    CT(112, 4, x); CT(112, 5, y); CT(104, 6, z); CT(104, 7, w);
    CT(96, 8, x);  CT(96, 9, y);  CT(88, 10, z); CT(88, 11, w);
    CT(80, 12, x); CT(80, 13, y); CT(72, 14, z); CT(72, 15, w);
#undef CT
    wg_rs<64>(acc, l0, l1, l2, l3, dU + 64);
    wg_tt64(acc, mkdesc(cb + CH_A3, 128, 512, 0), mkdesc(cb + CH_B3, 128, 256, 0), 1);
    wg_tt32(acc, mkdesc(cb + CH_A3 + 256, 128, 512, 0), mkdesc(cb + CH_B3 + 1024, 128, 256, 0), 1);
    WG_COMMIT();
    WG_WAIT(0);
    fence_acc(acc);
    if (bar_free && lane == 0) mbar_arrive(bar_free);
    const int src1 = (lane & ~3) | ((q + 1) & 3);
    float E[16][2];
    #pragma unroll
    for (int j = 0; j < 16; j++) {
        const float nxt = (j < 15) ? acc[4 * (j + 1) + 2] : 0.f;
        const float sup = (q == 0) ? nxt : acc[4 * j + 2];
        const float v = __shfl_sync(0xffffffffu, sup, src1);
        E[j][0] = acc[4 * j] + acc[4 * j + 3];
        E[j][1] = acc[4 * j + 1] + v;
    }
    const int src2 = gam ? ((lane & 12) | ((q + 3) & 3)) : (16 | (lane & 12) | ((q + 1) & 3));
    const bool c1 = gam && q != 0, c2 = gam && q == 0;
    #pragma unroll
    for (int a2 = 0; a2 < 8; a2++) {
        float y[2];
        #pragma unroll
        for (int e = 0; e < 2; e++) {
            const float sup = c1 ? E[2 * a2][e] : E[2 * a2 + 1][e];
            const float nxt = (a2 < 7) ? E[2 * a2 + 2][e] : 0.f;
            const float keep = c2 ? nxt : (c1 ? E[2 * a2 + 1][e] : E[2 * a2][e]);
            y[e] = keep + __shfl_sync(0xffffffffu, sup, src2);
        }
        res[a2] = pack2(y[1], y[0]);
    }
}

__device__ __forceinline__ void consumer(uint32_t sb, int warp, const Maps& M) {
    const int V = warp >> 2, w = warp & 3, lane = threadIdx.x & 31, q = lane & 3, g = lane >> 2;
    const int c = blockIdx.x;
    const uint32_t bars = sb + OFF_BAR, xb = sb + OFF_X + V * 2 * XBUF;
    {
        float ag[88], au[88];
        define_acc(ag); define_acc(au);
        if (V == 0) {
            sts128(xb + (w >> 1) * XBUF + 168 * 128 + (threadIdx.x & 63) * 16, 0x3f803f80u, 0x3f803f80u, 0x3f803f80u, 0x3f803f80u);
            fence_async_smem();
            bar_sync(1);
        } else mbar_wait(bars + 8 * B_GO, 0);
        #pragma unroll 1
        for (int st = 0; st < 8; st++) {
            mbar_wait(bars + 8 * (B_FULLW + (st & 3)), st >> 2);
            mbar_wait(bars + 8 * (B_FULLX + 2 * V + (st & 1)), (st >> 1) & 1);
            STAMP(40 + 8 * V + st);
            const uint64_t dG = mkdesc(sb + OFF_W + (st & 3) * 16384, 0, 1024, 1);
            const uint64_t dX = mkdesc(xb + (st & 1) * XBUF, 16, 1024, 1);
            WG_FENCE();
            #pragma unroll
            for (int k = 0; k < 4; k++) {
                wg_g1(ag, dG + k * 128, dX + k * 2, k ? 1 : st);
                wg_g1(au, dG + 512 + k * 128, dX + k * 2, k ? 1 : st);
            }
            WG_COMMIT();
            WG_WAIT(1);
            if (lane == 0 && st > 0) {
                mbar_arrive(bars + 8 * (B_EMPTYW + ((st - 1) & 3)));
                mbar_arrive(bars + 8 * (B_EMPTYX + 2 * V + ((st - 1) & 1)));
                if (warp < 4 && st == 1) mbar_arrive(bars + 8 * B_GO);
            }
        }
        WG_WAIT(0);
        fence_acc(ag); fence_acc(au);
        if (lane == 0) { mbar_arrive(bars + 8 * (B_EMPTYW + 3)); mbar_arrive(bars + 8 * (B_EMPTYX + 2 * V + 1)); }
        STAMP(8 * V + 1);
        {
            if (V == 0) {
                const float cv = (q & 2) ? ((q & 1) ? au[86] : au[84]) : ((q & 1) ? ag[86] : ag[84]), hi = bf_round(cv);
                sts128(sb + OFF_CSUM + (16 * w + g + 8 * (q & 1) + 32 * (q & 2)) * 16, pack2(hi, cv - hi), 0, 0, 0);
                fence_async_smem();
                mbar_arrive(bars + 8 * B_CS);
            }
            mbar_wait(bars + 8 * B_CS, 0);
            mbar_wait(bars + 8 * B_STATS, 0);
            const uint64_t dM = mkdesc(sb + OFF_MB + V * 168 * 16, 0, 128, 0), dC = mkdesc(sb + OFF_CSUM, 0, 128, 0);
            WG_FENCE();
            wg_kk176(ag, dC, dM, 1);
            wg_kk176(au, dC + 64, dM, 1);
            WG_COMMIT();
            mbar_wait(bars + 8 * (B_EMPTYX + 2 * V), 1);
            WG_WAIT(0);
            fence_acc(ag); fence_acc(au);
        }
        const uint32_t hs = xb + (2 * w + ((lane >> 3) & 1)) * (2688 + 128 * V) + (lane >> 4) * 128 + (lane & 7) * 16;
        const uint32_t hr = sb + OFF_HR + (168 * V + 2 * q) * 4;
        #pragma unroll
        for (int j = 0; j < 22; j += 2) {
            uint32_t o[4];
            #pragma unroll
            for (int jj = 0; jj < 2; jj++) {
                const uint2 rv = lds64(hr + (j + jj) * 32);
                float hv[4];
                #pragma unroll
                for (int i = 0; i < 4; i++) {
                    const float gh = ag[4 * (j + jj) + i] * UF((i & 1) ? rv.y : rv.x);
                    const float p = gh * au[4 * (j + jj) + i];
                    hv[i] = fmaf(p, tanh_fast(gh), p);
                }
                o[2 * jj] = pack2(hv[0], hv[1]); o[2 * jj + 1] = pack2(hv[2], hv[3]);
            }
            uint32_t ad = hs + j * 128;
            if (j == 20 && V == 0 && lane >= 16) ad = xb + 21504 + (lane & 7) * 16;
            stsm4(ad, o[0], o[1], o[2], o[3]);
        }
        fence_async_smem();
        mbar_arrive(bars + 8 * (B_EPI + V));
        STAMP(8 * V + 2);
    }
    if (c >= 128) return;
    {
        mbar_wait(bars + 8 * B_CONV, 0);
        uint32_t r0[8], r1[8];
        #pragma unroll
        for (int i = 0; i < 8; i++) asm volatile("" : "=r"(r1[i]));
        #pragma unroll 1
        for (int e = 0; e < 2; e++) {
            #pragma unroll
            for (int i = 0; i < 8; i++) r0[i] = r1[i];
            conv_channel(sb + OFF_CONV + (2 * V + e) * CH_STRIDE, w, lane, r1, (V + e == 0) ? bars + 8 * B_CH0 : 0);
            if (e == 0) STAMP(8 * V + 3);
        }
        const int gam = g >> 2, qq = gam ? ((q + 3) & 3) : q;
        uint2* sp = g_S + (2 * c + V) * 1024 + (63 - 4 * gam - qq) * 16 + 4 * w + (g & 3);
        #pragma unroll
        for (int a2 = 0; a2 < 8; a2++) sp[-a2 * 128] = make_uint2(r0[a2], r1[a2]);
        mbar_arrive(bars + 8 * (B_SIG + V));
        STAMP(8 * V + 4);
    }
    if (V == 1) return;
    {
        const int tau = c >> 2, dg = c & 3;
        const uint32_t row = 8 * (w & 1) + 32 * (w >> 1);
        float acc[64];
        define_acc(acc);
        uint2 sv[16];
        #pragma unroll
        for (int i = 0; i < 16; i++) asm volatile("" : "=r"(sv[i].x), "=r"(sv[i].y));
        const float rr0 = __ldcg(&g_stats[64 * tau + row + g].y), rr1 = __ldcg(&g_stats[64 * tau + row + g + 16].y);
        int sd = 0, sh = 0, psd = 0, psh = 0; uint32_t pd = 0, ph = 0;
        #pragma unroll 1
        for (int st = 0; st < 22; st++) {
            mbar_wait(bars + 8 * (B_FULLD + sd), pd);
            mbar_wait(bars + 8 * (B_FULLH + sh), ph);
            if (st == 0) STAMP(5);
            const uint64_t dB = mkdesc(sb + wd_slot(sd), 8192, 1024, 1);
            const uint64_t dA = mkdesc(sb + OFF_X + 2 * XBUF + sh * 8192, 1024, 128, 0);
            WG_FENCE();
            wg_tt128(acc, dA, dB, st);
            wg_tt128(acc, dA + 128, dB + 128, 1);
            if (st < 21) {
                wg_tt128(acc, dA + 256, dB + 256, 1);
                wg_tt128(acc, dA + 384, dB + 384, 1);
            }
            WG_COMMIT();
            WG_WAIT(1);
            if (lane == 0 && st > 0) { mbar_arrive(bars + 8 * (B_EMPTYD + psd)); mbar_arrive(bars + 8 * (B_EMPTYH + psh)); }
            psd = sd; psh = sh;
            if (++sd == 6) { sd = 0; pd ^= 1; }
            if (++sh == 5) { sh = 0; ph ^= 1; }
            if (st == 14) {
                mbar_wait(bars + 8 * B_S, 0);
                const uint2* sp = g_S + (dg * 64 + q) * 1024 + (2 * tau) * 16 + (row >> 1) + 4 * (w & 1) + g;
                #pragma unroll
                for (int j = 0; j < 16; j++)
                    asm volatile("ld.global.cg.v2.b32 {%0,%1}, [%2];" : "=r"(sv[j].x), "=r"(sv[j].y) : "l"(sp + j * 4096));
            }
        }
        WG_WAIT(0);
        fence_acc(acc);
        STAMP(6);
        mbar_wait(bars + 8 * B_XO, 0);
        const uint32_t xo = sb + OFF_CONV + (row + (lane & 7) + 16 * ((lane >> 3) & 1)) * 128;
        #pragma unroll
        for (int j = 0; j < 16; j += 2) {
            const uint32_t ad = xo + (j >> 3) * 8192 + ((((j & 7) + (lane >> 4)) ^ (lane & 7)) << 4);
            uint32_t xr[4];
            asm volatile("ldmatrix.sync.aligned.m8n8.x4.shared.b16 {%0,%1,%2,%3}, [%4];" : "=r"(xr[0]), "=r"(xr[1]), "=r"(xr[2]), "=r"(xr[3]) : "r"(ad));
            #pragma unroll
            for (int i = 0; i < 4; i++) {
                const int jj = j + (i >> 1), hh = i & 1;
                const float f0 = acc[4 * jj + 2 * hh] * (hh ? rr1 : rr0), f1 = acc[4 * jj + 2 * hh + 1] * (hh ? rr1 : rr0);
                const uint32_t G = pack2(fmaf(f0, tanh_fast(f0), f0), fmaf(f1, tanh_fast(f1), f1));
                const uint32_t s2 = __byte_perm(sv[jj].x, sv[jj].y, hh ? 0x7632 : 0x5410);
                asm("fma.rn.bf16x2 %0, %1, %2, %0;" : "+r"(xr[i]) : "r"(s2), "r"(G));
            }
            stsm4(ad, xr[0], xr[1], xr[2], xr[3]);
        }
        fence_async_smem();
        bar_sync(1);
        if (w == 0 && elect_one()) {
            #pragma unroll
            for (int i = 0; i < 2; i++)
                asm volatile("cp.async.bulk.tensor.2d.global.shared::cta.bulk_group [%0, {%2, %3}], [%1];"
                    :: "l"(&M.out), "r"(sb + OFF_CONV + i * 8192), "r"(dg * 128 + 64 * i), "r"(tau * 64) : "memory");
            asm volatile("cp.async.bulk.commit_group; cp.async.bulk.wait_group.read 0;" ::: "memory");
        }
        STAMP(7);
    }
}

__device__ __forceinline__ float2 cexp_p(float re2, float om, float p) {
    float sn, cs;
    const float mag = ex2(re2 * p);
    const float k = fmaf(om, p, 12582912.f) - 12582912.f;
    const float th = fmaf(om, p, -k) * 6.283185307179586f;
    asm("sin.approx.ftz.f32 %0, %1;" : "=f"(sn) : "f"(th));
    asm("cos.approx.ftz.f32 %0, %1;" : "=f"(cs) : "f"(th));
    return make_float2(mag * cs, mag * sn);
}
__device__ __forceinline__ float2 cmul(float2 a, float2 b) { return make_float2(fmaf(a.x, b.x, -a.y * b.y), fmaf(a.x, b.y, a.y * b.x)); }
__device__ __forceinline__ float2 csqr(float2 a) { const float t = a.x * a.y; return make_float2(fmaf(a.x, a.x, -a.y * a.y), t + t); }
__device__ __forceinline__ void mma1688(float (&d)[4], uint32_t a0, uint32_t a1, uint32_t b0) {
    asm volatile("mma.sync.aligned.m16n8k8.row.col.f32.bf16.bf16.f32 {%0,%1,%2,%3}, {%4,%5}, {%6}, {%0,%1,%2,%3};"
        : "+f"(d[0]), "+f"(d[1]), "+f"(d[2]), "+f"(d[3]) : "r"(a0), "r"(a1), "r"(b0));
}
__device__ __forceinline__ float warp_sum(float v) {
    #pragma unroll
    for (int o = 16; o; o >>= 1) v += __shfl_xor_sync(0xffffffffu, v, o);
    return v;
}

__device__ __forceinline__ void aux_role(uint32_t sb, int w, const Params& P) {
    const int tid = threadIdx.x & 127, lane = tid & 31, q = lane & 3, g = lane >> 2;
    const int c = blockIdx.x, tg = c / 22;
    const uint32_t bars = sb + OFF_BAR;
    if (c < 128) {
        const uint32_t cb = sb + OFF_CONV + w * CH_STRIDE;
        const uint32_t sF = cb + CH_A3, sP = cb + CH_A3 + 2064;
        const int tokb = 32 * (c >> 1) + 8 * (c & 1) + 16;
        if (w == 0) {
            if (lane == 0) mbar_expect(bars + 8 * B_LNX, 16384);
            __syncwarp();
            if (lane < 16) bulk_load(sb + OFF_CONV + lane * LNROW, P.x + (tokb + (lane & 7) - 2 * (lane & 8)) * DM, 1024, bars + 8 * B_LNX);
        }
        const int d = 4 * c + w;
        const uint2 la = *(const uint2*)(P.logA + d * 128 + 4 * lane), ai = *(const uint2*)(P.Aim + d * 128 + 4 * lane);
        const uint2 cr = *(const uint2*)(P.Cr + d * 128 + 4 * lane), ci = *(const uint2*)(P.Ci + d * 128 + 4 * lane);
        const float ldt = __bfloat162float(P.logdt[d]), dsk = __bfloat162float(P.Dskip[d]);
        mbar_wait(bars + 8 * B_LNX, 0);
        STAMP(34);
        #pragma unroll 1
        for (int r = w; r < 16; r += 4) {
            const uint32_t ra = sb + OFF_CONV + r * LNROW + lane * 16;
            uint32_t v[8];
            *(uint4*)&v[0] = lds128(ra); *(uint4*)&v[4] = lds128(ra + 512);
            float s = 0.f, a = 0.f;
            #pragma unroll
            for (int k = 0; k < 8; k++) s += bf_lo(v[k]) + bf_hi(v[k]);
            const float m = warp_sum(s) * (1.f / DM);
            #pragma unroll
            for (int k = 0; k < 8; k++) { const float t0 = bf_lo(v[k]) - m, t1 = bf_hi(v[k]) - m; a = fmaf(t0, t0, a); a = fmaf(t1, t1, a); }
            float sd, ri;
            asm("sqrt.approx.f32 %0, %1;" : "=f"(sd) : "f"(bf_round(bf_round(warp_sum(a) * (1.f / DM)) + 1e-5f)));
            asm("rcp.approx.f32 %0, %1;" : "=f"(ri) : "f"(bf_round(sd)));
            const uint32_t m2 = pack2(m, m);
            if (lane == 0) g_stats[tokb + (r & 7) - 2 * (r & 8)] = make_float2(bf_hi(m2), 0.5f * ri);
            #pragma unroll
            for (int k = 0; k < 8; k++) {
                uint32_t dv; asm("sub.rn.bf16x2 %0, %1, %2;" : "=r"(dv) : "r"(v[k]), "r"(m2));
                v[k] = pack2(bf_lo(dv) * ri, bf_hi(dv) * ri);
            }
            sts128(ra, v[0], v[1], v[2], v[3]); sts128(ra + 512, v[4], v[5], v[6], v[7]);
        }
        bar_sync(2);
        {
            uint32_t ad = sb + OFF_CONV + (4 * ((lane & 7) >> 1) + (lane & 1) + 2 * ((lane >> 3) & 1)) * LNROW + (16 * w + (lane >> 4)) * 16;
            uint2* dst = (uint2*)(g_xnT + (128 * w + g) * 256 + (c & 1) * 128 + (126 - 2 * (c >> 1))) + q;
            #pragma unroll 1
            for (int i = 0; i < 8; i++, ad += 32, dst += 16 * 512) {
                uint32_t r0, r1, r2, r3;
                asm volatile("ldmatrix.sync.aligned.m8n8.x4.trans.shared.b16 {%0,%1,%2,%3}, [%4];" : "=r"(r0), "=r"(r1), "=r"(r2), "=r"(r3) : "r"(ad));
                dst[0] = make_uint2(r0, r1); dst[8 * 512] = make_uint2(r2, r3);
            }
        }
        mbar_arrive(bars + 8 * B_LN);
        bar_sync(2);
        STAMP(16);
        {
            const float dt = bf_round(ex2(ldt * 1.4426950408889634f));
            #pragma unroll
            for (int i = 0; i < 4; i++) {
                const uint32_t l2 = (i & 2) ? la.y : la.x, a2 = (i & 2) ? ai.y : ai.x, r2 = (i & 2) ? cr.y : cr.x, i2 = (i & 2) ? ci.y : ci.x;
                const float re = bf_round(ex2(((i & 1) ? bf_hi(l2) : bf_lo(l2)) * 1.4426950408889634f)) * dt;
                const float im = ((i & 1) ? bf_hi(a2) : bf_lo(a2)) * dt;
                sts128(sP + (4 * lane + i) * 16, FU(re * -1.4426950408889634f), FU(im * 0.15915494309189535f),
                       FU(((i & 1) ? bf_hi(r2) : bf_lo(r2)) * (dt + dt)), FU(((i & 1) ? bf_hi(i2) : bf_lo(i2)) * (dt + dt)));
            }
        }
        __syncwarp();
        float dacc[2][3][4];
        #pragma unroll
        for (int i = 0; i < 24; i++) (&dacc[0][0][0])[i] = 0.f;
        const float p0 = (float)g, p8 = 8.f * p0;
        const float p1 = (float)((g < 4) ? 256 + 2 * g : 512 + 4 * (g & 1) + 128 * (g & 2));
        const float p2 = (g < 4) ? fmaf(p0, 256.f, 1032.f) : 1024.f;
        #pragma unroll 1
        for (uint32_t pa = sP + q * 16; pa < sP + 2048; pa += 64) {
            const uint4 pv = lds128(pa);
            const float re2 = UF(pv.x), om = UF(pv.y);
            const float2 C = make_float2(UF(pv.z), UF(pv.w));
            const float2 R0 = cexp_p(re2, om, p8);
            float2 z32; z32.x = __shfl_sync(0xffffffffu, R0.x, 16 + q); z32.y = __shfl_sync(0xffffffffu, R0.y, 16 + q);
            const float2 z64 = csqr(z32), z128 = csqr(z64);
            const float2 R1 = cmul(R0, z64), R2 = cmul(R0, z128), R3 = cmul(R1, z128);
            const float2 L0 = cmul(C, cexp_p(re2, om, p0)), L1 = cmul(C, cexp_p(re2, om, p1)), L2 = cmul(C, cexp_p(re2, om, p2));
            const uint32_t a0 = pack2(R0.x, R0.y), a1 = pack2(R1.x, R1.y), a2 = pack2(R2.x, R2.y), a3 = pack2(R3.x, R3.y);
            const uint32_t b0 = pack2(L0.x, -L0.y), b1 = pack2(L1.x, -L1.y), b2 = pack2(L2.x, -L2.y);
            mma1688(dacc[0][0], a0, a1, b0); mma1688(dacc[1][0], a2, a3, b0);
            mma1688(dacc[0][1], a0, a1, b1); mma1688(dacc[1][1], a2, a3, b1);
            mma1688(dacc[0][2], a0, a1, b2); mma1688(dacc[1][2], a2, a3, b2);
        }
        STAMP(18);
        const uint32_t sG = cb + CH_G;
        if (lane < 16) sts128(((lane & 8) ? cb + CH_U + 2048 + (lane & 4) * (UPLANE / 4) : sG + 128 + (lane & 4) * 48) + (lane & 3) * 16, 0, 0, 0, 0);
        {
            const uint32_t f0 = sF + (8 * g + 2 * q) * 4, f1 = sF + ((q < 2) ? 256 + 4 * g + 2 * q : 256 + 2 * g + 64 * q) * 4, st1 = (q < 2) ? 128 : 64;
            const uint32_t ga = sG + ((g & 1) ? 0 : 192) + (63 - (g >> 1) - 32 * q) * 2;
            #pragma unroll
            for (int i = 0; i < 4; i++) {
                const int mu = i >> 1, hh = i & 1;
                sts64(f0 + i * 256, FU(dacc[mu][0][2 * hh]), FU(dacc[mu][0][2 * hh + 1]));
                sts64(f1 + i * st1, FU(dacc[mu][1][2 * hh]), FU(dacc[mu][1][2 * hh + 1]));
                const uint32_t pk = pack2(dacc[mu][2][2 * hh], dacc[mu][2][2 * hh + 1]);
                if (q < 2) { sts16(ga - 8 * i, pk & 0xffff); sts16(ga - 8 * i - 32, pk >> 16); }
            }
            if (lane == 2) stsf(sF + 2048, dacc[0][2][0]);
        }
        __syncwarp();
        #pragma unroll 1
        for (int pass = 0; pass < 3; pass++) {
            const int rw = lane - 1 + 31 * pass;
            const int u = min(rw, 77) - 14;
            const uint32_t f0 = sF + u * 4, f1 = sF + (128 + ((u + ((u >> 1) & 1)) >> 1)) * 4, f2 = sF + (256 + ((u + 1 + ((u >> 2) & 1)) >> 2)) * 4;
            float kv[17];
            kv[0] = ldsf(u < 0 ? sF : f0); if (u < 0) kv[0] = 0.f; if (u == 0) kv[0] += dsk;
            #pragma unroll
            for (int s = 1; s < 4; s++) kv[s] = ldsf(f0 + s * 256);
            kv[4] = ldsf(u < 0 ? f0 + 1024 : f1 + 512);
            #pragma unroll
            for (int s = 5; s < 8; s++) kv[s] = ldsf(f1 + s * 128);
            kv[8] = ldsf(u < 0 ? f1 + 1024 : f2 + 512);
            #pragma unroll
            for (int s = 9; s < 16; s++) kv[s] = ldsf(f2 + s * 64);
            kv[16] = ldsf(u < 0 ? f2 + 1024 : sF + 2048); if (u > 4) kv[16] = 0.f;
            uint32_t o[17];
            #pragma unroll
            for (int s = 0; s < 17; s++) o[s] = pack2(kv[s], __shfl_up_sync(0xffffffffu, kv[s], 1));
            if (lane > 0 && rw < 78) {
                const uint32_t ta = cb + CH_T + rw * 80;
                #pragma unroll
                for (int s4 = 0; s4 < 4; s4++) sts128(ta + s4 * 16, o[4 * s4], o[4 * s4 + 1], o[4 * s4 + 2], o[4 * s4 + 3]);
                stsf(ta + 64, UF(o[16]));
            }
        }
        #pragma unroll 1
        for (int un = lane; un < 128; un += 32) {
            const uint32_t ga = sG + ((un >> 3) & 1) * 192 + (un >> 4) * 16 + (un & 7) * 8;
            const uint2 x0 = lds64(ga), x1 = lds64(ga + 8);
            sts128(cb + CH_B3 + un * 16, x0.x, x0.y, x1.x, x1.y);
        }
    } else mbar_arrive(bars + 8 * B_LN);
    STAMP(19);
    if (tid == 0) {
        flag_wait(F_A, NCTA);
        if (c < 128) {
            fence_async();
            mbar_expect(bars + 8 * B_U, 8 * 2048);
            #pragma unroll 1
            for (int i = 0; i < 8; i++)
                bulk_load(sb + OFF_CONV + (i >> 1) * CH_STRIDE + CH_U + (i & 1) * UPLANE, g_xnT + 4 * c * 256 + i * 128, 2048, bars + 8 * B_U);
        } else exit_count();
    }
    bar_sync(2);
    #pragma unroll 1
    for (int t = tid; t < TOKG; t += 128) {
        const float2 sv = __ldcg(g_stats + min(TOKG * tg + t, SEQ - 1));
        sts128(sb + OFF_MB + t * 16, pack2(-0.5f * sv.x, -0.5f * sv.x), 0, 0, 0);
        stsf(sb + OFF_HR + t * 4, sv.y);
    }
    fence_async_smem();
    mbar_arrive(bars + 8 * B_STATS);
    STAMP(20);
    if (c >= 128) return;
    mbar_wait(bars + 8 * B_U, 0);
    {
        const int kap = (lane >> 4) * 8 + ((lane >> 1) & 7), gam = lane & 1, hh = w >> 1, wp = w & 1;
        uint32_t ua = sb + OFF_CONV + CH_U + wp * UPLANE + (127 - 4 * kap - 2 * gam - hh) * 16;
        uint32_t ub = sb + OFF_CONV + CH_U + (wp ^ 1) * UPLANE + (128 - wp - 4 * kap - 2 * gam - hh) * 16;
        uint32_t ad = sb + OFF_CONV + CH_A3 + (4 * wp + hh) * 512 + (kap >> 3) * 256 + (kap & 7) * 16 + gam * 8;
        #pragma unroll 1
        for (int ch = 0; ch < 4; ch++, ua += CH_STRIDE, ub += CH_STRIDE, ad += CH_STRIDE) {
            float p[24];
            const uint2 r0 = lds64(ub + 24), r3 = lds64(ua);
            uint32_t r[8];
            *(uint4*)&r[0] = lds128(ua + 16); *(uint4*)&r[4] = lds128(ub);
            p[0] = 0.f;
            p[1] = bf_lo(r0.x); p[2] = p[1] + bf_hi(r0.x); p[3] = p[2] + bf_lo(r0.y); p[4] = p[3] + bf_hi(r0.y);
            #pragma unroll
            for (int i = 0; i < 8; i++) { p[5 + 2 * i] = p[4 + 2 * i] + bf_lo(r[i]); p[6 + 2 * i] = p[5 + 2 * i] + bf_hi(r[i]); }
            p[21] = p[20] + bf_lo(r3.x); p[22] = p[21] + bf_hi(r3.x); p[23] = p[22] + bf_lo(r3.y);
            #pragma unroll
            for (int i = 0; i < 8; i += 4) {
                sts64(ad + i * 256, pack2(p[i + 9] - p[i], p[i + 10] - p[i + 1]), pack2(p[i + 11] - p[i + 2], p[i + 12] - p[i + 3]));
                sts64(ad + i * 256 + 128, pack2(p[i + 16] - p[i + 9], p[i + 17] - p[i + 10]), pack2(p[i + 18] - p[i + 11], p[i + 19] - p[i + 12]));
            }
        }
    }
    fence_async_smem();
    mbar_arrive(bars + 8 * B_CONV);
    STAMP(21);
}

__global__ void __launch_bounds__(512, 1)
fused_kernel(const __grid_constant__ Maps M, const __grid_constant__ Params P) {
    extern __shared__ __align__(1024) uint8_t smem_raw[];
    const uint32_t sb = smem_u32(smem_raw);
    const uint32_t bars = sb + OFF_BAR;
    const int warp = __shfl_sync(0xffffffffu, threadIdx.x >> 5, 0);
    if (threadIdx.x < B_COUNT) {
        const int i = threadIdx.x;
        STAMP(24);
        const uint32_t cnt = i >= B_STATS ? 128 : ((0x00f0ull >> i) & 1) ? 8 : ((0x303e0fc0f000ull >> i) & 1) ? 4 : 1;
        asm volatile("mbarrier.init.shared::cta.b64 [%0], %1;" :: "r"(bars + 8 * i), "r"(cnt) : "memory");
        asm volatile("fence.mbarrier_init.release.cluster; fence.proxy.async.shared::cta;" ::: "memory");
        if (sb & 1023) __trap();
    }
    __syncthreads();
    if (warp < 8) {
        asm volatile("setmaxnreg.inc.sync.aligned.u32 208;");
        consumer(sb, warp, M);
    } else if (warp < 12) {
        asm volatile("setmaxnreg.dec.sync.aligned.u32 72;");
        STAMP(32);
        aux_role(sb, warp - 8, P);
    } else {
        asm volatile("setmaxnreg.dec.sync.aligned.u32 24;");
        const int c = blockIdx.x, tg = c / 22, fb = c - 22 * tg, tau = c >> 2, dg = c & 3;
        if (elect_one()) {
            if (warp == 12) {
                #pragma unroll 1
                for (int st = 0; st < 8; st++) {
                    const uint32_t s = st & 3, fb_ = bars + 8 * (B_FULLW + s);
                    mbar_wait(bars + 8 * (B_EMPTYW + s), (st >> 2) ^ 1);
                    mbar_expect(fb_, 16384);
                    tma2d(sb + OFF_W + s * 16384, &M.wg, 64 * fb, 64 * st, fb_);
                    tma2d(sb + OFF_W + s * 16384 + 8192, &M.wu, 64 * fb, 64 * st, fb_);
                    if (st == 0) STAMP(31);
                }
                if (c < 128) {
                    int sd = 0; uint32_t pe = 1;
                    #pragma unroll 1
                    for (int st = 0; st < 22; st++) {
                        if (st < 6) mbar_wait(bars + 8 * (uint32_t)((0x2a070d060504ull >> (8 * st)) & 0xff), st < 5);
                        else mbar_wait(bars + 8 * (B_EMPTYD + sd), pe);
                        const uint32_t da = sb + wd_slot(sd), fb_ = bars + 8 * (B_FULLD + sd);
                        mbar_expect(fb_, 16384);
                        tma2d(da, &M.wd, 128 * dg, 64 * st, fb_);
                        tma2d(da + 8192, &M.wd, 128 * dg + 64, 64 * st, fb_);
                        if (++sd == 6) { sd = 0; pe ^= 1; }
                    }
                }
            } else if (warp < 15) {
                const int V = warp - 13;
                #pragma unroll 1
                for (int st = 0; st < 8; st++) {
                    const uint32_t s = 2 * V + (st & 1);
                    mbar_wait(bars + 8 * (B_EMPTYX + s), ((st >> 1) & 1) ^ 1);
                    mbar_expect(bars + 8 * (B_FULLX + s), (168 + 8 * V) * 128);
                    tma2d(sb + OFF_X + s * XBUF, &M.x[V], 64 * st, TOKG * tg + 168 * V, bars + 8 * (B_FULLX + s));
                }
                if (c < 128) {
                    if (V == 0) {
                        mbar_wait(bars + 8 * (B_STG + 1), 0);
                        #pragma unroll 1
                        for (int o = 8 * tau; o < 8 * tau + 8; o += 7) flag_wait(F_H + 2 * (o / 43) + ((o % 43) >= 21), 22);
                        fence_async();
                        STAMP(25);
                        int sh = 0; uint32_t pe = 1;
                        #pragma unroll 1
                        for (int st = 0; st < 22; st++) {
                            const uint32_t fb_ = bars + 8 * (B_FULLH + sh);
                            mbar_wait(bars + 8 * (B_EMPTYH + sh), pe);
                            mbar_expect(fb_, 8192);
                            asm volatile("cp.async.bulk.tensor.5d.shared::cluster.global.mbarrier::complete_tx::bytes [%0], [%1, {%3, %3, %3, %4, %5}], [%2];"
                                :: "r"(sb + OFF_X + 2 * XBUF + sh * 8192), "l"(&M.hld), "r"(fb_), "r"(0), "r"(2 * tau), "r"(8 * st) : "memory");
                            if (++sh == 5) { sh = 0; pe ^= 1; }
                        }
                    } else {
                        mbar_wait(bars + 8 * B_CH0, 0);
                        mbar_expect(bars + 8 * B_XO, 16384);
                        tma2d(sb + OFF_CONV, &M.xo, 128 * dg, 64 * tau, bars + 8 * B_XO);
                        tma2d(sb + OFF_CONV + 8192, &M.xo, 128 * dg + 64, 64 * tau, bars + 8 * B_XO);
                        flag_wait(F_S + dg, 64);
                        STAMP(26);
                        mbar_arrive(bars + 8 * B_S);
                        mbar_wait(bars + 8 * B_FULLH, 0);
                        exit_count();
                    }
                }
            } else {
                mbar_wait(bars + 8 * B_LN, 0);
                flag_signal(F_A);
                #pragma unroll 1
                for (int V = 0; V < 2; V++) {
                    mbar_wait(bars + 8 * (B_EPI + V), 0);
                    asm volatile("cp.async.bulk.tensor.3d.global.shared::cta.bulk_group [%0, {%2, %3, %4}], [%1];"
                        :: "l"(&M.hst[V]), "r"(sb + OFF_X + V * 2 * XBUF), "r"(0), "r"(43 * tg + 21 * V), "r"(8 * fb) : "memory");
                    asm volatile("cp.async.bulk.commit_group; cp.async.bulk.wait_group 0;" ::: "memory");
                    mbar_arrive(bars + 8 * (B_STG + V));
                    flag_signal(F_H + 2 * tg + V);
                }
                if (c < 128) {
                    #pragma unroll 1
                    for (int V = 0; V < 2; V++) { mbar_wait(bars + 8 * (B_SIG + V), 0); flag_signal(F_S + (c >> 5)); }
                }
            }
        }
    }
}

typedef CUresult (*EncodeFn)(CUtensorMap*, CUtensorMapDataType, cuuint32_t, void*, const cuuint64_t*, const cuuint64_t*, const cuuint32_t*,
                             const cuuint32_t*, CUtensorMapInterleave, CUtensorMapSwizzle, CUtensorMapL2promotion, CUtensorMapFloatOOBfill);

void make_map(EncodeFn enc, CUtensorMap* m, const void* ptr, int rank, const cuuint64_t* dims, const cuuint64_t* strides, const cuuint32_t* box, bool swz) {
    const cuuint32_t es[5] = {1, 1, 1, 1, 1};
    enc(m, CU_TENSOR_MAP_DATA_TYPE_BFLOAT16, rank, (void*)ptr, dims, strides, box, es, CU_TENSOR_MAP_INTERLEAVE_NONE,
        swz ? CU_TENSOR_MAP_SWIZZLE_128B : CU_TENSOR_MAP_SWIZZLE_NONE, CU_TENSOR_MAP_L2_PROMOTION_L2_128B, CU_TENSOR_MAP_FLOAT_OOB_FILL_NONE);
}
void make_map2(EncodeFn enc, CUtensorMap* m, const void* ptr, cuuint64_t inner, cuuint64_t outer, cuuint32_t rows) {
    const cuuint64_t dims[2] = {inner, outer}, strides[1] = {inner * 2};
    const cuuint32_t box[2] = {64, rows};
    make_map(enc, m, ptr, 2, dims, strides, box, true);
}

}

extern "C" void kernel_launch(void* const* d_in, const int* in_sizes, int n_in, void* d_out, int out_size) {
    (void)in_sizes; (void)n_in; (void)out_size;
    static EncodeFn enc = nullptr;
    static void* hptr = nullptr;
    if (!enc) {
        cudaDriverEntryPointQueryResult qr;
        cudaGetDriverEntryPoint("cuTensorMapEncodeTiled", (void**)&enc, cudaEnableDefault, &qr);
        cudaFuncSetAttribute(fused_kernel, cudaFuncAttributeMaxDynamicSharedMemorySize, SMEM_BYTES);
        cudaGetSymbolAddress(&hptr, g_H);
    }
    Params P;
    P.x = (const __nv_bfloat16*)d_in[0]; P.logA = (const __nv_bfloat16*)d_in[1]; P.Aim = (const __nv_bfloat16*)d_in[2];
    P.Cr = (const __nv_bfloat16*)d_in[3]; P.Ci = (const __nv_bfloat16*)d_in[4]; P.logdt = (const __nv_bfloat16*)d_in[5];
    P.Dskip = (const __nv_bfloat16*)d_in[6];
    Maps M;
    make_map2(enc, &M.x[0], d_in[0], DM, SEQ, 168); make_map2(enc, &M.x[1], d_in[0], DM, SEQ, 176);
    make_map2(enc, &M.xo, d_in[0], DM, SEQ, 64);    make_map2(enc, &M.out, d_out, DM, SEQ, 64);
    make_map2(enc, &M.wg, d_in[8], FF, DM, 64);     make_map2(enc, &M.wu, d_in[9], FF, DM, 64);
    make_map2(enc, &M.wd, d_in[10], DM, FF, 64);
    for (int v = 0; v < 2; v++) {
        const cuuint64_t dims[3] = {64, 256, 172}, strides[2] = {128, 32768};
        const cuuint32_t box[3] = {64, (cuuint32_t)(21 + v), 8};
        make_map(enc, &M.hst[v], hptr, 3, dims, strides, box, false);
    }
    {
        const cuuint64_t dims[5] = {64, 2, 2, 64, 172}, strides[4] = {256, 128, 512, 32768};
        const cuuint32_t box[5] = {64, 2, 2, 2, 8};
        make_map(enc, &M.hld, hptr, 5, dims, strides, box, false);
    }
    fused_kernel<<<NCTA, 512, SMEM_BYTES>>>(M, P);
}
```

```cpp
#include <cuda_runtime.h>
#include <cuda_bf16.h>
#include <cuda.h>
#include <stdint.h>

#define PROF 0

namespace {

constexpr int SEQ = 2048, DM = 512, FF = 1376;
constexpr int NCTA = 132;
constexpr int TOKG = 344;

constexpr uint32_t OFF_W = 0;
constexpr uint32_t XBUF = 22528;
constexpr uint32_t OFF_X = 65536;
constexpr uint32_t OFF_CONV = 155648;
constexpr uint32_t CH_STRIDE = 16640;
constexpr uint32_t CH_T = 0;
constexpr uint32_t CH_A3 = 6272;
constexpr uint32_t CH_B3 = 10368;
constexpr uint32_t CH_U = 12416;
constexpr uint32_t CH_G = CH_A3 + 2064;
constexpr uint32_t UPLANE = 2112;
constexpr uint32_t LNROW = 1040;
constexpr uint32_t OFF_MB = 222208;
constexpr uint32_t OFF_HR = 227712;
constexpr uint32_t OFF_CSUM = 229120;
constexpr uint32_t OFF_BAR = 231168;
constexpr uint32_t SMEM_BYTES = 231680;

enum {
    B_FULLW = 0, B_EMPTYW = 4, B_FULLX = 8, B_EMPTYX = 12, B_FULLD = 16, B_EMPTYD = 22,
    B_U = 28, B_XO = 29, B_S = 30, B_STG = 31, B_HF = 33,
    B_LNX = 34, B_GO = 35, B_CH0 = 36,
    B_STATS = 37, B_CONV = 38, B_LN = 39, B_CS = 40, B_EPI = 41, B_SIG = 43,
    B_COUNT = 45
};
enum { F_A = 0, F_H = 1, F_S = 13, F_EXIT = 17, F_COUNT = 18 };

__device__ uint4 g_xnT[DM * 256];
__device__ float2 g_stats[SEQ];
__device__ uint4 g_H[172 * 256 * 8];
__device__ uint2 g_S[256 * 1024];
__device__ unsigned g_flags[F_COUNT * 32];
#define STAMP(i) do {} while (0)

__device__ __forceinline__ uint32_t smem_u32(const void* p) { return (uint32_t)__cvta_generic_to_shared(p); }
__device__ __forceinline__ void mbar_expect(uint32_t bar, uint32_t bytes) { asm volatile("mbarrier.arrive.expect_tx.shared::cta.b64 _, [%0], %1;" :: "r"(bar), "r"(bytes) : "memory"); }
__device__ __forceinline__ void mbar_arrive(uint32_t bar) { asm volatile("mbarrier.arrive.shared::cta.b64 _, [%0];" :: "r"(bar) : "memory"); }
__device__ __forceinline__ void mbar_wait(uint32_t bar, uint32_t parity) {
    asm volatile("{.reg .pred p; .reg .u32 n; mov.u32 n, 0x20000;\n"
                 "LW: mbarrier.try_wait.parity.shared::cta.b64 p, [%0], %1;\n"
                 "sub.u32 n, n, 1; setp.eq.or.u32 p, n, 0, p; @!p bra LW;}" :: "r"(bar), "r"(parity) : "memory");
}
__device__ __forceinline__ bool elect_one() { uint32_t p; asm volatile("{.reg .pred P; elect.sync _|P, 0xffffffff; selp.u32 %0, 1, 0, P;}" : "=r"(p)); return p; }
__device__ __forceinline__ void tma2d(uint32_t dst, const CUtensorMap* m, int c0, int c1, uint32_t bar) {
    asm volatile("cp.async.bulk.tensor.2d.shared::cluster.global.mbarrier::complete_tx::bytes [%0], [%1, {%3, %4}], [%2];"
        :: "r"(dst), "l"(m), "r"(bar), "r"(c0), "r"(c1) : "memory");
}
__device__ __forceinline__ void bulk_load(uint32_t dst, const void* src, uint32_t bytes, uint32_t bar) {
    asm volatile("cp.async.bulk.shared::cluster.global.mbarrier::complete_tx::bytes [%0], [%1], %2, [%3];" :: "r"(dst), "l"(src), "r"(bytes), "r"(bar) : "memory");
}
__device__ __forceinline__ void fence_async() { asm volatile("fence.proxy.async;" ::: "memory"); }
__device__ __forceinline__ void fence_async_smem() { asm volatile("fence.proxy.async.shared::cta;" ::: "memory"); }
__device__ __forceinline__ void flag_wait(int f, unsigned target) {
    asm volatile("{.reg .pred p; .reg .u32 n, v; mov.u32 n, 0x40000;\n"
                 "LF: ld.acquire.gpu.global.u32 v, [%0]; setp.ge.u32 p, v, %1; @p bra LD;\n"
                 "nanosleep.u32 20; sub.u32 n, n, 1; setp.ne.u32 p, n, 0; @p bra LF; trap;\nLD: }"
                 :: "l"(g_flags + f * 32), "r"(target) : "memory");
}
__device__ __forceinline__ void flag_signal(int f) {
    asm volatile("fence.acq_rel.gpu; red.relaxed.gpu.global.add.u32 [%0], 1;" :: "l"(g_flags + f * 32) : "memory");
}
__device__ __forceinline__ void exit_count() {
    if (atomicAdd(g_flags + F_EXIT * 32, 1u) == NCTA - 1) {
        #pragma unroll 1
        for (int i = 0; i < F_COUNT; i++) g_flags[i * 32] = 0;
    }
}
__device__ __forceinline__ void bar_sync(int id) { asm volatile("bar.sync %0, 128;" :: "r"(id) : "memory"); }
__device__ __forceinline__ uint64_t mkdesc(uint32_t addr, uint32_t lbo, uint32_t sbo, uint32_t swz) {
    return (uint64_t)((addr >> 4) | ((lbo >> 4) << 16)) | ((uint64_t)((sbo >> 4) | (swz << 30)) << 32);
}
#define WG_FENCE() asm volatile("wgmma.fence.sync.aligned;" ::: "memory")
#define WG_COMMIT() asm volatile("wgmma.commit_group.sync.aligned;" ::: "memory")
#define WG_WAIT(n) asm volatile("wgmma.wait_group.sync.aligned " #n ";" ::: "memory")
template <int N> __device__ __forceinline__ void fence_acc(float (&d)[N]) {
    #pragma unroll
    for (int i = 0; i < N; i++) asm volatile("" : "+f"(d[i]) :: "memory");
}
template <int N> __device__ __forceinline__ void define_acc(float (&d)[N]) {
    #pragma unroll
    for (int i = 0; i < N; i++) asm volatile("" : "=f"(d[i]));
}
__device__ __forceinline__ uint32_t pack2(float lo, float hi) { uint32_t r; asm("cvt.rn.bf16x2.f32 %0, %1, %2;" : "=r"(r) : "f"(hi), "f"(lo)); return r; }
__device__ __forceinline__ float bf_lo(uint32_t v) { return __uint_as_float(v << 16); }
__device__ __forceinline__ float bf_hi(uint32_t v) { return __uint_as_float(v & 0xffff0000u); }
__device__ __forceinline__ float bf_round(float v) { return bf_hi(pack2(0.f, v)); }
__device__ __forceinline__ float tanh_fast(float v) { float r; asm("tanh.approx.f32 %0, %1;" : "=f"(r) : "f"(v)); return r; }
__device__ __forceinline__ float ex2(float v) { float r; asm("ex2.approx.ftz.f32 %0, %1;" : "=f"(r) : "f"(v)); return r; }
__device__ __forceinline__ uint4 lds128(uint32_t a) { uint4 v; asm volatile("ld.shared.v4.b32 {%0,%1,%2,%3}, [%4];" : "=r"(v.x), "=r"(v.y), "=r"(v.z), "=r"(v.w) : "r"(a)); return v; }
__device__ __forceinline__ uint2 lds64(uint32_t a) { uint2 v; asm volatile("ld.shared.v2.b32 {%0,%1}, [%2];" : "=r"(v.x), "=r"(v.y) : "r"(a)); return v; }
__device__ __forceinline__ float ldsf(uint32_t a) { float v; asm volatile("ld.shared.f32 %0, [%1];" : "=f"(v) : "r"(a)); return v; }
__device__ __forceinline__ void sts128(uint32_t a, uint32_t x, uint32_t y, uint32_t z, uint32_t w) { asm volatile("st.shared.v4.b32 [%0], {%1,%2,%3,%4};" :: "r"(a), "r"(x), "r"(y), "r"(z), "r"(w) : "memory"); }
__device__ __forceinline__ void sts64(uint32_t a, uint32_t x, uint32_t y) { asm volatile("st.shared.v2.b32 [%0], {%1,%2};" :: "r"(a), "r"(x), "r"(y) : "memory"); }
__device__ __forceinline__ void stsf(uint32_t a, float x) { asm volatile("st.shared.f32 [%0], %1;" :: "r"(a), "f"(x) : "memory"); }
__device__ __forceinline__ void sts16(uint32_t a, uint32_t x) { asm volatile("st.shared.b16 [%0], %1;" :: "r"(a), "h"((unsigned short)x) : "memory"); }
__device__ __forceinline__ void stsm4(uint32_t a, uint32_t r0, uint32_t r1, uint32_t r2, uint32_t r3) {
    asm volatile("stmatrix.sync.aligned.m8n8.x4.shared.b16 [%0], {%1,%2,%3,%4};" :: "r"(a), "r"(r0), "r"(r1), "r"(r2), "r"(r3) : "memory");
}
#define FU(x) __float_as_uint(x)
#define UF(x) __uint_as_float(x)
__device__ __forceinline__ uint32_t wd_slot(int s) { return (uint32_t)((0x403056201000ull >> (8 * s)) & 0xff) << 10; }
__device__ __forceinline__ uint32_t h_slot(int s) { return s < 5 ? OFF_X + 2 * XBUF + s * 8192 : OFF_MB; }

template<int N> __device__ __forceinline__ void wg_rs(float (&d)[64], uint32_t a0, uint32_t a1, uint32_t a2, uint32_t a3, uint64_t db);
template<> __device__ __forceinline__ void wg_rs<128>(float (&d)[64], uint32_t a0, uint32_t a1, uint32_t a2, uint32_t a3, uint64_t db) {
  asm volatile("{.reg .pred p; setp.ne.b32 p, 1, 0; wgmma.mma_async.sync.aligned.m64n128k16.f32.bf16.bf16 {%0,%1,%2,%3,%4,%5,%6,%7,%8,%9,%10,%11,%12,%13,%14,%15,%16,%17,%18,%19,%20,%21,%22,%23,%24,%25,%26,%27,%28,%29,%30,%31,%32,%33,%34,%35,%36,%37,%38,%39,%40,%41,%42,%43,%44,%45,%46,%47,%48,%49,%50,%51,%52,%53,%54,%55,%56,%57,%58,%59,%60,%61,%62,%63}, {%64,%65,%66,%67}, %68, p, 1, 1, 0;}"
    : "+f"(d[0]),"+f"(d[1]),"+f"(d[2]),"+f"(d[3]),"+f"(d[4]),"+f"(d[5]),"+f"(d[6]),"+f"(d[7]),"+f"(d[8]),"+f"(d[9]),"+f"(d[10]),"+f"(d[11]),"+f"(d[12]),"+f"(d[13]),"+f"(d[14]),"+f"(d[15]),"+f"(d[16]),"+f"(d[17]),"+f"(d[18]),"+f"(d[19]),"+f"(d[20]),"+f"(d[21]),"+f"(d[22]),"+f"(d[23]),"+f"(d[24]),"+f"(d[25]),"+f"(d[26]),"+f"(d[27]),"+f"(d[28]),"+f"(d[29]),"+f"(d[30]),"+f"(d[31]),"+f"(d[32]),"+f"(d[33]),"+f"(d[34]),"+f"(d[35]),"+f"(d[36]),"+f"(d[37]),"+f"(d[38]),"+f"(d[39]),"+f"(d[40]),"+f"(d[41]),"+f"(d[42]),"+f"(d[43]),"+f"(d[44]),"+f"(d[45]),"+f"(d[46]),"+f"(d[47]),"+f"(d[48]),"+f"(d[49]),"+f"(d[50]),"+f"(d[51]),"+f"(d[52]),"+f"(d[53]),"+f"(d[54]),"+f"(d[55]),"+f"(d[56]),"+f"(d[57]),"+f"(d[58]),"+f"(d[59]),"+f"(d[60]),"+f"(d[61]),"+f"(d[62]),"+f"(d[63]) : "r"(a0), "r"(a1), "r"(a2), "r"(a3), "l"(db));
}
template<> __device__ __forceinline__ void wg_rs<120>(float (&d)[64], uint32_t a0, uint32_t a1, uint32_t a2, uint32_t a3, uint64_t db) {
  asm volatile("{.reg .pred p; setp.ne.b32 p, 1, 0; wgmma.mma_async.sync.aligned.m64n120k16.f32.bf16.bf16 {%0,%1,%2,%3,%4,%5,%6,%7,%8,%9,%10,%11,%12,%13,%14,%15,%16,%17,%18,%19,%20,%21,%22,%23,%24,%25,%26,%27,%28,%29,%30,%31,%32,%33,%34,%35,%36,%37,%38,%39,%40,%41,%42,%43,%44,%45,%46,%47,%48,%49,%50,%51,%52,%53,%54,%55,%56,%57,%58,%59}, {%60,%61,%62,%63}, %64, p, 1, 1, 0;}"
    : "+f"(d[0]),"+f"(d[1]),"+f"(d[2]),"+f"(d[3]),"+f"(d[4]),"+f"(d[5]),"+f"(d[6]),"+f"(d[7]),"+f"(d[8]),"+f"(d[9]),"+f"(d[10]),"+f"(d[11]),"+f"(d[12]),"+f"(d[13]),"+f"(d[14]),"+f"(d[15]),"+f"(d[16]),"+f"(d[17]),"+f"(d[18]),"+f"(d[19]),"+f"(d[20]),"+f"(d[21]),"+f"(d[22]),"+f"(d[23]),"+f"(d[24]),"+f"(d[25]),"+f"(d[26]),"+f"(d[27]),"+f"(d[28]),"+f"(d[29]),"+f"(d[30]),"+f"(d[31]),"+f"(d[32]),"+f"(d[33]),"+f"(d[34]),"+f"(d[35]),"+f"(d[36]),"+f"(d[37]),"+f"(d[38]),"+f"(d[39]),"+f"(d[40]),"+f"(d[41]),"+f"(d[42]),"+f"(d[43]),"+f"(d[44]),"+f"(d[45]),"+f"(d[46]),"+f"(d[47]),"+f"(d[48]),"+f"(d[49]),"+f"(d[50]),"+f"(d[51]),"+f"(d[52]),"+f"(d[53]),"+f"(d[54]),"+f"(d[55]),"+f"(d[56]),"+f"(d[57]),"+f"(d[58]),"+f"(d[59]) : "r"(a0), "r"(a1), "r"(a2), "r"(a3), "l"(db));
}
template<> __device__ __forceinline__ void wg_rs<112>(float (&d)[64], uint32_t a0, uint32_t a1, uint32_t a2, uint32_t a3, uint64_t db) {
  asm volatile("{.reg .pred p; setp.ne.b32 p, 1, 0; wgmma.mma_async.sync.aligned.m64n112k16.f32.bf16.bf16 {%0,%1,%2,%3,%4,%5,%6,%7,%8,%9,%10,%11,%12,%13,%14,%15,%16,%17,%18,%19,%20,%21,%22,%23,%24,%25,%26,%27,%28,%29,%30,%31,%32,%33,%34,%35,%36,%37,%38,%39,%40,%41,%42,%43,%44,%45,%46,%47,%48,%49,%50,%51,%52,%53,%54,%55}, {%56,%57,%58,%59}, %60, p, 1, 1, 0;}"
    : "+f"(d[0]),"+f"(d[1]),"+f"(d[2]),"+f"(d[3]),"+f"(d[4]),"+f"(d[5]),"+f"(d[6]),"+f"(d[7]),"+f"(d[8]),"+f"(d[9]),"+f"(d[10]),"+f"(d[11]),"+f"(d[12]),"+f"(d[13]),"+f"(d[14]),"+f"(d[15]),"+f"(d[16]),"+f"(d[17]),"+f"(d[18]),"+f"(d[19]),"+f"(d[20]),"+f"(d[21]),"+f"(d[22]),"+f"(d[23]),"+f"(d[24]),"+f"(d[25]),"+f"(d[26]),"+f"(d[27]),"+f"(d[28]),"+f"(d[29]),"+f"(d[30]),"+f"(d[31]),"+f"(d[32]),"+f"(d[33]),"+f"(d[34]),"+f"(d[35]),"+f"(d[36]),"+f"(d[37]),"+f"(d[38]),"+f"(d[39]),"+f"(d[40]),"+f"(d[41]),"+f"(d[42]),"+f"(d[43]),"+f"(d[44]),"+f"(d[45]),"+f"(d[46]),"+f"(d[47]),"+f"(d[48]),"+f"(d[49]),"+f"(d[50]),"+f"(d[51]),"+f"(d[52]),"+f"(d[53]),"+f"(d[54]),"+f"(d[55]) : "r"(a0), "r"(a1), "r"(a2), "r"(a3), "l"(db));
}
template<> __device__ __forceinline__ void wg_rs<104>(float (&d)[64], uint32_t a0, uint32_t a1, uint32_t a2, uint32_t a3, uint64_t db) {
  asm volatile("{.reg .pred p; setp.ne.b32 p, 1, 0; wgmma.mma_async.sync.aligned.m64n104k16.f32.bf16.bf16 {%0,%1,%2,%3,%4,%5,%6,%7,%8,%9,%10,%11,%12,%13,%14,%15,%16,%17,%18,%19,%20,%21,%22,%23,%24,%25,%26,%27,%28,%29,%30,%31,%32,%33,%34,%35,%36,%37,%38,%39,%40,%41,%42,%43,%44,%45,%46,%47,%48,%49,%50,%51}, {%52,%53,%54,%55}, %56, p, 1, 1, 0;}"
    : "+f"(d[0]),"+f"(d[1]),"+f"(d[2]),"+f"(d[3]),"+f"(d[4]),"+f"(d[5]),"+f"(d[6]),"+f"(d[7]),"+f"(d[8]),"+f"(d[9]),"+f"(d[10]),"+f"(d[11]),"+f"(d[12]),"+f"(d[13]),"+f"(d[14]),"+f"(d[15]),"+f"(d[16]),"+f"(d[17]),"+f"(d[18]),"+f"(d[19]),"+f"(d[20]),"+f"(d[21]),"+f"(d[22]),"+f"(d[23]),"+f"(d[24]),"+f"(d[25]),"+f"(d[26]),"+f"(d[27]),"+f"(d[28]),"+f"(d[29]),"+f"(d[30]),"+f"(d[31]),"+f"(d[32]),"+f"(d[33]),"+f"(d[34]),"+f"(d[35]),"+f"(d[36]),"+f"(d[37]),"+f"(d[38]),"+f"(d[39]),"+f"(d[40]),"+f"(d[41]),"+f"(d[42]),"+f"(d[43]),"+f"(d[44]),"+f"(d[45]),"+f"(d[46]),"+f"(d[47]),"+f"(d[48]),"+f"(d[49]),"+f"(d[50]),"+f"(d[51]) : "r"(a0), "r"(a1), "r"(a2), "r"(a3), "l"(db));
}
template<> __device__ __forceinline__ void wg_rs<96>(float (&d)[64], uint32_t a0, uint32_t a1, uint32_t a2, uint32_t a3, uint64_t db) {
  asm volatile("{.reg .pred p; setp.ne.b32 p, 1, 0; wgmma.mma_async.sync.aligned.m64n96k16.f32.bf16.bf16 {%0,%1,%2,%3,%4,%5,%6,%7,%8,%9,%10,%11,%12,%13,%14,%15,%16,%17,%18,%19,%20,%21,%22,%23,%24,%25,%26,%27,%28,%29,%30,%31,%32,%33,%34,%35,%36,%37,%38,%39,%40,%41,%42,%43,%44,%45,%46,%47}, {%48,%49,%50,%51}, %52, p, 1, 1, 0;}"
    : "+f"(d[0]),"+f"(d[1]),"+f"(d[2]),"+f"(d[3]),"+f"(d[4]),"+f"(d[5]),"+f"(d[6]),"+f"(d[7]),"+f"(d[8]),"+f"(d[9]),"+f"(d[10]),"+f"(d[11]),"+f"(d[12]),"+f"(d[13]),"+f"(d[14]),"+f"(d[15]),"+f"(d[16]),"+f"(d[17]),"+f"(d[18]),"+f"(d[19]),"+f"(d[20]),"+f"(d[21]),"+f"(d[22]),"+f"(d[23]),"+f"(d[24]),"+f"(d[25]),"+f"(d[26]),"+f"(d[27]),"+f"(d[28]),"+f"(d[29]),"+f"(d[30]),"+f"(d[31]),"+f"(d[32]),"+f"(d[33]),"+f"(d[34]),"+f"(d[35]),"+f"(d[36]),"+f"(d[37]),"+f"(d[38]),"+f"(d[39]),"+f"(d[40]),"+f"(d[41]),"+f"(d[42]),"+f"(d[43]),"+f"(d[44]),"+f"(d[45]),"+f"(d[46]),"+f"(d[47]) : "r"(a0), "r"(a1), "r"(a2), "r"(a3), "l"(db));
}
template<> __device__ __forceinline__ void wg_rs<88>(float (&d)[64], uint32_t a0, uint32_t a1, uint32_t a2, uint32_t a3, uint64_t db) {
  asm volatile("{.reg .pred p; setp.ne.b32 p, 1, 0; wgmma.mma_async.sync.aligned.m64n88k16.f32.bf16.bf16 {%0,%1,%2,%3,%4,%5,%6,%7,%8,%9,%10,%11,%12,%13,%14,%15,%16,%17,%18,%19,%20,%21,%22,%23,%24,%25,%26,%27,%28,%29,%30,%31,%32,%33,%34,%35,%36,%37,%38,%39,%40,%41,%42,%43}, {%44,%45,%46,%47}, %48, p, 1, 1, 0;}"
    : "+f"(d[0]),"+f"(d[1]),"+f"(d[2]),"+f"(d[3]),"+f"(d[4]),"+f"(d[5]),"+f"(d[6]),"+f"(d[7]),"+f"(d[8]),"+f"(d[9]),"+f"(d[10]),"+f"(d[11]),"+f"(d[12]),"+f"(d[13]),"+f"(d[14]),"+f"(d[15]),"+f"(d[16]),"+f"(d[17]),"+f"(d[18]),"+f"(d[19]),"+f"(d[20]),"+f"(d[21]),"+f"(d[22]),"+f"(d[23]),"+f"(d[24]),"+f"(d[25]),"+f"(d[26]),"+f"(d[27]),"+f"(d[28]),"+f"(d[29]),"+f"(d[30]),"+f"(d[31]),"+f"(d[32]),"+f"(d[33]),"+f"(d[34]),"+f"(d[35]),"+f"(d[36]),"+f"(d[37]),"+f"(d[38]),"+f"(d[39]),"+f"(d[40]),"+f"(d[41]),"+f"(d[42]),"+f"(d[43]) : "r"(a0), "r"(a1), "r"(a2), "r"(a3), "l"(db));
}
template<> __device__ __forceinline__ void wg_rs<80>(float (&d)[64], uint32_t a0, uint32_t a1, uint32_t a2, uint32_t a3, uint64_t db) {
  asm volatile("{.reg .pred p; setp.ne.b32 p, 1, 0; wgmma.mma_async.sync.aligned.m64n80k16.f32.bf16.bf16 {%0,%1,%2,%3,%4,%5,%6,%7,%8,%9,%10,%11,%12,%13,%14,%15,%16,%17,%18,%19,%20,%21,%22,%23,%24,%25,%26,%27,%28,%29,%30,%31,%32,%33,%34,%35,%36,%37,%38,%39}, {%40,%41,%42,%43}, %44, p, 1, 1, 0;}"
    : "+f"(d[0]),"+f"(d[1]),"+f"(d[2]),"+f"(d[3]),"+f"(d[4]),"+f"(d[5]),"+f"(d[6]),"+f"(d[7]),"+f"(d[8]),"+f"(d[9]),"+f"(d[10]),"+f"(d[11]),"+f"(d[12]),"+f"(d[13]),"+f"(d[14]),"+f"(d[15]),"+f"(d[16]),"+f"(d[17]),"+f"(d[18]),"+f"(d[19]),"+f"(d[20]),"+f"(d[21]),"+f"(d[22]),"+f"(d[23]),"+f"(d[24]),"+f"(d[25]),"+f"(d[26]),"+f"(d[27]),"+f"(d[28]),"+f"(d[29]),"+f"(d[30]),"+f"(d[31]),"+f"(d[32]),"+f"(d[33]),"+f"(d[34]),"+f"(d[35]),"+f"(d[36]),"+f"(d[37]),"+f"(d[38]),"+f"(d[39]) : "r"(a0), "r"(a1), "r"(a2), "r"(a3), "l"(db));
}
template<> __device__ __forceinline__ void wg_rs<72>(float (&d)[64], uint32_t a0, uint32_t a1, uint32_t a2, uint32_t a3, uint64_t db) {
  asm volatile("{.reg .pred p; setp.ne.b32 p, 1, 0; wgmma.mma_async.sync.aligned.m64n72k16.f32.bf16.bf16 {%0,%1,%2,%3,%4,%5,%6,%7,%8,%9,%10,%11,%12,%13,%14,%15,%16,%17,%18,%19,%20,%21,%22,%23,%24,%25,%26,%27,%28,%29,%30,%31,%32,%33,%34,%35}, {%36,%37,%38,%39}, %40, p, 1, 1, 0;}"
    : "+f"(d[0]),"+f"(d[1]),"+f"(d[2]),"+f"(d[3]),"+f"(d[4]),"+f"(d[5]),"+f"(d[6]),"+f"(d[7]),"+f"(d[8]),"+f"(d[9]),"+f"(d[10]),"+f"(d[11]),"+f"(d[12]),"+f"(d[13]),"+f"(d[14]),"+f"(d[15]),"+f"(d[16]),"+f"(d[17]),"+f"(d[18]),"+f"(d[19]),"+f"(d[20]),"+f"(d[21]),"+f"(d[22]),"+f"(d[23]),"+f"(d[24]),"+f"(d[25]),"+f"(d[26]),"+f"(d[27]),"+f"(d[28]),"+f"(d[29]),"+f"(d[30]),"+f"(d[31]),"+f"(d[32]),"+f"(d[33]),"+f"(d[34]),"+f"(d[35]) : "r"(a0), "r"(a1), "r"(a2), "r"(a3), "l"(db));
}
template<> __device__ __forceinline__ void wg_rs<64>(float (&d)[64], uint32_t a0, uint32_t a1, uint32_t a2, uint32_t a3, uint64_t db) {
  asm volatile("{.reg .pred p; setp.ne.b32 p, 1, 0; wgmma.mma_async.sync.aligned.m64n64k16.f32.bf16.bf16 {%0,%1,%2,%3,%4,%5,%6,%7,%8,%9,%10,%11,%12,%13,%14,%15,%16,%17,%18,%19,%20,%21,%22,%23,%24,%25,%26,%27,%28,%29,%30,%31}, {%32,%33,%34,%35}, %36, p, 1, 1, 0;}"
    : "+f"(d[0]),"+f"(d[1]),"+f"(d[2]),"+f"(d[3]),"+f"(d[4]),"+f"(d[5]),"+f"(d[6]),"+f"(d[7]),"+f"(d[8]),"+f"(d[9]),"+f"(d[10]),"+f"(d[11]),"+f"(d[12]),"+f"(d[13]),"+f"(d[14]),"+f"(d[15]),"+f"(d[16]),"+f"(d[17]),"+f"(d[18]),"+f"(d[19]),"+f"(d[20]),"+f"(d[21]),"+f"(d[22]),"+f"(d[23]),"+f"(d[24]),"+f"(d[25]),"+f"(d[26]),"+f"(d[27]),"+f"(d[28]),"+f"(d[29]),"+f"(d[30]),"+f"(d[31]) : "r"(a0), "r"(a1), "r"(a2), "r"(a3), "l"(db));
}
__device__ __forceinline__ void wg_rs_first(float (&d)[64], uint32_t a0, uint32_t a1, uint32_t a2, uint32_t a3, uint64_t db) {
  asm volatile("{.reg .pred p; setp.ne.b32 p, 0, 0; wgmma.mma_async.sync.aligned.m64n128k16.f32.bf16.bf16 {%0,%1,%2,%3,%4,%5,%6,%7,%8,%9,%10,%11,%12,%13,%14,%15,%16,%17,%18,%19,%20,%21,%22,%23,%24,%25,%26,%27,%28,%29,%30,%31,%32,%33,%34,%35,%36,%37,%38,%39,%40,%41,%42,%43,%44,%45,%46,%47,%48,%49,%50,%51,%52,%53,%54,%55,%56,%57,%58,%59,%60,%61,%62,%63}, {%64,%65,%66,%67}, %68, p, 1, 1, 0;}"
    : "=f"(d[0]),"=f"(d[1]),"=f"(d[2]),"=f"(d[3]),"=f"(d[4]),"=f"(d[5]),"=f"(d[6]),"=f"(d[7]),"=f"(d[8]),"=f"(d[9]),"=f"(d[10]),"=f"(d[11]),"=f"(d[12]),"=f"(d[13]),"=f"(d[14]),"=f"(d[15]),"=f"(d[16]),"=f"(d[17]),"=f"(d[18]),"=f"(d[19]),"=f"(d[20]),"=f"(d[21]),"=f"(d[22]),"=f"(d[23]),"=f"(d[24]),"=f"(d[25]),"=f"(d[26]),"=f"(d[27]),"=f"(d[28]),"=f"(d[29]),"=f"(d[30]),"=f"(d[31]),"=f"(d[32]),"=f"(d[33]),"=f"(d[34]),"=f"(d[35]),"=f"(d[36]),"=f"(d[37]),"=f"(d[38]),"=f"(d[39]),"=f"(d[40]),"=f"(d[41]),"=f"(d[42]),"=f"(d[43]),"=f"(d[44]),"=f"(d[45]),"=f"(d[46]),"=f"(d[47]),"=f"(d[48]),"=f"(d[49]),"=f"(d[50]),"=f"(d[51]),"=f"(d[52]),"=f"(d[53]),"=f"(d[54]),"=f"(d[55]),"=f"(d[56]),"=f"(d[57]),"=f"(d[58]),"=f"(d[59]),"=f"(d[60]),"=f"(d[61]),"=f"(d[62]),"=f"(d[63]) : "r"(a0), "r"(a1), "r"(a2), "r"(a3), "l"(db));
}
__device__ __forceinline__ void wg_kk176(float (&d)[88], uint64_t da, uint64_t db, int sc) {
  asm volatile("{.reg .pred p; setp.ne.b32 p, %90, 0; wgmma.mma_async.sync.aligned.m64n176k16.f32.bf16.bf16 {%0,%1,%2,%3,%4,%5,%6,%7,%8,%9,%10,%11,%12,%13,%14,%15,%16,%17,%18,%19,%20,%21,%22,%23,%24,%25,%26,%27,%28,%29,%30,%31,%32,%33,%34,%35,%36,%37,%38,%39,%40,%41,%42,%43,%44,%45,%46,%47,%48,%49,%50,%51,%52,%53,%54,%55,%56,%57,%58,%59,%60,%61,%62,%63,%64,%65,%66,%67,%68,%69,%70,%71,%72,%73,%74,%75,%76,%77,%78,%79,%80,%81,%82,%83,%84,%85,%86,%87}, %88, %89, p, 1, 1, 0, 0;}"
    : "+f"(d[0]),"+f"(d[1]),"+f"(d[2]),"+f"(d[3]),"+f"(d[4]),"+f"(d[5]),"+f"(d[6]),"+f"(d[7]),"+f"(d[8]),"+f"(d[9]),"+f"(d[10]),"+f"(d[11]),"+f"(d[12]),"+f"(d[13]),"+f"(d[14]),"+f"(d[15]),"+f"(d[16]),"+f"(d[17]),"+f"(d[18]),"+f"(d[19]),"+f"(d[20]),"+f"(d[21]),"+f"(d[22]),"+f"(d[23]),"+f"(d[24]),"+f"(d[25]),"+f"(d[26]),"+f"(d[27]),"+f"(d[28]),"+f"(d[29]),"+f"(d[30]),"+f"(d[31]),"+f"(d[32]),"+f"(d[33]),"+f"(d[34]),"+f"(d[35]),"+f"(d[36]),"+f"(d[37]),"+f"(d[38]),"+f"(d[39]),"+f"(d[40]),"+f"(d[41]),"+f"(d[42]),"+f"(d[43]),"+f"(d[44]),"+f"(d[45]),"+f"(d[46]),"+f"(d[47]),"+f"(d[48]),"+f"(d[49]),"+f"(d[50]),"+f"(d[51]),"+f"(d[52]),"+f"(d[53]),"+f"(d[54]),"+f"(d[55]),"+f"(d[56]),"+f"(d[57]),"+f"(d[58]),"+f"(d[59]),"+f"(d[60]),"+f"(d[61]),"+f"(d[62]),"+f"(d[63]),"+f"(d[64]),"+f"(d[65]),"+f"(d[66]),"+f"(d[67]),"+f"(d[68]),"+f"(d[69]),"+f"(d[70]),"+f"(d[71]),"+f"(d[72]),"+f"(d[73]),"+f"(d[74]),"+f"(d[75]),"+f"(d[76]),"+f"(d[77]),"+f"(d[78]),"+f"(d[79]),"+f"(d[80]),"+f"(d[81]),"+f"(d[82]),"+f"(d[83]),"+f"(d[84]),"+f"(d[85]),"+f"(d[86]),"+f"(d[87]) : "l"(da), "l"(db), "r"(sc));
}
__device__ __forceinline__ void wg_tt128(float (&d)[64], uint64_t da, uint64_t db, int sc) {
  asm volatile("{.reg .pred p; setp.ne.b32 p, %66, 0; wgmma.mma_async.sync.aligned.m64n128k16.f32.bf16.bf16 {%0,%1,%2,%3,%4,%5,%6,%7,%8,%9,%10,%11,%12,%13,%14,%15,%16,%17,%18,%19,%20,%21,%22,%23,%24,%25,%26,%27,%28,%29,%30,%31,%32,%33,%34,%35,%36,%37,%38,%39,%40,%41,%42,%43,%44,%45,%46,%47,%48,%49,%50,%51,%52,%53,%54,%55,%56,%57,%58,%59,%60,%61,%62,%63}, %64, %65, p, 1, 1, 1, 1;}"
    : "+f"(d[0]),"+f"(d[1]),"+f"(d[2]),"+f"(d[3]),"+f"(d[4]),"+f"(d[5]),"+f"(d[6]),"+f"(d[7]),"+f"(d[8]),"+f"(d[9]),"+f"(d[10]),"+f"(d[11]),"+f"(d[12]),"+f"(d[13]),"+f"(d[14]),"+f"(d[15]),"+f"(d[16]),"+f"(d[17]),"+f"(d[18]),"+f"(d[19]),"+f"(d[20]),"+f"(d[21]),"+f"(d[22]),"+f"(d[23]),"+f"(d[24]),"+f"(d[25]),"+f"(d[26]),"+f"(d[27]),"+f"(d[28]),"+f"(d[29]),"+f"(d[30]),"+f"(d[31]),"+f"(d[32]),"+f"(d[33]),"+f"(d[34]),"+f"(d[35]),"+f"(d[36]),"+f"(d[37]),"+f"(d[38]),"+f"(d[39]),"+f"(d[40]),"+f"(d[41]),"+f"(d[42]),"+f"(d[43]),"+f"(d[44]),"+f"(d[45]),"+f"(d[46]),"+f"(d[47]),"+f"(d[48]),"+f"(d[49]),"+f"(d[50]),"+f"(d[51]),"+f"(d[52]),"+f"(d[53]),"+f"(d[54]),"+f"(d[55]),"+f"(d[56]),"+f"(d[57]),"+f"(d[58]),"+f"(d[59]),"+f"(d[60]),"+f"(d[61]),"+f"(d[62]),"+f"(d[63]) : "l"(da), "l"(db), "r"(sc));
}
__device__ __forceinline__ void wg_tt64(float (&d)[64], uint64_t da, uint64_t db, int sc) {
  asm volatile("{.reg .pred p; setp.ne.b32 p, %34, 0; wgmma.mma_async.sync.aligned.m64n64k16.f32.bf16.bf16 {%0,%1,%2,%3,%4,%5,%6,%7,%8,%9,%10,%11,%12,%13,%14,%15,%16,%17,%18,%19,%20,%21,%22,%23,%24,%25,%26,%27,%28,%29,%30,%31}, %32, %33, p, 1, 1, 1, 1;}"
    : "+f"(d[0]),"+f"(d[1]),"+f"(d[2]),"+f"(d[3]),"+f"(d[4]),"+f"(d[5]),"+f"(d[6]),"+f"(d[7]),"+f"(d[8]),"+f"(d[9]),"+f"(d[10]),"+f"(d[11]),"+f"(d[12]),"+f"(d[13]),"+f"(d[14]),"+f"(d[15]),"+f"(d[16]),"+f"(d[17]),"+f"(d[18]),"+f"(d[19]),"+f"(d[20]),"+f"(d[21]),"+f"(d[22]),"+f"(d[23]),"+f"(d[24]),"+f"(d[25]),"+f"(d[26]),"+f"(d[27]),"+f"(d[28]),"+f"(d[29]),"+f"(d[30]),"+f"(d[31]) : "l"(da), "l"(db), "r"(sc));
}
__device__ __forceinline__ void wg_tt32(float (&d)[64], uint64_t da, uint64_t db, int sc) {
  asm volatile("{.reg .pred p; setp.ne.b32 p, %18, 0; wgmma.mma_async.sync.aligned.m64n32k16.f32.bf16.bf16 {%0,%1,%2,%3,%4,%5,%6,%7,%8,%9,%10,%11,%12,%13,%14,%15}, %16, %17, p, 1, 1, 1, 1;}"
    : "+f"(d[0]),"+f"(d[1]),"+f"(d[2]),"+f"(d[3]),"+f"(d[4]),"+f"(d[5]),"+f"(d[6]),"+f"(d[7]),"+f"(d[8]),"+f"(d[9]),"+f"(d[10]),"+f"(d[11]),"+f"(d[12]),"+f"(d[13]),"+f"(d[14]),"+f"(d[15]) : "l"(da), "l"(db), "r"(sc));
}
__device__ __forceinline__ void wg_g1(float (&d)[88], uint64_t da, uint64_t db, int sc) {
  asm volatile("{.reg .pred p; setp.ne.b32 p, %90, 0; wgmma.mma_async.sync.aligned.m64n176k16.f32.bf16.bf16 {%0,%1,%2,%3,%4,%5,%6,%7,%8,%9,%10,%11,%12,%13,%14,%15,%16,%17,%18,%19,%20,%21,%22,%23,%24,%25,%26,%27,%28,%29,%30,%31,%32,%33,%34,%35,%36,%37,%38,%39,%40,%41,%42,%43,%44,%45,%46,%47,%48,%49,%50,%51,%52,%53,%54,%55,%56,%57,%58,%59,%60,%61,%62,%63,%64,%65,%66,%67,%68,%69,%70,%71,%72,%73,%74,%75,%76,%77,%78,%79,%80,%81,%82,%83,%84,%85,%86,%87}, %88, %89, p, 1, 1, 1, 0;}"
    : "+f"(d[0]),"+f"(d[1]),"+f"(d[2]),"+f"(d[3]),"+f"(d[4]),"+f"(d[5]),"+f"(d[6]),"+f"(d[7]),"+f"(d[8]),"+f"(d[9]),"+f"(d[10]),"+f"(d[11]),"+f"(d[12]),"+f"(d[13]),"+f"(d[14]),"+f"(d[15]),"+f"(d[16]),"+f"(d[17]),"+f"(d[18]),"+f"(d[19]),"+f"(d[20]),"+f"(d[21]),"+f"(d[22]),"+f"(d[23]),"+f"(d[24]),"+f"(d[25]),"+f"(d[26]),"+f"(d[27]),"+f"(d[28]),"+f"(d[29]),"+f"(d[30]),"+f"(d[31]),"+f"(d[32]),"+f"(d[33]),"+f"(d[34]),"+f"(d[35]),"+f"(d[36]),"+f"(d[37]),"+f"(d[38]),"+f"(d[39]),"+f"(d[40]),"+f"(d[41]),"+f"(d[42]),"+f"(d[43]),"+f"(d[44]),"+f"(d[45]),"+f"(d[46]),"+f"(d[47]),"+f"(d[48]),"+f"(d[49]),"+f"(d[50]),"+f"(d[51]),"+f"(d[52]),"+f"(d[53]),"+f"(d[54]),"+f"(d[55]),"+f"(d[56]),"+f"(d[57]),"+f"(d[58]),"+f"(d[59]),"+f"(d[60]),"+f"(d[61]),"+f"(d[62]),"+f"(d[63]),"+f"(d[64]),"+f"(d[65]),"+f"(d[66]),"+f"(d[67]),"+f"(d[68]),"+f"(d[69]),"+f"(d[70]),"+f"(d[71]),"+f"(d[72]),"+f"(d[73]),"+f"(d[74]),"+f"(d[75]),"+f"(d[76]),"+f"(d[77]),"+f"(d[78]),"+f"(d[79]),"+f"(d[80]),"+f"(d[81]),"+f"(d[82]),"+f"(d[83]),"+f"(d[84]),"+f"(d[85]),"+f"(d[86]),"+f"(d[87]) : "l"(da), "l"(db), "r"(sc));
}

struct Params { const __nv_bfloat16 *x, *logA, *Aim, *Cr, *Ci, *logdt, *Dskip; };
struct Maps { CUtensorMap x[2], xo, out, wg, wu, wd, hst[2], hld; };

__device__ __forceinline__ void conv_channel(uint32_t cb, int w, int lane, uint32_t (&res)[8], uint32_t bar_free) {
    const int q = lane & 3, g = lane >> 2, gam = g >> 2;
    float acc[64];
    uint4 a[4][4];
    const uint32_t t0 = cb + CH_T + (uint32_t)(14 + 4 * w + (g & 3) + 32 * gam - 2 * q) * 80u;
    #pragma unroll
    for (int s4 = 0; s4 < 4; s4++) {
        a[s4][0] = lds128(t0 + s4 * 16);
        a[s4][1] = lds128(t0 + 16 * 80 + s4 * 16);
        a[s4][2] = lds128(t0 - 8 * 80 + s4 * 16);
        a[s4][3] = lds128(t0 + 8 * 80 + s4 * 16);
    }
    const uint32_t l0 = FU(ldsf(t0 + 64)), l1 = FU(ldsf(t0 + 16 * 80 + 64)), l2 = FU(ldsf(t0 - 8 * 80 + 64)), l3 = FU(ldsf(t0 + 8 * 80 + 64));
    const uint64_t dU = mkdesc(cb + CH_U, UPLANE, 128, 0);
    WG_FENCE();
#define CT(N, s, c) wg_rs<N>(acc, a[(s) >> 2][0].c, a[(s) >> 2][1].c, a[(s) >> 2][2].c, a[(s) >> 2][3].c, dU + 4 * (s))
    wg_rs_first(acc, a[0][0].x, a[0][1].x, a[0][2].x, a[0][3].x, dU);
    CT(128, 1, y); CT(120, 2, z); CT(120, 3, w);
    CT(112, 4, x); CT(112, 5, y); CT(104, 6, z); CT(104, 7, w);
    CT(96, 8, x);  CT(96, 9, y);  CT(88, 10, z); CT(88, 11, w);
    CT(80, 12, x); CT(80, 13, y); CT(72, 14, z); CT(72, 15, w);
#undef CT
    wg_rs<64>(acc, l0, l1, l2, l3, dU + 64);
    wg_tt64(acc, mkdesc(cb + CH_A3, 128, 512, 0), mkdesc(cb + CH_B3, 128, 256, 0), 1);
    wg_tt32(acc, mkdesc(cb + CH_A3 + 256, 128, 512, 0), mkdesc(cb + CH_B3 + 1024, 128, 256, 0), 1);
    WG_COMMIT();
    WG_WAIT(0);
    fence_acc(acc);
    if (bar_free && lane == 0) mbar_arrive(bar_free);
    const int src1 = (lane & ~3) | ((q + 1) & 3);
    float E[16][2];
    #pragma unroll
    for (int j = 0; j < 16; j++) {
        const float nxt = (j < 15) ? acc[4 * (j + 1) + 2] : 0.f;
        const float sup = (q == 0) ? nxt : acc[4 * j + 2];
        const float v = __shfl_sync(0xffffffffu, sup, src1);
        E[j][0] = acc[4 * j] + acc[4 * j + 3];
        E[j][1] = acc[4 * j + 1] + v;
    }
    const int src2 = gam ? ((lane & 12) | ((q + 3) & 3)) : (16 | (lane & 12) | ((q + 1) & 3));
    const bool c1 = gam && q != 0, c2 = gam && q == 0;
    #pragma unroll
    for (int a2 = 0; a2 < 8; a2++) {
        float y[2];
        #pragma unroll
        for (int e = 0; e < 2; e++) {
            const float sup = c1 ? E[2 * a2][e] : E[2 * a2 + 1][e];
            const float nxt = (a2 < 7) ? E[2 * a2 + 2][e] : 0.f;
            const float keep = c2 ? nxt : (c1 ? E[2 * a2 + 1][e] : E[2 * a2][e]);
            y[e] = keep + __shfl_sync(0xffffffffu, sup, src2);
        }
        res[a2] = pack2(y[1], y[0]);
    }
}

__device__ __forceinline__ void consumer(uint32_t sb, int warp, const Maps& M) {
    const int V = warp >> 2, w = warp & 3, lane = threadIdx.x & 31, q = lane & 3, g = lane >> 2;
    const int c = blockIdx.x;
    const uint32_t bars = sb + OFF_BAR, xb = sb + OFF_X + V * 2 * XBUF;
    {
        float ag[88], au[88];
        define_acc(ag); define_acc(au);
        if (V == 0) {
            sts128(xb + (w >> 1) * XBUF + 168 * 128 + (threadIdx.x & 63) * 16, 0x3f803f80u, 0x3f803f80u, 0x3f803f80u, 0x3f803f80u);
            fence_async_smem();
            bar_sync(1);
        } else mbar_wait(bars + 8 * B_GO, 0);
        #pragma unroll 1
        for (int st = 0; st < 8; st++) {
            mbar_wait(bars + 8 * (B_FULLW + (st & 3)), st >> 2);
            mbar_wait(bars + 8 * (B_FULLX + 2 * V + (st & 1)), (st >> 1) & 1);
            STAMP(40 + 8 * V + st);
            const uint64_t dG = mkdesc(sb + OFF_W + (st & 3) * 16384, 0, 1024, 1);
            const uint64_t dX = mkdesc(xb + (st & 1) * XBUF, 16, 1024, 1);
            WG_FENCE();
            #pragma unroll
            for (int k = 0; k < 4; k++) {
                wg_g1(ag, dG + k * 128, dX + k * 2, k ? 1 : st);
                wg_g1(au, dG + 512 + k * 128, dX + k * 2, k ? 1 : st);
            }
            WG_COMMIT();
            WG_WAIT(1);
            if (lane == 0 && st > 0) {
                mbar_arrive(bars + 8 * (B_EMPTYW + ((st - 1) & 3)));
                mbar_arrive(bars + 8 * (B_EMPTYX + 2 * V + ((st - 1) & 1)));
                if (warp < 4 && st == 1) mbar_arrive(bars + 8 * B_GO);
            }
        }
        WG_WAIT(0);
        fence_acc(ag); fence_acc(au);
        if (lane == 0) { mbar_arrive(bars + 8 * (B_EMPTYW + 3)); mbar_arrive(bars + 8 * (B_EMPTYX + 2 * V + 1)); }
        STAMP(8 * V + 1);
        {
            if (V == 0) {
                const float cv = (q & 2) ? ((q & 1) ? au[86] : au[84]) : ((q & 1) ? ag[86] : ag[84]), hi = bf_round(cv);
                sts128(sb + OFF_CSUM + (16 * w + g + 8 * (q & 1) + 32 * (q & 2)) * 16, pack2(hi, cv - hi), 0, 0, 0);
                fence_async_smem();
                mbar_arrive(bars + 8 * B_CS);
            }
            mbar_wait(bars + 8 * B_CS, 0);
            mbar_wait(bars + 8 * B_STATS, 0);
            const uint64_t dM = mkdesc(sb + OFF_MB + V * 168 * 16, 0, 128, 0), dC = mkdesc(sb + OFF_CSUM, 0, 128, 0);
            WG_FENCE();
            wg_kk176(ag, dC, dM, 1);
            wg_kk176(au, dC + 64, dM, 1);
            WG_COMMIT();
            mbar_wait(bars + 8 * (B_EMPTYX + 2 * V), 1);
            WG_WAIT(0);
            fence_acc(ag); fence_acc(au);
        }
        const uint32_t hs = xb + (2 * w + ((lane >> 3) & 1)) * (2688 + 128 * V) + (lane >> 4) * 128 + (lane & 7) * 16;
        const uint32_t hr = sb + OFF_HR + (168 * V + 2 * q) * 4;
        #pragma unroll
        for (int j = 0; j < 22; j += 2) {
            uint32_t o[4];
            #pragma unroll
            for (int jj = 0; jj < 2; jj++) {
                const uint2 rv = lds64(hr + (j + jj) * 32);
                float hv[4];
                #pragma unroll
                for (int i = 0; i < 4; i++) {
                    const float gh = ag[4 * (j + jj) + i] * UF((i & 1) ? rv.y : rv.x);
                    const float p = gh * au[4 * (j + jj) + i];
                    hv[i] = fmaf(p, tanh_fast(gh), p);
                }
                o[2 * jj] = pack2(hv[0], hv[1]); o[2 * jj + 1] = pack2(hv[2], hv[3]);
            }
            uint32_t ad = hs + j * 128;
            if (j == 20 && V == 0 && lane >= 16) ad = xb + 21504 + (lane & 7) * 16;
            stsm4(ad, o[0], o[1], o[2], o[3]);
        }
        fence_async_smem();
        mbar_arrive(bars + 8 * (B_EPI + V));
        STAMP(8 * V + 2);
    }
    if (c >= 128) return;
    {
        mbar_wait(bars + 8 * B_CONV, 0);
        uint32_t r0[8], r1[8];
        #pragma unroll
        for (int i = 0; i < 8; i++) asm volatile("" : "=r"(r1[i]));
        #pragma unroll 1
        for (int e = 0; e < 2; e++) {
            #pragma unroll
            for (int i = 0; i < 8; i++) r0[i] = r1[i];
            conv_channel(sb + OFF_CONV + (2 * V + e) * CH_STRIDE, w, lane, r1, (V + e == 0) ? bars + 8 * B_CH0 : 0);
            if (e == 0) STAMP(8 * V + 3);
        }
        const int gam = g >> 2, qq = gam ? ((q + 3) & 3) : q;
        uint2* sp = g_S + (2 * c + V) * 1024 + (63 - 4 * gam - qq) * 16 + 4 * w + (g & 3);
        #pragma unroll
        for (int a2 = 0; a2 < 8; a2++) sp[-a2 * 128] = make_uint2(r0[a2], r1[a2]);
        mbar_arrive(bars + 8 * (B_SIG + V));
        STAMP(8 * V + 4);
    }
    if (V == 1) return;
    {
        const int tau = c >> 2, dg = c & 3;
        const uint32_t row = 8 * (w & 1) + 32 * (w >> 1);
        float acc[64];
        define_acc(acc);
        uint2 sv[16];
        #pragma unroll
        for (int i = 0; i < 16; i++) asm volatile("" : "=r"(sv[i].x), "=r"(sv[i].y));
        const float rr0 = __ldcg(&g_stats[64 * tau + row + g].y), rr1 = __ldcg(&g_stats[64 * tau + row + g + 16].y);
        int sd = 0; uint32_t pd = 0;
        mbar_wait(bars + 8 * B_FULLD, 0);
        STAMP(5);
        uint64_t dB = mkdesc(sb + wd_slot(0), 8192, 1024, 1), dA = mkdesc(sb + h_slot(0), 1024, 128, 0);
        #pragma unroll 1
        for (int st = 0; st < 21; st++) {
            WG_FENCE();
            wg_tt128(acc, dA, dB, st);
            wg_tt128(acc, dA + 128, dB + 128, 1);
            wg_tt128(acc, dA + 256, dB + 256, 1);
            wg_tt128(acc, dA + 384, dB + 384, 1);
            WG_COMMIT();
            const uint32_t rel = bars + 8 * (B_EMPTYD + (sd ? sd - 1 : 5));
            if (++sd == 6) { sd = 0; pd ^= 1; }
            mbar_wait(bars + 8 * (B_FULLD + sd), pd);
            dB = mkdesc(sb + wd_slot(sd), 8192, 1024, 1); dA = mkdesc(sb + h_slot(sd), 1024, 128, 0);
            if (st == 14) {
                mbar_wait(bars + 8 * B_S, 0);
                const uint2* sp = g_S + (dg * 64 + q) * 1024 + (2 * tau) * 16 + (row >> 1) + 4 * (w & 1) + g;
                #pragma unroll
                for (int j = 0; j < 16; j++)
                    asm volatile("ld.global.cg.v2.b32 {%0,%1}, [%2];" : "=r"(sv[j].x), "=r"(sv[j].y) : "l"(sp + j * 4096));
            }
            WG_WAIT(1);
            if (lane == 0 && st > 0) mbar_arrive(rel);
        }
        WG_FENCE();
        wg_tt128(acc, dA, dB, 1);
        wg_tt128(acc, dA + 128, dB + 128, 1);
        WG_COMMIT();
        WG_WAIT(0);
        fence_acc(acc);
        STAMP(6);
        mbar_wait(bars + 8 * B_XO, 0);
        const uint32_t xo = sb + OFF_CONV + (row + (lane & 7) + 16 * ((lane >> 3) & 1)) * 128;
        #pragma unroll
        for (int j = 0; j < 16; j += 2) {
            const uint32_t ad = xo + (j >> 3) * 8192 + ((((j & 7) + (lane >> 4)) ^ (lane & 7)) << 4);
            uint32_t xr[4];
            asm volatile("ldmatrix.sync.aligned.m8n8.x4.shared.b16 {%0,%1,%2,%3}, [%4];" : "=r"(xr[0]), "=r"(xr[1]), "=r"(xr[2]), "=r"(xr[3]) : "r"(ad));
            #pragma unroll
            for (int i = 0; i < 4; i++) {
                const int jj = j + (i >> 1), hh = i & 1;
                const float f0 = acc[4 * jj + 2 * hh] * (hh ? rr1 : rr0), f1 = acc[4 * jj + 2 * hh + 1] * (hh ? rr1 : rr0);
                const uint32_t G = pack2(fmaf(f0, tanh_fast(f0), f0), fmaf(f1, tanh_fast(f1), f1));
                const uint32_t s2 = __byte_perm(sv[jj].x, sv[jj].y, hh ? 0x7632 : 0x5410);
                asm("fma.rn.bf16x2 %0, %1, %2, %0;" : "+r"(xr[i]) : "r"(s2), "r"(G));
            }
            stsm4(ad, xr[0], xr[1], xr[2], xr[3]);
        }
        fence_async_smem();
        bar_sync(1);
        if (w == 0 && elect_one()) {
            #pragma unroll
            for (int i = 0; i < 2; i++)
                asm volatile("cp.async.bulk.tensor.2d.global.shared::cta.bulk_group [%0, {%2, %3}], [%1];"
                    :: "l"(&M.out), "r"(sb + OFF_CONV + i * 8192), "r"(dg * 128 + 64 * i), "r"(tau * 64) : "memory");
            asm volatile("cp.async.bulk.commit_group; cp.async.bulk.wait_group.read 0;" ::: "memory");
        }
        STAMP(7);
    }
}

__device__ __forceinline__ float2 cexp_p(float re2, float im, float p) {
    float sn, cs;
    const float mag = ex2(re2 * p), th = im * p;
    asm("sin.approx.ftz.f32 %0, %1;" : "=f"(sn) : "f"(th));
    asm("cos.approx.ftz.f32 %0, %1;" : "=f"(cs) : "f"(th));
    return make_float2(mag * cs, mag * sn);
}
__device__ __forceinline__ uint32_t cmul_conj_pack(float2 a, float2 b) { return pack2(fmaf(a.x, b.x, -a.y * b.y), fmaf(-a.x, b.y, -a.y * b.x)); }
__device__ __forceinline__ float shfl(float v, int src) { float r; asm volatile("shfl.sync.idx.b32 %0, %1, %2, 31, -1;" : "=f"(r) : "f"(v), "r"(src)); return r; }
__device__ __forceinline__ float2 cmul(float2 a, float2 b) { return make_float2(fmaf(a.x, b.x, -a.y * b.y), fmaf(a.x, b.y, a.y * b.x)); }
__device__ __forceinline__ float2 csqr(float2 a) { const float t = a.x * a.y; return make_float2(fmaf(a.x, a.x, -a.y * a.y), t + t); }
__device__ __forceinline__ void mma16816(float (&d)[4], const uint32_t (&a)[4], uint32_t b0, uint32_t b1) {
    asm volatile("mma.sync.aligned.m16n8k16.row.col.f32.bf16.bf16.f32 {%0,%1,%2,%3}, {%4,%5,%6,%7}, {%8,%9}, {%0,%1,%2,%3};"
        : "+f"(d[0]), "+f"(d[1]), "+f"(d[2]), "+f"(d[3]) : "r"(a[0]), "r"(a[1]), "r"(a[2]), "r"(a[3]), "r"(b0), "r"(b1));
}

__device__ __forceinline__ void aux_role(uint32_t sb, int w, const Params& P) {
    const int tid = threadIdx.x & 127, lane = tid & 31, q = lane & 3, g = lane >> 2;
    const int c = blockIdx.x, tg = c / 22;
    const uint32_t bars = sb + OFF_BAR;
    if (c < 128) {
        const uint32_t cb = sb + OFF_CONV + w * CH_STRIDE;
        const uint32_t sF = cb + CH_A3, sP = cb + CH_A3 + 2064;
        const int tokb = 32 * (c >> 1) + 8 * (c & 1) + 16;
        if (elect_one()) {
            mbar_expect(bars + 8 * B_LNX, 4096);
            #pragma unroll
            for (int i = 0; i < 4; i++)
                bulk_load(sb + OFF_CONV + (w + 4 * i) * LNROW, P.x + (tokb + w + 4 * (i & 1) - 8 * (i & 2)) * DM, 1024, bars + 8 * B_LNX);
        }
        const int d = 4 * c + w;
        const uint2 la = *(const uint2*)(P.logA + d * 128 + 4 * lane), ai = *(const uint2*)(P.Aim + d * 128 + 4 * lane);
        const uint2 cr = *(const uint2*)(P.Cr + d * 128 + 4 * lane), ci = *(const uint2*)(P.Ci + d * 128 + 4 * lane);
        const float ldt = __bfloat162float(P.logdt[d]), dsk = __bfloat162float(P.Dskip[d]);
        mbar_wait(bars + 8 * B_LNX, 0);
        STAMP(34);
        #pragma unroll 1
        for (int r = w; r < 16; r += 4) {
            const uint32_t ra = sb + OFF_CONV + r * LNROW + lane * 16;
            uint32_t v[8];
            *(uint4*)&v[0] = lds128(ra); *(uint4*)&v[4] = lds128(ra + 512);
            const float pv = bf_lo(__shfl_sync(0xffffffffu, v[0], 0));
            float s = 0.f, a = 0.f;
            #pragma unroll
            for (int k = 0; k < 8; k++) { const float t0 = bf_lo(v[k]) - pv, t1 = bf_hi(v[k]) - pv; s += t0 + t1; a = fmaf(t0, t0, a); a = fmaf(t1, t1, a); }
            #pragma unroll
            for (int o = 16; o; o >>= 1) { s += __shfl_xor_sync(0xffffffffu, s, o); a += __shfl_xor_sync(0xffffffffu, a, o); }
            s *= 1.f / DM;
            const float m = pv + s, var = fmaxf(fmaf(-s, s, a * (1.f / DM)), 0.f);
            float sd, ri;
            asm("sqrt.approx.f32 %0, %1;" : "=f"(sd) : "f"(bf_round(bf_round(var) + 1e-5f)));
            asm("rcp.approx.f32 %0, %1;" : "=f"(ri) : "f"(bf_round(sd)));
            const uint32_t m2 = pack2(m, m);
            if (lane == 0) g_stats[tokb + (r & 7) - 2 * (r & 8)] = make_float2(bf_hi(m2), 0.5f * ri);
            #pragma unroll
            for (int k = 0; k < 8; k++) {
                uint32_t dv; asm("sub.rn.bf16x2 %0, %1, %2;" : "=r"(dv) : "r"(v[k]), "r"(m2));
                v[k] = pack2(bf_lo(dv) * ri, bf_hi(dv) * ri);
            }
            sts128(ra, v[0], v[1], v[2], v[3]); sts128(ra + 512, v[4], v[5], v[6], v[7]);
        }
        bar_sync(2);
        {
            uint32_t ad = sb + OFF_CONV + (4 * ((lane & 7) >> 1) + (lane & 1) + 2 * ((lane >> 3) & 1)) * LNROW + (16 * w + (lane >> 4)) * 16;
            uint2* dst = (uint2*)(g_xnT + (128 * w + g) * 256 + (c & 1) * 128 + (126 - 2 * (c >> 1))) + q;
            #pragma unroll
            for (int i = 0; i < 8; i++, ad += 32, dst += 16 * 512) {
                uint32_t r0, r1, r2, r3;
                asm volatile("ldmatrix.sync.aligned.m8n8.x4.trans.shared.b16 {%0,%1,%2,%3}, [%4];" : "=r"(r0), "=r"(r1), "=r"(r2), "=r"(r3) : "r"(ad));
                dst[0] = make_uint2(r0, r1); dst[8 * 512] = make_uint2(r2, r3);
            }
        }
        mbar_arrive(bars + 8 * B_LN);
        bar_sync(2);
        STAMP(16);
        {
            const float dt = bf_round(ex2(ldt * 1.4426950408889634f));
            #pragma unroll
            for (int i = 0; i < 4; i++) {
                const uint32_t l2 = (i & 2) ? la.y : la.x, a2 = (i & 2) ? ai.y : ai.x, r2 = (i & 2) ? cr.y : cr.x, i2 = (i & 2) ? ci.y : ci.x;
                const float re = bf_round(ex2(((i & 1) ? bf_hi(l2) : bf_lo(l2)) * 1.4426950408889634f)) * dt;
                const float im = ((i & 1) ? bf_hi(a2) : bf_lo(a2)) * dt;
                sts128(sP + (4 * lane + i) * 16, FU(re * -1.4426950408889634f), FU(im),
                       FU(((i & 1) ? bf_hi(r2) : bf_lo(r2)) * (dt + dt)), FU(((i & 1) ? bf_hi(i2) : bf_lo(i2)) * (dt + dt)));
            }
        }
        __syncwarp();
        float dacc[2][3][4];
        #pragma unroll
        for (int i = 0; i < 24; i++) (&dacc[0][0][0])[i] = 0.f;
        const float p0 = (float)g;
        const float p1 = (float)((g < 4) ? 256 + 2 * g : 512 + 4 * (g & 1) + 128 * (g & 2));
        const float p2 = (g < 4) ? fmaf(p0, 256.f, 1032.f) : 1024.f;
        #pragma unroll 1
        for (int ks = 0; ks < 16; ks++) {
            uint32_t a0[4], a1[4], b[3][2];
            #pragma unroll
            for (int mh = 0; mh < 2; mh++) {
                const uint4 pv = lds128(sP + q * 16 + ks * 128 + mh * 64);
                const float re2 = UF(pv.x), im = UF(pv.y);
                const float2 C = make_float2(UF(pv.z), UF(pv.w));
                const float2 E0 = cexp_p(re2, im, p0), R0 = csqr(csqr(csqr(E0)));
                const float2 z64 = csqr(make_float2(shfl(R0.x, 16 + q), shfl(R0.y, 16 + q))), z128 = csqr(z64);
                const float2 R1 = cmul(R0, z64), R2 = cmul(R0, z128), R3 = cmul(R1, z128);
                a0[2 * mh] = pack2(R0.x, R0.y); a0[2 * mh + 1] = pack2(R1.x, R1.y);
                a1[2 * mh] = pack2(R2.x, R2.y); a1[2 * mh + 1] = pack2(R3.x, R3.y);
                b[0][mh] = cmul_conj_pack(C, E0); b[1][mh] = cmul_conj_pack(C, cexp_p(re2, im, p1)); b[2][mh] = cmul_conj_pack(C, cexp_p(re2, im, p2));
            }
            #pragma unroll
            for (int t = 0; t < 3; t++) { mma16816(dacc[0][t], a0, b[t][0], b[t][1]); mma16816(dacc[1][t], a1, b[t][0], b[t][1]); }
        }
        STAMP(18);
        const uint32_t sG = cb + CH_G;
        if (lane < 16) sts128(((lane & 8) ? cb + CH_U + 2048 + (lane & 4) * (UPLANE / 4) : sG + 128 + (lane & 4) * 48) + (lane & 3) * 16, 0, 0, 0, 0);
        {
            const uint32_t f0 = sF + (8 * g + 2 * q) * 4, f1 = sF + ((q < 2) ? 256 + 4 * g + 2 * q : 256 + 2 * g + 64 * q) * 4, st1 = (q < 2) ? 128 : 64;
            const uint32_t ga = sG + ((g & 1) ? 0 : 192) + (63 - (g >> 1) - 32 * q) * 2;
            #pragma unroll
            for (int i = 0; i < 4; i++) {
                const int mu = i >> 1, hh = i & 1;
                sts64(f0 + i * 256, FU(dacc[mu][0][2 * hh]), FU(dacc[mu][0][2 * hh + 1]));
                sts64(f1 + i * st1, FU(dacc[mu][1][2 * hh]), FU(dacc[mu][1][2 * hh + 1]));
                const uint32_t pk = pack2(dacc[mu][2][2 * hh], dacc[mu][2][2 * hh + 1]);
                if (q < 2) { sts16(ga - 8 * i, pk & 0xffff); sts16(ga - 8 * i - 32, pk >> 16); }
            }
            if (lane == 2) stsf(sF + 2048, dacc[0][2][0]);
        }
        __syncwarp();
        #pragma unroll 1
        for (int pass = 0; pass < 3; pass++) {
            const int rw = lane - 1 + 31 * pass;
            const int u = min(rw, 77) - 14;
            const uint32_t f0 = sF + u * 4, f1 = sF + (128 + ((u + ((u >> 1) & 1)) >> 1)) * 4, f2 = sF + (256 + ((u + 1 + ((u >> 2) & 1)) >> 2)) * 4;
            float kv[17];
            kv[0] = ldsf(u < 0 ? sF : f0); if (u < 0) kv[0] = 0.f; if (u == 0) kv[0] += dsk;
            #pragma unroll
            for (int s = 1; s < 4; s++) kv[s] = ldsf(f0 + s * 256);
            kv[4] = ldsf(u < 0 ? f0 + 1024 : f1 + 512);
            #pragma unroll
            for (int s = 5; s < 8; s++) kv[s] = ldsf(f1 + s * 128);
            kv[8] = ldsf(u < 0 ? f1 + 1024 : f2 + 512);
            #pragma unroll
            for (int s = 9; s < 16; s++) kv[s] = ldsf(f2 + s * 64);
            kv[16] = ldsf(u < 0 ? f2 + 1024 : sF + 2048); if (u > 4) kv[16] = 0.f;
            uint32_t o[17];
            #pragma unroll
            for (int s = 0; s < 17; s++) o[s] = pack2(kv[s], __shfl_up_sync(0xffffffffu, kv[s], 1));
            if (lane > 0 && rw < 78) {
                const uint32_t ta = cb + CH_T + rw * 80;
                #pragma unroll
                for (int s4 = 0; s4 < 4; s4++) sts128(ta + s4 * 16, o[4 * s4], o[4 * s4 + 1], o[4 * s4 + 2], o[4 * s4 + 3]);
                stsf(ta + 64, UF(o[16]));
            }
        }
        #pragma unroll 1
        for (int un = lane; un < 128; un += 32) {
            const uint32_t ga = sG + ((un >> 3) & 1) * 192 + (un >> 4) * 16 + (un & 7) * 8;
            const uint2 x0 = lds64(ga), x1 = lds64(ga + 8);
            sts128(cb + CH_B3 + un * 16, x0.x, x0.y, x1.x, x1.y);
        }
    } else mbar_arrive(bars + 8 * B_LN);
    STAMP(19);
    if (w == 0 && elect_one()) {
        flag_wait(F_A, NCTA);
        if (c < 128) {
            fence_async();
            mbar_expect(bars + 8 * B_U, 8 * 2048);
            #pragma unroll 1
            for (int i = 0; i < 8; i++)
                bulk_load(sb + OFF_CONV + (i >> 1) * CH_STRIDE + CH_U + (i & 1) * UPLANE, g_xnT + 4 * c * 256 + i * 128, 2048, bars + 8 * B_U);
        } else exit_count();
    }
    bar_sync(2);
    {
        float2 sv[3];
        #pragma unroll
        for (int i = 0; i < 3; i++) sv[i] = __ldcg(g_stats + min(TOKG * tg + tid + 128 * i, SEQ - 1));
        #pragma unroll
        for (int i = 0; i < 3; i++) if (i < 2 || tid < TOKG - 256) {
            sts128(sb + OFF_MB + (tid + 128 * i) * 16, pack2(-0.5f * sv[i].x, -0.5f * sv[i].x), 0, 0, 0);
            stsf(sb + OFF_HR + (tid + 128 * i) * 4, sv[i].y);
        }
    }
    fence_async_smem();
    mbar_arrive(bars + 8 * B_STATS);
    STAMP(20);
    if (c >= 128) return;
    mbar_wait(bars + 8 * B_U, 0);
    {
        const int kap = (lane >> 4) * 8 + ((lane >> 1) & 7), gam = lane & 1, hh = w >> 1, wp = w & 1;
        uint32_t ua = sb + OFF_CONV + CH_U + wp * UPLANE + (127 - 4 * kap - 2 * gam - hh) * 16;
        uint32_t ub = sb + OFF_CONV + CH_U + (wp ^ 1) * UPLANE + (128 - wp - 4 * kap - 2 * gam - hh) * 16;
        uint32_t ad = sb + OFF_CONV + CH_A3 + (4 * wp + hh) * 512 + (kap >> 3) * 256 + (kap & 7) * 16 + gam * 8;
        #pragma unroll 1
        for (int ch = 0; ch < 4; ch++, ua += CH_STRIDE, ub += CH_STRIDE, ad += CH_STRIDE) {
            float p[24];
            const uint2 r0 = lds64(ub + 24), r3 = lds64(ua);
            uint32_t r[8];
            *(uint4*)&r[0] = lds128(ua + 16); *(uint4*)&r[4] = lds128(ub);
            p[0] = 0.f;
            p[1] = bf_lo(r0.x); p[2] = p[1] + bf_hi(r0.x); p[3] = p[2] + bf_lo(r0.y); p[4] = p[3] + bf_hi(r0.y);
            #pragma unroll
            for (int i = 0; i < 8; i++) { p[5 + 2 * i] = p[4 + 2 * i] + bf_lo(r[i]); p[6 + 2 * i] = p[5 + 2 * i] + bf_hi(r[i]); }
            p[21] = p[20] + bf_lo(r3.x); p[22] = p[21] + bf_hi(r3.x); p[23] = p[22] + bf_lo(r3.y);
            #pragma unroll
            for (int i = 0; i < 8; i += 4) {
                sts64(ad + i * 256, pack2(p[i + 9] - p[i], p[i + 10] - p[i + 1]), pack2(p[i + 11] - p[i + 2], p[i + 12] - p[i + 3]));
                sts64(ad + i * 256 + 128, pack2(p[i + 16] - p[i + 9], p[i + 17] - p[i + 10]), pack2(p[i + 18] - p[i + 11], p[i + 19] - p[i + 12]));
            }
        }
    }
    fence_async_smem();
    mbar_arrive(bars + 8 * B_CONV);
    STAMP(21);
}

__global__ void __launch_bounds__(512, 1)
fused_kernel(const __grid_constant__ Maps M, const __grid_constant__ Params P) {
    extern __shared__ __align__(1024) uint8_t smem_raw[];
    const uint32_t sb = smem_u32(smem_raw);
    const uint32_t bars = sb + OFF_BAR;
    const int warp = __shfl_sync(0xffffffffu, threadIdx.x >> 5, 0);
    if (elect_one()) {
        if (warp == 0) STAMP(24);
        if (warp < 10) asm volatile("prefetch.tensormap [%0];" :: "l"(&M.x[0] + warp) : "memory");
        #pragma unroll
        for (int k = 0; k < 3; k++) {
            const int i = 3 * warp + k;
            const uint32_t cnt = i >= B_STATS ? 128 : ((0xf0ull >> i) & 1) ? 8 : ((0x3f0000ull >> i) & 1) ? 2 : ((0x1c0fc0f000ull >> i) & 1) ? 4 : 1;
            asm volatile("mbarrier.init.shared::cta.b64 [%0], %1;" :: "r"(bars + 8 * i), "r"(cnt) : "memory");
        }
        asm volatile("fence.mbarrier_init.release.cluster;" ::: "memory");
        if (sb & 1023) __trap();
    }
    __syncthreads();
    if (warp < 8) {
        asm volatile("setmaxnreg.inc.sync.aligned.u32 208;");
        consumer(sb, warp, M);
    } else if (warp < 12) {
        asm volatile("setmaxnreg.dec.sync.aligned.u32 72;");
        STAMP(32);
        aux_role(sb, warp - 8, P);
    } else {
        asm volatile("setmaxnreg.dec.sync.aligned.u32 24;");
        const int c = blockIdx.x, tg = c / 22, fb = c - 22 * tg, tau = c >> 2, dg = c & 3;
        if (elect_one()) {
            if (warp == 12) {
                #pragma unroll 1
                for (int st = 0; st < 8; st++) {
                    const uint32_t s = st & 3, fb_ = bars + 8 * (B_FULLW + s);
                    mbar_wait(bars + 8 * (B_EMPTYW + s), (st >> 2) ^ 1);
                    mbar_expect(fb_, 16384);
                    tma2d(sb + OFF_W + s * 16384, &M.wg, 64 * fb, 64 * st, fb_);
                    tma2d(sb + OFF_W + s * 16384 + 8192, &M.wu, 64 * fb, 64 * st, fb_);
                    if (st == 0) STAMP(31);
                }
                if (c < 128) {
                    int sd = 0; uint32_t pe = 1;
                    #pragma unroll 1
                    for (int st = 0; st < 22; st++) {
                        if (st < 6) mbar_wait(bars + 8 * (uint32_t)((0x1f070d060504ull >> (8 * st)) & 0xff), st < 5);
                        else mbar_wait(bars + 8 * (B_EMPTYD + sd), pe);
                        const uint32_t da = sb + wd_slot(sd), fb_ = bars + 8 * (B_FULLD + sd);
                        mbar_expect(fb_, 16384);
                        tma2d(da, &M.wd, 128 * dg, 64 * st, fb_);
                        tma2d(da + 8192, &M.wd, 128 * dg + 64, 64 * st, fb_);
                        if (++sd == 6) { sd = 0; pe ^= 1; }
                    }
                }
            } else if (warp < 15) {
                const int V = warp - 13;
                #pragma unroll 1
                for (int st = 0; st < 8; st++) {
                    const uint32_t s = 2 * V + (st & 1);
                    mbar_wait(bars + 8 * (B_EMPTYX + s), ((st >> 1) & 1) ^ 1);
                    mbar_expect(bars + 8 * (B_FULLX + s), (168 + 8 * V) * 128);
                    tma2d(sb + OFF_X + s * XBUF, &M.x[V], 64 * st, TOKG * tg + 168 * V, bars + 8 * (B_FULLX + s));
                }
                if (c < 128) {
                    if (V == 0) {
                        mbar_wait(bars + 8 * (B_STG + 1), 0);
                        #pragma unroll 1
                        for (int o = 8 * tau; o < 8 * tau + 8; o += 7) flag_wait(F_H + 2 * (o / 43) + ((o % 43) >= 21), 22);
                        fence_async();
                        mbar_arrive(bars + 8 * B_HF);
                        STAMP(25);
                        int sh = 0; uint32_t pe = 1;
                        #pragma unroll 1
                        for (int st = 0; st < 22; st++) {
                            const uint32_t fb_ = bars + 8 * (B_FULLD + sh);
                            mbar_wait(bars + 8 * (B_EMPTYD + sh), pe);
                            mbar_expect(fb_, 8192);
                            asm volatile("cp.async.bulk.tensor.5d.shared::cluster.global.mbarrier::complete_tx::bytes [%0], [%1, {%3, %3, %3, %4, %5}], [%2];"
                                :: "r"(sb + h_slot(sh)), "l"(&M.hld), "r"(fb_), "r"(0), "r"(2 * tau), "r"(8 * st) : "memory");
                            if (++sh == 6) { sh = 0; pe ^= 1; }
                        }
                    } else {
                        mbar_wait(bars + 8 * B_CH0, 0);
                        mbar_expect(bars + 8 * B_XO, 16384);
                        tma2d(sb + OFF_CONV, &M.xo, 128 * dg, 64 * tau, bars + 8 * B_XO);
                        tma2d(sb + OFF_CONV + 8192, &M.xo, 128 * dg + 64, 64 * tau, bars + 8 * B_XO);
                        flag_wait(F_S + dg, 64);
                        STAMP(26);
                        mbar_arrive(bars + 8 * B_S);
                        mbar_wait(bars + 8 * B_HF, 0);
                        exit_count();
                    }
                }
            } else {
                mbar_wait(bars + 8 * B_LN, 0);
                flag_signal(F_A);
                #pragma unroll 1
                for (int V = 0; V < 2; V++) {
                    mbar_wait(bars + 8 * (B_EPI + V), 0);
                    asm volatile("cp.async.bulk.tensor.3d.global.shared::cta.bulk_group [%0, {%2, %3, %4}], [%1];"
                        :: "l"(&M.hst[V]), "r"(sb + OFF_X + V * 2 * XBUF), "r"(0), "r"(43 * tg + 21 * V), "r"(8 * fb) : "memory");
                    asm volatile("cp.async.bulk.commit_group; cp.async.bulk.wait_group 0;" ::: "memory");
                    mbar_arrive(bars + 8 * (B_STG + V));
                    flag_signal(F_H + 2 * tg + V);
                }
                if (c < 128) {
                    #pragma unroll 1
                    for (int V = 0; V < 2; V++) { mbar_wait(bars + 8 * (B_SIG + V), 0); flag_signal(F_S + (c >> 5)); }
                }
            }
        }
    }
}

typedef CUresult (*EncodeFn)(CUtensorMap*, CUtensorMapDataType, cuuint32_t, void*, const cuuint64_t*, const cuuint64_t*, const cuuint32_t*,
                             const cuuint32_t*, CUtensorMapInterleave, CUtensorMapSwizzle, CUtensorMapL2promotion, CUtensorMapFloatOOBfill);

void make_map(EncodeFn enc, CUtensorMap* m, const void* ptr, int rank, const cuuint64_t* dims, const cuuint64_t* strides, const cuuint32_t* box, bool swz) {
    const cuuint32_t es[5] = {1, 1, 1, 1, 1};
    enc(m, CU_TENSOR_MAP_DATA_TYPE_BFLOAT16, rank, (void*)ptr, dims, strides, box, es, CU_TENSOR_MAP_INTERLEAVE_NONE,
        swz ? CU_TENSOR_MAP_SWIZZLE_128B : CU_TENSOR_MAP_SWIZZLE_NONE, CU_TENSOR_MAP_L2_PROMOTION_L2_128B, CU_TENSOR_MAP_FLOAT_OOB_FILL_NONE);
}
void make_map2(EncodeFn enc, CUtensorMap* m, const void* ptr, cuuint64_t inner, cuuint64_t outer, cuuint32_t rows) {
    const cuuint64_t dims[2] = {inner, outer}, strides[1] = {inner * 2};
    const cuuint32_t box[2] = {64, rows};
    make_map(enc, m, ptr, 2, dims, strides, box, true);
}

}

extern "C" void kernel_launch(void* const* d_in, const int* in_sizes, int n_in, void* d_out, int out_size) {
    (void)in_sizes; (void)n_in; (void)out_size;
    static EncodeFn enc = nullptr;
    static void* hptr = nullptr;
    if (!enc) {
        cudaDriverEntryPointQueryResult qr;
        cudaGetDriverEntryPoint("cuTensorMapEncodeTiled", (void**)&enc, cudaEnableDefault, &qr);
        cudaFuncSetAttribute(fused_kernel, cudaFuncAttributeMaxDynamicSharedMemorySize, SMEM_BYTES);
        cudaGetSymbolAddress(&hptr, g_H);
    }
    Params P;
    P.x = (const __nv_bfloat16*)d_in[0]; P.logA = (const __nv_bfloat16*)d_in[1]; P.Aim = (const __nv_bfloat16*)d_in[2];
    P.Cr = (const __nv_bfloat16*)d_in[3]; P.Ci = (const __nv_bfloat16*)d_in[4]; P.logdt = (const __nv_bfloat16*)d_in[5];
    P.Dskip = (const __nv_bfloat16*)d_in[6];
    Maps M;
    make_map2(enc, &M.x[0], d_in[0], DM, SEQ, 168); make_map2(enc, &M.x[1], d_in[0], DM, SEQ, 176);
    make_map2(enc, &M.xo, d_in[0], DM, SEQ, 64);    make_map2(enc, &M.out, d_out, DM, SEQ, 64);
    make_map2(enc, &M.wg, d_in[8], FF, DM, 64);     make_map2(enc, &M.wu, d_in[9], FF, DM, 64);
    make_map2(enc, &M.wd, d_in[10], DM, FF, 64);
    for (int v = 0; v < 2; v++) {
        const cuuint64_t dims[3] = {64, 256, 172}, strides[2] = {128, 32768};
        const cuuint32_t box[3] = {64, (cuuint32_t)(21 + v), 8};
        make_map(enc, &M.hst[v], hptr, 3, dims, strides, box, false);
    }
    {
        const cuuint64_t dims[5] = {64, 2, 2, 64, 172}, strides[4] = {256, 128, 512, 32768};
        const cuuint32_t box[5] = {64, 2, 2, 2, 8};
        make_map(enc, &M.hld, hptr, 5, dims, strides, box, false);
    }
    fused_kernel<<<NCTA, 512, SMEM_BYTES>>>(M, P);
}
```

```cpp
#include <cuda_runtime.h>
#include <cuda_bf16.h>
#include <cuda.h>
#include <stdint.h>

#define PROF 0

namespace {

constexpr int SEQ = 2048, DM = 512, FF = 1376;
constexpr int NCTA = 132;
constexpr int TOKG = 344;

constexpr uint32_t OFF_W = 0;
constexpr uint32_t XBUF = 22528;
constexpr uint32_t OFF_X = 65536;
constexpr uint32_t OFF_CONV = 155648;
constexpr uint32_t CH_STRIDE = 16640;
constexpr uint32_t CH_T = 0;
constexpr uint32_t CH_A3 = 6272;
constexpr uint32_t CH_B3 = 10368;
constexpr uint32_t CH_U = 12416;
constexpr uint32_t CH_G = CH_A3 + 2064;
constexpr uint32_t UPLANE = 2112;
constexpr uint32_t LNROW = 1040;
constexpr uint32_t OFF_MB = 222208;
constexpr uint32_t OFF_HR = 227712;
constexpr uint32_t OFF_CSUM = 229120;
constexpr uint32_t OFF_BAR = 231168;
constexpr uint32_t SMEM_BYTES = 231680;

enum {
    B_FULLW = 0, B_EMPTYW = 4, B_FULLX = 8, B_EMPTYX = 12, B_FULLD = 16, B_EMPTYD = 22,
    B_U = 28, B_XO = 29, B_S = 30, B_STG = 31, B_HF = 33, B_STATS = 34,
    B_LNX = 35, B_GO = 36, B_CH0 = 37,
    B_CONV = 38, B_LN = 39, B_CS = 40, B_EPI = 41, B_SIG = 43,
    B_COUNT = 45
};
enum { F_A = 0, F_H = 1, F_S = 13, F_EXIT = 17, F_COUNT = 18 };

__device__ uint4 g_xnT[DM * 256];
__device__ uint4 g_mb[6 * TOKG];
__device__ float g_hr[6 * TOKG];
__device__ uint4 g_H[172 * 256 * 8];
__device__ uint2 g_S[256 * 1024];
__device__ unsigned g_flags[F_COUNT * 32];
#define STAMP(i) do {} while (0)

__device__ __forceinline__ uint32_t smem_u32(const void* p) { return (uint32_t)__cvta_generic_to_shared(p); }
__device__ __forceinline__ void mbar_expect(uint32_t bar, uint32_t bytes) { asm volatile("mbarrier.arrive.expect_tx.shared::cta.b64 _, [%0], %1;" :: "r"(bar), "r"(bytes) : "memory"); }
__device__ __forceinline__ void mbar_arrive(uint32_t bar) { asm volatile("mbarrier.arrive.shared::cta.b64 _, [%0];" :: "r"(bar) : "memory"); }
__device__ __forceinline__ void mbar_wait(uint32_t bar, uint32_t parity) {
    asm volatile("{.reg .pred p; .reg .u32 n; mov.u32 n, 0x20000;\n"
                 "LW: mbarrier.try_wait.parity.shared::cta.b64 p, [%0], %1;\n"
                 "sub.u32 n, n, 1; setp.eq.or.u32 p, n, 0, p; @!p bra LW;}" :: "r"(bar), "r"(parity) : "memory");
}
__device__ __forceinline__ bool elect_one() { uint32_t p; asm volatile("{.reg .pred P; elect.sync _|P, 0xffffffff; selp.u32 %0, 1, 0, P;}" : "=r"(p)); return p; }
__device__ __forceinline__ void tma2d(uint32_t dst, const CUtensorMap* m, int c0, int c1, uint32_t bar) {
    asm volatile("cp.async.bulk.tensor.2d.shared::cluster.global.mbarrier::complete_tx::bytes [%0], [%1, {%3, %4}], [%2];"
        :: "r"(dst), "l"(m), "r"(bar), "r"(c0), "r"(c1) : "memory");
}
__device__ __forceinline__ void bulk_load(uint32_t dst, const void* src, uint32_t bytes, uint32_t bar) {
    asm volatile("cp.async.bulk.shared::cluster.global.mbarrier::complete_tx::bytes [%0], [%1], %2, [%3];" :: "r"(dst), "l"(src), "r"(bytes), "r"(bar) : "memory");
}
__device__ __forceinline__ void fence_async() { asm volatile("fence.proxy.async;" ::: "memory"); }
__device__ __forceinline__ void fence_async_smem() { asm volatile("fence.proxy.async.shared::cta;" ::: "memory"); }
__device__ __forceinline__ void flag_wait(int f, unsigned target) {
    asm volatile("{.reg .pred p; .reg .u32 n, v; mov.u32 n, 0x40000;\n"
                 "LF: ld.acquire.gpu.global.u32 v, [%0]; setp.ge.u32 p, v, %1; @p bra LD;\n"
                 "nanosleep.u32 20; sub.u32 n, n, 1; setp.ne.u32 p, n, 0; @p bra LF; trap;\nLD: }"
                 :: "l"(g_flags + f * 32), "r"(target) : "memory");
}
__device__ __forceinline__ void flag_signal(int f) {
    asm volatile("fence.acq_rel.gpu; red.relaxed.gpu.global.add.u32 [%0], 1;" :: "l"(g_flags + f * 32) : "memory");
}
__device__ __forceinline__ void exit_count() {
    if (atomicAdd(g_flags + F_EXIT * 32, 1u) == NCTA - 1) {
        #pragma unroll 1
        for (int i = 0; i < F_COUNT; i++) g_flags[i * 32] = 0;
    }
}
__device__ __forceinline__ void bar_sync(int id) { asm volatile("bar.sync %0, 128;" :: "r"(id) : "memory"); }
__device__ __forceinline__ uint64_t mkdesc(uint32_t addr, uint32_t lbo, uint32_t sbo, uint32_t swz) {
    return (uint64_t)((addr >> 4) | ((lbo >> 4) << 16)) | ((uint64_t)((sbo >> 4) | (swz << 30)) << 32);
}
#define WG_FENCE() asm volatile("wgmma.fence.sync.aligned;" ::: "memory")
#define WG_COMMIT() asm volatile("wgmma.commit_group.sync.aligned;" ::: "memory")
#define WG_WAIT(n) asm volatile("wgmma.wait_group.sync.aligned " #n ";" ::: "memory")
template <int N> __device__ __forceinline__ void fence_acc(float (&d)[N]) {
    #pragma unroll
    for (int i = 0; i < N; i++) asm volatile("" : "+f"(d[i]) :: "memory");
}
template <int N> __device__ __forceinline__ void define_acc(float (&d)[N]) {
    #pragma unroll
    for (int i = 0; i < N; i++) asm volatile("" : "=f"(d[i]));
}
__device__ __forceinline__ uint32_t pack2(float lo, float hi) { uint32_t r; asm("cvt.rn.bf16x2.f32 %0, %1, %2;" : "=r"(r) : "f"(hi), "f"(lo)); return r; }
__device__ __forceinline__ float bf_lo(uint32_t v) { return __uint_as_float(v << 16); }
__device__ __forceinline__ float bf_hi(uint32_t v) { return __uint_as_float(v & 0xffff0000u); }
__device__ __forceinline__ float bf_round(float v) { return bf_hi(pack2(0.f, v)); }
__device__ __forceinline__ float tanh_fast(float v) { float r; asm("tanh.approx.f32 %0, %1;" : "=f"(r) : "f"(v)); return r; }
__device__ __forceinline__ float ex2(float v) { float r; asm("ex2.approx.ftz.f32 %0, %1;" : "=f"(r) : "f"(v)); return r; }
__device__ __forceinline__ uint4 lds128(uint32_t a) { uint4 v; asm volatile("ld.shared.v4.b32 {%0,%1,%2,%3}, [%4];" : "=r"(v.x), "=r"(v.y), "=r"(v.z), "=r"(v.w) : "r"(a)); return v; }
__device__ __forceinline__ uint2 lds64(uint32_t a) { uint2 v; asm volatile("ld.shared.v2.b32 {%0,%1}, [%2];" : "=r"(v.x), "=r"(v.y) : "r"(a)); return v; }
__device__ __forceinline__ float ldsf(uint32_t a) { float v; asm volatile("ld.shared.f32 %0, [%1];" : "=f"(v) : "r"(a)); return v; }
__device__ __forceinline__ void sts128(uint32_t a, uint32_t x, uint32_t y, uint32_t z, uint32_t w) { asm volatile("st.shared.v4.b32 [%0], {%1,%2,%3,%4};" :: "r"(a), "r"(x), "r"(y), "r"(z), "r"(w) : "memory"); }
__device__ __forceinline__ void sts64(uint32_t a, uint32_t x, uint32_t y) { asm volatile("st.shared.v2.b32 [%0], {%1,%2};" :: "r"(a), "r"(x), "r"(y) : "memory"); }
__device__ __forceinline__ void stsf(uint32_t a, float x) { asm volatile("st.shared.f32 [%0], %1;" :: "r"(a), "f"(x) : "memory"); }
__device__ __forceinline__ void sts16(uint32_t a, uint32_t x) { asm volatile("st.shared.b16 [%0], %1;" :: "r"(a), "h"((unsigned short)x) : "memory"); }
__device__ __forceinline__ void stsm4(uint32_t a, uint32_t r0, uint32_t r1, uint32_t r2, uint32_t r3) {
    asm volatile("stmatrix.sync.aligned.m8n8.x4.shared.b16 [%0], {%1,%2,%3,%4};" :: "r"(a), "r"(r0), "r"(r1), "r"(r2), "r"(r3) : "memory");
}
#define FU(x) __float_as_uint(x)
#define UF(x) __uint_as_float(x)
__device__ __forceinline__ uint32_t wd_slot(int s) { return (uint32_t)((0x403056201000ull >> (8 * s)) & 0xff) << 10; }
__device__ __forceinline__ uint32_t h_slot(int s) { return s < 5 ? OFF_X + 2 * XBUF + s * 8192 : OFF_MB; }

template<int N> __device__ __forceinline__ void wg_rs(float (&d)[64], uint32_t a0, uint32_t a1, uint32_t a2, uint32_t a3, uint64_t db);
template<> __device__ __forceinline__ void wg_rs<128>(float (&d)[64], uint32_t a0, uint32_t a1, uint32_t a2, uint32_t a3, uint64_t db) {
  asm volatile("{.reg .pred p; setp.ne.b32 p, 1, 0; wgmma.mma_async.sync.aligned.m64n128k16.f32.bf16.bf16 {%0,%1,%2,%3,%4,%5,%6,%7,%8,%9,%10,%11,%12,%13,%14,%15,%16,%17,%18,%19,%20,%21,%22,%23,%24,%25,%26,%27,%28,%29,%30,%31,%32,%33,%34,%35,%36,%37,%38,%39,%40,%41,%42,%43,%44,%45,%46,%47,%48,%49,%50,%51,%52,%53,%54,%55,%56,%57,%58,%59,%60,%61,%62,%63}, {%64,%65,%66,%67}, %68, p, 1, 1, 0;}"
    : "+f"(d[0]),"+f"(d[1]),"+f"(d[2]),"+f"(d[3]),"+f"(d[4]),"+f"(d[5]),"+f"(d[6]),"+f"(d[7]),"+f"(d[8]),"+f"(d[9]),"+f"(d[10]),"+f"(d[11]),"+f"(d[12]),"+f"(d[13]),"+f"(d[14]),"+f"(d[15]),"+f"(d[16]),"+f"(d[17]),"+f"(d[18]),"+f"(d[19]),"+f"(d[20]),"+f"(d[21]),"+f"(d[22]),"+f"(d[23]),"+f"(d[24]),"+f"(d[25]),"+f"(d[26]),"+f"(d[27]),"+f"(d[28]),"+f"(d[29]),"+f"(d[30]),"+f"(d[31]),"+f"(d[32]),"+f"(d[33]),"+f"(d[34]),"+f"(d[35]),"+f"(d[36]),"+f"(d[37]),"+f"(d[38]),"+f"(d[39]),"+f"(d[40]),"+f"(d[41]),"+f"(d[42]),"+f"(d[43]),"+f"(d[44]),"+f"(d[45]),"+f"(d[46]),"+f"(d[47]),"+f"(d[48]),"+f"(d[49]),"+f"(d[50]),"+f"(d[51]),"+f"(d[52]),"+f"(d[53]),"+f"(d[54]),"+f"(d[55]),"+f"(d[56]),"+f"(d[57]),"+f"(d[58]),"+f"(d[59]),"+f"(d[60]),"+f"(d[61]),"+f"(d[62]),"+f"(d[63]) : "r"(a0), "r"(a1), "r"(a2), "r"(a3), "l"(db));
}
template<> __device__ __forceinline__ void wg_rs<120>(float (&d)[64], uint32_t a0, uint32_t a1, uint32_t a2, uint32_t a3, uint64_t db) {
  asm volatile("{.reg .pred p; setp.ne.b32 p, 1, 0; wgmma.mma_async.sync.aligned.m64n120k16.f32.bf16.bf16 {%0,%1,%2,%3,%4,%5,%6,%7,%8,%9,%10,%11,%12,%13,%14,%15,%16,%17,%18,%19,%20,%21,%22,%23,%24,%25,%26,%27,%28,%29,%30,%31,%32,%33,%34,%35,%36,%37,%38,%39,%40,%41,%42,%43,%44,%45,%46,%47,%48,%49,%50,%51,%52,%53,%54,%55,%56,%57,%58,%59}, {%60,%61,%62,%63}, %64, p, 1, 1, 0;}"
    : "+f"(d[0]),"+f"(d[1]),"+f"(d[2]),"+f"(d[3]),"+f"(d[4]),"+f"(d[5]),"+f"(d[6]),"+f"(d[7]),"+f"(d[8]),"+f"(d[9]),"+f"(d[10]),"+f"(d[11]),"+f"(d[12]),"+f"(d[13]),"+f"(d[14]),"+f"(d[15]),"+f"(d[16]),"+f"(d[17]),"+f"(d[18]),"+f"(d[19]),"+f"(d[20]),"+f"(d[21]),"+f"(d[22]),"+f"(d[23]),"+f"(d[24]),"+f"(d[25]),"+f"(d[26]),"+f"(d[27]),"+f"(d[28]),"+f"(d[29]),"+f"(d[30]),"+f"(d[31]),"+f"(d[32]),"+f"(d[33]),"+f"(d[34]),"+f"(d[35]),"+f"(d[36]),"+f"(d[37]),"+f"(d[38]),"+f"(d[39]),"+f"(d[40]),"+f"(d[41]),"+f"(d[42]),"+f"(d[43]),"+f"(d[44]),"+f"(d[45]),"+f"(d[46]),"+f"(d[47]),"+f"(d[48]),"+f"(d[49]),"+f"(d[50]),"+f"(d[51]),"+f"(d[52]),"+f"(d[53]),"+f"(d[54]),"+f"(d[55]),"+f"(d[56]),"+f"(d[57]),"+f"(d[58]),"+f"(d[59]) : "r"(a0), "r"(a1), "r"(a2), "r"(a3), "l"(db));
}
template<> __device__ __forceinline__ void wg_rs<112>(float (&d)[64], uint32_t a0, uint32_t a1, uint32_t a2, uint32_t a3, uint64_t db) {
  asm volatile("{.reg .pred p; setp.ne.b32 p, 1, 0; wgmma.mma_async.sync.aligned.m64n112k16.f32.bf16.bf16 {%0,%1,%2,%3,%4,%5,%6,%7,%8,%9,%10,%11,%12,%13,%14,%15,%16,%17,%18,%19,%20,%21,%22,%23,%24,%25,%26,%27,%28,%29,%30,%31,%32,%33,%34,%35,%36,%37,%38,%39,%40,%41,%42,%43,%44,%45,%46,%47,%48,%49,%50,%51,%52,%53,%54,%55}, {%56,%57,%58,%59}, %60, p, 1, 1, 0;}"
    : "+f"(d[0]),"+f"(d[1]),"+f"(d[2]),"+f"(d[3]),"+f"(d[4]),"+f"(d[5]),"+f"(d[6]),"+f"(d[7]),"+f"(d[8]),"+f"(d[9]),"+f"(d[10]),"+f"(d[11]),"+f"(d[12]),"+f"(d[13]),"+f"(d[14]),"+f"(d[15]),"+f"(d[16]),"+f"(d[17]),"+f"(d[18]),"+f"(d[19]),"+f"(d[20]),"+f"(d[21]),"+f"(d[22]),"+f"(d[23]),"+f"(d[24]),"+f"(d[25]),"+f"(d[26]),"+f"(d[27]),"+f"(d[28]),"+f"(d[29]),"+f"(d[30]),"+f"(d[31]),"+f"(d[32]),"+f"(d[33]),"+f"(d[34]),"+f"(d[35]),"+f"(d[36]),"+f"(d[37]),"+f"(d[38]),"+f"(d[39]),"+f"(d[40]),"+f"(d[41]),"+f"(d[42]),"+f"(d[43]),"+f"(d[44]),"+f"(d[45]),"+f"(d[46]),"+f"(d[47]),"+f"(d[48]),"+f"(d[49]),"+f"(d[50]),"+f"(d[51]),"+f"(d[52]),"+f"(d[53]),"+f"(d[54]),"+f"(d[55]) : "r"(a0), "r"(a1), "r"(a2), "r"(a3), "l"(db));
}
template<> __device__ __forceinline__ void wg_rs<104>(float (&d)[64], uint32_t a0, uint32_t a1, uint32_t a2, uint32_t a3, uint64_t db) {
  asm volatile("{.reg .pred p; setp.ne.b32 p, 1, 0; wgmma.mma_async.sync.aligned.m64n104k16.f32.bf16.bf16 {%0,%1,%2,%3,%4,%5,%6,%7,%8,%9,%10,%11,%12,%13,%14,%15,%16,%17,%18,%19,%20,%21,%22,%23,%24,%25,%26,%27,%28,%29,%30,%31,%32,%33,%34,%35,%36,%37,%38,%39,%40,%41,%42,%43,%44,%45,%46,%47,%48,%49,%50,%51}, {%52,%53,%54,%55}, %56, p, 1, 1, 0;}"
    : "+f"(d[0]),"+f"(d[1]),"+f"(d[2]),"+f"(d[3]),"+f"(d[4]),"+f"(d[5]),"+f"(d[6]),"+f"(d[7]),"+f"(d[8]),"+f"(d[9]),"+f"(d[10]),"+f"(d[11]),"+f"(d[12]),"+f"(d[13]),"+f"(d[14]),"+f"(d[15]),"+f"(d[16]),"+f"(d[17]),"+f"(d[18]),"+f"(d[19]),"+f"(d[20]),"+f"(d[21]),"+f"(d[22]),"+f"(d[23]),"+f"(d[24]),"+f"(d[25]),"+f"(d[26]),"+f"(d[27]),"+f"(d[28]),"+f"(d[29]),"+f"(d[30]),"+f"(d[31]),"+f"(d[32]),"+f"(d[33]),"+f"(d[34]),"+f"(d[35]),"+f"(d[36]),"+f"(d[37]),"+f"(d[38]),"+f"(d[39]),"+f"(d[40]),"+f"(d[41]),"+f"(d[42]),"+f"(d[43]),"+f"(d[44]),"+f"(d[45]),"+f"(d[46]),"+f"(d[47]),"+f"(d[48]),"+f"(d[49]),"+f"(d[50]),"+f"(d[51]) : "r"(a0), "r"(a1), "r"(a2), "r"(a3), "l"(db));
}
template<> __device__ __forceinline__ void wg_rs<96>(float (&d)[64], uint32_t a0, uint32_t a1, uint32_t a2, uint32_t a3, uint64_t db) {
  asm volatile("{.reg .pred p; setp.ne.b32 p, 1, 0; wgmma.mma_async.sync.aligned.m64n96k16.f32.bf16.bf16 {%0,%1,%2,%3,%4,%5,%6,%7,%8,%9,%10,%11,%12,%13,%14,%15,%16,%17,%18,%19,%20,%21,%22,%23,%24,%25,%26,%27,%28,%29,%30,%31,%32,%33,%34,%35,%36,%37,%38,%39,%40,%41,%42,%43,%44,%45,%46,%47}, {%48,%49,%50,%51}, %52, p, 1, 1, 0;}"
    : "+f"(d[0]),"+f"(d[1]),"+f"(d[2]),"+f"(d[3]),"+f"(d[4]),"+f"(d[5]),"+f"(d[6]),"+f"(d[7]),"+f"(d[8]),"+f"(d[9]),"+f"(d[10]),"+f"(d[11]),"+f"(d[12]),"+f"(d[13]),"+f"(d[14]),"+f"(d[15]),"+f"(d[16]),"+f"(d[17]),"+f"(d[18]),"+f"(d[19]),"+f"(d[20]),"+f"(d[21]),"+f"(d[22]),"+f"(d[23]),"+f"(d[24]),"+f"(d[25]),"+f"(d[26]),"+f"(d[27]),"+f"(d[28]),"+f"(d[29]),"+f"(d[30]),"+f"(d[31]),"+f"(d[32]),"+f"(d[33]),"+f"(d[34]),"+f"(d[35]),"+f"(d[36]),"+f"(d[37]),"+f"(d[38]),"+f"(d[39]),"+f"(d[40]),"+f"(d[41]),"+f"(d[42]),"+f"(d[43]),"+f"(d[44]),"+f"(d[45]),"+f"(d[46]),"+f"(d[47]) : "r"(a0), "r"(a1), "r"(a2), "r"(a3), "l"(db));
}
template<> __device__ __forceinline__ void wg_rs<88>(float (&d)[64], uint32_t a0, uint32_t a1, uint32_t a2, uint32_t a3, uint64_t db) {
  asm volatile("{.reg .pred p; setp.ne.b32 p, 1, 0; wgmma.mma_async.sync.aligned.m64n88k16.f32.bf16.bf16 {%0,%1,%2,%3,%4,%5,%6,%7,%8,%9,%10,%11,%12,%13,%14,%15,%16,%17,%18,%19,%20,%21,%22,%23,%24,%25,%26,%27,%28,%29,%30,%31,%32,%33,%34,%35,%36,%37,%38,%39,%40,%41,%42,%43}, {%44,%45,%46,%47}, %48, p, 1, 1, 0;}"
    : "+f"(d[0]),"+f"(d[1]),"+f"(d[2]),"+f"(d[3]),"+f"(d[4]),"+f"(d[5]),"+f"(d[6]),"+f"(d[7]),"+f"(d[8]),"+f"(d[9]),"+f"(d[10]),"+f"(d[11]),"+f"(d[12]),"+f"(d[13]),"+f"(d[14]),"+f"(d[15]),"+f"(d[16]),"+f"(d[17]),"+f"(d[18]),"+f"(d[19]),"+f"(d[20]),"+f"(d[21]),"+f"(d[22]),"+f"(d[23]),"+f"(d[24]),"+f"(d[25]),"+f"(d[26]),"+f"(d[27]),"+f"(d[28]),"+f"(d[29]),"+f"(d[30]),"+f"(d[31]),"+f"(d[32]),"+f"(d[33]),"+f"(d[34]),"+f"(d[35]),"+f"(d[36]),"+f"(d[37]),"+f"(d[38]),"+f"(d[39]),"+f"(d[40]),"+f"(d[41]),"+f"(d[42]),"+f"(d[43]) : "r"(a0), "r"(a1), "r"(a2), "r"(a3), "l"(db));
}
template<> __device__ __forceinline__ void wg_rs<80>(float (&d)[64], uint32_t a0, uint32_t a1, uint32_t a2, uint32_t a3, uint64_t db) {
  asm volatile("{.reg .pred p; setp.ne.b32 p, 1, 0; wgmma.mma_async.sync.aligned.m64n80k16.f32.bf16.bf16 {%0,%1,%2,%3,%4,%5,%6,%7,%8,%9,%10,%11,%12,%13,%14,%15,%16,%17,%18,%19,%20,%21,%22,%23,%24,%25,%26,%27,%28,%29,%30,%31,%32,%33,%34,%35,%36,%37,%38,%39}, {%40,%41,%42,%43}, %44, p, 1, 1, 0;}"
    : "+f"(d[0]),"+f"(d[1]),"+f"(d[2]),"+f"(d[3]),"+f"(d[4]),"+f"(d[5]),"+f"(d[6]),"+f"(d[7]),"+f"(d[8]),"+f"(d[9]),"+f"(d[10]),"+f"(d[11]),"+f"(d[12]),"+f"(d[13]),"+f"(d[14]),"+f"(d[15]),"+f"(d[16]),"+f"(d[17]),"+f"(d[18]),"+f"(d[19]),"+f"(d[20]),"+f"(d[21]),"+f"(d[22]),"+f"(d[23]),"+f"(d[24]),"+f"(d[25]),"+f"(d[26]),"+f"(d[27]),"+f"(d[28]),"+f"(d[29]),"+f"(d[30]),"+f"(d[31]),"+f"(d[32]),"+f"(d[33]),"+f"(d[34]),"+f"(d[35]),"+f"(d[36]),"+f"(d[37]),"+f"(d[38]),"+f"(d[39]) : "r"(a0), "r"(a1), "r"(a2), "r"(a3), "l"(db));
}
template<> __device__ __forceinline__ void wg_rs<72>(float (&d)[64], uint32_t a0, uint32_t a1, uint32_t a2, uint32_t a3, uint64_t db) {
  asm volatile("{.reg .pred p; setp.ne.b32 p, 1, 0; wgmma.mma_async.sync.aligned.m64n72k16.f32.bf16.bf16 {%0,%1,%2,%3,%4,%5,%6,%7,%8,%9,%10,%11,%12,%13,%14,%15,%16,%17,%18,%19,%20,%21,%22,%23,%24,%25,%26,%27,%28,%29,%30,%31,%32,%33,%34,%35}, {%36,%37,%38,%39}, %40, p, 1, 1, 0;}"
    : "+f"(d[0]),"+f"(d[1]),"+f"(d[2]),"+f"(d[3]),"+f"(d[4]),"+f"(d[5]),"+f"(d[6]),"+f"(d[7]),"+f"(d[8]),"+f"(d[9]),"+f"(d[10]),"+f"(d[11]),"+f"(d[12]),"+f"(d[13]),"+f"(d[14]),"+f"(d[15]),"+f"(d[16]),"+f"(d[17]),"+f"(d[18]),"+f"(d[19]),"+f"(d[20]),"+f"(d[21]),"+f"(d[22]),"+f"(d[23]),"+f"(d[24]),"+f"(d[25]),"+f"(d[26]),"+f"(d[27]),"+f"(d[28]),"+f"(d[29]),"+f"(d[30]),"+f"(d[31]),"+f"(d[32]),"+f"(d[33]),"+f"(d[34]),"+f"(d[35]) : "r"(a0), "r"(a1), "r"(a2), "r"(a3), "l"(db));
}
template<> __device__ __forceinline__ void wg_rs<64>(float (&d)[64], uint32_t a0, uint32_t a1, uint32_t a2, uint32_t a3, uint64_t db) {
  asm volatile("{.reg .pred p; setp.ne.b32 p, 1, 0; wgmma.mma_async.sync.aligned.m64n64k16.f32.bf16.bf16 {%0,%1,%2,%3,%4,%5,%6,%7,%8,%9,%10,%11,%12,%13,%14,%15,%16,%17,%18,%19,%20,%21,%22,%23,%24,%25,%26,%27,%28,%29,%30,%31}, {%32,%33,%34,%35}, %36, p, 1, 1, 0;}"
    : "+f"(d[0]),"+f"(d[1]),"+f"(d[2]),"+f"(d[3]),"+f"(d[4]),"+f"(d[5]),"+f"(d[6]),"+f"(d[7]),"+f"(d[8]),"+f"(d[9]),"+f"(d[10]),"+f"(d[11]),"+f"(d[12]),"+f"(d[13]),"+f"(d[14]),"+f"(d[15]),"+f"(d[16]),"+f"(d[17]),"+f"(d[18]),"+f"(d[19]),"+f"(d[20]),"+f"(d[21]),"+f"(d[22]),"+f"(d[23]),"+f"(d[24]),"+f"(d[25]),"+f"(d[26]),"+f"(d[27]),"+f"(d[28]),"+f"(d[29]),"+f"(d[30]),"+f"(d[31]) : "r"(a0), "r"(a1), "r"(a2), "r"(a3), "l"(db));
}
__device__ __forceinline__ void wg_rs_first(float (&d)[64], uint32_t a0, uint32_t a1, uint32_t a2, uint32_t a3, uint64_t db) {
  asm volatile("{.reg .pred p; setp.ne.b32 p, 0, 0; wgmma.mma_async.sync.aligned.m64n128k16.f32.bf16.bf16 {%0,%1,%2,%3,%4,%5,%6,%7,%8,%9,%10,%11,%12,%13,%14,%15,%16,%17,%18,%19,%20,%21,%22,%23,%24,%25,%26,%27,%28,%29,%30,%31,%32,%33,%34,%35,%36,%37,%38,%39,%40,%41,%42,%43,%44,%45,%46,%47,%48,%49,%50,%51,%52,%53,%54,%55,%56,%57,%58,%59,%60,%61,%62,%63}, {%64,%65,%66,%67}, %68, p, 1, 1, 0;}"
    : "=f"(d[0]),"=f"(d[1]),"=f"(d[2]),"=f"(d[3]),"=f"(d[4]),"=f"(d[5]),"=f"(d[6]),"=f"(d[7]),"=f"(d[8]),"=f"(d[9]),"=f"(d[10]),"=f"(d[11]),"=f"(d[12]),"=f"(d[13]),"=f"(d[14]),"=f"(d[15]),"=f"(d[16]),"=f"(d[17]),"=f"(d[18]),"=f"(d[19]),"=f"(d[20]),"=f"(d[21]),"=f"(d[22]),"=f"(d[23]),"=f"(d[24]),"=f"(d[25]),"=f"(d[26]),"=f"(d[27]),"=f"(d[28]),"=f"(d[29]),"=f"(d[30]),"=f"(d[31]),"=f"(d[32]),"=f"(d[33]),"=f"(d[34]),"=f"(d[35]),"=f"(d[36]),"=f"(d[37]),"=f"(d[38]),"=f"(d[39]),"=f"(d[40]),"=f"(d[41]),"=f"(d[42]),"=f"(d[43]),"=f"(d[44]),"=f"(d[45]),"=f"(d[46]),"=f"(d[47]),"=f"(d[48]),"=f"(d[49]),"=f"(d[50]),"=f"(d[51]),"=f"(d[52]),"=f"(d[53]),"=f"(d[54]),"=f"(d[55]),"=f"(d[56]),"=f"(d[57]),"=f"(d[58]),"=f"(d[59]),"=f"(d[60]),"=f"(d[61]),"=f"(d[62]),"=f"(d[63]) : "r"(a0), "r"(a1), "r"(a2), "r"(a3), "l"(db));
}
__device__ __forceinline__ void wg_kk176(float (&d)[88], uint64_t da, uint64_t db, int sc) {
  asm volatile("{.reg .pred p; setp.ne.b32 p, %90, 0; wgmma.mma_async.sync.aligned.m64n176k16.f32.bf16.bf16 {%0,%1,%2,%3,%4,%5,%6,%7,%8,%9,%10,%11,%12,%13,%14,%15,%16,%17,%18,%19,%20,%21,%22,%23,%24,%25,%26,%27,%28,%29,%30,%31,%32,%33,%34,%35,%36,%37,%38,%39,%40,%41,%42,%43,%44,%45,%46,%47,%48,%49,%50,%51,%52,%53,%54,%55,%56,%57,%58,%59,%60,%61,%62,%63,%64,%65,%66,%67,%68,%69,%70,%71,%72,%73,%74,%75,%76,%77,%78,%79,%80,%81,%82,%83,%84,%85,%86,%87}, %88, %89, p, 1, 1, 0, 0;}"
    : "+f"(d[0]),"+f"(d[1]),"+f"(d[2]),"+f"(d[3]),"+f"(d[4]),"+f"(d[5]),"+f"(d[6]),"+f"(d[7]),"+f"(d[8]),"+f"(d[9]),"+f"(d[10]),"+f"(d[11]),"+f"(d[12]),"+f"(d[13]),"+f"(d[14]),"+f"(d[15]),"+f"(d[16]),"+f"(d[17]),"+f"(d[18]),"+f"(d[19]),"+f"(d[20]),"+f"(d[21]),"+f"(d[22]),"+f"(d[23]),"+f"(d[24]),"+f"(d[25]),"+f"(d[26]),"+f"(d[27]),"+f"(d[28]),"+f"(d[29]),"+f"(d[30]),"+f"(d[31]),"+f"(d[32]),"+f"(d[33]),"+f"(d[34]),"+f"(d[35]),"+f"(d[36]),"+f"(d[37]),"+f"(d[38]),"+f"(d[39]),"+f"(d[40]),"+f"(d[41]),"+f"(d[42]),"+f"(d[43]),"+f"(d[44]),"+f"(d[45]),"+f"(d[46]),"+f"(d[47]),"+f"(d[48]),"+f"(d[49]),"+f"(d[50]),"+f"(d[51]),"+f"(d[52]),"+f"(d[53]),"+f"(d[54]),"+f"(d[55]),"+f"(d[56]),"+f"(d[57]),"+f"(d[58]),"+f"(d[59]),"+f"(d[60]),"+f"(d[61]),"+f"(d[62]),"+f"(d[63]),"+f"(d[64]),"+f"(d[65]),"+f"(d[66]),"+f"(d[67]),"+f"(d[68]),"+f"(d[69]),"+f"(d[70]),"+f"(d[71]),"+f"(d[72]),"+f"(d[73]),"+f"(d[74]),"+f"(d[75]),"+f"(d[76]),"+f"(d[77]),"+f"(d[78]),"+f"(d[79]),"+f"(d[80]),"+f"(d[81]),"+f"(d[82]),"+f"(d[83]),"+f"(d[84]),"+f"(d[85]),"+f"(d[86]),"+f"(d[87]) : "l"(da), "l"(db), "r"(sc));
}
__device__ __forceinline__ void wg_tt128(float (&d)[64], uint64_t da, uint64_t db, int sc) {
  asm volatile("{.reg .pred p; setp.ne.b32 p, %66, 0; wgmma.mma_async.sync.aligned.m64n128k16.f32.bf16.bf16 {%0,%1,%2,%3,%4,%5,%6,%7,%8,%9,%10,%11,%12,%13,%14,%15,%16,%17,%18,%19,%20,%21,%22,%23,%24,%25,%26,%27,%28,%29,%30,%31,%32,%33,%34,%35,%36,%37,%38,%39,%40,%41,%42,%43,%44,%45,%46,%47,%48,%49,%50,%51,%52,%53,%54,%55,%56,%57,%58,%59,%60,%61,%62,%63}, %64, %65, p, 1, 1, 1, 1;}"
    : "+f"(d[0]),"+f"(d[1]),"+f"(d[2]),"+f"(d[3]),"+f"(d[4]),"+f"(d[5]),"+f"(d[6]),"+f"(d[7]),"+f"(d[8]),"+f"(d[9]),"+f"(d[10]),"+f"(d[11]),"+f"(d[12]),"+f"(d[13]),"+f"(d[14]),"+f"(d[15]),"+f"(d[16]),"+f"(d[17]),"+f"(d[18]),"+f"(d[19]),"+f"(d[20]),"+f"(d[21]),"+f"(d[22]),"+f"(d[23]),"+f"(d[24]),"+f"(d[25]),"+f"(d[26]),"+f"(d[27]),"+f"(d[28]),"+f"(d[29]),"+f"(d[30]),"+f"(d[31]),"+f"(d[32]),"+f"(d[33]),"+f"(d[34]),"+f"(d[35]),"+f"(d[36]),"+f"(d[37]),"+f"(d[38]),"+f"(d[39]),"+f"(d[40]),"+f"(d[41]),"+f"(d[42]),"+f"(d[43]),"+f"(d[44]),"+f"(d[45]),"+f"(d[46]),"+f"(d[47]),"+f"(d[48]),"+f"(d[49]),"+f"(d[50]),"+f"(d[51]),"+f"(d[52]),"+f"(d[53]),"+f"(d[54]),"+f"(d[55]),"+f"(d[56]),"+f"(d[57]),"+f"(d[58]),"+f"(d[59]),"+f"(d[60]),"+f"(d[61]),"+f"(d[62]),"+f"(d[63]) : "l"(da), "l"(db), "r"(sc));
}
__device__ __forceinline__ void wg_tt64(float (&d)[64], uint64_t da, uint64_t db, int sc) {
  asm volatile("{.reg .pred p; setp.ne.b32 p, %34, 0; wgmma.mma_async.sync.aligned.m64n64k16.f32.bf16.bf16 {%0,%1,%2,%3,%4,%5,%6,%7,%8,%9,%10,%11,%12,%13,%14,%15,%16,%17,%18,%19,%20,%21,%22,%23,%24,%25,%26,%27,%28,%29,%30,%31}, %32, %33, p, 1, 1, 1, 1;}"
    : "+f"(d[0]),"+f"(d[1]),"+f"(d[2]),"+f"(d[3]),"+f"(d[4]),"+f"(d[5]),"+f"(d[6]),"+f"(d[7]),"+f"(d[8]),"+f"(d[9]),"+f"(d[10]),"+f"(d[11]),"+f"(d[12]),"+f"(d[13]),"+f"(d[14]),"+f"(d[15]),"+f"(d[16]),"+f"(d[17]),"+f"(d[18]),"+f"(d[19]),"+f"(d[20]),"+f"(d[21]),"+f"(d[22]),"+f"(d[23]),"+f"(d[24]),"+f"(d[25]),"+f"(d[26]),"+f"(d[27]),"+f"(d[28]),"+f"(d[29]),"+f"(d[30]),"+f"(d[31]) : "l"(da), "l"(db), "r"(sc));
}
__device__ __forceinline__ void wg_tt32(float (&d)[64], uint64_t da, uint64_t db, int sc) {
  asm volatile("{.reg .pred p; setp.ne.b32 p, %18, 0; wgmma.mma_async.sync.aligned.m64n32k16.f32.bf16.bf16 {%0,%1,%2,%3,%4,%5,%6,%7,%8,%9,%10,%11,%12,%13,%14,%15}, %16, %17, p, 1, 1, 1, 1;}"
    : "+f"(d[0]),"+f"(d[1]),"+f"(d[2]),"+f"(d[3]),"+f"(d[4]),"+f"(d[5]),"+f"(d[6]),"+f"(d[7]),"+f"(d[8]),"+f"(d[9]),"+f"(d[10]),"+f"(d[11]),"+f"(d[12]),"+f"(d[13]),"+f"(d[14]),"+f"(d[15]) : "l"(da), "l"(db), "r"(sc));
}
__device__ __forceinline__ void wg_g1(float (&d)[88], uint64_t da, uint64_t db, int sc) {
  asm volatile("{.reg .pred p; setp.ne.b32 p, %90, 0; wgmma.mma_async.sync.aligned.m64n176k16.f32.bf16.bf16 {%0,%1,%2,%3,%4,%5,%6,%7,%8,%9,%10,%11,%12,%13,%14,%15,%16,%17,%18,%19,%20,%21,%22,%23,%24,%25,%26,%27,%28,%29,%30,%31,%32,%33,%34,%35,%36,%37,%38,%39,%40,%41,%42,%43,%44,%45,%46,%47,%48,%49,%50,%51,%52,%53,%54,%55,%56,%57,%58,%59,%60,%61,%62,%63,%64,%65,%66,%67,%68,%69,%70,%71,%72,%73,%74,%75,%76,%77,%78,%79,%80,%81,%82,%83,%84,%85,%86,%87}, %88, %89, p, 1, 1, 1, 0;}"
    : "+f"(d[0]),"+f"(d[1]),"+f"(d[2]),"+f"(d[3]),"+f"(d[4]),"+f"(d[5]),"+f"(d[6]),"+f"(d[7]),"+f"(d[8]),"+f"(d[9]),"+f"(d[10]),"+f"(d[11]),"+f"(d[12]),"+f"(d[13]),"+f"(d[14]),"+f"(d[15]),"+f"(d[16]),"+f"(d[17]),"+f"(d[18]),"+f"(d[19]),"+f"(d[20]),"+f"(d[21]),"+f"(d[22]),"+f"(d[23]),"+f"(d[24]),"+f"(d[25]),"+f"(d[26]),"+f"(d[27]),"+f"(d[28]),"+f"(d[29]),"+f"(d[30]),"+f"(d[31]),"+f"(d[32]),"+f"(d[33]),"+f"(d[34]),"+f"(d[35]),"+f"(d[36]),"+f"(d[37]),"+f"(d[38]),"+f"(d[39]),"+f"(d[40]),"+f"(d[41]),"+f"(d[42]),"+f"(d[43]),"+f"(d[44]),"+f"(d[45]),"+f"(d[46]),"+f"(d[47]),"+f"(d[48]),"+f"(d[49]),"+f"(d[50]),"+f"(d[51]),"+f"(d[52]),"+f"(d[53]),"+f"(d[54]),"+f"(d[55]),"+f"(d[56]),"+f"(d[57]),"+f"(d[58]),"+f"(d[59]),"+f"(d[60]),"+f"(d[61]),"+f"(d[62]),"+f"(d[63]),"+f"(d[64]),"+f"(d[65]),"+f"(d[66]),"+f"(d[67]),"+f"(d[68]),"+f"(d[69]),"+f"(d[70]),"+f"(d[71]),"+f"(d[72]),"+f"(d[73]),"+f"(d[74]),"+f"(d[75]),"+f"(d[76]),"+f"(d[77]),"+f"(d[78]),"+f"(d[79]),"+f"(d[80]),"+f"(d[81]),"+f"(d[82]),"+f"(d[83]),"+f"(d[84]),"+f"(d[85]),"+f"(d[86]),"+f"(d[87]) : "l"(da), "l"(db), "r"(sc));
}

struct Params { const __nv_bfloat16 *x, *logA, *Aim, *Cr, *Ci, *logdt, *Dskip; };
struct Maps { CUtensorMap x[2], xo, out, wg, wu, wd, hst[2], hld; };

__device__ __forceinline__ void conv_channel(uint32_t cb, int w, int lane, uint32_t (&res)[8], uint32_t bar_free) {
    const int q = lane & 3, g = lane >> 2, gam = g >> 2;
    float acc[64];
    uint4 a[4][4];
    const uint32_t t0 = cb + CH_T + (uint32_t)(14 + 4 * w + (g & 3) + 32 * gam - 2 * q) * 80u;
    #pragma unroll
    for (int s4 = 0; s4 < 4; s4++) {
        a[s4][0] = lds128(t0 + s4 * 16);
        a[s4][1] = lds128(t0 + 16 * 80 + s4 * 16);
        a[s4][2] = lds128(t0 - 8 * 80 + s4 * 16);
        a[s4][3] = lds128(t0 + 8 * 80 + s4 * 16);
    }
    const uint32_t l0 = FU(ldsf(t0 + 64)), l1 = FU(ldsf(t0 + 16 * 80 + 64)), l2 = FU(ldsf(t0 - 8 * 80 + 64)), l3 = FU(ldsf(t0 + 8 * 80 + 64));
    const uint64_t dU = mkdesc(cb + CH_U, UPLANE, 128, 0);
    WG_FENCE();
#define CT(N, s, c) wg_rs<N>(acc, a[(s) >> 2][0].c, a[(s) >> 2][1].c, a[(s) >> 2][2].c, a[(s) >> 2][3].c, dU + 4 * (s))
    wg_rs_first(acc, a[0][0].x, a[0][1].x, a[0][2].x, a[0][3].x, dU);
    CT(128, 1, y); CT(120, 2, z); CT(120, 3, w);
    CT(112, 4, x); CT(112, 5, y); CT(104, 6, z); CT(104, 7, w);
    CT(96, 8, x);  CT(96, 9, y);  CT(88, 10, z); CT(88, 11, w);
    CT(80, 12, x); CT(80, 13, y); CT(72, 14, z); CT(72, 15, w);
#undef CT
    wg_rs<64>(acc, l0, l1, l2, l3, dU + 64);
    wg_tt64(acc, mkdesc(cb + CH_A3, 128, 512, 0), mkdesc(cb + CH_B3, 128, 256, 0), 1);
    wg_tt32(acc, mkdesc(cb + CH_A3 + 256, 128, 512, 0), mkdesc(cb + CH_B3 + 1024, 128, 256, 0), 1);
    WG_COMMIT();
    WG_WAIT(0);
    fence_acc(acc);
    if (bar_free && lane == 0) mbar_arrive(bar_free);
    const int src1 = (lane & ~3) | ((q + 1) & 3);
    float E[16][2];
    #pragma unroll
    for (int j = 0; j < 16; j++) {
        const float nxt = (j < 15) ? acc[4 * (j + 1) + 2] : 0.f;
        const float sup = (q == 0) ? nxt : acc[4 * j + 2];
        const float v = __shfl_sync(0xffffffffu, sup, src1);
        E[j][0] = acc[4 * j] + acc[4 * j + 3];
        E[j][1] = acc[4 * j + 1] + v;
    }
    const int src2 = gam ? ((lane & 12) | ((q + 3) & 3)) : (16 | (lane & 12) | ((q + 1) & 3));
    const bool c1 = gam && q != 0, c2 = gam && q == 0;
    #pragma unroll
    for (int a2 = 0; a2 < 8; a2++) {
        float y[2];
        #pragma unroll
        for (int e = 0; e < 2; e++) {
            const float sup = c1 ? E[2 * a2][e] : E[2 * a2 + 1][e];
            const float nxt = (a2 < 7) ? E[2 * a2 + 2][e] : 0.f;
            const float keep = c2 ? nxt : (c1 ? E[2 * a2 + 1][e] : E[2 * a2][e]);
            y[e] = keep + __shfl_sync(0xffffffffu, sup, src2);
        }
        res[a2] = pack2(y[1], y[0]);
    }
}

__device__ __forceinline__ void consumer(uint32_t sb, int warp, const Maps& M) {
    const int V = warp >> 2, w = warp & 3, lane = threadIdx.x & 31, q = lane & 3, g = lane >> 2;
    const int c = blockIdx.x;
    const uint32_t bars = sb + OFF_BAR, xb = sb + OFF_X + V * 2 * XBUF;
    {
        float ag[88], au[88];
        define_acc(ag); define_acc(au);
        if (V == 0) {
            sts128(xb + (w >> 1) * XBUF + 168 * 128 + (threadIdx.x & 63) * 16, 0x3f803f80u, 0x3f803f80u, 0x3f803f80u, 0x3f803f80u);
            fence_async_smem();
            bar_sync(1);
        } else mbar_wait(bars + 8 * B_GO, 0);
        #pragma unroll 1
        for (int st = 0; st < 8; st++) {
            mbar_wait(bars + 8 * (B_FULLW + (st & 3)), st >> 2);
            mbar_wait(bars + 8 * (B_FULLX + 2 * V + (st & 1)), (st >> 1) & 1);
            STAMP(40 + 8 * V + st);
            const uint64_t dG = mkdesc(sb + OFF_W + (st & 3) * 16384, 0, 1024, 1);
            const uint64_t dX = mkdesc(xb + (st & 1) * XBUF, 16, 1024, 1);
            WG_FENCE();
            #pragma unroll
            for (int k = 0; k < 4; k++) {
                wg_g1(ag, dG + k * 128, dX + k * 2, k ? 1 : st);
                wg_g1(au, dG + 512 + k * 128, dX + k * 2, k ? 1 : st);
            }
            WG_COMMIT();
            WG_WAIT(1);
            if (lane == 0 && st > 0) {
                mbar_arrive(bars + 8 * (B_EMPTYW + ((st - 1) & 3)));
                mbar_arrive(bars + 8 * (B_EMPTYX + 2 * V + ((st - 1) & 1)));
                if (warp < 4 && st == 1) mbar_arrive(bars + 8 * B_GO);
            }
        }
        WG_WAIT(0);
        fence_acc(ag); fence_acc(au);
        if (lane == 0) { mbar_arrive(bars + 8 * (B_EMPTYW + 3)); mbar_arrive(bars + 8 * (B_EMPTYX + 2 * V + 1)); }
        STAMP(8 * V + 1);
        {
            if (V == 0) {
                const float cv = (q & 2) ? ((q & 1) ? au[86] : au[84]) : ((q & 1) ? ag[86] : ag[84]), hi = bf_round(cv);
                sts128(sb + OFF_CSUM + (16 * w + g + 8 * (q & 1) + 32 * (q & 2)) * 16, pack2(hi, cv - hi), 0, 0, 0);
                fence_async_smem();
                mbar_arrive(bars + 8 * B_CS);
            }
            mbar_wait(bars + 8 * B_CS, 0);
            mbar_wait(bars + 8 * B_STATS, 0);
            const uint64_t dM = mkdesc(sb + OFF_MB + V * 168 * 16, 0, 128, 0), dC = mkdesc(sb + OFF_CSUM, 0, 128, 0);
            WG_FENCE();
            wg_kk176(ag, dC, dM, 1);
            wg_kk176(au, dC + 64, dM, 1);
            WG_COMMIT();
            mbar_wait(bars + 8 * (B_EMPTYX + 2 * V), 1);
            WG_WAIT(0);
            fence_acc(ag); fence_acc(au);
        }
        const uint32_t hs = xb + (2 * w + ((lane >> 3) & 1)) * (2688 + 128 * V) + (lane >> 4) * 128 + (lane & 7) * 16;
        const uint32_t hr = sb + OFF_HR + (168 * V + 2 * q) * 4;
        #pragma unroll
        for (int j = 0; j < 22; j += 2) {
            uint32_t o[4];
            #pragma unroll
            for (int jj = 0; jj < 2; jj++) {
                const uint2 rv = lds64(hr + (j + jj) * 32);
                float hv[4];
                #pragma unroll
                for (int i = 0; i < 4; i++) {
                    const float gh = ag[4 * (j + jj) + i] * UF((i & 1) ? rv.y : rv.x);
                    const float p = gh * au[4 * (j + jj) + i];
                    hv[i] = fmaf(p, tanh_fast(gh), p);
                }
                o[2 * jj] = pack2(hv[0], hv[1]); o[2 * jj + 1] = pack2(hv[2], hv[3]);
            }
            uint32_t ad = hs + j * 128;
            if (j == 20 && V == 0 && lane >= 16) ad = xb + 21504 + (lane & 7) * 16;
            stsm4(ad, o[0], o[1], o[2], o[3]);
        }
        fence_async_smem();
        mbar_arrive(bars + 8 * (B_EPI + V));
        STAMP(8 * V + 2);
    }
    if (c >= 128) return;
    {
        mbar_wait(bars + 8 * B_CONV, 0);
        uint32_t r0[8], r1[8];
        #pragma unroll
        for (int i = 0; i < 8; i++) asm volatile("" : "=r"(r1[i]));
        #pragma unroll 1
        for (int e = 0; e < 2; e++) {
            #pragma unroll
            for (int i = 0; i < 8; i++) r0[i] = r1[i];
            conv_channel(sb + OFF_CONV + (2 * V + e) * CH_STRIDE, w, lane, r1, (V + e == 0) ? bars + 8 * B_CH0 : 0);
            if (e == 0) STAMP(8 * V + 3);
        }
        const int gam = g >> 2, qq = gam ? ((q + 3) & 3) : q;
        uint2* sp = g_S + (2 * c + V) * 1024 + (63 - 4 * gam - qq) * 16 + 4 * w + (g & 3);
        #pragma unroll
        for (int a2 = 0; a2 < 8; a2++) sp[-a2 * 128] = make_uint2(r0[a2], r1[a2]);
        mbar_arrive(bars + 8 * (B_SIG + V));
        STAMP(8 * V + 4);
    }
    if (V == 1) return;
    {
        const int tau = c >> 2, dg = c & 3;
        const uint32_t row = 8 * (w & 1) + 32 * (w >> 1);
        float acc[64];
        define_acc(acc);
        uint2 sv[16];
        #pragma unroll
        for (int i = 0; i < 16; i++) asm volatile("" : "=r"(sv[i].x), "=r"(sv[i].y));
        const float rr0 = __ldcg(g_hr + 64 * tau + row + g), rr1 = __ldcg(g_hr + 64 * tau + row + g + 16);
        int sd = 0; uint32_t pd = 0;
        mbar_wait(bars + 8 * B_FULLD, 0);
        STAMP(5);
        uint64_t dB = mkdesc(sb + wd_slot(0), 8192, 1024, 1), dA = mkdesc(sb + h_slot(0), 1024, 128, 0);
        #pragma unroll 1
        for (int st = 0; st < 21; st++) {
            WG_FENCE();
            wg_tt128(acc, dA, dB, st);
            wg_tt128(acc, dA + 128, dB + 128, 1);
            wg_tt128(acc, dA + 256, dB + 256, 1);
            wg_tt128(acc, dA + 384, dB + 384, 1);
            WG_COMMIT();
            const uint32_t rel = bars + 8 * (B_EMPTYD + (sd ? sd - 1 : 5));
            if (++sd == 6) { sd = 0; pd ^= 1; }
            mbar_wait(bars + 8 * (B_FULLD + sd), pd);
            dB = mkdesc(sb + wd_slot(sd), 8192, 1024, 1); dA = mkdesc(sb + h_slot(sd), 1024, 128, 0);
            if (st == 14) {
                mbar_wait(bars + 8 * B_S, 0);
                const uint2* sp = g_S + (dg * 64 + q) * 1024 + (2 * tau) * 16 + (row >> 1) + 4 * (w & 1) + g;
                #pragma unroll
                for (int j = 0; j < 16; j++)
                    asm volatile("ld.global.cg.v2.b32 {%0,%1}, [%2];" : "=r"(sv[j].x), "=r"(sv[j].y) : "l"(sp + j * 4096));
            }
            WG_WAIT(1);
            if (lane == 0 && st > 0) mbar_arrive(rel);
        }
        WG_FENCE();
        wg_tt128(acc, dA, dB, 1);
        wg_tt128(acc, dA + 128, dB + 128, 1);
        WG_COMMIT();
        WG_WAIT(0);
        fence_acc(acc);
        STAMP(6);
        mbar_wait(bars + 8 * B_XO, 0);
        const uint32_t xo = sb + OFF_CONV + (row + (lane & 7) + 16 * ((lane >> 3) & 1)) * 128;
        #pragma unroll
        for (int j = 0; j < 16; j += 2) {
            const uint32_t ad = xo + (j >> 3) * 8192 + ((((j & 7) + (lane >> 4)) ^ (lane & 7)) << 4);
            uint32_t xr[4];
            asm volatile("ldmatrix.sync.aligned.m8n8.x4.shared.b16 {%0,%1,%2,%3}, [%4];" : "=r"(xr[0]), "=r"(xr[1]), "=r"(xr[2]), "=r"(xr[3]) : "r"(ad));
            #pragma unroll
            for (int i = 0; i < 4; i++) {
                const int jj = j + (i >> 1), hh = i & 1;
                const float f0 = acc[4 * jj + 2 * hh] * (hh ? rr1 : rr0), f1 = acc[4 * jj + 2 * hh + 1] * (hh ? rr1 : rr0);
                const uint32_t G = pack2(fmaf(f0, tanh_fast(f0), f0), fmaf(f1, tanh_fast(f1), f1));
                const uint32_t s2 = __byte_perm(sv[jj].x, sv[jj].y, hh ? 0x7632 : 0x5410);
                asm("fma.rn.bf16x2 %0, %1, %2, %0;" : "+r"(xr[i]) : "r"(s2), "r"(G));
            }
            stsm4(ad, xr[0], xr[1], xr[2], xr[3]);
        }
        fence_async_smem();
        bar_sync(1);
        if (w == 0 && elect_one()) {
            #pragma unroll
            for (int i = 0; i < 2; i++)
                asm volatile("cp.async.bulk.tensor.2d.global.shared::cta.bulk_group [%0, {%2, %3}], [%1];"
                    :: "l"(&M.out), "r"(sb + OFF_CONV + i * 8192), "r"(dg * 128 + 64 * i), "r"(tau * 64) : "memory");
            asm volatile("cp.async.bulk.commit_group; cp.async.bulk.wait_group.read 0;" ::: "memory");
        }
        STAMP(7);
    }
}

__device__ __forceinline__ float2 cexp_p(float re2, float im, float p) {
    float sn, cs;
    const float mag = ex2(re2 * p), th = im * p;
    asm("sin.approx.ftz.f32 %0, %1;" : "=f"(sn) : "f"(th));
    asm("cos.approx.ftz.f32 %0, %1;" : "=f"(cs) : "f"(th));
    return make_float2(mag * cs, mag * sn);
}
__device__ __forceinline__ void ldsm4(uint32_t (&r)[4], uint32_t a) {
    asm volatile("ldmatrix.sync.aligned.m8n8.x4.shared.b16 {%0,%1,%2,%3}, [%4];" : "=r"(r[0]), "=r"(r[1]), "=r"(r[2]), "=r"(r[3]) : "r"(a) : "memory");
}
__device__ __forceinline__ float2 cmul(float2 a, float2 b) { return make_float2(fmaf(a.x, b.x, -a.y * b.y), fmaf(a.x, b.y, a.y * b.x)); }
__device__ __forceinline__ float2 csqr(float2 a) { const float t = a.x * a.y; return make_float2(fmaf(a.x, a.x, -a.y * a.y), t + t); }
__device__ __forceinline__ void mma16816(float (&d)[4], const uint32_t (&a)[4], uint32_t b0, uint32_t b1) {
    asm volatile("mma.sync.aligned.m16n8k16.row.col.f32.bf16.bf16.f32 {%0,%1,%2,%3}, {%4,%5,%6,%7}, {%8,%9}, {%0,%1,%2,%3};"
        : "+f"(d[0]), "+f"(d[1]), "+f"(d[2]), "+f"(d[3]) : "r"(a[0]), "r"(a[1]), "r"(a[2]), "r"(a[3]), "r"(b0), "r"(b1));
}

__device__ __forceinline__ void aux_role(uint32_t sb, int w, const Params& P) {
    const int tid = threadIdx.x & 127, lane = tid & 31, q = lane & 3, g = lane >> 2;
    const int c = blockIdx.x;
    const uint32_t bars = sb + OFF_BAR;
    if (c < 128) {
        const uint32_t cb = sb + OFF_CONV + w * CH_STRIDE;
        const uint32_t sF = cb + CH_A3;
        const int tokb = 32 * (c >> 1) + 8 * (c & 1) + 16;
        if (elect_one()) {
            mbar_expect(bars + 8 * B_LNX, 4096);
            #pragma unroll
            for (int i = 0; i < 4; i++)
                bulk_load(sb + OFF_CONV + (w + 4 * i) * LNROW, P.x + (tokb + w + 4 * (i & 1) - 8 * (i & 2)) * DM, 1024, bars + 8 * B_LNX);
        }
        const int d = 4 * c + w;
        const uint2 la2 = *(const uint2*)(P.logA + d * 128 + 4 * lane), ai2 = *(const uint2*)(P.Aim + d * 128 + 4 * lane);
        const uint2 cr2 = *(const uint2*)(P.Cr + d * 128 + 4 * lane), ci2 = *(const uint2*)(P.Ci + d * 128 + 4 * lane);
        const float ldt = __bfloat162float(P.logdt[d]), dsk = __bfloat162float(P.Dskip[d]);
        mbar_wait(bars + 8 * B_LNX, 0);
        STAMP(34);
        #pragma unroll 1
        for (int r = w; r < 16; r += 4) {
            const uint32_t ra = sb + OFF_CONV + r * LNROW + lane * 16;
            uint32_t v[8];
            *(uint4*)&v[0] = lds128(ra); *(uint4*)&v[4] = lds128(ra + 512);
            const float pv = bf_lo(__shfl_sync(0xffffffffu, v[0], 0));
            float s = 0.f, a = 0.f;
            #pragma unroll
            for (int k = 0; k < 8; k++) { const float t0 = bf_lo(v[k]) - pv, t1 = bf_hi(v[k]) - pv; s += t0 + t1; a = fmaf(t0, t0, a); a = fmaf(t1, t1, a); }
            #pragma unroll
            for (int o = 16; o; o >>= 1) { s += __shfl_xor_sync(0xffffffffu, s, o); a += __shfl_xor_sync(0xffffffffu, a, o); }
            s *= 1.f / DM;
            const float m = pv + s, var = fmaxf(fmaf(-s, s, a * (1.f / DM)), 0.f);
            float sd, ri;
            asm("sqrt.approx.f32 %0, %1;" : "=f"(sd) : "f"(bf_round(bf_round(var) + 1e-5f)));
            asm("rcp.approx.f32 %0, %1;" : "=f"(ri) : "f"(bf_round(sd)));
            const uint32_t m2 = pack2(m, m);
            if (lane == 0) {
                const int t = tokb + (r & 7) - 2 * (r & 8);
                const float mh = -0.5f * bf_hi(m2);
                g_mb[t] = make_uint4(pack2(mh, mh), 0, 0, 0); g_hr[t] = 0.5f * ri;
            }
            #pragma unroll
            for (int k = 0; k < 8; k++) {
                uint32_t dv; asm("sub.rn.bf16x2 %0, %1, %2;" : "=r"(dv) : "r"(v[k]), "r"(m2));
                v[k] = pack2(bf_lo(dv) * ri, bf_hi(dv) * ri);
            }
            sts128(ra, v[0], v[1], v[2], v[3]); sts128(ra + 512, v[4], v[5], v[6], v[7]);
        }
        bar_sync(2);
        {
            uint32_t ad = sb + OFF_CONV + (4 * ((lane & 7) >> 1) + (lane & 1) + 2 * ((lane >> 3) & 1)) * LNROW + (16 * w + (lane >> 4)) * 16;
            uint2* dst = (uint2*)(g_xnT + (128 * w + g) * 256 + (c & 1) * 128 + (126 - 2 * (c >> 1))) + q;
            #pragma unroll
            for (int i = 0; i < 8; i++, ad += 32, dst += 16 * 512) {
                uint32_t r0, r1, r2, r3;
                asm volatile("ldmatrix.sync.aligned.m8n8.x4.trans.shared.b16 {%0,%1,%2,%3}, [%4];" : "=r"(r0), "=r"(r1), "=r"(r2), "=r"(r3) : "r"(ad));
                dst[0] = make_uint2(r0, r1); dst[8 * 512] = make_uint2(r2, r3);
            }
        }
        mbar_arrive(bars + 8 * B_LN);
        bar_sync(2);
        STAMP(16);
        float dacc[2][3][4];
        #pragma unroll
        for (int i = 0; i < 24; i++) (&dacc[0][0][0])[i] = 0.f;
        const float dt = bf_round(ex2(ldt * 1.4426950408889634f));
        const uint32_t fa = cb + lane * 4;
        const uint32_t lda = cb + ((lane & 7) + 8 * ((lane >> 3) & 1)) * 144 + (lane >> 4) * 16;
        const uint32_t ldb = cb + (32 + (lane & 7)) * 144 + (lane >> 3) * 16;
        uint64_t la = *(const uint64_t*)&la2, ai = *(const uint64_t*)&ai2, cr = *(const uint64_t*)&cr2, ci = *(const uint64_t*)&ci2;
        #pragma unroll 1
        for (int ck = 0; ck < 4; ck++, la >>= 16, ai >>= 16, cr >>= 16, ci >>= 16) {
            const float re2 = bf_round(ex2(bf_lo((uint32_t)la) * 1.4426950408889634f)) * dt * -1.4426950408889634f, im = bf_lo((uint32_t)ai) * dt;
            const float2 C = make_float2(bf_lo((uint32_t)cr) * (dt + dt), bf_lo((uint32_t)ci) * -(dt + dt));
            const float2 z8 = cexp_p(re2, im, 8.f), y1 = cexp_p(re2, -im, 1.f), y256 = cexp_p(re2, -im, 256.f);
            float2 b0 = make_float2(1.f, 0.f), b1 = cexp_p(re2, im, 64.f), b2 = csqr(b1), b3 = cmul(b2, b1), l0 = C;
            __syncwarp();
            #pragma unroll 1
            for (uint32_t ra = fa; ra < fa + 8 * 144; ra += 144) {
                stsf(ra, UF(pack2(b0.x, b0.y))); stsf(ra + 8 * 144, UF(pack2(b1.x, b1.y))); stsf(ra + 16 * 144, UF(pack2(b2.x, b2.y)));
                stsf(ra + 24 * 144, UF(pack2(b3.x, b3.y))); stsf(ra + 32 * 144, UF(pack2(l0.x, l0.y)));
                b0 = cmul(b0, z8); b1 = cmul(b1, z8); b2 = cmul(b2, z8); b3 = cmul(b3, z8); l0 = cmul(l0, y1);
            }
            const float2 y2 = csqr(y1), y4 = csqr(y2), y8 = make_float2(z8.x, -z8.y);
#define PUT(r, v) stsf(fa + (32 + (r)) * 144, UF(pack2((v).x, (v).y)))
            float2 t = cmul(C, y256), u = t;
            PUT(8, u); u = cmul(u, y2); PUT(9, u); u = cmul(u, y2); PUT(10, u); u = cmul(u, y2); PUT(11, u);
            t = cmul(t, y256); PUT(12, t); u = cmul(t, y4); PUT(13, u);
            t = cmul(t, y256); PUT(14, t); u = cmul(t, y4); PUT(15, u);
            t = cmul(t, y256); PUT(20, t); t = cmul(t, y8); PUT(16, t);
            t = cmul(t, y256); PUT(17, t); t = cmul(t, y256); PUT(18, t); t = cmul(t, y256); PUT(19, t);
#undef PUT
            __syncwarp();
            #pragma unroll
            for (int k2 = 0; k2 < 2; k2++) {
                uint32_t b[3][4];
                #pragma unroll
                for (int t3 = 0; t3 < 3; t3++) ldsm4(b[t3], ldb + t3 * 8 * 144 + k2 * 64);
                #pragma unroll
                for (int k = 0; k < 2; k++)
                    #pragma unroll
                    for (int mu = 0; mu < 2; mu++) {
                        uint32_t a[4];
                        ldsm4(a, lda + mu * 16 * 144 + k2 * 64 + k * 32);
                        #pragma unroll
                        for (int t3 = 0; t3 < 3; t3++) mma16816(dacc[mu][t3], a, b[t3][2 * k], b[t3][2 * k + 1]);
                    }
            }
        }
        __syncwarp();
        STAMP(18);
        const uint32_t sG = cb + CH_G;
        if (lane < 16) sts128(((lane & 8) ? cb + CH_U + 2048 + (lane & 4) * (UPLANE / 4) : sG + 128 + (lane & 4) * 48) + (lane & 3) * 16, 0, 0, 0, 0);
        {
            const uint32_t f0 = sF + (8 * g + 2 * q) * 4, f1 = sF + ((q < 2) ? 256 + 4 * g + 2 * q : 256 + 2 * g + 64 * q) * 4, st1 = (q < 2) ? 128 : 64;
            const uint32_t ga = sG + ((g & 1) ? 0 : 192) + (63 - (g >> 1) - 32 * q) * 2;
            #pragma unroll
            for (int i = 0; i < 4; i++) {
                const int mu = i >> 1, hh = i & 1;
                sts64(f0 + i * 256, FU(dacc[mu][0][2 * hh]), FU(dacc[mu][0][2 * hh + 1]));
                sts64(f1 + i * st1, FU(dacc[mu][1][2 * hh]), FU(dacc[mu][1][2 * hh + 1]));
                const uint32_t pk = pack2(dacc[mu][2][2 * hh], dacc[mu][2][2 * hh + 1]);
                if (q < 2) { sts16(ga - 8 * i, pk & 0xffff); sts16(ga - 8 * i - 32, pk >> 16); }
            }
            if (lane == 2) stsf(sF + 2048, dacc[0][2][0]);
        }
        __syncwarp();
        #pragma unroll 1
        for (int pass = 0; pass < 3; pass++) {
            const int rw = lane - 1 + 31 * pass;
            const int u = min(rw, 77) - 14;
            const uint32_t f0 = sF + u * 4, f1 = sF + (128 + ((u + ((u >> 1) & 1)) >> 1)) * 4, f2 = sF + (256 + ((u + 1 + ((u >> 2) & 1)) >> 2)) * 4;
            float kv[17];
            kv[0] = ldsf(u < 0 ? sF : f0); if (u < 0) kv[0] = 0.f; if (u == 0) kv[0] += dsk;
            #pragma unroll
            for (int s = 1; s < 4; s++) kv[s] = ldsf(f0 + s * 256);
            kv[4] = ldsf(u < 0 ? f0 + 1024 : f1 + 512);
            #pragma unroll
            for (int s = 5; s < 8; s++) kv[s] = ldsf(f1 + s * 128);
            kv[8] = ldsf(u < 0 ? f1 + 1024 : f2 + 512);
            #pragma unroll
            for (int s = 9; s < 16; s++) kv[s] = ldsf(f2 + s * 64);
            kv[16] = ldsf(u < 0 ? f2 + 1024 : sF + 2048); if (u > 4) kv[16] = 0.f;
            uint32_t o[17];
            #pragma unroll
            for (int s = 0; s < 17; s++) o[s] = pack2(kv[s], __shfl_up_sync(0xffffffffu, kv[s], 1));
            if (lane > 0 && rw < 78) {
                const uint32_t ta = cb + CH_T + rw * 80;
                #pragma unroll
                for (int s4 = 0; s4 < 4; s4++) sts128(ta + s4 * 16, o[4 * s4], o[4 * s4 + 1], o[4 * s4 + 2], o[4 * s4 + 3]);
                stsf(ta + 64, UF(o[16]));
            }
        }
        #pragma unroll 1
        for (int un = lane; un < 128; un += 32) {
            const uint32_t ga = sG + ((un >> 3) & 1) * 192 + (un >> 4) * 16 + (un & 7) * 8;
            const uint2 x0 = lds64(ga), x1 = lds64(ga + 8);
            sts128(cb + CH_B3 + un * 16, x0.x, x0.y, x1.x, x1.y);
        }
    } else { mbar_arrive(bars + 8 * B_LN); return; }
    STAMP(19);
    bar_sync(2);
    mbar_wait(bars + 8 * B_U, 0);
    {
        const int kap = (lane >> 4) * 8 + ((lane >> 1) & 7), gam = lane & 1, hh = w >> 1, wp = w & 1;
        uint32_t ua = sb + OFF_CONV + CH_U + wp * UPLANE + (127 - 4 * kap - 2 * gam - hh) * 16;
        uint32_t ub = sb + OFF_CONV + CH_U + (wp ^ 1) * UPLANE + (128 - wp - 4 * kap - 2 * gam - hh) * 16;
        uint32_t ad = sb + OFF_CONV + CH_A3 + (4 * wp + hh) * 512 + (kap >> 3) * 256 + (kap & 7) * 16 + gam * 8;
        #pragma unroll 1
        for (int ch = 0; ch < 4; ch++, ua += CH_STRIDE, ub += CH_STRIDE, ad += CH_STRIDE) {
            float p[24];
            const uint2 r0 = lds64(ub + 24), r3 = lds64(ua);
            uint32_t r[8];
            *(uint4*)&r[0] = lds128(ua + 16); *(uint4*)&r[4] = lds128(ub);
            p[0] = 0.f;
            p[1] = bf_lo(r0.x); p[2] = p[1] + bf_hi(r0.x); p[3] = p[2] + bf_lo(r0.y); p[4] = p[3] + bf_hi(r0.y);
            #pragma unroll
            for (int i = 0; i < 8; i++) { p[5 + 2 * i] = p[4 + 2 * i] + bf_lo(r[i]); p[6 + 2 * i] = p[5 + 2 * i] + bf_hi(r[i]); }
            p[21] = p[20] + bf_lo(r3.x); p[22] = p[21] + bf_hi(r3.x); p[23] = p[22] + bf_lo(r3.y);
            #pragma unroll
            for (int i = 0; i < 8; i += 4) {
                sts64(ad + i * 256, pack2(p[i + 9] - p[i], p[i + 10] - p[i + 1]), pack2(p[i + 11] - p[i + 2], p[i + 12] - p[i + 3]));
                sts64(ad + i * 256 + 128, pack2(p[i + 16] - p[i + 9], p[i + 17] - p[i + 10]), pack2(p[i + 18] - p[i + 11], p[i + 19] - p[i + 12]));
            }
        }
    }
    fence_async_smem();
    mbar_arrive(bars + 8 * B_CONV);
    STAMP(21);
}

__global__ void __launch_bounds__(512, 1)
fused_kernel(const __grid_constant__ Params P, const __grid_constant__ Maps M) {
    extern __shared__ __align__(1024) uint8_t smem_raw[];
    const uint32_t sb = smem_u32(smem_raw);
    const uint32_t bars = sb + OFF_BAR;
    const int warp = __shfl_sync(0xffffffffu, threadIdx.x >> 5, 0);
    if (elect_one()) {
        if (warp == 0) STAMP(24);
        if (warp < 10) asm volatile("prefetch.tensormap [%0];" :: "l"(&M.x[0] + warp) : "memory");
        #pragma unroll
        for (int k = 0; k < 3; k++) {
            const int i = 3 * warp + k;
            const uint32_t cnt = i >= B_CONV ? 128 : ((0xf0ull >> i) & 1) ? 8 : ((0x3f0000ull >> i) & 1) ? 2 : ((0x380fc0f000ull >> i) & 1) ? 4 : 1;
            asm volatile("mbarrier.init.shared::cta.b64 [%0], %1;" :: "r"(bars + 8 * i), "r"(cnt) : "memory");
        }
        asm volatile("fence.mbarrier_init.release.cluster;" ::: "memory");
        if (sb & 1023) __trap();
    }
    __syncthreads();
    if (warp < 8) {
        asm volatile("setmaxnreg.inc.sync.aligned.u32 208;");
        consumer(sb, warp, M);
    } else if (warp < 12) {
        asm volatile("setmaxnreg.dec.sync.aligned.u32 72;");
        STAMP(32);
        aux_role(sb, warp - 8, P);
    } else {
        asm volatile("setmaxnreg.dec.sync.aligned.u32 24;");
        const int c = blockIdx.x, tg = c / 22, fb = c - 22 * tg, tau = c >> 2, dg = c & 3;
        if (elect_one()) {
            if (warp == 12) {
                #pragma unroll 1
                for (int st = 0; st < 8; st++) {
                    const uint32_t s = st & 3, fb_ = bars + 8 * (B_FULLW + s);
                    mbar_wait(bars + 8 * (B_EMPTYW + s), (st >> 2) ^ 1);
                    mbar_expect(fb_, 16384);
                    tma2d(sb + OFF_W + s * 16384, &M.wg, 64 * fb, 64 * st, fb_);
                    tma2d(sb + OFF_W + s * 16384 + 8192, &M.wu, 64 * fb, 64 * st, fb_);
                    if (st == 0) STAMP(31);
                }
                if (c < 128) {
                    int sd = 0; uint32_t pe = 1;
                    #pragma unroll 1
                    for (int st = 0; st < 22; st++) {
                        if (st < 6) mbar_wait(bars + 8 * (uint32_t)((0x1f070d060504ull >> (8 * st)) & 0xff), st < 5);
                        else mbar_wait(bars + 8 * (B_EMPTYD + sd), pe);
                        const uint32_t da = sb + wd_slot(sd), fb_ = bars + 8 * (B_FULLD + sd);
                        mbar_expect(fb_, 16384);
                        tma2d(da, &M.wd, 128 * dg, 64 * st, fb_);
                        tma2d(da + 8192, &M.wd, 128 * dg + 64, 64 * st, fb_);
                        if (++sd == 6) { sd = 0; pe ^= 1; }
                    }
                }
            } else if (warp < 15) {
                const int V = warp - 13;
                #pragma unroll 1
                for (int st = 0; st < 8; st++) {
                    const uint32_t s = 2 * V + (st & 1);
                    mbar_wait(bars + 8 * (B_EMPTYX + s), ((st >> 1) & 1) ^ 1);
                    mbar_expect(bars + 8 * (B_FULLX + s), (168 + 8 * V) * 128);
                    tma2d(sb + OFF_X + s * XBUF, &M.x[V], 64 * st, TOKG * tg + 168 * V, bars + 8 * (B_FULLX + s));
                }
                if (c < 128) {
                    if (V == 0) {
                        mbar_wait(bars + 8 * (B_STG + 1), 0);
                        #pragma unroll 1
                        for (int o = 8 * tau; o < 8 * tau + 8; o += 7) flag_wait(F_H + 2 * (o / 43) + ((o % 43) >= 21), 22);
                        fence_async();
                        mbar_arrive(bars + 8 * B_HF);
                        STAMP(25);
                        int sh = 0; uint32_t pe = 1;
                        #pragma unroll 1
                        for (int st = 0; st < 22; st++) {
                            const uint32_t fb_ = bars + 8 * (B_FULLD + sh);
                            mbar_wait(bars + 8 * (B_EMPTYD + sh), pe);
                            mbar_expect(fb_, 8192);
                            asm volatile("cp.async.bulk.tensor.5d.shared::cluster.global.mbarrier::complete_tx::bytes [%0], [%1, {%3, %3, %3, %4, %5}], [%2];"
                                :: "r"(sb + h_slot(sh)), "l"(&M.hld), "r"(fb_), "r"(0), "r"(2 * tau), "r"(8 * st) : "memory");
                            if (++sh == 6) { sh = 0; pe ^= 1; }
                        }
                    } else {
                        mbar_wait(bars + 8 * B_CH0, 0);
                        mbar_expect(bars + 8 * B_XO, 16384);
                        tma2d(sb + OFF_CONV, &M.xo, 128 * dg, 64 * tau, bars + 8 * B_XO);
                        tma2d(sb + OFF_CONV + 8192, &M.xo, 128 * dg + 64, 64 * tau, bars + 8 * B_XO);
                        flag_wait(F_S + dg, 64);
                        STAMP(26);
                        mbar_arrive(bars + 8 * B_S);
                        mbar_wait(bars + 8 * B_HF, 0);
                        exit_count();
                    }
                }
            } else {
                mbar_wait(bars + 8 * B_LN, 0);
                flag_signal(F_A);
                flag_wait(F_A, NCTA);
                fence_async();
                STAMP(20);
                mbar_expect(bars + 8 * B_STATS, TOKG * 20);
                bulk_load(sb + OFF_MB, g_mb + TOKG * tg, TOKG * 16, bars + 8 * B_STATS);
                bulk_load(sb + OFF_HR, g_hr + TOKG * tg, TOKG * 4, bars + 8 * B_STATS);
                if (c < 128) {
                    mbar_expect(bars + 8 * B_U, 8 * 2048);
                    #pragma unroll 1
                    for (int i = 0; i < 8; i++)
                        bulk_load(sb + OFF_CONV + (i >> 1) * CH_STRIDE + CH_U + (i & 1) * UPLANE, g_xnT + 4 * c * 256 + i * 128, 2048, bars + 8 * B_U);
                } else exit_count();
                #pragma unroll 1
                for (int V = 0; V < 2; V++) {
                    mbar_wait(bars + 8 * (B_EPI + V), 0);
                    asm volatile("cp.async.bulk.tensor.3d.global.shared::cta.bulk_group [%0, {%2, %3, %4}], [%1];"
                        :: "l"(&M.hst[V]), "r"(sb + OFF_X + V * 2 * XBUF), "r"(0), "r"(43 * tg + 21 * V), "r"(8 * fb) : "memory");
                    asm volatile("cp.async.bulk.commit_group; cp.async.bulk.wait_group 0;" ::: "memory");
                    mbar_arrive(bars + 8 * (B_STG + V));
                    flag_signal(F_H + 2 * tg + V);
                }
                if (c < 128) {
                    #pragma unroll 1
                    for (int V = 0; V < 2; V++) { mbar_wait(bars + 8 * (B_SIG + V), 0); flag_signal(F_S + (c >> 5)); }
                }
            }
        }
    }
}

typedef CUresult (*EncodeFn)(CUtensorMap*, CUtensorMapDataType, cuuint32_t, void*, const cuuint64_t*, const cuuint64_t*, const cuuint32_t*,
                             const cuuint32_t*, CUtensorMapInterleave, CUtensorMapSwizzle, CUtensorMapL2promotion, CUtensorMapFloatOOBfill);

void make_map(EncodeFn enc, CUtensorMap* m, const void* ptr, int rank, const cuuint64_t* dims, const cuuint64_t* strides, const cuuint32_t* box, bool swz) {
    const cuuint32_t es[5] = {1, 1, 1, 1, 1};
    enc(m, CU_TENSOR_MAP_DATA_TYPE_BFLOAT16, rank, (void*)ptr, dims, strides, box, es, CU_TENSOR_MAP_INTERLEAVE_NONE,
        swz ? CU_TENSOR_MAP_SWIZZLE_128B : CU_TENSOR_MAP_SWIZZLE_NONE, CU_TENSOR_MAP_L2_PROMOTION_L2_128B, CU_TENSOR_MAP_FLOAT_OOB_FILL_NONE);
}
void make_map2(EncodeFn enc, CUtensorMap* m, const void* ptr, cuuint64_t inner, cuuint64_t outer, cuuint32_t rows) {
    const cuuint64_t dims[2] = {inner, outer}, strides[1] = {inner * 2};
    const cuuint32_t box[2] = {64, rows};
    make_map(enc, m, ptr, 2, dims, strides, box, true);
}

}

extern "C" void kernel_launch(void* const* d_in, const int* in_sizes, int n_in, void* d_out, int out_size) {
    (void)in_sizes; (void)n_in; (void)out_size;
    static EncodeFn enc = nullptr;
    static void* hptr = nullptr;
    if (!enc) {
        cudaDriverEntryPointQueryResult qr;
        cudaGetDriverEntryPoint("cuTensorMapEncodeTiled", (void**)&enc, cudaEnableDefault, &qr);
        cudaFuncSetAttribute(fused_kernel, cudaFuncAttributeMaxDynamicSharedMemorySize, SMEM_BYTES);
        cudaGetSymbolAddress(&hptr, g_H);
    }
    Params P;
    P.x = (const __nv_bfloat16*)d_in[0]; P.logA = (const __nv_bfloat16*)d_in[1]; P.Aim = (const __nv_bfloat16*)d_in[2];
    P.Cr = (const __nv_bfloat16*)d_in[3]; P.Ci = (const __nv_bfloat16*)d_in[4]; P.logdt = (const __nv_bfloat16*)d_in[5];
    P.Dskip = (const __nv_bfloat16*)d_in[6];
    Maps M;
    make_map2(enc, &M.x[0], d_in[0], DM, SEQ, 168); make_map2(enc, &M.x[1], d_in[0], DM, SEQ, 176);
    make_map2(enc, &M.xo, d_in[0], DM, SEQ, 64);    make_map2(enc, &M.out, d_out, DM, SEQ, 64);
    make_map2(enc, &M.wg, d_in[8], FF, DM, 64);     make_map2(enc, &M.wu, d_in[9], FF, DM, 64);
    make_map2(enc, &M.wd, d_in[10], DM, FF, 64);
    for (int v = 0; v < 2; v++) {
        const cuuint64_t dims[3] = {64, 256, 172}, strides[2] = {128, 32768};
        const cuuint32_t box[3] = {64, (cuuint32_t)(21 + v), 8};
        make_map(enc, &M.hst[v], hptr, 3, dims, strides, box, false);
    }
    {
        const cuuint64_t dims[5] = {64, 2, 2, 64, 172}, strides[4] = {256, 128, 512, 32768};
        const cuuint32_t box[5] = {64, 2, 2, 2, 8};
        make_map(enc, &M.hld, hptr, 5, dims, strides, box, false);
    }
    fused_kernel<<<NCTA, 512, SMEM_BYTES>>>(P, M);
}
```

```cpp
#include <cuda_runtime.h>
#include <cuda_bf16.h>
#include <cuda.h>
#include <stdint.h>

#define PROF 0

namespace {

constexpr int SEQ = 2048, DM = 512, FF = 1376;
constexpr int NCTA = 132;
#define HOLD0 4
#define HOLD1 6
constexpr int TOKG = 344;

constexpr uint32_t OFF_W = 0;
constexpr uint32_t XBUF = 22528;
constexpr uint32_t OFF_X = 65536;
constexpr uint32_t OFF_CONV = 155648;
constexpr uint32_t CH_STRIDE = 16640;
constexpr uint32_t CH_T = 0;
constexpr uint32_t CH_A3 = 6272;
constexpr uint32_t CH_B3 = 10368;
constexpr uint32_t CH_U = 12416;
constexpr uint32_t CH_G = CH_A3 + 2064;
constexpr uint32_t UPLANE = 2112;
constexpr uint32_t LNROW = 1040;
constexpr uint32_t OFF_MB = 222208;
constexpr uint32_t OFF_HR = 227712;
constexpr uint32_t OFF_CSUM = 229120;
constexpr uint32_t OFF_BAR = 231168;
constexpr uint32_t SMEM_BYTES = 231680;

enum {
    B_FULLW = 0, B_EMPTYW = 4, B_FULLX = 8, B_EMPTYX = 12, B_FULLD = 16, B_EMPTYD = 22,
    B_U = 28, B_XO = 29, B_S = 30, B_STG = 31, B_HF = 33, B_STATS = 34,
    B_LNX = 35, B_GO = 36, B_CH0 = 37, B_K = 38,
    B_CONV = 40, B_LN = 41, B_CS = 42, B_EPI = 43, B_SIG = 45,
    B_COUNT = 47
};
enum { F_A = 0, F_H = 1, F_S = 13, F_EXIT = 17, F_COUNT = 18 };

__device__ uint4 g_xnT[DM * 256];
__device__ uint4 g_mb[6 * TOKG];
__device__ float g_hr[6 * TOKG];
__device__ uint4 g_H[172 * 256 * 8];
__device__ uint2 g_S[256 * 1024];
__device__ unsigned g_flags[F_COUNT * 32];
#define STAMP(i) do {} while (0)

__device__ __forceinline__ uint32_t smem_u32(const void* p) { return (uint32_t)__cvta_generic_to_shared(p); }
__device__ __forceinline__ void mbar_expect(uint32_t bar, uint32_t bytes) { asm volatile("mbarrier.arrive.expect_tx.shared::cta.b64 _, [%0], %1;" :: "r"(bar), "r"(bytes) : "memory"); }
__device__ __forceinline__ void mbar_arrive(uint32_t bar) { asm volatile("mbarrier.arrive.shared::cta.b64 _, [%0];" :: "r"(bar) : "memory"); }
__device__ __forceinline__ void mbar_wait(uint32_t bar, uint32_t parity) {
    asm volatile("{.reg .pred p; .reg .u32 n; mov.u32 n, 0x20000;\n"
                 "LW: mbarrier.try_wait.parity.shared::cta.b64 p, [%0], %1;\n"
                 "sub.u32 n, n, 1; setp.eq.or.u32 p, n, 0, p; @!p bra LW;}" :: "r"(bar), "r"(parity) : "memory");
}
__device__ __forceinline__ bool elect_one() { uint32_t p; asm volatile("{.reg .pred P; elect.sync _|P, 0xffffffff; selp.u32 %0, 1, 0, P;}" : "=r"(p)); return p; }
__device__ __forceinline__ void tma2d(uint32_t dst, const CUtensorMap* m, int c0, int c1, uint32_t bar) {
    asm volatile("cp.async.bulk.tensor.2d.shared::cluster.global.mbarrier::complete_tx::bytes [%0], [%1, {%3, %4}], [%2];"
        :: "r"(dst), "l"(m), "r"(bar), "r"(c0), "r"(c1) : "memory");
}
__device__ __forceinline__ void bulk_load(uint32_t dst, const void* src, uint32_t bytes, uint32_t bar) {
    asm volatile("cp.async.bulk.shared::cluster.global.mbarrier::complete_tx::bytes [%0], [%1], %2, [%3];" :: "r"(dst), "l"(src), "r"(bytes), "r"(bar) : "memory");
}
__device__ __forceinline__ void fence_async() { asm volatile("fence.proxy.async;" ::: "memory"); }
__device__ __forceinline__ void fence_async_smem() { asm volatile("fence.proxy.async.shared::cta;" ::: "memory"); }
__device__ __forceinline__ void flag_wait(unsigned* g_flags, int f, unsigned target) {
    asm volatile("{.reg .pred p; .reg .u32 n, v; mov.u32 n, 0x40000;\n"
                 "LF: ld.acquire.gpu.global.u32 v, [%0]; setp.ge.u32 p, v, %1; @p bra LD;\n"
                 "nanosleep.u32 20; sub.u32 n, n, 1; setp.ne.u32 p, n, 0; @p bra LF; trap;\nLD: }"
                 :: "l"(g_flags + f * 32), "r"(target) : "memory");
}
__device__ __forceinline__ void flag_signal(unsigned* g_flags, int f) {
    asm volatile("fence.acq_rel.gpu; red.relaxed.gpu.global.add.u32 [%0], 1;" :: "l"(g_flags + f * 32) : "memory");
}
__device__ __forceinline__ void exit_count(unsigned* g_flags) {
    if (atomicAdd(g_flags + F_EXIT * 32, 1u) == NCTA - 1) {
        #pragma unroll 1
        for (int i = 0; i < F_COUNT; i++) g_flags[i * 32] = 0;
    }
}
__device__ __forceinline__ void bar_sync(int id) { asm volatile("bar.sync %0, 128;" :: "r"(id) : "memory"); }
__device__ __forceinline__ uint64_t mkdesc(uint32_t addr, uint32_t lbo, uint32_t sbo, uint32_t swz) {
    return (uint64_t)((addr >> 4) | ((lbo >> 4) << 16)) | ((uint64_t)((sbo >> 4) | (swz << 30)) << 32);
}
#define WG_FENCE() asm volatile("wgmma.fence.sync.aligned;" ::: "memory")
#define WG_COMMIT() asm volatile("wgmma.commit_group.sync.aligned;" ::: "memory")
#define WG_WAIT(n) asm volatile("wgmma.wait_group.sync.aligned " #n ";" ::: "memory")
template <int N> __device__ __forceinline__ void fence_acc(float (&d)[N]) {
    #pragma unroll
    for (int i = 0; i < N; i++) asm volatile("" : "+f"(d[i]) :: "memory");
}
template <int N> __device__ __forceinline__ void define_acc(float (&d)[N]) {
    #pragma unroll
    for (int i = 0; i < N; i++) asm volatile("" : "=f"(d[i]));
}
__device__ __forceinline__ uint32_t pack2(float lo, float hi) { uint32_t r; asm("cvt.rn.bf16x2.f32 %0, %1, %2;" : "=r"(r) : "f"(hi), "f"(lo)); return r; }
__device__ __forceinline__ float bf_lo(uint32_t v) { return __uint_as_float(v << 16); }
__device__ __forceinline__ float bf_hi(uint32_t v) { return __uint_as_float(v & 0xffff0000u); }
__device__ __forceinline__ float bf_round(float v) { return bf_hi(pack2(0.f, v)); }
__device__ __forceinline__ float tanh_fast(float v) { float r; asm("tanh.approx.f32 %0, %1;" : "=f"(r) : "f"(v)); return r; }
__device__ __forceinline__ float ex2(float v) { float r; asm("ex2.approx.ftz.f32 %0, %1;" : "=f"(r) : "f"(v)); return r; }
__device__ __forceinline__ uint4 lds128(uint32_t a) { uint4 v; asm volatile("ld.shared.v4.b32 {%0,%1,%2,%3}, [%4];" : "=r"(v.x), "=r"(v.y), "=r"(v.z), "=r"(v.w) : "r"(a)); return v; }
__device__ __forceinline__ uint2 lds64(uint32_t a) { uint2 v; asm volatile("ld.shared.v2.b32 {%0,%1}, [%2];" : "=r"(v.x), "=r"(v.y) : "r"(a)); return v; }
__device__ __forceinline__ float ldsf(uint32_t a) { float v; asm volatile("ld.shared.f32 %0, [%1];" : "=f"(v) : "r"(a)); return v; }
__device__ __forceinline__ void sts128(uint32_t a, uint32_t x, uint32_t y, uint32_t z, uint32_t w) { asm volatile("st.shared.v4.b32 [%0], {%1,%2,%3,%4};" :: "r"(a), "r"(x), "r"(y), "r"(z), "r"(w) : "memory"); }
__device__ __forceinline__ void sts64(uint32_t a, uint32_t x, uint32_t y) { asm volatile("st.shared.v2.b32 [%0], {%1,%2};" :: "r"(a), "r"(x), "r"(y) : "memory"); }
__device__ __forceinline__ void stsf(uint32_t a, float x) { asm volatile("st.shared.f32 [%0], %1;" :: "r"(a), "f"(x) : "memory"); }
__device__ __forceinline__ void sts16(uint32_t a, uint32_t x) { asm volatile("st.shared.b16 [%0], %1;" :: "r"(a), "h"((unsigned short)x) : "memory"); }
__device__ __forceinline__ void stsm4(uint32_t a, uint32_t r0, uint32_t r1, uint32_t r2, uint32_t r3) {
    asm volatile("stmatrix.sync.aligned.m8n8.x4.shared.b16 [%0], {%1,%2,%3,%4};" :: "r"(a), "r"(r0), "r"(r1), "r"(r2), "r"(r3) : "memory");
}
#define FU(x) __float_as_uint(x)
#define UF(x) __uint_as_float(x)
__device__ __forceinline__ uint32_t wd_slot(int s) { return (uint32_t)((0x403056201000ull >> (8 * s)) & 0xff) << 10; }
__device__ __forceinline__ uint32_t h_slot(int s) { return s < 5 ? OFF_X + 2 * XBUF + s * 8192 : OFF_MB; }

template<int N> __device__ __forceinline__ void wg_rs(float (&d)[64], uint32_t a0, uint32_t a1, uint32_t a2, uint32_t a3, uint64_t db);
template<> __device__ __forceinline__ void wg_rs<128>(float (&d)[64], uint32_t a0, uint32_t a1, uint32_t a2, uint32_t a3, uint64_t db) {
  asm volatile("{.reg .pred p; setp.ne.b32 p, 1, 0; wgmma.mma_async.sync.aligned.m64n128k16.f32.bf16.bf16 {%0,%1,%2,%3,%4,%5,%6,%7,%8,%9,%10,%11,%12,%13,%14,%15,%16,%17,%18,%19,%20,%21,%22,%23,%24,%25,%26,%27,%28,%29,%30,%31,%32,%33,%34,%35,%36,%37,%38,%39,%40,%41,%42,%43,%44,%45,%46,%47,%48,%49,%50,%51,%52,%53,%54,%55,%56,%57,%58,%59,%60,%61,%62,%63}, {%64,%65,%66,%67}, %68, p, 1, 1, 0;}"
    : "+f"(d[0]),"+f"(d[1]),"+f"(d[2]),"+f"(d[3]),"+f"(d[4]),"+f"(d[5]),"+f"(d[6]),"+f"(d[7]),"+f"(d[8]),"+f"(d[9]),"+f"(d[10]),"+f"(d[11]),"+f"(d[12]),"+f"(d[13]),"+f"(d[14]),"+f"(d[15]),"+f"(d[16]),"+f"(d[17]),"+f"(d[18]),"+f"(d[19]),"+f"(d[20]),"+f"(d[21]),"+f"(d[22]),"+f"(d[23]),"+f"(d[24]),"+f"(d[25]),"+f"(d[26]),"+f"(d[27]),"+f"(d[28]),"+f"(d[29]),"+f"(d[30]),"+f"(d[31]),"+f"(d[32]),"+f"(d[33]),"+f"(d[34]),"+f"(d[35]),"+f"(d[36]),"+f"(d[37]),"+f"(d[38]),"+f"(d[39]),"+f"(d[40]),"+f"(d[41]),"+f"(d[42]),"+f"(d[43]),"+f"(d[44]),"+f"(d[45]),"+f"(d[46]),"+f"(d[47]),"+f"(d[48]),"+f"(d[49]),"+f"(d[50]),"+f"(d[51]),"+f"(d[52]),"+f"(d[53]),"+f"(d[54]),"+f"(d[55]),"+f"(d[56]),"+f"(d[57]),"+f"(d[58]),"+f"(d[59]),"+f"(d[60]),"+f"(d[61]),"+f"(d[62]),"+f"(d[63]) : "r"(a0), "r"(a1), "r"(a2), "r"(a3), "l"(db));
}
template<> __device__ __forceinline__ void wg_rs<120>(float (&d)[64], uint32_t a0, uint32_t a1, uint32_t a2, uint32_t a3, uint64_t db) {
  asm volatile("{.reg .pred p; setp.ne.b32 p, 1, 0; wgmma.mma_async.sync.aligned.m64n120k16.f32.bf16.bf16 {%0,%1,%2,%3,%4,%5,%6,%7,%8,%9,%10,%11,%12,%13,%14,%15,%16,%17,%18,%19,%20,%21,%22,%23,%24,%25,%26,%27,%28,%29,%30,%31,%32,%33,%34,%35,%36,%37,%38,%39,%40,%41,%42,%43,%44,%45,%46,%47,%48,%49,%50,%51,%52,%53,%54,%55,%56,%57,%58,%59}, {%60,%61,%62,%63}, %64, p, 1, 1, 0;}"
    : "+f"(d[0]),"+f"(d[1]),"+f"(d[2]),"+f"(d[3]),"+f"(d[4]),"+f"(d[5]),"+f"(d[6]),"+f"(d[7]),"+f"(d[8]),"+f"(d[9]),"+f"(d[10]),"+f"(d[11]),"+f"(d[12]),"+f"(d[13]),"+f"(d[14]),"+f"(d[15]),"+f"(d[16]),"+f"(d[17]),"+f"(d[18]),"+f"(d[19]),"+f"(d[20]),"+f"(d[21]),"+f"(d[22]),"+f"(d[23]),"+f"(d[24]),"+f"(d[25]),"+f"(d[26]),"+f"(d[27]),"+f"(d[28]),"+f"(d[29]),"+f"(d[30]),"+f"(d[31]),"+f"(d[32]),"+f"(d[33]),"+f"(d[34]),"+f"(d[35]),"+f"(d[36]),"+f"(d[37]),"+f"(d[38]),"+f"(d[39]),"+f"(d[40]),"+f"(d[41]),"+f"(d[42]),"+f"(d[43]),"+f"(d[44]),"+f"(d[45]),"+f"(d[46]),"+f"(d[47]),"+f"(d[48]),"+f"(d[49]),"+f"(d[50]),"+f"(d[51]),"+f"(d[52]),"+f"(d[53]),"+f"(d[54]),"+f"(d[55]),"+f"(d[56]),"+f"(d[57]),"+f"(d[58]),"+f"(d[59]) : "r"(a0), "r"(a1), "r"(a2), "r"(a3), "l"(db));
}
template<> __device__ __forceinline__ void wg_rs<112>(float (&d)[64], uint32_t a0, uint32_t a1, uint32_t a2, uint32_t a3, uint64_t db) {
  asm volatile("{.reg .pred p; setp.ne.b32 p, 1, 0; wgmma.mma_async.sync.aligned.m64n112k16.f32.bf16.bf16 {%0,%1,%2,%3,%4,%5,%6,%7,%8,%9,%10,%11,%12,%13,%14,%15,%16,%17,%18,%19,%20,%21,%22,%23,%24,%25,%26,%27,%28,%29,%30,%31,%32,%33,%34,%35,%36,%37,%38,%39,%40,%41,%42,%43,%44,%45,%46,%47,%48,%49,%50,%51,%52,%53,%54,%55}, {%56,%57,%58,%59}, %60, p, 1, 1, 0;}"
    : "+f"(d[0]),"+f"(d[1]),"+f"(d[2]),"+f"(d[3]),"+f"(d[4]),"+f"(d[5]),"+f"(d[6]),"+f"(d[7]),"+f"(d[8]),"+f"(d[9]),"+f"(d[10]),"+f"(d[11]),"+f"(d[12]),"+f"(d[13]),"+f"(d[14]),"+f"(d[15]),"+f"(d[16]),"+f"(d[17]),"+f"(d[18]),"+f"(d[19]),"+f"(d[20]),"+f"(d[21]),"+f"(d[22]),"+f"(d[23]),"+f"(d[24]),"+f"(d[25]),"+f"(d[26]),"+f"(d[27]),"+f"(d[28]),"+f"(d[29]),"+f"(d[30]),"+f"(d[31]),"+f"(d[32]),"+f"(d[33]),"+f"(d[34]),"+f"(d[35]),"+f"(d[36]),"+f"(d[37]),"+f"(d[38]),"+f"(d[39]),"+f"(d[40]),"+f"(d[41]),"+f"(d[42]),"+f"(d[43]),"+f"(d[44]),"+f"(d[45]),"+f"(d[46]),"+f"(d[47]),"+f"(d[48]),"+f"(d[49]),"+f"(d[50]),"+f"(d[51]),"+f"(d[52]),"+f"(d[53]),"+f"(d[54]),"+f"(d[55]) : "r"(a0), "r"(a1), "r"(a2), "r"(a3), "l"(db));
}
template<> __device__ __forceinline__ void wg_rs<104>(float (&d)[64], uint32_t a0, uint32_t a1, uint32_t a2, uint32_t a3, uint64_t db) {
  asm volatile("{.reg .pred p; setp.ne.b32 p, 1, 0; wgmma.mma_async.sync.aligned.m64n104k16.f32.bf16.bf16 {%0,%1,%2,%3,%4,%5,%6,%7,%8,%9,%10,%11,%12,%13,%14,%15,%16,%17,%18,%19,%20,%21,%22,%23,%24,%25,%26,%27,%28,%29,%30,%31,%32,%33,%34,%35,%36,%37,%38,%39,%40,%41,%42,%43,%44,%45,%46,%47,%48,%49,%50,%51}, {%52,%53,%54,%55}, %56, p, 1, 1, 0;}"
    : "+f"(d[0]),"+f"(d[1]),"+f"(d[2]),"+f"(d[3]),"+f"(d[4]),"+f"(d[5]),"+f"(d[6]),"+f"(d[7]),"+f"(d[8]),"+f"(d[9]),"+f"(d[10]),"+f"(d[11]),"+f"(d[12]),"+f"(d[13]),"+f"(d[14]),"+f"(d[15]),"+f"(d[16]),"+f"(d[17]),"+f"(d[18]),"+f"(d[19]),"+f"(d[20]),"+f"(d[21]),"+f"(d[22]),"+f"(d[23]),"+f"(d[24]),"+f"(d[25]),"+f"(d[26]),"+f"(d[27]),"+f"(d[28]),"+f"(d[29]),"+f"(d[30]),"+f"(d[31]),"+f"(d[32]),"+f"(d[33]),"+f"(d[34]),"+f"(d[35]),"+f"(d[36]),"+f"(d[37]),"+f"(d[38]),"+f"(d[39]),"+f"(d[40]),"+f"(d[41]),"+f"(d[42]),"+f"(d[43]),"+f"(d[44]),"+f"(d[45]),"+f"(d[46]),"+f"(d[47]),"+f"(d[48]),"+f"(d[49]),"+f"(d[50]),"+f"(d[51]) : "r"(a0), "r"(a1), "r"(a2), "r"(a3), "l"(db));
}
template<> __device__ __forceinline__ void wg_rs<96>(float (&d)[64], uint32_t a0, uint32_t a1, uint32_t a2, uint32_t a3, uint64_t db) {
  asm volatile("{.reg .pred p; setp.ne.b32 p, 1, 0; wgmma.mma_async.sync.aligned.m64n96k16.f32.bf16.bf16 {%0,%1,%2,%3,%4,%5,%6,%7,%8,%9,%10,%11,%12,%13,%14,%15,%16,%17,%18,%19,%20,%21,%22,%23,%24,%25,%26,%27,%28,%29,%30,%31,%32,%33,%34,%35,%36,%37,%38,%39,%40,%41,%42,%43,%44,%45,%46,%47}, {%48,%49,%50,%51}, %52, p, 1, 1, 0;}"
    : "+f"(d[0]),"+f"(d[1]),"+f"(d[2]),"+f"(d[3]),"+f"(d[4]),"+f"(d[5]),"+f"(d[6]),"+f"(d[7]),"+f"(d[8]),"+f"(d[9]),"+f"(d[10]),"+f"(d[11]),"+f"(d[12]),"+f"(d[13]),"+f"(d[14]),"+f"(d[15]),"+f"(d[16]),"+f"(d[17]),"+f"(d[18]),"+f"(d[19]),"+f"(d[20]),"+f"(d[21]),"+f"(d[22]),"+f"(d[23]),"+f"(d[24]),"+f"(d[25]),"+f"(d[26]),"+f"(d[27]),"+f"(d[28]),"+f"(d[29]),"+f"(d[30]),"+f"(d[31]),"+f"(d[32]),"+f"(d[33]),"+f"(d[34]),"+f"(d[35]),"+f"(d[36]),"+f"(d[37]),"+f"(d[38]),"+f"(d[39]),"+f"(d[40]),"+f"(d[41]),"+f"(d[42]),"+f"(d[43]),"+f"(d[44]),"+f"(d[45]),"+f"(d[46]),"+f"(d[47]) : "r"(a0), "r"(a1), "r"(a2), "r"(a3), "l"(db));
}
template<> __device__ __forceinline__ void wg_rs<88>(float (&d)[64], uint32_t a0, uint32_t a1, uint32_t a2, uint32_t a3, uint64_t db) {
  asm volatile("{.reg .pred p; setp.ne.b32 p, 1, 0; wgmma.mma_async.sync.aligned.m64n88k16.f32.bf16.bf16 {%0,%1,%2,%3,%4,%5,%6,%7,%8,%9,%10,%11,%12,%13,%14,%15,%16,%17,%18,%19,%20,%21,%22,%23,%24,%25,%26,%27,%28,%29,%30,%31,%32,%33,%34,%35,%36,%37,%38,%39,%40,%41,%42,%43}, {%44,%45,%46,%47}, %48, p, 1, 1, 0;}"
    : "+f"(d[0]),"+f"(d[1]),"+f"(d[2]),"+f"(d[3]),"+f"(d[4]),"+f"(d[5]),"+f"(d[6]),"+f"(d[7]),"+f"(d[8]),"+f"(d[9]),"+f"(d[10]),"+f"(d[11]),"+f"(d[12]),"+f"(d[13]),"+f"(d[14]),"+f"(d[15]),"+f"(d[16]),"+f"(d[17]),"+f"(d[18]),"+f"(d[19]),"+f"(d[20]),"+f"(d[21]),"+f"(d[22]),"+f"(d[23]),"+f"(d[24]),"+f"(d[25]),"+f"(d[26]),"+f"(d[27]),"+f"(d[28]),"+f"(d[29]),"+f"(d[30]),"+f"(d[31]),"+f"(d[32]),"+f"(d[33]),"+f"(d[34]),"+f"(d[35]),"+f"(d[36]),"+f"(d[37]),"+f"(d[38]),"+f"(d[39]),"+f"(d[40]),"+f"(d[41]),"+f"(d[42]),"+f"(d[43]) : "r"(a0), "r"(a1), "r"(a2), "r"(a3), "l"(db));
}
template<> __device__ __forceinline__ void wg_rs<80>(float (&d)[64], uint32_t a0, uint32_t a1, uint32_t a2, uint32_t a3, uint64_t db) {
  asm volatile("{.reg .pred p; setp.ne.b32 p, 1, 0; wgmma.mma_async.sync.aligned.m64n80k16.f32.bf16.bf16 {%0,%1,%2,%3,%4,%5,%6,%7,%8,%9,%10,%11,%12,%13,%14,%15,%16,%17,%18,%19,%20,%21,%22,%23,%24,%25,%26,%27,%28,%29,%30,%31,%32,%33,%34,%35,%36,%37,%38,%39}, {%40,%41,%42,%43}, %44, p, 1, 1, 0;}"
    : "+f"(d[0]),"+f"(d[1]),"+f"(d[2]),"+f"(d[3]),"+f"(d[4]),"+f"(d[5]),"+f"(d[6]),"+f"(d[7]),"+f"(d[8]),"+f"(d[9]),"+f"(d[10]),"+f"(d[11]),"+f"(d[12]),"+f"(d[13]),"+f"(d[14]),"+f"(d[15]),"+f"(d[16]),"+f"(d[17]),"+f"(d[18]),"+f"(d[19]),"+f"(d[20]),"+f"(d[21]),"+f"(d[22]),"+f"(d[23]),"+f"(d[24]),"+f"(d[25]),"+f"(d[26]),"+f"(d[27]),"+f"(d[28]),"+f"(d[29]),"+f"(d[30]),"+f"(d[31]),"+f"(d[32]),"+f"(d[33]),"+f"(d[34]),"+f"(d[35]),"+f"(d[36]),"+f"(d[37]),"+f"(d[38]),"+f"(d[39]) : "r"(a0), "r"(a1), "r"(a2), "r"(a3), "l"(db));
}
template<> __device__ __forceinline__ void wg_rs<72>(float (&d)[64], uint32_t a0, uint32_t a1, uint32_t a2, uint32_t a3, uint64_t db) {
  asm volatile("{.reg .pred p; setp.ne.b32 p, 1, 0; wgmma.mma_async.sync.aligned.m64n72k16.f32.bf16.bf16 {%0,%1,%2,%3,%4,%5,%6,%7,%8,%9,%10,%11,%12,%13,%14,%15,%16,%17,%18,%19,%20,%21,%22,%23,%24,%25,%26,%27,%28,%29,%30,%31,%32,%33,%34,%35}, {%36,%37,%38,%39}, %40, p, 1, 1, 0;}"
    : "+f"(d[0]),"+f"(d[1]),"+f"(d[2]),"+f"(d[3]),"+f"(d[4]),"+f"(d[5]),"+f"(d[6]),"+f"(d[7]),"+f"(d[8]),"+f"(d[9]),"+f"(d[10]),"+f"(d[11]),"+f"(d[12]),"+f"(d[13]),"+f"(d[14]),"+f"(d[15]),"+f"(d[16]),"+f"(d[17]),"+f"(d[18]),"+f"(d[19]),"+f"(d[20]),"+f"(d[21]),"+f"(d[22]),"+f"(d[23]),"+f"(d[24]),"+f"(d[25]),"+f"(d[26]),"+f"(d[27]),"+f"(d[28]),"+f"(d[29]),"+f"(d[30]),"+f"(d[31]),"+f"(d[32]),"+f"(d[33]),"+f"(d[34]),"+f"(d[35]) : "r"(a0), "r"(a1), "r"(a2), "r"(a3), "l"(db));
}
template<> __device__ __forceinline__ void wg_rs<64>(float (&d)[64], uint32_t a0, uint32_t a1, uint32_t a2, uint32_t a3, uint64_t db) {
  asm volatile("{.reg .pred p; setp.ne.b32 p, 1, 0; wgmma.mma_async.sync.aligned.m64n64k16.f32.bf16.bf16 {%0,%1,%2,%3,%4,%5,%6,%7,%8,%9,%10,%11,%12,%13,%14,%15,%16,%17,%18,%19,%20,%21,%22,%23,%24,%25,%26,%27,%28,%29,%30,%31}, {%32,%33,%34,%35}, %36, p, 1, 1, 0;}"
    : "+f"(d[0]),"+f"(d[1]),"+f"(d[2]),"+f"(d[3]),"+f"(d[4]),"+f"(d[5]),"+f"(d[6]),"+f"(d[7]),"+f"(d[8]),"+f"(d[9]),"+f"(d[10]),"+f"(d[11]),"+f"(d[12]),"+f"(d[13]),"+f"(d[14]),"+f"(d[15]),"+f"(d[16]),"+f"(d[17]),"+f"(d[18]),"+f"(d[19]),"+f"(d[20]),"+f"(d[21]),"+f"(d[22]),"+f"(d[23]),"+f"(d[24]),"+f"(d[25]),"+f"(d[26]),"+f"(d[27]),"+f"(d[28]),"+f"(d[29]),"+f"(d[30]),"+f"(d[31]) : "r"(a0), "r"(a1), "r"(a2), "r"(a3), "l"(db));
}
__device__ __forceinline__ void wg_rs_first(float (&d)[64], uint32_t a0, uint32_t a1, uint32_t a2, uint32_t a3, uint64_t db) {
  asm volatile("{.reg .pred p; setp.ne.b32 p, 0, 0; wgmma.mma_async.sync.aligned.m64n128k16.f32.bf16.bf16 {%0,%1,%2,%3,%4,%5,%6,%7,%8,%9,%10,%11,%12,%13,%14,%15,%16,%17,%18,%19,%20,%21,%22,%23,%24,%25,%26,%27,%28,%29,%30,%31,%32,%33,%34,%35,%36,%37,%38,%39,%40,%41,%42,%43,%44,%45,%46,%47,%48,%49,%50,%51,%52,%53,%54,%55,%56,%57,%58,%59,%60,%61,%62,%63}, {%64,%65,%66,%67}, %68, p, 1, 1, 0;}"
    : "=f"(d[0]),"=f"(d[1]),"=f"(d[2]),"=f"(d[3]),"=f"(d[4]),"=f"(d[5]),"=f"(d[6]),"=f"(d[7]),"=f"(d[8]),"=f"(d[9]),"=f"(d[10]),"=f"(d[11]),"=f"(d[12]),"=f"(d[13]),"=f"(d[14]),"=f"(d[15]),"=f"(d[16]),"=f"(d[17]),"=f"(d[18]),"=f"(d[19]),"=f"(d[20]),"=f"(d[21]),"=f"(d[22]),"=f"(d[23]),"=f"(d[24]),"=f"(d[25]),"=f"(d[26]),"=f"(d[27]),"=f"(d[28]),"=f"(d[29]),"=f"(d[30]),"=f"(d[31]),"=f"(d[32]),"=f"(d[33]),"=f"(d[34]),"=f"(d[35]),"=f"(d[36]),"=f"(d[37]),"=f"(d[38]),"=f"(d[39]),"=f"(d[40]),"=f"(d[41]),"=f"(d[42]),"=f"(d[43]),"=f"(d[44]),"=f"(d[45]),"=f"(d[46]),"=f"(d[47]),"=f"(d[48]),"=f"(d[49]),"=f"(d[50]),"=f"(d[51]),"=f"(d[52]),"=f"(d[53]),"=f"(d[54]),"=f"(d[55]),"=f"(d[56]),"=f"(d[57]),"=f"(d[58]),"=f"(d[59]),"=f"(d[60]),"=f"(d[61]),"=f"(d[62]),"=f"(d[63]) : "r"(a0), "r"(a1), "r"(a2), "r"(a3), "l"(db));
}
__device__ __forceinline__ void wg_kk176(float (&d)[88], uint64_t da, uint64_t db, int sc) {
  asm volatile("{.reg .pred p; setp.ne.b32 p, %90, 0; wgmma.mma_async.sync.aligned.m64n176k16.f32.bf16.bf16 {%0,%1,%2,%3,%4,%5,%6,%7,%8,%9,%10,%11,%12,%13,%14,%15,%16,%17,%18,%19,%20,%21,%22,%23,%24,%25,%26,%27,%28,%29,%30,%31,%32,%33,%34,%35,%36,%37,%38,%39,%40,%41,%42,%43,%44,%45,%46,%47,%48,%49,%50,%51,%52,%53,%54,%55,%56,%57,%58,%59,%60,%61,%62,%63,%64,%65,%66,%67,%68,%69,%70,%71,%72,%73,%74,%75,%76,%77,%78,%79,%80,%81,%82,%83,%84,%85,%86,%87}, %88, %89, p, 1, 1, 0, 0;}"
    : "+f"(d[0]),"+f"(d[1]),"+f"(d[2]),"+f"(d[3]),"+f"(d[4]),"+f"(d[5]),"+f"(d[6]),"+f"(d[7]),"+f"(d[8]),"+f"(d[9]),"+f"(d[10]),"+f"(d[11]),"+f"(d[12]),"+f"(d[13]),"+f"(d[14]),"+f"(d[15]),"+f"(d[16]),"+f"(d[17]),"+f"(d[18]),"+f"(d[19]),"+f"(d[20]),"+f"(d[21]),"+f"(d[22]),"+f"(d[23]),"+f"(d[24]),"+f"(d[25]),"+f"(d[26]),"+f"(d[27]),"+f"(d[28]),"+f"(d[29]),"+f"(d[30]),"+f"(d[31]),"+f"(d[32]),"+f"(d[33]),"+f"(d[34]),"+f"(d[35]),"+f"(d[36]),"+f"(d[37]),"+f"(d[38]),"+f"(d[39]),"+f"(d[40]),"+f"(d[41]),"+f"(d[42]),"+f"(d[43]),"+f"(d[44]),"+f"(d[45]),"+f"(d[46]),"+f"(d[47]),"+f"(d[48]),"+f"(d[49]),"+f"(d[50]),"+f"(d[51]),"+f"(d[52]),"+f"(d[53]),"+f"(d[54]),"+f"(d[55]),"+f"(d[56]),"+f"(d[57]),"+f"(d[58]),"+f"(d[59]),"+f"(d[60]),"+f"(d[61]),"+f"(d[62]),"+f"(d[63]),"+f"(d[64]),"+f"(d[65]),"+f"(d[66]),"+f"(d[67]),"+f"(d[68]),"+f"(d[69]),"+f"(d[70]),"+f"(d[71]),"+f"(d[72]),"+f"(d[73]),"+f"(d[74]),"+f"(d[75]),"+f"(d[76]),"+f"(d[77]),"+f"(d[78]),"+f"(d[79]),"+f"(d[80]),"+f"(d[81]),"+f"(d[82]),"+f"(d[83]),"+f"(d[84]),"+f"(d[85]),"+f"(d[86]),"+f"(d[87]) : "l"(da), "l"(db), "r"(sc));
}
__device__ __forceinline__ void wg_tt128(float (&d)[64], uint64_t da, uint64_t db, int sc) {
  asm volatile("{.reg .pred p; setp.ne.b32 p, %66, 0; wgmma.mma_async.sync.aligned.m64n128k16.f32.bf16.bf16 {%0,%1,%2,%3,%4,%5,%6,%7,%8,%9,%10,%11,%12,%13,%14,%15,%16,%17,%18,%19,%20,%21,%22,%23,%24,%25,%26,%27,%28,%29,%30,%31,%32,%33,%34,%35,%36,%37,%38,%39,%40,%41,%42,%43,%44,%45,%46,%47,%48,%49,%50,%51,%52,%53,%54,%55,%56,%57,%58,%59,%60,%61,%62,%63}, %64, %65, p, 1, 1, 1, 1;}"
    : "+f"(d[0]),"+f"(d[1]),"+f"(d[2]),"+f"(d[3]),"+f"(d[4]),"+f"(d[5]),"+f"(d[6]),"+f"(d[7]),"+f"(d[8]),"+f"(d[9]),"+f"(d[10]),"+f"(d[11]),"+f"(d[12]),"+f"(d[13]),"+f"(d[14]),"+f"(d[15]),"+f"(d[16]),"+f"(d[17]),"+f"(d[18]),"+f"(d[19]),"+f"(d[20]),"+f"(d[21]),"+f"(d[22]),"+f"(d[23]),"+f"(d[24]),"+f"(d[25]),"+f"(d[26]),"+f"(d[27]),"+f"(d[28]),"+f"(d[29]),"+f"(d[30]),"+f"(d[31]),"+f"(d[32]),"+f"(d[33]),"+f"(d[34]),"+f"(d[35]),"+f"(d[36]),"+f"(d[37]),"+f"(d[38]),"+f"(d[39]),"+f"(d[40]),"+f"(d[41]),"+f"(d[42]),"+f"(d[43]),"+f"(d[44]),"+f"(d[45]),"+f"(d[46]),"+f"(d[47]),"+f"(d[48]),"+f"(d[49]),"+f"(d[50]),"+f"(d[51]),"+f"(d[52]),"+f"(d[53]),"+f"(d[54]),"+f"(d[55]),"+f"(d[56]),"+f"(d[57]),"+f"(d[58]),"+f"(d[59]),"+f"(d[60]),"+f"(d[61]),"+f"(d[62]),"+f"(d[63]) : "l"(da), "l"(db), "r"(sc));
}
__device__ __forceinline__ void wg_tt64(float (&d)[64], uint64_t da, uint64_t db, int sc) {
  asm volatile("{.reg .pred p; setp.ne.b32 p, %34, 0; wgmma.mma_async.sync.aligned.m64n64k16.f32.bf16.bf16 {%0,%1,%2,%3,%4,%5,%6,%7,%8,%9,%10,%11,%12,%13,%14,%15,%16,%17,%18,%19,%20,%21,%22,%23,%24,%25,%26,%27,%28,%29,%30,%31}, %32, %33, p, 1, 1, 1, 1;}"
    : "+f"(d[0]),"+f"(d[1]),"+f"(d[2]),"+f"(d[3]),"+f"(d[4]),"+f"(d[5]),"+f"(d[6]),"+f"(d[7]),"+f"(d[8]),"+f"(d[9]),"+f"(d[10]),"+f"(d[11]),"+f"(d[12]),"+f"(d[13]),"+f"(d[14]),"+f"(d[15]),"+f"(d[16]),"+f"(d[17]),"+f"(d[18]),"+f"(d[19]),"+f"(d[20]),"+f"(d[21]),"+f"(d[22]),"+f"(d[23]),"+f"(d[24]),"+f"(d[25]),"+f"(d[26]),"+f"(d[27]),"+f"(d[28]),"+f"(d[29]),"+f"(d[30]),"+f"(d[31]) : "l"(da), "l"(db), "r"(sc));
}
__device__ __forceinline__ void wg_tt32(float (&d)[64], uint64_t da, uint64_t db, int sc) {
  asm volatile("{.reg .pred p; setp.ne.b32 p, %18, 0; wgmma.mma_async.sync.aligned.m64n32k16.f32.bf16.bf16 {%0,%1,%2,%3,%4,%5,%6,%7,%8,%9,%10,%11,%12,%13,%14,%15}, %16, %17, p, 1, 1, 1, 1;}"
    : "+f"(d[0]),"+f"(d[1]),"+f"(d[2]),"+f"(d[3]),"+f"(d[4]),"+f"(d[5]),"+f"(d[6]),"+f"(d[7]),"+f"(d[8]),"+f"(d[9]),"+f"(d[10]),"+f"(d[11]),"+f"(d[12]),"+f"(d[13]),"+f"(d[14]),"+f"(d[15]) : "l"(da), "l"(db), "r"(sc));
}
__device__ __forceinline__ void wg_g1(float (&d)[88], uint64_t da, uint64_t db, int sc) {
  asm volatile("{.reg .pred p; setp.ne.b32 p, %90, 0; wgmma.mma_async.sync.aligned.m64n176k16.f32.bf16.bf16 {%0,%1,%2,%3,%4,%5,%6,%7,%8,%9,%10,%11,%12,%13,%14,%15,%16,%17,%18,%19,%20,%21,%22,%23,%24,%25,%26,%27,%28,%29,%30,%31,%32,%33,%34,%35,%36,%37,%38,%39,%40,%41,%42,%43,%44,%45,%46,%47,%48,%49,%50,%51,%52,%53,%54,%55,%56,%57,%58,%59,%60,%61,%62,%63,%64,%65,%66,%67,%68,%69,%70,%71,%72,%73,%74,%75,%76,%77,%78,%79,%80,%81,%82,%83,%84,%85,%86,%87}, %88, %89, p, 1, 1, 1, 0;}"
    : "+f"(d[0]),"+f"(d[1]),"+f"(d[2]),"+f"(d[3]),"+f"(d[4]),"+f"(d[5]),"+f"(d[6]),"+f"(d[7]),"+f"(d[8]),"+f"(d[9]),"+f"(d[10]),"+f"(d[11]),"+f"(d[12]),"+f"(d[13]),"+f"(d[14]),"+f"(d[15]),"+f"(d[16]),"+f"(d[17]),"+f"(d[18]),"+f"(d[19]),"+f"(d[20]),"+f"(d[21]),"+f"(d[22]),"+f"(d[23]),"+f"(d[24]),"+f"(d[25]),"+f"(d[26]),"+f"(d[27]),"+f"(d[28]),"+f"(d[29]),"+f"(d[30]),"+f"(d[31]),"+f"(d[32]),"+f"(d[33]),"+f"(d[34]),"+f"(d[35]),"+f"(d[36]),"+f"(d[37]),"+f"(d[38]),"+f"(d[39]),"+f"(d[40]),"+f"(d[41]),"+f"(d[42]),"+f"(d[43]),"+f"(d[44]),"+f"(d[45]),"+f"(d[46]),"+f"(d[47]),"+f"(d[48]),"+f"(d[49]),"+f"(d[50]),"+f"(d[51]),"+f"(d[52]),"+f"(d[53]),"+f"(d[54]),"+f"(d[55]),"+f"(d[56]),"+f"(d[57]),"+f"(d[58]),"+f"(d[59]),"+f"(d[60]),"+f"(d[61]),"+f"(d[62]),"+f"(d[63]),"+f"(d[64]),"+f"(d[65]),"+f"(d[66]),"+f"(d[67]),"+f"(d[68]),"+f"(d[69]),"+f"(d[70]),"+f"(d[71]),"+f"(d[72]),"+f"(d[73]),"+f"(d[74]),"+f"(d[75]),"+f"(d[76]),"+f"(d[77]),"+f"(d[78]),"+f"(d[79]),"+f"(d[80]),"+f"(d[81]),"+f"(d[82]),"+f"(d[83]),"+f"(d[84]),"+f"(d[85]),"+f"(d[86]),"+f"(d[87]) : "l"(da), "l"(db), "r"(sc));
}

struct Params { const __nv_bfloat16 *x, *logA, *Aim, *Cr, *Ci, *logdt, *Dskip; uint4 *xnT, *mb; float* hr; uint2* S; unsigned* flags; };
struct Maps { CUtensorMap x[2], xo, out, wg, wu, wd, hst[2], hld; };

__device__ __forceinline__ void conv_channel(uint32_t cb, int w, int lane, uint32_t (&res)[8], uint32_t bar_free) {
    const int q = lane & 3, g = lane >> 2, gam = g >> 2;
    float acc[64];
    uint4 a[4][4];
    const uint32_t t0 = cb + CH_T + (uint32_t)(14 + 4 * w + (g & 3) + 32 * gam - 2 * q) * 80u;
    #pragma unroll
    for (int s4 = 0; s4 < 4; s4++) {
        a[s4][0] = lds128(t0 + s4 * 16);
        a[s4][1] = lds128(t0 + 16 * 80 + s4 * 16);
        a[s4][2] = lds128(t0 - 8 * 80 + s4 * 16);
        a[s4][3] = lds128(t0 + 8 * 80 + s4 * 16);
    }
    const uint32_t l0 = FU(ldsf(t0 + 64)), l1 = FU(ldsf(t0 + 16 * 80 + 64)), l2 = FU(ldsf(t0 - 8 * 80 + 64)), l3 = FU(ldsf(t0 + 8 * 80 + 64));
    const uint64_t dU = mkdesc(cb + CH_U, UPLANE, 128, 0);
    WG_FENCE();
#define CT(N, s, c) wg_rs<N>(acc, a[(s) >> 2][0].c, a[(s) >> 2][1].c, a[(s) >> 2][2].c, a[(s) >> 2][3].c, dU + 4 * (s))
    wg_rs_first(acc, a[0][0].x, a[0][1].x, a[0][2].x, a[0][3].x, dU);
    CT(128, 1, y); CT(120, 2, z); CT(120, 3, w);
    CT(112, 4, x); CT(112, 5, y); CT(104, 6, z); CT(104, 7, w);
    CT(96, 8, x);  CT(96, 9, y);  CT(88, 10, z); CT(88, 11, w);
    CT(80, 12, x); CT(80, 13, y); CT(72, 14, z); CT(72, 15, w);
#undef CT
    wg_rs<64>(acc, l0, l1, l2, l3, dU + 64);
    wg_tt64(acc, mkdesc(cb + CH_A3, 128, 512, 0), mkdesc(cb + CH_B3, 128, 256, 0), 1);
    wg_tt32(acc, mkdesc(cb + CH_A3 + 256, 128, 512, 0), mkdesc(cb + CH_B3 + 1024, 128, 256, 0), 1);
    WG_COMMIT();
    WG_WAIT(0);
    fence_acc(acc);
    if (bar_free && lane == 0) mbar_arrive(bar_free);
    const int src1 = (lane & ~3) | ((q + 1) & 3);
    float E[16][2];
    #pragma unroll
    for (int j = 0; j < 16; j++) {
        const float nxt = (j < 15) ? acc[4 * (j + 1) + 2] : 0.f;
        const float sup = (q == 0) ? nxt : acc[4 * j + 2];
        const float v = __shfl_sync(0xffffffffu, sup, src1);
        E[j][0] = acc[4 * j] + acc[4 * j + 3];
        E[j][1] = acc[4 * j + 1] + v;
    }
    const int src2 = gam ? ((lane & 12) | ((q + 3) & 3)) : (16 | (lane & 12) | ((q + 1) & 3));
    const bool c1 = gam && q != 0, c2 = gam && q == 0;
    #pragma unroll
    for (int a2 = 0; a2 < 8; a2++) {
        float y[2];
        #pragma unroll
        for (int e = 0; e < 2; e++) {
            const float sup = c1 ? E[2 * a2][e] : E[2 * a2 + 1][e];
            const float nxt = (a2 < 7) ? E[2 * a2 + 2][e] : 0.f;
            const float keep = c2 ? nxt : (c1 ? E[2 * a2 + 1][e] : E[2 * a2][e]);
            y[e] = keep + __shfl_sync(0xffffffffu, sup, src2);
        }
        res[a2] = pack2(y[1], y[0]);
    }
}

__device__ __forceinline__ void consumer(uint32_t sb, int warp, const Params& P, const Maps& M) {
    const int V = warp >> 2, w = warp & 3, lane = threadIdx.x & 31, q = lane & 3, g = lane >> 2;
    const int c = blockIdx.x;
    const uint32_t bars = sb + OFF_BAR, xb = sb + OFF_X + V * 2 * XBUF;
    {
        float ag[88], au[88];
        define_acc(ag); define_acc(au);
        if (V == 0) {
            sts128(xb + (w >> 1) * XBUF + 168 * 128 + (threadIdx.x & 63) * 16, 0x3f803f80u, 0x3f803f80u, 0x3f803f80u, 0x3f803f80u);
            fence_async_smem();
            bar_sync(1);
        } else mbar_wait(bars + 8 * B_GO, 0);
        #pragma unroll 1
        for (int st = 0; st < 8; st++) {
            if (st + V == HOLD0 || st + V == HOLD1) mbar_wait(bars + 8 * (B_K + (st + V == HOLD1)), 0);
            mbar_wait(bars + 8 * (B_FULLW + (st & 3)), st >> 2);
            mbar_wait(bars + 8 * (B_FULLX + 2 * V + (st & 1)), (st >> 1) & 1);
            STAMP(40 + 8 * V + st);
            const uint64_t dG = mkdesc(sb + OFF_W + (st & 3) * 16384, 0, 1024, 1);
            const uint64_t dX = mkdesc(xb + (st & 1) * XBUF, 16, 1024, 1);
            WG_FENCE();
            #pragma unroll
            for (int k = 0; k < 4; k++) {
                wg_g1(ag, dG + k * 128, dX + k * 2, k ? 1 : st);
                wg_g1(au, dG + 512 + k * 128, dX + k * 2, k ? 1 : st);
            }
            WG_COMMIT();
            WG_WAIT(1);
            if (lane == 0 && st > 0) {
                mbar_arrive(bars + 8 * (B_EMPTYW + ((st - 1) & 3)));
                mbar_arrive(bars + 8 * (B_EMPTYX + 2 * V + ((st - 1) & 1)));
                if (warp < 4 && st == 1) mbar_arrive(bars + 8 * B_GO);
            }
        }
        WG_WAIT(0);
        fence_acc(ag); fence_acc(au);
        if (lane == 0) { mbar_arrive(bars + 8 * (B_EMPTYW + 3)); mbar_arrive(bars + 8 * (B_EMPTYX + 2 * V + 1)); }
        STAMP(8 * V + 1);
        {
            if (V == 0) {
                const float cv = (q & 2) ? ((q & 1) ? au[86] : au[84]) : ((q & 1) ? ag[86] : ag[84]), hi = bf_round(cv);
                sts128(sb + OFF_CSUM + (16 * w + g + 8 * (q & 1) + 32 * (q & 2)) * 16, pack2(hi, cv - hi), 0, 0, 0);
                fence_async_smem();
                mbar_arrive(bars + 8 * B_CS);
            }
            mbar_wait(bars + 8 * B_CS, 0);
            mbar_wait(bars + 8 * B_STATS, 0);
            const uint64_t dM = mkdesc(sb + OFF_MB + V * 168 * 16, 0, 128, 0), dC = mkdesc(sb + OFF_CSUM, 0, 128, 0);
            WG_FENCE();
            wg_kk176(ag, dC, dM, 1);
            wg_kk176(au, dC + 64, dM, 1);
            WG_COMMIT();
            mbar_wait(bars + 8 * (B_EMPTYX + 2 * V), 1);
            WG_WAIT(0);
            fence_acc(ag); fence_acc(au);
        }
        const uint32_t hs = xb + (2 * w + ((lane >> 3) & 1)) * (2688 + 128 * V) + (lane >> 4) * 128 + (lane & 7) * 16;
        const uint32_t hr = sb + OFF_HR + (168 * V + 2 * q) * 4;
        #pragma unroll
        for (int j = 0; j < 22; j += 2) {
            uint32_t o[4];
            #pragma unroll
            for (int jj = 0; jj < 2; jj++) {
                const uint2 rv = lds64(hr + (j + jj) * 32);
                float hv[4];
                #pragma unroll
                for (int i = 0; i < 4; i++) {
                    const float gh = ag[4 * (j + jj) + i] * UF((i & 1) ? rv.y : rv.x);
                    const float p = gh * au[4 * (j + jj) + i];
                    hv[i] = fmaf(p, tanh_fast(gh), p);
                }
                o[2 * jj] = pack2(hv[0], hv[1]); o[2 * jj + 1] = pack2(hv[2], hv[3]);
            }
            uint32_t ad = hs + j * 128;
            if (j == 20 && V == 0 && lane >= 16) ad = xb + 21504 + (lane & 7) * 16;
            stsm4(ad, o[0], o[1], o[2], o[3]);
        }
        fence_async_smem();
        mbar_arrive(bars + 8 * (B_EPI + V));
        STAMP(8 * V + 2);
    }
    if (c >= 128) return;
    {
        mbar_wait(bars + 8 * B_CONV, 0);
        uint32_t r0[8], r1[8];
        #pragma unroll
        for (int i = 0; i < 8; i++) asm volatile("" : "=r"(r1[i]));
        #pragma unroll 1
        for (int e = 0; e < 2; e++) {
            #pragma unroll
            for (int i = 0; i < 8; i++) r0[i] = r1[i];
            conv_channel(sb + OFF_CONV + (2 * V + e) * CH_STRIDE, w, lane, r1, (V + e == 0) ? bars + 8 * B_CH0 : 0);
            if (e == 0) STAMP(8 * V + 3);
        }
        const int gam = g >> 2, qq = gam ? ((q + 3) & 3) : q;
        uint2* sp = P.S + (2 * c + V) * 1024 + (63 - 4 * gam - qq) * 16 + 4 * w + (g & 3);
        #pragma unroll
        for (int a2 = 0; a2 < 8; a2++) sp[-a2 * 128] = make_uint2(r0[a2], r1[a2]);
        mbar_arrive(bars + 8 * (B_SIG + V));
        STAMP(8 * V + 4);
    }
    if (V == 1) return;
    {
        const int tau = c >> 2, dg = c & 3;
        const uint32_t row = 8 * (w & 1) + 32 * (w >> 1);
        float acc[64];
        define_acc(acc);
        uint2 sv[16];
        #pragma unroll
        for (int i = 0; i < 16; i++) asm volatile("" : "=r"(sv[i].x), "=r"(sv[i].y));
        const float rr0 = __ldcg(P.hr + 64 * tau + row + g), rr1 = __ldcg(P.hr + 64 * tau + row + g + 16);
        int sd = 0; uint32_t pd = 0;
        mbar_wait(bars + 8 * B_FULLD, 0);
        STAMP(5);
        uint64_t dB = mkdesc(sb + wd_slot(0), 8192, 1024, 1), dA = mkdesc(sb + h_slot(0), 1024, 128, 0);
        #pragma unroll 1
        for (int st = 0; st < 21; st++) {
            WG_FENCE();
            wg_tt128(acc, dA, dB, st);
            wg_tt128(acc, dA + 128, dB + 128, 1);
            wg_tt128(acc, dA + 256, dB + 256, 1);
            wg_tt128(acc, dA + 384, dB + 384, 1);
            WG_COMMIT();
            const uint32_t rel = bars + 8 * (B_EMPTYD + (sd ? sd - 1 : 5));
            if (++sd == 6) { sd = 0; pd ^= 1; }
            mbar_wait(bars + 8 * (B_FULLD + sd), pd);
            dB = mkdesc(sb + wd_slot(sd), 8192, 1024, 1); dA = mkdesc(sb + h_slot(sd), 1024, 128, 0);
            if (st == 14) {
                mbar_wait(bars + 8 * B_S, 0);
                const uint2* sp = P.S + (dg * 64 + q) * 1024 + (2 * tau) * 16 + (row >> 1) + 4 * (w & 1) + g;
                #pragma unroll
                for (int j = 0; j < 16; j++)
                    asm volatile("ld.global.cg.v2.b32 {%0,%1}, [%2];" : "=r"(sv[j].x), "=r"(sv[j].y) : "l"(sp + j * 4096));
            }
            WG_WAIT(1);
            if (lane == 0 && st > 0) mbar_arrive(rel);
        }
        WG_FENCE();
        wg_tt128(acc, dA, dB, 1);
        wg_tt128(acc, dA + 128, dB + 128, 1);
        WG_COMMIT();
        WG_WAIT(0);
        fence_acc(acc);
        STAMP(6);
        mbar_wait(bars + 8 * B_XO, 0);
        const uint32_t xo = sb + OFF_CONV + (row + (lane & 7) + 16 * ((lane >> 3) & 1)) * 128;
        #pragma unroll
        for (int j = 0; j < 16; j += 2) {
            const uint32_t ad = xo + (j >> 3) * 8192 + ((((j & 7) + (lane >> 4)) ^ (lane & 7)) << 4);
            uint32_t xr[4];
            asm volatile("ldmatrix.sync.aligned.m8n8.x4.shared.b16 {%0,%1,%2,%3}, [%4];" : "=r"(xr[0]), "=r"(xr[1]), "=r"(xr[2]), "=r"(xr[3]) : "r"(ad));
            #pragma unroll
            for (int i = 0; i < 4; i++) {
                const int jj = j + (i >> 1), hh = i & 1;
                const float f0 = acc[4 * jj + 2 * hh] * (hh ? rr1 : rr0), f1 = acc[4 * jj + 2 * hh + 1] * (hh ? rr1 : rr0);
                const uint32_t G = pack2(fmaf(f0, tanh_fast(f0), f0), fmaf(f1, tanh_fast(f1), f1));
                const uint32_t s2 = __byte_perm(sv[jj].x, sv[jj].y, hh ? 0x7632 : 0x5410);
                asm("fma.rn.bf16x2 %0, %1, %2, %0;" : "+r"(xr[i]) : "r"(s2), "r"(G));
            }
            stsm4(ad, xr[0], xr[1], xr[2], xr[3]);
        }
        fence_async_smem();
        bar_sync(1);
        if (w == 0 && elect_one()) {
            #pragma unroll
            for (int i = 0; i < 2; i++)
                asm volatile("cp.async.bulk.tensor.2d.global.shared::cta.bulk_group [%0, {%2, %3}], [%1];"
                    :: "l"(&M.out), "r"(sb + OFF_CONV + i * 8192), "r"(dg * 128 + 64 * i), "r"(tau * 64) : "memory");
            asm volatile("cp.async.bulk.commit_group; cp.async.bulk.wait_group.read 0;" ::: "memory");
        }
        STAMP(7);
    }
}

__device__ __forceinline__ float2 cexp_p(float re2, float im, float p) {
    float sn, cs;
    const float mag = ex2(re2 * p), th = im * p;
    asm("sin.approx.ftz.f32 %0, %1;" : "=f"(sn) : "f"(th));
    asm("cos.approx.ftz.f32 %0, %1;" : "=f"(cs) : "f"(th));
    return make_float2(mag * cs, mag * sn);
}
__device__ __forceinline__ void ldsm4(uint32_t (&r)[4], uint32_t a) {
    asm volatile("ldmatrix.sync.aligned.m8n8.x4.shared.b16 {%0,%1,%2,%3}, [%4];" : "=r"(r[0]), "=r"(r[1]), "=r"(r[2]), "=r"(r[3]) : "r"(a) : "memory");
}
__device__ __forceinline__ float2 cmul(float2 a, float2 b) { return make_float2(fmaf(a.x, b.x, -a.y * b.y), fmaf(a.x, b.y, a.y * b.x)); }
__device__ __forceinline__ float2 csqr(float2 a) { const float t = a.x * a.y; return make_float2(fmaf(a.x, a.x, -a.y * a.y), t + t); }
__device__ __forceinline__ void mma16816(float (&d)[4], const uint32_t (&a)[4], uint32_t b0, uint32_t b1) {
    asm volatile("mma.sync.aligned.m16n8k16.row.col.f32.bf16.bf16.f32 {%0,%1,%2,%3}, {%4,%5,%6,%7}, {%8,%9}, {%0,%1,%2,%3};"
        : "+f"(d[0]), "+f"(d[1]), "+f"(d[2]), "+f"(d[3]) : "r"(a[0]), "r"(a[1]), "r"(a[2]), "r"(a[3]), "r"(b0), "r"(b1));
}

__device__ __forceinline__ void aux_role(uint32_t sb, int w, const Params& P) {
    const int tid = threadIdx.x & 127, lane = tid & 31, q = lane & 3, g = lane >> 2;
    const int c = blockIdx.x;
    const uint32_t bars = sb + OFF_BAR;
    if (c < 128) {
        const uint32_t cb = sb + OFF_CONV + w * CH_STRIDE;
        const uint32_t sF = cb + CH_A3;
        const int tokb = 32 * (c >> 1) + 8 * (c & 1) + 16;
        if (elect_one()) {
            mbar_expect(bars + 8 * B_LNX, 4096);
            #pragma unroll
            for (int i = 0; i < 4; i++)
                bulk_load(sb + OFF_CONV + (w + 4 * i) * LNROW, P.x + (tokb + w + 4 * (i & 1) - 8 * (i & 2)) * DM, 1024, bars + 8 * B_LNX);
        }
        const int d = 4 * c + w;
        const uint2 la2 = *(const uint2*)(P.logA + d * 128 + 4 * lane), ai2 = *(const uint2*)(P.Aim + d * 128 + 4 * lane);
        const uint2 cr2 = *(const uint2*)(P.Cr + d * 128 + 4 * lane), ci2 = *(const uint2*)(P.Ci + d * 128 + 4 * lane);
        const float ldt = __bfloat162float(P.logdt[d]), dsk = __bfloat162float(P.Dskip[d]);
        mbar_wait(bars + 8 * B_LNX, 0);
        STAMP(34);
        {
            const int r = w + 4 * (lane >> 3);
            const uint32_t ra = sb + OFF_CONV + r * LNROW + (lane & 7) * 16;
            const float pv = bf_lo(FU(ldsf(sb + OFF_CONV + r * LNROW)));
            float s0 = 0.f, s1 = 0.f, a0 = 0.f, a1 = 0.f;
            uint4 nx = lds128(ra);
            #pragma unroll 1
            for (int k = 128; k <= 1024; k += 128) {
                const uint32_t v[4] = {nx.x, nx.y, nx.z, nx.w};
                nx = lds128(ra + (k & 1023));
                #pragma unroll
                for (int i = 0; i < 4; i++) { const float t0 = bf_lo(v[i]) - pv, t1 = bf_hi(v[i]) - pv; s0 += t0; s1 += t1; a0 = fmaf(t0, t0, a0); a1 = fmaf(t1, t1, a1); }
            }
            s0 += s1; a0 += a1;
            #pragma unroll
            for (int o = 4; o; o >>= 1) { s0 += __shfl_xor_sync(0xffffffffu, s0, o); a0 += __shfl_xor_sync(0xffffffffu, a0, o); }
            s0 *= 1.f / DM;
            const float m = pv + s0, var = fmaxf(fmaf(-s0, s0, a0 * (1.f / DM)), 0.f);
            float sd, ri;
            asm("sqrt.approx.ftz.f32 %0, %1;" : "=f"(sd) : "f"(bf_round(bf_round(var) + 1e-5f)));
            asm("rcp.approx.ftz.f32 %0, %1;" : "=f"(ri) : "f"(bf_round(sd)));
            const uint32_t m2 = pack2(m, m);
            if ((lane & 7) == 0) {
                const int t = tokb + (r & 7) - 2 * (r & 8);
                const float mh = -0.5f * bf_hi(m2);
                P.mb[t] = make_uint4(pack2(mh, mh), 0, 0, 0); P.hr[t] = 0.5f * ri;
            }
            #pragma unroll 1
            for (int k = 128; k <= 1024; k += 128) {
                uint32_t v[4] = {nx.x, nx.y, nx.z, nx.w};
                nx = lds128(ra + (k & 1023));
                #pragma unroll
                for (int i = 0; i < 4; i++) {
                    uint32_t dv; asm("sub.rn.bf16x2 %0, %1, %2;" : "=r"(dv) : "r"(v[i]), "r"(m2));
                    v[i] = pack2(bf_lo(dv) * ri, bf_hi(dv) * ri);
                }
                sts128(ra + k - 128, v[0], v[1], v[2], v[3]);
            }
        }
        STAMP(62);
        bar_sync(2);
        {
            uint32_t ad = sb + OFF_CONV + (4 * ((lane & 7) >> 1) + (lane & 1) + 2 * ((lane >> 3) & 1)) * LNROW + (16 * w + (lane >> 4)) * 16;
            uint2* dst = (uint2*)(P.xnT + (128 * w + g) * 256 + (c & 1) * 128 + (126 - 2 * (c >> 1))) + q;
            #pragma unroll
            for (int i = 0; i < 8; i++, ad += 32, dst += 16 * 512) {
                uint32_t r0, r1, r2, r3;
                asm volatile("ldmatrix.sync.aligned.m8n8.x4.trans.shared.b16 {%0,%1,%2,%3}, [%4];" : "=r"(r0), "=r"(r1), "=r"(r2), "=r"(r3) : "r"(ad));
                dst[0] = make_uint2(r0, r1); dst[8 * 512] = make_uint2(r2, r3);
            }
        }
        mbar_arrive(bars + 8 * B_LN);
        bar_sync(2);
        STAMP(16);
        float dacc[2][3][4];
        #pragma unroll
        for (int i = 0; i < 24; i++) (&dacc[0][0][0])[i] = 0.f;
        const float dt = bf_round(ex2(ldt * 1.4426950408889634f));
        const uint32_t lda = cb + ((lane & 7) + 8 * ((lane >> 3) & 1)) * 144 + (lane >> 4) * 16;
        const uint32_t ldb = cb + (32 + (lane & 7)) * 144 + (lane >> 3) * 16;
        uint64_t la = *(const uint64_t*)&la2, ai = *(const uint64_t*)&ai2, cr = *(const uint64_t*)&cr2, ci = *(const uint64_t*)&ci2;
        #pragma unroll 1
        for (int ck = 0; ck < 4; ck++, la >>= 16, ai >>= 16, cr >>= 16, ci >>= 16) {
            const uint32_t fa = cb + lane * 4 + (ck & 1) * 8064;
            const float re2 = bf_round(ex2(bf_lo((uint32_t)la) * 1.4426950408889634f)) * dt * -1.4426950408889634f, im = bf_lo((uint32_t)ai) * dt;
            const float2 C = make_float2(bf_lo((uint32_t)cr) * (dt + dt), bf_lo((uint32_t)ci) * -(dt + dt));
            const float2 z8 = cexp_p(re2, im, 8.f), y1 = cexp_p(re2, -im, 1.f), y256 = cexp_p(re2, -im, 256.f);
            float2 b0 = make_float2(1.f, 0.f), b1 = cexp_p(re2, im, 64.f), b2 = csqr(b1), b3 = cmul(b2, b1), l0 = C;
            #pragma unroll 1
            for (uint32_t ra = fa; ra < fa + 8 * 144; ra += 144) {
                asm volatile("st.shared.b32 [%0], %1; st.shared.b32 [%0 + 1152], %2; st.shared.b32 [%0 + 2304], %3; st.shared.b32 [%0 + 3456], %4; st.shared.b32 [%0 + 4608], %5;"
                    :: "r"(ra), "r"(pack2(b0.x, b0.y)), "r"(pack2(b1.x, b1.y)), "r"(pack2(b2.x, b2.y)), "r"(pack2(b3.x, b3.y)), "r"(pack2(l0.x, l0.y)) : "memory");
                b0 = cmul(b0, z8); b1 = cmul(b1, z8); b2 = cmul(b2, z8); b3 = cmul(b3, z8); l0 = cmul(l0, y1);
            }
            if (ck < 2) STAMP(56 + 3 * ck);
            const float2 y2 = csqr(y1), y4 = csqr(y2), y8 = make_float2(z8.x, -z8.y);
#define PUT(r, v) stsf(fa + (32 + (r)) * 144, UF(pack2((v).x, (v).y)))
            float2 t = cmul(C, y256), u = t;
            PUT(8, u); u = cmul(u, y2); PUT(9, u); u = cmul(u, y2); PUT(10, u); u = cmul(u, y2); PUT(11, u);
            t = cmul(t, y256); PUT(12, t); u = cmul(t, y4); PUT(13, u);
            t = cmul(t, y256); PUT(14, t); u = cmul(t, y4); PUT(15, u);
            t = cmul(t, y256); PUT(20, t); t = cmul(t, y8); PUT(16, t);
            t = cmul(t, y256); PUT(17, t); t = cmul(t, y256); PUT(18, t); t = cmul(t, y256); PUT(19, t);
#undef PUT
            if (ck < 2) STAMP(57 + 3 * ck);
            if (ck & 1) {
                __syncwarp();
                #pragma unroll
                for (int k2 = 0; k2 < 4; k2++) {
                    const uint32_t ko = (k2 >> 1) * 8064 + (k2 & 1) * 64;
                    uint32_t b[3][4];
                    #pragma unroll
                    for (int t3 = 0; t3 < 3; t3++) ldsm4(b[t3], ldb + t3 * 8 * 144 + ko);
                    #pragma unroll
                    for (int k = 0; k < 2; k++)
                        #pragma unroll
                        for (int mu = 0; mu < 2; mu++) {
                            uint32_t a[4];
                            ldsm4(a, lda + mu * 16 * 144 + ko + k * 32);
                            #pragma unroll
                            for (int t3 = 0; t3 < 3; t3++) mma16816(dacc[mu][t3], a, b[t3][2 * k], b[t3][2 * k + 1]);
                        }
                }
                __syncwarp();
                if (lane == 0) mbar_arrive(bars + 8 * (B_K + (ck >> 1)));
                STAMP(58 + 3 * (ck >> 1));
            }
        }
        STAMP(18);
        const uint32_t sG = cb + CH_G;
        if (lane < 16) sts128(((lane & 8) ? cb + CH_U + 2048 + (lane & 4) * (UPLANE / 4) : sG + 128 + (lane & 4) * 48) + (lane & 3) * 16, 0, 0, 0, 0);
        {
            const uint32_t f0 = sF + (8 * g + 2 * q) * 4, f1 = sF + ((q < 2) ? 256 + 4 * g + 2 * q : 256 + 2 * g + 64 * q) * 4, st1 = (q < 2) ? 128 : 64;
            const uint32_t ga = sG + ((g & 1) ? 0 : 192) + (63 - (g >> 1) - 32 * q) * 2;
            #pragma unroll
            for (int i = 0; i < 4; i++) {
                const int mu = i >> 1, hh = i & 1;
                sts64(f0 + i * 256, FU(dacc[mu][0][2 * hh]), FU(dacc[mu][0][2 * hh + 1]));
                sts64(f1 + i * st1, FU(dacc[mu][1][2 * hh]), FU(dacc[mu][1][2 * hh + 1]));
                const uint32_t pk = pack2(dacc[mu][2][2 * hh], dacc[mu][2][2 * hh + 1]);
                if (q < 2) { sts16(ga - 8 * i, pk & 0xffff); sts16(ga - 8 * i - 32, pk >> 16); }
            }
            if (lane == 2) stsf(sF + 2048, dacc[0][2][0]);
        }
        __syncwarp();
        #pragma unroll 1
        for (int pass = 0; pass < 3; pass++) {
            const int rw = lane - 1 + 31 * pass;
            const int u = min(rw, 77) - 14;
            const uint32_t f0 = sF + u * 4, f1 = sF + (128 + ((u + ((u >> 1) & 1)) >> 1)) * 4, f2 = sF + (256 + ((u + 1 + ((u >> 2) & 1)) >> 2)) * 4;
            float kv[17];
            kv[0] = ldsf(u < 0 ? sF : f0); if (u < 0) kv[0] = 0.f; if (u == 0) kv[0] += dsk;
            #pragma unroll
            for (int s = 1; s < 4; s++) kv[s] = ldsf(f0 + s * 256);
            kv[4] = ldsf(u < 0 ? f0 + 1024 : f1 + 512);
            #pragma unroll
            for (int s = 5; s < 8; s++) kv[s] = ldsf(f1 + s * 128);
            kv[8] = ldsf(u < 0 ? f1 + 1024 : f2 + 512);
            #pragma unroll
            for (int s = 9; s < 16; s++) kv[s] = ldsf(f2 + s * 64);
            kv[16] = ldsf(u < 0 ? f2 + 1024 : sF + 2048); if (u > 4) kv[16] = 0.f;
            uint32_t o[17];
            #pragma unroll
            for (int s = 0; s < 17; s++) o[s] = pack2(kv[s], __shfl_up_sync(0xffffffffu, kv[s], 1));
            if (lane > 0 && rw < 78) {
                const uint32_t ta = cb + CH_T + rw * 80;
                #pragma unroll
                for (int s4 = 0; s4 < 4; s4++) sts128(ta + s4 * 16, o[4 * s4], o[4 * s4 + 1], o[4 * s4 + 2], o[4 * s4 + 3]);
                stsf(ta + 64, UF(o[16]));
            }
        }
        #pragma unroll 1
        for (int un = lane; un < 128; un += 32) {
            const uint32_t ga = sG + ((un >> 3) & 1) * 192 + (un >> 4) * 16 + (un & 7) * 8;
            const uint2 x0 = lds64(ga), x1 = lds64(ga + 8);
            sts128(cb + CH_B3 + un * 16, x0.x, x0.y, x1.x, x1.y);
        }
    } else {
        mbar_arrive(bars + 8 * B_LN);
        if (lane == 0) { mbar_arrive(bars + 8 * B_K); mbar_arrive(bars + 8 * (B_K + 1)); }
        return;
    }
    STAMP(19);
    bar_sync(2);
    mbar_wait(bars + 8 * B_U, 0);
    {
        const int kap = (lane >> 4) * 8 + ((lane >> 1) & 7), gam = lane & 1, hh = w >> 1, wp = w & 1;
        uint32_t ua = sb + OFF_CONV + CH_U + wp * UPLANE + (127 - 4 * kap - 2 * gam - hh) * 16;
        uint32_t ub = sb + OFF_CONV + CH_U + (wp ^ 1) * UPLANE + (128 - wp - 4 * kap - 2 * gam - hh) * 16;
        uint32_t ad = sb + OFF_CONV + CH_A3 + (4 * wp + hh) * 512 + (kap >> 3) * 256 + (kap & 7) * 16 + gam * 8;
        #pragma unroll 1
        for (int ch = 0; ch < 4; ch++, ua += CH_STRIDE, ub += CH_STRIDE, ad += CH_STRIDE) {
            float p[24];
            const uint2 r0 = lds64(ub + 24), r3 = lds64(ua);
            uint32_t r[8];
            *(uint4*)&r[0] = lds128(ua + 16); *(uint4*)&r[4] = lds128(ub);
            p[0] = 0.f;
            p[1] = bf_lo(r0.x); p[2] = p[1] + bf_hi(r0.x); p[3] = p[2] + bf_lo(r0.y); p[4] = p[3] + bf_hi(r0.y);
            #pragma unroll
            for (int i = 0; i < 8; i++) { p[5 + 2 * i] = p[4 + 2 * i] + bf_lo(r[i]); p[6 + 2 * i] = p[5 + 2 * i] + bf_hi(r[i]); }
            p[21] = p[20] + bf_lo(r3.x); p[22] = p[21] + bf_hi(r3.x); p[23] = p[22] + bf_lo(r3.y);
            #pragma unroll
            for (int i = 0; i < 8; i += 4) {
                sts64(ad + i * 256, pack2(p[i + 9] - p[i], p[i + 10] - p[i + 1]), pack2(p[i + 11] - p[i + 2], p[i + 12] - p[i + 3]));
                sts64(ad + i * 256 + 128, pack2(p[i + 16] - p[i + 9], p[i + 17] - p[i + 10]), pack2(p[i + 18] - p[i + 11], p[i + 19] - p[i + 12]));
            }
        }
    }
    fence_async_smem();
    mbar_arrive(bars + 8 * B_CONV);
    STAMP(21);
}

__global__ void __launch_bounds__(512, 1)
fused_kernel(const __grid_constant__ Params P, const __grid_constant__ Maps M) {
    extern __shared__ __align__(1024) uint8_t smem_raw[];
    const uint32_t sb = smem_u32(smem_raw);
    const uint32_t bars = sb + OFF_BAR;
    const int warp = __shfl_sync(0xffffffffu, threadIdx.x >> 5, 0);
    if (elect_one()) {
        if (warp == 0) STAMP(24);
        if (warp < 10) asm volatile("prefetch.tensormap [%0];" :: "l"(&M.x[0] + warp) : "memory");
        #pragma unroll
        for (int k = 0; k < 3; k++) {
            const int i = 3 * warp + k;
            const uint32_t cnt = i >= B_CONV ? 128 : ((0xf0ull >> i) & 1) ? 8 : ((0x3f0000ull >> i) & 1) ? 2 : ((0xf80fc0f000ull >> i) & 1) ? 4 : 1;
            asm volatile("mbarrier.init.shared::cta.b64 [%0], %1;" :: "r"(bars + 8 * i), "r"(cnt) : "memory");
        }
        asm volatile("fence.mbarrier_init.release.cluster;" ::: "memory");
        if (sb & 1023) __trap();
    }
    __syncthreads();
    if (warp < 8) {
        asm volatile("setmaxnreg.inc.sync.aligned.u32 208;");
        consumer(sb, warp, P, M);
    } else if (warp < 12) {
        asm volatile("setmaxnreg.dec.sync.aligned.u32 72;");
        STAMP(32);
        aux_role(sb, warp - 8, P);
    } else {
        asm volatile("setmaxnreg.dec.sync.aligned.u32 24;");
        const int c = blockIdx.x, tg = c / 22, fb = c - 22 * tg, tau = c >> 2, dg = c & 3;
        if (elect_one()) {
            if (warp == 12) {
                #pragma unroll 1
                for (int st = 0; st < 8; st++) {
                    const uint32_t s = st & 3, fb_ = bars + 8 * (B_FULLW + s);
                    mbar_wait(bars + 8 * (B_EMPTYW + s), (st >> 2) ^ 1);
                    mbar_expect(fb_, 16384);
                    tma2d(sb + OFF_W + s * 16384, &M.wg, 64 * fb, 64 * st, fb_);
                    tma2d(sb + OFF_W + s * 16384 + 8192, &M.wu, 64 * fb, 64 * st, fb_);
                    if (st == 0) STAMP(31);
                }
                if (c < 128) {
                    int sd = 0; uint32_t pe = 1;
                    #pragma unroll 1
                    for (int st = 0; st < 22; st++) {
                        if (st < 6) mbar_wait(bars + 8 * (uint32_t)((0x1f070d060504ull >> (8 * st)) & 0xff), st < 5);
                        else mbar_wait(bars + 8 * (B_EMPTYD + sd), pe);
                        const uint32_t da = sb + wd_slot(sd), fb_ = bars + 8 * (B_FULLD + sd);
                        mbar_expect(fb_, 16384);
                        tma2d(da, &M.wd, 128 * dg, 64 * st, fb_);
                        tma2d(da + 8192, &M.wd, 128 * dg + 64, 64 * st, fb_);
                        if (++sd == 6) { sd = 0; pe ^= 1; }
                    }
                }
            } else if (warp < 15) {
                const int V = warp - 13;
                #pragma unroll 1
                for (int st = 0; st < 8; st++) {
                    const uint32_t s = 2 * V + (st & 1);
                    mbar_wait(bars + 8 * (B_EMPTYX + s), ((st >> 1) & 1) ^ 1);
                    mbar_expect(bars + 8 * (B_FULLX + s), (168 + 8 * V) * 128);
                    tma2d(sb + OFF_X + s * XBUF, &M.x[V], 64 * st, TOKG * tg + 168 * V, bars + 8 * (B_FULLX + s));
                }
                if (c < 128) {
                    if (V == 0) {
                        mbar_wait(bars + 8 * (B_STG + 1), 0);
                        #pragma unroll 1
                        for (int o = 8 * tau; o < 8 * tau + 8; o += 7) flag_wait(P.flags, F_H + 2 * (o / 43) + ((o % 43) >= 21), 22);
                        fence_async();
                        mbar_arrive(bars + 8 * B_HF);
                        STAMP(25);
                        int sh = 0; uint32_t pe = 1;
                        #pragma unroll 1
                        for (int st = 0; st < 22; st++) {
                            const uint32_t fb_ = bars + 8 * (B_FULLD + sh);
                            mbar_wait(bars + 8 * (B_EMPTYD + sh), pe);
                            mbar_expect(fb_, 8192);
                            asm volatile("cp.async.bulk.tensor.5d.shared::cluster.global.mbarrier::complete_tx::bytes [%0], [%1, {%3, %3, %3, %4, %5}], [%2];"
                                :: "r"(sb + h_slot(sh)), "l"(&M.hld), "r"(fb_), "r"(0), "r"(2 * tau), "r"(8 * st) : "memory");
                            if (++sh == 6) { sh = 0; pe ^= 1; }
                        }
                    } else {
                        mbar_wait(bars + 8 * B_CH0, 0);
                        mbar_expect(bars + 8 * B_XO, 16384);
                        tma2d(sb + OFF_CONV, &M.xo, 128 * dg, 64 * tau, bars + 8 * B_XO);
                        tma2d(sb + OFF_CONV + 8192, &M.xo, 128 * dg + 64, 64 * tau, bars + 8 * B_XO);
                        flag_wait(P.flags, F_S + dg, 64);
                        STAMP(26);
                        mbar_arrive(bars + 8 * B_S);
                        mbar_wait(bars + 8 * B_HF, 0);
                        exit_count(P.flags);
                    }
                }
            } else {
                mbar_wait(bars + 8 * B_LN, 0);
                flag_signal(P.flags, F_A);
                flag_wait(P.flags, F_A, NCTA);
                fence_async();
                STAMP(20);
                mbar_expect(bars + 8 * B_STATS, TOKG * 20);
                bulk_load(sb + OFF_MB, P.mb + TOKG * tg, TOKG * 16, bars + 8 * B_STATS);
                bulk_load(sb + OFF_HR, P.hr + TOKG * tg, TOKG * 4, bars + 8 * B_STATS);
                if (c < 128) {
                    mbar_wait(bars + 8 * (B_K + 1), 0);
                    fence_async_smem();
                    mbar_expect(bars + 8 * B_U, 8 * 2048);
                    #pragma unroll 1
                    for (int i = 0; i < 8; i++)
                        bulk_load(sb + OFF_CONV + (i >> 1) * CH_STRIDE + CH_U + (i & 1) * UPLANE, P.xnT + 4 * c * 256 + i * 128, 2048, bars + 8 * B_U);
                } else exit_count(P.flags);
                #pragma unroll 1
                for (int V = 0; V < 2; V++) {
                    mbar_wait(bars + 8 * (B_EPI + V), 0);
                    asm volatile("cp.async.bulk.tensor.3d.global.shared::cta.bulk_group [%0, {%2, %3, %4}], [%1];"
                        :: "l"(&M.hst[V]), "r"(sb + OFF_X + V * 2 * XBUF), "r"(0), "r"(43 * tg + 21 * V), "r"(8 * fb) : "memory");
                    asm volatile("cp.async.bulk.commit_group; cp.async.bulk.wait_group 0;" ::: "memory");
                    mbar_arrive(bars + 8 * (B_STG + V));
                    flag_signal(P.flags, F_H + 2 * tg + V);
                }
                if (c < 128) {
                    #pragma unroll 1
                    for (int V = 0; V < 2; V++) { mbar_wait(bars + 8 * (B_SIG + V), 0); flag_signal(P.flags, F_S + (c >> 5)); }
                }
            }
        }
    }
}

typedef CUresult (*EncodeFn)(CUtensorMap*, CUtensorMapDataType, cuuint32_t, void*, const cuuint64_t*, const cuuint64_t*, const cuuint32_t*,
                             const cuuint32_t*, CUtensorMapInterleave, CUtensorMapSwizzle, CUtensorMapL2promotion, CUtensorMapFloatOOBfill);

void make_map(EncodeFn enc, CUtensorMap* m, const void* ptr, int rank, const cuuint64_t* dims, const cuuint64_t* strides, const cuuint32_t* box, bool swz) {
    const cuuint32_t es[5] = {1, 1, 1, 1, 1};
    enc(m, CU_TENSOR_MAP_DATA_TYPE_BFLOAT16, rank, (void*)ptr, dims, strides, box, es, CU_TENSOR_MAP_INTERLEAVE_NONE,
        swz ? CU_TENSOR_MAP_SWIZZLE_128B : CU_TENSOR_MAP_SWIZZLE_NONE, CU_TENSOR_MAP_L2_PROMOTION_L2_128B, CU_TENSOR_MAP_FLOAT_OOB_FILL_NONE);
}
void make_map2(EncodeFn enc, CUtensorMap* m, const void* ptr, cuuint64_t inner, cuuint64_t outer, cuuint32_t rows) {
    const cuuint64_t dims[2] = {inner, outer}, strides[1] = {inner * 2};
    const cuuint32_t box[2] = {64, rows};
    make_map(enc, m, ptr, 2, dims, strides, box, true);
}

}

extern "C" void kernel_launch(void* const* d_in, const int* in_sizes, int n_in, void* d_out, int out_size) {
    (void)in_sizes; (void)n_in; (void)out_size;
    static EncodeFn enc = nullptr;
    static void *hptr, *p_xnT, *p_mb, *p_hr, *p_S, *p_flags;
    if (!enc) {
        cudaDriverEntryPointQueryResult qr;
        cudaGetDriverEntryPoint("cuTensorMapEncodeTiled", (void**)&enc, cudaEnableDefault, &qr);
        cudaFuncSetAttribute(fused_kernel, cudaFuncAttributeMaxDynamicSharedMemorySize, SMEM_BYTES);
        cudaGetSymbolAddress(&hptr, g_H); cudaGetSymbolAddress(&p_xnT, g_xnT); cudaGetSymbolAddress(&p_mb, g_mb);
        cudaGetSymbolAddress(&p_hr, g_hr); cudaGetSymbolAddress(&p_S, g_S); cudaGetSymbolAddress(&p_flags, g_flags);
    }
    Params P;
    P.x = (const __nv_bfloat16*)d_in[0]; P.logA = (const __nv_bfloat16*)d_in[1]; P.Aim = (const __nv_bfloat16*)d_in[2];
    P.Cr = (const __nv_bfloat16*)d_in[3]; P.Ci = (const __nv_bfloat16*)d_in[4]; P.logdt = (const __nv_bfloat16*)d_in[5];
    P.Dskip = (const __nv_bfloat16*)d_in[6];
    P.xnT = (uint4*)p_xnT; P.mb = (uint4*)p_mb; P.hr = (float*)p_hr; P.S = (uint2*)p_S; P.flags = (unsigned*)p_flags;
    Maps M;
    make_map2(enc, &M.x[0], d_in[0], DM, SEQ, 168); make_map2(enc, &M.x[1], d_in[0], DM, SEQ, 176);
    make_map2(enc, &M.xo, d_in[0], DM, SEQ, 64);    make_map2(enc, &M.out, d_out, DM, SEQ, 64);
    make_map2(enc, &M.wg, d_in[8], FF, DM, 64);     make_map2(enc, &M.wu, d_in[9], FF, DM, 64);
    make_map2(enc, &M.wd, d_in[10], DM, FF, 64);
    for (int v = 0; v < 2; v++) {
        const cuuint64_t dims[3] = {64, 256, 172}, strides[2] = {128, 32768};
        const cuuint32_t box[3] = {64, (cuuint32_t)(21 + v), 8};
        make_map(enc, &M.hst[v], hptr, 3, dims, strides, box, false);
    }
    {
        const cuuint64_t dims[5] = {64, 2, 2, 64, 172}, strides[4] = {256, 128, 512, 32768};
        const cuuint32_t box[5] = {64, 2, 2, 2, 8};
        make_map(enc, &M.hld, hptr, 5, dims, strides, box, false);
    }
    fused_kernel<<<NCTA, 512, SMEM_BYTES>>>(P, M);
}
```

```cpp
#include <cuda_runtime.h>
#include <cuda_bf16.h>
#include <cuda.h>
#include <stdint.h>

#define PROF 0

namespace {

constexpr int SEQ = 2048, DM = 512, FF = 1376;
constexpr int NCTA = 132;
#define HOLD0 4
#define HOLD1 6
constexpr int TOKG = 344;

constexpr uint32_t OFF_W = 0;
constexpr uint32_t XBUF = 22528;
constexpr uint32_t OFF_X = 65536;
constexpr uint32_t OFF_CONV = 155648;
constexpr uint32_t CH_STRIDE = 16640;
constexpr uint32_t CH_T = 0;
constexpr uint32_t CH_A3 = 6272;
constexpr uint32_t CH_B3 = 10368;
constexpr uint32_t CH_U = 12416;
constexpr uint32_t CH_G = CH_A3 + 2064;
constexpr uint32_t UPLANE = 2112;
constexpr uint32_t LNROW = 1040;
constexpr uint32_t OFF_MB = 222208;
constexpr uint32_t OFF_HR = 227712;
constexpr uint32_t OFF_CSUM = 229120;
constexpr uint32_t OFF_BAR = 231168;
constexpr uint32_t SMEM_BYTES = 231680;

enum {
    B_FULLW = 0, B_EMPTYW = 4, B_FULLX = 8, B_EMPTYX = 12, B_FULLD = 16, B_EMPTYD = 22,
    B_U = 28, B_XO = 29, B_S = 30, B_STG = 31, B_HF = 33, B_STATS = 34,
    B_LNX = 35, B_GO = 36, B_CH0 = 37, B_K = 38,
    B_CONV = 40, B_LN = 41, B_CS = 42, B_EPI = 43, B_SIG = 45,
    B_COUNT = 47
};
enum { F_A = 0, F_H = 1, F_S = 13, F_EXIT = 17, F_COUNT = 18 };

__device__ uint4 g_xnT[DM * 256];
__device__ uint4 g_mb[6 * TOKG];
__device__ float g_hr[6 * TOKG];
__device__ uint4 g_H[172 * 256 * 8];
__device__ uint2 g_S[256 * 1024];
__device__ unsigned g_flags[F_COUNT * 32];
#define STAMP(i) do {} while (0)

__device__ __forceinline__ uint32_t smem_u32(const void* p) { return (uint32_t)__cvta_generic_to_shared(p); }
__device__ __forceinline__ void mbar_expect(uint32_t bar, uint32_t bytes) { asm volatile("mbarrier.arrive.expect_tx.shared::cta.b64 _, [%0], %1;" :: "r"(bar), "r"(bytes) : "memory"); }
__device__ __forceinline__ void mbar_arrive(uint32_t bar) { asm volatile("mbarrier.arrive.shared::cta.b64 _, [%0];" :: "r"(bar) : "memory"); }
__device__ __forceinline__ void mbar_wait(uint32_t bar, uint32_t parity) {
    asm volatile("{.reg .pred p; .reg .u32 n; mov.u32 n, 0x20000;\n"
                 "LW: mbarrier.try_wait.parity.shared::cta.b64 p, [%0], %1;\n"
                 "sub.u32 n, n, 1; setp.eq.or.u32 p, n, 0, p; @!p bra LW;}" :: "r"(bar), "r"(parity) : "memory");
}
__device__ __forceinline__ bool elect_one() { uint32_t p; asm volatile("{.reg .pred P; elect.sync _|P, 0xffffffff; selp.u32 %0, 1, 0, P;}" : "=r"(p)); return p; }
__device__ __forceinline__ void tma2d(uint32_t dst, const CUtensorMap* m, int c0, int c1, uint32_t bar) {
    asm volatile("cp.async.bulk.tensor.2d.shared::cluster.global.mbarrier::complete_tx::bytes [%0], [%1, {%3, %4}], [%2];"
        :: "r"(dst), "l"(m), "r"(bar), "r"(c0), "r"(c1) : "memory");
}
__device__ __forceinline__ void bulk_load(uint32_t dst, const void* src, uint32_t bytes, uint32_t bar) {
    asm volatile("cp.async.bulk.shared::cluster.global.mbarrier::complete_tx::bytes [%0], [%1], %2, [%3];" :: "r"(dst), "l"(src), "r"(bytes), "r"(bar) : "memory");
}
__device__ __forceinline__ void fence_async() { asm volatile("fence.proxy.async;" ::: "memory"); }
__device__ __forceinline__ void fence_async_smem() { asm volatile("fence.proxy.async.shared::cta;" ::: "memory"); }
__device__ __forceinline__ void flag_wait(unsigned* g_flags, int f, unsigned target) {
    asm volatile("{.reg .pred p; .reg .u32 n, v; mov.u32 n, 0x40000;\n"
                 "LF: ld.acquire.gpu.global.u32 v, [%0]; setp.ge.u32 p, v, %1; @p bra LD;\n"
                 "nanosleep.u32 20; sub.u32 n, n, 1; setp.ne.u32 p, n, 0; @p bra LF; trap;\nLD: }"
                 :: "l"(g_flags + f * 32), "r"(target) : "memory");
}
__device__ __forceinline__ void flag_signal(unsigned* g_flags, int f) {
    asm volatile("fence.acq_rel.gpu; red.relaxed.gpu.global.add.u32 [%0], 1;" :: "l"(g_flags + f * 32) : "memory");
}
__device__ __forceinline__ void exit_count(unsigned* g_flags) {
    if (atomicAdd(g_flags + F_EXIT * 32, 1u) == NCTA - 1) {
        #pragma unroll 1
        for (int i = 0; i < F_COUNT; i++) g_flags[i * 32] = 0;
    }
}
__device__ __forceinline__ void bar_sync(int id) { asm volatile("bar.sync %0, 128;" :: "r"(id) : "memory"); }
__device__ __forceinline__ uint64_t mkdesc(uint32_t addr, uint32_t lbo, uint32_t sbo, uint32_t swz) {
    return (uint64_t)((addr >> 4) | ((lbo >> 4) << 16)) | ((uint64_t)((sbo >> 4) | (swz << 30)) << 32);
}
#define WG_FENCE() asm volatile("wgmma.fence.sync.aligned;" ::: "memory")
#define WG_COMMIT() asm volatile("wgmma.commit_group.sync.aligned;" ::: "memory")
#define WG_WAIT(n) asm volatile("wgmma.wait_group.sync.aligned " #n ";" ::: "memory")
template <int N> __device__ __forceinline__ void fence_acc(float (&d)[N]) {
    #pragma unroll
    for (int i = 0; i < N; i++) asm volatile("" : "+f"(d[i]) :: "memory");
}
template <int N> __device__ __forceinline__ void define_acc(float (&d)[N]) {
    #pragma unroll
    for (int i = 0; i < N; i++) asm volatile("" : "=f"(d[i]));
}
__device__ __forceinline__ uint32_t pack2(float lo, float hi) { uint32_t r; asm("cvt.rn.bf16x2.f32 %0, %1, %2;" : "=r"(r) : "f"(hi), "f"(lo)); return r; }
__device__ __forceinline__ float bf_lo(uint32_t v) { return __uint_as_float(v << 16); }
__device__ __forceinline__ float bf_hi(uint32_t v) { return __uint_as_float(v & 0xffff0000u); }
__device__ __forceinline__ float bf_round(float v) { return bf_hi(pack2(0.f, v)); }
__device__ __forceinline__ float tanh_fast(float v) { float r; asm("tanh.approx.f32 %0, %1;" : "=f"(r) : "f"(v)); return r; }
__device__ __forceinline__ float ex2(float v) { float r; asm("ex2.approx.ftz.f32 %0, %1;" : "=f"(r) : "f"(v)); return r; }
__device__ __forceinline__ uint4 lds128(uint32_t a) { uint4 v; asm volatile("ld.shared.v4.b32 {%0,%1,%2,%3}, [%4];" : "=r"(v.x), "=r"(v.y), "=r"(v.z), "=r"(v.w) : "r"(a)); return v; }
__device__ __forceinline__ uint2 lds64(uint32_t a) { uint2 v; asm volatile("ld.shared.v2.b32 {%0,%1}, [%2];" : "=r"(v.x), "=r"(v.y) : "r"(a)); return v; }
__device__ __forceinline__ float ldsf(uint32_t a) { float v; asm volatile("ld.shared.f32 %0, [%1];" : "=f"(v) : "r"(a)); return v; }
__device__ __forceinline__ void sts128(uint32_t a, uint32_t x, uint32_t y, uint32_t z, uint32_t w) { asm volatile("st.shared.v4.b32 [%0], {%1,%2,%3,%4};" :: "r"(a), "r"(x), "r"(y), "r"(z), "r"(w) : "memory"); }
__device__ __forceinline__ void sts64(uint32_t a, uint32_t x, uint32_t y) { asm volatile("st.shared.v2.b32 [%0], {%1,%2};" :: "r"(a), "r"(x), "r"(y) : "memory"); }
__device__ __forceinline__ void stsf(uint32_t a, float x) { asm volatile("st.shared.f32 [%0], %1;" :: "r"(a), "f"(x) : "memory"); }
__device__ __forceinline__ void sts16(uint32_t a, uint32_t x) { asm volatile("st.shared.b16 [%0], %1;" :: "r"(a), "h"((unsigned short)x) : "memory"); }
__device__ __forceinline__ void stsm4(uint32_t a, uint32_t r0, uint32_t r1, uint32_t r2, uint32_t r3) {
    asm volatile("stmatrix.sync.aligned.m8n8.x4.shared.b16 [%0], {%1,%2,%3,%4};" :: "r"(a), "r"(r0), "r"(r1), "r"(r2), "r"(r3) : "memory");
}
#define FU(x) __float_as_uint(x)
#define UF(x) __uint_as_float(x)
__device__ __forceinline__ uint32_t wd_slot(int s) { return (uint32_t)((0x403056201000ull >> (8 * s)) & 0xff) << 10; }
__device__ __forceinline__ uint32_t h_slot(int s) { return s < 5 ? OFF_X + 2 * XBUF + s * 8192 : OFF_MB; }

template<int N> __device__ __forceinline__ void wg_rs(float (&d)[64], uint32_t a0, uint32_t a1, uint32_t a2, uint32_t a3, uint64_t db);
template<> __device__ __forceinline__ void wg_rs<128>(float (&d)[64], uint32_t a0, uint32_t a1, uint32_t a2, uint32_t a3, uint64_t db) {
  asm volatile("{.reg .pred p; setp.ne.b32 p, 1, 0; wgmma.mma_async.sync.aligned.m64n128k16.f32.bf16.bf16 {%0,%1,%2,%3,%4,%5,%6,%7,%8,%9,%10,%11,%12,%13,%14,%15,%16,%17,%18,%19,%20,%21,%22,%23,%24,%25,%26,%27,%28,%29,%30,%31,%32,%33,%34,%35,%36,%37,%38,%39,%40,%41,%42,%43,%44,%45,%46,%47,%48,%49,%50,%51,%52,%53,%54,%55,%56,%57,%58,%59,%60,%61,%62,%63}, {%64,%65,%66,%67}, %68, p, 1, 1, 0;}"
    : "+f"(d[0]),"+f"(d[1]),"+f"(d[2]),"+f"(d[3]),"+f"(d[4]),"+f"(d[5]),"+f"(d[6]),"+f"(d[7]),"+f"(d[8]),"+f"(d[9]),"+f"(d[10]),"+f"(d[11]),"+f"(d[12]),"+f"(d[13]),"+f"(d[14]),"+f"(d[15]),"+f"(d[16]),"+f"(d[17]),"+f"(d[18]),"+f"(d[19]),"+f"(d[20]),"+f"(d[21]),"+f"(d[22]),"+f"(d[23]),"+f"(d[24]),"+f"(d[25]),"+f"(d[26]),"+f"(d[27]),"+f"(d[28]),"+f"(d[29]),"+f"(d[30]),"+f"(d[31]),"+f"(d[32]),"+f"(d[33]),"+f"(d[34]),"+f"(d[35]),"+f"(d[36]),"+f"(d[37]),"+f"(d[38]),"+f"(d[39]),"+f"(d[40]),"+f"(d[41]),"+f"(d[42]),"+f"(d[43]),"+f"(d[44]),"+f"(d[45]),"+f"(d[46]),"+f"(d[47]),"+f"(d[48]),"+f"(d[49]),"+f"(d[50]),"+f"(d[51]),"+f"(d[52]),"+f"(d[53]),"+f"(d[54]),"+f"(d[55]),"+f"(d[56]),"+f"(d[57]),"+f"(d[58]),"+f"(d[59]),"+f"(d[60]),"+f"(d[61]),"+f"(d[62]),"+f"(d[63]) : "r"(a0), "r"(a1), "r"(a2), "r"(a3), "l"(db));
}
template<> __device__ __forceinline__ void wg_rs<120>(float (&d)[64], uint32_t a0, uint32_t a1, uint32_t a2, uint32_t a3, uint64_t db) {
  asm volatile("{.reg .pred p; setp.ne.b32 p, 1, 0; wgmma.mma_async.sync.aligned.m64n120k16.f32.bf16.bf16 {%0,%1,%2,%3,%4,%5,%6,%7,%8,%9,%10,%11,%12,%13,%14,%15,%16,%17,%18,%19,%20,%21,%22,%23,%24,%25,%26,%27,%28,%29,%30,%31,%32,%33,%34,%35,%36,%37,%38,%39,%40,%41,%42,%43,%44,%45,%46,%47,%48,%49,%50,%51,%52,%53,%54,%55,%56,%57,%58,%59}, {%60,%61,%62,%63}, %64, p, 1, 1, 0;}"
    : "+f"(d[0]),"+f"(d[1]),"+f"(d[2]),"+f"(d[3]),"+f"(d[4]),"+f"(d[5]),"+f"(d[6]),"+f"(d[7]),"+f"(d[8]),"+f"(d[9]),"+f"(d[10]),"+f"(d[11]),"+f"(d[12]),"+f"(d[13]),"+f"(d[14]),"+f"(d[15]),"+f"(d[16]),"+f"(d[17]),"+f"(d[18]),"+f"(d[19]),"+f"(d[20]),"+f"(d[21]),"+f"(d[22]),"+f"(d[23]),"+f"(d[24]),"+f"(d[25]),"+f"(d[26]),"+f"(d[27]),"+f"(d[28]),"+f"(d[29]),"+f"(d[30]),"+f"(d[31]),"+f"(d[32]),"+f"(d[33]),"+f"(d[34]),"+f"(d[35]),"+f"(d[36]),"+f"(d[37]),"+f"(d[38]),"+f"(d[39]),"+f"(d[40]),"+f"(d[41]),"+f"(d[42]),"+f"(d[43]),"+f"(d[44]),"+f"(d[45]),"+f"(d[46]),"+f"(d[47]),"+f"(d[48]),"+f"(d[49]),"+f"(d[50]),"+f"(d[51]),"+f"(d[52]),"+f"(d[53]),"+f"(d[54]),"+f"(d[55]),"+f"(d[56]),"+f"(d[57]),"+f"(d[58]),"+f"(d[59]) : "r"(a0), "r"(a1), "r"(a2), "r"(a3), "l"(db));
}
template<> __device__ __forceinline__ void wg_rs<112>(float (&d)[64], uint32_t a0, uint32_t a1, uint32_t a2, uint32_t a3, uint64_t db) {
  asm volatile("{.reg .pred p; setp.ne.b32 p, 1, 0; wgmma.mma_async.sync.aligned.m64n112k16.f32.bf16.bf16 {%0,%1,%2,%3,%4,%5,%6,%7,%8,%9,%10,%11,%12,%13,%14,%15,%16,%17,%18,%19,%20,%21,%22,%23,%24,%25,%26,%27,%28,%29,%30,%31,%32,%33,%34,%35,%36,%37,%38,%39,%40,%41,%42,%43,%44,%45,%46,%47,%48,%49,%50,%51,%52,%53,%54,%55}, {%56,%57,%58,%59}, %60, p, 1, 1, 0;}"
    : "+f"(d[0]),"+f"(d[1]),"+f"(d[2]),"+f"(d[3]),"+f"(d[4]),"+f"(d[5]),"+f"(d[6]),"+f"(d[7]),"+f"(d[8]),"+f"(d[9]),"+f"(d[10]),"+f"(d[11]),"+f"(d[12]),"+f"(d[13]),"+f"(d[14]),"+f"(d[15]),"+f"(d[16]),"+f"(d[17]),"+f"(d[18]),"+f"(d[19]),"+f"(d[20]),"+f"(d[21]),"+f"(d[22]),"+f"(d[23]),"+f"(d[24]),"+f"(d[25]),"+f"(d[26]),"+f"(d[27]),"+f"(d[28]),"+f"(d[29]),"+f"(d[30]),"+f"(d[31]),"+f"(d[32]),"+f"(d[33]),"+f"(d[34]),"+f"(d[35]),"+f"(d[36]),"+f"(d[37]),"+f"(d[38]),"+f"(d[39]),"+f"(d[40]),"+f"(d[41]),"+f"(d[42]),"+f"(d[43]),"+f"(d[44]),"+f"(d[45]),"+f"(d[46]),"+f"(d[47]),"+f"(d[48]),"+f"(d[49]),"+f"(d[50]),"+f"(d[51]),"+f"(d[52]),"+f"(d[53]),"+f"(d[54]),"+f"(d[55]) : "r"(a0), "r"(a1), "r"(a2), "r"(a3), "l"(db));
}
template<> __device__ __forceinline__ void wg_rs<104>(float (&d)[64], uint32_t a0, uint32_t a1, uint32_t a2, uint32_t a3, uint64_t db) {
  asm volatile("{.reg .pred p; setp.ne.b32 p, 1, 0; wgmma.mma_async.sync.aligned.m64n104k16.f32.bf16.bf16 {%0,%1,%2,%3,%4,%5,%6,%7,%8,%9,%10,%11,%12,%13,%14,%15,%16,%17,%18,%19,%20,%21,%22,%23,%24,%25,%26,%27,%28,%29,%30,%31,%32,%33,%34,%35,%36,%37,%38,%39,%40,%41,%42,%43,%44,%45,%46,%47,%48,%49,%50,%51}, {%52,%53,%54,%55}, %56, p, 1, 1, 0;}"
    : "+f"(d[0]),"+f"(d[1]),"+f"(d[2]),"+f"(d[3]),"+f"(d[4]),"+f"(d[5]),"+f"(d[6]),"+f"(d[7]),"+f"(d[8]),"+f"(d[9]),"+f"(d[10]),"+f"(d[11]),"+f"(d[12]),"+f"(d[13]),"+f"(d[14]),"+f"(d[15]),"+f"(d[16]),"+f"(d[17]),"+f"(d[18]),"+f"(d[19]),"+f"(d[20]),"+f"(d[21]),"+f"(d[22]),"+f"(d[23]),"+f"(d[24]),"+f"(d[25]),"+f"(d[26]),"+f"(d[27]),"+f"(d[28]),"+f"(d[29]),"+f"(d[30]),"+f"(d[31]),"+f"(d[32]),"+f"(d[33]),"+f"(d[34]),"+f"(d[35]),"+f"(d[36]),"+f"(d[37]),"+f"(d[38]),"+f"(d[39]),"+f"(d[40]),"+f"(d[41]),"+f"(d[42]),"+f"(d[43]),"+f"(d[44]),"+f"(d[45]),"+f"(d[46]),"+f"(d[47]),"+f"(d[48]),"+f"(d[49]),"+f"(d[50]),"+f"(d[51]) : "r"(a0), "r"(a1), "r"(a2), "r"(a3), "l"(db));
}
template<> __device__ __forceinline__ void wg_rs<96>(float (&d)[64], uint32_t a0, uint32_t a1, uint32_t a2, uint32_t a3, uint64_t db) {
  asm volatile("{.reg .pred p; setp.ne.b32 p, 1, 0; wgmma.mma_async.sync.aligned.m64n96k16.f32.bf16.bf16 {%0,%1,%2,%3,%4,%5,%6,%7,%8,%9,%10,%11,%12,%13,%14,%15,%16,%17,%18,%19,%20,%21,%22,%23,%24,%25,%26,%27,%28,%29,%30,%31,%32,%33,%34,%35,%36,%37,%38,%39,%40,%41,%42,%43,%44,%45,%46,%47}, {%48,%49,%50,%51}, %52, p, 1, 1, 0;}"
    : "+f"(d[0]),"+f"(d[1]),"+f"(d[2]),"+f"(d[3]),"+f"(d[4]),"+f"(d[5]),"+f"(d[6]),"+f"(d[7]),"+f"(d[8]),"+f"(d[9]),"+f"(d[10]),"+f"(d[11]),"+f"(d[12]),"+f"(d[13]),"+f"(d[14]),"+f"(d[15]),"+f"(d[16]),"+f"(d[17]),"+f"(d[18]),"+f"(d[19]),"+f"(d[20]),"+f"(d[21]),"+f"(d[22]),"+f"(d[23]),"+f"(d[24]),"+f"(d[25]),"+f"(d[26]),"+f"(d[27]),"+f"(d[28]),"+f"(d[29]),"+f"(d[30]),"+f"(d[31]),"+f"(d[32]),"+f"(d[33]),"+f"(d[34]),"+f"(d[35]),"+f"(d[36]),"+f"(d[37]),"+f"(d[38]),"+f"(d[39]),"+f"(d[40]),"+f"(d[41]),"+f"(d[42]),"+f"(d[43]),"+f"(d[44]),"+f"(d[45]),"+f"(d[46]),"+f"(d[47]) : "r"(a0), "r"(a1), "r"(a2), "r"(a3), "l"(db));
}
template<> __device__ __forceinline__ void wg_rs<88>(float (&d)[64], uint32_t a0, uint32_t a1, uint32_t a2, uint32_t a3, uint64_t db) {
  asm volatile("{.reg .pred p; setp.ne.b32 p, 1, 0; wgmma.mma_async.sync.aligned.m64n88k16.f32.bf16.bf16 {%0,%1,%2,%3,%4,%5,%6,%7,%8,%9,%10,%11,%12,%13,%14,%15,%16,%17,%18,%19,%20,%21,%22,%23,%24,%25,%26,%27,%28,%29,%30,%31,%32,%33,%34,%35,%36,%37,%38,%39,%40,%41,%42,%43}, {%44,%45,%46,%47}, %48, p, 1, 1, 0;}"
    : "+f"(d[0]),"+f"(d[1]),"+f"(d[2]),"+f"(d[3]),"+f"(d[4]),"+f"(d[5]),"+f"(d[6]),"+f"(d[7]),"+f"(d[8]),"+f"(d[9]),"+f"(d[10]),"+f"(d[11]),"+f"(d[12]),"+f"(d[13]),"+f"(d[14]),"+f"(d[15]),"+f"(d[16]),"+f"(d[17]),"+f"(d[18]),"+f"(d[19]),"+f"(d[20]),"+f"(d[21]),"+f"(d[22]),"+f"(d[23]),"+f"(d[24]),"+f"(d[25]),"+f"(d[26]),"+f"(d[27]),"+f"(d[28]),"+f"(d[29]),"+f"(d[30]),"+f"(d[31]),"+f"(d[32]),"+f"(d[33]),"+f"(d[34]),"+f"(d[35]),"+f"(d[36]),"+f"(d[37]),"+f"(d[38]),"+f"(d[39]),"+f"(d[40]),"+f"(d[41]),"+f"(d[42]),"+f"(d[43]) : "r"(a0), "r"(a1), "r"(a2), "r"(a3), "l"(db));
}
template<> __device__ __forceinline__ void wg_rs<80>(float (&d)[64], uint32_t a0, uint32_t a1, uint32_t a2, uint32_t a3, uint64_t db) {
  asm volatile("{.reg .pred p; setp.ne.b32 p, 1, 0; wgmma.mma_async.sync.aligned.m64n80k16.f32.bf16.bf16 {%0,%1,%2,%3,%4,%5,%6,%7,%8,%9,%10,%11,%12,%13,%14,%15,%16,%17,%18,%19,%20,%21,%22,%23,%24,%25,%26,%27,%28,%29,%30,%31,%32,%33,%34,%35,%36,%37,%38,%39}, {%40,%41,%42,%43}, %44, p, 1, 1, 0;}"
    : "+f"(d[0]),"+f"(d[1]),"+f"(d[2]),"+f"(d[3]),"+f"(d[4]),"+f"(d[5]),"+f"(d[6]),"+f"(d[7]),"+f"(d[8]),"+f"(d[9]),"+f"(d[10]),"+f"(d[11]),"+f"(d[12]),"+f"(d[13]),"+f"(d[14]),"+f"(d[15]),"+f"(d[16]),"+f"(d[17]),"+f"(d[18]),"+f"(d[19]),"+f"(d[20]),"+f"(d[21]),"+f"(d[22]),"+f"(d[23]),"+f"(d[24]),"+f"(d[25]),"+f"(d[26]),"+f"(d[27]),"+f"(d[28]),"+f"(d[29]),"+f"(d[30]),"+f"(d[31]),"+f"(d[32]),"+f"(d[33]),"+f"(d[34]),"+f"(d[35]),"+f"(d[36]),"+f"(d[37]),"+f"(d[38]),"+f"(d[39]) : "r"(a0), "r"(a1), "r"(a2), "r"(a3), "l"(db));
}
template<> __device__ __forceinline__ void wg_rs<72>(float (&d)[64], uint32_t a0, uint32_t a1, uint32_t a2, uint32_t a3, uint64_t db) {
  asm volatile("{.reg .pred p; setp.ne.b32 p, 1, 0; wgmma.mma_async.sync.aligned.m64n72k16.f32.bf16.bf16 {%0,%1,%2,%3,%4,%5,%6,%7,%8,%9,%10,%11,%12,%13,%14,%15,%16,%17,%18,%19,%20,%21,%22,%23,%24,%25,%26,%27,%28,%29,%30,%31,%32,%33,%34,%35}, {%36,%37,%38,%39}, %40, p, 1, 1, 0;}"
    : "+f"(d[0]),"+f"(d[1]),"+f"(d[2]),"+f"(d[3]),"+f"(d[4]),"+f"(d[5]),"+f"(d[6]),"+f"(d[7]),"+f"(d[8]),"+f"(d[9]),"+f"(d[10]),"+f"(d[11]),"+f"(d[12]),"+f"(d[13]),"+f"(d[14]),"+f"(d[15]),"+f"(d[16]),"+f"(d[17]),"+f"(d[18]),"+f"(d[19]),"+f"(d[20]),"+f"(d[21]),"+f"(d[22]),"+f"(d[23]),"+f"(d[24]),"+f"(d[25]),"+f"(d[26]),"+f"(d[27]),"+f"(d[28]),"+f"(d[29]),"+f"(d[30]),"+f"(d[31]),"+f"(d[32]),"+f"(d[33]),"+f"(d[34]),"+f"(d[35]) : "r"(a0), "r"(a1), "r"(a2), "r"(a3), "l"(db));
}
template<> __device__ __forceinline__ void wg_rs<64>(float (&d)[64], uint32_t a0, uint32_t a1, uint32_t a2, uint32_t a3, uint64_t db) {
  asm volatile("{.reg .pred p; setp.ne.b32 p, 1, 0; wgmma.mma_async.sync.aligned.m64n64k16.f32.bf16.bf16 {%0,%1,%2,%3,%4,%5,%6,%7,%8,%9,%10,%11,%12,%13,%14,%15,%16,%17,%18,%19,%20,%21,%22,%23,%24,%25,%26,%27,%28,%29,%30,%31}, {%32,%33,%34,%35}, %36, p, 1, 1, 0;}"
    : "+f"(d[0]),"+f"(d[1]),"+f"(d[2]),"+f"(d[3]),"+f"(d[4]),"+f"(d[5]),"+f"(d[6]),"+f"(d[7]),"+f"(d[8]),"+f"(d[9]),"+f"(d[10]),"+f"(d[11]),"+f"(d[12]),"+f"(d[13]),"+f"(d[14]),"+f"(d[15]),"+f"(d[16]),"+f"(d[17]),"+f"(d[18]),"+f"(d[19]),"+f"(d[20]),"+f"(d[21]),"+f"(d[22]),"+f"(d[23]),"+f"(d[24]),"+f"(d[25]),"+f"(d[26]),"+f"(d[27]),"+f"(d[28]),"+f"(d[29]),"+f"(d[30]),"+f"(d[31]) : "r"(a0), "r"(a1), "r"(a2), "r"(a3), "l"(db));
}
__device__ __forceinline__ void wg_rs_first(float (&d)[64], uint32_t a0, uint32_t a1, uint32_t a2, uint32_t a3, uint64_t db) {
  asm volatile("{.reg .pred p; setp.ne.b32 p, 0, 0; wgmma.mma_async.sync.aligned.m64n128k16.f32.bf16.bf16 {%0,%1,%2,%3,%4,%5,%6,%7,%8,%9,%10,%11,%12,%13,%14,%15,%16,%17,%18,%19,%20,%21,%22,%23,%24,%25,%26,%27,%28,%29,%30,%31,%32,%33,%34,%35,%36,%37,%38,%39,%40,%41,%42,%43,%44,%45,%46,%47,%48,%49,%50,%51,%52,%53,%54,%55,%56,%57,%58,%59,%60,%61,%62,%63}, {%64,%65,%66,%67}, %68, p, 1, 1, 0;}"
    : "=f"(d[0]),"=f"(d[1]),"=f"(d[2]),"=f"(d[3]),"=f"(d[4]),"=f"(d[5]),"=f"(d[6]),"=f"(d[7]),"=f"(d[8]),"=f"(d[9]),"=f"(d[10]),"=f"(d[11]),"=f"(d[12]),"=f"(d[13]),"=f"(d[14]),"=f"(d[15]),"=f"(d[16]),"=f"(d[17]),"=f"(d[18]),"=f"(d[19]),"=f"(d[20]),"=f"(d[21]),"=f"(d[22]),"=f"(d[23]),"=f"(d[24]),"=f"(d[25]),"=f"(d[26]),"=f"(d[27]),"=f"(d[28]),"=f"(d[29]),"=f"(d[30]),"=f"(d[31]),"=f"(d[32]),"=f"(d[33]),"=f"(d[34]),"=f"(d[35]),"=f"(d[36]),"=f"(d[37]),"=f"(d[38]),"=f"(d[39]),"=f"(d[40]),"=f"(d[41]),"=f"(d[42]),"=f"(d[43]),"=f"(d[44]),"=f"(d[45]),"=f"(d[46]),"=f"(d[47]),"=f"(d[48]),"=f"(d[49]),"=f"(d[50]),"=f"(d[51]),"=f"(d[52]),"=f"(d[53]),"=f"(d[54]),"=f"(d[55]),"=f"(d[56]),"=f"(d[57]),"=f"(d[58]),"=f"(d[59]),"=f"(d[60]),"=f"(d[61]),"=f"(d[62]),"=f"(d[63]) : "r"(a0), "r"(a1), "r"(a2), "r"(a3), "l"(db));
}
__device__ __forceinline__ void wg_kk176(float (&d)[88], uint64_t da, uint64_t db, int sc) {
  asm volatile("{.reg .pred p; setp.ne.b32 p, %90, 0; wgmma.mma_async.sync.aligned.m64n176k16.f32.bf16.bf16 {%0,%1,%2,%3,%4,%5,%6,%7,%8,%9,%10,%11,%12,%13,%14,%15,%16,%17,%18,%19,%20,%21,%22,%23,%24,%25,%26,%27,%28,%29,%30,%31,%32,%33,%34,%35,%36,%37,%38,%39,%40,%41,%42,%43,%44,%45,%46,%47,%48,%49,%50,%51,%52,%53,%54,%55,%56,%57,%58,%59,%60,%61,%62,%63,%64,%65,%66,%67,%68,%69,%70,%71,%72,%73,%74,%75,%76,%77,%78,%79,%80,%81,%82,%83,%84,%85,%86,%87}, %88, %89, p, 1, 1, 0, 0;}"
    : "+f"(d[0]),"+f"(d[1]),"+f"(d[2]),"+f"(d[3]),"+f"(d[4]),"+f"(d[5]),"+f"(d[6]),"+f"(d[7]),"+f"(d[8]),"+f"(d[9]),"+f"(d[10]),"+f"(d[11]),"+f"(d[12]),"+f"(d[13]),"+f"(d[14]),"+f"(d[15]),"+f"(d[16]),"+f"(d[17]),"+f"(d[18]),"+f"(d[19]),"+f"(d[20]),"+f"(d[21]),"+f"(d[22]),"+f"(d[23]),"+f"(d[24]),"+f"(d[25]),"+f"(d[26]),"+f"(d[27]),"+f"(d[28]),"+f"(d[29]),"+f"(d[30]),"+f"(d[31]),"+f"(d[32]),"+f"(d[33]),"+f"(d[34]),"+f"(d[35]),"+f"(d[36]),"+f"(d[37]),"+f"(d[38]),"+f"(d[39]),"+f"(d[40]),"+f"(d[41]),"+f"(d[42]),"+f"(d[43]),"+f"(d[44]),"+f"(d[45]),"+f"(d[46]),"+f"(d[47]),"+f"(d[48]),"+f"(d[49]),"+f"(d[50]),"+f"(d[51]),"+f"(d[52]),"+f"(d[53]),"+f"(d[54]),"+f"(d[55]),"+f"(d[56]),"+f"(d[57]),"+f"(d[58]),"+f"(d[59]),"+f"(d[60]),"+f"(d[61]),"+f"(d[62]),"+f"(d[63]),"+f"(d[64]),"+f"(d[65]),"+f"(d[66]),"+f"(d[67]),"+f"(d[68]),"+f"(d[69]),"+f"(d[70]),"+f"(d[71]),"+f"(d[72]),"+f"(d[73]),"+f"(d[74]),"+f"(d[75]),"+f"(d[76]),"+f"(d[77]),"+f"(d[78]),"+f"(d[79]),"+f"(d[80]),"+f"(d[81]),"+f"(d[82]),"+f"(d[83]),"+f"(d[84]),"+f"(d[85]),"+f"(d[86]),"+f"(d[87]) : "l"(da), "l"(db), "r"(sc));
}
__device__ __forceinline__ void wg_tt128(float (&d)[64], uint64_t da, uint64_t db, int sc) {
  asm volatile("{.reg .pred p; setp.ne.b32 p, %66, 0; wgmma.mma_async.sync.aligned.m64n128k16.f32.bf16.bf16 {%0,%1,%2,%3,%4,%5,%6,%7,%8,%9,%10,%11,%12,%13,%14,%15,%16,%17,%18,%19,%20,%21,%22,%23,%24,%25,%26,%27,%28,%29,%30,%31,%32,%33,%34,%35,%36,%37,%38,%39,%40,%41,%42,%43,%44,%45,%46,%47,%48,%49,%50,%51,%52,%53,%54,%55,%56,%57,%58,%59,%60,%61,%62,%63}, %64, %65, p, 1, 1, 1, 1;}"
    : "+f"(d[0]),"+f"(d[1]),"+f"(d[2]),"+f"(d[3]),"+f"(d[4]),"+f"(d[5]),"+f"(d[6]),"+f"(d[7]),"+f"(d[8]),"+f"(d[9]),"+f"(d[10]),"+f"(d[11]),"+f"(d[12]),"+f"(d[13]),"+f"(d[14]),"+f"(d[15]),"+f"(d[16]),"+f"(d[17]),"+f"(d[18]),"+f"(d[19]),"+f"(d[20]),"+f"(d[21]),"+f"(d[22]),"+f"(d[23]),"+f"(d[24]),"+f"(d[25]),"+f"(d[26]),"+f"(d[27]),"+f"(d[28]),"+f"(d[29]),"+f"(d[30]),"+f"(d[31]),"+f"(d[32]),"+f"(d[33]),"+f"(d[34]),"+f"(d[35]),"+f"(d[36]),"+f"(d[37]),"+f"(d[38]),"+f"(d[39]),"+f"(d[40]),"+f"(d[41]),"+f"(d[42]),"+f"(d[43]),"+f"(d[44]),"+f"(d[45]),"+f"(d[46]),"+f"(d[47]),"+f"(d[48]),"+f"(d[49]),"+f"(d[50]),"+f"(d[51]),"+f"(d[52]),"+f"(d[53]),"+f"(d[54]),"+f"(d[55]),"+f"(d[56]),"+f"(d[57]),"+f"(d[58]),"+f"(d[59]),"+f"(d[60]),"+f"(d[61]),"+f"(d[62]),"+f"(d[63]) : "l"(da), "l"(db), "r"(sc));
}
__device__ __forceinline__ void wg_tt64(float (&d)[64], uint64_t da, uint64_t db, int sc) {
  asm volatile("{.reg .pred p; setp.ne.b32 p, %34, 0; wgmma.mma_async.sync.aligned.m64n64k16.f32.bf16.bf16 {%0,%1,%2,%3,%4,%5,%6,%7,%8,%9,%10,%11,%12,%13,%14,%15,%16,%17,%18,%19,%20,%21,%22,%23,%24,%25,%26,%27,%28,%29,%30,%31}, %32, %33, p, 1, 1, 1, 1;}"
    : "+f"(d[0]),"+f"(d[1]),"+f"(d[2]),"+f"(d[3]),"+f"(d[4]),"+f"(d[5]),"+f"(d[6]),"+f"(d[7]),"+f"(d[8]),"+f"(d[9]),"+f"(d[10]),"+f"(d[11]),"+f"(d[12]),"+f"(d[13]),"+f"(d[14]),"+f"(d[15]),"+f"(d[16]),"+f"(d[17]),"+f"(d[18]),"+f"(d[19]),"+f"(d[20]),"+f"(d[21]),"+f"(d[22]),"+f"(d[23]),"+f"(d[24]),"+f"(d[25]),"+f"(d[26]),"+f"(d[27]),"+f"(d[28]),"+f"(d[29]),"+f"(d[30]),"+f"(d[31]) : "l"(da), "l"(db), "r"(sc));
}
__device__ __forceinline__ void wg_tt32(float (&d)[64], uint64_t da, uint64_t db, int sc) {
  asm volatile("{.reg .pred p; setp.ne.b32 p, %18, 0; wgmma.mma_async.sync.aligned.m64n32k16.f32.bf16.bf16 {%0,%1,%2,%3,%4,%5,%6,%7,%8,%9,%10,%11,%12,%13,%14,%15}, %16, %17, p, 1, 1, 1, 1;}"
    : "+f"(d[0]),"+f"(d[1]),"+f"(d[2]),"+f"(d[3]),"+f"(d[4]),"+f"(d[5]),"+f"(d[6]),"+f"(d[7]),"+f"(d[8]),"+f"(d[9]),"+f"(d[10]),"+f"(d[11]),"+f"(d[12]),"+f"(d[13]),"+f"(d[14]),"+f"(d[15]) : "l"(da), "l"(db), "r"(sc));
}
__device__ __forceinline__ void wg_g1(float (&d)[88], uint64_t da, uint64_t db, int sc) {
  asm volatile("{.reg .pred p; setp.ne.b32 p, %90, 0; wgmma.mma_async.sync.aligned.m64n176k16.f32.bf16.bf16 {%0,%1,%2,%3,%4,%5,%6,%7,%8,%9,%10,%11,%12,%13,%14,%15,%16,%17,%18,%19,%20,%21,%22,%23,%24,%25,%26,%27,%28,%29,%30,%31,%32,%33,%34,%35,%36,%37,%38,%39,%40,%41,%42,%43,%44,%45,%46,%47,%48,%49,%50,%51,%52,%53,%54,%55,%56,%57,%58,%59,%60,%61,%62,%63,%64,%65,%66,%67,%68,%69,%70,%71,%72,%73,%74,%75,%76,%77,%78,%79,%80,%81,%82,%83,%84,%85,%86,%87}, %88, %89, p, 1, 1, 1, 0;}"
    : "+f"(d[0]),"+f"(d[1]),"+f"(d[2]),"+f"(d[3]),"+f"(d[4]),"+f"(d[5]),"+f"(d[6]),"+f"(d[7]),"+f"(d[8]),"+f"(d[9]),"+f"(d[10]),"+f"(d[11]),"+f"(d[12]),"+f"(d[13]),"+f"(d[14]),"+f"(d[15]),"+f"(d[16]),"+f"(d[17]),"+f"(d[18]),"+f"(d[19]),"+f"(d[20]),"+f"(d[21]),"+f"(d[22]),"+f"(d[23]),"+f"(d[24]),"+f"(d[25]),"+f"(d[26]),"+f"(d[27]),"+f"(d[28]),"+f"(d[29]),"+f"(d[30]),"+f"(d[31]),"+f"(d[32]),"+f"(d[33]),"+f"(d[34]),"+f"(d[35]),"+f"(d[36]),"+f"(d[37]),"+f"(d[38]),"+f"(d[39]),"+f"(d[40]),"+f"(d[41]),"+f"(d[42]),"+f"(d[43]),"+f"(d[44]),"+f"(d[45]),"+f"(d[46]),"+f"(d[47]),"+f"(d[48]),"+f"(d[49]),"+f"(d[50]),"+f"(d[51]),"+f"(d[52]),"+f"(d[53]),"+f"(d[54]),"+f"(d[55]),"+f"(d[56]),"+f"(d[57]),"+f"(d[58]),"+f"(d[59]),"+f"(d[60]),"+f"(d[61]),"+f"(d[62]),"+f"(d[63]),"+f"(d[64]),"+f"(d[65]),"+f"(d[66]),"+f"(d[67]),"+f"(d[68]),"+f"(d[69]),"+f"(d[70]),"+f"(d[71]),"+f"(d[72]),"+f"(d[73]),"+f"(d[74]),"+f"(d[75]),"+f"(d[76]),"+f"(d[77]),"+f"(d[78]),"+f"(d[79]),"+f"(d[80]),"+f"(d[81]),"+f"(d[82]),"+f"(d[83]),"+f"(d[84]),"+f"(d[85]),"+f"(d[86]),"+f"(d[87]) : "l"(da), "l"(db), "r"(sc));
}

struct Params { const __nv_bfloat16 *x, *logA, *Aim, *Cr, *Ci, *logdt, *Dskip; uint4 *xnT, *mb; float* hr; uint2* S; unsigned* flags; };
struct Maps { CUtensorMap x[2], xo, out, wg, wu, wd, hst[2], hld; };

__device__ __forceinline__ void conv_channel(uint32_t cb, int w, int lane, uint32_t (&res)[8], uint32_t bar_free) {
    const int q = lane & 3, g = lane >> 2, gam = g >> 2;
    float acc[64];
    uint4 a[4][4];
    const uint32_t t0 = cb + CH_T + (uint32_t)(14 + 4 * w + (g & 3) + 32 * gam - 2 * q) * 80u;
    #pragma unroll
    for (int s4 = 0; s4 < 4; s4++) {
        a[s4][0] = lds128(t0 + s4 * 16);
        a[s4][1] = lds128(t0 + 16 * 80 + s4 * 16);
        a[s4][2] = lds128(t0 - 8 * 80 + s4 * 16);
        a[s4][3] = lds128(t0 + 8 * 80 + s4 * 16);
    }
    const uint32_t l0 = FU(ldsf(t0 + 64)), l1 = FU(ldsf(t0 + 16 * 80 + 64)), l2 = FU(ldsf(t0 - 8 * 80 + 64)), l3 = FU(ldsf(t0 + 8 * 80 + 64));
    const uint64_t dU = mkdesc(cb + CH_U, UPLANE, 128, 0);
    WG_FENCE();
#define CT(N, s, c) wg_rs<N>(acc, a[(s) >> 2][0].c, a[(s) >> 2][1].c, a[(s) >> 2][2].c, a[(s) >> 2][3].c, dU + 4 * (s))
    wg_rs_first(acc, a[0][0].x, a[0][1].x, a[0][2].x, a[0][3].x, dU);
    CT(128, 1, y); CT(120, 2, z); CT(120, 3, w);
    CT(112, 4, x); CT(112, 5, y); CT(104, 6, z); CT(104, 7, w);
    CT(96, 8, x);  CT(96, 9, y);  CT(88, 10, z); CT(88, 11, w);
    CT(80, 12, x); CT(80, 13, y); CT(72, 14, z); CT(72, 15, w);
#undef CT
    wg_rs<64>(acc, l0, l1, l2, l3, dU + 64);
    wg_tt64(acc, mkdesc(cb + CH_A3, 128, 512, 0), mkdesc(cb + CH_B3, 128, 256, 0), 1);
    wg_tt32(acc, mkdesc(cb + CH_A3 + 256, 128, 512, 0), mkdesc(cb + CH_B3 + 1024, 128, 256, 0), 1);
    WG_COMMIT();
    WG_WAIT(0);
    fence_acc(acc);
    if (bar_free && lane == 0) mbar_arrive(bar_free);
    const int src1 = (lane & ~3) | ((q + 1) & 3);
    float E[16][2];
    #pragma unroll
    for (int j = 0; j < 16; j++) {
        const float nxt = (j < 15) ? acc[4 * (j + 1) + 2] : 0.f;
        const float sup = (q == 0) ? nxt : acc[4 * j + 2];
        const float v = __shfl_sync(0xffffffffu, sup, src1);
        E[j][0] = acc[4 * j] + acc[4 * j + 3];
        E[j][1] = acc[4 * j + 1] + v;
    }
    const int src2 = gam ? ((lane & 12) | ((q + 3) & 3)) : (16 | (lane & 12) | ((q + 1) & 3));
    const bool c1 = gam && q != 0, c2 = gam && q == 0;
    #pragma unroll
    for (int a2 = 0; a2 < 8; a2++) {
        float y[2];
        #pragma unroll
        for (int e = 0; e < 2; e++) {
            const float sup = c1 ? E[2 * a2][e] : E[2 * a2 + 1][e];
            const float nxt = (a2 < 7) ? E[2 * a2 + 2][e] : 0.f;
            const float keep = c2 ? nxt : (c1 ? E[2 * a2 + 1][e] : E[2 * a2][e]);
            y[e] = keep + __shfl_sync(0xffffffffu, sup, src2);
        }
        res[a2] = pack2(y[1], y[0]);
    }
}

__device__ __forceinline__ void consumer(uint32_t sb, int warp, const Params& P, const Maps& M) {
    const int V = warp >> 2, w = warp & 3, lane = threadIdx.x & 31, q = lane & 3, g = lane >> 2;
    const int c = blockIdx.x;
    const uint32_t bars = sb + OFF_BAR, xb = sb + OFF_X + V * 2 * XBUF;
    {
        float ag[88], au[88];
        define_acc(ag); define_acc(au);
        if (V == 0) {
            sts128(xb + (w >> 1) * XBUF + 168 * 128 + (threadIdx.x & 63) * 16, 0x3f803f80u, 0x3f803f80u, 0x3f803f80u, 0x3f803f80u);
            fence_async_smem();
            bar_sync(1);
        } else mbar_wait(bars + 8 * B_GO, 0);
        #pragma unroll 1
        for (int st = 0; st < 8; st++) {
            if (st + V == HOLD0 || st + V == HOLD1) mbar_wait(bars + 8 * (B_K + (st + V == HOLD1)), 0);
            mbar_wait(bars + 8 * (B_FULLW + (st & 3)), st >> 2);
            mbar_wait(bars + 8 * (B_FULLX + 2 * V + (st & 1)), (st >> 1) & 1);
            STAMP(40 + 8 * V + st);
            const uint64_t dG = mkdesc(sb + OFF_W + (st & 3) * 16384, 0, 1024, 1);
            const uint64_t dX = mkdesc(xb + (st & 1) * XBUF, 16, 1024, 1);
            WG_FENCE();
            #pragma unroll
            for (int k = 0; k < 4; k++) {
                wg_g1(ag, dG + k * 128, dX + k * 2, k ? 1 : st);
                wg_g1(au, dG + 512 + k * 128, dX + k * 2, k ? 1 : st);
            }
            WG_COMMIT();
            WG_WAIT(1);
            if (lane == 0 && st > 0) {
                mbar_arrive(bars + 8 * (B_EMPTYW + ((st - 1) & 3)));
                mbar_arrive(bars + 8 * (B_EMPTYX + 2 * V + ((st - 1) & 1)));
                if (warp < 4 && st == 1) mbar_arrive(bars + 8 * B_GO);
            }
        }
        WG_WAIT(0);
        fence_acc(ag); fence_acc(au);
        if (lane == 0) { mbar_arrive(bars + 8 * (B_EMPTYW + 3)); mbar_arrive(bars + 8 * (B_EMPTYX + 2 * V + 1)); }
        STAMP(8 * V + 1);
        {
            if (V == 0) {
                const float cv = (q & 2) ? ((q & 1) ? au[86] : au[84]) : ((q & 1) ? ag[86] : ag[84]), hi = bf_round(cv);
                sts128(sb + OFF_CSUM + (16 * w + g + 8 * (q & 1) + 32 * (q & 2)) * 16, pack2(hi, cv - hi), 0, 0, 0);
                fence_async_smem();
                mbar_arrive(bars + 8 * B_CS);
            }
            mbar_wait(bars + 8 * B_CS, 0);
            mbar_wait(bars + 8 * B_STATS, 0);
            const uint64_t dM = mkdesc(sb + OFF_MB + V * 168 * 16, 0, 128, 0), dC = mkdesc(sb + OFF_CSUM, 0, 128, 0);
            WG_FENCE();
            wg_kk176(ag, dC, dM, 1);
            wg_kk176(au, dC + 64, dM, 1);
            WG_COMMIT();
            mbar_wait(bars + 8 * (B_EMPTYX + 2 * V), 1);
            WG_WAIT(0);
            fence_acc(ag); fence_acc(au);
        }
        const uint32_t hs = xb + (2 * w + ((lane >> 3) & 1)) * (2688 + 128 * V) + (lane >> 4) * 128 + (lane & 7) * 16;
        const uint32_t hr = sb + OFF_HR + (168 * V + 2 * q) * 4;
        #pragma unroll
        for (int j = 0; j < 22; j += 2) {
            uint32_t o[4];
            #pragma unroll
            for (int jj = 0; jj < 2; jj++) {
                const uint2 rv = lds64(hr + (j + jj) * 32);
                float hv[4];
                #pragma unroll
                for (int i = 0; i < 4; i++) {
                    const float gh = ag[4 * (j + jj) + i] * UF((i & 1) ? rv.y : rv.x);
                    const float p = gh * au[4 * (j + jj) + i];
                    hv[i] = fmaf(p, tanh_fast(gh), p);
                }
                o[2 * jj] = pack2(hv[0], hv[1]); o[2 * jj + 1] = pack2(hv[2], hv[3]);
            }
            uint32_t ad = hs + j * 128;
            if (j == 20 && V == 0 && lane >= 16) ad = xb + 21504 + (lane & 7) * 16;
            stsm4(ad, o[0], o[1], o[2], o[3]);
        }
        fence_async_smem();
        mbar_arrive(bars + 8 * (B_EPI + V));
        STAMP(8 * V + 2);
    }
    if (c >= 128) return;
    {
        mbar_wait(bars + 8 * B_CONV, 0);
        uint32_t r0[8], r1[8];
        #pragma unroll
        for (int i = 0; i < 8; i++) asm volatile("" : "=r"(r1[i]));
        #pragma unroll 1
        for (int e = 0; e < 2; e++) {
            #pragma unroll
            for (int i = 0; i < 8; i++) r0[i] = r1[i];
            conv_channel(sb + OFF_CONV + (2 * V + e) * CH_STRIDE, w, lane, r1, (V + e == 0) ? bars + 8 * B_CH0 : 0);
            if (e == 0) STAMP(8 * V + 3);
        }
        const int gam = g >> 2, qq = gam ? ((q + 3) & 3) : q;
        uint2* sp = P.S + (2 * c + V) * 1024 + (63 - 4 * gam - qq) * 16 + 4 * w + (g & 3);
        #pragma unroll
        for (int a2 = 0; a2 < 8; a2++) sp[-a2 * 128] = make_uint2(r0[a2], r1[a2]);
        mbar_arrive(bars + 8 * (B_SIG + V));
        STAMP(8 * V + 4);
    }
    if (V == 1) return;
    {
        const int tau = c >> 2, dg = c & 3;
        const uint32_t row = 8 * (w & 1) + 32 * (w >> 1);
        float acc[64];
        define_acc(acc);
        uint2 sv[16];
        #pragma unroll
        for (int i = 0; i < 16; i++) asm volatile("" : "=r"(sv[i].x), "=r"(sv[i].y));
        const float rr0 = __ldcg(P.hr + 64 * tau + row + g), rr1 = __ldcg(P.hr + 64 * tau + row + g + 16);
        int sd = 0; uint32_t pd = 0;
        mbar_wait(bars + 8 * B_FULLD, 0);
        STAMP(5);
        uint64_t dB = mkdesc(sb + wd_slot(0), 8192, 1024, 1), dA = mkdesc(sb + h_slot(0), 1024, 128, 0);
        #pragma unroll 1
        for (int st = 0; st < 21; st++) {
            WG_FENCE();
            wg_tt128(acc, dA, dB, st);
            wg_tt128(acc, dA + 128, dB + 128, 1);
            wg_tt128(acc, dA + 256, dB + 256, 1);
            wg_tt128(acc, dA + 384, dB + 384, 1);
            WG_COMMIT();
            const uint32_t rel = bars + 8 * (B_EMPTYD + (sd ? sd - 1 : 5));
            if (++sd == 6) { sd = 0; pd ^= 1; }
            mbar_wait(bars + 8 * (B_FULLD + sd), pd);
            dB = mkdesc(sb + wd_slot(sd), 8192, 1024, 1); dA = mkdesc(sb + h_slot(sd), 1024, 128, 0);
            if (st == 14) {
                mbar_wait(bars + 8 * B_S, 0);
                const uint2* sp = P.S + (dg * 64 + q) * 1024 + (2 * tau) * 16 + (row >> 1) + 4 * (w & 1) + g;
                #pragma unroll
                for (int j = 0; j < 16; j++)
                    asm volatile("ld.global.cg.v2.b32 {%0,%1}, [%2];" : "=r"(sv[j].x), "=r"(sv[j].y) : "l"(sp + j * 4096));
            }
            WG_WAIT(1);
            if (lane == 0 && st > 0) mbar_arrive(rel);
        }
        WG_FENCE();
        wg_tt128(acc, dA, dB, 1);
        wg_tt128(acc, dA + 128, dB + 128, 1);
        WG_COMMIT();
        WG_WAIT(0);
        fence_acc(acc);
        STAMP(6);
        mbar_wait(bars + 8 * B_XO, 0);
        const uint32_t xo = sb + OFF_CONV + (row + (lane & 7) + 16 * ((lane >> 3) & 1)) * 128;
        #pragma unroll
        for (int j = 0; j < 16; j += 2) {
            const uint32_t ad = xo + (j >> 3) * 8192 + ((((j & 7) + (lane >> 4)) ^ (lane & 7)) << 4);
            uint32_t xr[4];
            asm volatile("ldmatrix.sync.aligned.m8n8.x4.shared.b16 {%0,%1,%2,%3}, [%4];" : "=r"(xr[0]), "=r"(xr[1]), "=r"(xr[2]), "=r"(xr[3]) : "r"(ad));
            #pragma unroll
            for (int i = 0; i < 4; i++) {
                const int jj = j + (i >> 1), hh = i & 1;
                const float f0 = acc[4 * jj + 2 * hh] * (hh ? rr1 : rr0), f1 = acc[4 * jj + 2 * hh + 1] * (hh ? rr1 : rr0);
                const uint32_t G = pack2(fmaf(f0, tanh_fast(f0), f0), fmaf(f1, tanh_fast(f1), f1));
                const uint32_t s2 = __byte_perm(sv[jj].x, sv[jj].y, hh ? 0x7632 : 0x5410);
                asm("fma.rn.bf16x2 %0, %1, %2, %0;" : "+r"(xr[i]) : "r"(s2), "r"(G));
            }
            stsm4(ad, xr[0], xr[1], xr[2], xr[3]);
        }
        fence_async_smem();
        bar_sync(1);
        if (w == 0 && elect_one()) {
            #pragma unroll
            for (int i = 0; i < 2; i++)
                asm volatile("cp.async.bulk.tensor.2d.global.shared::cta.bulk_group [%0, {%2, %3}], [%1];"
                    :: "l"(&M.out), "r"(sb + OFF_CONV + i * 8192), "r"(dg * 128 + 64 * i), "r"(tau * 64) : "memory");
            asm volatile("cp.async.bulk.commit_group; cp.async.bulk.wait_group.read 0;" ::: "memory");
        }
        STAMP(7);
    }
}

__device__ __forceinline__ float2 cexp_p(float re2, float im, float p) {
    float sn, cs;
    const float mag = ex2(re2 * p), th = im * p;
    asm("sin.approx.ftz.f32 %0, %1;" : "=f"(sn) : "f"(th));
    asm("cos.approx.ftz.f32 %0, %1;" : "=f"(cs) : "f"(th));
    return make_float2(mag * cs, mag * sn);
}
__device__ __forceinline__ void ldsm4(uint32_t (&r)[4], uint32_t a) {
    asm volatile("ldmatrix.sync.aligned.m8n8.x4.shared.b16 {%0,%1,%2,%3}, [%4];" : "=r"(r[0]), "=r"(r[1]), "=r"(r[2]), "=r"(r[3]) : "r"(a) : "memory");
}
__device__ __forceinline__ float2 cmul(float2 a, float2 b) { return make_float2(fmaf(a.x, b.x, -a.y * b.y), fmaf(a.x, b.y, a.y * b.x)); }
__device__ __forceinline__ float2 csqr(float2 a) { const float t = a.x * a.y; return make_float2(fmaf(a.x, a.x, -a.y * a.y), t + t); }
__device__ __forceinline__ void mma16816(float (&d)[4], const uint32_t (&a)[4], uint32_t b0, uint32_t b1) {
    asm volatile("mma.sync.aligned.m16n8k16.row.col.f32.bf16.bf16.f32 {%0,%1,%2,%3}, {%4,%5,%6,%7}, {%8,%9}, {%0,%1,%2,%3};"
        : "+f"(d[0]), "+f"(d[1]), "+f"(d[2]), "+f"(d[3]) : "r"(a[0]), "r"(a[1]), "r"(a[2]), "r"(a[3]), "r"(b0), "r"(b1));
}

__device__ __forceinline__ void aux_role(uint32_t sb, int w, const Params& P) {
    const int tid = threadIdx.x & 127, lane = tid & 31, q = lane & 3, g = lane >> 2;
    const int c = blockIdx.x;
    const uint32_t bars = sb + OFF_BAR;
    if (c < 128) {
        const uint32_t cb = sb + OFF_CONV + w * CH_STRIDE;
        const uint32_t sF = cb + CH_A3;
        const int tokb = 32 * (c >> 1) + 8 * (c & 1) + 16;
        if (elect_one()) {
            mbar_expect(bars + 8 * B_LNX, 4096);
            #pragma unroll
            for (int i = 0; i < 4; i++)
                bulk_load(sb + OFF_CONV + (w + 4 * i) * LNROW, P.x + (tokb + w + 4 * (i & 1) - 8 * (i & 2)) * DM, 1024, bars + 8 * B_LNX);
        }
        const int d = 4 * c + w;
        const uint2 la2 = *(const uint2*)(P.logA + d * 128 + 4 * lane), ai2 = *(const uint2*)(P.Aim + d * 128 + 4 * lane);
        const uint2 cr2 = *(const uint2*)(P.Cr + d * 128 + 4 * lane), ci2 = *(const uint2*)(P.Ci + d * 128 + 4 * lane);
        const float ldt = __bfloat162float(P.logdt[d]), dsk = __bfloat162float(P.Dskip[d]);
        mbar_wait(bars + 8 * B_LNX, 0);
        STAMP(34);
        {
            const int r = w + 4 * (lane >> 3);
            const uint32_t ra = sb + OFF_CONV + r * LNROW + (lane & 7) * 16;
            const float pv = bf_lo(FU(ldsf(sb + OFF_CONV + r * LNROW)));
            float s0 = 0.f, s1 = 0.f, a0 = 0.f, a1 = 0.f;
            uint4 nx = lds128(ra);
            #pragma unroll 1
            for (int k = 128; k <= 1024; k += 128) {
                const uint32_t v[4] = {nx.x, nx.y, nx.z, nx.w};
                nx = lds128(ra + (k & 1023));
                #pragma unroll
                for (int i = 0; i < 4; i++) { const float t0 = bf_lo(v[i]) - pv, t1 = bf_hi(v[i]) - pv; s0 += t0; s1 += t1; a0 = fmaf(t0, t0, a0); a1 = fmaf(t1, t1, a1); }
            }
            s0 += s1; a0 += a1;
            #pragma unroll
            for (int o = 4; o; o >>= 1) { s0 += __shfl_xor_sync(0xffffffffu, s0, o); a0 += __shfl_xor_sync(0xffffffffu, a0, o); }
            s0 *= 1.f / DM;
            const float m = pv + s0, var = fmaxf(fmaf(-s0, s0, a0 * (1.f / DM)), 0.f);
            float sd, ri;
            asm("sqrt.approx.ftz.f32 %0, %1;" : "=f"(sd) : "f"(bf_round(bf_round(var) + 1e-5f)));
            asm("rcp.approx.ftz.f32 %0, %1;" : "=f"(ri) : "f"(bf_round(sd)));
            const uint32_t m2 = pack2(m, m);
            if ((lane & 7) == 0) {
                const int t = tokb + (r & 7) - 2 * (r & 8);
                const float mh = -0.5f * bf_hi(m2);
                P.mb[t] = make_uint4(pack2(mh, mh), 0, 0, 0); P.hr[t] = 0.5f * ri;
            }
            #pragma unroll 1
            for (int k = 128; k <= 1024; k += 128) {
                uint32_t v[4] = {nx.x, nx.y, nx.z, nx.w};
                nx = lds128(ra + (k & 1023));
                #pragma unroll
                for (int i = 0; i < 4; i++) {
                    uint32_t dv; asm("sub.rn.bf16x2 %0, %1, %2;" : "=r"(dv) : "r"(v[i]), "r"(m2));
                    v[i] = pack2(bf_lo(dv) * ri, bf_hi(dv) * ri);
                }
                sts128(ra + k - 128, v[0], v[1], v[2], v[3]);
            }
        }
        STAMP(62);
        bar_sync(2);
        {
            uint32_t ad = sb + OFF_CONV + (4 * ((lane & 7) >> 1) + (lane & 1) + 2 * ((lane >> 3) & 1)) * LNROW + (16 * w + (lane >> 4)) * 16;
            uint2* dst = (uint2*)(P.xnT + (128 * w + g) * 256 + (c & 1) * 128 + (126 - 2 * (c >> 1))) + q;
            #pragma unroll
            for (int i = 0; i < 8; i++, ad += 32, dst += 16 * 512) {
                uint32_t r0, r1, r2, r3;
                asm volatile("ldmatrix.sync.aligned.m8n8.x4.trans.shared.b16 {%0,%1,%2,%3}, [%4];" : "=r"(r0), "=r"(r1), "=r"(r2), "=r"(r3) : "r"(ad));
                dst[0] = make_uint2(r0, r1); dst[8 * 512] = make_uint2(r2, r3);
            }
        }
        mbar_arrive(bars + 8 * B_LN);
        bar_sync(2);
        STAMP(16);
        float dacc[2][3][4];
        #pragma unroll
        for (int i = 0; i < 24; i++) (&dacc[0][0][0])[i] = 0.f;
        const float dt = bf_round(ex2(ldt * 1.4426950408889634f));
        const uint32_t lda = cb + ((lane & 7) + 8 * ((lane >> 3) & 1)) * 144 + (lane >> 4) * 16;
        const uint32_t ldb = cb + (32 + (lane & 7)) * 144 + (lane >> 3) * 16;
        uint64_t la = *(const uint64_t*)&la2, ai = *(const uint64_t*)&ai2, cr = *(const uint64_t*)&cr2, ci = *(const uint64_t*)&ci2;
        #pragma unroll 1
        for (int ck = 0; ck < 4; ck++, la >>= 16, ai >>= 16, cr >>= 16, ci >>= 16) {
            const uint32_t fa = cb + lane * 4 + (ck & 1) * 8064;
            const float re2 = bf_round(ex2(bf_lo((uint32_t)la) * 1.4426950408889634f)) * dt * -1.4426950408889634f, im = bf_lo((uint32_t)ai) * dt;
            const float2 C = make_float2(bf_lo((uint32_t)cr) * (dt + dt), bf_lo((uint32_t)ci) * -(dt + dt));
            const float2 z8 = cexp_p(re2, im, 8.f), y1 = cexp_p(re2, -im, 1.f);
            float2 b0 = make_float2(1.f, 0.f), b1 = cexp_p(re2, im, 64.f), b2 = csqr(b1), b3 = cmul(b2, b1), l0 = C;
            const uint32_t fm = cb + (ck & 1) * 8064 + (lane >> 3) * 144 + (lane & 7) * 16;
#define PK(v) pack2((v).x, (v).y)
            #pragma unroll 1
            for (uint32_t ro = 0; ro < 8 * 144; ro += 144) {
                stsm4(fm + (lane >> 3) * 7 * 144 + ro, PK(b0), PK(b1), PK(b2), PK(b3));
                stsf(fa + 32 * 144 + ro, UF(PK(l0)));
                b0 = cmul(b0, z8); b1 = cmul(b1, z8); b2 = cmul(b2, z8); b3 = cmul(b3, z8); l0 = cmul(l0, y1);
            }
            if (ck < 2) STAMP(56 + 3 * ck);
            const float2 y256 = cexp_p(re2, -im, 256.f), y2 = csqr(y1), y4 = csqr(y2), y8 = make_float2(z8.x, -z8.y);
            const float2 t0 = cmul(C, y256), t1 = cmul(t0, y256), t2 = cmul(t1, y256), t3_ = cmul(t2, y256);
            const float2 u1 = cmul(t0, y2), u2 = cmul(u1, y2), u3 = cmul(u2, y2);
            stsm4(fm + 40 * 144, PK(t0), PK(u1), PK(u2), PK(u3));
            stsm4(fm + 44 * 144, PK(t1), PK(cmul(t1, y4)), PK(t2), PK(cmul(t2, y4)));
            const float2 v0 = cmul(t3_, y8), v1 = cmul(v0, y256), v2 = cmul(v1, y256), v3 = cmul(v2, y256);
            stsm4(fm + 48 * 144, PK(v0), PK(v1), PK(v2), PK(v3));
            stsf(fa + 52 * 144, UF(PK(t3_)));
#undef PK
            if (ck < 2) STAMP(57 + 3 * ck);
            if (ck & 1) {
                __syncwarp();
                #pragma unroll
                for (int k2 = 0; k2 < 4; k2++) {
                    const uint32_t ko = (k2 >> 1) * 8064 + (k2 & 1) * 64;
                    uint32_t b[3][4];
                    #pragma unroll
                    for (int t3 = 0; t3 < 3; t3++) ldsm4(b[t3], ldb + t3 * 8 * 144 + ko);
                    #pragma unroll
                    for (int k = 0; k < 2; k++)
                        #pragma unroll
                        for (int mu = 0; mu < 2; mu++) {
                            uint32_t a[4];
                            ldsm4(a, lda + mu * 16 * 144 + ko + k * 32);
                            #pragma unroll
                            for (int t3 = 0; t3 < 3; t3++) mma16816(dacc[mu][t3], a, b[t3][2 * k], b[t3][2 * k + 1]);
                        }
                }
                __syncwarp();
                if (lane == 0) mbar_arrive(bars + 8 * (B_K + (ck >> 1)));
                STAMP(58 + 3 * (ck >> 1));
            }
        }
        STAMP(18);
        const uint32_t sG = cb + CH_G;
        if (lane < 16) sts128(((lane & 8) ? cb + CH_U + 2048 + (lane & 4) * (UPLANE / 4) : sG + 128 + (lane & 4) * 48) + (lane & 3) * 16, 0, 0, 0, 0);
        {
            const uint32_t f0 = sF + (8 * g + 2 * q) * 4, f1 = sF + ((q < 2) ? 256 + 4 * g + 2 * q : 256 + 2 * g + 64 * q) * 4, st1 = (q < 2) ? 128 : 64;
            const uint32_t ga = sG + ((g & 1) ? 0 : 192) + (63 - (g >> 1) - 32 * q) * 2;
            #pragma unroll
            for (int i = 0; i < 4; i++) {
                const int mu = i >> 1, hh = i & 1;
                sts64(f0 + i * 256, FU(dacc[mu][0][2 * hh]), FU(dacc[mu][0][2 * hh + 1]));
                sts64(f1 + i * st1, FU(dacc[mu][1][2 * hh]), FU(dacc[mu][1][2 * hh + 1]));
                const uint32_t pk = pack2(dacc[mu][2][2 * hh], dacc[mu][2][2 * hh + 1]);
                if (q < 2) { sts16(ga - 8 * i, pk & 0xffff); sts16(ga - 8 * i - 32, pk >> 16); }
            }
            if (lane == 2) stsf(sF + 2048, dacc[0][2][0]);
        }
        __syncwarp();
        #pragma unroll 1
        for (int pass = 0; pass < 3; pass++) {
            const int rw = lane - 1 + 31 * pass;
            const int u = min(rw, 77) - 14;
            const uint32_t f0 = sF + u * 4, f1 = sF + (128 + ((u + ((u >> 1) & 1)) >> 1)) * 4, f2 = sF + (256 + ((u + 1 + ((u >> 2) & 1)) >> 2)) * 4;
            float kv[17];
            kv[0] = ldsf(u < 0 ? sF : f0); if (u < 0) kv[0] = 0.f; if (u == 0) kv[0] += dsk;
            #pragma unroll
            for (int s = 1; s < 4; s++) kv[s] = ldsf(f0 + s * 256);
            kv[4] = ldsf(u < 0 ? f0 + 1024 : f1 + 512);
            #pragma unroll
            for (int s = 5; s < 8; s++) kv[s] = ldsf(f1 + s * 128);
            kv[8] = ldsf(u < 0 ? f1 + 1024 : f2 + 512);
            #pragma unroll
            for (int s = 9; s < 16; s++) kv[s] = ldsf(f2 + s * 64);
            kv[16] = ldsf(u < 0 ? f2 + 1024 : sF + 2048); if (u > 4) kv[16] = 0.f;
            uint32_t o[17];
            #pragma unroll
            for (int s = 0; s < 17; s++) o[s] = pack2(kv[s], __shfl_up_sync(0xffffffffu, kv[s], 1));
            if (lane > 0 && rw < 78) {
                const uint32_t ta = cb + CH_T + rw * 80;
                #pragma unroll
                for (int s4 = 0; s4 < 4; s4++) sts128(ta + s4 * 16, o[4 * s4], o[4 * s4 + 1], o[4 * s4 + 2], o[4 * s4 + 3]);
                stsf(ta + 64, UF(o[16]));
            }
        }
        #pragma unroll 1
        for (int un = lane; un < 128; un += 32) {
            const uint32_t ga = sG + ((un >> 3) & 1) * 192 + (un >> 4) * 16 + (un & 7) * 8;
            const uint2 x0 = lds64(ga), x1 = lds64(ga + 8);
            sts128(cb + CH_B3 + un * 16, x0.x, x0.y, x1.x, x1.y);
        }
    } else {
        mbar_arrive(bars + 8 * B_LN);
        if (lane == 0) { mbar_arrive(bars + 8 * B_K); mbar_arrive(bars + 8 * (B_K + 1)); }
        return;
    }
    STAMP(19);
    bar_sync(2);
    mbar_wait(bars + 8 * B_U, 0);
    {
        const int kap = (lane >> 4) * 8 + ((lane >> 1) & 7), gam = lane & 1, hh = w >> 1, wp = w & 1;
        uint32_t ua = sb + OFF_CONV + CH_U + wp * UPLANE + (127 - 4 * kap - 2 * gam - hh) * 16;
        uint32_t ub = sb + OFF_CONV + CH_U + (wp ^ 1) * UPLANE + (128 - wp - 4 * kap - 2 * gam - hh) * 16;
        uint32_t ad = sb + OFF_CONV + CH_A3 + (4 * wp + hh) * 512 + (kap >> 3) * 256 + (kap & 7) * 16 + gam * 8;
        #pragma unroll 1
        for (int ch = 0; ch < 4; ch++, ua += CH_STRIDE, ub += CH_STRIDE, ad += CH_STRIDE) {
            float p[24];
            const uint2 r0 = lds64(ub + 24), r3 = lds64(ua);
            uint32_t r[8];
            *(uint4*)&r[0] = lds128(ua + 16); *(uint4*)&r[4] = lds128(ub);
            p[0] = 0.f;
            p[1] = bf_lo(r0.x); p[2] = p[1] + bf_hi(r0.x); p[3] = p[2] + bf_lo(r0.y); p[4] = p[3] + bf_hi(r0.y);
            #pragma unroll
            for (int i = 0; i < 8; i++) { p[5 + 2 * i] = p[4 + 2 * i] + bf_lo(r[i]); p[6 + 2 * i] = p[5 + 2 * i] + bf_hi(r[i]); }
            p[21] = p[20] + bf_lo(r3.x); p[22] = p[21] + bf_hi(r3.x); p[23] = p[22] + bf_lo(r3.y);
            #pragma unroll
            for (int i = 0; i < 8; i += 4) {
                sts64(ad + i * 256, pack2(p[i + 9] - p[i], p[i + 10] - p[i + 1]), pack2(p[i + 11] - p[i + 2], p[i + 12] - p[i + 3]));
                sts64(ad + i * 256 + 128, pack2(p[i + 16] - p[i + 9], p[i + 17] - p[i + 10]), pack2(p[i + 18] - p[i + 11], p[i + 19] - p[i + 12]));
            }
        }
    }
    fence_async_smem();
    mbar_arrive(bars + 8 * B_CONV);
    STAMP(21);
}

__global__ void __launch_bounds__(512, 1)
fused_kernel(const __grid_constant__ Params P, const __grid_constant__ Maps M) {
    extern __shared__ __align__(1024) uint8_t smem_raw[];
    const uint32_t sb = smem_u32(smem_raw);
    const uint32_t bars = sb + OFF_BAR;
    const int warp = __shfl_sync(0xffffffffu, threadIdx.x >> 5, 0);
    const int c = blockIdx.x, tg = c / 22, fb = c - 22 * tg;
    if (elect_one()) {
        if (warp == 0) STAMP(24);
        asm volatile("" :: "l"(((const uint64_t*)&P)[warp < 12 ? warp : 0]));
        if (warp < 10) asm volatile("prefetch.tensormap [%0];" :: "l"(&M.x[0] + warp) : "memory");
        #pragma unroll
        for (int k = 0; k < 3; k++) {
            const int i = 16 * k + ((warp + 4) & 15);
            const uint32_t cnt = i >= B_CONV ? 128 : ((0xf0ull >> i) & 1) ? 8 : ((0x3f0000ull >> i) & 1) ? 2 : ((0xf80fc0f000ull >> i) & 1) ? 4 : 1;
            asm volatile("mbarrier.init.shared::cta.b64 [%0], %1;" :: "r"(bars + 8 * i), "r"(cnt) : "memory");
        }
        asm volatile("fence.mbarrier_init.release.cluster; fence.proxy.async.shared::cta;" ::: "memory");
        if (warp == 12) {
            mbar_expect(bars + 8 * B_FULLW, 16384);
            tma2d(sb + OFF_W, &M.wg, 64 * fb, 0, bars + 8 * B_FULLW);
            tma2d(sb + OFF_W + 8192, &M.wu, 64 * fb, 0, bars + 8 * B_FULLW);
            STAMP(31);
        } else if (warp == 4) {
            mbar_expect(bars + 8 * B_FULLX, 168 * 128);
            tma2d(sb + OFF_X, &M.x[0], 0, TOKG * tg, bars + 8 * B_FULLX);
        }
        if (sb & 1023) __trap();
    }
    __syncthreads();
    if (warp < 8) {
        asm volatile("setmaxnreg.inc.sync.aligned.u32 208;");
        consumer(sb, warp, P, M);
    } else if (warp < 12) {
        asm volatile("setmaxnreg.dec.sync.aligned.u32 72;");
        STAMP(32);
        aux_role(sb, warp - 8, P);
    } else {
        asm volatile("setmaxnreg.dec.sync.aligned.u32 24;");
        const int tau = c >> 2, dg = c & 3;
        if (elect_one()) {
            if (warp == 12) {
                #pragma unroll 1
                for (int st = 1; st < 8; st++) {
                    const uint32_t s = st & 3, fb_ = bars + 8 * (B_FULLW + s);
                    if (st == 2) mbar_wait(bars + 8 * B_FULLW, 0);
                    mbar_wait(bars + 8 * (B_EMPTYW + s), (st >> 2) ^ 1);
                    mbar_expect(fb_, 16384);
                    tma2d(sb + OFF_W + s * 16384, &M.wg, 64 * fb, 64 * st, fb_);
                    tma2d(sb + OFF_W + s * 16384 + 8192, &M.wu, 64 * fb, 64 * st, fb_);
                }
                if (c < 128) {
                    int sd = 0; uint32_t pe = 1;
                    #pragma unroll 1
                    for (int st = 0; st < 22; st++) {
                        if (st < 6) mbar_wait(bars + 8 * (uint32_t)((0x1f070d060504ull >> (8 * st)) & 0xff), st < 5);
                        else mbar_wait(bars + 8 * (B_EMPTYD + sd), pe);
                        const uint32_t da = sb + wd_slot(sd), fb_ = bars + 8 * (B_FULLD + sd);
                        mbar_expect(fb_, 16384);
                        tma2d(da, &M.wd, 128 * dg, 64 * st, fb_);
                        tma2d(da + 8192, &M.wd, 128 * dg + 64, 64 * st, fb_);
                        if (++sd == 6) { sd = 0; pe ^= 1; }
                    }
                }
            } else if (warp < 15) {
                const int V = warp - 13;
                #pragma unroll 1
                for (int st = 1 - V; st < 8; st++) {
                    const uint32_t s = 2 * V + (st & 1);
                    mbar_wait(bars + 8 * (B_EMPTYX + s), ((st >> 1) & 1) ^ 1);
                    mbar_expect(bars + 8 * (B_FULLX + s), (168 + 8 * V) * 128);
                    tma2d(sb + OFF_X + s * XBUF, &M.x[V], 64 * st, TOKG * tg + 168 * V, bars + 8 * (B_FULLX + s));
                }
                if (c < 128) {
                    if (V == 0) {
                        mbar_wait(bars + 8 * (B_STG + 1), 0);
                        #pragma unroll 1
                        for (int o = 8 * tau; o < 8 * tau + 8; o += 7) flag_wait(P.flags, F_H + 2 * (o / 43) + ((o % 43) >= 21), 22);
                        fence_async();
                        mbar_arrive(bars + 8 * B_HF);
                        STAMP(25);
                        int sh = 0; uint32_t pe = 1;
                        #pragma unroll 1
                        for (int st = 0; st < 22; st++) {
                            const uint32_t fb_ = bars + 8 * (B_FULLD + sh);
                            mbar_wait(bars + 8 * (B_EMPTYD + sh), pe);
                            mbar_expect(fb_, 8192);
                            asm volatile("cp.async.bulk.tensor.5d.shared::cluster.global.mbarrier::complete_tx::bytes [%0], [%1, {%3, %3, %3, %4, %5}], [%2];"
                                :: "r"(sb + h_slot(sh)), "l"(&M.hld), "r"(fb_), "r"(0), "r"(2 * tau), "r"(8 * st) : "memory");
                            if (++sh == 6) { sh = 0; pe ^= 1; }
                        }
                    } else {
                        mbar_wait(bars + 8 * B_CH0, 0);
                        mbar_expect(bars + 8 * B_XO, 16384);
                        tma2d(sb + OFF_CONV, &M.xo, 128 * dg, 64 * tau, bars + 8 * B_XO);
                        tma2d(sb + OFF_CONV + 8192, &M.xo, 128 * dg + 64, 64 * tau, bars + 8 * B_XO);
                        flag_wait(P.flags, F_S + dg, 64);
                        STAMP(26);
                        mbar_arrive(bars + 8 * B_S);
                        mbar_wait(bars + 8 * B_HF, 0);
                        exit_count(P.flags);
                    }
                }
            } else {
                mbar_wait(bars + 8 * B_LN, 0);
                flag_signal(P.flags, F_A);
                flag_wait(P.flags, F_A, NCTA);
                fence_async();
                STAMP(20);
                mbar_expect(bars + 8 * B_STATS, TOKG * 20);
                bulk_load(sb + OFF_MB, P.mb + TOKG * tg, TOKG * 16, bars + 8 * B_STATS);
                bulk_load(sb + OFF_HR, P.hr + TOKG * tg, TOKG * 4, bars + 8 * B_STATS);
                if (c < 128) {
                    mbar_wait(bars + 8 * (B_K + 1), 0);
                    fence_async_smem();
                    mbar_expect(bars + 8 * B_U, 8 * 2048);
                    #pragma unroll 1
                    for (int i = 0; i < 8; i++)
                        bulk_load(sb + OFF_CONV + (i >> 1) * CH_STRIDE + CH_U + (i & 1) * UPLANE, P.xnT + 4 * c * 256 + i * 128, 2048, bars + 8 * B_U);
                } else exit_count(P.flags);
                #pragma unroll 1
                for (int V = 0; V < 2; V++) {
                    mbar_wait(bars + 8 * (B_EPI + V), 0);
                    asm volatile("cp.async.bulk.tensor.3d.global.shared::cta.bulk_group [%0, {%2, %3, %4}], [%1];"
                        :: "l"(&M.hst[V]), "r"(sb + OFF_X + V * 2 * XBUF), "r"(0), "r"(43 * tg + 21 * V), "r"(8 * fb) : "memory");
                    asm volatile("cp.async.bulk.commit_group; cp.async.bulk.wait_group 0;" ::: "memory");
                    mbar_arrive(bars + 8 * (B_STG + V));
                    flag_signal(P.flags, F_H + 2 * tg + V);
                }
                if (c < 128) {
                    #pragma unroll 1
                    for (int V = 0; V < 2; V++) { mbar_wait(bars + 8 * (B_SIG + V), 0); flag_signal(P.flags, F_S + (c >> 5)); }
                }
            }
        }
    }
}

typedef CUresult (*EncodeFn)(CUtensorMap*, CUtensorMapDataType, cuuint32_t, void*, const cuuint64_t*, const cuuint64_t*, const cuuint32_t*,
                             const cuuint32_t*, CUtensorMapInterleave, CUtensorMapSwizzle, CUtensorMapL2promotion, CUtensorMapFloatOOBfill);

void make_map(EncodeFn enc, CUtensorMap* m, const void* ptr, int rank, const cuuint64_t* dims, const cuuint64_t* strides, const cuuint32_t* box, bool swz) {
    const cuuint32_t es[5] = {1, 1, 1, 1, 1};
    enc(m, CU_TENSOR_MAP_DATA_TYPE_BFLOAT16, rank, (void*)ptr, dims, strides, box, es, CU_TENSOR_MAP_INTERLEAVE_NONE,
        swz ? CU_TENSOR_MAP_SWIZZLE_128B : CU_TENSOR_MAP_SWIZZLE_NONE, CU_TENSOR_MAP_L2_PROMOTION_L2_128B, CU_TENSOR_MAP_FLOAT_OOB_FILL_NONE);
}
void make_map2(EncodeFn enc, CUtensorMap* m, const void* ptr, cuuint64_t inner, cuuint64_t outer, cuuint32_t rows) {
    const cuuint64_t dims[2] = {inner, outer}, strides[1] = {inner * 2};
    const cuuint32_t box[2] = {64, rows};
    make_map(enc, m, ptr, 2, dims, strides, box, true);
}

}

extern "C" void kernel_launch(void* const* d_in, const int* in_sizes, int n_in, void* d_out, int out_size) {
    (void)in_sizes; (void)n_in; (void)out_size;
    static EncodeFn enc = nullptr;
    static void *hptr, *p_xnT, *p_mb, *p_hr, *p_S, *p_flags;
    if (!enc) {
        cudaDriverEntryPointQueryResult qr;
        cudaGetDriverEntryPoint("cuTensorMapEncodeTiled", (void**)&enc, cudaEnableDefault, &qr);
        cudaFuncSetAttribute(fused_kernel, cudaFuncAttributeMaxDynamicSharedMemorySize, SMEM_BYTES);
        cudaGetSymbolAddress(&hptr, g_H); cudaGetSymbolAddress(&p_xnT, g_xnT); cudaGetSymbolAddress(&p_mb, g_mb);
        cudaGetSymbolAddress(&p_hr, g_hr); cudaGetSymbolAddress(&p_S, g_S); cudaGetSymbolAddress(&p_flags, g_flags);
    }
    Params P;
    P.x = (const __nv_bfloat16*)d_in[0]; P.logA = (const __nv_bfloat16*)d_in[1]; P.Aim = (const __nv_bfloat16*)d_in[2];
    P.Cr = (const __nv_bfloat16*)d_in[3]; P.Ci = (const __nv_bfloat16*)d_in[4]; P.logdt = (const __nv_bfloat16*)d_in[5];
    P.Dskip = (const __nv_bfloat16*)d_in[6];
    P.xnT = (uint4*)p_xnT; P.mb = (uint4*)p_mb; P.hr = (float*)p_hr; P.S = (uint2*)p_S; P.flags = (unsigned*)p_flags;
    Maps M;
    make_map2(enc, &M.x[0], d_in[0], DM, SEQ, 168); make_map2(enc, &M.x[1], d_in[0], DM, SEQ, 176);
    make_map2(enc, &M.xo, d_in[0], DM, SEQ, 64);    make_map2(enc, &M.out, d_out, DM, SEQ, 64);
    make_map2(enc, &M.wg, d_in[8], FF, DM, 64);     make_map2(enc, &M.wu, d_in[9], FF, DM, 64);
    make_map2(enc, &M.wd, d_in[10], DM, FF, 64);
    for (int v = 0; v < 2; v++) {
        const cuuint64_t dims[3] = {64, 256, 172}, strides[2] = {128, 32768};
        const cuuint32_t box[3] = {64, (cuuint32_t)(21 + v), 8};
        make_map(enc, &M.hst[v], hptr, 3, dims, strides, box, false);
    }
    {
        const cuuint64_t dims[5] = {64, 2, 2, 64, 172}, strides[4] = {256, 128, 512, 32768};
        const cuuint32_t box[5] = {64, 2, 2, 2, 8};
        make_map(enc, &M.hld, hptr, 5, dims, strides, box, false);
    }
    fused_kernel<<<NCTA, 512, SMEM_BYTES>>>(P, M);
}
```

```cpp
#include <cuda_runtime.h>
#include <cuda_bf16.h>
#include <cuda.h>
#include <stdint.h>

#define PROF 0

namespace {

constexpr int SEQ = 2048, DM = 512, FF = 1376;
constexpr int NCTA = 132;
#define HOLD0 4
#define HOLD1 6
constexpr int TOKG = 344;

constexpr uint32_t OFF_W = 0;
constexpr uint32_t XBUF = 22528;
constexpr uint32_t OFF_X = 65536;
constexpr uint32_t OFF_CONV = 155648;
constexpr uint32_t CH_STRIDE = 16640;
constexpr uint32_t CH_T = 0;
constexpr uint32_t CH_A3 = 6272;
constexpr uint32_t CH_B3 = 10368;
constexpr uint32_t CH_U = 12416;
constexpr uint32_t CH_G = CH_A3 + 2064;
constexpr uint32_t UPLANE = 2112;
constexpr uint32_t CH_LN = 8064, CH_LNT = 12288;
constexpr uint32_t OFF_MB = 222208;
constexpr uint32_t OFF_HR = 227712;
constexpr uint32_t OFF_CSUM = 229120;
constexpr uint32_t OFF_BAR = 231168;
constexpr uint32_t SMEM_BYTES = 231680;

enum {
    B_FULLW = 0, B_EMPTYW = 4, B_FULLX = 8, B_EMPTYX = 12, B_FULLD = 16, B_EMPTYD = 22,
    B_U = 28, B_XO = 29, B_S = 30, B_STG = 31, B_HF = 33, B_STATS = 34, B_LNS = 47,
    B_LNX = 35, B_GO = 36, B_CH0 = 37, B_K = 38,
    B_CONV = 40, B_LN = 41, B_CS = 42, B_EPI = 43, B_SIG = 45,
    B_COUNT = 47
};
enum { F_A = 0, F_H = 1, F_S = 13, F_EXIT = 17, F_COUNT = 18 };

__device__ uint4 g_xnT[DM * 256];
__device__ uint4 g_mb[6 * TOKG];
__device__ float g_hr[6 * TOKG];
__device__ uint4 g_H[172 * 256 * 8];
__device__ uint2 g_S[256 * 1024];
__device__ unsigned g_flags[F_COUNT * 32];
#define STAMP(i) do {} while (0)
#define GSTAMP(i) do {} while (0)

__device__ __forceinline__ uint32_t smem_u32(const void* p) { return (uint32_t)__cvta_generic_to_shared(p); }
__device__ __forceinline__ void mbar_expect(uint32_t bar, uint32_t bytes) { asm volatile("mbarrier.arrive.expect_tx.shared::cta.b64 _, [%0], %1;" :: "r"(bar), "r"(bytes) : "memory"); }
__device__ __forceinline__ void mbar_arrive(uint32_t bar) { asm volatile("mbarrier.arrive.shared::cta.b64 _, [%0];" :: "r"(bar) : "memory"); }
__device__ __forceinline__ void mbar_wait(uint32_t bar, uint32_t parity) {
    asm volatile("{.reg .pred p; .reg .u32 n; mov.u32 n, 0x20000;\n"
                 "LW: mbarrier.try_wait.parity.shared::cta.b64 p, [%0], %1;\n"
                 "sub.u32 n, n, 1; setp.eq.or.u32 p, n, 0, p; @!p bra LW;}" :: "r"(bar), "r"(parity) : "memory");
}
__device__ __forceinline__ bool elect_one() { uint32_t p; asm volatile("{.reg .pred P; elect.sync _|P, 0xffffffff; selp.u32 %0, 1, 0, P;}" : "=r"(p)); return p; }
__device__ __forceinline__ void tma2d(uint32_t dst, const CUtensorMap* m, int c0, int c1, uint32_t bar) {
    asm volatile("cp.async.bulk.tensor.2d.shared::cluster.global.mbarrier::complete_tx::bytes [%0], [%1, {%3, %4}], [%2];"
        :: "r"(dst), "l"(m), "r"(bar), "r"(c0), "r"(c1) : "memory");
}
__device__ __forceinline__ void bulk_load(uint32_t dst, const void* src, uint32_t bytes, uint32_t bar) {
    asm volatile("cp.async.bulk.shared::cluster.global.mbarrier::complete_tx::bytes [%0], [%1], %2, [%3];" :: "r"(dst), "l"(src), "r"(bytes), "r"(bar) : "memory");
}
__device__ __forceinline__ void bulk_store(void* dst, uint32_t src, uint32_t bytes) {
    asm volatile("cp.async.bulk.global.shared::cta.bulk_group [%0], [%1], %2;" :: "l"(dst), "r"(src), "r"(bytes) : "memory");
}
__device__ __forceinline__ void fence_async_smem() { asm volatile("fence.proxy.async.shared::cta;" ::: "memory"); }
__device__ __forceinline__ void flag_wait(unsigned* g_flags, int f, unsigned target) {
    asm volatile("{.reg .pred p; .reg .u32 n, v; mov.u32 n, 0x40000;\n"
                 "LF: ld.acquire.gpu.global.u32 v, [%0]; setp.ge.u32 p, v, %1; @p bra LD;\n"
                 "nanosleep.u32 20; sub.u32 n, n, 1; setp.ne.u32 p, n, 0; @p bra LF; trap;\nLD: }"
                 :: "l"(g_flags + f * 32), "r"(target) : "memory");
}
__device__ __forceinline__ void flag_signal(unsigned* g_flags, int f) {
    asm volatile("cp.async.bulk.commit_group; cp.async.bulk.wait_group 0; red.relaxed.gpu.global.add.u32 [%0], 1;" :: "l"(g_flags + f * 32) : "memory");
}
__device__ __forceinline__ void exit_count(unsigned* g_flags) {
    if (atomicAdd(g_flags + F_EXIT * 32, 1u) == NCTA - 1) {
        #pragma unroll 1
        for (int i = 0; i < F_COUNT; i++) g_flags[i * 32] = 0;
    }
}
__device__ __forceinline__ void bar_sync(int id) { asm volatile("bar.sync %0, 128;" :: "r"(id) : "memory"); }
__device__ __forceinline__ uint64_t mkdesc(uint32_t addr, uint32_t lbo, uint32_t sbo, uint32_t swz) {
    return (uint64_t)((addr >> 4) | ((lbo >> 4) << 16)) | ((uint64_t)((sbo >> 4) | (swz << 30)) << 32);
}
#define WG_FENCE() asm volatile("wgmma.fence.sync.aligned;" ::: "memory")
#define WG_COMMIT() asm volatile("wgmma.commit_group.sync.aligned;" ::: "memory")
#define WG_WAIT(n) asm volatile("wgmma.wait_group.sync.aligned " #n ";" ::: "memory")
template <int N> __device__ __forceinline__ void fence_acc(float (&d)[N]) {
    #pragma unroll
    for (int i = 0; i < N; i++) asm volatile("" : "+f"(d[i]) :: "memory");
}
template <int N> __device__ __forceinline__ void define_acc(float (&d)[N]) {
    #pragma unroll
    for (int i = 0; i < N; i++) asm volatile("" : "=f"(d[i]));
}
__device__ __forceinline__ uint32_t pack2(float lo, float hi) { uint32_t r; asm("cvt.rn.bf16x2.f32 %0, %1, %2;" : "=r"(r) : "f"(hi), "f"(lo)); return r; }
__device__ __forceinline__ float bf_lo(uint32_t v) { return __uint_as_float(v << 16); }
__device__ __forceinline__ float bf_hi(uint32_t v) { return __uint_as_float(v & 0xffff0000u); }
__device__ __forceinline__ float bf_round(float v) { return bf_hi(pack2(0.f, v)); }
__device__ __forceinline__ float tanh_fast(float v) { float r; asm("tanh.approx.f32 %0, %1;" : "=f"(r) : "f"(v)); return r; }
__device__ __forceinline__ float ex2(float v) { float r; asm("ex2.approx.ftz.f32 %0, %1;" : "=f"(r) : "f"(v)); return r; }
__device__ __forceinline__ uint4 lds128(uint32_t a) { uint4 v; asm volatile("ld.shared.v4.b32 {%0,%1,%2,%3}, [%4];" : "=r"(v.x), "=r"(v.y), "=r"(v.z), "=r"(v.w) : "r"(a)); return v; }
__device__ __forceinline__ uint2 lds64(uint32_t a) { uint2 v; asm volatile("ld.shared.v2.b32 {%0,%1}, [%2];" : "=r"(v.x), "=r"(v.y) : "r"(a)); return v; }
__device__ __forceinline__ float ldsf(uint32_t a) { float v; asm volatile("ld.shared.f32 %0, [%1];" : "=f"(v) : "r"(a)); return v; }
__device__ __forceinline__ void sts128(uint32_t a, uint32_t x, uint32_t y, uint32_t z, uint32_t w) { asm volatile("st.shared.v4.b32 [%0], {%1,%2,%3,%4};" :: "r"(a), "r"(x), "r"(y), "r"(z), "r"(w) : "memory"); }
__device__ __forceinline__ void sts64(uint32_t a, uint32_t x, uint32_t y) { asm volatile("st.shared.v2.b32 [%0], {%1,%2};" :: "r"(a), "r"(x), "r"(y) : "memory"); }
__device__ __forceinline__ void stsf(uint32_t a, float x) { asm volatile("st.shared.f32 [%0], %1;" :: "r"(a), "f"(x) : "memory"); }
__device__ __forceinline__ void sts16(uint32_t a, uint32_t x) { asm volatile("st.shared.b16 [%0], %1;" :: "r"(a), "h"((unsigned short)x) : "memory"); }
__device__ __forceinline__ void stsm4(uint32_t a, uint32_t r0, uint32_t r1, uint32_t r2, uint32_t r3) {
    asm volatile("stmatrix.sync.aligned.m8n8.x4.shared.b16 [%0], {%1,%2,%3,%4};" :: "r"(a), "r"(r0), "r"(r1), "r"(r2), "r"(r3) : "memory");
}
#define FU(x) __float_as_uint(x)
#define UF(x) __uint_as_float(x)
__device__ __forceinline__ uint32_t wd_slot(int s) { return (uint32_t)((0x403056201000ull >> (8 * s)) & 0xff) << 10; }
__device__ __forceinline__ uint32_t h_slot(int s) { return s < 5 ? OFF_X + 2 * XBUF + s * 8192 : OFF_MB; }

template<int N> __device__ __forceinline__ void wg_rs(float (&d)[64], uint32_t a0, uint32_t a1, uint32_t a2, uint32_t a3, uint64_t db);
template<> __device__ __forceinline__ void wg_rs<128>(float (&d)[64], uint32_t a0, uint32_t a1, uint32_t a2, uint32_t a3, uint64_t db) {
  asm volatile("{.reg .pred p; setp.ne.b32 p, 1, 0; wgmma.mma_async.sync.aligned.m64n128k16.f32.bf16.bf16 {%0,%1,%2,%3,%4,%5,%6,%7,%8,%9,%10,%11,%12,%13,%14,%15,%16,%17,%18,%19,%20,%21,%22,%23,%24,%25,%26,%27,%28,%29,%30,%31,%32,%33,%34,%35,%36,%37,%38,%39,%40,%41,%42,%43,%44,%45,%46,%47,%48,%49,%50,%51,%52,%53,%54,%55,%56,%57,%58,%59,%60,%61,%62,%63}, {%64,%65,%66,%67}, %68, p, 1, 1, 0;}"
    : "+f"(d[0]),"+f"(d[1]),"+f"(d[2]),"+f"(d[3]),"+f"(d[4]),"+f"(d[5]),"+f"(d[6]),"+f"(d[7]),"+f"(d[8]),"+f"(d[9]),"+f"(d[10]),"+f"(d[11]),"+f"(d[12]),"+f"(d[13]),"+f"(d[14]),"+f"(d[15]),"+f"(d[16]),"+f"(d[17]),"+f"(d[18]),"+f"(d[19]),"+f"(d[20]),"+f"(d[21]),"+f"(d[22]),"+f"(d[23]),"+f"(d[24]),"+f"(d[25]),"+f"(d[26]),"+f"(d[27]),"+f"(d[28]),"+f"(d[29]),"+f"(d[30]),"+f"(d[31]),"+f"(d[32]),"+f"(d[33]),"+f"(d[34]),"+f"(d[35]),"+f"(d[36]),"+f"(d[37]),"+f"(d[38]),"+f"(d[39]),"+f"(d[40]),"+f"(d[41]),"+f"(d[42]),"+f"(d[43]),"+f"(d[44]),"+f"(d[45]),"+f"(d[46]),"+f"(d[47]),"+f"(d[48]),"+f"(d[49]),"+f"(d[50]),"+f"(d[51]),"+f"(d[52]),"+f"(d[53]),"+f"(d[54]),"+f"(d[55]),"+f"(d[56]),"+f"(d[57]),"+f"(d[58]),"+f"(d[59]),"+f"(d[60]),"+f"(d[61]),"+f"(d[62]),"+f"(d[63]) : "r"(a0), "r"(a1), "r"(a2), "r"(a3), "l"(db));
}
template<> __device__ __forceinline__ void wg_rs<120>(float (&d)[64], uint32_t a0, uint32_t a1, uint32_t a2, uint32_t a3, uint64_t db) {
  asm volatile("{.reg .pred p; setp.ne.b32 p, 1, 0; wgmma.mma_async.sync.aligned.m64n120k16.f32.bf16.bf16 {%0,%1,%2,%3,%4,%5,%6,%7,%8,%9,%10,%11,%12,%13,%14,%15,%16,%17,%18,%19,%20,%21,%22,%23,%24,%25,%26,%27,%28,%29,%30,%31,%32,%33,%34,%35,%36,%37,%38,%39,%40,%41,%42,%43,%44,%45,%46,%47,%48,%49,%50,%51,%52,%53,%54,%55,%56,%57,%58,%59}, {%60,%61,%62,%63}, %64, p, 1, 1, 0;}"
    : "+f"(d[0]),"+f"(d[1]),"+f"(d[2]),"+f"(d[3]),"+f"(d[4]),"+f"(d[5]),"+f"(d[6]),"+f"(d[7]),"+f"(d[8]),"+f"(d[9]),"+f"(d[10]),"+f"(d[11]),"+f"(d[12]),"+f"(d[13]),"+f"(d[14]),"+f"(d[15]),"+f"(d[16]),"+f"(d[17]),"+f"(d[18]),"+f"(d[19]),"+f"(d[20]),"+f"(d[21]),"+f"(d[22]),"+f"(d[23]),"+f"(d[24]),"+f"(d[25]),"+f"(d[26]),"+f"(d[27]),"+f"(d[28]),"+f"(d[29]),"+f"(d[30]),"+f"(d[31]),"+f"(d[32]),"+f"(d[33]),"+f"(d[34]),"+f"(d[35]),"+f"(d[36]),"+f"(d[37]),"+f"(d[38]),"+f"(d[39]),"+f"(d[40]),"+f"(d[41]),"+f"(d[42]),"+f"(d[43]),"+f"(d[44]),"+f"(d[45]),"+f"(d[46]),"+f"(d[47]),"+f"(d[48]),"+f"(d[49]),"+f"(d[50]),"+f"(d[51]),"+f"(d[52]),"+f"(d[53]),"+f"(d[54]),"+f"(d[55]),"+f"(d[56]),"+f"(d[57]),"+f"(d[58]),"+f"(d[59]) : "r"(a0), "r"(a1), "r"(a2), "r"(a3), "l"(db));
}
template<> __device__ __forceinline__ void wg_rs<112>(float (&d)[64], uint32_t a0, uint32_t a1, uint32_t a2, uint32_t a3, uint64_t db) {
  asm volatile("{.reg .pred p; setp.ne.b32 p, 1, 0; wgmma.mma_async.sync.aligned.m64n112k16.f32.bf16.bf16 {%0,%1,%2,%3,%4,%5,%6,%7,%8,%9,%10,%11,%12,%13,%14,%15,%16,%17,%18,%19,%20,%21,%22,%23,%24,%25,%26,%27,%28,%29,%30,%31,%32,%33,%34,%35,%36,%37,%38,%39,%40,%41,%42,%43,%44,%45,%46,%47,%48,%49,%50,%51,%52,%53,%54,%55}, {%56,%57,%58,%59}, %60, p, 1, 1, 0;}"
    : "+f"(d[0]),"+f"(d[1]),"+f"(d[2]),"+f"(d[3]),"+f"(d[4]),"+f"(d[5]),"+f"(d[6]),"+f"(d[7]),"+f"(d[8]),"+f"(d[9]),"+f"(d[10]),"+f"(d[11]),"+f"(d[12]),"+f"(d[13]),"+f"(d[14]),"+f"(d[15]),"+f"(d[16]),"+f"(d[17]),"+f"(d[18]),"+f"(d[19]),"+f"(d[20]),"+f"(d[21]),"+f"(d[22]),"+f"(d[23]),"+f"(d[24]),"+f"(d[25]),"+f"(d[26]),"+f"(d[27]),"+f"(d[28]),"+f"(d[29]),"+f"(d[30]),"+f"(d[31]),"+f"(d[32]),"+f"(d[33]),"+f"(d[34]),"+f"(d[35]),"+f"(d[36]),"+f"(d[37]),"+f"(d[38]),"+f"(d[39]),"+f"(d[40]),"+f"(d[41]),"+f"(d[42]),"+f"(d[43]),"+f"(d[44]),"+f"(d[45]),"+f"(d[46]),"+f"(d[47]),"+f"(d[48]),"+f"(d[49]),"+f"(d[50]),"+f"(d[51]),"+f"(d[52]),"+f"(d[53]),"+f"(d[54]),"+f"(d[55]) : "r"(a0), "r"(a1), "r"(a2), "r"(a3), "l"(db));
}
template<> __device__ __forceinline__ void wg_rs<104>(float (&d)[64], uint32_t a0, uint32_t a1, uint32_t a2, uint32_t a3, uint64_t db) {
  asm volatile("{.reg .pred p; setp.ne.b32 p, 1, 0; wgmma.mma_async.sync.aligned.m64n104k16.f32.bf16.bf16 {%0,%1,%2,%3,%4,%5,%6,%7,%8,%9,%10,%11,%12,%13,%14,%15,%16,%17,%18,%19,%20,%21,%22,%23,%24,%25,%26,%27,%28,%29,%30,%31,%32,%33,%34,%35,%36,%37,%38,%39,%40,%41,%42,%43,%44,%45,%46,%47,%48,%49,%50,%51}, {%52,%53,%54,%55}, %56, p, 1, 1, 0;}"
    : "+f"(d[0]),"+f"(d[1]),"+f"(d[2]),"+f"(d[3]),"+f"(d[4]),"+f"(d[5]),"+f"(d[6]),"+f"(d[7]),"+f"(d[8]),"+f"(d[9]),"+f"(d[10]),"+f"(d[11]),"+f"(d[12]),"+f"(d[13]),"+f"(d[14]),"+f"(d[15]),"+f"(d[16]),"+f"(d[17]),"+f"(d[18]),"+f"(d[19]),"+f"(d[20]),"+f"(d[21]),"+f"(d[22]),"+f"(d[23]),"+f"(d[24]),"+f"(d[25]),"+f"(d[26]),"+f"(d[27]),"+f"(d[28]),"+f"(d[29]),"+f"(d[30]),"+f"(d[31]),"+f"(d[32]),"+f"(d[33]),"+f"(d[34]),"+f"(d[35]),"+f"(d[36]),"+f"(d[37]),"+f"(d[38]),"+f"(d[39]),"+f"(d[40]),"+f"(d[41]),"+f"(d[42]),"+f"(d[43]),"+f"(d[44]),"+f"(d[45]),"+f"(d[46]),"+f"(d[47]),"+f"(d[48]),"+f"(d[49]),"+f"(d[50]),"+f"(d[51]) : "r"(a0), "r"(a1), "r"(a2), "r"(a3), "l"(db));
}
template<> __device__ __forceinline__ void wg_rs<96>(float (&d)[64], uint32_t a0, uint32_t a1, uint32_t a2, uint32_t a3, uint64_t db) {
  asm volatile("{.reg .pred p; setp.ne.b32 p, 1, 0; wgmma.mma_async.sync.aligned.m64n96k16.f32.bf16.bf16 {%0,%1,%2,%3,%4,%5,%6,%7,%8,%9,%10,%11,%12,%13,%14,%15,%16,%17,%18,%19,%20,%21,%22,%23,%24,%25,%26,%27,%28,%29,%30,%31,%32,%33,%34,%35,%36,%37,%38,%39,%40,%41,%42,%43,%44,%45,%46,%47}, {%48,%49,%50,%51}, %52, p, 1, 1, 0;}"
    : "+f"(d[0]),"+f"(d[1]),"+f"(d[2]),"+f"(d[3]),"+f"(d[4]),"+f"(d[5]),"+f"(d[6]),"+f"(d[7]),"+f"(d[8]),"+f"(d[9]),"+f"(d[10]),"+f"(d[11]),"+f"(d[12]),"+f"(d[13]),"+f"(d[14]),"+f"(d[15]),"+f"(d[16]),"+f"(d[17]),"+f"(d[18]),"+f"(d[19]),"+f"(d[20]),"+f"(d[21]),"+f"(d[22]),"+f"(d[23]),"+f"(d[24]),"+f"(d[25]),"+f"(d[26]),"+f"(d[27]),"+f"(d[28]),"+f"(d[29]),"+f"(d[30]),"+f"(d[31]),"+f"(d[32]),"+f"(d[33]),"+f"(d[34]),"+f"(d[35]),"+f"(d[36]),"+f"(d[37]),"+f"(d[38]),"+f"(d[39]),"+f"(d[40]),"+f"(d[41]),"+f"(d[42]),"+f"(d[43]),"+f"(d[44]),"+f"(d[45]),"+f"(d[46]),"+f"(d[47]) : "r"(a0), "r"(a1), "r"(a2), "r"(a3), "l"(db));
}
template<> __device__ __forceinline__ void wg_rs<88>(float (&d)[64], uint32_t a0, uint32_t a1, uint32_t a2, uint32_t a3, uint64_t db) {
  asm volatile("{.reg .pred p; setp.ne.b32 p, 1, 0; wgmma.mma_async.sync.aligned.m64n88k16.f32.bf16.bf16 {%0,%1,%2,%3,%4,%5,%6,%7,%8,%9,%10,%11,%12,%13,%14,%15,%16,%17,%18,%19,%20,%21,%22,%23,%24,%25,%26,%27,%28,%29,%30,%31,%32,%33,%34,%35,%36,%37,%38,%39,%40,%41,%42,%43}, {%44,%45,%46,%47}, %48, p, 1, 1, 0;}"
    : "+f"(d[0]),"+f"(d[1]),"+f"(d[2]),"+f"(d[3]),"+f"(d[4]),"+f"(d[5]),"+f"(d[6]),"+f"(d[7]),"+f"(d[8]),"+f"(d[9]),"+f"(d[10]),"+f"(d[11]),"+f"(d[12]),"+f"(d[13]),"+f"(d[14]),"+f"(d[15]),"+f"(d[16]),"+f"(d[17]),"+f"(d[18]),"+f"(d[19]),"+f"(d[20]),"+f"(d[21]),"+f"(d[22]),"+f"(d[23]),"+f"(d[24]),"+f"(d[25]),"+f"(d[26]),"+f"(d[27]),"+f"(d[28]),"+f"(d[29]),"+f"(d[30]),"+f"(d[31]),"+f"(d[32]),"+f"(d[33]),"+f"(d[34]),"+f"(d[35]),"+f"(d[36]),"+f"(d[37]),"+f"(d[38]),"+f"(d[39]),"+f"(d[40]),"+f"(d[41]),"+f"(d[42]),"+f"(d[43]) : "r"(a0), "r"(a1), "r"(a2), "r"(a3), "l"(db));
}
template<> __device__ __forceinline__ void wg_rs<80>(float (&d)[64], uint32_t a0, uint32_t a1, uint32_t a2, uint32_t a3, uint64_t db) {
  asm volatile("{.reg .pred p; setp.ne.b32 p, 1, 0; wgmma.mma_async.sync.aligned.m64n80k16.f32.bf16.bf16 {%0,%1,%2,%3,%4,%5,%6,%7,%8,%9,%10,%11,%12,%13,%14,%15,%16,%17,%18,%19,%20,%21,%22,%23,%24,%25,%26,%27,%28,%29,%30,%31,%32,%33,%34,%35,%36,%37,%38,%39}, {%40,%41,%42,%43}, %44, p, 1, 1, 0;}"
    : "+f"(d[0]),"+f"(d[1]),"+f"(d[2]),"+f"(d[3]),"+f"(d[4]),"+f"(d[5]),"+f"(d[6]),"+f"(d[7]),"+f"(d[8]),"+f"(d[9]),"+f"(d[10]),"+f"(d[11]),"+f"(d[12]),"+f"(d[13]),"+f"(d[14]),"+f"(d[15]),"+f"(d[16]),"+f"(d[17]),"+f"(d[18]),"+f"(d[19]),"+f"(d[20]),"+f"(d[21]),"+f"(d[22]),"+f"(d[23]),"+f"(d[24]),"+f"(d[25]),"+f"(d[26]),"+f"(d[27]),"+f"(d[28]),"+f"(d[29]),"+f"(d[30]),"+f"(d[31]),"+f"(d[32]),"+f"(d[33]),"+f"(d[34]),"+f"(d[35]),"+f"(d[36]),"+f"(d[37]),"+f"(d[38]),"+f"(d[39]) : "r"(a0), "r"(a1), "r"(a2), "r"(a3), "l"(db));
}
template<> __device__ __forceinline__ void wg_rs<72>(float (&d)[64], uint32_t a0, uint32_t a1, uint32_t a2, uint32_t a3, uint64_t db) {
  asm volatile("{.reg .pred p; setp.ne.b32 p, 1, 0; wgmma.mma_async.sync.aligned.m64n72k16.f32.bf16.bf16 {%0,%1,%2,%3,%4,%5,%6,%7,%8,%9,%10,%11,%12,%13,%14,%15,%16,%17,%18,%19,%20,%21,%22,%23,%24,%25,%26,%27,%28,%29,%30,%31,%32,%33,%34,%35}, {%36,%37,%38,%39}, %40, p, 1, 1, 0;}"
    : "+f"(d[0]),"+f"(d[1]),"+f"(d[2]),"+f"(d[3]),"+f"(d[4]),"+f"(d[5]),"+f"(d[6]),"+f"(d[7]),"+f"(d[8]),"+f"(d[9]),"+f"(d[10]),"+f"(d[11]),"+f"(d[12]),"+f"(d[13]),"+f"(d[14]),"+f"(d[15]),"+f"(d[16]),"+f"(d[17]),"+f"(d[18]),"+f"(d[19]),"+f"(d[20]),"+f"(d[21]),"+f"(d[22]),"+f"(d[23]),"+f"(d[24]),"+f"(d[25]),"+f"(d[26]),"+f"(d[27]),"+f"(d[28]),"+f"(d[29]),"+f"(d[30]),"+f"(d[31]),"+f"(d[32]),"+f"(d[33]),"+f"(d[34]),"+f"(d[35]) : "r"(a0), "r"(a1), "r"(a2), "r"(a3), "l"(db));
}
template<> __device__ __forceinline__ void wg_rs<64>(float (&d)[64], uint32_t a0, uint32_t a1, uint32_t a2, uint32_t a3, uint64_t db) {
  asm volatile("{.reg .pred p; setp.ne.b32 p, 1, 0; wgmma.mma_async.sync.aligned.m64n64k16.f32.bf16.bf16 {%0,%1,%2,%3,%4,%5,%6,%7,%8,%9,%10,%11,%12,%13,%14,%15,%16,%17,%18,%19,%20,%21,%22,%23,%24,%25,%26,%27,%28,%29,%30,%31}, {%32,%33,%34,%35}, %36, p, 1, 1, 0;}"
    : "+f"(d[0]),"+f"(d[1]),"+f"(d[2]),"+f"(d[3]),"+f"(d[4]),"+f"(d[5]),"+f"(d[6]),"+f"(d[7]),"+f"(d[8]),"+f"(d[9]),"+f"(d[10]),"+f"(d[11]),"+f"(d[12]),"+f"(d[13]),"+f"(d[14]),"+f"(d[15]),"+f"(d[16]),"+f"(d[17]),"+f"(d[18]),"+f"(d[19]),"+f"(d[20]),"+f"(d[21]),"+f"(d[22]),"+f"(d[23]),"+f"(d[24]),"+f"(d[25]),"+f"(d[26]),"+f"(d[27]),"+f"(d[28]),"+f"(d[29]),"+f"(d[30]),"+f"(d[31]) : "r"(a0), "r"(a1), "r"(a2), "r"(a3), "l"(db));
}
__device__ __forceinline__ void wg_rs_first(float (&d)[64], uint32_t a0, uint32_t a1, uint32_t a2, uint32_t a3, uint64_t db) {
  asm volatile("{.reg .pred p; setp.ne.b32 p, 0, 0; wgmma.mma_async.sync.aligned.m64n128k16.f32.bf16.bf16 {%0,%1,%2,%3,%4,%5,%6,%7,%8,%9,%10,%11,%12,%13,%14,%15,%16,%17,%18,%19,%20,%21,%22,%23,%24,%25,%26,%27,%28,%29,%30,%31,%32,%33,%34,%35,%36,%37,%38,%39,%40,%41,%42,%43,%44,%45,%46,%47,%48,%49,%50,%51,%52,%53,%54,%55,%56,%57,%58,%59,%60,%61,%62,%63}, {%64,%65,%66,%67}, %68, p, 1, 1, 0;}"
    : "=f"(d[0]),"=f"(d[1]),"=f"(d[2]),"=f"(d[3]),"=f"(d[4]),"=f"(d[5]),"=f"(d[6]),"=f"(d[7]),"=f"(d[8]),"=f"(d[9]),"=f"(d[10]),"=f"(d[11]),"=f"(d[12]),"=f"(d[13]),"=f"(d[14]),"=f"(d[15]),"=f"(d[16]),"=f"(d[17]),"=f"(d[18]),"=f"(d[19]),"=f"(d[20]),"=f"(d[21]),"=f"(d[22]),"=f"(d[23]),"=f"(d[24]),"=f"(d[25]),"=f"(d[26]),"=f"(d[27]),"=f"(d[28]),"=f"(d[29]),"=f"(d[30]),"=f"(d[31]),"=f"(d[32]),"=f"(d[33]),"=f"(d[34]),"=f"(d[35]),"=f"(d[36]),"=f"(d[37]),"=f"(d[38]),"=f"(d[39]),"=f"(d[40]),"=f"(d[41]),"=f"(d[42]),"=f"(d[43]),"=f"(d[44]),"=f"(d[45]),"=f"(d[46]),"=f"(d[47]),"=f"(d[48]),"=f"(d[49]),"=f"(d[50]),"=f"(d[51]),"=f"(d[52]),"=f"(d[53]),"=f"(d[54]),"=f"(d[55]),"=f"(d[56]),"=f"(d[57]),"=f"(d[58]),"=f"(d[59]),"=f"(d[60]),"=f"(d[61]),"=f"(d[62]),"=f"(d[63]) : "r"(a0), "r"(a1), "r"(a2), "r"(a3), "l"(db));
}
__device__ __forceinline__ void wg_kk176(float (&d)[88], uint64_t da, uint64_t db, int sc) {
  asm volatile("{.reg .pred p; setp.ne.b32 p, %90, 0; wgmma.mma_async.sync.aligned.m64n176k16.f32.bf16.bf16 {%0,%1,%2,%3,%4,%5,%6,%7,%8,%9,%10,%11,%12,%13,%14,%15,%16,%17,%18,%19,%20,%21,%22,%23,%24,%25,%26,%27,%28,%29,%30,%31,%32,%33,%34,%35,%36,%37,%38,%39,%40,%41,%42,%43,%44,%45,%46,%47,%48,%49,%50,%51,%52,%53,%54,%55,%56,%57,%58,%59,%60,%61,%62,%63,%64,%65,%66,%67,%68,%69,%70,%71,%72,%73,%74,%75,%76,%77,%78,%79,%80,%81,%82,%83,%84,%85,%86,%87}, %88, %89, p, 1, 1, 0, 0;}"
    : "+f"(d[0]),"+f"(d[1]),"+f"(d[2]),"+f"(d[3]),"+f"(d[4]),"+f"(d[5]),"+f"(d[6]),"+f"(d[7]),"+f"(d[8]),"+f"(d[9]),"+f"(d[10]),"+f"(d[11]),"+f"(d[12]),"+f"(d[13]),"+f"(d[14]),"+f"(d[15]),"+f"(d[16]),"+f"(d[17]),"+f"(d[18]),"+f"(d[19]),"+f"(d[20]),"+f"(d[21]),"+f"(d[22]),"+f"(d[23]),"+f"(d[24]),"+f"(d[25]),"+f"(d[26]),"+f"(d[27]),"+f"(d[28]),"+f"(d[29]),"+f"(d[30]),"+f"(d[31]),"+f"(d[32]),"+f"(d[33]),"+f"(d[34]),"+f"(d[35]),"+f"(d[36]),"+f"(d[37]),"+f"(d[38]),"+f"(d[39]),"+f"(d[40]),"+f"(d[41]),"+f"(d[42]),"+f"(d[43]),"+f"(d[44]),"+f"(d[45]),"+f"(d[46]),"+f"(d[47]),"+f"(d[48]),"+f"(d[49]),"+f"(d[50]),"+f"(d[51]),"+f"(d[52]),"+f"(d[53]),"+f"(d[54]),"+f"(d[55]),"+f"(d[56]),"+f"(d[57]),"+f"(d[58]),"+f"(d[59]),"+f"(d[60]),"+f"(d[61]),"+f"(d[62]),"+f"(d[63]),"+f"(d[64]),"+f"(d[65]),"+f"(d[66]),"+f"(d[67]),"+f"(d[68]),"+f"(d[69]),"+f"(d[70]),"+f"(d[71]),"+f"(d[72]),"+f"(d[73]),"+f"(d[74]),"+f"(d[75]),"+f"(d[76]),"+f"(d[77]),"+f"(d[78]),"+f"(d[79]),"+f"(d[80]),"+f"(d[81]),"+f"(d[82]),"+f"(d[83]),"+f"(d[84]),"+f"(d[85]),"+f"(d[86]),"+f"(d[87]) : "l"(da), "l"(db), "r"(sc));
}
__device__ __forceinline__ void wg_tt128(float (&d)[64], uint64_t da, uint64_t db, int sc) {
  asm volatile("{.reg .pred p; setp.ne.b32 p, %66, 0; wgmma.mma_async.sync.aligned.m64n128k16.f32.bf16.bf16 {%0,%1,%2,%3,%4,%5,%6,%7,%8,%9,%10,%11,%12,%13,%14,%15,%16,%17,%18,%19,%20,%21,%22,%23,%24,%25,%26,%27,%28,%29,%30,%31,%32,%33,%34,%35,%36,%37,%38,%39,%40,%41,%42,%43,%44,%45,%46,%47,%48,%49,%50,%51,%52,%53,%54,%55,%56,%57,%58,%59,%60,%61,%62,%63}, %64, %65, p, 1, 1, 1, 1;}"
    : "+f"(d[0]),"+f"(d[1]),"+f"(d[2]),"+f"(d[3]),"+f"(d[4]),"+f"(d[5]),"+f"(d[6]),"+f"(d[7]),"+f"(d[8]),"+f"(d[9]),"+f"(d[10]),"+f"(d[11]),"+f"(d[12]),"+f"(d[13]),"+f"(d[14]),"+f"(d[15]),"+f"(d[16]),"+f"(d[17]),"+f"(d[18]),"+f"(d[19]),"+f"(d[20]),"+f"(d[21]),"+f"(d[22]),"+f"(d[23]),"+f"(d[24]),"+f"(d[25]),"+f"(d[26]),"+f"(d[27]),"+f"(d[28]),"+f"(d[29]),"+f"(d[30]),"+f"(d[31]),"+f"(d[32]),"+f"(d[33]),"+f"(d[34]),"+f"(d[35]),"+f"(d[36]),"+f"(d[37]),"+f"(d[38]),"+f"(d[39]),"+f"(d[40]),"+f"(d[41]),"+f"(d[42]),"+f"(d[43]),"+f"(d[44]),"+f"(d[45]),"+f"(d[46]),"+f"(d[47]),"+f"(d[48]),"+f"(d[49]),"+f"(d[50]),"+f"(d[51]),"+f"(d[52]),"+f"(d[53]),"+f"(d[54]),"+f"(d[55]),"+f"(d[56]),"+f"(d[57]),"+f"(d[58]),"+f"(d[59]),"+f"(d[60]),"+f"(d[61]),"+f"(d[62]),"+f"(d[63]) : "l"(da), "l"(db), "r"(sc));
}
__device__ __forceinline__ void wg_tt64(float (&d)[64], uint64_t da, uint64_t db, int sc) {
  asm volatile("{.reg .pred p; setp.ne.b32 p, %34, 0; wgmma.mma_async.sync.aligned.m64n64k16.f32.bf16.bf16 {%0,%1,%2,%3,%4,%5,%6,%7,%8,%9,%10,%11,%12,%13,%14,%15,%16,%17,%18,%19,%20,%21,%22,%23,%24,%25,%26,%27,%28,%29,%30,%31}, %32, %33, p, 1, 1, 1, 1;}"
    : "+f"(d[0]),"+f"(d[1]),"+f"(d[2]),"+f"(d[3]),"+f"(d[4]),"+f"(d[5]),"+f"(d[6]),"+f"(d[7]),"+f"(d[8]),"+f"(d[9]),"+f"(d[10]),"+f"(d[11]),"+f"(d[12]),"+f"(d[13]),"+f"(d[14]),"+f"(d[15]),"+f"(d[16]),"+f"(d[17]),"+f"(d[18]),"+f"(d[19]),"+f"(d[20]),"+f"(d[21]),"+f"(d[22]),"+f"(d[23]),"+f"(d[24]),"+f"(d[25]),"+f"(d[26]),"+f"(d[27]),"+f"(d[28]),"+f"(d[29]),"+f"(d[30]),"+f"(d[31]) : "l"(da), "l"(db), "r"(sc));
}
__device__ __forceinline__ void wg_tt32(float (&d)[64], uint64_t da, uint64_t db, int sc) {
  asm volatile("{.reg .pred p; setp.ne.b32 p, %18, 0; wgmma.mma_async.sync.aligned.m64n32k16.f32.bf16.bf16 {%0,%1,%2,%3,%4,%5,%6,%7,%8,%9,%10,%11,%12,%13,%14,%15}, %16, %17, p, 1, 1, 1, 1;}"
    : "+f"(d[0]),"+f"(d[1]),"+f"(d[2]),"+f"(d[3]),"+f"(d[4]),"+f"(d[5]),"+f"(d[6]),"+f"(d[7]),"+f"(d[8]),"+f"(d[9]),"+f"(d[10]),"+f"(d[11]),"+f"(d[12]),"+f"(d[13]),"+f"(d[14]),"+f"(d[15]) : "l"(da), "l"(db), "r"(sc));
}
__device__ __forceinline__ void wg_g1(float (&d)[88], uint64_t da, uint64_t db, int sc) {
  asm volatile("{.reg .pred p; setp.ne.b32 p, %90, 0; wgmma.mma_async.sync.aligned.m64n176k16.f32.bf16.bf16 {%0,%1,%2,%3,%4,%5,%6,%7,%8,%9,%10,%11,%12,%13,%14,%15,%16,%17,%18,%19,%20,%21,%22,%23,%24,%25,%26,%27,%28,%29,%30,%31,%32,%33,%34,%35,%36,%37,%38,%39,%40,%41,%42,%43,%44,%45,%46,%47,%48,%49,%50,%51,%52,%53,%54,%55,%56,%57,%58,%59,%60,%61,%62,%63,%64,%65,%66,%67,%68,%69,%70,%71,%72,%73,%74,%75,%76,%77,%78,%79,%80,%81,%82,%83,%84,%85,%86,%87}, %88, %89, p, 1, 1, 1, 0;}"
    : "+f"(d[0]),"+f"(d[1]),"+f"(d[2]),"+f"(d[3]),"+f"(d[4]),"+f"(d[5]),"+f"(d[6]),"+f"(d[7]),"+f"(d[8]),"+f"(d[9]),"+f"(d[10]),"+f"(d[11]),"+f"(d[12]),"+f"(d[13]),"+f"(d[14]),"+f"(d[15]),"+f"(d[16]),"+f"(d[17]),"+f"(d[18]),"+f"(d[19]),"+f"(d[20]),"+f"(d[21]),"+f"(d[22]),"+f"(d[23]),"+f"(d[24]),"+f"(d[25]),"+f"(d[26]),"+f"(d[27]),"+f"(d[28]),"+f"(d[29]),"+f"(d[30]),"+f"(d[31]),"+f"(d[32]),"+f"(d[33]),"+f"(d[34]),"+f"(d[35]),"+f"(d[36]),"+f"(d[37]),"+f"(d[38]),"+f"(d[39]),"+f"(d[40]),"+f"(d[41]),"+f"(d[42]),"+f"(d[43]),"+f"(d[44]),"+f"(d[45]),"+f"(d[46]),"+f"(d[47]),"+f"(d[48]),"+f"(d[49]),"+f"(d[50]),"+f"(d[51]),"+f"(d[52]),"+f"(d[53]),"+f"(d[54]),"+f"(d[55]),"+f"(d[56]),"+f"(d[57]),"+f"(d[58]),"+f"(d[59]),"+f"(d[60]),"+f"(d[61]),"+f"(d[62]),"+f"(d[63]),"+f"(d[64]),"+f"(d[65]),"+f"(d[66]),"+f"(d[67]),"+f"(d[68]),"+f"(d[69]),"+f"(d[70]),"+f"(d[71]),"+f"(d[72]),"+f"(d[73]),"+f"(d[74]),"+f"(d[75]),"+f"(d[76]),"+f"(d[77]),"+f"(d[78]),"+f"(d[79]),"+f"(d[80]),"+f"(d[81]),"+f"(d[82]),"+f"(d[83]),"+f"(d[84]),"+f"(d[85]),"+f"(d[86]),"+f"(d[87]) : "l"(da), "l"(db), "r"(sc));
}

struct Params { const __nv_bfloat16 *x, *logA, *Aim, *Cr, *Ci, *logdt, *Dskip; uint4 *xnT, *mb; float* hr; uint2* S; unsigned* flags; };
struct Maps { CUtensorMap x[2], xo, out, wg, wu, wd, hst[2], hld, xt; };

__device__ __forceinline__ void conv_channel(uint32_t cb, int w, int lane, uint32_t (&res)[8], uint32_t bar_free) {
    const int q = lane & 3, g = lane >> 2, gam = g >> 2;
    float acc[64];
    uint4 a[4][4];
    const uint32_t t0 = cb + CH_T + (uint32_t)(14 + 4 * w + (g & 3) + 32 * gam - 2 * q) * 80u;
    #pragma unroll
    for (int s4 = 0; s4 < 4; s4++) {
        a[s4][0] = lds128(t0 + s4 * 16);
        a[s4][1] = lds128(t0 + 16 * 80 + s4 * 16);
        a[s4][2] = lds128(t0 - 8 * 80 + s4 * 16);
        a[s4][3] = lds128(t0 + 8 * 80 + s4 * 16);
    }
    const uint32_t l0 = FU(ldsf(t0 + 64)), l1 = FU(ldsf(t0 + 16 * 80 + 64)), l2 = FU(ldsf(t0 - 8 * 80 + 64)), l3 = FU(ldsf(t0 + 8 * 80 + 64));
    const uint64_t dU = mkdesc(cb + CH_U, UPLANE, 128, 0);
    WG_FENCE();
#define CT(N, s, c) wg_rs<N>(acc, a[(s) >> 2][0].c, a[(s) >> 2][1].c, a[(s) >> 2][2].c, a[(s) >> 2][3].c, dU + 4 * (s))
    wg_rs_first(acc, a[0][0].x, a[0][1].x, a[0][2].x, a[0][3].x, dU);
    CT(128, 1, y); CT(120, 2, z); CT(120, 3, w);
    CT(112, 4, x); CT(112, 5, y); CT(104, 6, z); CT(104, 7, w);
    CT(96, 8, x);  CT(96, 9, y);  CT(88, 10, z); CT(88, 11, w);
    CT(80, 12, x); CT(80, 13, y); CT(72, 14, z); CT(72, 15, w);
#undef CT
    wg_rs<64>(acc, l0, l1, l2, l3, dU + 64);
    wg_tt64(acc, mkdesc(cb + CH_A3, 128, 512, 0), mkdesc(cb + CH_B3, 128, 256, 0), 1);
    wg_tt32(acc, mkdesc(cb + CH_A3 + 256, 128, 512, 0), mkdesc(cb + CH_B3 + 1024, 128, 256, 0), 1);
    WG_COMMIT();
    WG_WAIT(0);
    fence_acc(acc);
    if (bar_free && lane == 0) mbar_arrive(bar_free);
    const int src1 = (lane & ~3) | ((q + 1) & 3);
    float E[16][2];
    #pragma unroll
    for (int j = 0; j < 16; j++) {
        const float nxt = (j < 15) ? acc[4 * (j + 1) + 2] : 0.f;
        const float sup = (q == 0) ? nxt : acc[4 * j + 2];
        const float v = __shfl_sync(0xffffffffu, sup, src1);
        E[j][0] = acc[4 * j] + acc[4 * j + 3];
        E[j][1] = acc[4 * j + 1] + v;
    }
    const int src2 = gam ? ((lane & 12) | ((q + 3) & 3)) : (16 | (lane & 12) | ((q + 1) & 3));
    const bool c1 = gam && q != 0, c2 = gam && q == 0;
    #pragma unroll
    for (int a2 = 0; a2 < 8; a2++) {
        float y[2];
        #pragma unroll
        for (int e = 0; e < 2; e++) {
            const float sup = c1 ? E[2 * a2][e] : E[2 * a2 + 1][e];
            const float nxt = (a2 < 7) ? E[2 * a2 + 2][e] : 0.f;
            const float keep = c2 ? nxt : (c1 ? E[2 * a2 + 1][e] : E[2 * a2][e]);
            y[e] = keep + __shfl_sync(0xffffffffu, sup, src2);
        }
        res[a2] = pack2(y[1], y[0]);
    }
}

__device__ __forceinline__ void consumer(uint32_t sb, int warp, const Params& P, const Maps& M) {
    const int V = warp >> 2, w = warp & 3, lane = threadIdx.x & 31, q = lane & 3, g = lane >> 2;
    const int c = blockIdx.x;
    const uint32_t bars = sb + OFF_BAR, xb = sb + OFF_X + V * 2 * XBUF;
    {
        float ag[88], au[88];
        define_acc(ag); define_acc(au);
        if (V == 0) {
            sts128(xb + (w >> 1) * XBUF + 168 * 128 + (threadIdx.x & 63) * 16, 0x3f803f80u, 0x3f803f80u, 0x3f803f80u, 0x3f803f80u);
            fence_async_smem();
            bar_sync(1);
        } else mbar_wait(bars + 8 * B_GO, 0);
        #pragma unroll 1
        for (int st = 0; st < 8; st++) {
            if (st + V == HOLD0 || st + V == HOLD1) mbar_wait(bars + 8 * (B_K + (st + V == HOLD1)), 0);
            mbar_wait(bars + 8 * (B_FULLW + (st & 3)), st >> 2);
            mbar_wait(bars + 8 * (B_FULLX + 2 * V + (st & 1)), (st >> 1) & 1);
            STAMP(40 + 8 * V + st);
            const uint64_t dG = mkdesc(sb + OFF_W + (st & 3) * 16384, 0, 1024, 1);
            const uint64_t dX = mkdesc(xb + (st & 1) * XBUF, 16, 1024, 1);
            WG_FENCE();
            #pragma unroll
            for (int k = 0; k < 4; k++) {
                wg_g1(ag, dG + k * 128, dX + k * 2, k ? 1 : st);
                wg_g1(au, dG + 512 + k * 128, dX + k * 2, k ? 1 : st);
            }
            WG_COMMIT();
            WG_WAIT(1);
            if (lane == 0 && st > 0) {
                mbar_arrive(bars + 8 * (B_EMPTYW + ((st - 1) & 3)));
                mbar_arrive(bars + 8 * (B_EMPTYX + 2 * V + ((st - 1) & 1)));
                if (warp < 4 && st == 1) mbar_arrive(bars + 8 * B_GO);
            }
        }
        WG_WAIT(0);
        fence_acc(ag); fence_acc(au);
        if (lane == 0) { mbar_arrive(bars + 8 * (B_EMPTYW + 3)); mbar_arrive(bars + 8 * (B_EMPTYX + 2 * V + 1)); }
        STAMP(8 * V + 1);
        {
            if (V == 0) {
                const float cv = (q & 2) ? ((q & 1) ? au[86] : au[84]) : ((q & 1) ? ag[86] : ag[84]), hi = bf_round(cv);
                sts128(sb + OFF_CSUM + (16 * w + g + 8 * (q & 1) + 32 * (q & 2)) * 16, pack2(hi, cv - hi), 0, 0, 0);
                fence_async_smem();
                mbar_arrive(bars + 8 * B_CS);
            }
            mbar_wait(bars + 8 * B_CS, 0);
            mbar_wait(bars + 8 * B_STATS, 0);
            const uint64_t dM = mkdesc(sb + OFF_MB + V * 168 * 16, 0, 128, 0), dC = mkdesc(sb + OFF_CSUM, 0, 128, 0);
            WG_FENCE();
            wg_kk176(ag, dC, dM, 1);
            wg_kk176(au, dC + 64, dM, 1);
            WG_COMMIT();
            mbar_wait(bars + 8 * (B_EMPTYX + 2 * V), 1);
            WG_WAIT(0);
            fence_acc(ag); fence_acc(au);
            STAMP(13 + V);
        }
        const uint32_t hs = xb + (2 * w + ((lane >> 3) & 1)) * (2688 + 128 * V) + (lane >> 4) * 128 + (lane & 7) * 16;
        const uint32_t hr = sb + OFF_HR + (168 * V + 2 * q) * 4;
        #pragma unroll
        for (int j = 0; j < 22; j += 2) {
            uint32_t o[4];
            #pragma unroll
            for (int jj = 0; jj < 2; jj++) {
                const uint2 rv = lds64(hr + (j + jj) * 32);
                float hv[4];
                #pragma unroll
                for (int i = 0; i < 4; i++) {
                    const float gh = ag[4 * (j + jj) + i] * UF((i & 1) ? rv.y : rv.x);
                    const float p = gh * au[4 * (j + jj) + i];
                    hv[i] = fmaf(p, tanh_fast(gh), p);
                }
                o[2 * jj] = pack2(hv[0], hv[1]); o[2 * jj + 1] = pack2(hv[2], hv[3]);
            }
            uint32_t ad = hs + j * 128;
            if (j == 20 && V == 0 && lane >= 16) ad = xb + 21504 + (lane & 7) * 16;
            stsm4(ad, o[0], o[1], o[2], o[3]);
        }
        fence_async_smem();
        mbar_arrive(bars + 8 * (B_EPI + V));
        STAMP(8 * V + 2);
    }
    if (c >= 128) return;
    {
        mbar_wait(bars + 8 * B_CONV, 0);
        uint32_t r0[8], r1[8];
        #pragma unroll
        for (int i = 0; i < 8; i++) asm volatile("" : "=r"(r1[i]));
        #pragma unroll 1
        for (int e = 0; e < 2; e++) {
            #pragma unroll
            for (int i = 0; i < 8; i++) r0[i] = r1[i];
            conv_channel(sb + OFF_CONV + (2 * V + e) * CH_STRIDE, w, lane, r1, (V + e == 0) ? bars + 8 * B_CH0 : 0);
            if (e == 0) STAMP(8 * V + 3);
        }
        const int gam = g >> 2, qq = gam ? ((q + 3) & 3) : q;
        const uint32_t sp = sb + OFF_CONV + (2 * V + 1) * CH_STRIDE + ((63 - 4 * gam - qq) * 16 + 4 * w + (g & 3)) * 8;
        bar_sync(3 + V);
        #pragma unroll
        for (int a2 = 0; a2 < 8; a2++) sts64(sp - a2 * 1024, r0[a2], r1[a2]);
        fence_async_smem();
        mbar_arrive(bars + 8 * (B_SIG + V));
        STAMP(8 * V + 4);
    }
    if (V == 1) return;
    {
        const int tau = c >> 2, dg = c & 3;
        const uint32_t row = 8 * (w & 1) + 32 * (w >> 1);
        float acc[64];
        define_acc(acc);
        uint2 sv[16];
        #pragma unroll
        for (int i = 0; i < 16; i++) asm volatile("" : "=r"(sv[i].x), "=r"(sv[i].y));
        const float rr0 = __ldcg(P.hr + 64 * tau + row + g), rr1 = __ldcg(P.hr + 64 * tau + row + g + 16);
        int sd = 0; uint32_t pd = 0;
        mbar_wait(bars + 8 * B_FULLD, 0);
        STAMP(5);
        uint64_t dB = mkdesc(sb + wd_slot(0), 8192, 1024, 1), dA = mkdesc(sb + h_slot(0), 1024, 128, 0);
        #pragma unroll 1
        for (int st = 0; st < 21; st++) {
            WG_FENCE();
            wg_tt128(acc, dA, dB, st);
            wg_tt128(acc, dA + 128, dB + 128, 1);
            wg_tt128(acc, dA + 256, dB + 256, 1);
            wg_tt128(acc, dA + 384, dB + 384, 1);
            WG_COMMIT();
            const uint32_t rel = bars + 8 * (B_EMPTYD + (sd ? sd - 1 : 5));
            if (++sd == 6) { sd = 0; pd ^= 1; }
            mbar_wait(bars + 8 * (B_FULLD + sd), pd);
            dB = mkdesc(sb + wd_slot(sd), 8192, 1024, 1); dA = mkdesc(sb + h_slot(sd), 1024, 128, 0);
            if (st == 14) {
                mbar_wait(bars + 8 * B_S, 0);
                const uint2* sp = P.S + (dg * 64 + q) * 1024 + (2 * tau) * 16 + (row >> 1) + 4 * (w & 1) + g;
                #pragma unroll
                for (int j = 0; j < 16; j++)
                    asm volatile("ld.global.cg.v2.b32 {%0,%1}, [%2];" : "=r"(sv[j].x), "=r"(sv[j].y) : "l"(sp + j * 4096));
            }
            WG_WAIT(1);
            if (lane == 0 && st > 0) mbar_arrive(rel);
        }
        WG_FENCE();
        wg_tt128(acc, dA, dB, 1);
        wg_tt128(acc, dA + 128, dB + 128, 1);
        WG_COMMIT();
        WG_WAIT(0);
        fence_acc(acc);
        STAMP(6);
        mbar_wait(bars + 8 * B_XO, 0);
        const uint32_t xo = sb + OFF_CONV + (row + (lane & 7) + 16 * ((lane >> 3) & 1)) * 128;
        #pragma unroll
        for (int j = 0; j < 16; j += 2) {
            const uint32_t ad = xo + (j >> 3) * 8192 + ((((j & 7) + (lane >> 4)) ^ (lane & 7)) << 4);
            uint32_t xr[4];
            asm volatile("ldmatrix.sync.aligned.m8n8.x4.shared.b16 {%0,%1,%2,%3}, [%4];" : "=r"(xr[0]), "=r"(xr[1]), "=r"(xr[2]), "=r"(xr[3]) : "r"(ad));
            #pragma unroll
            for (int i = 0; i < 4; i++) {
                const int jj = j + (i >> 1), hh = i & 1;
                const float f0 = acc[4 * jj + 2 * hh] * (hh ? rr1 : rr0), f1 = acc[4 * jj + 2 * hh + 1] * (hh ? rr1 : rr0);
                const uint32_t G = pack2(fmaf(f0, tanh_fast(f0), f0), fmaf(f1, tanh_fast(f1), f1));
                const uint32_t s2 = __byte_perm(sv[jj].x, sv[jj].y, hh ? 0x7632 : 0x5410);
                asm("fma.rn.bf16x2 %0, %1, %2, %0;" : "+r"(xr[i]) : "r"(s2), "r"(G));
            }
            stsm4(ad, xr[0], xr[1], xr[2], xr[3]);
        }
        fence_async_smem();
        bar_sync(1);
        if (w == 0 && elect_one()) {
            #pragma unroll
            for (int i = 0; i < 2; i++)
                asm volatile("cp.async.bulk.tensor.2d.global.shared::cta.bulk_group [%0, {%2, %3}], [%1];"
                    :: "l"(&M.out), "r"(sb + OFF_CONV + i * 8192), "r"(dg * 128 + 64 * i), "r"(tau * 64) : "memory");
            asm volatile("cp.async.bulk.commit_group; cp.async.bulk.wait_group.read 0;" ::: "memory");
        }
        STAMP(7); GSTAMP(23);
    }
}

__device__ __forceinline__ float2 cexp_p(float re2, float im, float p) {
    float sn, cs;
    const float mag = ex2(re2 * p), th = im * p;
    asm("sin.approx.ftz.f32 %0, %1;" : "=f"(sn) : "f"(th));
    asm("cos.approx.ftz.f32 %0, %1;" : "=f"(cs) : "f"(th));
    return make_float2(mag * cs, mag * sn);
}
__device__ __forceinline__ void ldsm4(uint32_t (&r)[4], uint32_t a) {
    asm volatile("ldmatrix.sync.aligned.m8n8.x4.shared.b16 {%0,%1,%2,%3}, [%4];" : "=r"(r[0]), "=r"(r[1]), "=r"(r[2]), "=r"(r[3]) : "r"(a) : "memory");
}
__device__ __forceinline__ float2 cmul(float2 a, float2 b) { return make_float2(fmaf(a.x, b.x, -a.y * b.y), fmaf(a.x, b.y, a.y * b.x)); }
__device__ __forceinline__ float2 csqr(float2 a) { const float t = a.x * a.y; return make_float2(fmaf(a.x, a.x, -a.y * a.y), t + t); }
__device__ __forceinline__ void mma16816(float (&d)[4], const uint32_t (&a)[4], uint32_t b0, uint32_t b1) {
    asm volatile("mma.sync.aligned.m16n8k16.row.col.f32.bf16.bf16.f32 {%0,%1,%2,%3}, {%4,%5,%6,%7}, {%8,%9}, {%0,%1,%2,%3};"
        : "+f"(d[0]), "+f"(d[1]), "+f"(d[2]), "+f"(d[3]) : "r"(a[0]), "r"(a[1]), "r"(a[2]), "r"(a[3]), "r"(b0), "r"(b1));
}

__device__ __forceinline__ void aux_role(uint32_t sb, int w, const Params& P) {
    const int tid = threadIdx.x & 127, lane = tid & 31, q = lane & 3, g = lane >> 2;
    const int c = blockIdx.x;
    const uint32_t bars = sb + OFF_BAR;
    if (c < 128) {
        const uint32_t cb = sb + OFF_CONV + w * CH_STRIDE;
        const uint32_t sF = cb + CH_A3;
        const int tokb = 32 * (c >> 1) + 8 * (c & 1) + 16;
        if (elect_one()) {
            mbar_expect(bars + 8 * B_LNX, 4096);
            #pragma unroll
            for (int i = 0; i < 4; i++)
                bulk_load(cb + CH_LN + (w & 1) * 64 + i * 1040, P.x + (tokb + w + 4 * (i & 1) - 8 * (i & 2)) * DM, 1024, bars + 8 * B_LNX);
        }
        const int d = 4 * c + w;
        const uint2 la2 = *(const uint2*)(P.logA + d * 128 + 4 * lane), ai2 = *(const uint2*)(P.Aim + d * 128 + 4 * lane);
        const uint2 cr2 = *(const uint2*)(P.Cr + d * 128 + 4 * lane), ci2 = *(const uint2*)(P.Ci + d * 128 + 4 * lane);
        const float ldt = __bfloat162float(P.logdt[d]), dsk = __bfloat162float(P.Dskip[d]);
        mbar_wait(bars + 8 * B_LNX, 0);
        STAMP(34);
        {
            const int r = w + 4 * (lane >> 3);
            const uint32_t r0 = cb + CH_LN + (w & 1) * 64 + (lane >> 3) * 1040, ra = r0 + (lane & 7) * 16;
            const float pv = bf_lo(FU(ldsf(r0)));
            float s0 = 0.f, s1 = 0.f, a0 = 0.f, a1 = 0.f;
            uint4 nx = lds128(ra);
            #pragma unroll 1
            for (int k = 128; k <= 1024; k += 128) {
                const uint32_t v[4] = {nx.x, nx.y, nx.z, nx.w};
                nx = lds128(ra + (k & 1023));
                #pragma unroll
                for (int i = 0; i < 4; i++) { const float t0 = bf_lo(v[i]) - pv, t1 = bf_hi(v[i]) - pv; s0 += t0; s1 += t1; a0 = fmaf(t0, t0, a0); a1 = fmaf(t1, t1, a1); }
            }
            s0 += s1; a0 += a1;
            #pragma unroll
            for (int o = 4; o; o >>= 1) { s0 += __shfl_xor_sync(0xffffffffu, s0, o); a0 += __shfl_xor_sync(0xffffffffu, a0, o); }
            s0 *= 1.f / DM;
            const float m = pv + s0, var = fmaxf(fmaf(-s0, s0, a0 * (1.f / DM)), 0.f);
            float sd, ri;
            asm("sqrt.approx.ftz.f32 %0, %1;" : "=f"(sd) : "f"(bf_round(bf_round(var) + 1e-5f)));
            asm("rcp.approx.ftz.f32 %0, %1;" : "=f"(ri) : "f"(bf_round(sd)));
            const uint32_t m2 = pack2(m, m);
            if ((lane & 7) == 0) {
                const float mh = -0.5f * bf_hi(m2);
                sts128(sb + OFF_CSUM + r * 16, pack2(mh, mh), 0, 0, 0); stsf(sb + OFF_CSUM + 256 + r * 4, 0.5f * ri);
            }
            #pragma unroll 1
            for (int k = 128; k <= 1024; k += 128) {
                uint32_t v[4] = {nx.x, nx.y, nx.z, nx.w};
                nx = lds128(ra + (k & 1023));
                #pragma unroll
                for (int i = 0; i < 4; i++) {
                    uint32_t dv; asm("sub.rn.bf16x2 %0, %1, %2;" : "=r"(dv) : "r"(v[i]), "r"(m2));
                    v[i] = pack2(bf_lo(dv) * ri, bf_hi(dv) * ri);
                }
                sts128(ra + k - 128, v[0], v[1], v[2], v[3]);
            }
        }
        STAMP(62);
        bar_sync(2);
        {
            const int r = 4 * ((lane & 7) >> 1) + (lane & 1) + 2 * ((lane >> 3) & 1);
            const uint32_t ad = sb + OFF_CONV + (r & 3) * CH_STRIDE + CH_LN + (r & 1) * 64 + (r >> 2) * 1040 + (16 * w + (lane >> 4)) * 16;
            #pragma unroll
            for (int i = 0; i < 8; i++) {
                uint32_t r0, r1, r2, r3;
                asm volatile("ldmatrix.sync.aligned.m8n8.x4.trans.shared.b16 {%0,%1,%2,%3}, [%4];" : "=r"(r0), "=r"(r1), "=r"(r2), "=r"(r3) : "r"(ad + 32 * i));
                sts64(cb + CH_LNT + lane * 8 + i * 512, r0, r1); sts64(cb + CH_LNT + lane * 8 + i * 512 + 256, r2, r3);
            }
        }
        fence_async_smem();
        mbar_arrive(bars + 8 * B_LN);
        STAMP(16);
        float dacc[2][3][4];
        #pragma unroll
        for (int i = 0; i < 24; i++) (&dacc[0][0][0])[i] = 0.f;
        const float dt = bf_round(ex2(ldt * 1.4426950408889634f));
        const uint32_t lda = cb + ((lane & 7) + 8 * ((lane >> 3) & 1)) * 144 + (lane >> 4) * 16;
        const uint32_t ldb = cb + (32 + (lane & 7)) * 144 + (lane >> 3) * 16;
        uint64_t la = *(const uint64_t*)&la2, ai = *(const uint64_t*)&ai2, cr = *(const uint64_t*)&cr2, ci = *(const uint64_t*)&ci2;
        #pragma unroll 1
        for (int ck = 0; ck < 4; ck++, la >>= 16, ai >>= 16, cr >>= 16, ci >>= 16) {
            const uint32_t fa = cb + lane * 4 + (ck & 1) * 8064;
            if (ck == 1) mbar_wait(bars + 8 * B_LNS, 0);
            const float re2 = bf_round(ex2(bf_lo((uint32_t)la) * 1.4426950408889634f)) * dt * -1.4426950408889634f, im = bf_lo((uint32_t)ai) * dt;
            const float2 C = make_float2(bf_lo((uint32_t)cr) * (dt + dt), bf_lo((uint32_t)ci) * -(dt + dt));
            const float2 z8 = cexp_p(re2, im, 8.f), y1 = cexp_p(re2, -im, 1.f);
            float2 b0 = make_float2(1.f, 0.f), b1 = cexp_p(re2, im, 64.f), b2 = csqr(b1), b3 = cmul(b2, b1), l0 = C;
            const uint32_t fm = cb + (ck & 1) * 8064 + (lane >> 3) * 144 + (lane & 7) * 16;
#define PK(v) pack2((v).x, (v).y)
            #pragma unroll 1
            for (uint32_t ro = 0; ro < 8 * 144; ro += 144) {
                stsm4(fm + (lane >> 3) * 7 * 144 + ro, PK(b0), PK(b1), PK(b2), PK(b3));
                stsf(fa + 32 * 144 + ro, UF(PK(l0)));
                b0 = cmul(b0, z8); b1 = cmul(b1, z8); b2 = cmul(b2, z8); b3 = cmul(b3, z8); l0 = cmul(l0, y1);
            }
            if (ck < 2) STAMP(56 + 3 * ck);
            const float2 y256 = cexp_p(re2, -im, 256.f), y2 = csqr(y1), y4 = csqr(y2), y8 = make_float2(z8.x, -z8.y);
            const float2 t0 = cmul(C, y256), t1 = cmul(t0, y256), t2 = cmul(t1, y256), t3_ = cmul(t2, y256);
            const float2 u1 = cmul(t0, y2), u2 = cmul(u1, y2), u3 = cmul(u2, y2);
            stsm4(fm + 40 * 144, PK(t0), PK(u1), PK(u2), PK(u3));
            stsm4(fm + 44 * 144, PK(t1), PK(cmul(t1, y4)), PK(t2), PK(cmul(t2, y4)));
            const float2 v0 = cmul(t3_, y8), v1 = cmul(v0, y256), v2 = cmul(v1, y256), v3 = cmul(v2, y256);
            stsm4(fm + 48 * 144, PK(v0), PK(v1), PK(v2), PK(v3));
            stsf(fa + 52 * 144, UF(PK(t3_)));
#undef PK
            if (ck < 2) STAMP(57 + 3 * ck);
            if (ck & 1) {
                __syncwarp();
                #pragma unroll
                for (int k2 = 0; k2 < 4; k2++) {
                    const uint32_t ko = (k2 >> 1) * 8064 + (k2 & 1) * 64;
                    uint32_t b[3][4];
                    #pragma unroll
                    for (int t3 = 0; t3 < 3; t3++) ldsm4(b[t3], ldb + t3 * 8 * 144 + ko);
                    #pragma unroll
                    for (int k = 0; k < 2; k++)
                        #pragma unroll
                        for (int mu = 0; mu < 2; mu++) {
                            uint32_t a[4];
                            ldsm4(a, lda + mu * 16 * 144 + ko + k * 32);
                            #pragma unroll
                            for (int t3 = 0; t3 < 3; t3++) mma16816(dacc[mu][t3], a, b[t3][2 * k], b[t3][2 * k + 1]);
                        }
                }
                __syncwarp();
                if (lane == 0) mbar_arrive(bars + 8 * (B_K + (ck >> 1)));
                STAMP(58 + 3 * (ck >> 1));
            }
        }
        STAMP(18);
        const uint32_t sG = cb + CH_G;
        if (lane < 16) sts128(((lane & 8) ? cb + CH_U + 2048 + (lane & 4) * (UPLANE / 4) : sG + 128 + (lane & 4) * 48) + (lane & 3) * 16, 0, 0, 0, 0);
        {
            const uint32_t f0 = sF + (8 * g + 2 * q) * 4, f1 = sF + ((q < 2) ? 256 + 4 * g + 2 * q : 256 + 2 * g + 64 * q) * 4, st1 = (q < 2) ? 128 : 64;
            const uint32_t ga = sG + ((g & 1) ? 0 : 192) + (63 - (g >> 1) - 32 * q) * 2;
            #pragma unroll
            for (int i = 0; i < 4; i++) {
                const int mu = i >> 1, hh = i & 1;
                sts64(f0 + i * 256, FU(dacc[mu][0][2 * hh]), FU(dacc[mu][0][2 * hh + 1]));
                sts64(f1 + i * st1, FU(dacc[mu][1][2 * hh]), FU(dacc[mu][1][2 * hh + 1]));
                const uint32_t pk = pack2(dacc[mu][2][2 * hh], dacc[mu][2][2 * hh + 1]);
                if (q < 2) { sts16(ga - 8 * i, pk & 0xffff); sts16(ga - 8 * i - 32, pk >> 16); }
            }
            if (lane == 2) stsf(sF + 2048, dacc[0][2][0]);
        }
        __syncwarp();
        #pragma unroll 1
        for (int pass = 0; pass < 3; pass++) {
            const int rw = lane - 1 + 31 * pass;
            const int u = min(rw, 77) - 14;
            const uint32_t f0 = sF + u * 4, f1 = sF + (128 + ((u + ((u >> 1) & 1)) >> 1)) * 4, f2 = sF + (256 + ((u + 1 + ((u >> 2) & 1)) >> 2)) * 4;
            float kv[17];
            kv[0] = ldsf(u < 0 ? sF : f0); if (u < 0) kv[0] = 0.f; if (u == 0) kv[0] += dsk;
            #pragma unroll
            for (int s = 1; s < 4; s++) kv[s] = ldsf(f0 + s * 256);
            kv[4] = ldsf(u < 0 ? f0 + 1024 : f1 + 512);
            #pragma unroll
            for (int s = 5; s < 8; s++) kv[s] = ldsf(f1 + s * 128);
            kv[8] = ldsf(u < 0 ? f1 + 1024 : f2 + 512);
            #pragma unroll
            for (int s = 9; s < 16; s++) kv[s] = ldsf(f2 + s * 64);
            kv[16] = ldsf(u < 0 ? f2 + 1024 : sF + 2048); if (u > 4) kv[16] = 0.f;
            uint32_t o[17];
            #pragma unroll
            for (int s = 0; s < 17; s++) o[s] = pack2(kv[s], __shfl_up_sync(0xffffffffu, kv[s], 1));
            if (lane > 0 && rw < 78) {
                const uint32_t ta = cb + CH_T + rw * 80;
                #pragma unroll
                for (int s4 = 0; s4 < 4; s4++) sts128(ta + s4 * 16, o[4 * s4], o[4 * s4 + 1], o[4 * s4 + 2], o[4 * s4 + 3]);
                stsf(ta + 64, UF(o[16]));
            }
        }
        #pragma unroll 1
        for (int un = lane; un < 128; un += 32) {
            const uint32_t ga = sG + ((un >> 3) & 1) * 192 + (un >> 4) * 16 + (un & 7) * 8;
            const uint2 x0 = lds64(ga), x1 = lds64(ga + 8);
            sts128(cb + CH_B3 + un * 16, x0.x, x0.y, x1.x, x1.y);
        }
    } else {
        mbar_arrive(bars + 8 * B_LN);
        if (lane == 0) { mbar_arrive(bars + 8 * B_K); mbar_arrive(bars + 8 * (B_K + 1)); }
        return;
    }
    STAMP(19);
    bar_sync(2);
    mbar_wait(bars + 8 * B_U, 0);
    {
        const int kap = (lane >> 4) * 8 + ((lane >> 1) & 7), gam = lane & 1, hh = w >> 1, wp = w & 1;
        uint32_t ua = sb + OFF_CONV + CH_U + wp * UPLANE + (127 - 4 * kap - 2 * gam - hh) * 16;
        uint32_t ub = sb + OFF_CONV + CH_U + (wp ^ 1) * UPLANE + (128 - wp - 4 * kap - 2 * gam - hh) * 16;
        uint32_t ad = sb + OFF_CONV + CH_A3 + (4 * wp + hh) * 512 + (kap >> 3) * 256 + (kap & 7) * 16 + gam * 8;
        #pragma unroll 1
        for (int ch = 0; ch < 4; ch++, ua += CH_STRIDE, ub += CH_STRIDE, ad += CH_STRIDE) {
            float p[24];
            const uint2 r0 = lds64(ub + 24), r3 = lds64(ua);
            uint32_t r[8];
            *(uint4*)&r[0] = lds128(ua + 16); *(uint4*)&r[4] = lds128(ub);
            p[0] = 0.f;
            p[1] = bf_lo(r0.x); p[2] = p[1] + bf_hi(r0.x); p[3] = p[2] + bf_lo(r0.y); p[4] = p[3] + bf_hi(r0.y);
            #pragma unroll
            for (int i = 0; i < 8; i++) { p[5 + 2 * i] = p[4 + 2 * i] + bf_lo(r[i]); p[6 + 2 * i] = p[5 + 2 * i] + bf_hi(r[i]); }
            p[21] = p[20] + bf_lo(r3.x); p[22] = p[21] + bf_hi(r3.x); p[23] = p[22] + bf_lo(r3.y);
            #pragma unroll
            for (int i = 0; i < 8; i += 4) {
                sts64(ad + i * 256, pack2(p[i + 9] - p[i], p[i + 10] - p[i + 1]), pack2(p[i + 11] - p[i + 2], p[i + 12] - p[i + 3]));
                sts64(ad + i * 256 + 128, pack2(p[i + 16] - p[i + 9], p[i + 17] - p[i + 10]), pack2(p[i + 18] - p[i + 11], p[i + 19] - p[i + 12]));
            }
        }
    }
    fence_async_smem();
    mbar_arrive(bars + 8 * B_CONV);
    STAMP(21);
}

__global__ void __launch_bounds__(512, 1)
fused_kernel(const __grid_constant__ Params P, const __grid_constant__ Maps M) {
    extern __shared__ __align__(1024) uint8_t smem_raw[];
    const uint32_t sb = smem_u32(smem_raw);
    const uint32_t bars = sb + OFF_BAR;
    const int warp = __shfl_sync(0xffffffffu, threadIdx.x >> 5, 0);
    const int c = blockIdx.x, tg = c / 22, fb = c - 22 * tg;
    if (elect_one()) {
        if (warp == 0) { STAMP(24); GSTAMP(22); }
        asm volatile("" :: "l"(((const uint64_t*)&P)[warp < 12 ? warp : 0]));
        if (warp < 11) asm volatile("prefetch.tensormap [%0];" :: "l"(&M.x[0] + warp) : "memory");
        #pragma unroll
        for (int k = 0; k < 3; k++) {
            const int i = 16 * k + ((warp + 4) & 15);
            const uint32_t cnt = (i >= B_CONV && i != B_LNS) ? 128 : ((0xf0ull >> i) & 1) ? 8 : ((0x3f0000ull >> i) & 1) ? 2 : ((0xf80fc0f000ull >> i) & 1) ? 4 : 1;
            asm volatile("mbarrier.init.shared::cta.b64 [%0], %1;" :: "r"(bars + 8 * i), "r"(cnt) : "memory");
        }
        asm volatile("fence.mbarrier_init.release.cluster; fence.proxy.async.shared::cta;" ::: "memory");
        if (warp == 12) {
            mbar_expect(bars + 8 * B_FULLW, 16384);
            tma2d(sb + OFF_W, &M.wg, 64 * fb, 0, bars + 8 * B_FULLW);
            tma2d(sb + OFF_W + 8192, &M.wu, 64 * fb, 0, bars + 8 * B_FULLW);
            STAMP(31);
        } else if (warp == 4) {
            mbar_expect(bars + 8 * B_FULLX, 168 * 128);
            tma2d(sb + OFF_X, &M.x[0], 0, TOKG * tg, bars + 8 * B_FULLX);
        }
        if (sb & 1023) __trap();
    }
    __syncthreads();
    if (warp < 8) {
        asm volatile("setmaxnreg.inc.sync.aligned.u32 208;");
        consumer(sb, warp, P, M);
    } else if (warp < 12) {
        asm volatile("setmaxnreg.dec.sync.aligned.u32 72;");
        STAMP(32);
        aux_role(sb, warp - 8, P);
    } else {
        asm volatile("setmaxnreg.dec.sync.aligned.u32 24;");
        const int tau = c >> 2, dg = c & 3;
        if (elect_one()) {
            if (warp == 12) {
                #pragma unroll 1
                for (int st = 1; st < 8; st++) {
                    const uint32_t s = st & 3, fb_ = bars + 8 * (B_FULLW + s);
                    if (st == 2) mbar_wait(bars + 8 * B_FULLW, 0);
                    mbar_wait(bars + 8 * (B_EMPTYW + s), (st >> 2) ^ 1);
                    mbar_expect(fb_, 16384);
                    tma2d(sb + OFF_W + s * 16384, &M.wg, 64 * fb, 64 * st, fb_);
                    tma2d(sb + OFF_W + s * 16384 + 8192, &M.wu, 64 * fb, 64 * st, fb_);
                }
                if (c < 128) {
                    int sd = 0; uint32_t pe = 1;
                    #pragma unroll 1
                    for (int st = 0; st < 22; st++) {
                        if (st < 6) mbar_wait(bars + 8 * (uint32_t)((0x1f070d060504ull >> (8 * st)) & 0xff), st < 5);
                        else mbar_wait(bars + 8 * (B_EMPTYD + sd), pe);
                        const uint32_t da = sb + wd_slot(sd), fb_ = bars + 8 * (B_FULLD + sd);
                        mbar_expect(fb_, 16384);
                        tma2d(da, &M.wd, 128 * dg, 64 * st, fb_);
                        tma2d(da + 8192, &M.wd, 128 * dg + 64, 64 * st, fb_);
                        if (++sd == 6) { sd = 0; pe ^= 1; }
                    }
                }
            } else if (warp < 15) {
                const int V = warp - 13;
                #pragma unroll 1
                for (int st = 1 - V; st < 8; st++) {
                    const uint32_t s = 2 * V + (st & 1);
                    mbar_wait(bars + 8 * (B_EMPTYX + s), ((st >> 1) & 1) ^ 1);
                    mbar_expect(bars + 8 * (B_FULLX + s), (168 + 8 * V) * 128);
                    tma2d(sb + OFF_X + s * XBUF, &M.x[V], 64 * st, TOKG * tg + 168 * V, bars + 8 * (B_FULLX + s));
                }
                if (c < 128) {
                    if (V == 0) {
                        mbar_wait(bars + 8 * (B_STG + 1), 0);
                        #pragma unroll 1
                        for (int o = 8 * tau; o < 8 * tau + 8; o += 7) flag_wait(P.flags, F_H + 2 * (o / 43) + ((o % 43) >= 21), 22);
                        mbar_arrive(bars + 8 * B_HF);
                        STAMP(25);
                        int sh = 0; uint32_t pe = 1;
                        #pragma unroll 1
                        for (int st = 0; st < 22; st++) {
                            const uint32_t fb_ = bars + 8 * (B_FULLD + sh);
                            mbar_wait(bars + 8 * (B_EMPTYD + sh), pe);
                            mbar_expect(fb_, 8192);
                            asm volatile("cp.async.bulk.tensor.5d.shared::cluster.global.mbarrier::complete_tx::bytes [%0], [%1, {%3, %3, %3, %4, %5}], [%2];"
                                :: "r"(sb + h_slot(sh)), "l"(&M.hld), "r"(fb_), "r"(0), "r"(2 * tau), "r"(8 * st) : "memory");
                            if (++sh == 6) { sh = 0; pe ^= 1; }
                        }
                    } else {
                        mbar_wait(bars + 8 * B_CH0, 0);
                        mbar_expect(bars + 8 * B_XO, 16384);
                        tma2d(sb + OFF_CONV, &M.xo, 128 * dg, 64 * tau, bars + 8 * B_XO);
                        tma2d(sb + OFF_CONV + 8192, &M.xo, 128 * dg + 64, 64 * tau, bars + 8 * B_XO);
                        flag_wait(P.flags, F_S + dg, 64);
                        STAMP(26);
                        mbar_arrive(bars + 8 * B_S);
                        mbar_wait(bars + 8 * B_HF, 0);
                        exit_count(P.flags);
                    }
                }
            } else {
                mbar_wait(bars + 8 * B_LN, 0);
                if (c < 128) {
                    #pragma unroll 1
                    for (int i = 0; i < 4; i++)
                        asm volatile("cp.async.bulk.tensor.2d.global.shared::cta.bulk_group [%0, {%2, %3}], [%1];"
                            :: "l"(&M.xt), "r"(sb + OFF_CONV + i * CH_STRIDE + CH_LNT), "r"((c & 1) * 1024 + (126 - (c & ~1)) * 8), "r"(128 * i) : "memory");
                    #pragma unroll 1
                    for (int i = 0; i < 2; i++) {
                        const int t = 16 * (c & ~1) + 8 * (c & 1) + 16 - 16 * i;
                        bulk_store(P.mb + t, sb + OFF_CSUM + 128 * i, 128); bulk_store(P.hr + t, sb + OFF_CSUM + 256 + 32 * i, 32);
                    }
                }
                flag_signal(P.flags, F_A);
                mbar_arrive(bars + 8 * B_LNS);
                flag_wait(P.flags, F_A, NCTA);
                STAMP(20);
                mbar_expect(bars + 8 * B_STATS, TOKG * 20);
                bulk_load(sb + OFF_MB, P.mb + TOKG * tg, TOKG * 16, bars + 8 * B_STATS);
                bulk_load(sb + OFF_HR, P.hr + TOKG * tg, TOKG * 4, bars + 8 * B_STATS);
                if (c < 128) {
                    mbar_wait(bars + 8 * (B_K + 1), 0);
                    fence_async_smem();
                    mbar_expect(bars + 8 * B_U, 8 * 2048);
                    #pragma unroll 1
                    for (int i = 0; i < 8; i++)
                        bulk_load(sb + OFF_CONV + (i >> 1) * CH_STRIDE + CH_U + (i & 1) * UPLANE, P.xnT + 4 * c * 256 + i * 128, 2048, bars + 8 * B_U);
                } else exit_count(P.flags);
                #pragma unroll 1
                for (int V = 0; V < 2; V++) {
                    mbar_wait(bars + 8 * (B_EPI + V), 0);
                    asm volatile("cp.async.bulk.tensor.3d.global.shared::cta.bulk_group [%0, {%2, %3, %4}], [%1];"
                        :: "l"(&M.hst[V]), "r"(sb + OFF_X + V * 2 * XBUF), "r"(0), "r"(43 * tg + 21 * V), "r"(8 * fb) : "memory");
                    flag_signal(P.flags, F_H + 2 * tg + V);
                    mbar_arrive(bars + 8 * (B_STG + V));
                }
                if (c < 128) {
                    #pragma unroll 1
                    for (int V = 0; V < 2; V++) {
                        mbar_wait(bars + 8 * (B_SIG + V), 0);
                        bulk_store(P.S + (2 * c + V) * 1024, sb + OFF_CONV + (2 * V + 1) * CH_STRIDE, 8192);
                        flag_signal(P.flags, F_S + (c >> 5));
                    }
                }
            }
        }
    }
}

typedef CUresult (*EncodeFn)(CUtensorMap*, CUtensorMapDataType, cuuint32_t, void*, const cuuint64_t*, const cuuint64_t*, const cuuint32_t*,
                             const cuuint32_t*, CUtensorMapInterleave, CUtensorMapSwizzle, CUtensorMapL2promotion, CUtensorMapFloatOOBfill);

void make_map(EncodeFn enc, CUtensorMap* m, const void* ptr, int rank, const cuuint64_t* dims, const cuuint64_t* strides, const cuuint32_t* box, bool swz) {
    const cuuint32_t es[5] = {1, 1, 1, 1, 1};
    enc(m, CU_TENSOR_MAP_DATA_TYPE_BFLOAT16, rank, (void*)ptr, dims, strides, box, es, CU_TENSOR_MAP_INTERLEAVE_NONE,
        swz ? CU_TENSOR_MAP_SWIZZLE_128B : CU_TENSOR_MAP_SWIZZLE_NONE, CU_TENSOR_MAP_L2_PROMOTION_L2_128B, CU_TENSOR_MAP_FLOAT_OOB_FILL_NONE);
}
void make_map2(EncodeFn enc, CUtensorMap* m, const void* ptr, cuuint64_t inner, cuuint64_t outer, cuuint32_t rows) {
    const cuuint64_t dims[2] = {inner, outer}, strides[1] = {inner * 2};
    const cuuint32_t box[2] = {64, rows};
    make_map(enc, m, ptr, 2, dims, strides, box, true);
}

}

extern "C" void kernel_launch(void* const* d_in, const int* in_sizes, int n_in, void* d_out, int out_size) {
    (void)in_sizes; (void)n_in; (void)out_size;
    static EncodeFn enc = nullptr;
    static void *hptr, *p_xnT, *p_mb, *p_hr, *p_S, *p_flags;
    if (!enc) {
        cudaDriverEntryPointQueryResult qr;
        cudaGetDriverEntryPoint("cuTensorMapEncodeTiled", (void**)&enc, cudaEnableDefault, &qr);
        cudaFuncSetAttribute(fused_kernel, cudaFuncAttributeMaxDynamicSharedMemorySize, SMEM_BYTES);
        cudaGetSymbolAddress(&hptr, g_H); cudaGetSymbolAddress(&p_xnT, g_xnT); cudaGetSymbolAddress(&p_mb, g_mb);
        cudaGetSymbolAddress(&p_hr, g_hr); cudaGetSymbolAddress(&p_S, g_S); cudaGetSymbolAddress(&p_flags, g_flags);
    }
    Params P;
    P.x = (const __nv_bfloat16*)d_in[0]; P.logA = (const __nv_bfloat16*)d_in[1]; P.Aim = (const __nv_bfloat16*)d_in[2];
    P.Cr = (const __nv_bfloat16*)d_in[3]; P.Ci = (const __nv_bfloat16*)d_in[4]; P.logdt = (const __nv_bfloat16*)d_in[5];
    P.Dskip = (const __nv_bfloat16*)d_in[6];
    P.xnT = (uint4*)p_xnT; P.mb = (uint4*)p_mb; P.hr = (float*)p_hr; P.S = (uint2*)p_S; P.flags = (unsigned*)p_flags;
    Maps M;
    make_map2(enc, &M.x[0], d_in[0], DM, SEQ, 168); make_map2(enc, &M.x[1], d_in[0], DM, SEQ, 176);
    make_map2(enc, &M.xo, d_in[0], DM, SEQ, 64);    make_map2(enc, &M.out, d_out, DM, SEQ, 64);
    make_map2(enc, &M.wg, d_in[8], FF, DM, 64);     make_map2(enc, &M.wu, d_in[9], FF, DM, 64);
    make_map2(enc, &M.wd, d_in[10], DM, FF, 64);
    for (int v = 0; v < 2; v++) {
        const cuuint64_t dims[3] = {64, 256, 172}, strides[2] = {128, 32768};
        const cuuint32_t box[3] = {64, (cuuint32_t)(21 + v), 8};
        make_map(enc, &M.hst[v], hptr, 3, dims, strides, box, false);
    }
    {
        const cuuint64_t dims[2] = {2048, 512}, strides[1] = {4096};
        const cuuint32_t box[2] = {16, 128};
        make_map(enc, &M.xt, p_xnT, 2, dims, strides, box, false);
    }
    {
        const cuuint64_t dims[5] = {64, 2, 2, 64, 172}, strides[4] = {256, 128, 512, 32768};
        const cuuint32_t box[5] = {64, 2, 2, 2, 8};
        make_map(enc, &M.hld, hptr, 5, dims, strides, box, false);
    }
    fused_kernel<<<NCTA, 512, SMEM_BYTES>>>(P, M);
}
```

```cpp
#include <cuda_runtime.h>
#include <cuda_bf16.h>
#include <cuda.h>
#include <stdint.h>

#define PROF 0

namespace {

constexpr int SEQ = 2048, DM = 512, FF = 1376;
constexpr int NCTA = 132;
#define HOLD0 2
#define HOLD1 6
#define LAG 2
constexpr int TOKG = 344;

constexpr uint32_t OFF_W = 0;
constexpr uint32_t XBUF = 22528;
constexpr uint32_t OFF_X = 65536;
constexpr uint32_t OFF_CONV = 155648;
constexpr uint32_t CH_STRIDE = 16640;
constexpr uint32_t CH_T = 0;
constexpr uint32_t CH_A3 = 6272;
constexpr uint32_t CH_B3 = 10368;
constexpr uint32_t CH_U = 12416;
constexpr uint32_t CH_G = CH_A3 + 2064;
constexpr uint32_t UPLANE = 2112;
constexpr uint32_t CH_LNT = 12288;
constexpr uint32_t OFF_LN = OFF_X + 3 * XBUF;
constexpr uint32_t OFF_ST = 222208;
constexpr uint32_t OFF_CSUM = 230400;
constexpr uint32_t OFF_BAR = 231168;
constexpr uint32_t SMEM_BYTES = 231680;

enum {
    B_FULLW = 0, B_EMPTYW = 4, B_FULLX = 8, B_EMPTYX = 12, B_FULLD = 16, B_EMPTYD = 24,
    B_U = 32, B_XO = 33, B_S = 34, B_STG = 35, B_HF = 37, B_STATS = 38, B_LNS = 39, B_SST = 40,
    B_LNX = 41, B_GO = 42, B_CH0 = 43, B_K = 44,
    B_CONV = 46, B_LN = 50, B_CS = 51, B_EPI = 52, B_SIG = 54,
    B_COUNT = 56
};
enum { F_A = 0, F_H = 1, F_S = 13, F_EXIT = 17, F_COUNT = 18 };

__device__ uint4 g_xnT[DM * 256];
__device__ float2 g_st[6 * TOKG];
__device__ uint4 g_H[172 * 256 * 8];
__device__ uint2 g_S[256 * 1024];
__device__ unsigned g_flags[F_COUNT * 32];
#define STAMP(i) do {} while (0)
#define GSTAMP(i) do {} while (0)

__device__ __forceinline__ uint32_t smem_u32(const void* p) { return (uint32_t)__cvta_generic_to_shared(p); }
__device__ __forceinline__ void mbar_expect(uint32_t bar, uint32_t bytes) { asm volatile("mbarrier.arrive.expect_tx.shared::cta.b64 _, [%0], %1;" :: "r"(bar), "r"(bytes) : "memory"); }
__device__ __forceinline__ void mbar_arrive(uint32_t bar) { asm volatile("mbarrier.arrive.shared::cta.b64 _, [%0];" :: "r"(bar) : "memory"); }
__device__ __forceinline__ void mbar_wait(uint32_t bar, uint32_t parity) {
    asm volatile("{.reg .pred p; .reg .u32 n; mov.u32 n, 0x20000;\n"
                 "LW: mbarrier.try_wait.parity.shared::cta.b64 p, [%0], %1;\n"
                 "sub.u32 n, n, 1; setp.eq.or.u32 p, n, 0, p; @!p bra LW;}" :: "r"(bar), "r"(parity) : "memory");
}
__device__ __forceinline__ bool elect_one() { uint32_t p; asm volatile("{.reg .pred P; elect.sync _|P, 0xffffffff; selp.u32 %0, 1, 0, P;}" : "=r"(p)); return p; }
__device__ __forceinline__ void tma2d(uint32_t dst, const CUtensorMap* m, int c0, int c1, uint32_t bar) {
    asm volatile("cp.async.bulk.tensor.2d.shared::cluster.global.mbarrier::complete_tx::bytes [%0], [%1, {%3, %4}], [%2];"
        :: "r"(dst), "l"(m), "r"(bar), "r"(c0), "r"(c1) : "memory");
}
__device__ __forceinline__ void bulk_load(uint32_t dst, const void* src, uint32_t bytes, uint32_t bar) {
    asm volatile("cp.async.bulk.shared::cluster.global.mbarrier::complete_tx::bytes [%0], [%1], %2, [%3];" :: "r"(dst), "l"(src), "r"(bytes), "r"(bar) : "memory");
}
__device__ __forceinline__ void bulk_store(void* dst, uint32_t src, uint32_t bytes) {
    asm volatile("cp.async.bulk.global.shared::cta.bulk_group [%0], [%1], %2;" :: "l"(dst), "r"(src), "r"(bytes) : "memory");
}
__device__ __forceinline__ void fence_async_smem() { asm volatile("fence.proxy.async.shared::cta;" ::: "memory"); }
__device__ __forceinline__ void flag_wait(unsigned* g_flags, int f, unsigned target) {
    asm volatile("{.reg .pred p; .reg .u32 n, v; mov.u32 n, 0x40000;\n"
                 "LF: ld.acquire.gpu.global.u32 v, [%0]; setp.ge.u32 p, v, %1; @p bra LD;\n"
                 "nanosleep.u32 20; sub.u32 n, n, 1; setp.ne.u32 p, n, 0; @p bra LF; trap;\nLD: }"
                 :: "l"(g_flags + f * 32), "r"(target) : "memory");
}
__device__ __forceinline__ void flag_signal(unsigned* g_flags, int f) {
    asm volatile("cp.async.bulk.commit_group; cp.async.bulk.wait_group 0; red.relaxed.gpu.global.add.u32 [%0], 1;" :: "l"(g_flags + f * 32) : "memory");
}
__device__ __forceinline__ void exit_count(unsigned* g_flags) {
    if (atomicAdd(g_flags + F_EXIT * 32, 1u) == NCTA - 1) {
        #pragma unroll 1
        for (int i = 0; i < F_COUNT; i++) g_flags[i * 32] = 0;
    }
}
__device__ __forceinline__ void bar_sync(int id) { asm volatile("bar.sync %0, 128;" :: "r"(id) : "memory"); }
__device__ __forceinline__ uint64_t mkdesc(uint32_t addr, uint32_t lbo, uint32_t sbo, uint32_t swz) {
    return (uint64_t)((addr >> 4) | ((lbo >> 4) << 16)) | ((uint64_t)((sbo >> 4) | (swz << 30)) << 32);
}
#define WG_FENCE() asm volatile("wgmma.fence.sync.aligned;" ::: "memory")
#define WG_COMMIT() asm volatile("wgmma.commit_group.sync.aligned;" ::: "memory")
#define WG_WAIT(n) asm volatile("wgmma.wait_group.sync.aligned " #n ";" ::: "memory")
template <int N> __device__ __forceinline__ void fence_acc(float (&d)[N]) {
    #pragma unroll
    for (int i = 0; i < N; i++) asm volatile("" : "+f"(d[i]) :: "memory");
}
template <int N> __device__ __forceinline__ void define_acc(float (&d)[N]) {
    #pragma unroll
    for (int i = 0; i < N; i++) asm volatile("" : "=f"(d[i]));
}
__device__ __forceinline__ uint32_t pack2(float lo, float hi) { uint32_t r; asm("cvt.rn.bf16x2.f32 %0, %1, %2;" : "=r"(r) : "f"(hi), "f"(lo)); return r; }
__device__ __forceinline__ float bf_lo(uint32_t v) { return __uint_as_float(v << 16); }
__device__ __forceinline__ float bf_hi(uint32_t v) { return __uint_as_float(v & 0xffff0000u); }
__device__ __forceinline__ float bf_round(float v) { return bf_hi(pack2(0.f, v)); }
__device__ __forceinline__ float tanh_fast(float v) { float r; asm("tanh.approx.f32 %0, %1;" : "=f"(r) : "f"(v)); return r; }
__device__ __forceinline__ float ex2(float v) { float r; asm("ex2.approx.ftz.f32 %0, %1;" : "=f"(r) : "f"(v)); return r; }
__device__ __forceinline__ uint4 lds128(uint32_t a) { uint4 v; asm volatile("ld.shared.v4.b32 {%0,%1,%2,%3}, [%4];" : "=r"(v.x), "=r"(v.y), "=r"(v.z), "=r"(v.w) : "r"(a)); return v; }
__device__ __forceinline__ uint2 lds64(uint32_t a) { uint2 v; asm volatile("ld.shared.v2.b32 {%0,%1}, [%2];" : "=r"(v.x), "=r"(v.y) : "r"(a)); return v; }
__device__ __forceinline__ float ldsf(uint32_t a) { float v; asm volatile("ld.shared.f32 %0, [%1];" : "=f"(v) : "r"(a)); return v; }
__device__ __forceinline__ void sts128(uint32_t a, uint32_t x, uint32_t y, uint32_t z, uint32_t w) { asm volatile("st.shared.v4.b32 [%0], {%1,%2,%3,%4};" :: "r"(a), "r"(x), "r"(y), "r"(z), "r"(w) : "memory"); }
__device__ __forceinline__ void sts64(uint32_t a, uint32_t x, uint32_t y) { asm volatile("st.shared.v2.b32 [%0], {%1,%2};" :: "r"(a), "r"(x), "r"(y) : "memory"); }
__device__ __forceinline__ void stsf(uint32_t a, float x) { asm volatile("st.shared.f32 [%0], %1;" :: "r"(a), "f"(x) : "memory"); }
__device__ __forceinline__ void sts16(uint32_t a, uint32_t x) { asm volatile("st.shared.b16 [%0], %1;" :: "r"(a), "h"((unsigned short)x) : "memory"); }
__device__ __forceinline__ void stsm4(uint32_t a, uint32_t r0, uint32_t r1, uint32_t r2, uint32_t r3) {
    asm volatile("stmatrix.sync.aligned.m8n8.x4.shared.b16 [%0], {%1,%2,%3,%4};" :: "r"(a), "r"(r0), "r"(r1), "r"(r2), "r"(r3) : "memory");
}
#define FU(x) __float_as_uint(x)
#define UF(x) __uint_as_float(x)
__device__ __forceinline__ uint32_t wd_slot(int s) { return (uint32_t)((0xb9a9403056201000ull >> (8 * s)) & 0xff) << 10; }
__device__ __forceinline__ uint32_t h_slot(int s) { return (uint32_t)((0xd1c9d98c847c746cull >> (8 * s)) & 0xff) << 10; }

template<int N> __device__ __forceinline__ void wg_rs(float (&d)[64], uint32_t a0, uint32_t a1, uint32_t a2, uint32_t a3, uint64_t db);
template<> __device__ __forceinline__ void wg_rs<128>(float (&d)[64], uint32_t a0, uint32_t a1, uint32_t a2, uint32_t a3, uint64_t db) {
  asm volatile("{.reg .pred p; setp.ne.b32 p, 1, 0; wgmma.mma_async.sync.aligned.m64n128k16.f32.bf16.bf16 {%0,%1,%2,%3,%4,%5,%6,%7,%8,%9,%10,%11,%12,%13,%14,%15,%16,%17,%18,%19,%20,%21,%22,%23,%24,%25,%26,%27,%28,%29,%30,%31,%32,%33,%34,%35,%36,%37,%38,%39,%40,%41,%42,%43,%44,%45,%46,%47,%48,%49,%50,%51,%52,%53,%54,%55,%56,%57,%58,%59,%60,%61,%62,%63}, {%64,%65,%66,%67}, %68, p, 1, 1, 0;}"
    : "+f"(d[0]),"+f"(d[1]),"+f"(d[2]),"+f"(d[3]),"+f"(d[4]),"+f"(d[5]),"+f"(d[6]),"+f"(d[7]),"+f"(d[8]),"+f"(d[9]),"+f"(d[10]),"+f"(d[11]),"+f"(d[12]),"+f"(d[13]),"+f"(d[14]),"+f"(d[15]),"+f"(d[16]),"+f"(d[17]),"+f"(d[18]),"+f"(d[19]),"+f"(d[20]),"+f"(d[21]),"+f"(d[22]),"+f"(d[23]),"+f"(d[24]),"+f"(d[25]),"+f"(d[26]),"+f"(d[27]),"+f"(d[28]),"+f"(d[29]),"+f"(d[30]),"+f"(d[31]),"+f"(d[32]),"+f"(d[33]),"+f"(d[34]),"+f"(d[35]),"+f"(d[36]),"+f"(d[37]),"+f"(d[38]),"+f"(d[39]),"+f"(d[40]),"+f"(d[41]),"+f"(d[42]),"+f"(d[43]),"+f"(d[44]),"+f"(d[45]),"+f"(d[46]),"+f"(d[47]),"+f"(d[48]),"+f"(d[49]),"+f"(d[50]),"+f"(d[51]),"+f"(d[52]),"+f"(d[53]),"+f"(d[54]),"+f"(d[55]),"+f"(d[56]),"+f"(d[57]),"+f"(d[58]),"+f"(d[59]),"+f"(d[60]),"+f"(d[61]),"+f"(d[62]),"+f"(d[63]) : "r"(a0), "r"(a1), "r"(a2), "r"(a3), "l"(db));
}
template<> __device__ __forceinline__ void wg_rs<120>(float (&d)[64], uint32_t a0, uint32_t a1, uint32_t a2, uint32_t a3, uint64_t db) {
  asm volatile("{.reg .pred p; setp.ne.b32 p, 1, 0; wgmma.mma_async.sync.aligned.m64n120k16.f32.bf16.bf16 {%0,%1,%2,%3,%4,%5,%6,%7,%8,%9,%10,%11,%12,%13,%14,%15,%16,%17,%18,%19,%20,%21,%22,%23,%24,%25,%26,%27,%28,%29,%30,%31,%32,%33,%34,%35,%36,%37,%38,%39,%40,%41,%42,%43,%44,%45,%46,%47,%48,%49,%50,%51,%52,%53,%54,%55,%56,%57,%58,%59}, {%60,%61,%62,%63}, %64, p, 1, 1, 0;}"
    : "+f"(d[0]),"+f"(d[1]),"+f"(d[2]),"+f"(d[3]),"+f"(d[4]),"+f"(d[5]),"+f"(d[6]),"+f"(d[7]),"+f"(d[8]),"+f"(d[9]),"+f"(d[10]),"+f"(d[11]),"+f"(d[12]),"+f"(d[13]),"+f"(d[14]),"+f"(d[15]),"+f"(d[16]),"+f"(d[17]),"+f"(d[18]),"+f"(d[19]),"+f"(d[20]),"+f"(d[21]),"+f"(d[22]),"+f"(d[23]),"+f"(d[24]),"+f"(d[25]),"+f"(d[26]),"+f"(d[27]),"+f"(d[28]),"+f"(d[29]),"+f"(d[30]),"+f"(d[31]),"+f"(d[32]),"+f"(d[33]),"+f"(d[34]),"+f"(d[35]),"+f"(d[36]),"+f"(d[37]),"+f"(d[38]),"+f"(d[39]),"+f"(d[40]),"+f"(d[41]),"+f"(d[42]),"+f"(d[43]),"+f"(d[44]),"+f"(d[45]),"+f"(d[46]),"+f"(d[47]),"+f"(d[48]),"+f"(d[49]),"+f"(d[50]),"+f"(d[51]),"+f"(d[52]),"+f"(d[53]),"+f"(d[54]),"+f"(d[55]),"+f"(d[56]),"+f"(d[57]),"+f"(d[58]),"+f"(d[59]) : "r"(a0), "r"(a1), "r"(a2), "r"(a3), "l"(db));
}
template<> __device__ __forceinline__ void wg_rs<112>(float (&d)[64], uint32_t a0, uint32_t a1, uint32_t a2, uint32_t a3, uint64_t db) {
  asm volatile("{.reg .pred p; setp.ne.b32 p, 1, 0; wgmma.mma_async.sync.aligned.m64n112k16.f32.bf16.bf16 {%0,%1,%2,%3,%4,%5,%6,%7,%8,%9,%10,%11,%12,%13,%14,%15,%16,%17,%18,%19,%20,%21,%22,%23,%24,%25,%26,%27,%28,%29,%30,%31,%32,%33,%34,%35,%36,%37,%38,%39,%40,%41,%42,%43,%44,%45,%46,%47,%48,%49,%50,%51,%52,%53,%54,%55}, {%56,%57,%58,%59}, %60, p, 1, 1, 0;}"
    : "+f"(d[0]),"+f"(d[1]),"+f"(d[2]),"+f"(d[3]),"+f"(d[4]),"+f"(d[5]),"+f"(d[6]),"+f"(d[7]),"+f"(d[8]),"+f"(d[9]),"+f"(d[10]),"+f"(d[11]),"+f"(d[12]),"+f"(d[13]),"+f"(d[14]),"+f"(d[15]),"+f"(d[16]),"+f"(d[17]),"+f"(d[18]),"+f"(d[19]),"+f"(d[20]),"+f"(d[21]),"+f"(d[22]),"+f"(d[23]),"+f"(d[24]),"+f"(d[25]),"+f"(d[26]),"+f"(d[27]),"+f"(d[28]),"+f"(d[29]),"+f"(d[30]),"+f"(d[31]),"+f"(d[32]),"+f"(d[33]),"+f"(d[34]),"+f"(d[35]),"+f"(d[36]),"+f"(d[37]),"+f"(d[38]),"+f"(d[39]),"+f"(d[40]),"+f"(d[41]),"+f"(d[42]),"+f"(d[43]),"+f"(d[44]),"+f"(d[45]),"+f"(d[46]),"+f"(d[47]),"+f"(d[48]),"+f"(d[49]),"+f"(d[50]),"+f"(d[51]),"+f"(d[52]),"+f"(d[53]),"+f"(d[54]),"+f"(d[55]) : "r"(a0), "r"(a1), "r"(a2), "r"(a3), "l"(db));
}
template<> __device__ __forceinline__ void wg_rs<104>(float (&d)[64], uint32_t a0, uint32_t a1, uint32_t a2, uint32_t a3, uint64_t db) {
  asm volatile("{.reg .pred p; setp.ne.b32 p, 1, 0; wgmma.mma_async.sync.aligned.m64n104k16.f32.bf16.bf16 {%0,%1,%2,%3,%4,%5,%6,%7,%8,%9,%10,%11,%12,%13,%14,%15,%16,%17,%18,%19,%20,%21,%22,%23,%24,%25,%26,%27,%28,%29,%30,%31,%32,%33,%34,%35,%36,%37,%38,%39,%40,%41,%42,%43,%44,%45,%46,%47,%48,%49,%50,%51}, {%52,%53,%54,%55}, %56, p, 1, 1, 0;}"
    : "+f"(d[0]),"+f"(d[1]),"+f"(d[2]),"+f"(d[3]),"+f"(d[4]),"+f"(d[5]),"+f"(d[6]),"+f"(d[7]),"+f"(d[8]),"+f"(d[9]),"+f"(d[10]),"+f"(d[11]),"+f"(d[12]),"+f"(d[13]),"+f"(d[14]),"+f"(d[15]),"+f"(d[16]),"+f"(d[17]),"+f"(d[18]),"+f"(d[19]),"+f"(d[20]),"+f"(d[21]),"+f"(d[22]),"+f"(d[23]),"+f"(d[24]),"+f"(d[25]),"+f"(d[26]),"+f"(d[27]),"+f"(d[28]),"+f"(d[29]),"+f"(d[30]),"+f"(d[31]),"+f"(d[32]),"+f"(d[33]),"+f"(d[34]),"+f"(d[35]),"+f"(d[36]),"+f"(d[37]),"+f"(d[38]),"+f"(d[39]),"+f"(d[40]),"+f"(d[41]),"+f"(d[42]),"+f"(d[43]),"+f"(d[44]),"+f"(d[45]),"+f"(d[46]),"+f"(d[47]),"+f"(d[48]),"+f"(d[49]),"+f"(d[50]),"+f"(d[51]) : "r"(a0), "r"(a1), "r"(a2), "r"(a3), "l"(db));
}
template<> __device__ __forceinline__ void wg_rs<96>(float (&d)[64], uint32_t a0, uint32_t a1, uint32_t a2, uint32_t a3, uint64_t db) {
  asm volatile("{.reg .pred p; setp.ne.b32 p, 1, 0; wgmma.mma_async.sync.aligned.m64n96k16.f32.bf16.bf16 {%0,%1,%2,%3,%4,%5,%6,%7,%8,%9,%10,%11,%12,%13,%14,%15,%16,%17,%18,%19,%20,%21,%22,%23,%24,%25,%26,%27,%28,%29,%30,%31,%32,%33,%34,%35,%36,%37,%38,%39,%40,%41,%42,%43,%44,%45,%46,%47}, {%48,%49,%50,%51}, %52, p, 1, 1, 0;}"
    : "+f"(d[0]),"+f"(d[1]),"+f"(d[2]),"+f"(d[3]),"+f"(d[4]),"+f"(d[5]),"+f"(d[6]),"+f"(d[7]),"+f"(d[8]),"+f"(d[9]),"+f"(d[10]),"+f"(d[11]),"+f"(d[12]),"+f"(d[13]),"+f"(d[14]),"+f"(d[15]),"+f"(d[16]),"+f"(d[17]),"+f"(d[18]),"+f"(d[19]),"+f"(d[20]),"+f"(d[21]),"+f"(d[22]),"+f"(d[23]),"+f"(d[24]),"+f"(d[25]),"+f"(d[26]),"+f"(d[27]),"+f"(d[28]),"+f"(d[29]),"+f"(d[30]),"+f"(d[31]),"+f"(d[32]),"+f"(d[33]),"+f"(d[34]),"+f"(d[35]),"+f"(d[36]),"+f"(d[37]),"+f"(d[38]),"+f"(d[39]),"+f"(d[40]),"+f"(d[41]),"+f"(d[42]),"+f"(d[43]),"+f"(d[44]),"+f"(d[45]),"+f"(d[46]),"+f"(d[47]) : "r"(a0), "r"(a1), "r"(a2), "r"(a3), "l"(db));
}
template<> __device__ __forceinline__ void wg_rs<88>(float (&d)[64], uint32_t a0, uint32_t a1, uint32_t a2, uint32_t a3, uint64_t db) {
  asm volatile("{.reg .pred p; setp.ne.b32 p, 1, 0; wgmma.mma_async.sync.aligned.m64n88k16.f32.bf16.bf16 {%0,%1,%2,%3,%4,%5,%6,%7,%8,%9,%10,%11,%12,%13,%14,%15,%16,%17,%18,%19,%20,%21,%22,%23,%24,%25,%26,%27,%28,%29,%30,%31,%32,%33,%34,%35,%36,%37,%38,%39,%40,%41,%42,%43}, {%44,%45,%46,%47}, %48, p, 1, 1, 0;}"
    : "+f"(d[0]),"+f"(d[1]),"+f"(d[2]),"+f"(d[3]),"+f"(d[4]),"+f"(d[5]),"+f"(d[6]),"+f"(d[7]),"+f"(d[8]),"+f"(d[9]),"+f"(d[10]),"+f"(d[11]),"+f"(d[12]),"+f"(d[13]),"+f"(d[14]),"+f"(d[15]),"+f"(d[16]),"+f"(d[17]),"+f"(d[18]),"+f"(d[19]),"+f"(d[20]),"+f"(d[21]),"+f"(d[22]),"+f"(d[23]),"+f"(d[24]),"+f"(d[25]),"+f"(d[26]),"+f"(d[27]),"+f"(d[28]),"+f"(d[29]),"+f"(d[30]),"+f"(d[31]),"+f"(d[32]),"+f"(d[33]),"+f"(d[34]),"+f"(d[35]),"+f"(d[36]),"+f"(d[37]),"+f"(d[38]),"+f"(d[39]),"+f"(d[40]),"+f"(d[41]),"+f"(d[42]),"+f"(d[43]) : "r"(a0), "r"(a1), "r"(a2), "r"(a3), "l"(db));
}
template<> __device__ __forceinline__ void wg_rs<80>(float (&d)[64], uint32_t a0, uint32_t a1, uint32_t a2, uint32_t a3, uint64_t db) {
  asm volatile("{.reg .pred p; setp.ne.b32 p, 1, 0; wgmma.mma_async.sync.aligned.m64n80k16.f32.bf16.bf16 {%0,%1,%2,%3,%4,%5,%6,%7,%8,%9,%10,%11,%12,%13,%14,%15,%16,%17,%18,%19,%20,%21,%22,%23,%24,%25,%26,%27,%28,%29,%30,%31,%32,%33,%34,%35,%36,%37,%38,%39}, {%40,%41,%42,%43}, %44, p, 1, 1, 0;}"
    : "+f"(d[0]),"+f"(d[1]),"+f"(d[2]),"+f"(d[3]),"+f"(d[4]),"+f"(d[5]),"+f"(d[6]),"+f"(d[7]),"+f"(d[8]),"+f"(d[9]),"+f"(d[10]),"+f"(d[11]),"+f"(d[12]),"+f"(d[13]),"+f"(d[14]),"+f"(d[15]),"+f"(d[16]),"+f"(d[17]),"+f"(d[18]),"+f"(d[19]),"+f"(d[20]),"+f"(d[21]),"+f"(d[22]),"+f"(d[23]),"+f"(d[24]),"+f"(d[25]),"+f"(d[26]),"+f"(d[27]),"+f"(d[28]),"+f"(d[29]),"+f"(d[30]),"+f"(d[31]),"+f"(d[32]),"+f"(d[33]),"+f"(d[34]),"+f"(d[35]),"+f"(d[36]),"+f"(d[37]),"+f"(d[38]),"+f"(d[39]) : "r"(a0), "r"(a1), "r"(a2), "r"(a3), "l"(db));
}
template<> __device__ __forceinline__ void wg_rs<72>(float (&d)[64], uint32_t a0, uint32_t a1, uint32_t a2, uint32_t a3, uint64_t db) {
  asm volatile("{.reg .pred p; setp.ne.b32 p, 1, 0; wgmma.mma_async.sync.aligned.m64n72k16.f32.bf16.bf16 {%0,%1,%2,%3,%4,%5,%6,%7,%8,%9,%10,%11,%12,%13,%14,%15,%16,%17,%18,%19,%20,%21,%22,%23,%24,%25,%26,%27,%28,%29,%30,%31,%32,%33,%34,%35}, {%36,%37,%38,%39}, %40, p, 1, 1, 0;}"
    : "+f"(d[0]),"+f"(d[1]),"+f"(d[2]),"+f"(d[3]),"+f"(d[4]),"+f"(d[5]),"+f"(d[6]),"+f"(d[7]),"+f"(d[8]),"+f"(d[9]),"+f"(d[10]),"+f"(d[11]),"+f"(d[12]),"+f"(d[13]),"+f"(d[14]),"+f"(d[15]),"+f"(d[16]),"+f"(d[17]),"+f"(d[18]),"+f"(d[19]),"+f"(d[20]),"+f"(d[21]),"+f"(d[22]),"+f"(d[23]),"+f"(d[24]),"+f"(d[25]),"+f"(d[26]),"+f"(d[27]),"+f"(d[28]),"+f"(d[29]),"+f"(d[30]),"+f"(d[31]),"+f"(d[32]),"+f"(d[33]),"+f"(d[34]),"+f"(d[35]) : "r"(a0), "r"(a1), "r"(a2), "r"(a3), "l"(db));
}
template<> __device__ __forceinline__ void wg_rs<64>(float (&d)[64], uint32_t a0, uint32_t a1, uint32_t a2, uint32_t a3, uint64_t db) {
  asm volatile("{.reg .pred p; setp.ne.b32 p, 1, 0; wgmma.mma_async.sync.aligned.m64n64k16.f32.bf16.bf16 {%0,%1,%2,%3,%4,%5,%6,%7,%8,%9,%10,%11,%12,%13,%14,%15,%16,%17,%18,%19,%20,%21,%22,%23,%24,%25,%26,%27,%28,%29,%30,%31}, {%32,%33,%34,%35}, %36, p, 1, 1, 0;}"
    : "+f"(d[0]),"+f"(d[1]),"+f"(d[2]),"+f"(d[3]),"+f"(d[4]),"+f"(d[5]),"+f"(d[6]),"+f"(d[7]),"+f"(d[8]),"+f"(d[9]),"+f"(d[10]),"+f"(d[11]),"+f"(d[12]),"+f"(d[13]),"+f"(d[14]),"+f"(d[15]),"+f"(d[16]),"+f"(d[17]),"+f"(d[18]),"+f"(d[19]),"+f"(d[20]),"+f"(d[21]),"+f"(d[22]),"+f"(d[23]),"+f"(d[24]),"+f"(d[25]),"+f"(d[26]),"+f"(d[27]),"+f"(d[28]),"+f"(d[29]),"+f"(d[30]),"+f"(d[31]) : "r"(a0), "r"(a1), "r"(a2), "r"(a3), "l"(db));
}
__device__ __forceinline__ void wg_rs_first(float (&d)[64], uint32_t a0, uint32_t a1, uint32_t a2, uint32_t a3, uint64_t db) {
  asm volatile("{.reg .pred p; setp.ne.b32 p, 0, 0; wgmma.mma_async.sync.aligned.m64n128k16.f32.bf16.bf16 {%0,%1,%2,%3,%4,%5,%6,%7,%8,%9,%10,%11,%12,%13,%14,%15,%16,%17,%18,%19,%20,%21,%22,%23,%24,%25,%26,%27,%28,%29,%30,%31,%32,%33,%34,%35,%36,%37,%38,%39,%40,%41,%42,%43,%44,%45,%46,%47,%48,%49,%50,%51,%52,%53,%54,%55,%56,%57,%58,%59,%60,%61,%62,%63}, {%64,%65,%66,%67}, %68, p, 1, 1, 0;}"
    : "=f"(d[0]),"=f"(d[1]),"=f"(d[2]),"=f"(d[3]),"=f"(d[4]),"=f"(d[5]),"=f"(d[6]),"=f"(d[7]),"=f"(d[8]),"=f"(d[9]),"=f"(d[10]),"=f"(d[11]),"=f"(d[12]),"=f"(d[13]),"=f"(d[14]),"=f"(d[15]),"=f"(d[16]),"=f"(d[17]),"=f"(d[18]),"=f"(d[19]),"=f"(d[20]),"=f"(d[21]),"=f"(d[22]),"=f"(d[23]),"=f"(d[24]),"=f"(d[25]),"=f"(d[26]),"=f"(d[27]),"=f"(d[28]),"=f"(d[29]),"=f"(d[30]),"=f"(d[31]),"=f"(d[32]),"=f"(d[33]),"=f"(d[34]),"=f"(d[35]),"=f"(d[36]),"=f"(d[37]),"=f"(d[38]),"=f"(d[39]),"=f"(d[40]),"=f"(d[41]),"=f"(d[42]),"=f"(d[43]),"=f"(d[44]),"=f"(d[45]),"=f"(d[46]),"=f"(d[47]),"=f"(d[48]),"=f"(d[49]),"=f"(d[50]),"=f"(d[51]),"=f"(d[52]),"=f"(d[53]),"=f"(d[54]),"=f"(d[55]),"=f"(d[56]),"=f"(d[57]),"=f"(d[58]),"=f"(d[59]),"=f"(d[60]),"=f"(d[61]),"=f"(d[62]),"=f"(d[63]) : "r"(a0), "r"(a1), "r"(a2), "r"(a3), "l"(db));
}
__device__ __forceinline__ void wg_tt128(float (&d)[64], uint64_t da, uint64_t db, int sc) {
  asm volatile("{.reg .pred p; setp.ne.b32 p, %66, 0; wgmma.mma_async.sync.aligned.m64n128k16.f32.bf16.bf16 {%0,%1,%2,%3,%4,%5,%6,%7,%8,%9,%10,%11,%12,%13,%14,%15,%16,%17,%18,%19,%20,%21,%22,%23,%24,%25,%26,%27,%28,%29,%30,%31,%32,%33,%34,%35,%36,%37,%38,%39,%40,%41,%42,%43,%44,%45,%46,%47,%48,%49,%50,%51,%52,%53,%54,%55,%56,%57,%58,%59,%60,%61,%62,%63}, %64, %65, p, 1, 1, 1, 1;}"
    : "+f"(d[0]),"+f"(d[1]),"+f"(d[2]),"+f"(d[3]),"+f"(d[4]),"+f"(d[5]),"+f"(d[6]),"+f"(d[7]),"+f"(d[8]),"+f"(d[9]),"+f"(d[10]),"+f"(d[11]),"+f"(d[12]),"+f"(d[13]),"+f"(d[14]),"+f"(d[15]),"+f"(d[16]),"+f"(d[17]),"+f"(d[18]),"+f"(d[19]),"+f"(d[20]),"+f"(d[21]),"+f"(d[22]),"+f"(d[23]),"+f"(d[24]),"+f"(d[25]),"+f"(d[26]),"+f"(d[27]),"+f"(d[28]),"+f"(d[29]),"+f"(d[30]),"+f"(d[31]),"+f"(d[32]),"+f"(d[33]),"+f"(d[34]),"+f"(d[35]),"+f"(d[36]),"+f"(d[37]),"+f"(d[38]),"+f"(d[39]),"+f"(d[40]),"+f"(d[41]),"+f"(d[42]),"+f"(d[43]),"+f"(d[44]),"+f"(d[45]),"+f"(d[46]),"+f"(d[47]),"+f"(d[48]),"+f"(d[49]),"+f"(d[50]),"+f"(d[51]),"+f"(d[52]),"+f"(d[53]),"+f"(d[54]),"+f"(d[55]),"+f"(d[56]),"+f"(d[57]),"+f"(d[58]),"+f"(d[59]),"+f"(d[60]),"+f"(d[61]),"+f"(d[62]),"+f"(d[63]) : "l"(da), "l"(db), "r"(sc));
}
__device__ __forceinline__ void wg_tt64(float (&d)[64], uint64_t da, uint64_t db, int sc) {
  asm volatile("{.reg .pred p; setp.ne.b32 p, %34, 0; wgmma.mma_async.sync.aligned.m64n64k16.f32.bf16.bf16 {%0,%1,%2,%3,%4,%5,%6,%7,%8,%9,%10,%11,%12,%13,%14,%15,%16,%17,%18,%19,%20,%21,%22,%23,%24,%25,%26,%27,%28,%29,%30,%31}, %32, %33, p, 1, 1, 1, 1;}"
    : "+f"(d[0]),"+f"(d[1]),"+f"(d[2]),"+f"(d[3]),"+f"(d[4]),"+f"(d[5]),"+f"(d[6]),"+f"(d[7]),"+f"(d[8]),"+f"(d[9]),"+f"(d[10]),"+f"(d[11]),"+f"(d[12]),"+f"(d[13]),"+f"(d[14]),"+f"(d[15]),"+f"(d[16]),"+f"(d[17]),"+f"(d[18]),"+f"(d[19]),"+f"(d[20]),"+f"(d[21]),"+f"(d[22]),"+f"(d[23]),"+f"(d[24]),"+f"(d[25]),"+f"(d[26]),"+f"(d[27]),"+f"(d[28]),"+f"(d[29]),"+f"(d[30]),"+f"(d[31]) : "l"(da), "l"(db), "r"(sc));
}
__device__ __forceinline__ void wg_tt32(float (&d)[64], uint64_t da, uint64_t db, int sc) {
  asm volatile("{.reg .pred p; setp.ne.b32 p, %18, 0; wgmma.mma_async.sync.aligned.m64n32k16.f32.bf16.bf16 {%0,%1,%2,%3,%4,%5,%6,%7,%8,%9,%10,%11,%12,%13,%14,%15}, %16, %17, p, 1, 1, 1, 1;}"
    : "+f"(d[0]),"+f"(d[1]),"+f"(d[2]),"+f"(d[3]),"+f"(d[4]),"+f"(d[5]),"+f"(d[6]),"+f"(d[7]),"+f"(d[8]),"+f"(d[9]),"+f"(d[10]),"+f"(d[11]),"+f"(d[12]),"+f"(d[13]),"+f"(d[14]),"+f"(d[15]) : "l"(da), "l"(db), "r"(sc));
}
__device__ __forceinline__ void wg_g1(float (&d)[88], uint64_t da, uint64_t db, int sc) {
  asm volatile("{.reg .pred p; setp.ne.b32 p, %90, 0; wgmma.mma_async.sync.aligned.m64n176k16.f32.bf16.bf16 {%0,%1,%2,%3,%4,%5,%6,%7,%8,%9,%10,%11,%12,%13,%14,%15,%16,%17,%18,%19,%20,%21,%22,%23,%24,%25,%26,%27,%28,%29,%30,%31,%32,%33,%34,%35,%36,%37,%38,%39,%40,%41,%42,%43,%44,%45,%46,%47,%48,%49,%50,%51,%52,%53,%54,%55,%56,%57,%58,%59,%60,%61,%62,%63,%64,%65,%66,%67,%68,%69,%70,%71,%72,%73,%74,%75,%76,%77,%78,%79,%80,%81,%82,%83,%84,%85,%86,%87}, %88, %89, p, 1, 1, 1, 0;}"
    : "+f"(d[0]),"+f"(d[1]),"+f"(d[2]),"+f"(d[3]),"+f"(d[4]),"+f"(d[5]),"+f"(d[6]),"+f"(d[7]),"+f"(d[8]),"+f"(d[9]),"+f"(d[10]),"+f"(d[11]),"+f"(d[12]),"+f"(d[13]),"+f"(d[14]),"+f"(d[15]),"+f"(d[16]),"+f"(d[17]),"+f"(d[18]),"+f"(d[19]),"+f"(d[20]),"+f"(d[21]),"+f"(d[22]),"+f"(d[23]),"+f"(d[24]),"+f"(d[25]),"+f"(d[26]),"+f"(d[27]),"+f"(d[28]),"+f"(d[29]),"+f"(d[30]),"+f"(d[31]),"+f"(d[32]),"+f"(d[33]),"+f"(d[34]),"+f"(d[35]),"+f"(d[36]),"+f"(d[37]),"+f"(d[38]),"+f"(d[39]),"+f"(d[40]),"+f"(d[41]),"+f"(d[42]),"+f"(d[43]),"+f"(d[44]),"+f"(d[45]),"+f"(d[46]),"+f"(d[47]),"+f"(d[48]),"+f"(d[49]),"+f"(d[50]),"+f"(d[51]),"+f"(d[52]),"+f"(d[53]),"+f"(d[54]),"+f"(d[55]),"+f"(d[56]),"+f"(d[57]),"+f"(d[58]),"+f"(d[59]),"+f"(d[60]),"+f"(d[61]),"+f"(d[62]),"+f"(d[63]),"+f"(d[64]),"+f"(d[65]),"+f"(d[66]),"+f"(d[67]),"+f"(d[68]),"+f"(d[69]),"+f"(d[70]),"+f"(d[71]),"+f"(d[72]),"+f"(d[73]),"+f"(d[74]),"+f"(d[75]),"+f"(d[76]),"+f"(d[77]),"+f"(d[78]),"+f"(d[79]),"+f"(d[80]),"+f"(d[81]),"+f"(d[82]),"+f"(d[83]),"+f"(d[84]),"+f"(d[85]),"+f"(d[86]),"+f"(d[87]) : "l"(da), "l"(db), "r"(sc));
}

struct Params { const __nv_bfloat16 *x, *logA, *Aim, *Cr, *Ci, *logdt, *Dskip, *Wd; uint4* xnT; float2* st; uint2* S; unsigned* flags; };
struct Maps { CUtensorMap x[2], xo, out, wg, wu, wd, hst[2], hld, xt; };

__device__ __forceinline__ void conv_channel(uint32_t cb, int w, int lane, uint32_t (&res)[8], uint32_t bar_free) {
    const int q = lane & 3, g = lane >> 2, gam = g >> 2;
    float acc[64];
    uint4 a[4][4];
    const uint32_t t0 = cb + CH_T + (uint32_t)(14 + 4 * w + (g & 3) + 32 * gam - 2 * q) * 80u;
    #pragma unroll
    for (int s4 = 0; s4 < 4; s4++) {
        a[s4][0] = lds128(t0 + s4 * 16);
        a[s4][1] = lds128(t0 + 16 * 80 + s4 * 16);
        a[s4][2] = lds128(t0 - 8 * 80 + s4 * 16);
        a[s4][3] = lds128(t0 + 8 * 80 + s4 * 16);
    }
    const uint32_t l0 = FU(ldsf(t0 + 64)), l1 = FU(ldsf(t0 + 16 * 80 + 64)), l2 = FU(ldsf(t0 - 8 * 80 + 64)), l3 = FU(ldsf(t0 + 8 * 80 + 64));
    const uint64_t dU = mkdesc(cb + CH_U, UPLANE, 128, 0);
    WG_FENCE();
#define CT(N, s, c) wg_rs<N>(acc, a[(s) >> 2][0].c, a[(s) >> 2][1].c, a[(s) >> 2][2].c, a[(s) >> 2][3].c, dU + 4 * (s))
    wg_rs_first(acc, a[0][0].x, a[0][1].x, a[0][2].x, a[0][3].x, dU);
    CT(128, 1, y); CT(120, 2, z); CT(120, 3, w);
    CT(112, 4, x); CT(112, 5, y); CT(104, 6, z); CT(104, 7, w);
    CT(96, 8, x);  CT(96, 9, y);  CT(88, 10, z); CT(88, 11, w);
    CT(80, 12, x); CT(80, 13, y); CT(72, 14, z); CT(72, 15, w);
#undef CT
    wg_rs<64>(acc, l0, l1, l2, l3, dU + 64);
    wg_tt64(acc, mkdesc(cb + CH_A3, 128, 512, 0), mkdesc(cb + CH_B3, 128, 256, 0), 1);
    wg_tt32(acc, mkdesc(cb + CH_A3 + 256, 128, 512, 0), mkdesc(cb + CH_B3 + 1024, 128, 256, 0), 1);
    WG_COMMIT();
    WG_WAIT(0);
    fence_acc(acc);
    if (bar_free && lane == 0) mbar_arrive(bar_free);
    const int src1 = (lane & ~3) | ((q + 1) & 3);
    float E[16][2];
    #pragma unroll
    for (int j = 0; j < 16; j++) {
        const float nxt = (j < 15) ? acc[4 * (j + 1) + 2] : 0.f;
        const float sup = (q == 0) ? nxt : acc[4 * j + 2];
        const float v = __shfl_sync(0xffffffffu, sup, src1);
        E[j][0] = acc[4 * j] + acc[4 * j + 3];
        E[j][1] = acc[4 * j + 1] + v;
    }
    const int src2 = gam ? ((lane & 12) | ((q + 3) & 3)) : (16 | (lane & 12) | ((q + 1) & 3));
    const bool c1 = gam && q != 0, c2 = gam && q == 0;
    #pragma unroll
    for (int a2 = 0; a2 < 8; a2++) {
        float y[2];
        #pragma unroll
        for (int e = 0; e < 2; e++) {
            const float sup = c1 ? E[2 * a2][e] : E[2 * a2 + 1][e];
            const float nxt = (a2 < 7) ? E[2 * a2 + 2][e] : 0.f;
            const float keep = c2 ? nxt : (c1 ? E[2 * a2 + 1][e] : E[2 * a2][e]);
            y[e] = keep + __shfl_sync(0xffffffffu, sup, src2);
        }
        res[a2] = pack2(y[1], y[0]);
    }
}

__device__ __forceinline__ void consumer(uint32_t sb, int warp, const Params& P, const Maps& M) {
    const int V = warp >> 2, w = warp & 3, lane = threadIdx.x & 31, q = lane & 3, g = lane >> 2;
    const int c = blockIdx.x;
    const uint32_t bars = sb + OFF_BAR, xb = sb + OFF_X + V * 2 * XBUF;
    {
        float ag[88], au[88];
        define_acc(ag); define_acc(au);
        if (V == 0) {
            sts128(xb + (w >> 1) * XBUF + 168 * 128 + (threadIdx.x & 63) * 16, 0x3f803f80u, 0x3f803f80u, 0x3f803f80u, 0x3f803f80u);
            fence_async_smem();
            bar_sync(1);
        } else mbar_wait(bars + 8 * B_GO, 0);
        #pragma unroll 1
        for (int st = 0; st < 8; st++) {
            if (st + LAG * V == HOLD0 || st + LAG * V == HOLD1) mbar_wait(bars + 8 * (B_K + (st + LAG * V == HOLD1)), 0);
            mbar_wait(bars + 8 * (B_FULLW + (st & 3)), st >> 2);
            mbar_wait(bars + 8 * (B_FULLX + 2 * V + (st & 1)), (st >> 1) & 1);
            STAMP(40 + 8 * V + st);
            const uint64_t dG = mkdesc(sb + OFF_W + (st & 3) * 16384, 0, 1024, 1);
            const uint64_t dX = mkdesc(xb + (st & 1) * XBUF, 16, 1024, 1);
            WG_FENCE();
            #pragma unroll
            for (int k = 0; k < 4; k++) {
                wg_g1(ag, dG + k * 128, dX + k * 2, k ? 1 : st);
                wg_g1(au, dG + 512 + k * 128, dX + k * 2, k ? 1 : st);
            }
            WG_COMMIT();
            WG_WAIT(1);
            if (lane == 0 && st > 0) {
                mbar_arrive(bars + 8 * (B_EMPTYW + ((st - 1) & 3)));
                mbar_arrive(bars + 8 * (B_EMPTYX + 2 * V + ((st - 1) & 1)));
                if (warp < 4 && st == LAG) mbar_arrive(bars + 8 * B_GO);
            }
        }
        WG_WAIT(0);
        fence_acc(ag); fence_acc(au);
        if (lane == 0) { mbar_arrive(bars + 8 * (B_EMPTYW + 3)); mbar_arrive(bars + 8 * (B_EMPTYX + 2 * V + 1)); }
        STAMP(8 * V + 1);
        float cg0 = ag[84], cg1 = ag[86], cu0 = au[84], cu1 = au[86];
        const uint32_t ca = sb + OFF_CSUM + (8 * w + g) * 16;
        if (V == 0) { sts128(ca, FU(cg0), FU(cg1), FU(cu0), FU(cu1)); mbar_arrive(bars + 8 * B_CS); }
        else { mbar_wait(bars + 8 * B_CS, 0); const uint4 t = lds128(ca); cg0 = UF(t.x); cg1 = UF(t.y); cu0 = UF(t.z); cu1 = UF(t.w); }
        mbar_wait(bars + 8 * B_STATS, 0);
        mbar_wait(bars + 8 * (B_EMPTYX + 2 * V), 1);
        STAMP(13 + V);
        const uint32_t hs = xb + (2 * w + ((lane >> 3) & 1)) * (2688 + 128 * V) + (lane >> 4) * 128 + (lane & 7) * 16;
        const uint32_t sa = sb + OFF_ST + (168 * V + 2 * q) * 8;
        #pragma unroll
        for (int j = 0; j < 22; j += 2) {
            uint32_t o[4];
            #pragma unroll
            for (int jj = 0; jj < 2; jj++) {
                const uint4 sv = lds128(sa + (j + jj) * 64);
                float hv[4];
                #pragma unroll
                for (int i = 0; i < 4; i++) {
                    const float m = UF((i & 1) ? sv.z : sv.x);
                    const float gh = fmaf(-m, (i & 2) ? cg1 : cg0, ag[4 * (j + jj) + i]) * UF((i & 1) ? sv.w : sv.y);
                    const float p = gh * fmaf(-m, (i & 2) ? cu1 : cu0, au[4 * (j + jj) + i]);
                    hv[i] = fmaf(p, tanh_fast(gh), p);
                }
                o[2 * jj] = pack2(hv[0], hv[1]); o[2 * jj + 1] = pack2(hv[2], hv[3]);
            }
            uint32_t ad = hs + j * 128;
            if (j == 20 && V == 0 && lane >= 16) ad = xb + 21504 + (lane & 7) * 16;
            stsm4(ad, o[0], o[1], o[2], o[3]);
        }
        fence_async_smem();
        mbar_arrive(bars + 8 * (B_EPI + V));
        STAMP(8 * V + 2);
    }
    if (c >= 128) return;
    {
        uint32_t r0[8], r1[8];
        #pragma unroll
        for (int i = 0; i < 8; i++) asm volatile("" : "=r"(r1[i]));
        #pragma unroll 1
        for (int e = 0; e < 2; e++) {
            #pragma unroll
            for (int i = 0; i < 8; i++) r0[i] = r1[i];
            mbar_wait(bars + 8 * (B_CONV + 2 * V + e), 0);
            conv_channel(sb + OFF_CONV + (2 * V + e) * CH_STRIDE, w, lane, r1, (V + e == 0) ? bars + 8 * B_CH0 : 0);
            if (e == 0) STAMP(8 * V + 3);
        }
        const int gam = g >> 2, qq = gam ? ((q + 3) & 3) : q;
        const uint32_t sp = sb + OFF_CONV + (2 * V + 1) * CH_STRIDE + ((63 - 4 * gam - qq) * 16 + 4 * w + (g & 3)) * 8;
        bar_sync(3 + V);
        #pragma unroll
        for (int a2 = 0; a2 < 8; a2++) sts64(sp - a2 * 1024, r0[a2], r1[a2]);
        fence_async_smem();
        mbar_arrive(bars + 8 * (B_SIG + V));
        STAMP(8 * V + 4);
    }
    if (V == 1) return;
    {
        const int tau = c >> 2, dg = c & 3;
        const uint32_t row = 8 * (w & 1) + 32 * (w >> 1);
        float acc[64];
        define_acc(acc);
        uint2 sv[16];
        #pragma unroll
        for (int i = 0; i < 16; i++) asm volatile("" : "=r"(sv[i].x), "=r"(sv[i].y));
        const float rr0 = __ldcg(&P.st[64 * tau + row + g].y), rr1 = __ldcg(&P.st[64 * tau + row + g + 16].y);
        mbar_wait(bars + 8 * B_FULLD, 0);
        STAMP(5);
        uint64_t dB = mkdesc(sb + wd_slot(0), 8192, 1024, 1), dA = mkdesc(sb + h_slot(0), 1024, 128, 0);
        #pragma unroll 1
        for (int st = 0; st < 21; st++) {
            WG_FENCE();
            wg_tt128(acc, dA, dB, st);
            wg_tt128(acc, dA + 128, dB + 128, 1);
            wg_tt128(acc, dA + 256, dB + 256, 1);
            wg_tt128(acc, dA + 384, dB + 384, 1);
            WG_COMMIT();
            const int sd = (st + 1) & 7;
            const uint32_t nb = bars + 8 * (B_FULLD + sd), np = ((st + 1) >> 3) & 1;
            uint32_t ok;
            asm volatile("{.reg .pred p; mbarrier.test_wait.parity.shared::cta.b64 p, [%1], %2; selp.u32 %0, 1, 0, p;}" : "=r"(ok) : "r"(nb), "r"(np) : "memory");
            dB = mkdesc(sb + wd_slot(sd), 8192, 1024, 1); dA = mkdesc(sb + h_slot(sd), 1024, 128, 0);
            if (st == 14) {
                mbar_wait(bars + 8 * B_S, 0);
                const uint2* sp = P.S + (dg * 64 + q) * 1024 + (2 * tau) * 16 + (row >> 1) + 4 * (w & 1) + g;
                #pragma unroll
                for (int j = 0; j < 16; j++)
                    asm volatile("ld.global.cg.v2.b32 {%0,%1}, [%2];" : "=r"(sv[j].x), "=r"(sv[j].y) : "l"(sp + j * 4096));
            }
            WG_WAIT(1);
            if (lane == 0 && st > 0) mbar_arrive(bars + 8 * (B_EMPTYD + ((st - 1) & 7)));
            if (!ok) mbar_wait(nb, np);
        }
        WG_FENCE();
        wg_tt128(acc, dA, dB, 1);
        wg_tt128(acc, dA + 128, dB + 128, 1);
        WG_COMMIT();
        WG_WAIT(0);
        fence_acc(acc);
        STAMP(6);
        mbar_wait(bars + 8 * B_XO, 0);
        const uint32_t xo = sb + OFF_CONV + (row + (lane & 7) + 16 * ((lane >> 3) & 1)) * 128;
        #pragma unroll
        for (int j = 0; j < 16; j += 2) {
            const uint32_t ad = xo + (j >> 3) * 8192 + ((((j & 7) + (lane >> 4)) ^ (lane & 7)) << 4);
            uint32_t xr[4];
            asm volatile("ldmatrix.sync.aligned.m8n8.x4.shared.b16 {%0,%1,%2,%3}, [%4];" : "=r"(xr[0]), "=r"(xr[1]), "=r"(xr[2]), "=r"(xr[3]) : "r"(ad));
            #pragma unroll
            for (int i = 0; i < 4; i++) {
                const int jj = j + (i >> 1), hh = i & 1;
                const float f0 = acc[4 * jj + 2 * hh] * (hh ? rr1 : rr0), f1 = acc[4 * jj + 2 * hh + 1] * (hh ? rr1 : rr0);
                const uint32_t G = pack2(fmaf(f0, tanh_fast(f0), f0), fmaf(f1, tanh_fast(f1), f1));
                const uint32_t s2 = __byte_perm(sv[jj].x, sv[jj].y, hh ? 0x7632 : 0x5410);
                asm("fma.rn.bf16x2 %0, %1, %2, %0;" : "+r"(xr[i]) : "r"(s2), "r"(G));
            }
            stsm4(ad, xr[0], xr[1], xr[2], xr[3]);
        }
        fence_async_smem();
        bar_sync(1);
        if (w == 0 && elect_one()) {
            #pragma unroll
            for (int i = 0; i < 2; i++)
                asm volatile("cp.async.bulk.tensor.2d.global.shared::cta.bulk_group [%0, {%2, %3}], [%1];"
                    :: "l"(&M.out), "r"(sb + OFF_CONV + i * 8192), "r"(dg * 128 + 64 * i), "r"(tau * 64) : "memory");
            asm volatile("cp.async.bulk.commit_group; cp.async.bulk.wait_group.read 0;" ::: "memory");
        }
        STAMP(7); GSTAMP(23);
    }
}

__device__ __forceinline__ float2 cexp_p(float re2, float im, float p) {
    float sn, cs;
    const float mag = ex2(re2 * p), th = im * p;
    asm("sin.approx.ftz.f32 %0, %1;" : "=f"(sn) : "f"(th));
    asm("cos.approx.ftz.f32 %0, %1;" : "=f"(cs) : "f"(th));
    return make_float2(mag * cs, mag * sn);
}
__device__ __forceinline__ void ldsm4(uint32_t (&r)[4], uint32_t a) {
    asm volatile("ldmatrix.sync.aligned.m8n8.x4.shared.b16 {%0,%1,%2,%3}, [%4];" : "=r"(r[0]), "=r"(r[1]), "=r"(r[2]), "=r"(r[3]) : "r"(a) : "memory");
}
__device__ __forceinline__ float2 cmul(float2 a, float2 b) { return make_float2(fmaf(a.x, b.x, -a.y * b.y), fmaf(a.x, b.y, a.y * b.x)); }
__device__ __forceinline__ float2 csqr(float2 a) { const float t = a.x * a.y; return make_float2(fmaf(a.x, a.x, -a.y * a.y), t + t); }
__device__ __forceinline__ void mma16816(float (&d)[4], const uint32_t (&a)[4], uint32_t b0, uint32_t b1) {
    asm volatile("mma.sync.aligned.m16n8k16.row.col.f32.bf16.bf16.f32 {%0,%1,%2,%3}, {%4,%5,%6,%7}, {%8,%9}, {%0,%1,%2,%3};"
        : "+f"(d[0]), "+f"(d[1]), "+f"(d[2]), "+f"(d[3]) : "r"(a[0]), "r"(a[1]), "r"(a[2]), "r"(a[3]), "r"(b0), "r"(b1));
}

__device__ __forceinline__ void layer_norm(uint32_t sb, uint32_t cb, int w, int lane) {
    const uint32_t bars = sb + OFF_BAR;
    {
        mbar_wait(bars + 8 * B_LNX, 0);
        STAMP(34);
        {
            const int r = w + 4 * (lane >> 3);
            const uint32_t r0 = sb + OFF_LN + r * 1040, ra = r0 + (lane & 7) * 16;
            const float pv = bf_lo(FU(ldsf(r0)));
            float s0 = 0.f, s1 = 0.f, a0 = 0.f, a1 = 0.f;
            uint4 nx = lds128(ra);
            #pragma unroll 1
            for (int k = 128; k <= 1024; k += 128) {
                const uint32_t v[4] = {nx.x, nx.y, nx.z, nx.w};
                nx = lds128(ra + (k & 1023));
                #pragma unroll
                for (int i = 0; i < 4; i++) { const float t0 = bf_lo(v[i]) - pv, t1 = bf_hi(v[i]) - pv; s0 += t0; s1 += t1; a0 = fmaf(t0, t0, a0); a1 = fmaf(t1, t1, a1); }
            }
            s0 += s1; a0 += a1;
            #pragma unroll
            for (int o = 4; o; o >>= 1) { s0 += __shfl_xor_sync(0xffffffffu, s0, o); a0 += __shfl_xor_sync(0xffffffffu, a0, o); }
            s0 *= 1.f / DM;
            const float m = pv + s0, var = fmaxf(fmaf(-s0, s0, a0 * (1.f / DM)), 0.f);
            float sd, ri;
            asm("sqrt.approx.ftz.f32 %0, %1;" : "=f"(sd) : "f"(bf_round(bf_round(var) + 1e-5f)));
            asm("rcp.approx.ftz.f32 %0, %1;" : "=f"(ri) : "f"(bf_round(sd)));
            const uint32_t m2 = pack2(m, m);
            if ((lane & 7) == 0) {
                sts64(sb + OFF_CSUM + r * 8, m2 & 0xffff0000u, FU(0.5f * ri));
            }
            #pragma unroll 1
            for (int k = 128; k <= 1024; k += 128) {
                uint32_t v[4] = {nx.x, nx.y, nx.z, nx.w};
                nx = lds128(ra + (k & 1023));
                #pragma unroll
                for (int i = 0; i < 4; i++) {
                    uint32_t dv; asm("sub.rn.bf16x2 %0, %1, %2;" : "=r"(dv) : "r"(v[i]), "r"(m2));
                    v[i] = pack2(bf_lo(dv) * ri, bf_hi(dv) * ri);
                }
                sts128(ra + k - 128, v[0], v[1], v[2], v[3]);
            }
        }
        STAMP(62);
        bar_sync(2);
        {
            const uint32_t ad = sb + OFF_LN + (4 * ((lane & 7) >> 1) + (lane & 1) + 2 * ((lane >> 3) & 1)) * 1040 + (16 * w + (lane >> 4)) * 16;
            #pragma unroll 4
            for (int i = 0; i < 8; i++) {
                uint32_t r0, r1, r2, r3;
                asm volatile("ldmatrix.sync.aligned.m8n8.x4.trans.shared.b16 {%0,%1,%2,%3}, [%4];" : "=r"(r0), "=r"(r1), "=r"(r2), "=r"(r3) : "r"(ad + 32 * i));
                sts64(cb + CH_LNT + lane * 8 + i * 512, r0, r1); sts64(cb + CH_LNT + lane * 8 + i * 512 + 256, r2, r3);
            }
        }
        fence_async_smem();
        mbar_arrive(bars + 8 * B_LN);
        STAMP(16);
    }
}

__device__ __forceinline__ void aux_role(uint32_t sb, int w, const Params& P) {
    const int lane = threadIdx.x & 31, q = lane & 3, g = lane >> 2;
    const int c = blockIdx.x;
    const uint32_t bars = sb + OFF_BAR;
    if (c >= 128) {
        mbar_arrive(bars + 8 * B_LN);
        if (lane == 0) { mbar_arrive(bars + 8 * B_K); mbar_arrive(bars + 8 * (B_K + 1)); }
        return;
    }
    {
        const uint32_t cb = sb + OFF_CONV + w * CH_STRIDE;
        const uint32_t sF = cb + CH_A3;
        const int d = 4 * c + w;
        const uint2 la2 = *(const uint2*)(P.logA + d * 128 + 4 * lane), ai2 = *(const uint2*)(P.Aim + d * 128 + 4 * lane);
        const uint2 cr2 = *(const uint2*)(P.Cr + d * 128 + 4 * lane), ci2 = *(const uint2*)(P.Ci + d * 128 + 4 * lane);
        const float ldt = __bfloat162float(P.logdt[d]), dsk = __bfloat162float(P.Dskip[d]);
        float dacc[2][3][4];
        #pragma unroll
        for (int i = 0; i < 24; i++) (&dacc[0][0][0])[i] = 0.f;
        const float dt = bf_round(ex2(ldt * 1.4426950408889634f));
        const uint32_t lda = cb + ((lane & 7) + 8 * ((lane >> 3) & 1)) * 144 + (lane >> 4) * 16;
        const uint32_t ldb = cb + (32 + (lane & 7)) * 144 + (lane >> 3) * 16;
        uint64_t la = *(const uint64_t*)&la2, ai = *(const uint64_t*)&ai2, cr = *(const uint64_t*)&cr2, ci = *(const uint64_t*)&ci2;
        #pragma unroll 1
        for (int ck = 0; ck < 4; ck++, la >>= 16, ai >>= 16, cr >>= 16, ci >>= 16) {
            const uint32_t fa = cb + lane * 4 + (ck & 1) * 8064;
            if (ck == 1 && elect_one()) {
                mbar_expect(bars + 8 * B_LNX, 4096);
                #pragma unroll
                for (int i = 0; i < 4; i++)
                    bulk_load(sb + OFF_LN + (w + 4 * i) * 1040, P.x + (16 * (c & ~1) + 8 * (c & 1) + 16 + w + 4 * (i & 1) - 8 * (i & 2)) * DM, 1024, bars + 8 * B_LNX);
            }
            if (ck == 2) layer_norm(sb, cb, w, lane);
            if (ck == 3) mbar_wait(bars + 8 * B_LNS, 0);
            const float re2 = bf_round(ex2(bf_lo((uint32_t)la) * 1.4426950408889634f)) * dt * -1.4426950408889634f, im = bf_lo((uint32_t)ai) * dt;
            const float2 C = make_float2(bf_lo((uint32_t)cr) * (dt + dt), bf_lo((uint32_t)ci) * -(dt + dt));
            const float2 z8 = cexp_p(re2, im, 8.f), y1 = cexp_p(re2, -im, 1.f);
            float2 b0 = make_float2(1.f, 0.f), b1 = cexp_p(re2, im, 64.f), b2 = csqr(b1), b3 = cmul(b2, b1), l0 = C;
            const uint32_t fm = cb + (ck & 1) * 8064 + (lane >> 3) * 144 + (lane & 7) * 16;
#define PK(v) pack2((v).x, (v).y)
            #pragma unroll 1
            for (uint32_t ro = 0; ro < 8 * 144; ro += 144) {
                stsm4(fm + (lane >> 3) * 7 * 144 + ro, PK(b0), PK(b1), PK(b2), PK(b3));
                stsf(fa + 32 * 144 + ro, UF(PK(l0)));
                b0 = cmul(b0, z8); b1 = cmul(b1, z8); b2 = cmul(b2, z8); b3 = cmul(b3, z8); l0 = cmul(l0, y1);
            }
            if (ck < 2) STAMP(56 + 3 * ck);
            const float2 y256 = cexp_p(re2, -im, 256.f), y2 = csqr(y1), y4 = csqr(y2), y8 = make_float2(z8.x, -z8.y);
            const float2 t0 = cmul(C, y256), t1 = cmul(t0, y256), t2 = cmul(t1, y256), t3_ = cmul(t2, y256);
            const float2 u1 = cmul(t0, y2), u2 = cmul(u1, y2), u3 = cmul(u2, y2);
            stsm4(fm + 40 * 144, PK(t0), PK(u1), PK(u2), PK(u3));
            stsm4(fm + 44 * 144, PK(t1), PK(cmul(t1, y4)), PK(t2), PK(cmul(t2, y4)));
            const float2 v0 = cmul(t3_, y8), v1 = cmul(v0, y256), v2 = cmul(v1, y256), v3 = cmul(v2, y256);
            stsm4(fm + 48 * 144, PK(v0), PK(v1), PK(v2), PK(v3));
            stsf(fa + 52 * 144, UF(PK(t3_)));
#undef PK
            if (ck < 2) STAMP(57 + 3 * ck);
            if (ck & 1) {
                __syncwarp();
                #pragma unroll
                for (int k2 = 0; k2 < 4; k2++) {
                    const uint32_t ko = (k2 >> 1) * 8064 + (k2 & 1) * 64;
                    uint32_t b[3][4];
                    #pragma unroll
                    for (int t3 = 0; t3 < 3; t3++) ldsm4(b[t3], ldb + t3 * 8 * 144 + ko);
                    #pragma unroll
                    for (int k = 0; k < 2; k++)
                        #pragma unroll
                        for (int mu = 0; mu < 2; mu++) {
                            uint32_t a[4];
                            ldsm4(a, lda + mu * 16 * 144 + ko + k * 32);
                            #pragma unroll
                            for (int t3 = 0; t3 < 3; t3++) mma16816(dacc[mu][t3], a, b[t3][2 * k], b[t3][2 * k + 1]);
                        }
                }
                __syncwarp();
                if (lane == 0) mbar_arrive(bars + 8 * (B_K + (ck >> 1)));
                STAMP(58 + 3 * (ck >> 1));
            }
        }
        STAMP(18);
        const uint32_t sG = cb + CH_G;
        if (lane == 0) dacc[0][0][0] += dsk;
        if (lane < 16) sts128(((lane & 8) ? cb + CH_U + 2048 + (lane & 4) * (UPLANE / 4) : sG + 128 + (lane & 4) * 48) + (lane & 3) * 16, 0, 0, 0, 0);
        {
            const uint32_t f0 = sF + (8 * g + 2 * q) * 4, f1 = sF + ((q < 2) ? 256 + 4 * g + 2 * q : 256 + 2 * g + 64 * q) * 4, st1 = (q < 2) ? 128 : 64;
            const uint32_t ga = sG + ((g & 1) ? 0 : 192) + (63 - (g >> 1) - 32 * q) * 2;
            #pragma unroll
            for (int i = 0; i < 4; i++) {
                const int mu = i >> 1, hh = i & 1;
                sts64(f0 + i * 256, FU(dacc[mu][0][2 * hh]), FU(dacc[mu][0][2 * hh + 1]));
                sts64(f1 + i * st1, FU(dacc[mu][1][2 * hh]), FU(dacc[mu][1][2 * hh + 1]));
                const uint32_t pk = pack2(dacc[mu][2][2 * hh], dacc[mu][2][2 * hh + 1]);
                if (q < 2) { sts16(ga - 8 * i, pk & 0xffff); sts16(ga - 8 * i - 32, pk >> 16); }
            }
            if (lane == 2) stsf(sF + 2048, dacc[0][2][0]);
        }
    }
    bar_sync(2);
    STAMP(19);
    const int rw = lane - 1 + 31 * w, u = min(rw, 77) - 14;
    const uint32_t o0 = CH_A3 + u * 4, o1 = CH_A3 + (128 + ((u + ((u >> 1) & 1)) >> 1)) * 4, o2 = CH_A3 + (256 + ((u + 1 + ((u >> 2) & 1)) >> 2)) * 4;
    const int kap = (lane >> 4) * 8 + ((lane >> 1) & 7), gam = lane & 1, hh = w >> 1, wp = w & 1;
    const uint32_t oa = CH_U + wp * UPLANE + (127 - 4 * kap - 2 * gam - hh) * 16;
    const uint32_t ob = CH_U + (wp ^ 1) * UPLANE + (128 - wp - 4 * kap - 2 * gam - hh) * 16;
    const uint32_t od = CH_A3 + (4 * wp + hh) * 512 + (kap >> 3) * 256 + (kap & 7) * 16 + gam * 8;
    #pragma unroll 1
    for (int k = 0; k < 4; k++) {
        const int ch = 2 * (k & 1) + (k >> 1);
        const uint32_t cb = sb + OFF_CONV + ch * CH_STRIDE;
        if (w < 3) {
            const uint32_t f0 = cb + o0, f1 = cb + o1, f2 = cb + o2;
            float kv[17];
            kv[0] = ldsf(u < 0 ? f1 : f0); if (u < 0) kv[0] = 0.f;
            #pragma unroll
            for (int s = 1; s < 4; s++) kv[s] = ldsf(f0 + s * 256);
            kv[4] = ldsf(u < 0 ? f0 + 1024 : f1 + 512);
            #pragma unroll
            for (int s = 5; s < 8; s++) kv[s] = ldsf(f1 + s * 128);
            kv[8] = ldsf(u < 0 ? f1 + 1024 : f2 + 512);
            #pragma unroll
            for (int s = 9; s < 16; s++) kv[s] = ldsf(f2 + s * 64);
            kv[16] = ldsf(u < 0 ? f2 + 1024 : cb + CH_A3 + 2048); if (u > 4) kv[16] = 0.f;
            uint32_t o[17];
            #pragma unroll
            for (int s = 0; s < 17; s++) o[s] = pack2(kv[s], __shfl_up_sync(0xffffffffu, kv[s], 1));
            if (lane > 0 && rw < 78) {
                const uint32_t ta = cb + CH_T + rw * 80;
                #pragma unroll
                for (int s4 = 0; s4 < 4; s4++) sts128(ta + s4 * 16, o[4 * s4], o[4 * s4 + 1], o[4 * s4 + 2], o[4 * s4 + 3]);
                stsf(ta + 64, UF(o[16]));
            }
        } else {
            const uint32_t ga = cb + CH_G + ((lane >> 3) & 1) * 192 + (lane >> 4) * 16 + (lane & 7) * 8;
            #pragma unroll
            for (int i = 0; i < 4; i++) {
                const uint2 x0 = lds64(ga + 32 * i), x1 = lds64(ga + 32 * i + 8);
                sts128(cb + CH_B3 + lane * 16 + 512 * i, x0.x, x0.y, x1.x, x1.y);
            }
        }
        mbar_wait(bars + 8 * B_U, 0);
        float p[24];
        const uint2 r0 = lds64(cb + ob + 24), r3 = lds64(cb + oa);
        uint32_t r[8];
        *(uint4*)&r[0] = lds128(cb + oa + 16); *(uint4*)&r[4] = lds128(cb + ob);
        p[0] = 0.f;
        p[1] = bf_lo(r0.x); p[2] = p[1] + bf_hi(r0.x); p[3] = p[2] + bf_lo(r0.y); p[4] = p[3] + bf_hi(r0.y);
        #pragma unroll
        for (int i = 0; i < 8; i++) { p[5 + 2 * i] = p[4 + 2 * i] + bf_lo(r[i]); p[6 + 2 * i] = p[5 + 2 * i] + bf_hi(r[i]); }
        p[21] = p[20] + bf_lo(r3.x); p[22] = p[21] + bf_hi(r3.x); p[23] = p[22] + bf_lo(r3.y);
        bar_sync(2);
        #pragma unroll
        for (int i = 0; i < 8; i += 4) {
            sts64(cb + od + i * 256, pack2(p[i + 9] - p[i], p[i + 10] - p[i + 1]), pack2(p[i + 11] - p[i + 2], p[i + 12] - p[i + 3]));
            sts64(cb + od + i * 256 + 128, pack2(p[i + 16] - p[i + 9], p[i + 17] - p[i + 10]), pack2(p[i + 18] - p[i + 11], p[i + 19] - p[i + 12]));
        }
        fence_async_smem();
        mbar_arrive(bars + 8 * (B_CONV + ch));
        if (k == 0) STAMP(17);
    }
    STAMP(21);
}

__global__ void __launch_bounds__(512, 1)
fused_kernel(const __grid_constant__ Params P, const __grid_constant__ Maps M) {
    extern __shared__ __align__(1024) uint8_t smem_raw[];
    const uint32_t sb = smem_u32(smem_raw);
    const uint32_t bars = sb + OFF_BAR;
    const int warp = __shfl_sync(0xffffffffu, threadIdx.x >> 5, 0);
    const int c = blockIdx.x, tg = c / 22, fb = c - 22 * tg;
    if (elect_one()) {
        if (warp == 0) { STAMP(24); GSTAMP(22); }
        asm volatile("" :: "l"(((const uint64_t*)&P)[warp < 12 ? warp : 0]));
        if (warp < 11) asm volatile("prefetch.tensormap [%0];" :: "l"(&M.x[0] + warp) : "memory");
        #pragma unroll
        for (int k = 0; k < 4; k++) {
            const int i = 16 * k + ((warp + 4) & 15);
            const uint32_t cnt = i >= B_CONV ? 128 : ((0xf0ull >> i) & 1) ? 8 : ((0xff0000ull >> i) & 1) ? 2 : ((0x3e00ff00f000ull >> i) & 1) ? 4 : 1;
            asm volatile("mbarrier.init.shared::cta.b64 [%0], %1;" :: "r"(bars + 8 * i), "r"(cnt) : "memory");
        }
        asm volatile("fence.mbarrier_init.release.cluster; fence.proxy.async.shared::cta;" ::: "memory");
        if (warp == 12) {
            mbar_expect(bars + 8 * B_FULLW, 16384);
            tma2d(sb + OFF_W, &M.wg, 64 * fb, 0, bars + 8 * B_FULLW);
            tma2d(sb + OFF_W + 8192, &M.wu, 64 * fb, 0, bars + 8 * B_FULLW);
            STAMP(31);
        } else if (warp == 4) {
            mbar_expect(bars + 8 * B_FULLX, 168 * 128);
            tma2d(sb + OFF_X, &M.x[0], 0, TOKG * tg, bars + 8 * B_FULLX);
        }
        if (sb & 1023) __trap();
    }
    __syncthreads();
    if (warp < 8) {
        asm volatile("setmaxnreg.inc.sync.aligned.u32 208;");
        consumer(sb, warp, P, M);
    } else if (warp < 12) {
        asm volatile("setmaxnreg.dec.sync.aligned.u32 72;");
        STAMP(32);
        aux_role(sb, warp - 8, P);
    } else {
        asm volatile("setmaxnreg.dec.sync.aligned.u32 24;");
        const int tau = c >> 2, dg = c & 3;
        if (elect_one()) {
            if (warp == 12) {
                #pragma unroll 1
                for (int st = 1; st < 8; st++) {
                    const uint32_t s = st & 3, fb_ = bars + 8 * (B_FULLW + s);
                    if (st == 2) mbar_wait(bars + 8 * B_FULLW, 0);
                    mbar_wait(bars + 8 * (B_EMPTYW + s), (st >> 2) ^ 1);
                    mbar_expect(fb_, 16384);
                    tma2d(sb + OFF_W + s * 16384, &M.wg, 64 * fb, 64 * st, fb_);
                    tma2d(sb + OFF_W + s * 16384 + 8192, &M.wu, 64 * fb, 64 * st, fb_);
                }
                if (c < 128) {
                    #pragma unroll 1
                    for (int st = 0; st < 22; st++) {
                        const int sd = st & 7;
                        if (st < 8) mbar_wait(bars + 8 * (uint32_t)((0x282823070d060504ull >> (8 * st)) & 0xff), st < 5);
                        else mbar_wait(bars + 8 * (B_EMPTYD + sd), ((st >> 3) & 1) ^ 1);
                        const uint32_t da = sb + wd_slot(sd), fb_ = bars + 8 * (B_FULLD + sd);
                        mbar_expect(fb_, 16384);
                        tma2d(da, &M.wd, 128 * dg, 64 * st, fb_);
                        tma2d(da + 8192, &M.wd, 128 * dg + 64, 64 * st, fb_);
                    }
                }
            } else if (warp < 15) {
                const int V = warp - 13;
                #pragma unroll 1
                for (int st = 1 - V; st < 8; st++) {
                    const uint32_t s = 2 * V + (st & 1);
                    if (s == 3 && st == 1) mbar_wait(bars + 8 * B_LN, 0);
                    mbar_wait(bars + 8 * (B_EMPTYX + s), ((st >> 1) & 1) ^ 1);
                    mbar_expect(bars + 8 * (B_FULLX + s), (168 + 8 * V) * 128);
                    tma2d(sb + OFF_X + s * XBUF, &M.x[V], 64 * st, TOKG * tg + 168 * V, bars + 8 * (B_FULLX + s));
                }
                if (c < 128) {
                    if (V == 0) {
                        mbar_wait(bars + 8 * (B_STG + 1), 0);
                        #pragma unroll 1
                        for (int o = 8 * tau; o < 8 * tau + 8; o += 7) flag_wait(P.flags, F_H + 2 * (o / 43) + ((o % 43) >= 21), 22);
                        mbar_arrive(bars + 8 * B_HF);
                        STAMP(25);
                        #pragma unroll 1
                        for (int st = 0; st < 22; st++) {
                            const uint32_t fb_ = bars + 8 * (B_FULLD + (st & 7));
                            if (st == 6) mbar_wait(bars + 8 * B_SST, 0);
                            mbar_wait(bars + 8 * (B_EMPTYD + (st & 7)), ((st >> 3) & 1) ^ 1);
                            mbar_expect(fb_, 8192);
                            asm volatile("cp.async.bulk.tensor.5d.shared::cluster.global.mbarrier::complete_tx::bytes [%0], [%1, {%3, %3, %3, %4, %5}], [%2];"
                                :: "r"(sb + h_slot(st & 7)), "l"(&M.hld), "r"(fb_), "r"(0), "r"(2 * tau), "r"(8 * st) : "memory");
                        }
                    } else {
                        mbar_wait(bars + 8 * B_CH0, 0);
                        mbar_expect(bars + 8 * B_XO, 16384);
                        tma2d(sb + OFF_CONV, &M.xo, 128 * dg, 64 * tau, bars + 8 * B_XO);
                        tma2d(sb + OFF_CONV + 8192, &M.xo, 128 * dg + 64, 64 * tau, bars + 8 * B_XO);
                        flag_wait(P.flags, F_S + dg, 64);
                        STAMP(26);
                        mbar_arrive(bars + 8 * B_S);
                        mbar_wait(bars + 8 * B_HF, 0);
                        exit_count(P.flags);
                    }
                }
            } else {
                mbar_wait(bars + 8 * B_LN, 0);
                if (c < 128) {
                    #pragma unroll 1
                    for (int i = 0; i < 4; i++)
                        asm volatile("cp.async.bulk.tensor.2d.global.shared::cta.bulk_group [%0, {%2, %3}], [%1];"
                            :: "l"(&M.xt), "r"(sb + OFF_CONV + i * CH_STRIDE + CH_LNT), "r"((c & 1) * 1024 + (126 - (c & ~1)) * 8), "r"(128 * i) : "memory");
                    #pragma unroll 1
                    for (int i = 0; i < 2; i++) bulk_store(P.st + 16 * (c & ~1) + 8 * (c & 1) + 16 - 16 * i, sb + OFF_CSUM + 64 * i, 64);
                    asm volatile("cp.async.bulk.prefetch.L2.global [%0], %1;" :: "l"(P.Wd + c * (FF * DM / 128)), "r"(FF * DM / 64) : "memory");
                }
                flag_signal(P.flags, F_A);
                mbar_arrive(bars + 8 * B_LNS);
                flag_wait(P.flags, F_A, NCTA);
                STAMP(20);
                mbar_expect(bars + 8 * B_STATS, TOKG * 8);
                bulk_load(sb + OFF_ST, P.st + TOKG * tg, TOKG * 8, bars + 8 * B_STATS);
                if (c < 128) {
                    mbar_wait(bars + 8 * (B_K + 1), 0);
                    fence_async_smem();
                    mbar_expect(bars + 8 * B_U, 8 * 2048);
                    #pragma unroll 1
                    for (int i = 0; i < 8; i++)
                        bulk_load(sb + OFF_CONV + (i >> 1) * CH_STRIDE + CH_U + (i & 1) * UPLANE, P.xnT + 4 * c * 256 + i * 128, 2048, bars + 8 * B_U);
                } else exit_count(P.flags);
                #pragma unroll 1
                for (int V = 0; V < 2; V++) {
                    mbar_wait(bars + 8 * (B_EPI + V), 0);
                    asm volatile("cp.async.bulk.tensor.3d.global.shared::cta.bulk_group [%0, {%2, %3, %4}], [%1];"
                        :: "l"(&M.hst[V]), "r"(sb + OFF_X + V * 2 * XBUF), "r"(0), "r"(43 * tg + 21 * V), "r"(8 * fb) : "memory");
                    flag_signal(P.flags, F_H + 2 * tg + V);
                    mbar_arrive(bars + 8 * (B_STG + V));
                }
                if (c < 128) {
                    #pragma unroll 1
                    for (int V = 0; V < 2; V++) {
                        mbar_wait(bars + 8 * (B_SIG + V), 0);
                        bulk_store(P.S + (2 * c + V) * 1024, sb + OFF_CONV + (2 * V + 1) * CH_STRIDE, 8192);
                        flag_signal(P.flags, F_S + (c >> 5));
                    }
                    mbar_arrive(bars + 8 * B_SST);
                }
            }
        }
    }
}

typedef CUresult (*EncodeFn)(CUtensorMap*, CUtensorMapDataType, cuuint32_t, void*, const cuuint64_t*, const cuuint64_t*, const cuuint32_t*,
                             const cuuint32_t*, CUtensorMapInterleave, CUtensorMapSwizzle, CUtensorMapL2promotion, CUtensorMapFloatOOBfill);

void make_map(EncodeFn enc, CUtensorMap* m, const void* ptr, int rank, const cuuint64_t* dims, const cuuint64_t* strides, const cuuint32_t* box, bool swz) {
    const cuuint32_t es[5] = {1, 1, 1, 1, 1};
    enc(m, CU_TENSOR_MAP_DATA_TYPE_BFLOAT16, rank, (void*)ptr, dims, strides, box, es, CU_TENSOR_MAP_INTERLEAVE_NONE,
        swz ? CU_TENSOR_MAP_SWIZZLE_128B : CU_TENSOR_MAP_SWIZZLE_NONE, CU_TENSOR_MAP_L2_PROMOTION_L2_128B, CU_TENSOR_MAP_FLOAT_OOB_FILL_NONE);
}
void make_map2(EncodeFn enc, CUtensorMap* m, const void* ptr, cuuint64_t inner, cuuint64_t outer, cuuint32_t rows) {
    const cuuint64_t dims[2] = {inner, outer}, strides[1] = {inner * 2};
    const cuuint32_t box[2] = {64, rows};
    make_map(enc, m, ptr, 2, dims, strides, box, true);
}

}

extern "C" void kernel_launch(void* const* d_in, const int* in_sizes, int n_in, void* d_out, int out_size) {
    (void)in_sizes; (void)n_in; (void)out_size;
    static EncodeFn enc = nullptr;
    static void *hptr, *p_xnT, *p_st, *p_S, *p_flags;
    if (!enc) {
        cudaDriverEntryPointQueryResult qr;
        cudaGetDriverEntryPoint("cuTensorMapEncodeTiled", (void**)&enc, cudaEnableDefault, &qr);
        cudaFuncSetAttribute(fused_kernel, cudaFuncAttributeMaxDynamicSharedMemorySize, SMEM_BYTES);
        cudaGetSymbolAddress(&hptr, g_H); cudaGetSymbolAddress(&p_xnT, g_xnT); cudaGetSymbolAddress(&p_st, g_st);
        cudaGetSymbolAddress(&p_S, g_S); cudaGetSymbolAddress(&p_flags, g_flags);
    }
    Params P;
    P.x = (const __nv_bfloat16*)d_in[0]; P.logA = (const __nv_bfloat16*)d_in[1]; P.Aim = (const __nv_bfloat16*)d_in[2];
    P.Cr = (const __nv_bfloat16*)d_in[3]; P.Ci = (const __nv_bfloat16*)d_in[4]; P.logdt = (const __nv_bfloat16*)d_in[5];
    P.Dskip = (const __nv_bfloat16*)d_in[6];
    P.Wd = (const __nv_bfloat16*)d_in[10]; P.xnT = (uint4*)p_xnT; P.st = (float2*)p_st; P.S = (uint2*)p_S; P.flags = (unsigned*)p_flags;
    Maps M;
    make_map2(enc, &M.x[0], d_in[0], DM, SEQ, 168); make_map2(enc, &M.x[1], d_in[0], DM, SEQ, 176);
    make_map2(enc, &M.xo, d_in[0], DM, SEQ, 64);    make_map2(enc, &M.out, d_out, DM, SEQ, 64);
    make_map2(enc, &M.wg, d_in[8], FF, DM, 64);     make_map2(enc, &M.wu, d_in[9], FF, DM, 64);
    make_map2(enc, &M.wd, d_in[10], DM, FF, 64);
    for (int v = 0; v < 2; v++) {
        const cuuint64_t dims[3] = {64, 256, 172}, strides[2] = {128, 32768};
        const cuuint32_t box[3] = {64, (cuuint32_t)(21 + v), 8};
        make_map(enc, &M.hst[v], hptr, 3, dims, strides, box, false);
    }
    {
        const cuuint64_t dims[2] = {2048, 512}, strides[1] = {4096};
        const cuuint32_t box[2] = {16, 128};
        make_map(enc, &M.xt, p_xnT, 2, dims, strides, box, false);
    }
    {
        const cuuint64_t dims[5] = {64, 2, 2, 64, 172}, strides[4] = {256, 128, 512, 32768};
        const cuuint32_t box[5] = {64, 2, 2, 2, 8};
        make_map(enc, &M.hld, hptr, 5, dims, strides, box, false);
    }
    fused_kernel<<<NCTA, 512, SMEM_BYTES>>>(P, M);
}
```

```cpp
#include <cuda_runtime.h>
#include <cuda_bf16.h>
#include <cuda.h>
#include <stdint.h>

#define PROF 0

namespace {

constexpr int SEQ = 2048, DM = 512, FF = 1376;
constexpr int NCTA = 132;
#define HOLD0 2
#define HOLD1 4
#define LAG 2
constexpr int TOKG = 344;

constexpr uint32_t OFF_W = 0;
constexpr uint32_t XBUF = 22528;
constexpr uint32_t OFF_X = 65536;
constexpr uint32_t OFF_CONV = 155648;
constexpr uint32_t CH_STRIDE = 16640;
constexpr uint32_t CH_T = 0;
constexpr uint32_t CH_A3 = 6272;
constexpr uint32_t CH_B3 = 10368;
constexpr uint32_t CH_U = 12416;
constexpr uint32_t CH_G = CH_A3 + 2064;
constexpr uint32_t UPLANE = 2112;
constexpr uint32_t OFF_LN = OFF_X + 3 * XBUF;
constexpr uint32_t OFF_ST = 222208;
constexpr uint32_t OFF_CSUM = 230400;
constexpr uint32_t OFF_BAR = 231168;
constexpr uint32_t SMEM_BYTES = 231680;

enum {
    B_FULLW = 0, B_EMPTYW = 4, B_FULLX = 8, B_EMPTYX = 12, B_FULLD = 16, B_EMPTYD = 24,
    B_U = 32, B_XO = 33, B_S = 34, B_STG = 35, B_HF = 37, B_STATS = 38, B_LNS = 39, B_SST = 40,
    B_LNX = 41, B_GO = 42, B_CH0 = 43, B_K = 44,
    B_CONV = 46, B_LN = 50, B_CS = 51, B_EPI = 52, B_SIG = 54,
    B_COUNT = 56
};
enum { F_A = 0, F_H = 1, F_S = 13, F_EXIT = 17, F_COUNT = 18 };

__device__ uint4 g_xnT[DM * 256];
__device__ float2 g_st[6 * TOKG];
__device__ uint4 g_H[172 * 256 * 8];
__device__ uint2 g_S[256 * 1024];
__device__ unsigned g_flags[F_COUNT * 32];
#define STAMP(i) do {} while (0)
#define GSTAMP(i) do {} while (0)

__device__ __forceinline__ uint32_t smem_u32(const void* p) { return (uint32_t)__cvta_generic_to_shared(p); }
__device__ __forceinline__ void mbar_expect(uint32_t bar, uint32_t bytes) { asm volatile("mbarrier.arrive.expect_tx.shared::cta.b64 _, [%0], %1;" :: "r"(bar), "r"(bytes) : "memory"); }
__device__ __forceinline__ void mbar_arrive(uint32_t bar) { asm volatile("mbarrier.arrive.shared::cta.b64 _, [%0];" :: "r"(bar) : "memory"); }
__device__ __forceinline__ void mbar_wait(uint32_t bar, uint32_t parity) {
    asm volatile("{.reg .pred p; .reg .u32 n; mov.u32 n, 0x20000;\n"
                 "LW: mbarrier.try_wait.parity.shared::cta.b64 p, [%0], %1;\n"
                 "sub.u32 n, n, 1; setp.eq.or.u32 p, n, 0, p; @!p bra LW;}" :: "r"(bar), "r"(parity) : "memory");
}
__device__ __forceinline__ bool elect_one() { uint32_t p; asm volatile("{.reg .pred P; elect.sync _|P, 0xffffffff; selp.u32 %0, 1, 0, P;}" : "=r"(p)); return p; }
__device__ __forceinline__ void tma2d(uint32_t dst, const CUtensorMap* m, int c0, int c1, uint32_t bar) {
    asm volatile("cp.async.bulk.tensor.2d.shared::cluster.global.mbarrier::complete_tx::bytes [%0], [%1, {%3, %4}], [%2];"
        :: "r"(dst), "l"(m), "r"(bar), "r"(c0), "r"(c1) : "memory");
}
__device__ __forceinline__ void bulk_load(uint32_t dst, const void* src, uint32_t bytes, uint32_t bar) {
    asm volatile("cp.async.bulk.shared::cluster.global.mbarrier::complete_tx::bytes [%0], [%1], %2, [%3];" :: "r"(dst), "l"(src), "r"(bytes), "r"(bar) : "memory");
}
__device__ __forceinline__ void bulk_store(void* dst, uint32_t src, uint32_t bytes) {
    asm volatile("cp.async.bulk.global.shared::cta.bulk_group [%0], [%1], %2;" :: "l"(dst), "r"(src), "r"(bytes) : "memory");
}
__device__ __forceinline__ void fence_async_smem() { asm volatile("fence.proxy.async.shared::cta;" ::: "memory"); }
__device__ __forceinline__ void flag_wait(unsigned* g_flags, int f, unsigned target) {
    asm volatile("{.reg .pred p; .reg .u32 n, v; mov.u32 n, 0x40000;\n"
                 "LF: ld.acquire.gpu.global.u32 v, [%0]; setp.ge.u32 p, v, %1; @p bra LD;\n"
                 "nanosleep.u32 20; sub.u32 n, n, 1; setp.ne.u32 p, n, 0; @p bra LF; trap;\nLD: }"
                 :: "l"(g_flags + f * 32), "r"(target) : "memory");
}
__device__ __forceinline__ void flag_signal(unsigned* g_flags, int f) {
    asm volatile("cp.async.bulk.commit_group; cp.async.bulk.wait_group 0; red.relaxed.gpu.global.add.u32 [%0], 1;" :: "l"(g_flags + f * 32) : "memory");
}
__device__ __forceinline__ void exit_count(unsigned* g_flags) {
    if (atomicAdd(g_flags + F_EXIT * 32, 1u) == NCTA - 1) {
        #pragma unroll 1
        for (int i = 0; i < F_COUNT; i++) g_flags[i * 32] = 0;
    }
}
__device__ __forceinline__ void bar_sync(int id) { asm volatile("bar.sync %0, 128;" :: "r"(id) : "memory"); }
__device__ __forceinline__ uint64_t mkdesc(uint32_t addr, uint32_t lbo, uint32_t sbo, uint32_t swz) {
    return (uint64_t)((addr >> 4) | ((lbo >> 4) << 16)) | ((uint64_t)((sbo >> 4) | (swz << 30)) << 32);
}
#define WG_FENCE() asm volatile("wgmma.fence.sync.aligned;" ::: "memory")
#define WG_COMMIT() asm volatile("wgmma.commit_group.sync.aligned;" ::: "memory")
#define WG_WAIT(n) asm volatile("wgmma.wait_group.sync.aligned " #n ";" ::: "memory")
template <int N> __device__ __forceinline__ void fence_acc(float (&d)[N]) {
    #pragma unroll
    for (int i = 0; i < N; i++) asm volatile("" : "+f"(d[i]) :: "memory");
}
template <int N> __device__ __forceinline__ void define_acc(float (&d)[N]) {
    #pragma unroll
    for (int i = 0; i < N; i++) asm volatile("" : "=f"(d[i]));
}
__device__ __forceinline__ uint32_t pack2(float lo, float hi) { uint32_t r; asm("cvt.rn.bf16x2.f32 %0, %1, %2;" : "=r"(r) : "f"(hi), "f"(lo)); return r; }
__device__ __forceinline__ float bf_lo(uint32_t v) { return __uint_as_float(v << 16); }
__device__ __forceinline__ float bf_hi(uint32_t v) { return __uint_as_float(v & 0xffff0000u); }
__device__ __forceinline__ float bf_round(float v) { return bf_hi(pack2(0.f, v)); }
__device__ __forceinline__ float tanh_fast(float v) { float r; asm("tanh.approx.f32 %0, %1;" : "=f"(r) : "f"(v)); return r; }
__device__ __forceinline__ float ex2(float v) { float r; asm("ex2.approx.ftz.f32 %0, %1;" : "=f"(r) : "f"(v)); return r; }
__device__ __forceinline__ uint4 lds128(uint32_t a) { uint4 v; asm volatile("ld.shared.v4.b32 {%0,%1,%2,%3}, [%4];" : "=r"(v.x), "=r"(v.y), "=r"(v.z), "=r"(v.w) : "r"(a)); return v; }
__device__ __forceinline__ uint2 lds64(uint32_t a) { uint2 v; asm volatile("ld.shared.v2.b32 {%0,%1}, [%2];" : "=r"(v.x), "=r"(v.y) : "r"(a)); return v; }
__device__ __forceinline__ float ldsf(uint32_t a) { float v; asm volatile("ld.shared.f32 %0, [%1];" : "=f"(v) : "r"(a)); return v; }
__device__ __forceinline__ void sts128(uint32_t a, uint32_t x, uint32_t y, uint32_t z, uint32_t w) { asm volatile("st.shared.v4.b32 [%0], {%1,%2,%3,%4};" :: "r"(a), "r"(x), "r"(y), "r"(z), "r"(w) : "memory"); }
__device__ __forceinline__ void sts64(uint32_t a, uint32_t x, uint32_t y) { asm volatile("st.shared.v2.b32 [%0], {%1,%2};" :: "r"(a), "r"(x), "r"(y) : "memory"); }
__device__ __forceinline__ void stsf(uint32_t a, float x) { asm volatile("st.shared.f32 [%0], %1;" :: "r"(a), "f"(x) : "memory"); }
__device__ __forceinline__ void sts16(uint32_t a, uint32_t x) { asm volatile("st.shared.b16 [%0], %1;" :: "r"(a), "h"((unsigned short)x) : "memory"); }
__device__ __forceinline__ void stsm4(uint32_t a, uint32_t r0, uint32_t r1, uint32_t r2, uint32_t r3) {
    asm volatile("stmatrix.sync.aligned.m8n8.x4.shared.b16 [%0], {%1,%2,%3,%4};" :: "r"(a), "r"(r0), "r"(r1), "r"(r2), "r"(r3) : "memory");
}
#define FU(x) __float_as_uint(x)
#define UF(x) __uint_as_float(x)
__device__ __forceinline__ uint32_t wd_slot(int s) { return (uint32_t)((0xb9a9403056201000ull >> (8 * s)) & 0xff) << 10; }
__device__ __forceinline__ uint32_t h_slot(int s) { return (uint32_t)((0xd1c9d98c847c746cull >> (8 * s)) & 0xff) << 10; }

template<int N> __device__ __forceinline__ void wg_rs(float (&d)[64], uint32_t a0, uint32_t a1, uint32_t a2, uint32_t a3, uint64_t db);
template<> __device__ __forceinline__ void wg_rs<128>(float (&d)[64], uint32_t a0, uint32_t a1, uint32_t a2, uint32_t a3, uint64_t db) {
  asm volatile("{.reg .pred p; setp.ne.b32 p, 1, 0; wgmma.mma_async.sync.aligned.m64n128k16.f32.bf16.bf16 {%0,%1,%2,%3,%4,%5,%6,%7,%8,%9,%10,%11,%12,%13,%14,%15,%16,%17,%18,%19,%20,%21,%22,%23,%24,%25,%26,%27,%28,%29,%30,%31,%32,%33,%34,%35,%36,%37,%38,%39,%40,%41,%42,%43,%44,%45,%46,%47,%48,%49,%50,%51,%52,%53,%54,%55,%56,%57,%58,%59,%60,%61,%62,%63}, {%64,%65,%66,%67}, %68, p, 1, 1, 0;}"
    : "+f"(d[0]),"+f"(d[1]),"+f"(d[2]),"+f"(d[3]),"+f"(d[4]),"+f"(d[5]),"+f"(d[6]),"+f"(d[7]),"+f"(d[8]),"+f"(d[9]),"+f"(d[10]),"+f"(d[11]),"+f"(d[12]),"+f"(d[13]),"+f"(d[14]),"+f"(d[15]),"+f"(d[16]),"+f"(d[17]),"+f"(d[18]),"+f"(d[19]),"+f"(d[20]),"+f"(d[21]),"+f"(d[22]),"+f"(d[23]),"+f"(d[24]),"+f"(d[25]),"+f"(d[26]),"+f"(d[27]),"+f"(d[28]),"+f"(d[29]),"+f"(d[30]),"+f"(d[31]),"+f"(d[32]),"+f"(d[33]),"+f"(d[34]),"+f"(d[35]),"+f"(d[36]),"+f"(d[37]),"+f"(d[38]),"+f"(d[39]),"+f"(d[40]),"+f"(d[41]),"+f"(d[42]),"+f"(d[43]),"+f"(d[44]),"+f"(d[45]),"+f"(d[46]),"+f"(d[47]),"+f"(d[48]),"+f"(d[49]),"+f"(d[50]),"+f"(d[51]),"+f"(d[52]),"+f"(d[53]),"+f"(d[54]),"+f"(d[55]),"+f"(d[56]),"+f"(d[57]),"+f"(d[58]),"+f"(d[59]),"+f"(d[60]),"+f"(d[61]),"+f"(d[62]),"+f"(d[63]) : "r"(a0), "r"(a1), "r"(a2), "r"(a3), "l"(db));
}
template<> __device__ __forceinline__ void wg_rs<120>(float (&d)[64], uint32_t a0, uint32_t a1, uint32_t a2, uint32_t a3, uint64_t db) {
  asm volatile("{.reg .pred p; setp.ne.b32 p, 1, 0; wgmma.mma_async.sync.aligned.m64n120k16.f32.bf16.bf16 {%0,%1,%2,%3,%4,%5,%6,%7,%8,%9,%10,%11,%12,%13,%14,%15,%16,%17,%18,%19,%20,%21,%22,%23,%24,%25,%26,%27,%28,%29,%30,%31,%32,%33,%34,%35,%36,%37,%38,%39,%40,%41,%42,%43,%44,%45,%46,%47,%48,%49,%50,%51,%52,%53,%54,%55,%56,%57,%58,%59}, {%60,%61,%62,%63}, %64, p, 1, 1, 0;}"
    : "+f"(d[0]),"+f"(d[1]),"+f"(d[2]),"+f"(d[3]),"+f"(d[4]),"+f"(d[5]),"+f"(d[6]),"+f"(d[7]),"+f"(d[8]),"+f"(d[9]),"+f"(d[10]),"+f"(d[11]),"+f"(d[12]),"+f"(d[13]),"+f"(d[14]),"+f"(d[15]),"+f"(d[16]),"+f"(d[17]),"+f"(d[18]),"+f"(d[19]),"+f"(d[20]),"+f"(d[21]),"+f"(d[22]),"+f"(d[23]),"+f"(d[24]),"+f"(d[25]),"+f"(d[26]),"+f"(d[27]),"+f"(d[28]),"+f"(d[29]),"+f"(d[30]),"+f"(d[31]),"+f"(d[32]),"+f"(d[33]),"+f"(d[34]),"+f"(d[35]),"+f"(d[36]),"+f"(d[37]),"+f"(d[38]),"+f"(d[39]),"+f"(d[40]),"+f"(d[41]),"+f"(d[42]),"+f"(d[43]),"+f"(d[44]),"+f"(d[45]),"+f"(d[46]),"+f"(d[47]),"+f"(d[48]),"+f"(d[49]),"+f"(d[50]),"+f"(d[51]),"+f"(d[52]),"+f"(d[53]),"+f"(d[54]),"+f"(d[55]),"+f"(d[56]),"+f"(d[57]),"+f"(d[58]),"+f"(d[59]) : "r"(a0), "r"(a1), "r"(a2), "r"(a3), "l"(db));
}
template<> __device__ __forceinline__ void wg_rs<112>(float (&d)[64], uint32_t a0, uint32_t a1, uint32_t a2, uint32_t a3, uint64_t db) {
  asm volatile("{.reg .pred p; setp.ne.b32 p, 1, 0; wgmma.mma_async.sync.aligned.m64n112k16.f32.bf16.bf16 {%0,%1,%2,%3,%4,%5,%6,%7,%8,%9,%10,%11,%12,%13,%14,%15,%16,%17,%18,%19,%20,%21,%22,%23,%24,%25,%26,%27,%28,%29,%30,%31,%32,%33,%34,%35,%36,%37,%38,%39,%40,%41,%42,%43,%44,%45,%46,%47,%48,%49,%50,%51,%52,%53,%54,%55}, {%56,%57,%58,%59}, %60, p, 1, 1, 0;}"
    : "+f"(d[0]),"+f"(d[1]),"+f"(d[2]),"+f"(d[3]),"+f"(d[4]),"+f"(d[5]),"+f"(d[6]),"+f"(d[7]),"+f"(d[8]),"+f"(d[9]),"+f"(d[10]),"+f"(d[11]),"+f"(d[12]),"+f"(d[13]),"+f"(d[14]),"+f"(d[15]),"+f"(d[16]),"+f"(d[17]),"+f"(d[18]),"+f"(d[19]),"+f"(d[20]),"+f"(d[21]),"+f"(d[22]),"+f"(d[23]),"+f"(d[24]),"+f"(d[25]),"+f"(d[26]),"+f"(d[27]),"+f"(d[28]),"+f"(d[29]),"+f"(d[30]),"+f"(d[31]),"+f"(d[32]),"+f"(d[33]),"+f"(d[34]),"+f"(d[35]),"+f"(d[36]),"+f"(d[37]),"+f"(d[38]),"+f"(d[39]),"+f"(d[40]),"+f"(d[41]),"+f"(d[42]),"+f"(d[43]),"+f"(d[44]),"+f"(d[45]),"+f"(d[46]),"+f"(d[47]),"+f"(d[48]),"+f"(d[49]),"+f"(d[50]),"+f"(d[51]),"+f"(d[52]),"+f"(d[53]),"+f"(d[54]),"+f"(d[55]) : "r"(a0), "r"(a1), "r"(a2), "r"(a3), "l"(db));
}
template<> __device__ __forceinline__ void wg_rs<104>(float (&d)[64], uint32_t a0, uint32_t a1, uint32_t a2, uint32_t a3, uint64_t db) {
  asm volatile("{.reg .pred p; setp.ne.b32 p, 1, 0; wgmma.mma_async.sync.aligned.m64n104k16.f32.bf16.bf16 {%0,%1,%2,%3,%4,%5,%6,%7,%8,%9,%10,%11,%12,%13,%14,%15,%16,%17,%18,%19,%20,%21,%22,%23,%24,%25,%26,%27,%28,%29,%30,%31,%32,%33,%34,%35,%36,%37,%38,%39,%40,%41,%42,%43,%44,%45,%46,%47,%48,%49,%50,%51}, {%52,%53,%54,%55}, %56, p, 1, 1, 0;}"
    : "+f"(d[0]),"+f"(d[1]),"+f"(d[2]),"+f"(d[3]),"+f"(d[4]),"+f"(d[5]),"+f"(d[6]),"+f"(d[7]),"+f"(d[8]),"+f"(d[9]),"+f"(d[10]),"+f"(d[11]),"+f"(d[12]),"+f"(d[13]),"+f"(d[14]),"+f"(d[15]),"+f"(d[16]),"+f"(d[17]),"+f"(d[18]),"+f"(d[19]),"+f"(d[20]),"+f"(d[21]),"+f"(d[22]),"+f"(d[23]),"+f"(d[24]),"+f"(d[25]),"+f"(d[26]),"+f"(d[27]),"+f"(d[28]),"+f"(d[29]),"+f"(d[30]),"+f"(d[31]),"+f"(d[32]),"+f"(d[33]),"+f"(d[34]),"+f"(d[35]),"+f"(d[36]),"+f"(d[37]),"+f"(d[38]),"+f"(d[39]),"+f"(d[40]),"+f"(d[41]),"+f"(d[42]),"+f"(d[43]),"+f"(d[44]),"+f"(d[45]),"+f"(d[46]),"+f"(d[47]),"+f"(d[48]),"+f"(d[49]),"+f"(d[50]),"+f"(d[51]) : "r"(a0), "r"(a1), "r"(a2), "r"(a3), "l"(db));
}
template<> __device__ __forceinline__ void wg_rs<96>(float (&d)[64], uint32_t a0, uint32_t a1, uint32_t a2, uint32_t a3, uint64_t db) {
  asm volatile("{.reg .pred p; setp.ne.b32 p, 1, 0; wgmma.mma_async.sync.aligned.m64n96k16.f32.bf16.bf16 {%0,%1,%2,%3,%4,%5,%6,%7,%8,%9,%10,%11,%12,%13,%14,%15,%16,%17,%18,%19,%20,%21,%22,%23,%24,%25,%26,%27,%28,%29,%30,%31,%32,%33,%34,%35,%36,%37,%38,%39,%40,%41,%42,%43,%44,%45,%46,%47}, {%48,%49,%50,%51}, %52, p, 1, 1, 0;}"
    : "+f"(d[0]),"+f"(d[1]),"+f"(d[2]),"+f"(d[3]),"+f"(d[4]),"+f"(d[5]),"+f"(d[6]),"+f"(d[7]),"+f"(d[8]),"+f"(d[9]),"+f"(d[10]),"+f"(d[11]),"+f"(d[12]),"+f"(d[13]),"+f"(d[14]),"+f"(d[15]),"+f"(d[16]),"+f"(d[17]),"+f"(d[18]),"+f"(d[19]),"+f"(d[20]),"+f"(d[21]),"+f"(d[22]),"+f"(d[23]),"+f"(d[24]),"+f"(d[25]),"+f"(d[26]),"+f"(d[27]),"+f"(d[28]),"+f"(d[29]),"+f"(d[30]),"+f"(d[31]),"+f"(d[32]),"+f"(d[33]),"+f"(d[34]),"+f"(d[35]),"+f"(d[36]),"+f"(d[37]),"+f"(d[38]),"+f"(d[39]),"+f"(d[40]),"+f"(d[41]),"+f"(d[42]),"+f"(d[43]),"+f"(d[44]),"+f"(d[45]),"+f"(d[46]),"+f"(d[47]) : "r"(a0), "r"(a1), "r"(a2), "r"(a3), "l"(db));
}
template<> __device__ __forceinline__ void wg_rs<88>(float (&d)[64], uint32_t a0, uint32_t a1, uint32_t a2, uint32_t a3, uint64_t db) {
  asm volatile("{.reg .pred p; setp.ne.b32 p, 1, 0; wgmma.mma_async.sync.aligned.m64n88k16.f32.bf16.bf16 {%0,%1,%2,%3,%4,%5,%6,%7,%8,%9,%10,%11,%12,%13,%14,%15,%16,%17,%18,%19,%20,%21,%22,%23,%24,%25,%26,%27,%28,%29,%30,%31,%32,%33,%34,%35,%36,%37,%38,%39,%40,%41,%42,%43}, {%44,%45,%46,%47}, %48, p, 1, 1, 0;}"
    : "+f"(d[0]),"+f"(d[1]),"+f"(d[2]),"+f"(d[3]),"+f"(d[4]),"+f"(d[5]),"+f"(d[6]),"+f"(d[7]),"+f"(d[8]),"+f"(d[9]),"+f"(d[10]),"+f"(d[11]),"+f"(d[12]),"+f"(d[13]),"+f"(d[14]),"+f"(d[15]),"+f"(d[16]),"+f"(d[17]),"+f"(d[18]),"+f"(d[19]),"+f"(d[20]),"+f"(d[21]),"+f"(d[22]),"+f"(d[23]),"+f"(d[24]),"+f"(d[25]),"+f"(d[26]),"+f"(d[27]),"+f"(d[28]),"+f"(d[29]),"+f"(d[30]),"+f"(d[31]),"+f"(d[32]),"+f"(d[33]),"+f"(d[34]),"+f"(d[35]),"+f"(d[36]),"+f"(d[37]),"+f"(d[38]),"+f"(d[39]),"+f"(d[40]),"+f"(d[41]),"+f"(d[42]),"+f"(d[43]) : "r"(a0), "r"(a1), "r"(a2), "r"(a3), "l"(db));
}
template<> __device__ __forceinline__ void wg_rs<80>(float (&d)[64], uint32_t a0, uint32_t a1, uint32_t a2, uint32_t a3, uint64_t db) {
  asm volatile("{.reg .pred p; setp.ne.b32 p, 1, 0; wgmma.mma_async.sync.aligned.m64n80k16.f32.bf16.bf16 {%0,%1,%2,%3,%4,%5,%6,%7,%8,%9,%10,%11,%12,%13,%14,%15,%16,%17,%18,%19,%20,%21,%22,%23,%24,%25,%26,%27,%28,%29,%30,%31,%32,%33,%34,%35,%36,%37,%38,%39}, {%40,%41,%42,%43}, %44, p, 1, 1, 0;}"
    : "+f"(d[0]),"+f"(d[1]),"+f"(d[2]),"+f"(d[3]),"+f"(d[4]),"+f"(d[5]),"+f"(d[6]),"+f"(d[7]),"+f"(d[8]),"+f"(d[9]),"+f"(d[10]),"+f"(d[11]),"+f"(d[12]),"+f"(d[13]),"+f"(d[14]),"+f"(d[15]),"+f"(d[16]),"+f"(d[17]),"+f"(d[18]),"+f"(d[19]),"+f"(d[20]),"+f"(d[21]),"+f"(d[22]),"+f"(d[23]),"+f"(d[24]),"+f"(d[25]),"+f"(d[26]),"+f"(d[27]),"+f"(d[28]),"+f"(d[29]),"+f"(d[30]),"+f"(d[31]),"+f"(d[32]),"+f"(d[33]),"+f"(d[34]),"+f"(d[35]),"+f"(d[36]),"+f"(d[37]),"+f"(d[38]),"+f"(d[39]) : "r"(a0), "r"(a1), "r"(a2), "r"(a3), "l"(db));
}
template<> __device__ __forceinline__ void wg_rs<72>(float (&d)[64], uint32_t a0, uint32_t a1, uint32_t a2, uint32_t a3, uint64_t db) {
  asm volatile("{.reg .pred p; setp.ne.b32 p, 1, 0; wgmma.mma_async.sync.aligned.m64n72k16.f32.bf16.bf16 {%0,%1,%2,%3,%4,%5,%6,%7,%8,%9,%10,%11,%12,%13,%14,%15,%16,%17,%18,%19,%20,%21,%22,%23,%24,%25,%26,%27,%28,%29,%30,%31,%32,%33,%34,%35}, {%36,%37,%38,%39}, %40, p, 1, 1, 0;}"
    : "+f"(d[0]),"+f"(d[1]),"+f"(d[2]),"+f"(d[3]),"+f"(d[4]),"+f"(d[5]),"+f"(d[6]),"+f"(d[7]),"+f"(d[8]),"+f"(d[9]),"+f"(d[10]),"+f"(d[11]),"+f"(d[12]),"+f"(d[13]),"+f"(d[14]),"+f"(d[15]),"+f"(d[16]),"+f"(d[17]),"+f"(d[18]),"+f"(d[19]),"+f"(d[20]),"+f"(d[21]),"+f"(d[22]),"+f"(d[23]),"+f"(d[24]),"+f"(d[25]),"+f"(d[26]),"+f"(d[27]),"+f"(d[28]),"+f"(d[29]),"+f"(d[30]),"+f"(d[31]),"+f"(d[32]),"+f"(d[33]),"+f"(d[34]),"+f"(d[35]) : "r"(a0), "r"(a1), "r"(a2), "r"(a3), "l"(db));
}
template<> __device__ __forceinline__ void wg_rs<64>(float (&d)[64], uint32_t a0, uint32_t a1, uint32_t a2, uint32_t a3, uint64_t db) {
  asm volatile("{.reg .pred p; setp.ne.b32 p, 1, 0; wgmma.mma_async.sync.aligned.m64n64k16.f32.bf16.bf16 {%0,%1,%2,%3,%4,%5,%6,%7,%8,%9,%10,%11,%12,%13,%14,%15,%16,%17,%18,%19,%20,%21,%22,%23,%24,%25,%26,%27,%28,%29,%30,%31}, {%32,%33,%34,%35}, %36, p, 1, 1, 0;}"
    : "+f"(d[0]),"+f"(d[1]),"+f"(d[2]),"+f"(d[3]),"+f"(d[4]),"+f"(d[5]),"+f"(d[6]),"+f"(d[7]),"+f"(d[8]),"+f"(d[9]),"+f"(d[10]),"+f"(d[11]),"+f"(d[12]),"+f"(d[13]),"+f"(d[14]),"+f"(d[15]),"+f"(d[16]),"+f"(d[17]),"+f"(d[18]),"+f"(d[19]),"+f"(d[20]),"+f"(d[21]),"+f"(d[22]),"+f"(d[23]),"+f"(d[24]),"+f"(d[25]),"+f"(d[26]),"+f"(d[27]),"+f"(d[28]),"+f"(d[29]),"+f"(d[30]),"+f"(d[31]) : "r"(a0), "r"(a1), "r"(a2), "r"(a3), "l"(db));
}
__device__ __forceinline__ void wg_rs_first(float (&d)[64], uint32_t a0, uint32_t a1, uint32_t a2, uint32_t a3, uint64_t db) {
  asm volatile("{.reg .pred p; setp.ne.b32 p, 0, 0; wgmma.mma_async.sync.aligned.m64n128k16.f32.bf16.bf16 {%0,%1,%2,%3,%4,%5,%6,%7,%8,%9,%10,%11,%12,%13,%14,%15,%16,%17,%18,%19,%20,%21,%22,%23,%24,%25,%26,%27,%28,%29,%30,%31,%32,%33,%34,%35,%36,%37,%38,%39,%40,%41,%42,%43,%44,%45,%46,%47,%48,%49,%50,%51,%52,%53,%54,%55,%56,%57,%58,%59,%60,%61,%62,%63}, {%64,%65,%66,%67}, %68, p, 1, 1, 0;}"
    : "=f"(d[0]),"=f"(d[1]),"=f"(d[2]),"=f"(d[3]),"=f"(d[4]),"=f"(d[5]),"=f"(d[6]),"=f"(d[7]),"=f"(d[8]),"=f"(d[9]),"=f"(d[10]),"=f"(d[11]),"=f"(d[12]),"=f"(d[13]),"=f"(d[14]),"=f"(d[15]),"=f"(d[16]),"=f"(d[17]),"=f"(d[18]),"=f"(d[19]),"=f"(d[20]),"=f"(d[21]),"=f"(d[22]),"=f"(d[23]),"=f"(d[24]),"=f"(d[25]),"=f"(d[26]),"=f"(d[27]),"=f"(d[28]),"=f"(d[29]),"=f"(d[30]),"=f"(d[31]),"=f"(d[32]),"=f"(d[33]),"=f"(d[34]),"=f"(d[35]),"=f"(d[36]),"=f"(d[37]),"=f"(d[38]),"=f"(d[39]),"=f"(d[40]),"=f"(d[41]),"=f"(d[42]),"=f"(d[43]),"=f"(d[44]),"=f"(d[45]),"=f"(d[46]),"=f"(d[47]),"=f"(d[48]),"=f"(d[49]),"=f"(d[50]),"=f"(d[51]),"=f"(d[52]),"=f"(d[53]),"=f"(d[54]),"=f"(d[55]),"=f"(d[56]),"=f"(d[57]),"=f"(d[58]),"=f"(d[59]),"=f"(d[60]),"=f"(d[61]),"=f"(d[62]),"=f"(d[63]) : "r"(a0), "r"(a1), "r"(a2), "r"(a3), "l"(db));
}
__device__ __forceinline__ void wg_tt128(float (&d)[64], uint64_t da, uint64_t db, int sc) {
  asm volatile("{.reg .pred p; setp.ne.b32 p, %66, 0; wgmma.mma_async.sync.aligned.m64n128k16.f32.bf16.bf16 {%0,%1,%2,%3,%4,%5,%6,%7,%8,%9,%10,%11,%12,%13,%14,%15,%16,%17,%18,%19,%20,%21,%22,%23,%24,%25,%26,%27,%28,%29,%30,%31,%32,%33,%34,%35,%36,%37,%38,%39,%40,%41,%42,%43,%44,%45,%46,%47,%48,%49,%50,%51,%52,%53,%54,%55,%56,%57,%58,%59,%60,%61,%62,%63}, %64, %65, p, 1, 1, 1, 1;}"
    : "+f"(d[0]),"+f"(d[1]),"+f"(d[2]),"+f"(d[3]),"+f"(d[4]),"+f"(d[5]),"+f"(d[6]),"+f"(d[7]),"+f"(d[8]),"+f"(d[9]),"+f"(d[10]),"+f"(d[11]),"+f"(d[12]),"+f"(d[13]),"+f"(d[14]),"+f"(d[15]),"+f"(d[16]),"+f"(d[17]),"+f"(d[18]),"+f"(d[19]),"+f"(d[20]),"+f"(d[21]),"+f"(d[22]),"+f"(d[23]),"+f"(d[24]),"+f"(d[25]),"+f"(d[26]),"+f"(d[27]),"+f"(d[28]),"+f"(d[29]),"+f"(d[30]),"+f"(d[31]),"+f"(d[32]),"+f"(d[33]),"+f"(d[34]),"+f"(d[35]),"+f"(d[36]),"+f"(d[37]),"+f"(d[38]),"+f"(d[39]),"+f"(d[40]),"+f"(d[41]),"+f"(d[42]),"+f"(d[43]),"+f"(d[44]),"+f"(d[45]),"+f"(d[46]),"+f"(d[47]),"+f"(d[48]),"+f"(d[49]),"+f"(d[50]),"+f"(d[51]),"+f"(d[52]),"+f"(d[53]),"+f"(d[54]),"+f"(d[55]),"+f"(d[56]),"+f"(d[57]),"+f"(d[58]),"+f"(d[59]),"+f"(d[60]),"+f"(d[61]),"+f"(d[62]),"+f"(d[63]) : "l"(da), "l"(db), "r"(sc));
}
__device__ __forceinline__ void wg_tt64(float (&d)[64], uint64_t da, uint64_t db, int sc) {
  asm volatile("{.reg .pred p; setp.ne.b32 p, %34, 0; wgmma.mma_async.sync.aligned.m64n64k16.f32.bf16.bf16 {%0,%1,%2,%3,%4,%5,%6,%7,%8,%9,%10,%11,%12,%13,%14,%15,%16,%17,%18,%19,%20,%21,%22,%23,%24,%25,%26,%27,%28,%29,%30,%31}, %32, %33, p, 1, 1, 1, 1;}"
    : "+f"(d[0]),"+f"(d[1]),"+f"(d[2]),"+f"(d[3]),"+f"(d[4]),"+f"(d[5]),"+f"(d[6]),"+f"(d[7]),"+f"(d[8]),"+f"(d[9]),"+f"(d[10]),"+f"(d[11]),"+f"(d[12]),"+f"(d[13]),"+f"(d[14]),"+f"(d[15]),"+f"(d[16]),"+f"(d[17]),"+f"(d[18]),"+f"(d[19]),"+f"(d[20]),"+f"(d[21]),"+f"(d[22]),"+f"(d[23]),"+f"(d[24]),"+f"(d[25]),"+f"(d[26]),"+f"(d[27]),"+f"(d[28]),"+f"(d[29]),"+f"(d[30]),"+f"(d[31]) : "l"(da), "l"(db), "r"(sc));
}
__device__ __forceinline__ void wg_tt32(float (&d)[64], uint64_t da, uint64_t db, int sc) {
  asm volatile("{.reg .pred p; setp.ne.b32 p, %18, 0; wgmma.mma_async.sync.aligned.m64n32k16.f32.bf16.bf16 {%0,%1,%2,%3,%4,%5,%6,%7,%8,%9,%10,%11,%12,%13,%14,%15}, %16, %17, p, 1, 1, 1, 1;}"
    : "+f"(d[0]),"+f"(d[1]),"+f"(d[2]),"+f"(d[3]),"+f"(d[4]),"+f"(d[5]),"+f"(d[6]),"+f"(d[7]),"+f"(d[8]),"+f"(d[9]),"+f"(d[10]),"+f"(d[11]),"+f"(d[12]),"+f"(d[13]),"+f"(d[14]),"+f"(d[15]) : "l"(da), "l"(db), "r"(sc));
}
__device__ __forceinline__ void wg_g1(float (&d)[88], uint64_t da, uint64_t db, int sc) {
  asm volatile("{.reg .pred p; setp.ne.b32 p, %90, 0; wgmma.mma_async.sync.aligned.m64n176k16.f32.bf16.bf16 {%0,%1,%2,%3,%4,%5,%6,%7,%8,%9,%10,%11,%12,%13,%14,%15,%16,%17,%18,%19,%20,%21,%22,%23,%24,%25,%26,%27,%28,%29,%30,%31,%32,%33,%34,%35,%36,%37,%38,%39,%40,%41,%42,%43,%44,%45,%46,%47,%48,%49,%50,%51,%52,%53,%54,%55,%56,%57,%58,%59,%60,%61,%62,%63,%64,%65,%66,%67,%68,%69,%70,%71,%72,%73,%74,%75,%76,%77,%78,%79,%80,%81,%82,%83,%84,%85,%86,%87}, %88, %89, p, 1, 1, 1, 0;}"
    : "+f"(d[0]),"+f"(d[1]),"+f"(d[2]),"+f"(d[3]),"+f"(d[4]),"+f"(d[5]),"+f"(d[6]),"+f"(d[7]),"+f"(d[8]),"+f"(d[9]),"+f"(d[10]),"+f"(d[11]),"+f"(d[12]),"+f"(d[13]),"+f"(d[14]),"+f"(d[15]),"+f"(d[16]),"+f"(d[17]),"+f"(d[18]),"+f"(d[19]),"+f"(d[20]),"+f"(d[21]),"+f"(d[22]),"+f"(d[23]),"+f"(d[24]),"+f"(d[25]),"+f"(d[26]),"+f"(d[27]),"+f"(d[28]),"+f"(d[29]),"+f"(d[30]),"+f"(d[31]),"+f"(d[32]),"+f"(d[33]),"+f"(d[34]),"+f"(d[35]),"+f"(d[36]),"+f"(d[37]),"+f"(d[38]),"+f"(d[39]),"+f"(d[40]),"+f"(d[41]),"+f"(d[42]),"+f"(d[43]),"+f"(d[44]),"+f"(d[45]),"+f"(d[46]),"+f"(d[47]),"+f"(d[48]),"+f"(d[49]),"+f"(d[50]),"+f"(d[51]),"+f"(d[52]),"+f"(d[53]),"+f"(d[54]),"+f"(d[55]),"+f"(d[56]),"+f"(d[57]),"+f"(d[58]),"+f"(d[59]),"+f"(d[60]),"+f"(d[61]),"+f"(d[62]),"+f"(d[63]),"+f"(d[64]),"+f"(d[65]),"+f"(d[66]),"+f"(d[67]),"+f"(d[68]),"+f"(d[69]),"+f"(d[70]),"+f"(d[71]),"+f"(d[72]),"+f"(d[73]),"+f"(d[74]),"+f"(d[75]),"+f"(d[76]),"+f"(d[77]),"+f"(d[78]),"+f"(d[79]),"+f"(d[80]),"+f"(d[81]),"+f"(d[82]),"+f"(d[83]),"+f"(d[84]),"+f"(d[85]),"+f"(d[86]),"+f"(d[87]) : "l"(da), "l"(db), "r"(sc));
}

struct Params { const __nv_bfloat16 *x, *logA, *Aim, *Cr, *Ci, *logdt, *Dskip, *Wd; uint4* xnT; float2* st; uint2* S; unsigned* flags; };
struct Maps { CUtensorMap x[2], xo, out, wg, wu, wd, hst[2], hld, xt; };

__device__ __forceinline__ void conv_channel(uint32_t cb, int w, int lane, uint32_t (&res)[8], uint32_t bar_free) {
    const int q = lane & 3, g = lane >> 2, gam = g >> 2;
    float acc[64];
    uint4 a[4][4];
    const uint32_t t0 = cb + CH_T + (uint32_t)(14 + 4 * w + (g & 3) + 32 * gam - 2 * q) * 80u;
    #pragma unroll
    for (int s4 = 0; s4 < 4; s4++) {
        a[s4][0] = lds128(t0 + s4 * 16);
        a[s4][1] = lds128(t0 + 16 * 80 + s4 * 16);
        a[s4][2] = lds128(t0 - 8 * 80 + s4 * 16);
        a[s4][3] = lds128(t0 + 8 * 80 + s4 * 16);
    }
    const uint32_t l0 = FU(ldsf(t0 + 64)), l1 = FU(ldsf(t0 + 16 * 80 + 64)), l2 = FU(ldsf(t0 - 8 * 80 + 64)), l3 = FU(ldsf(t0 + 8 * 80 + 64));
    const uint64_t dU = mkdesc(cb + CH_U, UPLANE, 128, 0);
    WG_FENCE();
#define CT(N, s, c) wg_rs<N>(acc, a[(s) >> 2][0].c, a[(s) >> 2][1].c, a[(s) >> 2][2].c, a[(s) >> 2][3].c, dU + 4 * (s))
    wg_rs_first(acc, a[0][0].x, a[0][1].x, a[0][2].x, a[0][3].x, dU);
    CT(128, 1, y); CT(120, 2, z); CT(120, 3, w);
    CT(112, 4, x); CT(112, 5, y); CT(104, 6, z); CT(104, 7, w);
    CT(96, 8, x);  CT(96, 9, y);  CT(88, 10, z); CT(88, 11, w);
    CT(80, 12, x); CT(80, 13, y); CT(72, 14, z); CT(72, 15, w);
#undef CT
    wg_rs<64>(acc, l0, l1, l2, l3, dU + 64);
    wg_tt64(acc, mkdesc(cb + CH_A3, 128, 512, 0), mkdesc(cb + CH_B3, 128, 256, 0), 1);
    wg_tt32(acc, mkdesc(cb + CH_A3 + 256, 128, 512, 0), mkdesc(cb + CH_B3 + 1024, 128, 256, 0), 1);
    WG_COMMIT();
    WG_WAIT(0);
    fence_acc(acc);
    if (bar_free && lane == 0) mbar_arrive(bar_free);
    const int src1 = (lane & ~3) | ((q + 1) & 3);
    float E[16][2];
    #pragma unroll
    for (int j = 0; j < 16; j++) {
        const float nxt = (j < 15) ? acc[4 * (j + 1) + 2] : 0.f;
        const float sup = (q == 0) ? nxt : acc[4 * j + 2];
        const float v = __shfl_sync(0xffffffffu, sup, src1);
        E[j][0] = acc[4 * j] + acc[4 * j + 3];
        E[j][1] = acc[4 * j + 1] + v;
    }
    const int src2 = gam ? ((lane & 12) | ((q + 3) & 3)) : (16 | (lane & 12) | ((q + 1) & 3));
    const bool c1 = gam && q != 0, c2 = gam && q == 0;
    #pragma unroll
    for (int a2 = 0; a2 < 8; a2++) {
        float y[2];
        #pragma unroll
        for (int e = 0; e < 2; e++) {
            const float sup = c1 ? E[2 * a2][e] : E[2 * a2 + 1][e];
            const float nxt = (a2 < 7) ? E[2 * a2 + 2][e] : 0.f;
            const float keep = c2 ? nxt : (c1 ? E[2 * a2 + 1][e] : E[2 * a2][e]);
            y[e] = keep + __shfl_sync(0xffffffffu, sup, src2);
        }
        res[a2] = pack2(y[1], y[0]);
    }
}

__device__ __forceinline__ void layer_norm(uint32_t sb, int w, int lane, const __nv_bfloat16* x) {
    const uint32_t bars = sb + OFF_BAR;
    const int c = blockIdx.x;
    {
        if (elect_one()) {
            mbar_expect(bars + 8 * B_LNX, 4096);
            #pragma unroll
            for (int i = 0; i < 4; i++)
                bulk_load(sb + OFF_LN + (w + 4 * i) * 1040, x + (16 * (c & ~1) + 8 * (c & 1) + 16 + w + 4 * (i & 1) - 8 * (i & 2)) * DM, 1024, bars + 8 * B_LNX);
        }
        mbar_wait(bars + 8 * B_LNX, 0);
        STAMP(34);
        {
            const int r = w + 4 * (lane >> 3);
            const uint32_t r0 = sb + OFF_LN + r * 1040, ra = r0 + (lane & 7) * 16;
            const float pv = bf_lo(FU(ldsf(r0)));
            float s0 = 0.f, s1 = 0.f, a0 = 0.f, a1 = 0.f;
            uint4 nx = lds128(ra);
            #pragma unroll 1
            for (int k = 128; k <= 1024; k += 128) {
                const uint32_t v[4] = {nx.x, nx.y, nx.z, nx.w};
                nx = lds128(ra + (k & 1023));
                #pragma unroll
                for (int i = 0; i < 4; i++) { const float t0 = bf_lo(v[i]) - pv, t1 = bf_hi(v[i]) - pv; s0 += t0; s1 += t1; a0 = fmaf(t0, t0, a0); a1 = fmaf(t1, t1, a1); }
            }
            s0 += s1; a0 += a1;
            #pragma unroll
            for (int o = 4; o; o >>= 1) { s0 += __shfl_xor_sync(0xffffffffu, s0, o); a0 += __shfl_xor_sync(0xffffffffu, a0, o); }
            s0 *= 1.f / DM;
            const float m = pv + s0, var = fmaxf(fmaf(-s0, s0, a0 * (1.f / DM)), 0.f);
            float sd, ri;
            asm("sqrt.approx.ftz.f32 %0, %1;" : "=f"(sd) : "f"(bf_round(bf_round(var) + 1e-5f)));
            asm("rcp.approx.ftz.f32 %0, %1;" : "=f"(ri) : "f"(bf_round(sd)));
            const uint32_t m2 = pack2(m, m);
            if ((lane & 7) == 0) {
                sts64(sb + OFF_CSUM + r * 8, m2 & 0xffff0000u, FU(0.5f * ri));
            }
            #pragma unroll 1
            for (int k = 128; k <= 1024; k += 128) {
                uint32_t v[4] = {nx.x, nx.y, nx.z, nx.w};
                nx = lds128(ra + (k & 1023));
                #pragma unroll
                for (int i = 0; i < 4; i++) {
                    uint32_t dv; asm("sub.rn.bf16x2 %0, %1, %2;" : "=r"(dv) : "r"(v[i]), "r"(m2));
                    v[i] = pack2(bf_lo(dv) * ri, bf_hi(dv) * ri);
                }
                sts128(ra + k - 128, v[0], v[1], v[2], v[3]);
            }
        }
        STAMP(62);
        bar_sync(4);
        {
            const uint32_t ad = sb + OFF_LN + (4 * ((lane & 7) >> 1) + (lane & 1) + 2 * ((lane >> 3) & 1)) * 1040 + (16 * w + (lane >> 4)) * 16;
            uint32_t r[8][4];
            #pragma unroll
            for (int i = 0; i < 8; i++)
                asm volatile("ldmatrix.sync.aligned.m8n8.x4.trans.shared.b16 {%0,%1,%2,%3}, [%4];" : "=r"(r[i][0]), "=r"(r[i][1]), "=r"(r[i][2]), "=r"(r[i][3]) : "r"(ad + 32 * i) : "memory");
            bar_sync(4);
            const uint32_t od = sb + OFF_LN + w * 4096 + lane * 8;
            #pragma unroll
            for (int i = 0; i < 8; i++) { sts64(od + i * 512, r[i][0], r[i][1]); sts64(od + i * 512 + 256, r[i][2], r[i][3]); }
        }
        fence_async_smem();
        mbar_arrive(bars + 8 * B_LN);
        STAMP(16);
    }
}

__device__ __forceinline__ void consumer(uint32_t sb, int warp, const Params& P, const Maps& M) {
    const int V = warp >> 2, w = warp & 3, lane = threadIdx.x & 31, q = lane & 3, g = lane >> 2;
    const int c = blockIdx.x;
    const uint32_t bars = sb + OFF_BAR, xb = sb + OFF_X + V * 2 * XBUF;
    {
        float ag[88], au[88];
        if (V == 0) {
            sts128(xb + (w >> 1) * XBUF + 168 * 128 + (threadIdx.x & 63) * 16, 0x3f803f80u, 0x3f803f80u, 0x3f803f80u, 0x3f803f80u);
            fence_async_smem();
            bar_sync(1);
        } else {
            if (c < 128) layer_norm(sb, w, lane, P.x); else mbar_arrive(bars + 8 * B_LN);
            mbar_wait(bars + 8 * B_GO, 0);
        }
        define_acc(ag); define_acc(au);
        #pragma unroll 1
        for (int st = 0; st < 8; st++) {
            if (st + LAG * V == HOLD0 || st + LAG * V == HOLD1) mbar_wait(bars + 8 * (B_K + (st + LAG * V == HOLD1)), 0);
            mbar_wait(bars + 8 * (B_FULLW + (st & 3)), st >> 2);
            mbar_wait(bars + 8 * (B_FULLX + 2 * V + (st & 1)), (st >> 1) & 1);
            STAMP(40 + 8 * V + st);
            const uint64_t dG = mkdesc(sb + OFF_W + (st & 3) * 16384, 0, 1024, 1);
            const uint64_t dX = mkdesc(xb + (st & 1) * XBUF, 16, 1024, 1);
            WG_FENCE();
            #pragma unroll
            for (int k = 0; k < 4; k++) {
                wg_g1(ag, dG + k * 128, dX + k * 2, k ? 1 : st);
                wg_g1(au, dG + 512 + k * 128, dX + k * 2, k ? 1 : st);
            }
            WG_COMMIT();
            WG_WAIT(1);
            if (lane == 0 && st > 0) {
                mbar_arrive(bars + 8 * (B_EMPTYW + ((st - 1) & 3)));
                mbar_arrive(bars + 8 * (B_EMPTYX + 2 * V + ((st - 1) & 1)));
                if (warp < 4 && st == LAG) mbar_arrive(bars + 8 * B_GO);
            }
        }
        WG_WAIT(0);
        fence_acc(ag); fence_acc(au);
        if (lane == 0) { mbar_arrive(bars + 8 * (B_EMPTYW + 3)); mbar_arrive(bars + 8 * (B_EMPTYX + 2 * V + 1)); }
        STAMP(8 * V + 1);
        float cg0 = ag[84], cg1 = ag[86], cu0 = au[84], cu1 = au[86];
        const uint32_t ca = sb + OFF_CSUM + (8 * w + g) * 16;
        if (V == 0) { sts128(ca, FU(cg0), FU(cg1), FU(cu0), FU(cu1)); mbar_arrive(bars + 8 * B_CS); }
        else { mbar_wait(bars + 8 * B_CS, 0); const uint4 t = lds128(ca); cg0 = UF(t.x); cg1 = UF(t.y); cu0 = UF(t.z); cu1 = UF(t.w); }
        mbar_wait(bars + 8 * B_STATS, 0);
        mbar_wait(bars + 8 * (B_EMPTYX + 2 * V), 1);
        STAMP(13 + V);
        const uint32_t hs = xb + (2 * w + ((lane >> 3) & 1)) * (2688 + 128 * V) + (lane >> 4) * 128 + (lane & 7) * 16;
        const uint32_t sa = sb + OFF_ST + (168 * V + 2 * q) * 8;
        #pragma unroll
        for (int j = 0; j < 22; j += 2) {
            uint32_t o[4];
            #pragma unroll
            for (int jj = 0; jj < 2; jj++) {
                const uint4 sv = lds128(sa + (j + jj) * 64);
                float hv[4];
                #pragma unroll
                for (int i = 0; i < 4; i++) {
                    const float m = UF((i & 1) ? sv.z : sv.x);
                    const float gh = fmaf(-m, (i & 2) ? cg1 : cg0, ag[4 * (j + jj) + i]) * UF((i & 1) ? sv.w : sv.y);
                    const float p = gh * fmaf(-m, (i & 2) ? cu1 : cu0, au[4 * (j + jj) + i]);
                    hv[i] = fmaf(p, tanh_fast(gh), p);
                }
                o[2 * jj] = pack2(hv[0], hv[1]); o[2 * jj + 1] = pack2(hv[2], hv[3]);
            }
            uint32_t ad = hs + j * 128;
            if (j == 20 && V == 0 && lane >= 16) ad = xb + 21504 + (lane & 7) * 16;
            stsm4(ad, o[0], o[1], o[2], o[3]);
        }
        fence_async_smem();
        mbar_arrive(bars + 8 * (B_EPI + V));
        STAMP(8 * V + 2);
    }
    if (c >= 128) return;
    {
        uint32_t r0[8], r1[8];
        #pragma unroll
        for (int i = 0; i < 8; i++) asm volatile("" : "=r"(r1[i]));
        #pragma unroll 1
        for (int e = 0; e < 2; e++) {
            #pragma unroll
            for (int i = 0; i < 8; i++) r0[i] = r1[i];
            mbar_wait(bars + 8 * (B_CONV + 2 * V + e), 0);
            conv_channel(sb + OFF_CONV + (2 * V + e) * CH_STRIDE, w, lane, r1, (V + e == 0) ? bars + 8 * B_CH0 : 0);
            if (e == 0) STAMP(8 * V + 3);
        }
        const int gam = g >> 2, qq = gam ? ((q + 3) & 3) : q;
        const uint32_t sp = sb + OFF_CONV + (2 * V + 1) * CH_STRIDE + ((63 - 4 * gam - qq) * 16 + 4 * w + (g & 3)) * 8;
        bar_sync(3 + V);
        #pragma unroll
        for (int a2 = 0; a2 < 8; a2++) sts64(sp - a2 * 1024, r0[a2], r1[a2]);
        fence_async_smem();
        mbar_arrive(bars + 8 * (B_SIG + V));
        STAMP(8 * V + 4);
    }
    if (V == 1) return;
    {
        const int tau = c >> 2, dg = c & 3;
        const uint32_t row = 8 * (w & 1) + 32 * (w >> 1);
        float acc[64];
        define_acc(acc);
        uint2 sv[16];
        #pragma unroll
        for (int i = 0; i < 16; i++) asm volatile("" : "=r"(sv[i].x), "=r"(sv[i].y));
        const float rr0 = __ldcg(&P.st[64 * tau + row + g].y), rr1 = __ldcg(&P.st[64 * tau + row + g + 16].y);
        mbar_wait(bars + 8 * B_FULLD, 0);
        STAMP(5);
        uint64_t dB = mkdesc(sb + wd_slot(0), 8192, 1024, 1), dA = mkdesc(sb + h_slot(0), 1024, 128, 0);
        #pragma unroll 1
        for (int st = 0; st < 21; st++) {
            WG_FENCE();
            wg_tt128(acc, dA, dB, st);
            wg_tt128(acc, dA + 128, dB + 128, 1);
            wg_tt128(acc, dA + 256, dB + 256, 1);
            wg_tt128(acc, dA + 384, dB + 384, 1);
            WG_COMMIT();
            const int sd = (st + 1) & 7;
            const uint32_t nb = bars + 8 * (B_FULLD + sd), np = ((st + 1) >> 3) & 1;
            uint32_t ok;
            asm volatile("{.reg .pred p; mbarrier.test_wait.parity.shared::cta.b64 p, [%1], %2; selp.u32 %0, 1, 0, p;}" : "=r"(ok) : "r"(nb), "r"(np) : "memory");
            dB = mkdesc(sb + wd_slot(sd), 8192, 1024, 1); dA = mkdesc(sb + h_slot(sd), 1024, 128, 0);
            if (st == 14) {
                mbar_wait(bars + 8 * B_S, 0);
                const uint2* sp = P.S + (dg * 64 + q) * 1024 + (2 * tau) * 16 + (row >> 1) + 4 * (w & 1) + g;
                #pragma unroll
                for (int j = 0; j < 16; j++)
                    asm volatile("ld.global.cg.v2.b32 {%0,%1}, [%2];" : "=r"(sv[j].x), "=r"(sv[j].y) : "l"(sp + j * 4096));
            }
            WG_WAIT(1);
            if (lane == 0 && st > 0) mbar_arrive(bars + 8 * (B_EMPTYD + ((st - 1) & 7)));
            if (!ok) mbar_wait(nb, np);
        }
        WG_FENCE();
        wg_tt128(acc, dA, dB, 1);
        wg_tt128(acc, dA + 128, dB + 128, 1);
        WG_COMMIT();
        WG_WAIT(0);
        fence_acc(acc);
        STAMP(6);
        mbar_wait(bars + 8 * B_XO, 0);
        const uint32_t xo = sb + OFF_CONV + (row + (lane & 7) + 16 * ((lane >> 3) & 1)) * 128;
        #pragma unroll
        for (int j = 0; j < 16; j += 2) {
            const uint32_t ad = xo + (j >> 3) * 8192 + ((((j & 7) + (lane >> 4)) ^ (lane & 7)) << 4);
            uint32_t xr[4];
            asm volatile("ldmatrix.sync.aligned.m8n8.x4.shared.b16 {%0,%1,%2,%3}, [%4];" : "=r"(xr[0]), "=r"(xr[1]), "=r"(xr[2]), "=r"(xr[3]) : "r"(ad));
            #pragma unroll
            for (int i = 0; i < 4; i++) {
                const int jj = j + (i >> 1), hh = i & 1;
                const float f0 = acc[4 * jj + 2 * hh] * (hh ? rr1 : rr0), f1 = acc[4 * jj + 2 * hh + 1] * (hh ? rr1 : rr0);
                const uint32_t G = pack2(fmaf(f0, tanh_fast(f0), f0), fmaf(f1, tanh_fast(f1), f1));
                const uint32_t s2 = __byte_perm(sv[jj].x, sv[jj].y, hh ? 0x7632 : 0x5410);
                asm("fma.rn.bf16x2 %0, %1, %2, %0;" : "+r"(xr[i]) : "r"(s2), "r"(G));
            }
            stsm4(ad, xr[0], xr[1], xr[2], xr[3]);
        }
        fence_async_smem();
        bar_sync(1);
        if (w == 0 && elect_one()) {
            #pragma unroll
            for (int i = 0; i < 2; i++)
                asm volatile("cp.async.bulk.tensor.2d.global.shared::cta.bulk_group [%0, {%2, %3}], [%1];"
                    :: "l"(&M.out), "r"(sb + OFF_CONV + i * 8192), "r"(dg * 128 + 64 * i), "r"(tau * 64) : "memory");
            asm volatile("cp.async.bulk.commit_group; cp.async.bulk.wait_group.read 0;" ::: "memory");
        }
        STAMP(7); GSTAMP(23);
    }
}

__device__ __forceinline__ float2 cexp_p(float re2, float im, float p) {
    float sn, cs;
    const float mag = ex2(re2 * p), th = im * p;
    asm("sin.approx.ftz.f32 %0, %1;" : "=f"(sn) : "f"(th));
    asm("cos.approx.ftz.f32 %0, %1;" : "=f"(cs) : "f"(th));
    return make_float2(mag * cs, mag * sn);
}
__device__ __forceinline__ unsigned short ldu16(const void* p) { unsigned short v; asm volatile("ld.global.nc.u16 %0, [%1];" : "=h"(v) : "l"(p)); return v; }
__device__ __forceinline__ void ldsm4(uint32_t (&r)[4], uint32_t a) {
    asm volatile("ldmatrix.sync.aligned.m8n8.x4.shared.b16 {%0,%1,%2,%3}, [%4];" : "=r"(r[0]), "=r"(r[1]), "=r"(r[2]), "=r"(r[3]) : "r"(a) : "memory");
}
__device__ __forceinline__ float2 cmul(float2 a, float2 b) { return make_float2(fmaf(a.x, b.x, -a.y * b.y), fmaf(a.x, b.y, a.y * b.x)); }
__device__ __forceinline__ float2 csqr(float2 a) { const float t = a.x * a.y; return make_float2(fmaf(a.x, a.x, -a.y * a.y), t + t); }
__device__ __forceinline__ void mma16816(float (&d)[4], const uint32_t (&a)[4], uint32_t b0, uint32_t b1) {
    asm volatile("mma.sync.aligned.m16n8k16.row.col.f32.bf16.bf16.f32 {%0,%1,%2,%3}, {%4,%5,%6,%7}, {%8,%9}, {%0,%1,%2,%3};"
        : "+f"(d[0]), "+f"(d[1]), "+f"(d[2]), "+f"(d[3]) : "r"(a[0]), "r"(a[1]), "r"(a[2]), "r"(a[3]), "r"(b0), "r"(b1));
}

__device__ __forceinline__ void aux_role(uint32_t sb, int w, const Params& P) {
    const int lane = threadIdx.x & 31, q = lane & 3, g = lane >> 2;
    const int c = blockIdx.x;
    const uint32_t bars = sb + OFF_BAR;
    if (c >= 128) {
        if (lane == 0) { mbar_arrive(bars + 8 * B_K); mbar_arrive(bars + 8 * (B_K + 1)); }
        return;
    }
    {
        const uint32_t cb = sb + OFF_CONV + w * CH_STRIDE;
        const uint32_t sF = cb + CH_A3;
        const int d = 4 * c + w;
        const int po = d * 128 + lane;
        unsigned short la = ldu16(P.logA + po), ai = ldu16(P.Aim + po), cr = ldu16(P.Cr + po), ci = ldu16(P.Ci + po);
        const float ldt = __bfloat162float(P.logdt[d]), dsk = __bfloat162float(P.Dskip[d]);
        float dacc[2][3][4];
        #pragma unroll
        for (int i = 0; i < 24; i++) (&dacc[0][0][0])[i] = 0.f;
        const float dt = bf_round(ex2(ldt * 1.4426950408889634f));
        #pragma unroll 1
        for (int ck = 0; ck < 4; ck++) {
            const uint32_t fa = cb + lane * 4 + (ck & 1) * 8064;
            const float re2 = bf_round(ex2(bf_lo((uint32_t)la) * 1.4426950408889634f)) * dt * -1.4426950408889634f, im = bf_lo((uint32_t)ai) * dt;
            const float2 C = make_float2(bf_lo((uint32_t)cr) * (dt + dt), bf_lo((uint32_t)ci) * -(dt + dt));
            {
                const int pn = po + 32 * min(ck + 1, 3);
                la = ldu16(P.logA + pn); ai = ldu16(P.Aim + pn); cr = ldu16(P.Cr + pn); ci = ldu16(P.Ci + pn);
            }
            const float2 z8 = cexp_p(re2, im, 8.f), y1 = cexp_p(re2, -im, 1.f);
            float2 b0 = make_float2(1.f, 0.f), b1 = cexp_p(re2, im, 64.f), b2 = csqr(b1), b3 = cmul(b2, b1), l0 = C;
            const uint32_t fm = cb + (ck & 1) * 8064 + (lane >> 3) * 144 + (lane & 7) * 16;
#define PK(v) pack2((v).x, (v).y)
            #pragma unroll 1
            for (uint32_t ro = 0; ro < 8 * 144; ro += 144) {
                stsm4(fm + (lane >> 3) * 7 * 144 + ro, PK(b0), PK(b1), PK(b2), PK(b3));
                stsf(fa + 32 * 144 + ro, UF(PK(l0)));
                b0 = cmul(b0, z8); b1 = cmul(b1, z8); b2 = cmul(b2, z8); b3 = cmul(b3, z8); l0 = cmul(l0, y1);
            }
            if (ck < 2) STAMP(56 + 3 * ck);
            const float2 y256 = cexp_p(re2, -im, 256.f), y2 = csqr(y1), y4 = csqr(y2), y8 = make_float2(z8.x, -z8.y);
            const float2 t0 = cmul(C, y256), t1 = cmul(t0, y256), t2 = cmul(t1, y256), t3_ = cmul(t2, y256);
            const float2 u1 = cmul(t0, y2), u2 = cmul(u1, y2), u3 = cmul(u2, y2);
            stsm4(fm + 40 * 144, PK(t0), PK(u1), PK(u2), PK(u3));
            stsm4(fm + 44 * 144, PK(t1), PK(cmul(t1, y4)), PK(t2), PK(cmul(t2, y4)));
            const float2 v0 = cmul(t3_, y8), v1 = cmul(v0, y256), v2 = cmul(v1, y256), v3 = cmul(v2, y256);
            stsm4(fm + 48 * 144, PK(v0), PK(v1), PK(v2), PK(v3));
            stsf(fa + 52 * 144, UF(PK(t3_)));
#undef PK
            if (ck < 2) STAMP(57 + 3 * ck);
            if (ck & 1) {
                uint32_t ln_; asm volatile("mov.u32 %0, %%laneid;" : "=r"(ln_));
                const uint32_t lda = cb + (ln_ & 15) * 144 + (ln_ & 16);
                const uint32_t ldb = cb + (32 + (ln_ & 7)) * 144 + (ln_ >> 3) * 16;
                __syncwarp();
                #pragma unroll
                for (int k2 = 0; k2 < 4; k2++) {
                    const uint32_t ko = (k2 >> 1) * 8064 + (k2 & 1) * 64;
                    uint32_t b[3][4];
                    #pragma unroll
                    for (int t3 = 0; t3 < 3; t3++) ldsm4(b[t3], ldb + t3 * 8 * 144 + ko);
                    #pragma unroll
                    for (int k = 0; k < 2; k++)
                        #pragma unroll
                        for (int mu = 0; mu < 2; mu++) {
                            uint32_t a[4];
                            ldsm4(a, lda + mu * 16 * 144 + ko + k * 32);
                            #pragma unroll
                            for (int t3 = 0; t3 < 3; t3++) mma16816(dacc[mu][t3], a, b[t3][2 * k], b[t3][2 * k + 1]);
                        }
                }
                __syncwarp();
                if (lane == 0) mbar_arrive(bars + 8 * (B_K + (ck >> 1)));
                STAMP(58 + 3 * (ck >> 1));
            }
        }
        STAMP(18);
        const uint32_t sG = cb + CH_G;
        if (lane == 0) dacc[0][0][0] += dsk;
        if (lane < 16) sts128(((lane & 8) ? cb + CH_U + 2048 + (lane & 4) * (UPLANE / 4) : sG + 128 + (lane & 4) * 48) + (lane & 3) * 16, 0, 0, 0, 0);
        {
            const uint32_t f0 = sF + (8 * g + 2 * q) * 4, f1 = sF + ((q < 2) ? 256 + 4 * g + 2 * q : 256 + 2 * g + 64 * q) * 4, st1 = (q < 2) ? 128 : 64;
            const uint32_t ga = sG + ((g & 1) ? 0 : 192) + (63 - (g >> 1) - 32 * q) * 2;
            #pragma unroll
            for (int i = 0; i < 4; i++) {
                const int mu = i >> 1, hh = i & 1;
                sts64(f0 + i * 256, FU(dacc[mu][0][2 * hh]), FU(dacc[mu][0][2 * hh + 1]));
                sts64(f1 + i * st1, FU(dacc[mu][1][2 * hh]), FU(dacc[mu][1][2 * hh + 1]));
                const uint32_t pk = pack2(dacc[mu][2][2 * hh], dacc[mu][2][2 * hh + 1]);
                if (q < 2) { sts16(ga - 8 * i, pk & 0xffff); sts16(ga - 8 * i - 32, pk >> 16); }
            }
            if (lane == 2) stsf(sF + 2048, dacc[0][2][0]);
        }
    }
    bar_sync(2);
    STAMP(19);
    const int rw = lane - 1 + 31 * w, u = min(rw, 77) - 14;
    const uint32_t o0 = CH_A3 + u * 4, o1 = CH_A3 + (128 + ((u + ((u >> 1) & 1)) >> 1)) * 4, o2 = CH_A3 + (256 + ((u + 1 + ((u >> 2) & 1)) >> 2)) * 4;
    const int kap = (lane >> 4) * 8 + ((lane >> 1) & 7), gam = lane & 1, hh = w >> 1, wp = w & 1;
    const uint32_t oa = CH_U + wp * UPLANE + (127 - 4 * kap - 2 * gam - hh) * 16;
    const uint32_t ob = CH_U + (wp ^ 1) * UPLANE + (128 - wp - 4 * kap - 2 * gam - hh) * 16;
    const uint32_t od = CH_A3 + (4 * wp + hh) * 512 + (kap >> 3) * 256 + (kap & 7) * 16 + gam * 8;
    #pragma unroll 1
    for (int k = 0; k < 4; k++) {
        const int ch = 2 * (k & 1) + (k >> 1);
        const uint32_t cb = sb + OFF_CONV + ch * CH_STRIDE;
        if (w < 3) {
            const uint32_t f0 = cb + o0, f1 = cb + o1, f2 = cb + o2;
            float kv[17];
            kv[0] = ldsf(u < 0 ? f1 : f0); if (u < 0) kv[0] = 0.f;
            #pragma unroll
            for (int s = 1; s < 4; s++) kv[s] = ldsf(f0 + s * 256);
            kv[4] = ldsf(u < 0 ? f0 + 1024 : f1 + 512);
            #pragma unroll
            for (int s = 5; s < 8; s++) kv[s] = ldsf(f1 + s * 128);
            kv[8] = ldsf(u < 0 ? f1 + 1024 : f2 + 512);
            #pragma unroll
            for (int s = 9; s < 16; s++) kv[s] = ldsf(f2 + s * 64);
            kv[16] = ldsf(u < 0 ? f2 + 1024 : cb + CH_A3 + 2048); if (u > 4) kv[16] = 0.f;
            uint32_t o[17];
            #pragma unroll
            for (int s = 0; s < 17; s++) o[s] = pack2(kv[s], __shfl_up_sync(0xffffffffu, kv[s], 1));
            if (lane > 0 && rw < 78) {
                const uint32_t ta = cb + CH_T + rw * 80;
                #pragma unroll
                for (int s4 = 0; s4 < 4; s4++) sts128(ta + s4 * 16, o[4 * s4], o[4 * s4 + 1], o[4 * s4 + 2], o[4 * s4 + 3]);
                stsf(ta + 64, UF(o[16]));
            }
        } else {
            const uint32_t ga = cb + CH_G + ((lane >> 3) & 1) * 192 + (lane >> 4) * 16 + (lane & 7) * 8;
            #pragma unroll
            for (int i = 0; i < 4; i++) {
                const uint2 x0 = lds64(ga + 32 * i), x1 = lds64(ga + 32 * i + 8);
                sts128(cb + CH_B3 + lane * 16 + 512 * i, x0.x, x0.y, x1.x, x1.y);
            }
        }
        mbar_wait(bars + 8 * B_U, 0);
        float p[24];
        const uint2 r0 = lds64(cb + ob + 24), r3 = lds64(cb + oa);
        uint32_t r[8];
        *(uint4*)&r[0] = lds128(cb + oa + 16); *(uint4*)&r[4] = lds128(cb + ob);
        p[0] = 0.f;
        p[1] = bf_lo(r0.x); p[2] = p[1] + bf_hi(r0.x); p[3] = p[2] + bf_lo(r0.y); p[4] = p[3] + bf_hi(r0.y);
        #pragma unroll
        for (int i = 0; i < 8; i++) { p[5 + 2 * i] = p[4 + 2 * i] + bf_lo(r[i]); p[6 + 2 * i] = p[5 + 2 * i] + bf_hi(r[i]); }
        p[21] = p[20] + bf_lo(r3.x); p[22] = p[21] + bf_hi(r3.x); p[23] = p[22] + bf_lo(r3.y);
        bar_sync(2);
        #pragma unroll
        for (int i = 0; i < 8; i += 4) {
            sts64(cb + od + i * 256, pack2(p[i + 9] - p[i], p[i + 10] - p[i + 1]), pack2(p[i + 11] - p[i + 2], p[i + 12] - p[i + 3]));
            sts64(cb + od + i * 256 + 128, pack2(p[i + 16] - p[i + 9], p[i + 17] - p[i + 10]), pack2(p[i + 18] - p[i + 11], p[i + 19] - p[i + 12]));
        }
        fence_async_smem();
        mbar_arrive(bars + 8 * (B_CONV + ch));
        if (k == 0) STAMP(17);
    }
    STAMP(21);
}

__global__ void __launch_bounds__(512, 1)
fused_kernel(const __grid_constant__ Params P, const __grid_constant__ Maps M) {
    extern __shared__ __align__(1024) uint8_t smem_raw[];
    const uint32_t sb = smem_u32(smem_raw);
    const uint32_t bars = sb + OFF_BAR;
    const int warp = __shfl_sync(0xffffffffu, threadIdx.x >> 5, 0);
    const int c = blockIdx.x, tg = c / 22, fb = c - 22 * tg;
    if (elect_one()) {
        if (warp == 0) { STAMP(24); GSTAMP(22); }
        asm volatile("" :: "l"(((const uint64_t*)&P)[warp < 12 ? warp : 0]));
        if (warp < 11) asm volatile("prefetch.tensormap [%0];" :: "l"(&M.x[0] + warp) : "memory");
        #pragma unroll
        for (int k = 0; k < 4; k++) {
            const int i = 16 * k + ((warp + 4) & 15);
            const uint32_t cnt = i >= B_CONV ? 128 : ((0xf0ull >> i) & 1) ? 8 : ((0xff0000ull >> i) & 1) ? 2 : ((0x3e00ff00f000ull >> i) & 1) ? 4 : 1;
            asm volatile("mbarrier.init.shared::cta.b64 [%0], %1;" :: "r"(bars + 8 * i), "r"(cnt) : "memory");
        }
        asm volatile("fence.mbarrier_init.release.cluster; fence.proxy.async.shared::cta;" ::: "memory");
        if (warp == 12) {
            mbar_expect(bars + 8 * B_FULLW, 16384);
            tma2d(sb + OFF_W, &M.wg, 64 * fb, 0, bars + 8 * B_FULLW);
            tma2d(sb + OFF_W + 8192, &M.wu, 64 * fb, 0, bars + 8 * B_FULLW);
            STAMP(31);
        } else if (warp == 4) {
            mbar_expect(bars + 8 * B_FULLX, 168 * 128);
            tma2d(sb + OFF_X, &M.x[0], 0, TOKG * tg, bars + 8 * B_FULLX);
        }
        if (sb & 1023) __trap();
    }
    __syncthreads();
    if (warp < 8) {
        asm volatile("setmaxnreg.inc.sync.aligned.u32 208;");
        consumer(sb, warp, P, M);
    } else if (warp < 12) {
        asm volatile("setmaxnreg.dec.sync.aligned.u32 72;");
        STAMP(32);
        aux_role(sb, warp - 8, P);
    } else {
        asm volatile("setmaxnreg.dec.sync.aligned.u32 24;");
        const int tau = c >> 2, dg = c & 3;
        if (elect_one()) {
            if (warp == 12) {
                #pragma unroll 1
                for (int st = 1; st < 8; st++) {
                    const uint32_t s = st & 3, fb_ = bars + 8 * (B_FULLW + s);
                    if (st == 2) mbar_wait(bars + 8 * B_FULLW, 0);
                    mbar_wait(bars + 8 * (B_EMPTYW + s), (st >> 2) ^ 1);
                    mbar_expect(fb_, 16384);
                    tma2d(sb + OFF_W + s * 16384, &M.wg, 64 * fb, 64 * st, fb_);
                    tma2d(sb + OFF_W + s * 16384 + 8192, &M.wu, 64 * fb, 64 * st, fb_);
                }
                if (c < 128) {
                    #pragma unroll 1
                    for (int st = 0; st < 22; st++) {
                        const int sd = st & 7;
                        if (st < 8) mbar_wait(bars + 8 * (uint32_t)((0x282823070d060504ull >> (8 * st)) & 0xff), st < 5);
                        else mbar_wait(bars + 8 * (B_EMPTYD + sd), ((st >> 3) & 1) ^ 1);
                        const uint32_t da = sb + wd_slot(sd), fb_ = bars + 8 * (B_FULLD + sd);
                        mbar_expect(fb_, 16384);
                        tma2d(da, &M.wd, 128 * dg, 64 * st, fb_);
                        tma2d(da + 8192, &M.wd, 128 * dg + 64, 64 * st, fb_);
                    }
                }
            } else if (warp < 15) {
                const int V = warp - 13;
                #pragma unroll 1
                for (int st = 1 - V; st < 8; st++) {
                    const uint32_t s = 2 * V + (st & 1);
                    if (s == 3 && st == 1) mbar_wait(bars + 8 * B_LNS, 0);
                    mbar_wait(bars + 8 * (B_EMPTYX + s), ((st >> 1) & 1) ^ 1);
                    mbar_expect(bars + 8 * (B_FULLX + s), (168 + 8 * V) * 128);
                    tma2d(sb + OFF_X + s * XBUF, &M.x[V], 64 * st, TOKG * tg + 168 * V, bars + 8 * (B_FULLX + s));
                }
                if (c < 128) {
                    if (V == 0) {
                        mbar_wait(bars + 8 * (B_STG + 1), 0);
                        #pragma unroll 1
                        for (int o = 8 * tau; o < 8 * tau + 8; o += 7) flag_wait(P.flags, F_H + 2 * (o / 43) + ((o % 43) >= 21), 22);
                        mbar_arrive(bars + 8 * B_HF);
                        STAMP(25);
                        #pragma unroll 1
                        for (int st = 0; st < 22; st++) {
                            const uint32_t fb_ = bars + 8 * (B_FULLD + (st & 7));
                            if (st == 6) mbar_wait(bars + 8 * B_SST, 0);
                            mbar_wait(bars + 8 * (B_EMPTYD + (st & 7)), ((st >> 3) & 1) ^ 1);
                            mbar_expect(fb_, 8192);
                            asm volatile("cp.async.bulk.tensor.5d.shared::cluster.global.mbarrier::complete_tx::bytes [%0], [%1, {%3, %3, %3, %4, %5}], [%2];"
                                :: "r"(sb + h_slot(st & 7)), "l"(&M.hld), "r"(fb_), "r"(0), "r"(2 * tau), "r"(8 * st) : "memory");
                        }
                    } else {
                        mbar_wait(bars + 8 * B_CH0, 0);
                        mbar_expect(bars + 8 * B_XO, 16384);
                        tma2d(sb + OFF_CONV, &M.xo, 128 * dg, 64 * tau, bars + 8 * B_XO);
                        tma2d(sb + OFF_CONV + 8192, &M.xo, 128 * dg + 64, 64 * tau, bars + 8 * B_XO);
                        flag_wait(P.flags, F_S + dg, 64);
                        STAMP(26);
                        mbar_arrive(bars + 8 * B_S);
                        mbar_wait(bars + 8 * B_HF, 0);
                        exit_count(P.flags);
                    }
                }
            } else {
                mbar_wait(bars + 8 * B_LN, 0);
                if (c < 128) {
                    #pragma unroll 1
                    for (int i = 0; i < 2; i++)
                        asm volatile("cp.async.bulk.tensor.2d.global.shared::cta.bulk_group [%0, {%2, %3}], [%1];"
                            :: "l"(&M.xt), "r"(sb + OFF_LN + i * 8192), "r"((c & 1) * 1024 + (126 - (c & ~1)) * 8), "r"(256 * i) : "memory");
                    #pragma unroll 1
                    for (int i = 0; i < 2; i++) bulk_store(P.st + 16 * (c & ~1) + 8 * (c & 1) + 16 - 16 * i, sb + OFF_CSUM + 64 * i, 64);
                    asm volatile("cp.async.bulk.prefetch.L2.global [%0], %1;" :: "l"(P.Wd + c * (FF * DM / 128)), "r"(FF * DM / 64) : "memory");
                }
                asm volatile("cp.async.bulk.commit_group; cp.async.bulk.wait_group.read 0;" ::: "memory");
                mbar_arrive(bars + 8 * B_LNS);
                flag_signal(P.flags, F_A);
                flag_wait(P.flags, F_A, NCTA);
                STAMP(20);
                mbar_expect(bars + 8 * B_STATS, TOKG * 8);
                bulk_load(sb + OFF_ST, P.st + TOKG * tg, TOKG * 8, bars + 8 * B_STATS);
                if (c < 128) {
                    mbar_wait(bars + 8 * (B_K + 1), 0);
                    fence_async_smem();
                    mbar_expect(bars + 8 * B_U, 8 * 2048);
                    #pragma unroll 1
                    for (int i = 0; i < 8; i++)
                        bulk_load(sb + OFF_CONV + (i >> 1) * CH_STRIDE + CH_U + (i & 1) * UPLANE, P.xnT + 4 * c * 256 + i * 128, 2048, bars + 8 * B_U);
                } else exit_count(P.flags);
                #pragma unroll 1
                for (int V = 0; V < 2; V++) {
                    mbar_wait(bars + 8 * (B_EPI + V), 0);
                    asm volatile("cp.async.bulk.tensor.3d.global.shared::cta.bulk_group [%0, {%2, %3, %4}], [%1];"
                        :: "l"(&M.hst[V]), "r"(sb + OFF_X + V * 2 * XBUF), "r"(0), "r"(43 * tg + 21 * V), "r"(8 * fb) : "memory");
                    flag_signal(P.flags, F_H + 2 * tg + V);
                    mbar_arrive(bars + 8 * (B_STG + V));
                }
                if (c < 128) {
                    #pragma unroll 1
                    for (int V = 0; V < 2; V++) {
                        mbar_wait(bars + 8 * (B_SIG + V), 0);
                        bulk_store(P.S + (2 * c + V) * 1024, sb + OFF_CONV + (2 * V + 1) * CH_STRIDE, 8192);
                        flag_signal(P.flags, F_S + (c >> 5));
                    }
                    mbar_arrive(bars + 8 * B_SST);
                }
            }
        }
    }
}

typedef CUresult (*EncodeFn)(CUtensorMap*, CUtensorMapDataType, cuuint32_t, void*, const cuuint64_t*, const cuuint64_t*, const cuuint32_t*,
                             const cuuint32_t*, CUtensorMapInterleave, CUtensorMapSwizzle, CUtensorMapL2promotion, CUtensorMapFloatOOBfill);

void make_map(EncodeFn enc, CUtensorMap* m, const void* ptr, int rank, const cuuint64_t* dims, const cuuint64_t* strides, const cuuint32_t* box, bool swz) {
    const cuuint32_t es[5] = {1, 1, 1, 1, 1};
    enc(m, CU_TENSOR_MAP_DATA_TYPE_BFLOAT16, rank, (void*)ptr, dims, strides, box, es, CU_TENSOR_MAP_INTERLEAVE_NONE,
        swz ? CU_TENSOR_MAP_SWIZZLE_128B : CU_TENSOR_MAP_SWIZZLE_NONE, CU_TENSOR_MAP_L2_PROMOTION_L2_128B, CU_TENSOR_MAP_FLOAT_OOB_FILL_NONE);
}
void make_map2(EncodeFn enc, CUtensorMap* m, const void* ptr, cuuint64_t inner, cuuint64_t outer, cuuint32_t rows) {
    const cuuint64_t dims[2] = {inner, outer}, strides[1] = {inner * 2};
    const cuuint32_t box[2] = {64, rows};
    make_map(enc, m, ptr, 2, dims, strides, box, true);
}

}

extern "C" void kernel_launch(void* const* d_in, const int* in_sizes, int n_in, void* d_out, int out_size) {
    (void)in_sizes; (void)n_in; (void)out_size;
    static EncodeFn enc = nullptr;
    static void *hptr, *p_xnT, *p_st, *p_S, *p_flags;
    if (!enc) {
        cudaDriverEntryPointQueryResult qr;
        cudaGetDriverEntryPoint("cuTensorMapEncodeTiled", (void**)&enc, cudaEnableDefault, &qr);
        cudaFuncSetAttribute(fused_kernel, cudaFuncAttributeMaxDynamicSharedMemorySize, SMEM_BYTES);
        cudaGetSymbolAddress(&hptr, g_H); cudaGetSymbolAddress(&p_xnT, g_xnT); cudaGetSymbolAddress(&p_st, g_st);
        cudaGetSymbolAddress(&p_S, g_S); cudaGetSymbolAddress(&p_flags, g_flags);
    }
    Params P;
    P.x = (const __nv_bfloat16*)d_in[0]; P.logA = (const __nv_bfloat16*)d_in[1]; P.Aim = (const __nv_bfloat16*)d_in[2];
    P.Cr = (const __nv_bfloat16*)d_in[3]; P.Ci = (const __nv_bfloat16*)d_in[4]; P.logdt = (const __nv_bfloat16*)d_in[5];
    P.Dskip = (const __nv_bfloat16*)d_in[6];
    P.Wd = (const __nv_bfloat16*)d_in[10]; P.xnT = (uint4*)p_xnT; P.st = (float2*)p_st; P.S = (uint2*)p_S; P.flags = (unsigned*)p_flags;
    Maps M;
    make_map2(enc, &M.x[0], d_in[0], DM, SEQ, 168); make_map2(enc, &M.x[1], d_in[0], DM, SEQ, 176);
    make_map2(enc, &M.xo, d_in[0], DM, SEQ, 64);    make_map2(enc, &M.out, d_out, DM, SEQ, 64);
    make_map2(enc, &M.wg, d_in[8], FF, DM, 64);     make_map2(enc, &M.wu, d_in[9], FF, DM, 64);
    make_map2(enc, &M.wd, d_in[10], DM, FF, 64);
    for (int v = 0; v < 2; v++) {
        const cuuint64_t dims[3] = {64, 256, 172}, strides[2] = {128, 32768};
        const cuuint32_t box[3] = {64, (cuuint32_t)(21 + v), 8};
        make_map(enc, &M.hst[v], hptr, 3, dims, strides, box, false);
    }
    {
        const cuuint64_t dims[2] = {2048, 512}, strides[1] = {4096};
        const cuuint32_t box[2] = {16, 256};
        make_map(enc, &M.xt, p_xnT, 2, dims, strides, box, false);
    }
    {
        const cuuint64_t dims[5] = {64, 2, 2, 64, 172}, strides[4] = {256, 128, 512, 32768};
        const cuuint32_t box[5] = {64, 2, 2, 2, 8};
        make_map(enc, &M.hld, hptr, 5, dims, strides, box, false);
    }
    fused_kernel<<<NCTA, 512, SMEM_BYTES>>>(P, M);
}
```

```cpp
#include <cuda_runtime.h>
#include <cuda_bf16.h>
#include <cuda.h>
#include <stdint.h>

#define PROF 0

namespace {

constexpr int SEQ = 2048, DM = 512, FF = 1376;
constexpr int NCTA = 132;
#define HOLD0 4
#define HOLD1 7
#define LAG 2
constexpr int TOKG = 344;

constexpr uint32_t OFF_W = 0;
constexpr uint32_t XBUF = 22528;
constexpr uint32_t OFF_X = 65536;
constexpr uint32_t OFF_CONV = 155648;
constexpr uint32_t CH_STRIDE = 16640;
constexpr uint32_t CH_T = 0;
constexpr uint32_t CH_A3 = 6272;
constexpr uint32_t CH_B3 = 10368;
constexpr uint32_t CH_U = 12416;
constexpr uint32_t CH_G = CH_A3 + 2064;
constexpr uint32_t UPLANE = 2112;
constexpr uint32_t OFF_LN = OFF_X + 3 * XBUF;
constexpr uint32_t OFF_ST = 222208;
constexpr uint32_t OFF_CSUM = 230400;
constexpr uint32_t OFF_BAR = 231168;
constexpr uint32_t SMEM_BYTES = 231680;

enum {
    B_FULLW = 0, B_EMPTYW = 4, B_FULLX = 8, B_EMPTYX = 12, B_FULLD = 16, B_EMPTYD = 24,
    B_U = 32, B_XO = 33, B_S = 34, B_STG = 35, B_HF = 37, B_STATS = 38, B_LNS = 39, B_SST = 40,
    B_LNX = 41, B_GO = 42, B_CH0 = 43, B_K = 44,
    B_CONV = 46, B_LN = 50, B_CS = 51, B_EPI = 52, B_SIG = 54,
    B_COUNT = 56
};
enum { F_A = 0, F_H = 1, F_S = 13, F_EXIT = 17, F_COUNT = 18 };

__device__ uint4 g_xnT[DM * 256];
__device__ float2 g_st[6 * TOKG];
__device__ uint4 g_H[172 * 256 * 8];
__device__ uint2 g_S[256 * 1024];
__device__ unsigned g_flags[F_COUNT * 32];
#define STAMP(i) do {} while (0)
#define GSTAMP(i) do {} while (0)
#define STAMP2(i) do {} while (0)

__device__ __forceinline__ uint32_t smem_u32(const void* p) { return (uint32_t)__cvta_generic_to_shared(p); }
__device__ __forceinline__ void mbar_expect(uint32_t bar, uint32_t bytes) { asm volatile("mbarrier.arrive.expect_tx.shared::cta.b64 _, [%0], %1;" :: "r"(bar), "r"(bytes) : "memory"); }
__device__ __forceinline__ void mbar_arrive(uint32_t bar) { asm volatile("mbarrier.arrive.shared::cta.b64 _, [%0];" :: "r"(bar) : "memory"); }
__device__ __forceinline__ void mbar_wait(uint32_t bar, uint32_t parity) {
    asm volatile("{.reg .pred p; .reg .u32 n; mov.u32 n, 0x20000;\n"
                 "LW: mbarrier.try_wait.parity.shared::cta.b64 p, [%0], %1;\n"
                 "sub.u32 n, n, 1; setp.eq.or.u32 p, n, 0, p; @!p bra LW;}" :: "r"(bar), "r"(parity) : "memory");
}
__device__ __forceinline__ bool elect_one() { uint32_t p; asm volatile("{.reg .pred P; elect.sync _|P, 0xffffffff; selp.u32 %0, 1, 0, P;}" : "=r"(p)); return p; }
__device__ __forceinline__ void tma2d(uint32_t dst, const CUtensorMap* m, int c0, int c1, uint32_t bar) {
    asm volatile("cp.async.bulk.tensor.2d.shared::cluster.global.mbarrier::complete_tx::bytes [%0], [%1, {%3, %4}], [%2];"
        :: "r"(dst), "l"(m), "r"(bar), "r"(c0), "r"(c1) : "memory");
}
__device__ __forceinline__ void bulk_load(uint32_t dst, const void* src, uint32_t bytes, uint32_t bar) {
    asm volatile("cp.async.bulk.shared::cluster.global.mbarrier::complete_tx::bytes [%0], [%1], %2, [%3];" :: "r"(dst), "l"(src), "r"(bytes), "r"(bar) : "memory");
}
__device__ __forceinline__ void bulk_store(void* dst, uint32_t src, uint32_t bytes) {
    asm volatile("cp.async.bulk.global.shared::cta.bulk_group [%0], [%1], %2;" :: "l"(dst), "r"(src), "r"(bytes) : "memory");
}
__device__ __forceinline__ void fence_async_smem() { asm volatile("fence.proxy.async.shared::cta;" ::: "memory"); }
__device__ __forceinline__ void flag_wait(unsigned* g_flags, int f, unsigned target) {
    asm volatile("{.reg .pred p; .reg .u32 n, v; mov.u32 n, 0x40000;\n"
                 "LF: ld.acquire.gpu.global.u32 v, [%0]; setp.ge.u32 p, v, %1; @p bra LD;\n"
                 "nanosleep.u32 20; sub.u32 n, n, 1; setp.ne.u32 p, n, 0; @p bra LF; trap;\nLD: }"
                 :: "l"(g_flags + f * 32), "r"(target) : "memory");
}
__device__ __forceinline__ void flag_signal(unsigned* g_flags, int f) {
    asm volatile("cp.async.bulk.commit_group; cp.async.bulk.wait_group 0; red.relaxed.gpu.global.add.u32 [%0], 1;" :: "l"(g_flags + f * 32) : "memory");
}
__device__ __forceinline__ void exit_count(unsigned* g_flags) {
    if (atomicAdd(g_flags + F_EXIT * 32, 1u) == NCTA - 1) {
        #pragma unroll 1
        for (int i = 0; i < F_COUNT; i++) g_flags[i * 32] = 0;
    }
}
__device__ __forceinline__ void bar_sync(int id) { asm volatile("bar.sync %0, 128;" :: "r"(id) : "memory"); }
__device__ __forceinline__ uint64_t mkdesc(uint32_t addr, uint32_t lbo, uint32_t sbo, uint32_t swz) {
    return (uint64_t)((addr >> 4) | ((lbo >> 4) << 16)) | ((uint64_t)((sbo >> 4) | (swz << 30)) << 32);
}
#define WG_FENCE() asm volatile("wgmma.fence.sync.aligned;" ::: "memory")
#define WG_COMMIT() asm volatile("wgmma.commit_group.sync.aligned;" ::: "memory")
#define WG_WAIT(n) asm volatile("wgmma.wait_group.sync.aligned " #n ";" ::: "memory")
template <int N> __device__ __forceinline__ void fence_acc(float (&d)[N]) {
    #pragma unroll
    for (int i = 0; i < N; i++) asm volatile("" : "+f"(d[i]) :: "memory");
}
template <int N> __device__ __forceinline__ void define_acc(float (&d)[N]) {
    #pragma unroll
    for (int i = 0; i < N; i++) asm volatile("" : "=f"(d[i]));
}
__device__ __forceinline__ uint32_t pack2(float lo, float hi) { uint32_t r; asm("cvt.rn.bf16x2.f32 %0, %1, %2;" : "=r"(r) : "f"(hi), "f"(lo)); return r; }
__device__ __forceinline__ float bf_lo(uint32_t v) { return __uint_as_float(v << 16); }
__device__ __forceinline__ float bf_hi(uint32_t v) { return __uint_as_float(v & 0xffff0000u); }
__device__ __forceinline__ float bf_round(float v) { return bf_hi(pack2(0.f, v)); }
__device__ __forceinline__ float tanh_fast(float v) { float r; asm("tanh.approx.f32 %0, %1;" : "=f"(r) : "f"(v)); return r; }
__device__ __forceinline__ float ex2(float v) { float r; asm("ex2.approx.ftz.f32 %0, %1;" : "=f"(r) : "f"(v)); return r; }
__device__ __forceinline__ uint4 lds128(uint32_t a) { uint4 v; asm volatile("ld.shared.v4.b32 {%0,%1,%2,%3}, [%4];" : "=r"(v.x), "=r"(v.y), "=r"(v.z), "=r"(v.w) : "r"(a)); return v; }
__device__ __forceinline__ uint2 lds64(uint32_t a) { uint2 v; asm volatile("ld.shared.v2.b32 {%0,%1}, [%2];" : "=r"(v.x), "=r"(v.y) : "r"(a)); return v; }
__device__ __forceinline__ float ldsf(uint32_t a) { float v; asm volatile("ld.shared.f32 %0, [%1];" : "=f"(v) : "r"(a)); return v; }
__device__ __forceinline__ void sts128(uint32_t a, uint32_t x, uint32_t y, uint32_t z, uint32_t w) { asm volatile("st.shared.v4.b32 [%0], {%1,%2,%3,%4};" :: "r"(a), "r"(x), "r"(y), "r"(z), "r"(w) : "memory"); }
__device__ __forceinline__ void sts64(uint32_t a, uint32_t x, uint32_t y) { asm volatile("st.shared.v2.b32 [%0], {%1,%2};" :: "r"(a), "r"(x), "r"(y) : "memory"); }
__device__ __forceinline__ void stsf(uint32_t a, float x) { asm volatile("st.shared.f32 [%0], %1;" :: "r"(a), "f"(x) : "memory"); }
__device__ __forceinline__ void sts16(uint32_t a, uint32_t x) { asm volatile("st.shared.b16 [%0], %1;" :: "r"(a), "h"((unsigned short)x) : "memory"); }
__device__ __forceinline__ void stsm4(uint32_t a, uint32_t r0, uint32_t r1, uint32_t r2, uint32_t r3) {
    asm volatile("stmatrix.sync.aligned.m8n8.x4.shared.b16 [%0], {%1,%2,%3,%4};" :: "r"(a), "r"(r0), "r"(r1), "r"(r2), "r"(r3) : "memory");
}
#define FU(x) __float_as_uint(x)
#define UF(x) __uint_as_float(x)
__device__ __forceinline__ uint32_t wd_slot(int s) { return (uint32_t)((0xb9a9403056201000ull >> (8 * s)) & 0xff) << 10; }
__device__ __forceinline__ uint32_t h_slot(int s) { return (uint32_t)((0xd1c9d98c847c746cull >> (8 * s)) & 0xff) << 10; }

template<int N> __device__ __forceinline__ void wg_rs(float (&d)[64], uint32_t a0, uint32_t a1, uint32_t a2, uint32_t a3, uint64_t db);
template<> __device__ __forceinline__ void wg_rs<128>(float (&d)[64], uint32_t a0, uint32_t a1, uint32_t a2, uint32_t a3, uint64_t db) {
  asm volatile("{.reg .pred p; setp.ne.b32 p, 1, 0; wgmma.mma_async.sync.aligned.m64n128k16.f32.bf16.bf16 {%0,%1,%2,%3,%4,%5,%6,%7,%8,%9,%10,%11,%12,%13,%14,%15,%16,%17,%18,%19,%20,%21,%22,%23,%24,%25,%26,%27,%28,%29,%30,%31,%32,%33,%34,%35,%36,%37,%38,%39,%40,%41,%42,%43,%44,%45,%46,%47,%48,%49,%50,%51,%52,%53,%54,%55,%56,%57,%58,%59,%60,%61,%62,%63}, {%64,%65,%66,%67}, %68, p, 1, 1, 0;}"
    : "+f"(d[0]),"+f"(d[1]),"+f"(d[2]),"+f"(d[3]),"+f"(d[4]),"+f"(d[5]),"+f"(d[6]),"+f"(d[7]),"+f"(d[8]),"+f"(d[9]),"+f"(d[10]),"+f"(d[11]),"+f"(d[12]),"+f"(d[13]),"+f"(d[14]),"+f"(d[15]),"+f"(d[16]),"+f"(d[17]),"+f"(d[18]),"+f"(d[19]),"+f"(d[20]),"+f"(d[21]),"+f"(d[22]),"+f"(d[23]),"+f"(d[24]),"+f"(d[25]),"+f"(d[26]),"+f"(d[27]),"+f"(d[28]),"+f"(d[29]),"+f"(d[30]),"+f"(d[31]),"+f"(d[32]),"+f"(d[33]),"+f"(d[34]),"+f"(d[35]),"+f"(d[36]),"+f"(d[37]),"+f"(d[38]),"+f"(d[39]),"+f"(d[40]),"+f"(d[41]),"+f"(d[42]),"+f"(d[43]),"+f"(d[44]),"+f"(d[45]),"+f"(d[46]),"+f"(d[47]),"+f"(d[48]),"+f"(d[49]),"+f"(d[50]),"+f"(d[51]),"+f"(d[52]),"+f"(d[53]),"+f"(d[54]),"+f"(d[55]),"+f"(d[56]),"+f"(d[57]),"+f"(d[58]),"+f"(d[59]),"+f"(d[60]),"+f"(d[61]),"+f"(d[62]),"+f"(d[63]) : "r"(a0), "r"(a1), "r"(a2), "r"(a3), "l"(db));
}
template<> __device__ __forceinline__ void wg_rs<120>(float (&d)[64], uint32_t a0, uint32_t a1, uint32_t a2, uint32_t a3, uint64_t db) {
  asm volatile("{.reg .pred p; setp.ne.b32 p, 1, 0; wgmma.mma_async.sync.aligned.m64n120k16.f32.bf16.bf16 {%0,%1,%2,%3,%4,%5,%6,%7,%8,%9,%10,%11,%12,%13,%14,%15,%16,%17,%18,%19,%20,%21,%22,%23,%24,%25,%26,%27,%28,%29,%30,%31,%32,%33,%34,%35,%36,%37,%38,%39,%40,%41,%42,%43,%44,%45,%46,%47,%48,%49,%50,%51,%52,%53,%54,%55,%56,%57,%58,%59}, {%60,%61,%62,%63}, %64, p, 1, 1, 0;}"
    : "+f"(d[0]),"+f"(d[1]),"+f"(d[2]),"+f"(d[3]),"+f"(d[4]),"+f"(d[5]),"+f"(d[6]),"+f"(d[7]),"+f"(d[8]),"+f"(d[9]),"+f"(d[10]),"+f"(d[11]),"+f"(d[12]),"+f"(d[13]),"+f"(d[14]),"+f"(d[15]),"+f"(d[16]),"+f"(d[17]),"+f"(d[18]),"+f"(d[19]),"+f"(d[20]),"+f"(d[21]),"+f"(d[22]),"+f"(d[23]),"+f"(d[24]),"+f"(d[25]),"+f"(d[26]),"+f"(d[27]),"+f"(d[28]),"+f"(d[29]),"+f"(d[30]),"+f"(d[31]),"+f"(d[32]),"+f"(d[33]),"+f"(d[34]),"+f"(d[35]),"+f"(d[36]),"+f"(d[37]),"+f"(d[38]),"+f"(d[39]),"+f"(d[40]),"+f"(d[41]),"+f"(d[42]),"+f"(d[43]),"+f"(d[44]),"+f"(d[45]),"+f"(d[46]),"+f"(d[47]),"+f"(d[48]),"+f"(d[49]),"+f"(d[50]),"+f"(d[51]),"+f"(d[52]),"+f"(d[53]),"+f"(d[54]),"+f"(d[55]),"+f"(d[56]),"+f"(d[57]),"+f"(d[58]),"+f"(d[59]) : "r"(a0), "r"(a1), "r"(a2), "r"(a3), "l"(db));
}
template<> __device__ __forceinline__ void wg_rs<112>(float (&d)[64], uint32_t a0, uint32_t a1, uint32_t a2, uint32_t a3, uint64_t db) {
  asm volatile("{.reg .pred p; setp.ne.b32 p, 1, 0; wgmma.mma_async.sync.aligned.m64n112k16.f32.bf16.bf16 {%0,%1,%2,%3,%4,%5,%6,%7,%8,%9,%10,%11,%12,%13,%14,%15,%16,%17,%18,%19,%20,%21,%22,%23,%24,%25,%26,%27,%28,%29,%30,%31,%32,%33,%34,%35,%36,%37,%38,%39,%40,%41,%42,%43,%44,%45,%46,%47,%48,%49,%50,%51,%52,%53,%54,%55}, {%56,%57,%58,%59}, %60, p, 1, 1, 0;}"
    : "+f"(d[0]),"+f"(d[1]),"+f"(d[2]),"+f"(d[3]),"+f"(d[4]),"+f"(d[5]),"+f"(d[6]),"+f"(d[7]),"+f"(d[8]),"+f"(d[9]),"+f"(d[10]),"+f"(d[11]),"+f"(d[12]),"+f"(d[13]),"+f"(d[14]),"+f"(d[15]),"+f"(d[16]),"+f"(d[17]),"+f"(d[18]),"+f"(d[19]),"+f"(d[20]),"+f"(d[21]),"+f"(d[22]),"+f"(d[23]),"+f"(d[24]),"+f"(d[25]),"+f"(d[26]),"+f"(d[27]),"+f"(d[28]),"+f"(d[29]),"+f"(d[30]),"+f"(d[31]),"+f"(d[32]),"+f"(d[33]),"+f"(d[34]),"+f"(d[35]),"+f"(d[36]),"+f"(d[37]),"+f"(d[38]),"+f"(d[39]),"+f"(d[40]),"+f"(d[41]),"+f"(d[42]),"+f"(d[43]),"+f"(d[44]),"+f"(d[45]),"+f"(d[46]),"+f"(d[47]),"+f"(d[48]),"+f"(d[49]),"+f"(d[50]),"+f"(d[51]),"+f"(d[52]),"+f"(d[53]),"+f"(d[54]),"+f"(d[55]) : "r"(a0), "r"(a1), "r"(a2), "r"(a3), "l"(db));
}
template<> __device__ __forceinline__ void wg_rs<104>(float (&d)[64], uint32_t a0, uint32_t a1, uint32_t a2, uint32_t a3, uint64_t db) {
  asm volatile("{.reg .pred p; setp.ne.b32 p, 1, 0; wgmma.mma_async.sync.aligned.m64n104k16.f32.bf16.bf16 {%0,%1,%2,%3,%4,%5,%6,%7,%8,%9,%10,%11,%12,%13,%14,%15,%16,%17,%18,%19,%20,%21,%22,%23,%24,%25,%26,%27,%28,%29,%30,%31,%32,%33,%34,%35,%36,%37,%38,%39,%40,%41,%42,%43,%44,%45,%46,%47,%48,%49,%50,%51}, {%52,%53,%54,%55}, %56, p, 1, 1, 0;}"
    : "+f"(d[0]),"+f"(d[1]),"+f"(d[2]),"+f"(d[3]),"+f"(d[4]),"+f"(d[5]),"+f"(d[6]),"+f"(d[7]),"+f"(d[8]),"+f"(d[9]),"+f"(d[10]),"+f"(d[11]),"+f"(d[12]),"+f"(d[13]),"+f"(d[14]),"+f"(d[15]),"+f"(d[16]),"+f"(d[17]),"+f"(d[18]),"+f"(d[19]),"+f"(d[20]),"+f"(d[21]),"+f"(d[22]),"+f"(d[23]),"+f"(d[24]),"+f"(d[25]),"+f"(d[26]),"+f"(d[27]),"+f"(d[28]),"+f"(d[29]),"+f"(d[30]),"+f"(d[31]),"+f"(d[32]),"+f"(d[33]),"+f"(d[34]),"+f"(d[35]),"+f"(d[36]),"+f"(d[37]),"+f"(d[38]),"+f"(d[39]),"+f"(d[40]),"+f"(d[41]),"+f"(d[42]),"+f"(d[43]),"+f"(d[44]),"+f"(d[45]),"+f"(d[46]),"+f"(d[47]),"+f"(d[48]),"+f"(d[49]),"+f"(d[50]),"+f"(d[51]) : "r"(a0), "r"(a1), "r"(a2), "r"(a3), "l"(db));
}
template<> __device__ __forceinline__ void wg_rs<96>(float (&d)[64], uint32_t a0, uint32_t a1, uint32_t a2, uint32_t a3, uint64_t db) {
  asm volatile("{.reg .pred p; setp.ne.b32 p, 1, 0; wgmma.mma_async.sync.aligned.m64n96k16.f32.bf16.bf16 {%0,%1,%2,%3,%4,%5,%6,%7,%8,%9,%10,%11,%12,%13,%14,%15,%16,%17,%18,%19,%20,%21,%22,%23,%24,%25,%26,%27,%28,%29,%30,%31,%32,%33,%34,%35,%36,%37,%38,%39,%40,%41,%42,%43,%44,%45,%46,%47}, {%48,%49,%50,%51}, %52, p, 1, 1, 0;}"
    : "+f"(d[0]),"+f"(d[1]),"+f"(d[2]),"+f"(d[3]),"+f"(d[4]),"+f"(d[5]),"+f"(d[6]),"+f"(d[7]),"+f"(d[8]),"+f"(d[9]),"+f"(d[10]),"+f"(d[11]),"+f"(d[12]),"+f"(d[13]),"+f"(d[14]),"+f"(d[15]),"+f"(d[16]),"+f"(d[17]),"+f"(d[18]),"+f"(d[19]),"+f"(d[20]),"+f"(d[21]),"+f"(d[22]),"+f"(d[23]),"+f"(d[24]),"+f"(d[25]),"+f"(d[26]),"+f"(d[27]),"+f"(d[28]),"+f"(d[29]),"+f"(d[30]),"+f"(d[31]),"+f"(d[32]),"+f"(d[33]),"+f"(d[34]),"+f"(d[35]),"+f"(d[36]),"+f"(d[37]),"+f"(d[38]),"+f"(d[39]),"+f"(d[40]),"+f"(d[41]),"+f"(d[42]),"+f"(d[43]),"+f"(d[44]),"+f"(d[45]),"+f"(d[46]),"+f"(d[47]) : "r"(a0), "r"(a1), "r"(a2), "r"(a3), "l"(db));
}
template<> __device__ __forceinline__ void wg_rs<88>(float (&d)[64], uint32_t a0, uint32_t a1, uint32_t a2, uint32_t a3, uint64_t db) {
  asm volatile("{.reg .pred p; setp.ne.b32 p, 1, 0; wgmma.mma_async.sync.aligned.m64n88k16.f32.bf16.bf16 {%0,%1,%2,%3,%4,%5,%6,%7,%8,%9,%10,%11,%12,%13,%14,%15,%16,%17,%18,%19,%20,%21,%22,%23,%24,%25,%26,%27,%28,%29,%30,%31,%32,%33,%34,%35,%36,%37,%38,%39,%40,%41,%42,%43}, {%44,%45,%46,%47}, %48, p, 1, 1, 0;}"
    : "+f"(d[0]),"+f"(d[1]),"+f"(d[2]),"+f"(d[3]),"+f"(d[4]),"+f"(d[5]),"+f"(d[6]),"+f"(d[7]),"+f"(d[8]),"+f"(d[9]),"+f"(d[10]),"+f"(d[11]),"+f"(d[12]),"+f"(d[13]),"+f"(d[14]),"+f"(d[15]),"+f"(d[16]),"+f"(d[17]),"+f"(d[18]),"+f"(d[19]),"+f"(d[20]),"+f"(d[21]),"+f"(d[22]),"+f"(d[23]),"+f"(d[24]),"+f"(d[25]),"+f"(d[26]),"+f"(d[27]),"+f"(d[28]),"+f"(d[29]),"+f"(d[30]),"+f"(d[31]),"+f"(d[32]),"+f"(d[33]),"+f"(d[34]),"+f"(d[35]),"+f"(d[36]),"+f"(d[37]),"+f"(d[38]),"+f"(d[39]),"+f"(d[40]),"+f"(d[41]),"+f"(d[42]),"+f"(d[43]) : "r"(a0), "r"(a1), "r"(a2), "r"(a3), "l"(db));
}
template<> __device__ __forceinline__ void wg_rs<80>(float (&d)[64], uint32_t a0, uint32_t a1, uint32_t a2, uint32_t a3, uint64_t db) {
  asm volatile("{.reg .pred p; setp.ne.b32 p, 1, 0; wgmma.mma_async.sync.aligned.m64n80k16.f32.bf16.bf16 {%0,%1,%2,%3,%4,%5,%6,%7,%8,%9,%10,%11,%12,%13,%14,%15,%16,%17,%18,%19,%20,%21,%22,%23,%24,%25,%26,%27,%28,%29,%30,%31,%32,%33,%34,%35,%36,%37,%38,%39}, {%40,%41,%42,%43}, %44, p, 1, 1, 0;}"
    : "+f"(d[0]),"+f"(d[1]),"+f"(d[2]),"+f"(d[3]),"+f"(d[4]),"+f"(d[5]),"+f"(d[6]),"+f"(d[7]),"+f"(d[8]),"+f"(d[9]),"+f"(d[10]),"+f"(d[11]),"+f"(d[12]),"+f"(d[13]),"+f"(d[14]),"+f"(d[15]),"+f"(d[16]),"+f"(d[17]),"+f"(d[18]),"+f"(d[19]),"+f"(d[20]),"+f"(d[21]),"+f"(d[22]),"+f"(d[23]),"+f"(d[24]),"+f"(d[25]),"+f"(d[26]),"+f"(d[27]),"+f"(d[28]),"+f"(d[29]),"+f"(d[30]),"+f"(d[31]),"+f"(d[32]),"+f"(d[33]),"+f"(d[34]),"+f"(d[35]),"+f"(d[36]),"+f"(d[37]),"+f"(d[38]),"+f"(d[39]) : "r"(a0), "r"(a1), "r"(a2), "r"(a3), "l"(db));
}
template<> __device__ __forceinline__ void wg_rs<72>(float (&d)[64], uint32_t a0, uint32_t a1, uint32_t a2, uint32_t a3, uint64_t db) {
  asm volatile("{.reg .pred p; setp.ne.b32 p, 1, 0; wgmma.mma_async.sync.aligned.m64n72k16.f32.bf16.bf16 {%0,%1,%2,%3,%4,%5,%6,%7,%8,%9,%10,%11,%12,%13,%14,%15,%16,%17,%18,%19,%20,%21,%22,%23,%24,%25,%26,%27,%28,%29,%30,%31,%32,%33,%34,%35}, {%36,%37,%38,%39}, %40, p, 1, 1, 0;}"
    : "+f"(d[0]),"+f"(d[1]),"+f"(d[2]),"+f"(d[3]),"+f"(d[4]),"+f"(d[5]),"+f"(d[6]),"+f"(d[7]),"+f"(d[8]),"+f"(d[9]),"+f"(d[10]),"+f"(d[11]),"+f"(d[12]),"+f"(d[13]),"+f"(d[14]),"+f"(d[15]),"+f"(d[16]),"+f"(d[17]),"+f"(d[18]),"+f"(d[19]),"+f"(d[20]),"+f"(d[21]),"+f"(d[22]),"+f"(d[23]),"+f"(d[24]),"+f"(d[25]),"+f"(d[26]),"+f"(d[27]),"+f"(d[28]),"+f"(d[29]),"+f"(d[30]),"+f"(d[31]),"+f"(d[32]),"+f"(d[33]),"+f"(d[34]),"+f"(d[35]) : "r"(a0), "r"(a1), "r"(a2), "r"(a3), "l"(db));
}
template<> __device__ __forceinline__ void wg_rs<64>(float (&d)[64], uint32_t a0, uint32_t a1, uint32_t a2, uint32_t a3, uint64_t db) {
  asm volatile("{.reg .pred p; setp.ne.b32 p, 1, 0; wgmma.mma_async.sync.aligned.m64n64k16.f32.bf16.bf16 {%0,%1,%2,%3,%4,%5,%6,%7,%8,%9,%10,%11,%12,%13,%14,%15,%16,%17,%18,%19,%20,%21,%22,%23,%24,%25,%26,%27,%28,%29,%30,%31}, {%32,%33,%34,%35}, %36, p, 1, 1, 0;}"
    : "+f"(d[0]),"+f"(d[1]),"+f"(d[2]),"+f"(d[3]),"+f"(d[4]),"+f"(d[5]),"+f"(d[6]),"+f"(d[7]),"+f"(d[8]),"+f"(d[9]),"+f"(d[10]),"+f"(d[11]),"+f"(d[12]),"+f"(d[13]),"+f"(d[14]),"+f"(d[15]),"+f"(d[16]),"+f"(d[17]),"+f"(d[18]),"+f"(d[19]),"+f"(d[20]),"+f"(d[21]),"+f"(d[22]),"+f"(d[23]),"+f"(d[24]),"+f"(d[25]),"+f"(d[26]),"+f"(d[27]),"+f"(d[28]),"+f"(d[29]),"+f"(d[30]),"+f"(d[31]) : "r"(a0), "r"(a1), "r"(a2), "r"(a3), "l"(db));
}
__device__ __forceinline__ void wg_rs_first(float (&d)[64], uint32_t a0, uint32_t a1, uint32_t a2, uint32_t a3, uint64_t db) {
  asm volatile("{.reg .pred p; setp.ne.b32 p, 0, 0; wgmma.mma_async.sync.aligned.m64n128k16.f32.bf16.bf16 {%0,%1,%2,%3,%4,%5,%6,%7,%8,%9,%10,%11,%12,%13,%14,%15,%16,%17,%18,%19,%20,%21,%22,%23,%24,%25,%26,%27,%28,%29,%30,%31,%32,%33,%34,%35,%36,%37,%38,%39,%40,%41,%42,%43,%44,%45,%46,%47,%48,%49,%50,%51,%52,%53,%54,%55,%56,%57,%58,%59,%60,%61,%62,%63}, {%64,%65,%66,%67}, %68, p, 1, 1, 0;}"
    : "=f"(d[0]),"=f"(d[1]),"=f"(d[2]),"=f"(d[3]),"=f"(d[4]),"=f"(d[5]),"=f"(d[6]),"=f"(d[7]),"=f"(d[8]),"=f"(d[9]),"=f"(d[10]),"=f"(d[11]),"=f"(d[12]),"=f"(d[13]),"=f"(d[14]),"=f"(d[15]),"=f"(d[16]),"=f"(d[17]),"=f"(d[18]),"=f"(d[19]),"=f"(d[20]),"=f"(d[21]),"=f"(d[22]),"=f"(d[23]),"=f"(d[24]),"=f"(d[25]),"=f"(d[26]),"=f"(d[27]),"=f"(d[28]),"=f"(d[29]),"=f"(d[30]),"=f"(d[31]),"=f"(d[32]),"=f"(d[33]),"=f"(d[34]),"=f"(d[35]),"=f"(d[36]),"=f"(d[37]),"=f"(d[38]),"=f"(d[39]),"=f"(d[40]),"=f"(d[41]),"=f"(d[42]),"=f"(d[43]),"=f"(d[44]),"=f"(d[45]),"=f"(d[46]),"=f"(d[47]),"=f"(d[48]),"=f"(d[49]),"=f"(d[50]),"=f"(d[51]),"=f"(d[52]),"=f"(d[53]),"=f"(d[54]),"=f"(d[55]),"=f"(d[56]),"=f"(d[57]),"=f"(d[58]),"=f"(d[59]),"=f"(d[60]),"=f"(d[61]),"=f"(d[62]),"=f"(d[63]) : "r"(a0), "r"(a1), "r"(a2), "r"(a3), "l"(db));
}
__device__ __forceinline__ void wg_tt128(float (&d)[64], uint64_t da, uint64_t db, int sc) {
  asm volatile("{.reg .pred p; setp.ne.b32 p, %66, 0; wgmma.mma_async.sync.aligned.m64n128k16.f32.bf16.bf16 {%0,%1,%2,%3,%4,%5,%6,%7,%8,%9,%10,%11,%12,%13,%14,%15,%16,%17,%18,%19,%20,%21,%22,%23,%24,%25,%26,%27,%28,%29,%30,%31,%32,%33,%34,%35,%36,%37,%38,%39,%40,%41,%42,%43,%44,%45,%46,%47,%48,%49,%50,%51,%52,%53,%54,%55,%56,%57,%58,%59,%60,%61,%62,%63}, %64, %65, p, 1, 1, 1, 1;}"
    : "+f"(d[0]),"+f"(d[1]),"+f"(d[2]),"+f"(d[3]),"+f"(d[4]),"+f"(d[5]),"+f"(d[6]),"+f"(d[7]),"+f"(d[8]),"+f"(d[9]),"+f"(d[10]),"+f"(d[11]),"+f"(d[12]),"+f"(d[13]),"+f"(d[14]),"+f"(d[15]),"+f"(d[16]),"+f"(d[17]),"+f"(d[18]),"+f"(d[19]),"+f"(d[20]),"+f"(d[21]),"+f"(d[22]),"+f"(d[23]),"+f"(d[24]),"+f"(d[25]),"+f"(d[26]),"+f"(d[27]),"+f"(d[28]),"+f"(d[29]),"+f"(d[30]),"+f"(d[31]),"+f"(d[32]),"+f"(d[33]),"+f"(d[34]),"+f"(d[35]),"+f"(d[36]),"+f"(d[37]),"+f"(d[38]),"+f"(d[39]),"+f"(d[40]),"+f"(d[41]),"+f"(d[42]),"+f"(d[43]),"+f"(d[44]),"+f"(d[45]),"+f"(d[46]),"+f"(d[47]),"+f"(d[48]),"+f"(d[49]),"+f"(d[50]),"+f"(d[51]),"+f"(d[52]),"+f"(d[53]),"+f"(d[54]),"+f"(d[55]),"+f"(d[56]),"+f"(d[57]),"+f"(d[58]),"+f"(d[59]),"+f"(d[60]),"+f"(d[61]),"+f"(d[62]),"+f"(d[63]) : "l"(da), "l"(db), "r"(sc));
}
__device__ __forceinline__ void wg_tt64(float (&d)[64], uint64_t da, uint64_t db, int sc) {
  asm volatile("{.reg .pred p; setp.ne.b32 p, %34, 0; wgmma.mma_async.sync.aligned.m64n64k16.f32.bf16.bf16 {%0,%1,%2,%3,%4,%5,%6,%7,%8,%9,%10,%11,%12,%13,%14,%15,%16,%17,%18,%19,%20,%21,%22,%23,%24,%25,%26,%27,%28,%29,%30,%31}, %32, %33, p, 1, 1, 1, 1;}"
    : "+f"(d[0]),"+f"(d[1]),"+f"(d[2]),"+f"(d[3]),"+f"(d[4]),"+f"(d[5]),"+f"(d[6]),"+f"(d[7]),"+f"(d[8]),"+f"(d[9]),"+f"(d[10]),"+f"(d[11]),"+f"(d[12]),"+f"(d[13]),"+f"(d[14]),"+f"(d[15]),"+f"(d[16]),"+f"(d[17]),"+f"(d[18]),"+f"(d[19]),"+f"(d[20]),"+f"(d[21]),"+f"(d[22]),"+f"(d[23]),"+f"(d[24]),"+f"(d[25]),"+f"(d[26]),"+f"(d[27]),"+f"(d[28]),"+f"(d[29]),"+f"(d[30]),"+f"(d[31]) : "l"(da), "l"(db), "r"(sc));
}
__device__ __forceinline__ void wg_tt32(float (&d)[64], uint64_t da, uint64_t db, int sc) {
  asm volatile("{.reg .pred p; setp.ne.b32 p, %18, 0; wgmma.mma_async.sync.aligned.m64n32k16.f32.bf16.bf16 {%0,%1,%2,%3,%4,%5,%6,%7,%8,%9,%10,%11,%12,%13,%14,%15}, %16, %17, p, 1, 1, 1, 1;}"
    : "+f"(d[0]),"+f"(d[1]),"+f"(d[2]),"+f"(d[3]),"+f"(d[4]),"+f"(d[5]),"+f"(d[6]),"+f"(d[7]),"+f"(d[8]),"+f"(d[9]),"+f"(d[10]),"+f"(d[11]),"+f"(d[12]),"+f"(d[13]),"+f"(d[14]),"+f"(d[15]) : "l"(da), "l"(db), "r"(sc));
}
__device__ __forceinline__ void wg_g1(float (&d)[88], uint64_t da, uint64_t db, int sc) {
  asm volatile("{.reg .pred p; setp.ne.b32 p, %90, 0; wgmma.mma_async.sync.aligned.m64n176k16.f32.bf16.bf16 {%0,%1,%2,%3,%4,%5,%6,%7,%8,%9,%10,%11,%12,%13,%14,%15,%16,%17,%18,%19,%20,%21,%22,%23,%24,%25,%26,%27,%28,%29,%30,%31,%32,%33,%34,%35,%36,%37,%38,%39,%40,%41,%42,%43,%44,%45,%46,%47,%48,%49,%50,%51,%52,%53,%54,%55,%56,%57,%58,%59,%60,%61,%62,%63,%64,%65,%66,%67,%68,%69,%70,%71,%72,%73,%74,%75,%76,%77,%78,%79,%80,%81,%82,%83,%84,%85,%86,%87}, %88, %89, p, 1, 1, 1, 0;}"
    : "+f"(d[0]),"+f"(d[1]),"+f"(d[2]),"+f"(d[3]),"+f"(d[4]),"+f"(d[5]),"+f"(d[6]),"+f"(d[7]),"+f"(d[8]),"+f"(d[9]),"+f"(d[10]),"+f"(d[11]),"+f"(d[12]),"+f"(d[13]),"+f"(d[14]),"+f"(d[15]),"+f"(d[16]),"+f"(d[17]),"+f"(d[18]),"+f"(d[19]),"+f"(d[20]),"+f"(d[21]),"+f"(d[22]),"+f"(d[23]),"+f"(d[24]),"+f"(d[25]),"+f"(d[26]),"+f"(d[27]),"+f"(d[28]),"+f"(d[29]),"+f"(d[30]),"+f"(d[31]),"+f"(d[32]),"+f"(d[33]),"+f"(d[34]),"+f"(d[35]),"+f"(d[36]),"+f"(d[37]),"+f"(d[38]),"+f"(d[39]),"+f"(d[40]),"+f"(d[41]),"+f"(d[42]),"+f"(d[43]),"+f"(d[44]),"+f"(d[45]),"+f"(d[46]),"+f"(d[47]),"+f"(d[48]),"+f"(d[49]),"+f"(d[50]),"+f"(d[51]),"+f"(d[52]),"+f"(d[53]),"+f"(d[54]),"+f"(d[55]),"+f"(d[56]),"+f"(d[57]),"+f"(d[58]),"+f"(d[59]),"+f"(d[60]),"+f"(d[61]),"+f"(d[62]),"+f"(d[63]),"+f"(d[64]),"+f"(d[65]),"+f"(d[66]),"+f"(d[67]),"+f"(d[68]),"+f"(d[69]),"+f"(d[70]),"+f"(d[71]),"+f"(d[72]),"+f"(d[73]),"+f"(d[74]),"+f"(d[75]),"+f"(d[76]),"+f"(d[77]),"+f"(d[78]),"+f"(d[79]),"+f"(d[80]),"+f"(d[81]),"+f"(d[82]),"+f"(d[83]),"+f"(d[84]),"+f"(d[85]),"+f"(d[86]),"+f"(d[87]) : "l"(da), "l"(db), "r"(sc));
}

struct Params { const __nv_bfloat16 *x, *logA, *Aim, *Cr, *Ci, *logdt, *Dskip, *Wd; uint4* xnT; float2* st; uint2* S; unsigned* flags; };
struct Maps { CUtensorMap x[2], xo, out, wg, wu, wd, hst[2], hld, xt; };

__device__ __forceinline__ void conv_channel(uint32_t cb, int w, int lane, uint32_t (&res)[8], uint32_t bar_free) {
    const int q = lane & 3, g = lane >> 2, gam = g >> 2;
    float acc[64];
    uint4 a[4][4];
    const uint32_t t0 = cb + CH_T + (uint32_t)(14 + 4 * w + (g & 3) + 32 * gam - 2 * q) * 80u;
    #pragma unroll
    for (int s4 = 0; s4 < 4; s4++) {
        a[s4][0] = lds128(t0 + s4 * 16);
        a[s4][1] = lds128(t0 + 16 * 80 + s4 * 16);
        a[s4][2] = lds128(t0 - 8 * 80 + s4 * 16);
        a[s4][3] = lds128(t0 + 8 * 80 + s4 * 16);
    }
    const uint32_t l0 = FU(ldsf(t0 + 64)), l1 = FU(ldsf(t0 + 16 * 80 + 64)), l2 = FU(ldsf(t0 - 8 * 80 + 64)), l3 = FU(ldsf(t0 + 8 * 80 + 64));
    const uint64_t dU = mkdesc(cb + CH_U, UPLANE, 128, 0);
    WG_FENCE();
#define CT(N, s, c) wg_rs<N>(acc, a[(s) >> 2][0].c, a[(s) >> 2][1].c, a[(s) >> 2][2].c, a[(s) >> 2][3].c, dU + 4 * (s))
    wg_rs_first(acc, a[0][0].x, a[0][1].x, a[0][2].x, a[0][3].x, dU);
    CT(128, 1, y); CT(120, 2, z); CT(120, 3, w);
    CT(112, 4, x); CT(112, 5, y); CT(104, 6, z); CT(104, 7, w);
    CT(96, 8, x);  CT(96, 9, y);  CT(88, 10, z); CT(88, 11, w);
    CT(80, 12, x); CT(80, 13, y); CT(72, 14, z); CT(72, 15, w);
#undef CT
    wg_rs<64>(acc, l0, l1, l2, l3, dU + 64);
    wg_tt64(acc, mkdesc(cb + CH_A3, 128, 512, 0), mkdesc(cb + CH_B3, 128, 256, 0), 1);
    wg_tt32(acc, mkdesc(cb + CH_A3 + 256, 128, 512, 0), mkdesc(cb + CH_B3 + 1024, 128, 256, 0), 1);
    WG_COMMIT();
    WG_WAIT(0);
    fence_acc(acc);
    if (bar_free && lane == 0) mbar_arrive(bar_free);
    const int src1 = (lane & ~3) | ((q + 1) & 3);
    float E[16][2];
    #pragma unroll
    for (int j = 0; j < 16; j++) {
        const float nxt = (j < 15) ? acc[4 * (j + 1) + 2] : 0.f;
        const float sup = (q == 0) ? nxt : acc[4 * j + 2];
        const float v = __shfl_sync(0xffffffffu, sup, src1);
        E[j][0] = acc[4 * j] + acc[4 * j + 3];
        E[j][1] = acc[4 * j + 1] + v;
    }
    const int src2 = gam ? ((lane & 12) | ((q + 3) & 3)) : (16 | (lane & 12) | ((q + 1) & 3));
    const bool c1 = gam && q != 0, c2 = gam && q == 0;
    #pragma unroll
    for (int a2 = 0; a2 < 8; a2++) {
        float y[2];
        #pragma unroll
        for (int e = 0; e < 2; e++) {
            const float sup = c1 ? E[2 * a2][e] : E[2 * a2 + 1][e];
            const float nxt = (a2 < 7) ? E[2 * a2 + 2][e] : 0.f;
            const float keep = c2 ? nxt : (c1 ? E[2 * a2 + 1][e] : E[2 * a2][e]);
            y[e] = keep + __shfl_sync(0xffffffffu, sup, src2);
        }
        res[a2] = pack2(y[1], y[0]);
    }
}

__device__ __forceinline__ void layer_norm(uint32_t sb, int w, int lane, const __nv_bfloat16* x) {
    const uint32_t bars = sb + OFF_BAR;
    const int c = blockIdx.x;
    {
        if (elect_one()) {
            mbar_expect(bars + 8 * B_LNX, 4096);
            #pragma unroll
            for (int i = 0; i < 4; i++)
                bulk_load(sb + OFF_LN + (w + 4 * i) * 1040, x + (16 * (c & ~1) + 8 * (c & 1) + 16 + w + 4 * (i & 1) - 8 * (i & 2)) * DM, 1024, bars + 8 * B_LNX);
        }
        mbar_wait(bars + 8 * B_LNX, 0);
        STAMP(34);
        {
            const int r = w + 4 * (lane >> 3);
            const uint32_t r0 = sb + OFF_LN + r * 1040, ra = r0 + (lane & 7) * 16;
            const float pv = bf_lo(FU(ldsf(r0)));
            float s0 = 0.f, s1 = 0.f, a0 = 0.f, a1 = 0.f;
            uint4 nx = lds128(ra);
            #pragma unroll 1
            for (int k = 128; k <= 1024; k += 128) {
                const uint32_t v[4] = {nx.x, nx.y, nx.z, nx.w};
                nx = lds128(ra + (k & 1023));
                #pragma unroll
                for (int i = 0; i < 4; i++) { const float t0 = bf_lo(v[i]) - pv, t1 = bf_hi(v[i]) - pv; s0 += t0; s1 += t1; a0 = fmaf(t0, t0, a0); a1 = fmaf(t1, t1, a1); }
            }
            s0 += s1; a0 += a1;
            #pragma unroll
            for (int o = 4; o; o >>= 1) { s0 += __shfl_xor_sync(0xffffffffu, s0, o); a0 += __shfl_xor_sync(0xffffffffu, a0, o); }
            s0 *= 1.f / DM;
            const float m = pv + s0, var = fmaxf(fmaf(-s0, s0, a0 * (1.f / DM)), 0.f);
            float sd, ri;
            asm("sqrt.approx.ftz.f32 %0, %1;" : "=f"(sd) : "f"(bf_round(bf_round(var) + 1e-5f)));
            asm("rcp.approx.ftz.f32 %0, %1;" : "=f"(ri) : "f"(bf_round(sd)));
            const uint32_t m2 = pack2(m, m);
            if ((lane & 7) == 0) {
                sts64(sb + OFF_CSUM + r * 8, m2 & 0xffff0000u, FU(0.5f * ri));
            }
            #pragma unroll 1
            for (int k = 128; k <= 1024; k += 128) {
                uint32_t v[4] = {nx.x, nx.y, nx.z, nx.w};
                nx = lds128(ra + (k & 1023));
                #pragma unroll
                for (int i = 0; i < 4; i++) {
                    uint32_t dv; asm("sub.rn.bf16x2 %0, %1, %2;" : "=r"(dv) : "r"(v[i]), "r"(m2));
                    v[i] = pack2(bf_lo(dv) * ri, bf_hi(dv) * ri);
                }
                sts128(ra + k - 128, v[0], v[1], v[2], v[3]);
            }
        }
        STAMP(62);
        bar_sync(4);
        {
            const uint32_t ad = sb + OFF_LN + (4 * ((lane & 7) >> 1) + (lane & 1) + 2 * ((lane >> 3) & 1)) * 1040 + (16 * w + (lane >> 4)) * 16;
            uint32_t r[8][4];
            #pragma unroll
            for (int i = 0; i < 8; i++)
                asm volatile("ldmatrix.sync.aligned.m8n8.x4.trans.shared.b16 {%0,%1,%2,%3}, [%4];" : "=r"(r[i][0]), "=r"(r[i][1]), "=r"(r[i][2]), "=r"(r[i][3]) : "r"(ad + 32 * i) : "memory");
            bar_sync(4);
            const uint32_t od = sb + OFF_LN + w * 4096 + lane * 8;
            #pragma unroll
            for (int i = 0; i < 8; i++) { sts64(od + i * 512, r[i][0], r[i][1]); sts64(od + i * 512 + 256, r[i][2], r[i][3]); }
        }
        fence_async_smem();
        mbar_arrive(bars + 8 * B_LN);
        STAMP(16);
    }
}

__device__ __forceinline__ void consumer(uint32_t sb, int warp, const Params& P, const Maps& M) {
    const int V = warp >> 2, w = warp & 3, lane = threadIdx.x & 31, q = lane & 3, g = lane >> 2;
    const int c = blockIdx.x;
    const uint32_t bars = sb + OFF_BAR, xb = sb + OFF_X + V * 2 * XBUF;
    {
        float ag[88], au[88];
        if (V == 0) {
            sts128(xb + (w >> 1) * XBUF + 168 * 128 + (threadIdx.x & 63) * 16, 0x3f803f80u, 0x3f803f80u, 0x3f803f80u, 0x3f803f80u);
            fence_async_smem();
            bar_sync(1);
        } else {
            if (c < 128) layer_norm(sb, w, lane, P.x); else mbar_arrive(bars + 8 * B_LN);
            mbar_wait(bars + 8 * B_GO, 0);
        }
        define_acc(ag); define_acc(au);
        #pragma unroll 1
        for (int st = 0; st < 8; st++) {
            if (st + LAG * V == HOLD0 || st + LAG * V == HOLD1) mbar_wait(bars + 8 * (B_K + (st + LAG * V == HOLD1)), 0);
            mbar_wait(bars + 8 * (B_FULLW + (st & 3)), st >> 2);
            mbar_wait(bars + 8 * (B_FULLX + 2 * V + (st & 1)), (st >> 1) & 1);
            STAMP(40 + 8 * V + st);
            const uint64_t dG = mkdesc(sb + OFF_W + (st & 3) * 16384, 0, 1024, 1);
            const uint64_t dX = mkdesc(xb + (st & 1) * XBUF, 16, 1024, 1);
            WG_FENCE();
            #pragma unroll
            for (int k = 0; k < 4; k++) {
                wg_g1(ag, dG + k * 128, dX + k * 2, k ? 1 : st);
                wg_g1(au, dG + 512 + k * 128, dX + k * 2, k ? 1 : st);
            }
            WG_COMMIT();
            WG_WAIT(1);
            if (lane == 0 && st > 0) {
                mbar_arrive(bars + 8 * (B_EMPTYW + ((st - 1) & 3)));
                mbar_arrive(bars + 8 * (B_EMPTYX + 2 * V + ((st - 1) & 1)));
                if (warp < 4 && st == LAG) mbar_arrive(bars + 8 * B_GO);
            }
        }
        WG_WAIT(0);
        fence_acc(ag); fence_acc(au);
        if (lane == 0) { mbar_arrive(bars + 8 * (B_EMPTYW + 3)); mbar_arrive(bars + 8 * (B_EMPTYX + 2 * V + 1)); }
        STAMP(8 * V + 1);
        float cg0 = ag[84], cg1 = ag[86], cu0 = au[84], cu1 = au[86];
        const uint32_t ca = sb + OFF_CSUM + (8 * w + g) * 16;
        if (V == 0) { sts128(ca, FU(cg0), FU(cg1), FU(cu0), FU(cu1)); mbar_arrive(bars + 8 * B_CS); }
        else { mbar_wait(bars + 8 * B_CS, 0); const uint4 t = lds128(ca); cg0 = UF(t.x); cg1 = UF(t.y); cu0 = UF(t.z); cu1 = UF(t.w); }
        mbar_wait(bars + 8 * B_STATS, 0);
        mbar_wait(bars + 8 * (B_EMPTYX + 2 * V), 1);
        STAMP(13 + V);
        const uint32_t hs = xb + (2 * w + ((lane >> 3) & 1)) * (2688 + 128 * V) + (lane >> 4) * 128 + (lane & 7) * 16;
        const uint32_t sa = sb + OFF_ST + (168 * V + 2 * q) * 8;
        #pragma unroll
        for (int j = 0; j < 22; j += 2) {
            uint32_t o[4];
            #pragma unroll
            for (int jj = 0; jj < 2; jj++) {
                const uint4 sv = lds128(sa + (j + jj) * 64);
                float hv[4];
                #pragma unroll
                for (int i = 0; i < 4; i++) {
                    const float m = UF((i & 1) ? sv.z : sv.x);
                    const float gh = fmaf(-m, (i & 2) ? cg1 : cg0, ag[4 * (j + jj) + i]) * UF((i & 1) ? sv.w : sv.y);
                    const float p = gh * fmaf(-m, (i & 2) ? cu1 : cu0, au[4 * (j + jj) + i]);
                    hv[i] = fmaf(p, tanh_fast(gh), p);
                }
                o[2 * jj] = pack2(hv[0], hv[1]); o[2 * jj + 1] = pack2(hv[2], hv[3]);
            }
            uint32_t ad = hs + j * 128;
            if (j == 20 && V == 0 && lane >= 16) ad = xb + 21504 + (lane & 7) * 16;
            stsm4(ad, o[0], o[1], o[2], o[3]);
        }
        fence_async_smem();
        mbar_arrive(bars + 8 * (B_EPI + V));
        STAMP(8 * V + 2);
    }
    if (c >= 128) return;
    {
        uint32_t r0[8], r1[8];
        #pragma unroll
        for (int i = 0; i < 8; i++) asm volatile("" : "=r"(r1[i]));
        #pragma unroll 1
        for (int e = 0; e < 2; e++) {
            #pragma unroll
            for (int i = 0; i < 8; i++) r0[i] = r1[i];
            mbar_wait(bars + 8 * (B_CONV + 2 * V + e), 0);
            conv_channel(sb + OFF_CONV + (2 * V + e) * CH_STRIDE, w, lane, r1, (V + e == 0) ? bars + 8 * B_CH0 : 0);
            if (e == 0) STAMP(8 * V + 3);
        }
        const int gam = g >> 2, qq = gam ? ((q + 3) & 3) : q;
        const uint32_t sp = sb + OFF_CONV + (2 * V + 1) * CH_STRIDE + ((63 - 4 * gam - qq) * 16 + 4 * w + (g & 3)) * 8;
        bar_sync(3 + V);
        #pragma unroll
        for (int a2 = 0; a2 < 8; a2++) sts64(sp - a2 * 1024, r0[a2], r1[a2]);
        fence_async_smem();
        mbar_arrive(bars + 8 * (B_SIG + V));
        STAMP(8 * V + 4);
    }
    if (V == 1) return;
    {
        const int tau = c >> 2, dg = c & 3;
        const uint32_t row = 8 * (w & 1) + 32 * (w >> 1);
        float acc[64];
        define_acc(acc);
        uint2 sv[16];
        #pragma unroll
        for (int i = 0; i < 16; i++) asm volatile("" : "=r"(sv[i].x), "=r"(sv[i].y));
        const float rr0 = __ldcg(&P.st[64 * tau + row + g].y), rr1 = __ldcg(&P.st[64 * tau + row + g + 16].y);
        mbar_wait(bars + 8 * B_FULLD, 0);
        STAMP(5);
        uint64_t dB = mkdesc(sb + wd_slot(0), 8192, 1024, 1), dA = mkdesc(sb + h_slot(0), 1024, 128, 0);
        #pragma unroll 1
        for (int st = 0; st < 21; st++) {
            WG_FENCE();
            wg_tt128(acc, dA, dB, st);
            wg_tt128(acc, dA + 128, dB + 128, 1);
            wg_tt128(acc, dA + 256, dB + 256, 1);
            wg_tt128(acc, dA + 384, dB + 384, 1);
            WG_COMMIT();
            const int sd = (st + 1) & 7;
            const uint32_t nb = bars + 8 * (B_FULLD + sd), np = ((st + 1) >> 3) & 1;
            uint32_t ok;
            asm volatile("{.reg .pred p; mbarrier.test_wait.parity.shared::cta.b64 p, [%1], %2; selp.u32 %0, 1, 0, p;}" : "=r"(ok) : "r"(nb), "r"(np) : "memory");
            dB = mkdesc(sb + wd_slot(sd), 8192, 1024, 1); dA = mkdesc(sb + h_slot(sd), 1024, 128, 0);
            if (st == 14) {
                mbar_wait(bars + 8 * B_S, 0);
                const uint2* sp = P.S + (dg * 64 + q) * 1024 + (2 * tau) * 16 + (row >> 1) + 4 * (w & 1) + g;
                #pragma unroll
                for (int j = 0; j < 16; j++)
                    asm volatile("ld.global.cg.v2.b32 {%0,%1}, [%2];" : "=r"(sv[j].x), "=r"(sv[j].y) : "l"(sp + j * 4096));
            }
            WG_WAIT(1);
            if (lane == 0 && st > 0) mbar_arrive(bars + 8 * (B_EMPTYD + ((st - 1) & 7)));
            if (!ok) mbar_wait(nb, np);
            if (w == 0) STAMP2(20 + st);
        }
        WG_FENCE();
        wg_tt128(acc, dA, dB, 1);
        wg_tt128(acc, dA + 128, dB + 128, 1);
        WG_COMMIT();
        WG_WAIT(0);
        fence_acc(acc);
        STAMP(6);
        mbar_wait(bars + 8 * B_XO, 0);
        const uint32_t xo = sb + OFF_CONV + (row + (lane & 7) + 16 * ((lane >> 3) & 1)) * 128;
        #pragma unroll
        for (int j = 0; j < 16; j += 2) {
            const uint32_t ad = xo + (j >> 3) * 8192 + ((((j & 7) + (lane >> 4)) ^ (lane & 7)) << 4);
            uint32_t xr[4];
            asm volatile("ldmatrix.sync.aligned.m8n8.x4.shared.b16 {%0,%1,%2,%3}, [%4];" : "=r"(xr[0]), "=r"(xr[1]), "=r"(xr[2]), "=r"(xr[3]) : "r"(ad));
            #pragma unroll
            for (int i = 0; i < 4; i++) {
                const int jj = j + (i >> 1), hh = i & 1;
                const float f0 = acc[4 * jj + 2 * hh] * (hh ? rr1 : rr0), f1 = acc[4 * jj + 2 * hh + 1] * (hh ? rr1 : rr0);
                const uint32_t G = pack2(fmaf(f0, tanh_fast(f0), f0), fmaf(f1, tanh_fast(f1), f1));
                const uint32_t s2 = __byte_perm(sv[jj].x, sv[jj].y, hh ? 0x7632 : 0x5410);
                asm("fma.rn.bf16x2 %0, %1, %2, %0;" : "+r"(xr[i]) : "r"(s2), "r"(G));
            }
            stsm4(ad, xr[0], xr[1], xr[2], xr[3]);
        }
        fence_async_smem();
        bar_sync(1);
        if (w == 0 && elect_one()) {
            #pragma unroll
            for (int i = 0; i < 2; i++)
                asm volatile("cp.async.bulk.tensor.2d.global.shared::cta.bulk_group [%0, {%2, %3}], [%1];"
                    :: "l"(&M.out), "r"(sb + OFF_CONV + i * 8192), "r"(dg * 128 + 64 * i), "r"(tau * 64) : "memory");
            asm volatile("cp.async.bulk.commit_group; cp.async.bulk.wait_group.read 0;" ::: "memory");
        }
        STAMP(7); GSTAMP(23);
    }
}

__device__ __forceinline__ float2 cexp_p(float re2, float im, float p) {
    float sn, cs;
    const float mag = ex2(re2 * p), th = im * p;
    asm("sin.approx.ftz.f32 %0, %1;" : "=f"(sn) : "f"(th));
    asm("cos.approx.ftz.f32 %0, %1;" : "=f"(cs) : "f"(th));
    return make_float2(mag * cs, mag * sn);
}
__device__ __forceinline__ unsigned short ldu16(const void* p) { unsigned short v; asm volatile("ld.global.nc.u16 %0, [%1];" : "=h"(v) : "l"(p)); return v; }
__device__ __forceinline__ void ldsm4(uint32_t (&r)[4], uint32_t a) {
    asm volatile("ldmatrix.sync.aligned.m8n8.x4.shared.b16 {%0,%1,%2,%3}, [%4];" : "=r"(r[0]), "=r"(r[1]), "=r"(r[2]), "=r"(r[3]) : "r"(a) : "memory");
}
__device__ __forceinline__ float2 cmul(float2 a, float2 b) { return make_float2(fmaf(a.x, b.x, -a.y * b.y), fmaf(a.x, b.y, a.y * b.x)); }
__device__ __forceinline__ float2 csqr(float2 a) { const float t = a.x * a.y; return make_float2(fmaf(a.x, a.x, -a.y * a.y), t + t); }
__device__ __forceinline__ void mma16816(float (&d)[4], const uint32_t (&a)[4], uint32_t b0, uint32_t b1) {
    asm volatile("mma.sync.aligned.m16n8k16.row.col.f32.bf16.bf16.f32 {%0,%1,%2,%3}, {%4,%5,%6,%7}, {%8,%9}, {%0,%1,%2,%3};"
        : "+f"(d[0]), "+f"(d[1]), "+f"(d[2]), "+f"(d[3]) : "r"(a[0]), "r"(a[1]), "r"(a[2]), "r"(a[3]), "r"(b0), "r"(b1));
}

__device__ __forceinline__ void aux_role(uint32_t sb, int w, const Params& P) {
    const int lane = threadIdx.x & 31, q = lane & 3, g = lane >> 2;
    const int c = blockIdx.x;
    const uint32_t bars = sb + OFF_BAR;
    if (c >= 128) {
        if (lane == 0) { mbar_arrive(bars + 8 * B_K); mbar_arrive(bars + 8 * (B_K + 1)); }
        return;
    }
    {
        const uint32_t cb = sb + OFF_CONV + w * CH_STRIDE;
        const uint32_t sF = cb + CH_A3;
        const int d = 4 * c + w;
        const int po = d * 128 + lane;
        unsigned short la = ldu16(P.logA + po), ai = ldu16(P.Aim + po), cr = ldu16(P.Cr + po), ci = ldu16(P.Ci + po);
        const float ldt = __bfloat162float(P.logdt[d]), dsk = __bfloat162float(P.Dskip[d]);
        float dacc[2][3][4];
        #pragma unroll
        for (int i = 0; i < 24; i++) (&dacc[0][0][0])[i] = 0.f;
        const float dt = bf_round(ex2(ldt * 1.4426950408889634f));
        #pragma unroll 1
        for (int ck = 0; ck < 4; ck++) {
            const uint32_t fa = cb + lane * 4 + (ck & 1) * 8064;
            const float re2 = bf_round(ex2(bf_lo((uint32_t)la) * 1.4426950408889634f)) * dt * -1.4426950408889634f, im = bf_lo((uint32_t)ai) * dt;
            const float2 C = make_float2(bf_lo((uint32_t)cr) * (dt + dt), bf_lo((uint32_t)ci) * -(dt + dt));
            {
                const int pn = po + 32 * min(ck + 1, 3);
                la = ldu16(P.logA + pn); ai = ldu16(P.Aim + pn); cr = ldu16(P.Cr + pn); ci = ldu16(P.Ci + pn);
            }
            const float2 z8 = cexp_p(re2, im, 8.f), y1 = cexp_p(re2, -im, 1.f);
            float2 b0 = make_float2(1.f, 0.f), b1 = cexp_p(re2, im, 64.f), b2 = csqr(b1), b3 = cmul(b2, b1), l0 = C;
            const uint32_t fm = cb + (ck & 1) * 8064 + (lane >> 3) * 144 + (lane & 7) * 16;
#define PK(v) pack2((v).x, (v).y)
            #pragma unroll 1
            for (uint32_t ro = 0; ro < 8 * 144; ro += 144) {
                stsm4(fm + (lane >> 3) * 7 * 144 + ro, PK(b0), PK(b1), PK(b2), PK(b3));
                stsf(fa + 32 * 144 + ro, UF(PK(l0)));
                b0 = cmul(b0, z8); b1 = cmul(b1, z8); b2 = cmul(b2, z8); b3 = cmul(b3, z8); l0 = cmul(l0, y1);
            }
            if (ck < 2) STAMP(56 + 3 * ck);
            const float2 y256 = cexp_p(re2, -im, 256.f), y2 = csqr(y1), y4 = csqr(y2), y8 = make_float2(z8.x, -z8.y);
            const float2 t0 = cmul(C, y256), t1 = cmul(t0, y256), t2 = cmul(t1, y256), t3_ = cmul(t2, y256);
            const float2 u1 = cmul(t0, y2), u2 = cmul(u1, y2), u3 = cmul(u2, y2);
            stsm4(fm + 40 * 144, PK(t0), PK(u1), PK(u2), PK(u3));
            stsm4(fm + 44 * 144, PK(t1), PK(cmul(t1, y4)), PK(t2), PK(cmul(t2, y4)));
            const float2 v0 = cmul(t3_, y8), v1 = cmul(v0, y256), v2 = cmul(v1, y256), v3 = cmul(v2, y256);
            stsm4(fm + 48 * 144, PK(v0), PK(v1), PK(v2), PK(v3));
            stsf(fa + 52 * 144, UF(PK(t3_)));
#undef PK
            if (ck < 2) STAMP(57 + 3 * ck);
            if (ck & 1) {
                uint32_t ln_; asm volatile("mov.u32 %0, %%laneid;" : "=r"(ln_));
                const uint32_t lda = cb + (ln_ & 15) * 144 + (ln_ & 16);
                const uint32_t ldb = cb + (32 + (ln_ & 7)) * 144 + (ln_ >> 3) * 16;
                __syncwarp();
                #pragma unroll
                for (int k2 = 0; k2 < 4; k2++) {
                    const uint32_t ko = (k2 >> 1) * 8064 + (k2 & 1) * 64;
                    uint32_t b[3][4];
                    #pragma unroll
                    for (int t3 = 0; t3 < 3; t3++) ldsm4(b[t3], ldb + t3 * 8 * 144 + ko);
                    #pragma unroll
                    for (int k = 0; k < 2; k++)
                        #pragma unroll
                        for (int mu = 0; mu < 2; mu++) {
                            uint32_t a[4];
                            ldsm4(a, lda + mu * 16 * 144 + ko + k * 32);
                            #pragma unroll
                            for (int t3 = 0; t3 < 3; t3++) mma16816(dacc[mu][t3], a, b[t3][2 * k], b[t3][2 * k + 1]);
                        }
                }
                __syncwarp();
                if (lane == 0) mbar_arrive(bars + 8 * (B_K + (ck >> 1)));
                STAMP(58 + 3 * (ck >> 1));
            }
        }
        STAMP(18);
        const uint32_t sG = cb + CH_G;
        if (lane == 0) dacc[0][0][0] += dsk;
        if (lane < 16) sts128(((lane & 8) ? cb + CH_U + 2048 + (lane & 4) * (UPLANE / 4) : sG + 128 + (lane & 4) * 48) + (lane & 3) * 16, 0, 0, 0, 0);
        {
            const uint32_t f0 = sF + (8 * g + 2 * q) * 4, f1 = sF + ((q < 2) ? 256 + 4 * g + 2 * q : 256 + 2 * g + 64 * q) * 4, st1 = (q < 2) ? 128 : 64;
            const uint32_t ga = sG + ((g & 1) ? 0 : 192) + (63 - (g >> 1) - 32 * q) * 2;
            #pragma unroll
            for (int i = 0; i < 4; i++) {
                const int mu = i >> 1, hh = i & 1;
                sts64(f0 + i * 256, FU(dacc[mu][0][2 * hh]), FU(dacc[mu][0][2 * hh + 1]));
                sts64(f1 + i * st1, FU(dacc[mu][1][2 * hh]), FU(dacc[mu][1][2 * hh + 1]));
                const uint32_t pk = pack2(dacc[mu][2][2 * hh], dacc[mu][2][2 * hh + 1]);
                if (q < 2) { sts16(ga - 8 * i, pk & 0xffff); sts16(ga - 8 * i - 32, pk >> 16); }
            }
            if (lane == 2) stsf(sF + 2048, dacc[0][2][0]);
        }
    }
    bar_sync(2);
    STAMP(19);
    const int rw = lane - 1 + 31 * w, u = min(rw, 77) - 14;
    const uint32_t o0 = CH_A3 + u * 4, o1 = CH_A3 + (128 + ((u + ((u >> 1) & 1)) >> 1)) * 4, o2 = CH_A3 + (256 + ((u + 1 + ((u >> 2) & 1)) >> 2)) * 4;
    const int kap = (lane >> 4) * 8 + ((lane >> 1) & 7), gam = lane & 1, hh = w >> 1, wp = w & 1;
    const uint32_t oa = CH_U + wp * UPLANE + (127 - 4 * kap - 2 * gam - hh) * 16;
    const uint32_t ob = CH_U + (wp ^ 1) * UPLANE + (128 - wp - 4 * kap - 2 * gam - hh) * 16;
    const uint32_t od = CH_A3 + (4 * wp + hh) * 512 + (kap >> 3) * 256 + (kap & 7) * 16 + gam * 8;
    #pragma unroll 1
    for (int k = 0; k < 4; k++) {
        const int ch = 2 * (k & 1) + (k >> 1);
        const uint32_t cb = sb + OFF_CONV + ch * CH_STRIDE;
        if (w < 3) {
            const uint32_t f0 = cb + o0, f1 = cb + o1, f2 = cb + o2;
            float kv[17];
            kv[0] = ldsf(u < 0 ? f1 : f0); if (u < 0) kv[0] = 0.f;
            #pragma unroll
            for (int s = 1; s < 4; s++) kv[s] = ldsf(f0 + s * 256);
            kv[4] = ldsf(u < 0 ? f0 + 1024 : f1 + 512);
            #pragma unroll
            for (int s = 5; s < 8; s++) kv[s] = ldsf(f1 + s * 128);
            kv[8] = ldsf(u < 0 ? f1 + 1024 : f2 + 512);
            #pragma unroll
            for (int s = 9; s < 16; s++) kv[s] = ldsf(f2 + s * 64);
            kv[16] = ldsf(u < 0 ? f2 + 1024 : cb + CH_A3 + 2048); if (u > 4) kv[16] = 0.f;
            uint32_t o[17];
            #pragma unroll
            for (int s = 0; s < 17; s++) o[s] = pack2(kv[s], __shfl_up_sync(0xffffffffu, kv[s], 1));
            if (lane > 0 && rw < 78) {
                const uint32_t ta = cb + CH_T + rw * 80;
                #pragma unroll
                for (int s4 = 0; s4 < 4; s4++) sts128(ta + s4 * 16, o[4 * s4], o[4 * s4 + 1], o[4 * s4 + 2], o[4 * s4 + 3]);
                stsf(ta + 64, UF(o[16]));
            }
        } else {
            const uint32_t ga = cb + CH_G + ((lane >> 3) & 1) * 192 + (lane >> 4) * 16 + (lane & 7) * 8;
            #pragma unroll
            for (int i = 0; i < 4; i++) {
                const uint2 x0 = lds64(ga + 32 * i), x1 = lds64(ga + 32 * i + 8);
                sts128(cb + CH_B3 + lane * 16 + 512 * i, x0.x, x0.y, x1.x, x1.y);
            }
        }
        mbar_wait(bars + 8 * B_U, 0);
        float p[24];
        const uint2 r0 = lds64(cb + ob + 24), r3 = lds64(cb + oa);
        uint32_t r[8];
        *(uint4*)&r[0] = lds128(cb + oa + 16); *(uint4*)&r[4] = lds128(cb + ob);
        p[0] = 0.f;
        p[1] = bf_lo(r0.x); p[2] = p[1] + bf_hi(r0.x); p[3] = p[2] + bf_lo(r0.y); p[4] = p[3] + bf_hi(r0.y);
        #pragma unroll
        for (int i = 0; i < 8; i++) { p[5 + 2 * i] = p[4 + 2 * i] + bf_lo(r[i]); p[6 + 2 * i] = p[5 + 2 * i] + bf_hi(r[i]); }
        p[21] = p[20] + bf_lo(r3.x); p[22] = p[21] + bf_hi(r3.x); p[23] = p[22] + bf_lo(r3.y);
        bar_sync(2);
        #pragma unroll
        for (int i = 0; i < 8; i += 4) {
            sts64(cb + od + i * 256, pack2(p[i + 9] - p[i], p[i + 10] - p[i + 1]), pack2(p[i + 11] - p[i + 2], p[i + 12] - p[i + 3]));
            sts64(cb + od + i * 256 + 128, pack2(p[i + 16] - p[i + 9], p[i + 17] - p[i + 10]), pack2(p[i + 18] - p[i + 11], p[i + 19] - p[i + 12]));
        }
        fence_async_smem();
        mbar_arrive(bars + 8 * (B_CONV + ch));
        if (k == 0) STAMP(17);
    }
    STAMP(21);
}

__global__ void __launch_bounds__(512, 1)
fused_kernel(const __grid_constant__ Params P, const __grid_constant__ Maps M) {
    extern __shared__ __align__(1024) uint8_t smem_raw[];
    const uint32_t sb = smem_u32(smem_raw);
    const uint32_t bars = sb + OFF_BAR;
    const int warp = __shfl_sync(0xffffffffu, threadIdx.x >> 5, 0);
    const int c = blockIdx.x, tg = c / 22, fb = c - 22 * tg;
    if (elect_one()) {
        if (warp == 0) { STAMP(24); GSTAMP(22); }
        asm volatile("" :: "l"(((const uint64_t*)&P)[warp < 12 ? warp : 0]));
        if (warp < 11) asm volatile("prefetch.tensormap [%0];" :: "l"(&M.x[0] + warp) : "memory");
        #pragma unroll
        for (int k = 0; k < 4; k++) {
            const int i = 16 * k + ((warp + 4) & 15);
            const uint32_t cnt = i >= B_CONV ? 128 : ((0xf0ull >> i) & 1) ? 8 : ((0xff0000ull >> i) & 1) ? 2 : ((0x3e00ff00f000ull >> i) & 1) ? 4 : 1;
            asm volatile("mbarrier.init.shared::cta.b64 [%0], %1;" :: "r"(bars + 8 * i), "r"(cnt) : "memory");
        }
        asm volatile("fence.mbarrier_init.release.cluster; fence.proxy.async.shared::cta;" ::: "memory");
        if (warp == 12) {
            mbar_expect(bars + 8 * B_FULLW, 16384);
            tma2d(sb + OFF_W, &M.wg, 64 * fb, 0, bars + 8 * B_FULLW);
            tma2d(sb + OFF_W + 8192, &M.wu, 64 * fb, 0, bars + 8 * B_FULLW);
            STAMP(31);
        } else if (warp == 4) {
            mbar_expect(bars + 8 * B_FULLX, 168 * 128);
            tma2d(sb + OFF_X, &M.x[0], 0, TOKG * tg, bars + 8 * B_FULLX);
        }
        if (sb & 1023) __trap();
    }
    __syncthreads();
    if (warp < 8) {
        asm volatile("setmaxnreg.inc.sync.aligned.u32 208;");
        consumer(sb, warp, P, M);
    } else if (warp < 12) {
        asm volatile("setmaxnreg.dec.sync.aligned.u32 72;");
        STAMP(32);
        aux_role(sb, warp - 8, P);
    } else {
        asm volatile("setmaxnreg.dec.sync.aligned.u32 24;");
        const int tau = c >> 2, dg = c & 3;
        if (elect_one()) {
            if (warp == 12) {
                #pragma unroll 1
                for (int st = 1; st < 8; st++) {
                    const uint32_t s = st & 3, fb_ = bars + 8 * (B_FULLW + s);
                    if (st == 2) mbar_wait(bars + 8 * B_FULLW, 0);
                    mbar_wait(bars + 8 * (B_EMPTYW + s), (st >> 2) ^ 1);
                    mbar_expect(fb_, 16384);
                    tma2d(sb + OFF_W + s * 16384, &M.wg, 64 * fb, 64 * st, fb_);
                    tma2d(sb + OFF_W + s * 16384 + 8192, &M.wu, 64 * fb, 64 * st, fb_);
                }
                if (c < 128) {
                    #pragma unroll 1
                    for (int st = 0; st < 22; st++) {
                        const int sd = st & 7;
                        if (st < 8) mbar_wait(bars + 8 * (uint32_t)((0x282823070d060504ull >> (8 * st)) & 0xff), st < 5);
                        else mbar_wait(bars + 8 * (B_EMPTYD + sd), ((st >> 3) & 1) ^ 1);
                        const uint32_t da = sb + wd_slot(sd), fb_ = bars + 8 * (B_FULLD + sd);
                        mbar_expect(fb_, 16384);
                        tma2d(da, &M.wd, 128 * dg, 64 * st, fb_);
                        tma2d(da + 8192, &M.wd, 128 * dg + 64, 64 * st, fb_);
                    }
                }
            } else if (warp < 15) {
                const int V = warp - 13;
                #pragma unroll 1
                for (int st = 1 - V; st < 8; st++) {
                    const uint32_t s = 2 * V + (st & 1);
                    if (s == 3 && st == 1) mbar_wait(bars + 8 * B_LNS, 0);
                    mbar_wait(bars + 8 * (B_EMPTYX + s), ((st >> 1) & 1) ^ 1);
                    mbar_expect(bars + 8 * (B_FULLX + s), (168 + 8 * V) * 128);
                    tma2d(sb + OFF_X + s * XBUF, &M.x[V], 64 * st, TOKG * tg + 168 * V, bars + 8 * (B_FULLX + s));
                }
                if (c < 128) {
                    if (V == 0) {
                        mbar_wait(bars + 8 * (B_STG + 1), 0);
                        #pragma unroll 1
                        for (int o = 8 * tau; o < 8 * tau + 8; o += 7) flag_wait(P.flags, F_H + 2 * (o / 43) + ((o % 43) >= 21), 22);
                        mbar_arrive(bars + 8 * B_HF);
                        STAMP(25);
                        #pragma unroll 1
                        for (int st = 0; st < 22; st++) {
                            const uint32_t fb_ = bars + 8 * (B_FULLD + (st & 7));
                            if (st == 6) mbar_wait(bars + 8 * B_SST, 0);
                            mbar_wait(bars + 8 * (B_EMPTYD + (st & 7)), ((st >> 3) & 1) ^ 1);
                            mbar_expect(fb_, 8192);
                            asm volatile("cp.async.bulk.tensor.5d.shared::cluster.global.mbarrier::complete_tx::bytes [%0], [%1, {%3, %3, %3, %4, %5}], [%2];"
                                :: "r"(sb + h_slot(st & 7)), "l"(&M.hld), "r"(fb_), "r"(0), "r"(2 * tau), "r"(8 * st) : "memory");
                        }
                    } else {
                        mbar_wait(bars + 8 * B_CH0, 0);
                        mbar_expect(bars + 8 * B_XO, 16384);
                        tma2d(sb + OFF_CONV, &M.xo, 128 * dg, 64 * tau, bars + 8 * B_XO);
                        tma2d(sb + OFF_CONV + 8192, &M.xo, 128 * dg + 64, 64 * tau, bars + 8 * B_XO);
                        flag_wait(P.flags, F_S + dg, 64);
                        STAMP(26);
                        mbar_arrive(bars + 8 * B_S);
                        mbar_wait(bars + 8 * B_HF, 0);
                        exit_count(P.flags);
                    }
                }
            } else {
                mbar_wait(bars + 8 * B_LN, 0);
                STAMP2(0);
                if (c < 128) {
                    #pragma unroll 1
                    for (int i = 0; i < 2; i++)
                        asm volatile("cp.async.bulk.tensor.2d.global.shared::cta.bulk_group [%0, {%2, %3}], [%1];"
                            :: "l"(&M.xt), "r"(sb + OFF_LN + i * 8192), "r"((c & 1) * 1024 + (126 - (c & ~1)) * 8), "r"(256 * i) : "memory");
                    #pragma unroll 1
                    for (int i = 0; i < 2; i++) bulk_store(P.st + 16 * (c & ~1) + 8 * (c & 1) + 16 - 16 * i, sb + OFF_CSUM + 64 * i, 64);
                    asm volatile("cp.async.bulk.prefetch.L2.global [%0], %1;" :: "l"(P.Wd + c * (FF * DM / 128)), "r"(FF * DM / 64) : "memory");
                }
                asm volatile("cp.async.bulk.commit_group; cp.async.bulk.wait_group.read 0;" ::: "memory");
                mbar_arrive(bars + 8 * B_LNS);
                STAMP2(1);
                flag_signal(P.flags, F_A);
                STAMP2(2);
                flag_wait(P.flags, F_A, NCTA);
                STAMP(20);
                mbar_expect(bars + 8 * B_STATS, TOKG * 8);
                bulk_load(sb + OFF_ST, P.st + TOKG * tg, TOKG * 8, bars + 8 * B_STATS);
                if (c < 128) {
                    mbar_wait(bars + 8 * (B_K + 1), 0);
                    fence_async_smem();
                    mbar_expect(bars + 8 * B_U, 8 * 2048);
                    #pragma unroll 1
                    for (int i = 0; i < 8; i++)
                        bulk_load(sb + OFF_CONV + (i >> 1) * CH_STRIDE + CH_U + (i & 1) * UPLANE, P.xnT + 4 * c * 256 + i * 128, 2048, bars + 8 * B_U);
                } else exit_count(P.flags);
                #pragma unroll 1
                for (int V = 0; V < 2; V++) {
                    mbar_wait(bars + 8 * (B_EPI + V), 0);
                    STAMP2(3 + 2 * V);
                    asm volatile("cp.async.bulk.tensor.3d.global.shared::cta.bulk_group [%0, {%2, %3, %4}], [%1];"
                        :: "l"(&M.hst[V]), "r"(sb + OFF_X + V * 2 * XBUF), "r"(0), "r"(43 * tg + 21 * V), "r"(8 * fb) : "memory");
                    flag_signal(P.flags, F_H + 2 * tg + V);
                    mbar_arrive(bars + 8 * (B_STG + V));
                    STAMP2(4 + 2 * V);
                }
                if (c < 128) {
                    #pragma unroll 1
                    for (int V = 0; V < 2; V++) {
                        mbar_wait(bars + 8 * (B_SIG + V), 0);
                        STAMP2(7 + 2 * V);
                        bulk_store(P.S + (2 * c + V) * 1024, sb + OFF_CONV + (2 * V + 1) * CH_STRIDE, 8192);
                        flag_signal(P.flags, F_S + (c >> 5));
                        STAMP2(8 + 2 * V);
                    }
                    mbar_arrive(bars + 8 * B_SST);
                }
            }
        }
    }
}

typedef CUresult (*EncodeFn)(CUtensorMap*, CUtensorMapDataType, cuuint32_t, void*, const cuuint64_t*, const cuuint64_t*, const cuuint32_t*,
                             const cuuint32_t*, CUtensorMapInterleave, CUtensorMapSwizzle, CUtensorMapL2promotion, CUtensorMapFloatOOBfill);

void make_map(EncodeFn enc, CUtensorMap* m, const void* ptr, int rank, const cuuint64_t* dims, const cuuint64_t* strides, const cuuint32_t* box, bool swz) {
    const cuuint32_t es[5] = {1, 1, 1, 1, 1};
    enc(m, CU_TENSOR_MAP_DATA_TYPE_BFLOAT16, rank, (void*)ptr, dims, strides, box, es, CU_TENSOR_MAP_INTERLEAVE_NONE,
        swz ? CU_TENSOR_MAP_SWIZZLE_128B : CU_TENSOR_MAP_SWIZZLE_NONE, CU_TENSOR_MAP_L2_PROMOTION_L2_128B, CU_TENSOR_MAP_FLOAT_OOB_FILL_NONE);
}
void make_map2(EncodeFn enc, CUtensorMap* m, const void* ptr, cuuint64_t inner, cuuint64_t outer, cuuint32_t rows) {
    const cuuint64_t dims[2] = {inner, outer}, strides[1] = {inner * 2};
    const cuuint32_t box[2] = {64, rows};
    make_map(enc, m, ptr, 2, dims, strides, box, true);
}

}

extern "C" void kernel_launch(void* const* d_in, const int* in_sizes, int n_in, void* d_out, int out_size) {
    (void)in_sizes; (void)n_in; (void)out_size;
    static EncodeFn enc = nullptr;
    static void *hptr, *p_xnT, *p_st, *p_S, *p_flags;
    if (!enc) {
        cudaDriverEntryPointQueryResult qr;
        cudaGetDriverEntryPoint("cuTensorMapEncodeTiled", (void**)&enc, cudaEnableDefault, &qr);
        cudaFuncSetAttribute(fused_kernel, cudaFuncAttributeMaxDynamicSharedMemorySize, SMEM_BYTES);
        cudaGetSymbolAddress(&hptr, g_H); cudaGetSymbolAddress(&p_xnT, g_xnT); cudaGetSymbolAddress(&p_st, g_st);
        cudaGetSymbolAddress(&p_S, g_S); cudaGetSymbolAddress(&p_flags, g_flags);
    }
    Params P;
    P.x = (const __nv_bfloat16*)d_in[0]; P.logA = (const __nv_bfloat16*)d_in[1]; P.Aim = (const __nv_bfloat16*)d_in[2];
    P.Cr = (const __nv_bfloat16*)d_in[3]; P.Ci = (const __nv_bfloat16*)d_in[4]; P.logdt = (const __nv_bfloat16*)d_in[5];
    P.Dskip = (const __nv_bfloat16*)d_in[6];
    P.Wd = (const __nv_bfloat16*)d_in[10]; P.xnT = (uint4*)p_xnT; P.st = (float2*)p_st; P.S = (uint2*)p_S; P.flags = (unsigned*)p_flags;
    Maps M;
    make_map2(enc, &M.x[0], d_in[0], DM, SEQ, 168); make_map2(enc, &M.x[1], d_in[0], DM, SEQ, 176);
    make_map2(enc, &M.xo, d_in[0], DM, SEQ, 64);    make_map2(enc, &M.out, d_out, DM, SEQ, 64);
    make_map2(enc, &M.wg, d_in[8], FF, DM, 64);     make_map2(enc, &M.wu, d_in[9], FF, DM, 64);
    make_map2(enc, &M.wd, d_in[10], DM, FF, 64);
    for (int v = 0; v < 2; v++) {
        const cuuint64_t dims[3] = {64, 256, 172}, strides[2] = {128, 32768};
        const cuuint32_t box[3] = {64, (cuuint32_t)(21 + v), 8};
        make_map(enc, &M.hst[v], hptr, 3, dims, strides, box, false);
    }
    {
        const cuuint64_t dims[2] = {2048, 512}, strides[1] = {4096};
        const cuuint32_t box[2] = {16, 256};
        make_map(enc, &M.xt, p_xnT, 2, dims, strides, box, false);
    }
    {
        const cuuint64_t dims[5] = {64, 2, 2, 64, 172}, strides[4] = {256, 128, 512, 32768};
        const cuuint32_t box[5] = {64, 2, 2, 2, 8};
        make_map(enc, &M.hld, hptr, 5, dims, strides, box, false);
    }
    fused_kernel<<<NCTA, 512, SMEM_BYTES>>>(P, M);
}
```

```cpp
#include <cuda_runtime.h>
#include <cuda_bf16.h>
#include <cuda.h>
#include <stdint.h>

#define PROF 0

namespace {

constexpr int SEQ = 2048, DM = 512, FF = 1376;
constexpr int NCTA = 132;
#define HOLD0 4
#define HOLD1 7
#define LAG 2
constexpr int TOKG = 344;

constexpr uint32_t OFF_W = 0;
constexpr uint32_t XBUF = 22528;
constexpr uint32_t OFF_X = 65536;
constexpr uint32_t OFF_CONV = 155648;
constexpr uint32_t CH_STRIDE = 16640;
constexpr uint32_t CH_T = 0;
constexpr uint32_t CH_A3 = 6272;
constexpr uint32_t CH_B3 = 10368;
constexpr uint32_t CH_U = 12416;
constexpr uint32_t CH_G = CH_A3 + 2064;
constexpr uint32_t UPLANE = 2112;
constexpr uint32_t OFF_LN = OFF_X + 3 * XBUF;
constexpr uint32_t OFF_ST = 222208;
constexpr uint32_t OFF_CSUM = 230400;
constexpr uint32_t OFF_BAR = 231168;
constexpr uint32_t SMEM_BYTES = 231680;

enum {
    B_FULLW = 0, B_EMPTYW = 4, B_FULLX = 8, B_EMPTYX = 12, B_FULLD = 16, B_EMPTYD = 24,
    B_U = 32, B_XO = 33, B_S = 34, B_STG = 35, B_HF = 37, B_STATS = 38, B_LNS = 39, B_SST = 40,
    B_LNX = 41, B_GO = 42, B_CH0 = 43, B_K = 44,
    B_CONV = 46, B_LN = 50, B_CS = 51, B_EPI = 52, B_SIG = 54,
    B_COUNT = 56
};
enum { F_A = 0, F_H = 1, F_S = 13, F_EXIT = 17, F_COUNT = 18 };

__device__ uint4 g_xnT[DM * 256];
__device__ float2 g_st[6 * TOKG];
__device__ uint4 g_H[172 * 256 * 8];
__device__ uint2 g_S[256 * 1024];
__device__ unsigned g_flags[F_COUNT * 32];
#define STAMP(i) do {} while (0)
#define GSTAMP(i) do {} while (0)
#define STAMP2(i) do {} while (0)

__device__ __forceinline__ uint32_t smem_u32(const void* p) { return (uint32_t)__cvta_generic_to_shared(p); }
__device__ __forceinline__ void mbar_expect(uint32_t bar, uint32_t bytes) { asm volatile("mbarrier.arrive.expect_tx.shared::cta.b64 _, [%0], %1;" :: "r"(bar), "r"(bytes) : "memory"); }
__device__ __forceinline__ void mbar_arrive(uint32_t bar) { asm volatile("mbarrier.arrive.shared::cta.b64 _, [%0];" :: "r"(bar) : "memory"); }
__device__ __forceinline__ void mbar_wait(uint32_t bar, uint32_t parity) {
    asm volatile("{.reg .pred p; .reg .u32 n; mov.u32 n, 0x20000;\n"
                 "LW: mbarrier.try_wait.parity.shared::cta.b64 p, [%0], %1;\n"
                 "sub.u32 n, n, 1; setp.eq.or.u32 p, n, 0, p; @!p bra LW;}" :: "r"(bar), "r"(parity) : "memory");
}
__device__ __forceinline__ bool elect_one() { uint32_t p; asm volatile("{.reg .pred P; elect.sync _|P, 0xffffffff; selp.u32 %0, 1, 0, P;}" : "=r"(p)); return p; }
__device__ __forceinline__ void tma2d(uint32_t dst, const CUtensorMap* m, int c0, int c1, uint32_t bar) {
    asm volatile("cp.async.bulk.tensor.2d.shared::cluster.global.mbarrier::complete_tx::bytes [%0], [%1, {%3, %4}], [%2];"
        :: "r"(dst), "l"(m), "r"(bar), "r"(c0), "r"(c1) : "memory");
}
__device__ __forceinline__ void bulk_load(uint32_t dst, const void* src, uint32_t bytes, uint32_t bar) {
    asm volatile("cp.async.bulk.shared::cluster.global.mbarrier::complete_tx::bytes [%0], [%1], %2, [%3];" :: "r"(dst), "l"(src), "r"(bytes), "r"(bar) : "memory");
}
__device__ __forceinline__ void bulk_store(void* dst, uint32_t src, uint32_t bytes) {
    asm volatile("cp.async.bulk.global.shared::cta.bulk_group [%0], [%1], %2;" :: "l"(dst), "r"(src), "r"(bytes) : "memory");
}
__device__ __forceinline__ void fence_async_smem() { asm volatile("fence.proxy.async.shared::cta;" ::: "memory"); }
__device__ __forceinline__ void flag_wait(unsigned* g_flags, int f, unsigned target) {
    asm volatile("{.reg .pred p; .reg .u32 n, v; mov.u32 n, 0x40000;\n"
                 "LF: ld.acquire.gpu.global.u32 v, [%0]; setp.ge.u32 p, v, %1; @p bra LD;\n"
                 "sub.u32 n, n, 1; setp.ne.u32 p, n, 0; @p bra LF; trap;\nLD: }"
                 :: "l"(g_flags + f * 32), "r"(target) : "memory");
}
__device__ __forceinline__ void flag_signal(unsigned* g_flags, int f) {
    asm volatile("cp.async.bulk.commit_group; cp.async.bulk.wait_group 0; red.relaxed.gpu.global.add.u32 [%0], 1;" :: "l"(g_flags + f * 32) : "memory");
}
__device__ __forceinline__ void exit_count(unsigned* g_flags) {
    if (atomicAdd(g_flags + F_EXIT * 32, 1u) == NCTA - 1) {
        #pragma unroll 1
        for (int i = 0; i < F_COUNT; i++) g_flags[i * 32] = 0;
    }
}
__device__ __forceinline__ void bar_sync(int id) { asm volatile("bar.sync %0, 128;" :: "r"(id) : "memory"); }
__device__ __forceinline__ uint64_t mkdesc(uint32_t addr, uint32_t lbo, uint32_t sbo, uint32_t swz) {
    return (uint64_t)((addr >> 4) | ((lbo >> 4) << 16)) | ((uint64_t)((sbo >> 4) | (swz << 30)) << 32);
}
#define WG_FENCE() asm volatile("wgmma.fence.sync.aligned;" ::: "memory")
#define WG_COMMIT() asm volatile("wgmma.commit_group.sync.aligned;" ::: "memory")
#define WG_WAIT(n) asm volatile("wgmma.wait_group.sync.aligned " #n ";" ::: "memory")
template <int N> __device__ __forceinline__ void fence_acc(float (&d)[N]) {
    #pragma unroll
    for (int i = 0; i < N; i++) asm volatile("" : "+f"(d[i]) :: "memory");
}
template <int N> __device__ __forceinline__ void define_acc(float (&d)[N]) {
    #pragma unroll
    for (int i = 0; i < N; i++) asm volatile("" : "=f"(d[i]));
}
__device__ __forceinline__ uint32_t pack2(float lo, float hi) { uint32_t r; asm("cvt.rn.bf16x2.f32 %0, %1, %2;" : "=r"(r) : "f"(hi), "f"(lo)); return r; }
__device__ __forceinline__ float bf_lo(uint32_t v) { return __uint_as_float(v << 16); }
__device__ __forceinline__ float bf_hi(uint32_t v) { return __uint_as_float(v & 0xffff0000u); }
__device__ __forceinline__ float bf_round(float v) { return bf_hi(pack2(0.f, v)); }
__device__ __forceinline__ float tanh_fast(float v) { float r; asm("tanh.approx.f32 %0, %1;" : "=f"(r) : "f"(v)); return r; }
__device__ __forceinline__ float ex2(float v) { float r; asm("ex2.approx.ftz.f32 %0, %1;" : "=f"(r) : "f"(v)); return r; }
__device__ __forceinline__ uint4 lds128(uint32_t a) { uint4 v; asm volatile("ld.shared.v4.b32 {%0,%1,%2,%3}, [%4];" : "=r"(v.x), "=r"(v.y), "=r"(v.z), "=r"(v.w) : "r"(a)); return v; }
__device__ __forceinline__ uint2 lds64(uint32_t a) { uint2 v; asm volatile("ld.shared.v2.b32 {%0,%1}, [%2];" : "=r"(v.x), "=r"(v.y) : "r"(a)); return v; }
__device__ __forceinline__ float ldsf(uint32_t a) { float v; asm volatile("ld.shared.f32 %0, [%1];" : "=f"(v) : "r"(a)); return v; }
__device__ __forceinline__ void sts128(uint32_t a, uint32_t x, uint32_t y, uint32_t z, uint32_t w) { asm volatile("st.shared.v4.b32 [%0], {%1,%2,%3,%4};" :: "r"(a), "r"(x), "r"(y), "r"(z), "r"(w) : "memory"); }
__device__ __forceinline__ void sts64(uint32_t a, uint32_t x, uint32_t y) { asm volatile("st.shared.v2.b32 [%0], {%1,%2};" :: "r"(a), "r"(x), "r"(y) : "memory"); }
__device__ __forceinline__ void stsf(uint32_t a, float x) { asm volatile("st.shared.f32 [%0], %1;" :: "r"(a), "f"(x) : "memory"); }
__device__ __forceinline__ void sts16(uint32_t a, uint32_t x) { asm volatile("st.shared.b16 [%0], %1;" :: "r"(a), "h"((unsigned short)x) : "memory"); }
__device__ __forceinline__ void stsm4(uint32_t a, uint32_t r0, uint32_t r1, uint32_t r2, uint32_t r3) {
    asm volatile("stmatrix.sync.aligned.m8n8.x4.shared.b16 [%0], {%1,%2,%3,%4};" :: "r"(a), "r"(r0), "r"(r1), "r"(r2), "r"(r3) : "memory");
}
__device__ __forceinline__ void ldsm4(uint32_t (&r)[4], uint32_t a) {
    asm volatile("ldmatrix.sync.aligned.m8n8.x4.shared.b16 {%0,%1,%2,%3}, [%4];" : "=r"(r[0]), "=r"(r[1]), "=r"(r[2]), "=r"(r[3]) : "r"(a) : "memory");
}
#define FU(x) __float_as_uint(x)
#define UF(x) __uint_as_float(x)
__device__ __forceinline__ uint32_t wd_slot(int s) { return (uint32_t)((0xb9a9403056201000ull >> (8 * s)) & 0xff) << 10; }
__device__ __forceinline__ uint32_t h_slot(int s) { return (uint32_t)((0xd1c9d98c847c746cull >> (8 * s)) & 0xff) << 10; }

template<int N> __device__ __forceinline__ void wg_rs(float (&d)[64], uint32_t a0, uint32_t a1, uint32_t a2, uint32_t a3, uint64_t db);
template<> __device__ __forceinline__ void wg_rs<128>(float (&d)[64], uint32_t a0, uint32_t a1, uint32_t a2, uint32_t a3, uint64_t db) {
  asm volatile("{.reg .pred p; setp.ne.b32 p, 1, 0; wgmma.mma_async.sync.aligned.m64n128k16.f32.bf16.bf16 {%0,%1,%2,%3,%4,%5,%6,%7,%8,%9,%10,%11,%12,%13,%14,%15,%16,%17,%18,%19,%20,%21,%22,%23,%24,%25,%26,%27,%28,%29,%30,%31,%32,%33,%34,%35,%36,%37,%38,%39,%40,%41,%42,%43,%44,%45,%46,%47,%48,%49,%50,%51,%52,%53,%54,%55,%56,%57,%58,%59,%60,%61,%62,%63}, {%64,%65,%66,%67}, %68, p, 1, 1, 0;}"
    : "+f"(d[0]),"+f"(d[1]),"+f"(d[2]),"+f"(d[3]),"+f"(d[4]),"+f"(d[5]),"+f"(d[6]),"+f"(d[7]),"+f"(d[8]),"+f"(d[9]),"+f"(d[10]),"+f"(d[11]),"+f"(d[12]),"+f"(d[13]),"+f"(d[14]),"+f"(d[15]),"+f"(d[16]),"+f"(d[17]),"+f"(d[18]),"+f"(d[19]),"+f"(d[20]),"+f"(d[21]),"+f"(d[22]),"+f"(d[23]),"+f"(d[24]),"+f"(d[25]),"+f"(d[26]),"+f"(d[27]),"+f"(d[28]),"+f"(d[29]),"+f"(d[30]),"+f"(d[31]),"+f"(d[32]),"+f"(d[33]),"+f"(d[34]),"+f"(d[35]),"+f"(d[36]),"+f"(d[37]),"+f"(d[38]),"+f"(d[39]),"+f"(d[40]),"+f"(d[41]),"+f"(d[42]),"+f"(d[43]),"+f"(d[44]),"+f"(d[45]),"+f"(d[46]),"+f"(d[47]),"+f"(d[48]),"+f"(d[49]),"+f"(d[50]),"+f"(d[51]),"+f"(d[52]),"+f"(d[53]),"+f"(d[54]),"+f"(d[55]),"+f"(d[56]),"+f"(d[57]),"+f"(d[58]),"+f"(d[59]),"+f"(d[60]),"+f"(d[61]),"+f"(d[62]),"+f"(d[63]) : "r"(a0), "r"(a1), "r"(a2), "r"(a3), "l"(db));
}
template<> __device__ __forceinline__ void wg_rs<120>(float (&d)[64], uint32_t a0, uint32_t a1, uint32_t a2, uint32_t a3, uint64_t db) {
  asm volatile("{.reg .pred p; setp.ne.b32 p, 1, 0; wgmma.mma_async.sync.aligned.m64n120k16.f32.bf16.bf16 {%0,%1,%2,%3,%4,%5,%6,%7,%8,%9,%10,%11,%12,%13,%14,%15,%16,%17,%18,%19,%20,%21,%22,%23,%24,%25,%26,%27,%28,%29,%30,%31,%32,%33,%34,%35,%36,%37,%38,%39,%40,%41,%42,%43,%44,%45,%46,%47,%48,%49,%50,%51,%52,%53,%54,%55,%56,%57,%58,%59}, {%60,%61,%62,%63}, %64, p, 1, 1, 0;}"
    : "+f"(d[0]),"+f"(d[1]),"+f"(d[2]),"+f"(d[3]),"+f"(d[4]),"+f"(d[5]),"+f"(d[6]),"+f"(d[7]),"+f"(d[8]),"+f"(d[9]),"+f"(d[10]),"+f"(d[11]),"+f"(d[12]),"+f"(d[13]),"+f"(d[14]),"+f"(d[15]),"+f"(d[16]),"+f"(d[17]),"+f"(d[18]),"+f"(d[19]),"+f"(d[20]),"+f"(d[21]),"+f"(d[22]),"+f"(d[23]),"+f"(d[24]),"+f"(d[25]),"+f"(d[26]),"+f"(d[27]),"+f"(d[28]),"+f"(d[29]),"+f"(d[30]),"+f"(d[31]),"+f"(d[32]),"+f"(d[33]),"+f"(d[34]),"+f"(d[35]),"+f"(d[36]),"+f"(d[37]),"+f"(d[38]),"+f"(d[39]),"+f"(d[40]),"+f"(d[41]),"+f"(d[42]),"+f"(d[43]),"+f"(d[44]),"+f"(d[45]),"+f"(d[46]),"+f"(d[47]),"+f"(d[48]),"+f"(d[49]),"+f"(d[50]),"+f"(d[51]),"+f"(d[52]),"+f"(d[53]),"+f"(d[54]),"+f"(d[55]),"+f"(d[56]),"+f"(d[57]),"+f"(d[58]),"+f"(d[59]) : "r"(a0), "r"(a1), "r"(a2), "r"(a3), "l"(db));
}
template<> __device__ __forceinline__ void wg_rs<112>(float (&d)[64], uint32_t a0, uint32_t a1, uint32_t a2, uint32_t a3, uint64_t db) {
  asm volatile("{.reg .pred p; setp.ne.b32 p, 1, 0; wgmma.mma_async.sync.aligned.m64n112k16.f32.bf16.bf16 {%0,%1,%2,%3,%4,%5,%6,%7,%8,%9,%10,%11,%12,%13,%14,%15,%16,%17,%18,%19,%20,%21,%22,%23,%24,%25,%26,%27,%28,%29,%30,%31,%32,%33,%34,%35,%36,%37,%38,%39,%40,%41,%42,%43,%44,%45,%46,%47,%48,%49,%50,%51,%52,%53,%54,%55}, {%56,%57,%58,%59}, %60, p, 1, 1, 0;}"
    : "+f"(d[0]),"+f"(d[1]),"+f"(d[2]),"+f"(d[3]),"+f"(d[4]),"+f"(d[5]),"+f"(d[6]),"+f"(d[7]),"+f"(d[8]),"+f"(d[9]),"+f"(d[10]),"+f"(d[11]),"+f"(d[12]),"+f"(d[13]),"+f"(d[14]),"+f"(d[15]),"+f"(d[16]),"+f"(d[17]),"+f"(d[18]),"+f"(d[19]),"+f"(d[20]),"+f"(d[21]),"+f"(d[22]),"+f"(d[23]),"+f"(d[24]),"+f"(d[25]),"+f"(d[26]),"+f"(d[27]),"+f"(d[28]),"+f"(d[29]),"+f"(d[30]),"+f"(d[31]),"+f"(d[32]),"+f"(d[33]),"+f"(d[34]),"+f"(d[35]),"+f"(d[36]),"+f"(d[37]),"+f"(d[38]),"+f"(d[39]),"+f"(d[40]),"+f"(d[41]),"+f"(d[42]),"+f"(d[43]),"+f"(d[44]),"+f"(d[45]),"+f"(d[46]),"+f"(d[47]),"+f"(d[48]),"+f"(d[49]),"+f"(d[50]),"+f"(d[51]),"+f"(d[52]),"+f"(d[53]),"+f"(d[54]),"+f"(d[55]) : "r"(a0), "r"(a1), "r"(a2), "r"(a3), "l"(db));
}
template<> __device__ __forceinline__ void wg_rs<104>(float (&d)[64], uint32_t a0, uint32_t a1, uint32_t a2, uint32_t a3, uint64_t db) {
  asm volatile("{.reg .pred p; setp.ne.b32 p, 1, 0; wgmma.mma_async.sync.aligned.m64n104k16.f32.bf16.bf16 {%0,%1,%2,%3,%4,%5,%6,%7,%8,%9,%10,%11,%12,%13,%14,%15,%16,%17,%18,%19,%20,%21,%22,%23,%24,%25,%26,%27,%28,%29,%30,%31,%32,%33,%34,%35,%36,%37,%38,%39,%40,%41,%42,%43,%44,%45,%46,%47,%48,%49,%50,%51}, {%52,%53,%54,%55}, %56, p, 1, 1, 0;}"
    : "+f"(d[0]),"+f"(d[1]),"+f"(d[2]),"+f"(d[3]),"+f"(d[4]),"+f"(d[5]),"+f"(d[6]),"+f"(d[7]),"+f"(d[8]),"+f"(d[9]),"+f"(d[10]),"+f"(d[11]),"+f"(d[12]),"+f"(d[13]),"+f"(d[14]),"+f"(d[15]),"+f"(d[16]),"+f"(d[17]),"+f"(d[18]),"+f"(d[19]),"+f"(d[20]),"+f"(d[21]),"+f"(d[22]),"+f"(d[23]),"+f"(d[24]),"+f"(d[25]),"+f"(d[26]),"+f"(d[27]),"+f"(d[28]),"+f"(d[29]),"+f"(d[30]),"+f"(d[31]),"+f"(d[32]),"+f"(d[33]),"+f"(d[34]),"+f"(d[35]),"+f"(d[36]),"+f"(d[37]),"+f"(d[38]),"+f"(d[39]),"+f"(d[40]),"+f"(d[41]),"+f"(d[42]),"+f"(d[43]),"+f"(d[44]),"+f"(d[45]),"+f"(d[46]),"+f"(d[47]),"+f"(d[48]),"+f"(d[49]),"+f"(d[50]),"+f"(d[51]) : "r"(a0), "r"(a1), "r"(a2), "r"(a3), "l"(db));
}
template<> __device__ __forceinline__ void wg_rs<96>(float (&d)[64], uint32_t a0, uint32_t a1, uint32_t a2, uint32_t a3, uint64_t db) {
  asm volatile("{.reg .pred p; setp.ne.b32 p, 1, 0; wgmma.mma_async.sync.aligned.m64n96k16.f32.bf16.bf16 {%0,%1,%2,%3,%4,%5,%6,%7,%8,%9,%10,%11,%12,%13,%14,%15,%16,%17,%18,%19,%20,%21,%22,%23,%24,%25,%26,%27,%28,%29,%30,%31,%32,%33,%34,%35,%36,%37,%38,%39,%40,%41,%42,%43,%44,%45,%46,%47}, {%48,%49,%50,%51}, %52, p, 1, 1, 0;}"
    : "+f"(d[0]),"+f"(d[1]),"+f"(d[2]),"+f"(d[3]),"+f"(d[4]),"+f"(d[5]),"+f"(d[6]),"+f"(d[7]),"+f"(d[8]),"+f"(d[9]),"+f"(d[10]),"+f"(d[11]),"+f"(d[12]),"+f"(d[13]),"+f"(d[14]),"+f"(d[15]),"+f"(d[16]),"+f"(d[17]),"+f"(d[18]),"+f"(d[19]),"+f"(d[20]),"+f"(d[21]),"+f"(d[22]),"+f"(d[23]),"+f"(d[24]),"+f"(d[25]),"+f"(d[26]),"+f"(d[27]),"+f"(d[28]),"+f"(d[29]),"+f"(d[30]),"+f"(d[31]),"+f"(d[32]),"+f"(d[33]),"+f"(d[34]),"+f"(d[35]),"+f"(d[36]),"+f"(d[37]),"+f"(d[38]),"+f"(d[39]),"+f"(d[40]),"+f"(d[41]),"+f"(d[42]),"+f"(d[43]),"+f"(d[44]),"+f"(d[45]),"+f"(d[46]),"+f"(d[47]) : "r"(a0), "r"(a1), "r"(a2), "r"(a3), "l"(db));
}
template<> __device__ __forceinline__ void wg_rs<88>(float (&d)[64], uint32_t a0, uint32_t a1, uint32_t a2, uint32_t a3, uint64_t db) {
  asm volatile("{.reg .pred p; setp.ne.b32 p, 1, 0; wgmma.mma_async.sync.aligned.m64n88k16.f32.bf16.bf16 {%0,%1,%2,%3,%4,%5,%6,%7,%8,%9,%10,%11,%12,%13,%14,%15,%16,%17,%18,%19,%20,%21,%22,%23,%24,%25,%26,%27,%28,%29,%30,%31,%32,%33,%34,%35,%36,%37,%38,%39,%40,%41,%42,%43}, {%44,%45,%46,%47}, %48, p, 1, 1, 0;}"
    : "+f"(d[0]),"+f"(d[1]),"+f"(d[2]),"+f"(d[3]),"+f"(d[4]),"+f"(d[5]),"+f"(d[6]),"+f"(d[7]),"+f"(d[8]),"+f"(d[9]),"+f"(d[10]),"+f"(d[11]),"+f"(d[12]),"+f"(d[13]),"+f"(d[14]),"+f"(d[15]),"+f"(d[16]),"+f"(d[17]),"+f"(d[18]),"+f"(d[19]),"+f"(d[20]),"+f"(d[21]),"+f"(d[22]),"+f"(d[23]),"+f"(d[24]),"+f"(d[25]),"+f"(d[26]),"+f"(d[27]),"+f"(d[28]),"+f"(d[29]),"+f"(d[30]),"+f"(d[31]),"+f"(d[32]),"+f"(d[33]),"+f"(d[34]),"+f"(d[35]),"+f"(d[36]),"+f"(d[37]),"+f"(d[38]),"+f"(d[39]),"+f"(d[40]),"+f"(d[41]),"+f"(d[42]),"+f"(d[43]) : "r"(a0), "r"(a1), "r"(a2), "r"(a3), "l"(db));
}
template<> __device__ __forceinline__ void wg_rs<80>(float (&d)[64], uint32_t a0, uint32_t a1, uint32_t a2, uint32_t a3, uint64_t db) {
  asm volatile("{.reg .pred p; setp.ne.b32 p, 1, 0; wgmma.mma_async.sync.aligned.m64n80k16.f32.bf16.bf16 {%0,%1,%2,%3,%4,%5,%6,%7,%8,%9,%10,%11,%12,%13,%14,%15,%16,%17,%18,%19,%20,%21,%22,%23,%24,%25,%26,%27,%28,%29,%30,%31,%32,%33,%34,%35,%36,%37,%38,%39}, {%40,%41,%42,%43}, %44, p, 1, 1, 0;}"
    : "+f"(d[0]),"+f"(d[1]),"+f"(d[2]),"+f"(d[3]),"+f"(d[4]),"+f"(d[5]),"+f"(d[6]),"+f"(d[7]),"+f"(d[8]),"+f"(d[9]),"+f"(d[10]),"+f"(d[11]),"+f"(d[12]),"+f"(d[13]),"+f"(d[14]),"+f"(d[15]),"+f"(d[16]),"+f"(d[17]),"+f"(d[18]),"+f"(d[19]),"+f"(d[20]),"+f"(d[21]),"+f"(d[22]),"+f"(d[23]),"+f"(d[24]),"+f"(d[25]),"+f"(d[26]),"+f"(d[27]),"+f"(d[28]),"+f"(d[29]),"+f"(d[30]),"+f"(d[31]),"+f"(d[32]),"+f"(d[33]),"+f"(d[34]),"+f"(d[35]),"+f"(d[36]),"+f"(d[37]),"+f"(d[38]),"+f"(d[39]) : "r"(a0), "r"(a1), "r"(a2), "r"(a3), "l"(db));
}
template<> __device__ __forceinline__ void wg_rs<72>(float (&d)[64], uint32_t a0, uint32_t a1, uint32_t a2, uint32_t a3, uint64_t db) {
  asm volatile("{.reg .pred p; setp.ne.b32 p, 1, 0; wgmma.mma_async.sync.aligned.m64n72k16.f32.bf16.bf16 {%0,%1,%2,%3,%4,%5,%6,%7,%8,%9,%10,%11,%12,%13,%14,%15,%16,%17,%18,%19,%20,%21,%22,%23,%24,%25,%26,%27,%28,%29,%30,%31,%32,%33,%34,%35}, {%36,%37,%38,%39}, %40, p, 1, 1, 0;}"
    : "+f"(d[0]),"+f"(d[1]),"+f"(d[2]),"+f"(d[3]),"+f"(d[4]),"+f"(d[5]),"+f"(d[6]),"+f"(d[7]),"+f"(d[8]),"+f"(d[9]),"+f"(d[10]),"+f"(d[11]),"+f"(d[12]),"+f"(d[13]),"+f"(d[14]),"+f"(d[15]),"+f"(d[16]),"+f"(d[17]),"+f"(d[18]),"+f"(d[19]),"+f"(d[20]),"+f"(d[21]),"+f"(d[22]),"+f"(d[23]),"+f"(d[24]),"+f"(d[25]),"+f"(d[26]),"+f"(d[27]),"+f"(d[28]),"+f"(d[29]),"+f"(d[30]),"+f"(d[31]),"+f"(d[32]),"+f"(d[33]),"+f"(d[34]),"+f"(d[35]) : "r"(a0), "r"(a1), "r"(a2), "r"(a3), "l"(db));
}
template<> __device__ __forceinline__ void wg_rs<64>(float (&d)[64], uint32_t a0, uint32_t a1, uint32_t a2, uint32_t a3, uint64_t db) {
  asm volatile("{.reg .pred p; setp.ne.b32 p, 1, 0; wgmma.mma_async.sync.aligned.m64n64k16.f32.bf16.bf16 {%0,%1,%2,%3,%4,%5,%6,%7,%8,%9,%10,%11,%12,%13,%14,%15,%16,%17,%18,%19,%20,%21,%22,%23,%24,%25,%26,%27,%28,%29,%30,%31}, {%32,%33,%34,%35}, %36, p, 1, 1, 0;}"
    : "+f"(d[0]),"+f"(d[1]),"+f"(d[2]),"+f"(d[3]),"+f"(d[4]),"+f"(d[5]),"+f"(d[6]),"+f"(d[7]),"+f"(d[8]),"+f"(d[9]),"+f"(d[10]),"+f"(d[11]),"+f"(d[12]),"+f"(d[13]),"+f"(d[14]),"+f"(d[15]),"+f"(d[16]),"+f"(d[17]),"+f"(d[18]),"+f"(d[19]),"+f"(d[20]),"+f"(d[21]),"+f"(d[22]),"+f"(d[23]),"+f"(d[24]),"+f"(d[25]),"+f"(d[26]),"+f"(d[27]),"+f"(d[28]),"+f"(d[29]),"+f"(d[30]),"+f"(d[31]) : "r"(a0), "r"(a1), "r"(a2), "r"(a3), "l"(db));
}
__device__ __forceinline__ void wg_rs_first(float (&d)[64], uint32_t a0, uint32_t a1, uint32_t a2, uint32_t a3, uint64_t db) {
  asm volatile("{.reg .pred p; setp.ne.b32 p, 0, 0; wgmma.mma_async.sync.aligned.m64n128k16.f32.bf16.bf16 {%0,%1,%2,%3,%4,%5,%6,%7,%8,%9,%10,%11,%12,%13,%14,%15,%16,%17,%18,%19,%20,%21,%22,%23,%24,%25,%26,%27,%28,%29,%30,%31,%32,%33,%34,%35,%36,%37,%38,%39,%40,%41,%42,%43,%44,%45,%46,%47,%48,%49,%50,%51,%52,%53,%54,%55,%56,%57,%58,%59,%60,%61,%62,%63}, {%64,%65,%66,%67}, %68, p, 1, 1, 0;}"
    : "=f"(d[0]),"=f"(d[1]),"=f"(d[2]),"=f"(d[3]),"=f"(d[4]),"=f"(d[5]),"=f"(d[6]),"=f"(d[7]),"=f"(d[8]),"=f"(d[9]),"=f"(d[10]),"=f"(d[11]),"=f"(d[12]),"=f"(d[13]),"=f"(d[14]),"=f"(d[15]),"=f"(d[16]),"=f"(d[17]),"=f"(d[18]),"=f"(d[19]),"=f"(d[20]),"=f"(d[21]),"=f"(d[22]),"=f"(d[23]),"=f"(d[24]),"=f"(d[25]),"=f"(d[26]),"=f"(d[27]),"=f"(d[28]),"=f"(d[29]),"=f"(d[30]),"=f"(d[31]),"=f"(d[32]),"=f"(d[33]),"=f"(d[34]),"=f"(d[35]),"=f"(d[36]),"=f"(d[37]),"=f"(d[38]),"=f"(d[39]),"=f"(d[40]),"=f"(d[41]),"=f"(d[42]),"=f"(d[43]),"=f"(d[44]),"=f"(d[45]),"=f"(d[46]),"=f"(d[47]),"=f"(d[48]),"=f"(d[49]),"=f"(d[50]),"=f"(d[51]),"=f"(d[52]),"=f"(d[53]),"=f"(d[54]),"=f"(d[55]),"=f"(d[56]),"=f"(d[57]),"=f"(d[58]),"=f"(d[59]),"=f"(d[60]),"=f"(d[61]),"=f"(d[62]),"=f"(d[63]) : "r"(a0), "r"(a1), "r"(a2), "r"(a3), "l"(db));
}
__device__ __forceinline__ void wg_tt128(float (&d)[64], uint64_t da, uint64_t db, int sc) {
  asm volatile("{.reg .pred p; setp.ne.b32 p, %66, 0; wgmma.mma_async.sync.aligned.m64n128k16.f32.bf16.bf16 {%0,%1,%2,%3,%4,%5,%6,%7,%8,%9,%10,%11,%12,%13,%14,%15,%16,%17,%18,%19,%20,%21,%22,%23,%24,%25,%26,%27,%28,%29,%30,%31,%32,%33,%34,%35,%36,%37,%38,%39,%40,%41,%42,%43,%44,%45,%46,%47,%48,%49,%50,%51,%52,%53,%54,%55,%56,%57,%58,%59,%60,%61,%62,%63}, %64, %65, p, 1, 1, 1, 1;}"
    : "+f"(d[0]),"+f"(d[1]),"+f"(d[2]),"+f"(d[3]),"+f"(d[4]),"+f"(d[5]),"+f"(d[6]),"+f"(d[7]),"+f"(d[8]),"+f"(d[9]),"+f"(d[10]),"+f"(d[11]),"+f"(d[12]),"+f"(d[13]),"+f"(d[14]),"+f"(d[15]),"+f"(d[16]),"+f"(d[17]),"+f"(d[18]),"+f"(d[19]),"+f"(d[20]),"+f"(d[21]),"+f"(d[22]),"+f"(d[23]),"+f"(d[24]),"+f"(d[25]),"+f"(d[26]),"+f"(d[27]),"+f"(d[28]),"+f"(d[29]),"+f"(d[30]),"+f"(d[31]),"+f"(d[32]),"+f"(d[33]),"+f"(d[34]),"+f"(d[35]),"+f"(d[36]),"+f"(d[37]),"+f"(d[38]),"+f"(d[39]),"+f"(d[40]),"+f"(d[41]),"+f"(d[42]),"+f"(d[43]),"+f"(d[44]),"+f"(d[45]),"+f"(d[46]),"+f"(d[47]),"+f"(d[48]),"+f"(d[49]),"+f"(d[50]),"+f"(d[51]),"+f"(d[52]),"+f"(d[53]),"+f"(d[54]),"+f"(d[55]),"+f"(d[56]),"+f"(d[57]),"+f"(d[58]),"+f"(d[59]),"+f"(d[60]),"+f"(d[61]),"+f"(d[62]),"+f"(d[63]) : "l"(da), "l"(db), "r"(sc));
}
__device__ __forceinline__ void wg_tt64(float (&d)[64], uint64_t da, uint64_t db, int sc) {
  asm volatile("{.reg .pred p; setp.ne.b32 p, %34, 0; wgmma.mma_async.sync.aligned.m64n64k16.f32.bf16.bf16 {%0,%1,%2,%3,%4,%5,%6,%7,%8,%9,%10,%11,%12,%13,%14,%15,%16,%17,%18,%19,%20,%21,%22,%23,%24,%25,%26,%27,%28,%29,%30,%31}, %32, %33, p, 1, 1, 1, 1;}"
    : "+f"(d[0]),"+f"(d[1]),"+f"(d[2]),"+f"(d[3]),"+f"(d[4]),"+f"(d[5]),"+f"(d[6]),"+f"(d[7]),"+f"(d[8]),"+f"(d[9]),"+f"(d[10]),"+f"(d[11]),"+f"(d[12]),"+f"(d[13]),"+f"(d[14]),"+f"(d[15]),"+f"(d[16]),"+f"(d[17]),"+f"(d[18]),"+f"(d[19]),"+f"(d[20]),"+f"(d[21]),"+f"(d[22]),"+f"(d[23]),"+f"(d[24]),"+f"(d[25]),"+f"(d[26]),"+f"(d[27]),"+f"(d[28]),"+f"(d[29]),"+f"(d[30]),"+f"(d[31]) : "l"(da), "l"(db), "r"(sc));
}
__device__ __forceinline__ void wg_tt32(float (&d)[64], uint64_t da, uint64_t db, int sc) {
  asm volatile("{.reg .pred p; setp.ne.b32 p, %18, 0; wgmma.mma_async.sync.aligned.m64n32k16.f32.bf16.bf16 {%0,%1,%2,%3,%4,%5,%6,%7,%8,%9,%10,%11,%12,%13,%14,%15}, %16, %17, p, 1, 1, 1, 1;}"
    : "+f"(d[0]),"+f"(d[1]),"+f"(d[2]),"+f"(d[3]),"+f"(d[4]),"+f"(d[5]),"+f"(d[6]),"+f"(d[7]),"+f"(d[8]),"+f"(d[9]),"+f"(d[10]),"+f"(d[11]),"+f"(d[12]),"+f"(d[13]),"+f"(d[14]),"+f"(d[15]) : "l"(da), "l"(db), "r"(sc));
}
__device__ __forceinline__ void wg_g1(float (&d)[88], uint64_t da, uint64_t db, int sc) {
  asm volatile("{.reg .pred p; setp.ne.b32 p, %90, 0; wgmma.mma_async.sync.aligned.m64n176k16.f32.bf16.bf16 {%0,%1,%2,%3,%4,%5,%6,%7,%8,%9,%10,%11,%12,%13,%14,%15,%16,%17,%18,%19,%20,%21,%22,%23,%24,%25,%26,%27,%28,%29,%30,%31,%32,%33,%34,%35,%36,%37,%38,%39,%40,%41,%42,%43,%44,%45,%46,%47,%48,%49,%50,%51,%52,%53,%54,%55,%56,%57,%58,%59,%60,%61,%62,%63,%64,%65,%66,%67,%68,%69,%70,%71,%72,%73,%74,%75,%76,%77,%78,%79,%80,%81,%82,%83,%84,%85,%86,%87}, %88, %89, p, 1, 1, 1, 0;}"
    : "+f"(d[0]),"+f"(d[1]),"+f"(d[2]),"+f"(d[3]),"+f"(d[4]),"+f"(d[5]),"+f"(d[6]),"+f"(d[7]),"+f"(d[8]),"+f"(d[9]),"+f"(d[10]),"+f"(d[11]),"+f"(d[12]),"+f"(d[13]),"+f"(d[14]),"+f"(d[15]),"+f"(d[16]),"+f"(d[17]),"+f"(d[18]),"+f"(d[19]),"+f"(d[20]),"+f"(d[21]),"+f"(d[22]),"+f"(d[23]),"+f"(d[24]),"+f"(d[25]),"+f"(d[26]),"+f"(d[27]),"+f"(d[28]),"+f"(d[29]),"+f"(d[30]),"+f"(d[31]),"+f"(d[32]),"+f"(d[33]),"+f"(d[34]),"+f"(d[35]),"+f"(d[36]),"+f"(d[37]),"+f"(d[38]),"+f"(d[39]),"+f"(d[40]),"+f"(d[41]),"+f"(d[42]),"+f"(d[43]),"+f"(d[44]),"+f"(d[45]),"+f"(d[46]),"+f"(d[47]),"+f"(d[48]),"+f"(d[49]),"+f"(d[50]),"+f"(d[51]),"+f"(d[52]),"+f"(d[53]),"+f"(d[54]),"+f"(d[55]),"+f"(d[56]),"+f"(d[57]),"+f"(d[58]),"+f"(d[59]),"+f"(d[60]),"+f"(d[61]),"+f"(d[62]),"+f"(d[63]),"+f"(d[64]),"+f"(d[65]),"+f"(d[66]),"+f"(d[67]),"+f"(d[68]),"+f"(d[69]),"+f"(d[70]),"+f"(d[71]),"+f"(d[72]),"+f"(d[73]),"+f"(d[74]),"+f"(d[75]),"+f"(d[76]),"+f"(d[77]),"+f"(d[78]),"+f"(d[79]),"+f"(d[80]),"+f"(d[81]),"+f"(d[82]),"+f"(d[83]),"+f"(d[84]),"+f"(d[85]),"+f"(d[86]),"+f"(d[87]) : "l"(da), "l"(db), "r"(sc));
}

struct Params { const __nv_bfloat16 *x, *logA, *Aim, *Cr, *Ci, *logdt, *Dskip, *Wd; uint4* xnT; float2* st; uint2* S; unsigned* flags; };
struct Maps { CUtensorMap x[2], xo, out, wg, wu, wd, hst[2], hld, xt, sld; };

__device__ __forceinline__ void conv_channel(uint32_t cb, int w, int lane, uint32_t (&res)[8], uint32_t bar_free) {
    const int q = lane & 3, g = lane >> 2, gam = g >> 2;
    float acc[64];
    uint4 a[4][4];
    const uint32_t t0 = cb + CH_T + (uint32_t)(14 + 4 * w + (g & 3) + 32 * gam - 2 * q) * 80u;
    #pragma unroll
    for (int s4 = 0; s4 < 4; s4++) {
        a[s4][0] = lds128(t0 + s4 * 16);
        a[s4][1] = lds128(t0 + 16 * 80 + s4 * 16);
        a[s4][2] = lds128(t0 - 8 * 80 + s4 * 16);
        a[s4][3] = lds128(t0 + 8 * 80 + s4 * 16);
    }
    const uint32_t l0 = FU(ldsf(t0 + 64)), l1 = FU(ldsf(t0 + 16 * 80 + 64)), l2 = FU(ldsf(t0 - 8 * 80 + 64)), l3 = FU(ldsf(t0 + 8 * 80 + 64));
    const uint64_t dU = mkdesc(cb + CH_U, UPLANE, 128, 0);
    WG_FENCE();
#define CT(N, s, c) wg_rs<N>(acc, a[(s) >> 2][0].c, a[(s) >> 2][1].c, a[(s) >> 2][2].c, a[(s) >> 2][3].c, dU + 4 * (s))
    wg_rs_first(acc, a[0][0].x, a[0][1].x, a[0][2].x, a[0][3].x, dU);
    CT(128, 1, y); CT(120, 2, z); CT(120, 3, w);
    CT(112, 4, x); CT(112, 5, y); CT(104, 6, z); CT(104, 7, w);
    CT(96, 8, x);  CT(96, 9, y);  CT(88, 10, z); CT(88, 11, w);
    CT(80, 12, x); CT(80, 13, y); CT(72, 14, z); CT(72, 15, w);
#undef CT
    wg_rs<64>(acc, l0, l1, l2, l3, dU + 64);
    wg_tt64(acc, mkdesc(cb + CH_A3, 128, 512, 0), mkdesc(cb + CH_B3, 128, 256, 0), 1);
    wg_tt32(acc, mkdesc(cb + CH_A3 + 256, 128, 512, 0), mkdesc(cb + CH_B3 + 1024, 128, 256, 0), 1);
    WG_COMMIT();
    WG_WAIT(0);
    fence_acc(acc);
    if (bar_free && lane == 0) mbar_arrive(bar_free);
    const int src1 = (lane & ~3) | ((q + 1) & 3);
    float E[16][2];
    #pragma unroll
    for (int j = 0; j < 16; j++) {
        const float nxt = (j < 15) ? acc[4 * (j + 1) + 2] : 0.f;
        const float sup = (q == 0) ? nxt : acc[4 * j + 2];
        const float v = __shfl_sync(0xffffffffu, sup, src1);
        E[j][0] = acc[4 * j] + acc[4 * j + 3];
        E[j][1] = acc[4 * j + 1] + v;
    }
    const int src2 = gam ? ((lane & 12) | ((q + 3) & 3)) : (16 | (lane & 12) | ((q + 1) & 3));
    const bool c1 = gam && q != 0, c2 = gam && q == 0;
    #pragma unroll
    for (int a2 = 0; a2 < 8; a2++) {
        float y[2];
        #pragma unroll
        for (int e = 0; e < 2; e++) {
            const float sup = c1 ? E[2 * a2][e] : E[2 * a2 + 1][e];
            const float nxt = (a2 < 7) ? E[2 * a2 + 2][e] : 0.f;
            const float keep = c2 ? nxt : (c1 ? E[2 * a2 + 1][e] : E[2 * a2][e]);
            y[e] = keep + __shfl_sync(0xffffffffu, sup, src2);
        }
        res[a2] = pack2(y[1], y[0]);
    }
}

__device__ __forceinline__ void layer_norm(uint32_t sb, int w, int lane, const __nv_bfloat16* x) {
    const uint32_t bars = sb + OFF_BAR;
    const int c = blockIdx.x;
    {
        if (elect_one()) {
            mbar_expect(bars + 8 * B_LNX, 4096);
            #pragma unroll
            for (int i = 0; i < 4; i++)
                bulk_load(sb + OFF_LN + (w + 4 * i) * 1040, x + (16 * (c & ~1) + 8 * (c & 1) + 16 + w + 4 * (i & 1) - 8 * (i & 2)) * DM, 1024, bars + 8 * B_LNX);
        }
        mbar_wait(bars + 8 * B_LNX, 0);
        STAMP(34);
        {
            const int r = w + 4 * (lane >> 3);
            const uint32_t r0 = sb + OFF_LN + r * 1040, ra = r0 + (lane & 7) * 16;
            const float pv = bf_lo(FU(ldsf(r0)));
            float s0 = 0.f, s1 = 0.f, a0 = 0.f, a1 = 0.f;
            uint4 nx = lds128(ra), ny = lds128(ra + 128);
            #pragma unroll 1
            for (int k = 128; k <= 1024; k += 128) {
                const uint32_t v[4] = {nx.x, nx.y, nx.z, nx.w};
                nx = ny; ny = lds128(ra + ((k + 128) & 1023));
                #pragma unroll
                for (int i = 0; i < 4; i++) { const float t0 = bf_lo(v[i]) - pv, t1 = bf_hi(v[i]) - pv; s0 += t0; s1 += t1; a0 = fmaf(t0, t0, a0); a1 = fmaf(t1, t1, a1); }
            }
            s0 += s1; a0 += a1;
            #pragma unroll
            for (int o = 4; o; o >>= 1) { s0 += __shfl_xor_sync(0xffffffffu, s0, o); a0 += __shfl_xor_sync(0xffffffffu, a0, o); }
            s0 *= 1.f / DM;
            const float m = pv + s0, var = fmaxf(fmaf(-s0, s0, a0 * (1.f / DM)), 0.f);
            float sd, ri;
            asm("sqrt.approx.ftz.f32 %0, %1;" : "=f"(sd) : "f"(bf_round(bf_round(var) + 1e-5f)));
            asm("rcp.approx.ftz.f32 %0, %1;" : "=f"(ri) : "f"(bf_round(sd)));
            const uint32_t m2 = pack2(m, m);
            if ((lane & 7) == 0) {
                sts64(sb + OFF_CSUM + r * 8, m2 & 0xffff0000u, FU(0.5f * ri));
            }
            #pragma unroll 1
            for (int k = 128; k <= 1024; k += 128) {
                uint32_t v[4] = {nx.x, nx.y, nx.z, nx.w};
                nx = ny; ny = lds128(ra + ((k + 128) & 1023));
                #pragma unroll
                for (int i = 0; i < 4; i++) {
                    uint32_t dv; asm("sub.rn.bf16x2 %0, %1, %2;" : "=r"(dv) : "r"(v[i]), "r"(m2));
                    v[i] = pack2(bf_lo(dv) * ri, bf_hi(dv) * ri);
                }
                sts128(ra + k - 128, v[0], v[1], v[2], v[3]);
            }
        }
        STAMP(62);
        bar_sync(4);
        {
            const uint32_t ad = sb + OFF_LN + (4 * ((lane & 7) >> 1) + (lane & 1) + 2 * ((lane >> 3) & 1)) * 1040 + (16 * w + (lane >> 4)) * 16;
            uint32_t r[8][4];
            #pragma unroll
            for (int i = 0; i < 8; i++)
                asm volatile("ldmatrix.sync.aligned.m8n8.x4.trans.shared.b16 {%0,%1,%2,%3}, [%4];" : "=r"(r[i][0]), "=r"(r[i][1]), "=r"(r[i][2]), "=r"(r[i][3]) : "r"(ad + 32 * i) : "memory");
            bar_sync(4);
            const uint32_t od = sb + OFF_LN + w * 4096 + lane * 8;
            #pragma unroll
            for (int i = 0; i < 8; i++) { sts64(od + i * 512, r[i][0], r[i][1]); sts64(od + i * 512 + 256, r[i][2], r[i][3]); }
        }
        fence_async_smem();
        mbar_arrive(bars + 8 * B_LN);
        STAMP(16);
    }
}

__device__ __forceinline__ void consumer(uint32_t sb, int warp, const Params& P, const Maps& M) {
    const int V = warp >> 2, w = warp & 3, lane = threadIdx.x & 31, q = lane & 3, g = lane >> 2;
    const int c = blockIdx.x;
    const uint32_t bars = sb + OFF_BAR, xb = sb + OFF_X + V * 2 * XBUF;
    {
        float ag[88], au[88];
        if (V == 0) {
            sts128(xb + (w >> 1) * XBUF + 168 * 128 + (threadIdx.x & 63) * 16, 0x3f803f80u, 0x3f803f80u, 0x3f803f80u, 0x3f803f80u);
            fence_async_smem();
            bar_sync(1);
        } else {
            if (c < 128) layer_norm(sb, w, lane, P.x); else mbar_arrive(bars + 8 * B_LN);
            mbar_wait(bars + 8 * B_GO, 0);
        }
        define_acc(ag); define_acc(au);
        #pragma unroll 1
        for (int st = 0; st < 8; st++) {
            if (st + LAG * V == HOLD0 || st + LAG * V == HOLD1) mbar_wait(bars + 8 * (B_K + (st + LAG * V == HOLD1)), 0);
            mbar_wait(bars + 8 * (B_FULLW + (st & 3)), st >> 2);
            mbar_wait(bars + 8 * (B_FULLX + 2 * V + (st & 1)), (st >> 1) & 1);
            STAMP(40 + 8 * V + st);
            const uint64_t dG = mkdesc(sb + OFF_W + (st & 3) * 16384, 0, 1024, 1);
            const uint64_t dX = mkdesc(xb + (st & 1) * XBUF, 16, 1024, 1);
            WG_FENCE();
            #pragma unroll
            for (int k = 0; k < 4; k++) {
                wg_g1(ag, dG + k * 128, dX + k * 2, k ? 1 : st);
                wg_g1(au, dG + 512 + k * 128, dX + k * 2, k ? 1 : st);
            }
            WG_COMMIT();
            WG_WAIT(1);
            if (lane == 0 && st > 0) {
                mbar_arrive(bars + 8 * (B_EMPTYW + ((st - 1) & 3)));
                mbar_arrive(bars + 8 * (B_EMPTYX + 2 * V + ((st - 1) & 1)));
                if (warp < 4 && st == LAG) mbar_arrive(bars + 8 * B_GO);
            }
        }
        WG_WAIT(0);
        fence_acc(ag); fence_acc(au);
        if (lane == 0) { mbar_arrive(bars + 8 * (B_EMPTYW + 3)); mbar_arrive(bars + 8 * (B_EMPTYX + 2 * V + 1)); }
        STAMP(8 * V + 1);
        float cg0 = ag[84], cg1 = ag[86], cu0 = au[84], cu1 = au[86];
        const uint32_t ca = sb + OFF_CSUM + (8 * w + g) * 16;
        if (V == 0) { sts128(ca, FU(cg0), FU(cg1), FU(cu0), FU(cu1)); mbar_arrive(bars + 8 * B_CS); }
        else { mbar_wait(bars + 8 * B_CS, 0); const uint4 t = lds128(ca); cg0 = UF(t.x); cg1 = UF(t.y); cu0 = UF(t.z); cu1 = UF(t.w); }
        mbar_wait(bars + 8 * B_STATS, 0);
        mbar_wait(bars + 8 * (B_EMPTYX + 2 * V), 1);
        STAMP(13 + V);
        const uint32_t hs = xb + (2 * w + ((lane >> 3) & 1)) * (2688 + 128 * V) + (lane >> 4) * 128 + (lane & 7) * 16;
        const uint32_t sa = sb + OFF_ST + (168 * V + 2 * q) * 8;
        uint4 sq[22];
        #pragma unroll
        for (int j = 0; j < 3; j++) sq[j] = lds128(sa + j * 64);
        #pragma unroll
        for (int j = 0; j < 22; j += 2) {
            uint32_t o[4];
            #pragma unroll
            for (int jj = 0; jj < 2; jj++) {
                const uint4 sv = sq[j + jj];
                float hv[4];
                #pragma unroll
                for (int i = 0; i < 4; i++) {
                    const float m = UF((i & 1) ? sv.z : sv.x);
                    const float gh = fmaf(-m, (i & 2) ? cg1 : cg0, ag[4 * (j + jj) + i]) * UF((i & 1) ? sv.w : sv.y);
                    const float p = gh * fmaf(-m, (i & 2) ? cu1 : cu0, au[4 * (j + jj) + i]);
                    hv[i] = fmaf(p, tanh_fast(gh), p);
                }
                o[2 * jj] = pack2(hv[0], hv[1]); o[2 * jj + 1] = pack2(hv[2], hv[3]);
            }
            #pragma unroll
            for (int k = (j ? 3 + 3 * j / 2 : 3); k < 6 + 3 * j / 2 && k < 22; k++) sq[k] = lds128(sa + k * 64);
            uint32_t ad = hs + j * 128;
            if (j == 20 && V == 0 && lane >= 16) ad = xb + 21504 + (lane & 7) * 16;
            stsm4(ad, o[0], o[1], o[2], o[3]);
        }
        fence_async_smem();
        mbar_arrive(bars + 8 * (B_EPI + V));
        STAMP(8 * V + 2);
    }
    if (c >= 128) return;
    {
        uint32_t r0[8], r1[8];
        #pragma unroll
        for (int i = 0; i < 8; i++) asm volatile("" : "=r"(r1[i]));
        #pragma unroll 1
        for (int e = 0; e < 2; e++) {
            #pragma unroll
            for (int i = 0; i < 8; i++) r0[i] = r1[i];
            mbar_wait(bars + 8 * (B_CONV + 2 * V + e), 0);
            conv_channel(sb + OFF_CONV + (2 * V + e) * CH_STRIDE, w, lane, r1, (V + e == 0) ? bars + 8 * B_CH0 : 0);
            if (e == 0) STAMP(8 * V + 3);
        }
        const int gam = g >> 2, qq = gam ? ((q + 3) & 3) : q;
        const uint32_t sp = sb + OFF_CONV + (2 * V + 1) * CH_STRIDE + ((63 - 4 * gam - qq) * 16 + 4 * w + (g & 3)) * 8;
        bar_sync(3 + V);
        #pragma unroll
        for (int a2 = 0; a2 < 8; a2++) sts64(sp - a2 * 1024, r0[a2], r1[a2]);
        fence_async_smem();
        mbar_arrive(bars + 8 * (B_SIG + V));
        STAMP(8 * V + 4);
    }
    if (V == 1) return;
    {
        const int tau = c >> 2, dg = c & 3;
        const uint32_t row = 8 * (w & 1) + 32 * (w >> 1);
        float acc[64];
        define_acc(acc);
        const float rr0 = __ldcg(&P.st[64 * tau + row + g].y), rr1 = __ldcg(&P.st[64 * tau + row + g + 16].y);
        mbar_wait(bars + 8 * B_FULLD, 0);
        STAMP(5);
        uint64_t dB = mkdesc(sb + wd_slot(0), 8192, 1024, 1), dA = mkdesc(sb + h_slot(0), 1024, 128, 0);
        #pragma unroll 1
        for (int st = 0; st < 21; st++) {
            WG_FENCE();
            wg_tt128(acc, dA, dB, st);
            wg_tt128(acc, dA + 128, dB + 128, 1);
            wg_tt128(acc, dA + 256, dB + 256, 1);
            wg_tt128(acc, dA + 384, dB + 384, 1);
            WG_COMMIT();
            const int sd = (st + 1) & 7;
            const uint32_t nb = bars + 8 * (B_FULLD + sd), np = ((st + 1) >> 3) & 1;
            uint32_t ok;
            asm volatile("{.reg .pred p; mbarrier.test_wait.parity.shared::cta.b64 p, [%1], %2; selp.u32 %0, 1, 0, p;}" : "=r"(ok) : "r"(nb), "r"(np) : "memory");
            dB = mkdesc(sb + wd_slot(sd), 8192, 1024, 1); dA = mkdesc(sb + h_slot(sd), 1024, 128, 0);
            WG_WAIT(1);
            if (lane == 0 && st > 0) mbar_arrive(bars + 8 * (st == 15 ? B_CH0 : B_EMPTYD + ((st - 1) & 7)));
            if (!ok) mbar_wait(nb, np);
            if (w == 0) STAMP2(20 + st);
        }
        WG_FENCE();
        wg_tt128(acc, dA, dB, 1);
        wg_tt128(acc, dA + 128, dB + 128, 1);
        WG_COMMIT();
        mbar_wait(bars + 8 * B_XO, 0);
        mbar_wait(bars + 8 * B_S, 0);
        const uint32_t xo = sb + OFF_CONV + (row + (lane & 7) + 16 * ((lane >> 3) & 1)) * 128;
        const uint32_t so = sb + wd_slot(6) + (w >> 1) * 8192 + q * 256 + (g & 1) * 8;
        uint32_t xr[8][4];
        uint2 sv[16];
        #pragma unroll
        for (int j = 0; j < 16; j += 2) {
            ldsm4(xr[j >> 1], xo + (j >> 3) * 8192 + ((((j & 7) + (lane >> 4)) ^ (lane & 7)) << 4));
            sv[j] = lds64(so + j * 512 + (((4 * (w & 1) + (g >> 1)) ^ (2 * q)) << 4));
            sv[j + 1] = lds64(so + j * 512 + 128 + (((4 * (w & 1) + (g >> 1)) ^ (2 * q + 1)) << 4));
        }
        WG_WAIT(0);
        fence_acc(acc);
        STAMP(6);
        #pragma unroll
        for (int j = 0; j < 16; j += 2) {
            #pragma unroll
            for (int i = 0; i < 4; i++) {
                const int jj = j + (i >> 1), hh = i & 1;
                const float f0 = acc[4 * jj + 2 * hh] * (hh ? rr1 : rr0), f1 = acc[4 * jj + 2 * hh + 1] * (hh ? rr1 : rr0);
                const uint32_t G = pack2(fmaf(f0, tanh_fast(f0), f0), fmaf(f1, tanh_fast(f1), f1));
                const uint32_t s2 = __byte_perm(sv[jj].x, sv[jj].y, hh ? 0x7632 : 0x5410);
                asm("fma.rn.bf16x2 %0, %1, %2, %0;" : "+r"(xr[j >> 1][i]) : "r"(s2), "r"(G));
            }
            stsm4(xo + (j >> 3) * 8192 + ((((j & 7) + (lane >> 4)) ^ (lane & 7)) << 4), xr[j >> 1][0], xr[j >> 1][1], xr[j >> 1][2], xr[j >> 1][3]);
        }
        fence_async_smem();
        bar_sync(1);
        if (w == 0 && elect_one()) {
            #pragma unroll
            for (int i = 0; i < 2; i++)
                asm volatile("cp.async.bulk.tensor.2d.global.shared::cta.bulk_group [%0, {%2, %3}], [%1];"
                    :: "l"(&M.out), "r"(sb + OFF_CONV + i * 8192), "r"(dg * 128 + 64 * i), "r"(tau * 64) : "memory");
            asm volatile("cp.async.bulk.commit_group; cp.async.bulk.wait_group.read 0;" ::: "memory");
        }
        STAMP(7); GSTAMP(23);
    }
}

__device__ __forceinline__ float2 cexp_p(float re2, float im, float p) {
    float sn, cs;
    const float mag = ex2(re2 * p), th = im * p;
    asm("sin.approx.ftz.f32 %0, %1;" : "=f"(sn) : "f"(th));
    asm("cos.approx.ftz.f32 %0, %1;" : "=f"(cs) : "f"(th));
    return make_float2(mag * cs, mag * sn);
}
__device__ __forceinline__ unsigned short ldu16(const void* p) { unsigned short v; asm volatile("ld.global.nc.u16 %0, [%1];" : "=h"(v) : "l"(p)); return v; }
__device__ __forceinline__ float2 cmul(float2 a, float2 b) { return make_float2(fmaf(a.x, b.x, -a.y * b.y), fmaf(a.x, b.y, a.y * b.x)); }
__device__ __forceinline__ float2 csqr(float2 a) { const float t = a.x * a.y; return make_float2(fmaf(a.x, a.x, -a.y * a.y), t + t); }
__device__ __forceinline__ void mma16816(float (&d)[4], const uint32_t (&a)[4], uint32_t b0, uint32_t b1) {
    asm volatile("mma.sync.aligned.m16n8k16.row.col.f32.bf16.bf16.f32 {%0,%1,%2,%3}, {%4,%5,%6,%7}, {%8,%9}, {%0,%1,%2,%3};"
        : "+f"(d[0]), "+f"(d[1]), "+f"(d[2]), "+f"(d[3]) : "r"(a[0]), "r"(a[1]), "r"(a[2]), "r"(a[3]), "r"(b0), "r"(b1));
}

__device__ __forceinline__ void aux_role(uint32_t sb, int w, const Params& P) {
    const int lane = threadIdx.x & 31, q = lane & 3, g = lane >> 2;
    const int c = blockIdx.x;
    const uint32_t bars = sb + OFF_BAR;
    if (c >= 128) {
        if (lane == 0) { mbar_arrive(bars + 8 * B_K); mbar_arrive(bars + 8 * (B_K + 1)); }
        return;
    }
    {
        const uint32_t cb = sb + OFF_CONV + w * CH_STRIDE;
        const uint32_t sF = cb + CH_A3;
        const int d = 4 * c + w;
        const int po = d * 128 + lane;
        unsigned short la = ldu16(P.logA + po), ai = ldu16(P.Aim + po), cr = ldu16(P.Cr + po), ci = ldu16(P.Ci + po);
        const float ldt = __bfloat162float(P.logdt[d]), dsk = __bfloat162float(P.Dskip[d]);
        float dacc[2][3][4];
        #pragma unroll
        for (int i = 0; i < 24; i++) (&dacc[0][0][0])[i] = 0.f;
        const float dt = bf_round(ex2(ldt * 1.4426950408889634f));
        #pragma unroll 1
        for (int ck = 0; ck < 4; ck++) {
            const uint32_t fa = cb + lane * 4 + (ck & 1) * 8064;
            const float re2 = bf_round(ex2(bf_lo((uint32_t)la) * 1.4426950408889634f)) * dt * -1.4426950408889634f, im = bf_lo((uint32_t)ai) * dt;
            const float2 C = make_float2(bf_lo((uint32_t)cr) * (dt + dt), bf_lo((uint32_t)ci) * -(dt + dt));
            {
                const int pn = po + 32 * min(ck + 1, 3);
                la = ldu16(P.logA + pn); ai = ldu16(P.Aim + pn); cr = ldu16(P.Cr + pn); ci = ldu16(P.Ci + pn);
            }
            const float2 z8 = cexp_p(re2, im, 8.f), y1 = cexp_p(re2, -im, 1.f);
            float2 b0 = make_float2(1.f, 0.f), b1 = cexp_p(re2, im, 64.f), b2 = csqr(b1), b3 = cmul(b2, b1), l0 = C;
            const uint32_t fm = cb + (ck & 1) * 8064 + (lane >> 3) * 144 + (lane & 7) * 16;
#define PK(v) pack2((v).x, (v).y)
            #pragma unroll 1
            for (uint32_t ro = 0; ro < 8 * 144; ro += 144) {
                stsm4(fm + (lane >> 3) * 7 * 144 + ro, PK(b0), PK(b1), PK(b2), PK(b3));
                stsf(fa + 32 * 144 + ro, UF(PK(l0)));
                b0 = cmul(b0, z8); b1 = cmul(b1, z8); b2 = cmul(b2, z8); b3 = cmul(b3, z8); l0 = cmul(l0, y1);
            }
            if (ck < 2) STAMP(56 + 3 * ck);
            const float2 y256 = cexp_p(re2, -im, 256.f), y2 = csqr(y1), y4 = csqr(y2), y8 = make_float2(z8.x, -z8.y);
            const float2 t0 = cmul(C, y256), t1 = cmul(t0, y256), t2 = cmul(t1, y256), t3_ = cmul(t2, y256);
            const float2 u1 = cmul(t0, y2), u2 = cmul(u1, y2), u3 = cmul(u2, y2);
            stsm4(fm + 40 * 144, PK(t0), PK(u1), PK(u2), PK(u3));
            stsm4(fm + 44 * 144, PK(t1), PK(cmul(t1, y4)), PK(t2), PK(cmul(t2, y4)));
            const float2 v0 = cmul(t3_, y8), v1 = cmul(v0, y256), v2 = cmul(v1, y256), v3 = cmul(v2, y256);
            stsm4(fm + 48 * 144, PK(v0), PK(v1), PK(v2), PK(v3));
            stsf(fa + 52 * 144, UF(PK(t3_)));
#undef PK
            if (ck < 2) STAMP(57 + 3 * ck);
            if (ck & 1) {
                uint32_t ln_; asm volatile("mov.u32 %0, %%laneid;" : "=r"(ln_));
                const uint32_t lda = cb + (ln_ & 15) * 144 + (ln_ & 16);
                const uint32_t ldb = cb + (32 + (ln_ & 7)) * 144 + (ln_ >> 3) * 16;
                __syncwarp();
                #pragma unroll
                for (int k2 = 0; k2 < 4; k2++) {
                    const uint32_t ko = (k2 >> 1) * 8064 + (k2 & 1) * 64;
                    uint32_t b[3][4];
                    #pragma unroll
                    for (int t3 = 0; t3 < 3; t3++) ldsm4(b[t3], ldb + t3 * 8 * 144 + ko);
                    #pragma unroll
                    for (int k = 0; k < 2; k++)
                        #pragma unroll
                        for (int mu = 0; mu < 2; mu++) {
                            uint32_t a[4];
                            ldsm4(a, lda + mu * 16 * 144 + ko + k * 32);
                            #pragma unroll
                            for (int t3 = 0; t3 < 3; t3++) mma16816(dacc[mu][t3], a, b[t3][2 * k], b[t3][2 * k + 1]);
                        }
                }
                __syncwarp();
                if (lane == 0) mbar_arrive(bars + 8 * (B_K + (ck >> 1)));
                STAMP(58 + 3 * (ck >> 1));
            }
        }
        STAMP(18);
        const uint32_t sG = cb + CH_G;
        if (lane == 0) dacc[0][0][0] += dsk;
        if (lane < 16) sts128(((lane & 8) ? cb + CH_U + 2048 + (lane & 4) * (UPLANE / 4) : sG + 128 + (lane & 4) * 48) + (lane & 3) * 16, 0, 0, 0, 0);
        {
            const uint32_t f0 = sF + (8 * g + 2 * q) * 4, f1 = sF + ((q < 2) ? 256 + 4 * g + 2 * q : 256 + 2 * g + 64 * q) * 4, st1 = (q < 2) ? 128 : 64;
            const uint32_t ga = sG + ((g & 1) ? 0 : 192) + (63 - (g >> 1) - 32 * q) * 2;
            #pragma unroll
            for (int i = 0; i < 4; i++) {
                const int mu = i >> 1, hh = i & 1;
                sts64(f0 + i * 256, FU(dacc[mu][0][2 * hh]), FU(dacc[mu][0][2 * hh + 1]));
                sts64(f1 + i * st1, FU(dacc[mu][1][2 * hh]), FU(dacc[mu][1][2 * hh + 1]));
                const uint32_t pk = pack2(dacc[mu][2][2 * hh], dacc[mu][2][2 * hh + 1]);
                if (q < 2) { sts16(ga - 8 * i, pk & 0xffff); sts16(ga - 8 * i - 32, pk >> 16); }
            }
            if (lane == 2) stsf(sF + 2048, dacc[0][2][0]);
        }
    }
    bar_sync(2);
    STAMP(19);
    const int rw = lane - 1 + 31 * w, u = min(rw, 77) - 14;
    const uint32_t o0 = CH_A3 + u * 4, o1 = CH_A3 + (128 + ((u + ((u >> 1) & 1)) >> 1)) * 4, o2 = CH_A3 + (256 + ((u + 1 + ((u >> 2) & 1)) >> 2)) * 4;
    const int kap = (lane >> 4) * 8 + ((lane >> 1) & 7), gam = lane & 1, hh = w >> 1, wp = w & 1;
    const uint32_t oa = CH_U + wp * UPLANE + (127 - 4 * kap - 2 * gam - hh) * 16;
    const uint32_t ob = CH_U + (wp ^ 1) * UPLANE + (128 - wp - 4 * kap - 2 * gam - hh) * 16;
    const uint32_t od = CH_A3 + (4 * wp + hh) * 512 + (kap >> 3) * 256 + (kap & 7) * 16 + gam * 8;
    #pragma unroll 1
    for (int k = 0; k < 4; k++) {
        const int ch = 2 * (k & 1) + (k >> 1);
        const uint32_t cb = sb + OFF_CONV + ch * CH_STRIDE;
        if (w < 3) {
            const uint32_t f0 = cb + o0, f1 = cb + o1, f2 = cb + o2;
            float kv[17];
            kv[0] = ldsf(u < 0 ? f1 : f0); if (u < 0) kv[0] = 0.f;
            #pragma unroll
            for (int s = 1; s < 4; s++) kv[s] = ldsf(f0 + s * 256);
            kv[4] = ldsf(u < 0 ? f0 + 1024 : f1 + 512);
            #pragma unroll
            for (int s = 5; s < 8; s++) kv[s] = ldsf(f1 + s * 128);
            kv[8] = ldsf(u < 0 ? f1 + 1024 : f2 + 512);
            #pragma unroll
            for (int s = 9; s < 16; s++) kv[s] = ldsf(f2 + s * 64);
            kv[16] = ldsf(u < 0 ? f2 + 1024 : cb + CH_A3 + 2048); if (u > 4) kv[16] = 0.f;
            uint32_t o[17];
            #pragma unroll
            for (int s = 0; s < 17; s++) o[s] = pack2(kv[s], __shfl_up_sync(0xffffffffu, kv[s], 1));
            if (lane > 0 && rw < 78) {
                const uint32_t ta = cb + CH_T + rw * 80;
                #pragma unroll
                for (int s4 = 0; s4 < 4; s4++) sts128(ta + s4 * 16, o[4 * s4], o[4 * s4 + 1], o[4 * s4 + 2], o[4 * s4 + 3]);
                stsf(ta + 64, UF(o[16]));
            }
        } else {
            const uint32_t ga = cb + CH_G + ((lane >> 3) & 1) * 192 + (lane >> 4) * 16 + (lane & 7) * 8;
            #pragma unroll
            for (int i = 0; i < 4; i++) {
                const uint2 x0 = lds64(ga + 32 * i), x1 = lds64(ga + 32 * i + 8);
                sts128(cb + CH_B3 + lane * 16 + 512 * i, x0.x, x0.y, x1.x, x1.y);
            }
        }
        mbar_wait(bars + 8 * B_U, 0);
        float p[24];
        const uint2 r0 = lds64(cb + ob + 24), r3 = lds64(cb + oa);
        uint32_t r[8];
        *(uint4*)&r[0] = lds128(cb + oa + 16); *(uint4*)&r[4] = lds128(cb + ob);
        p[0] = 0.f;
        p[1] = bf_lo(r0.x); p[2] = p[1] + bf_hi(r0.x); p[3] = p[2] + bf_lo(r0.y); p[4] = p[3] + bf_hi(r0.y);
        #pragma unroll
        for (int i = 0; i < 8; i++) { p[5 + 2 * i] = p[4 + 2 * i] + bf_lo(r[i]); p[6 + 2 * i] = p[5 + 2 * i] + bf_hi(r[i]); }
        p[21] = p[20] + bf_lo(r3.x); p[22] = p[21] + bf_hi(r3.x); p[23] = p[22] + bf_lo(r3.y);
        bar_sync(2);
        #pragma unroll
        for (int i = 0; i < 8; i += 4) {
            sts64(cb + od + i * 256, pack2(p[i + 9] - p[i], p[i + 10] - p[i + 1]), pack2(p[i + 11] - p[i + 2], p[i + 12] - p[i + 3]));
            sts64(cb + od + i * 256 + 128, pack2(p[i + 16] - p[i + 9], p[i + 17] - p[i + 10]), pack2(p[i + 18] - p[i + 11], p[i + 19] - p[i + 12]));
        }
        fence_async_smem();
        mbar_arrive(bars + 8 * (B_CONV + ch));
        if (k == 0) STAMP(17);
    }
    STAMP(21);
}

__global__ void __launch_bounds__(512, 1)
fused_kernel(const __grid_constant__ Params P, const __grid_constant__ Maps M) {
    extern __shared__ __align__(1024) uint8_t smem_raw[];
    const uint32_t sb = smem_u32(smem_raw);
    const uint32_t bars = sb + OFF_BAR;
    const int warp = __shfl_sync(0xffffffffu, threadIdx.x >> 5, 0);
    const int c = blockIdx.x, tg = c / 22, fb = c - 22 * tg;
    if (elect_one()) {
        if (warp == 0) { STAMP(24); GSTAMP(22); }
        asm volatile("" :: "l"(((const uint64_t*)&P)[warp < 12 ? warp : 0]));
        if (warp < 12) asm volatile("prefetch.tensormap [%0];" :: "l"(&M.x[0] + warp) : "memory");
        #pragma unroll
        for (int k = 0; k < 4; k++) {
            const int i = 16 * k + ((warp + 4) & 15);
            const uint32_t cnt = i >= B_CONV ? 128 : ((0xf0ull >> i) & 1) ? 8 : ((0xff0000ull >> i) & 1) ? 2 : ((0x3e00ff00f000ull >> i) & 1) ? 4 : 1;
            asm volatile("mbarrier.init.shared::cta.b64 [%0], %1;" :: "r"(bars + 8 * i), "r"(cnt) : "memory");
        }
        asm volatile("fence.mbarrier_init.release.cluster; fence.proxy.async.shared::cta;" ::: "memory");
        if (warp == 12) {
            mbar_expect(bars + 8 * B_FULLW, 16384);
            tma2d(sb + OFF_W, &M.wg, 64 * fb, 0, bars + 8 * B_FULLW);
            tma2d(sb + OFF_W + 8192, &M.wu, 64 * fb, 0, bars + 8 * B_FULLW);
            STAMP(31);
        } else if (warp == 4) {
            mbar_expect(bars + 8 * B_FULLX, 168 * 128);
            tma2d(sb + OFF_X, &M.x[0], 0, TOKG * tg, bars + 8 * B_FULLX);
        }
        if (sb & 1023) __trap();
    }
    __syncthreads();
    if (warp < 8) {
        asm volatile("setmaxnreg.inc.sync.aligned.u32 208;");
        consumer(sb, warp, P, M);
    } else if (warp < 12) {
        asm volatile("setmaxnreg.dec.sync.aligned.u32 72;");
        STAMP(32);
        aux_role(sb, warp - 8, P);
    } else {
        asm volatile("setmaxnreg.dec.sync.aligned.u32 24;");
        const int tau = c >> 2, dg = c & 3;
        if (elect_one()) {
            if (warp == 12) {
                #pragma unroll 1
                for (int st = 1; st < 8; st++) {
                    const uint32_t s = st & 3, fb_ = bars + 8 * (B_FULLW + s);
                    if (st == 2) mbar_wait(bars + 8 * B_FULLW, 0);
                    mbar_wait(bars + 8 * (B_EMPTYW + s), (st >> 2) ^ 1);
                    mbar_expect(fb_, 16384);
                    tma2d(sb + OFF_W + s * 16384, &M.wg, 64 * fb, 64 * st, fb_);
                    tma2d(sb + OFF_W + s * 16384 + 8192, &M.wu, 64 * fb, 64 * st, fb_);
                }
                if (c < 128) {
                    #pragma unroll 1
                    for (int st = 0; st < 22; st++) {
                        const int sd = st & 7;
                        if (st < 8) mbar_wait(bars + 8 * (uint32_t)((0x282823070d060504ull >> (8 * st)) & 0xff), st < 5);
                        else mbar_wait(bars + 8 * (B_EMPTYD + sd), ((st >> 3) & 1) ^ 1);
                        const uint32_t da = sb + wd_slot(sd), fb_ = bars + 8 * (B_FULLD + sd);
                        mbar_expect(fb_, 16384);
                        tma2d(da, &M.wd, 128 * dg, 64 * st, fb_);
                        tma2d(da + 8192, &M.wd, 128 * dg + 64, 64 * st, fb_);
                    }
                }
            } else if (warp < 15) {
                const int V = warp - 13;
                #pragma unroll 1
                for (int st = 1 - V; st < 8; st++) {
                    const uint32_t s = 2 * V + (st & 1);
                    if (s == 3 && st == 1) mbar_wait(bars + 8 * B_LNS, 0);
                    mbar_wait(bars + 8 * (B_EMPTYX + s), ((st >> 1) & 1) ^ 1);
                    mbar_expect(bars + 8 * (B_FULLX + s), (168 + 8 * V) * 128);
                    tma2d(sb + OFF_X + s * XBUF, &M.x[V], 64 * st, TOKG * tg + 168 * V, bars + 8 * (B_FULLX + s));
                }
                if (c < 128) {
                    if (V == 0) {
                        mbar_wait(bars + 8 * (B_STG + 1), 0);
                        #pragma unroll 1
                        for (int o = 8 * tau; o < 8 * tau + 8; o += 7) flag_wait(P.flags, F_H + 2 * (o / 43) + ((o % 43) >= 21), 22);
                        mbar_arrive(bars + 8 * B_HF);
                        STAMP(25);
                        #pragma unroll 1
                        for (int st = 0; st < 22; st++) {
                            const uint32_t fb_ = bars + 8 * (B_FULLD + (st & 7));
                            if (st == 6) mbar_wait(bars + 8 * B_SST, 0);
                            mbar_wait(bars + 8 * (B_EMPTYD + (st & 7)), ((st >> 3) & 1) ^ 1);
                            mbar_expect(fb_, 8192);
                            asm volatile("cp.async.bulk.tensor.5d.shared::cluster.global.mbarrier::complete_tx::bytes [%0], [%1, {%3, %3, %3, %4, %5}], [%2];"
                                :: "r"(sb + h_slot(st & 7)), "l"(&M.hld), "r"(fb_), "r"(0), "r"(2 * tau), "r"(8 * st) : "memory");
                        }
                    } else {
                        mbar_wait(bars + 8 * B_CH0, 0);
                        mbar_expect(bars + 8 * B_XO, 16384);
                        tma2d(sb + OFF_CONV, &M.xo, 128 * dg, 64 * tau, bars + 8 * B_XO);
                        tma2d(sb + OFF_CONV + 8192, &M.xo, 128 * dg + 64, 64 * tau, bars + 8 * B_XO);
                        flag_wait(P.flags, F_S + dg, 64);
                        STAMP(26);
                        mbar_wait(bars + 8 * B_CH0, 1);
                        mbar_expect(bars + 8 * B_S, 16384);
                        asm volatile("cp.async.bulk.tensor.5d.shared::cluster.global.mbarrier::complete_tx::bytes [%0], [%1, {%3, %3, %3, %4, %5}], [%2];"
                            :: "r"(sb + wd_slot(6)), "l"(&M.sld), "r"(bars + 8 * B_S), "r"(0), "r"(8 * dg), "r"(2 * tau) : "memory");
                        mbar_wait(bars + 8 * B_HF, 0);
                        exit_count(P.flags);
                    }
                }
            } else {
                mbar_wait(bars + 8 * B_LN, 0);
                STAMP2(0);
                if (c < 128) {
                    #pragma unroll 1
                    for (int i = 0; i < 2; i++)
                        asm volatile("cp.async.bulk.tensor.2d.global.shared::cta.bulk_group [%0, {%2, %3}], [%1];"
                            :: "l"(&M.xt), "r"(sb + OFF_LN + i * 8192), "r"((c & 1) * 1024 + (126 - (c & ~1)) * 8), "r"(256 * i) : "memory");
                    #pragma unroll 1
                    for (int i = 0; i < 2; i++) bulk_store(P.st + 16 * (c & ~1) + 8 * (c & 1) + 16 - 16 * i, sb + OFF_CSUM + 64 * i, 64);
                    asm volatile("cp.async.bulk.prefetch.L2.global [%0], %1;" :: "l"(P.Wd + c * (FF * DM / 128)), "r"(FF * DM / 64) : "memory");
                }
                asm volatile("cp.async.bulk.commit_group; cp.async.bulk.wait_group.read 0;" ::: "memory");
                mbar_arrive(bars + 8 * B_LNS);
                STAMP2(1);
                flag_signal(P.flags, F_A);
                STAMP2(2);
                flag_wait(P.flags, F_A, NCTA);
                STAMP(20);
                mbar_expect(bars + 8 * B_STATS, TOKG * 8);
                bulk_load(sb + OFF_ST, P.st + TOKG * tg, TOKG * 8, bars + 8 * B_STATS);
                if (c < 128) {
                    mbar_wait(bars + 8 * (B_K + 1), 0);
                    fence_async_smem();
                    mbar_expect(bars + 8 * B_U, 8 * 2048);
                    #pragma unroll 1
                    for (int i = 0; i < 8; i++)
                        bulk_load(sb + OFF_CONV + (i >> 1) * CH_STRIDE + CH_U + (i & 1) * UPLANE, P.xnT + 4 * c * 256 + i * 128, 2048, bars + 8 * B_U);
                } else exit_count(P.flags);
                #pragma unroll 1
                for (int V = 0; V < 2; V++) {
                    mbar_wait(bars + 8 * (B_EPI + V), 0);
                    STAMP2(3 + 2 * V);
                    asm volatile("cp.async.bulk.tensor.3d.global.shared::cta.bulk_group [%0, {%2, %3, %4}], [%1];"
                        :: "l"(&M.hst[V]), "r"(sb + OFF_X + V * 2 * XBUF), "r"(0), "r"(43 * tg + 21 * V), "r"(8 * fb) : "memory");
                    flag_signal(P.flags, F_H + 2 * tg + V);
                    mbar_arrive(bars + 8 * (B_STG + V));
                    STAMP2(4 + 2 * V);
                }
                if (c < 128) {
                    #pragma unroll 1
                    for (int V = 0; V < 2; V++) {
                        mbar_wait(bars + 8 * (B_SIG + V), 0);
                        STAMP2(7 + 2 * V);
                        bulk_store(P.S + (2 * c + V) * 1024, sb + OFF_CONV + (2 * V + 1) * CH_STRIDE, 8192);
                        flag_signal(P.flags, F_S + (c >> 5));
                        STAMP2(8 + 2 * V);
                    }
                    mbar_arrive(bars + 8 * B_SST);
                }
            }
        }
    }
}

typedef CUresult (*EncodeFn)(CUtensorMap*, CUtensorMapDataType, cuuint32_t, void*, const cuuint64_t*, const cuuint64_t*, const cuuint32_t*,
                             const cuuint32_t*, CUtensorMapInterleave, CUtensorMapSwizzle, CUtensorMapL2promotion, CUtensorMapFloatOOBfill);

void make_map(EncodeFn enc, CUtensorMap* m, const void* ptr, int rank, const cuuint64_t* dims, const cuuint64_t* strides, const cuuint32_t* box, bool swz) {
    const cuuint32_t es[5] = {1, 1, 1, 1, 1};
    enc(m, CU_TENSOR_MAP_DATA_TYPE_BFLOAT16, rank, (void*)ptr, dims, strides, box, es, CU_TENSOR_MAP_INTERLEAVE_NONE,
        swz ? CU_TENSOR_MAP_SWIZZLE_128B : CU_TENSOR_MAP_SWIZZLE_NONE, CU_TENSOR_MAP_L2_PROMOTION_L2_128B, CU_TENSOR_MAP_FLOAT_OOB_FILL_NONE);
}
void make_map2(EncodeFn enc, CUtensorMap* m, const void* ptr, cuuint64_t inner, cuuint64_t outer, cuuint32_t rows) {
    const cuuint64_t dims[2] = {inner, outer}, strides[1] = {inner * 2};
    const cuuint32_t box[2] = {64, rows};
    make_map(enc, m, ptr, 2, dims, strides, box, true);
}

}

extern "C" void kernel_launch(void* const* d_in, const int* in_sizes, int n_in, void* d_out, int out_size) {
    (void)in_sizes; (void)n_in; (void)out_size;
    static EncodeFn enc = nullptr;
    static void *hptr, *p_xnT, *p_st, *p_S, *p_flags;
    if (!enc) {
        cudaDriverEntryPointQueryResult qr;
        cudaGetDriverEntryPoint("cuTensorMapEncodeTiled", (void**)&enc, cudaEnableDefault, &qr);
        cudaFuncSetAttribute(fused_kernel, cudaFuncAttributeMaxDynamicSharedMemorySize, SMEM_BYTES);
        cudaGetSymbolAddress(&hptr, g_H); cudaGetSymbolAddress(&p_xnT, g_xnT); cudaGetSymbolAddress(&p_st, g_st);
        cudaGetSymbolAddress(&p_S, g_S); cudaGetSymbolAddress(&p_flags, g_flags);
    }
    Params P;
    P.x = (const __nv_bfloat16*)d_in[0]; P.logA = (const __nv_bfloat16*)d_in[1]; P.Aim = (const __nv_bfloat16*)d_in[2];
    P.Cr = (const __nv_bfloat16*)d_in[3]; P.Ci = (const __nv_bfloat16*)d_in[4]; P.logdt = (const __nv_bfloat16*)d_in[5];
    P.Dskip = (const __nv_bfloat16*)d_in[6];
    P.Wd = (const __nv_bfloat16*)d_in[10]; P.xnT = (uint4*)p_xnT; P.st = (float2*)p_st; P.S = (uint2*)p_S; P.flags = (unsigned*)p_flags;
    Maps M;
    make_map2(enc, &M.x[0], d_in[0], DM, SEQ, 168); make_map2(enc, &M.x[1], d_in[0], DM, SEQ, 176);
    make_map2(enc, &M.xo, d_in[0], DM, SEQ, 64);    make_map2(enc, &M.out, d_out, DM, SEQ, 64);
    make_map2(enc, &M.wg, d_in[8], FF, DM, 64);     make_map2(enc, &M.wu, d_in[9], FF, DM, 64);
    make_map2(enc, &M.wd, d_in[10], DM, FF, 64);
    for (int v = 0; v < 2; v++) {
        const cuuint64_t dims[3] = {64, 256, 172}, strides[2] = {128, 32768};
        const cuuint32_t box[3] = {64, (cuuint32_t)(21 + v), 8};
        make_map(enc, &M.hst[v], hptr, 3, dims, strides, box, false);
    }
    {
        const cuuint64_t dims[2] = {2048, 512}, strides[1] = {4096};
        const cuuint32_t box[2] = {16, 256};
        make_map(enc, &M.xt, p_xnT, 2, dims, strides, box, false);
    }
    {
        const cuuint64_t dims[5] = {64, 2, 4, 32, 64}, strides[4] = {4 * 8192, 8192, 8 * 8192, 128};
        const cuuint32_t box[5] = {64, 2, 4, 8, 2};
        make_map(enc, &M.sld, p_S, 5, dims, strides, box, true);
    }
    {
        const cuuint64_t dims[5] = {64, 2, 2, 64, 172}, strides[4] = {256, 128, 512, 32768};
        const cuuint32_t box[5] = {64, 2, 2, 2, 8};
        make_map(enc, &M.hld, hptr, 5, dims, strides, box, false);
    }
    fused_kernel<<<NCTA, 512, SMEM_BYTES>>>(P, M);
}
```

```cpp
#include <cuda_runtime.h>
#include <cuda_bf16.h>
#include <cuda.h>
#include <stdint.h>

#define PROF 0

namespace {

constexpr int SEQ = 2048, DM = 512, FF = 1376;
constexpr int NCTA = 132;
#define HOLD0 4
#define HOLD1 7
#define LAG 2
constexpr int TOKG = 344;

constexpr uint32_t OFF_W = 0;
constexpr uint32_t XBUF = 22528;
constexpr uint32_t OFF_X = 65536;
constexpr uint32_t OFF_CONV = 155648;
constexpr uint32_t CH_STRIDE = 16640;
constexpr uint32_t CH_T = 0;
constexpr uint32_t CH_A3 = 6272;
constexpr uint32_t CH_B3 = 10368;
constexpr uint32_t CH_U = 12416;
constexpr uint32_t CH_G = CH_A3 + 2064;
constexpr uint32_t UPLANE = 2112;
constexpr uint32_t OFF_LN = OFF_X + 3 * XBUF;
constexpr uint32_t OFF_ST = 222208;
constexpr uint32_t OFF_CSUM = 230400;
constexpr uint32_t OFF_BAR = 231168;
constexpr uint32_t SMEM_BYTES = 231680;

enum {
    B_FULLW = 0, B_EMPTYW = 4, B_FULLX = 8, B_EMPTYX = 12, B_FULLD = 16, B_EMPTYD = 24,
    B_U = 32, B_XO = 33, B_S = 34, B_STG = 35, B_HF = 37, B_STATS = 38, B_LNS = 39, B_SST = 40,
    B_LNX = 41, B_GO = 42, B_CH0 = 43, B_K = 44,
    B_CONV = 46, B_LN = 50, B_CS = 51, B_EPI = 52, B_SIG = 54,
    B_RDY = 56,
    B_COUNT = 64
};
enum { F_A = 0, F_H = 1, F_S = 13, F_EXIT = 17, F_COUNT = 18 };

__device__ uint4 g_xnT[DM * 256];
__device__ float2 g_st[6 * TOKG];
__device__ uint4 g_H[172 * 256 * 8];
__device__ uint2 g_S[256 * 1024];
__device__ unsigned g_flags[F_COUNT * 32];
#define STAMP(i) do {} while (0)
#define GSTAMP(i) do {} while (0)
#define STAMP2(i) do {} while (0)

__device__ __forceinline__ uint32_t smem_u32(const void* p) { return (uint32_t)__cvta_generic_to_shared(p); }
__device__ __forceinline__ void mbar_expect(uint32_t bar, uint32_t bytes) { asm volatile("mbarrier.arrive.expect_tx.shared::cta.b64 _, [%0], %1;" :: "r"(bar), "r"(bytes) : "memory"); }
__device__ __forceinline__ void mbar_arrive(uint32_t bar) { asm volatile("mbarrier.arrive.shared::cta.b64 _, [%0];" :: "r"(bar) : "memory"); }
__device__ __forceinline__ void mbar_wait(uint32_t bar, uint32_t parity) {
    asm volatile("{.reg .pred p; .reg .u32 n; mov.u32 n, 0x20000;\n"
                 "LW: mbarrier.try_wait.parity.shared::cta.b64 p, [%0], %1;\n"
                 "sub.u32 n, n, 1; setp.eq.or.u32 p, n, 0, p; @!p bra LW;}" :: "r"(bar), "r"(parity) : "memory");
}
__device__ __forceinline__ void mbar_arrive_pair(uint32_t bar) {
    asm volatile("{.reg .b32 r, p; mov.u32 p, %%cluster_ctarank; xor.b32 p, p, 1; mapa.shared::cluster.u32 r, %0, p;\n"
                 "mbarrier.arrive.shared::cta.b64 _, [%0]; mbarrier.arrive.shared::cluster.b64 _, [r];}" :: "r"(bar) : "memory");
}
__device__ __forceinline__ bool elect_one() { uint32_t p; asm volatile("{.reg .pred P; elect.sync _|P, 0xffffffff; selp.u32 %0, 1, 0, P;}" : "=r"(p)); return p; }
__device__ __forceinline__ void tma2d(uint32_t dst, const CUtensorMap* m, int c0, int c1, uint32_t bar) {
    asm volatile("cp.async.bulk.tensor.2d.shared::cluster.global.mbarrier::complete_tx::bytes [%0], [%1, {%3, %4}], [%2];"
        :: "r"(dst), "l"(m), "r"(bar), "r"(c0), "r"(c1) : "memory");
}
__device__ __forceinline__ void bulk_load(uint32_t dst, const void* src, uint32_t bytes, uint32_t bar) {
    asm volatile("cp.async.bulk.shared::cluster.global.mbarrier::complete_tx::bytes [%0], [%1], %2, [%3];" :: "r"(dst), "l"(src), "r"(bytes), "r"(bar) : "memory");
}
__device__ __forceinline__ void bulk_store(void* dst, uint32_t src, uint32_t bytes) {
    asm volatile("cp.async.bulk.global.shared::cta.bulk_group [%0], [%1], %2;" :: "l"(dst), "r"(src), "r"(bytes) : "memory");
}
__device__ __forceinline__ void fence_async_smem() { asm volatile("fence.proxy.async.shared::cta;" ::: "memory"); }
__device__ __forceinline__ void flag_wait(unsigned* g_flags, int f, unsigned target) {
    asm volatile("{.reg .pred p; .reg .u32 n, v; mov.u32 n, 0x40000;\n"
                 "LF: ld.acquire.gpu.global.u32 v, [%0]; setp.ge.u32 p, v, %1; @p bra LD;\n"
                 "sub.u32 n, n, 1; setp.ne.u32 p, n, 0; @p bra LF; trap;\nLD: }"
                 :: "l"(g_flags + f * 32), "r"(target) : "memory");
}
__device__ __forceinline__ void flag_signal(unsigned* g_flags, int f) {
    asm volatile("cp.async.bulk.commit_group; cp.async.bulk.wait_group 0; red.relaxed.gpu.global.add.u32 [%0], 1;" :: "l"(g_flags + f * 32) : "memory");
}
__device__ __forceinline__ void exit_count(unsigned* g_flags) {
    if (atomicAdd(g_flags + F_EXIT * 32, 1u) == NCTA - 1) {
        #pragma unroll 1
        for (int i = 0; i < F_COUNT; i++) g_flags[i * 32] = 0;
    }
}
__device__ __forceinline__ void bar_sync(int id) { asm volatile("bar.sync %0, 128;" :: "r"(id) : "memory"); }
__device__ __forceinline__ uint64_t mkdesc(uint32_t addr, uint32_t lbo, uint32_t sbo, uint32_t swz) {
    return (uint64_t)(((addr & 0x3FFFF) >> 4) | ((lbo >> 4) << 16)) | ((uint64_t)((sbo >> 4) | (swz << 30)) << 32);
}
#define WG_FENCE() asm volatile("wgmma.fence.sync.aligned;" ::: "memory")
#define WG_COMMIT() asm volatile("wgmma.commit_group.sync.aligned;" ::: "memory")
#define WG_WAIT(n) asm volatile("wgmma.wait_group.sync.aligned " #n ";" ::: "memory")
template <int N> __device__ __forceinline__ void fence_acc(float (&d)[N]) {
    #pragma unroll
    for (int i = 0; i < N; i++) asm volatile("" : "+f"(d[i]) :: "memory");
}
template <int N> __device__ __forceinline__ void define_acc(float (&d)[N]) {
    #pragma unroll
    for (int i = 0; i < N; i++) asm volatile("" : "=f"(d[i]));
}
__device__ __forceinline__ uint32_t pack2(float lo, float hi) { uint32_t r; asm("cvt.rn.bf16x2.f32 %0, %1, %2;" : "=r"(r) : "f"(hi), "f"(lo)); return r; }
__device__ __forceinline__ float bf_lo(uint32_t v) { return __uint_as_float(v << 16); }
__device__ __forceinline__ float bf_hi(uint32_t v) { return __uint_as_float(v & 0xffff0000u); }
__device__ __forceinline__ float bf_round(float v) { return bf_hi(pack2(0.f, v)); }
__device__ __forceinline__ float tanh_fast(float v) { float r; asm("tanh.approx.f32 %0, %1;" : "=f"(r) : "f"(v)); return r; }
__device__ __forceinline__ float ex2(float v) { float r; asm("ex2.approx.ftz.f32 %0, %1;" : "=f"(r) : "f"(v)); return r; }
__device__ __forceinline__ uint4 lds128(uint32_t a) { uint4 v; asm volatile("ld.shared.v4.b32 {%0,%1,%2,%3}, [%4];" : "=r"(v.x), "=r"(v.y), "=r"(v.z), "=r"(v.w) : "r"(a)); return v; }
__device__ __forceinline__ uint2 lds64(uint32_t a) { uint2 v; asm volatile("ld.shared.v2.b32 {%0,%1}, [%2];" : "=r"(v.x), "=r"(v.y) : "r"(a)); return v; }
__device__ __forceinline__ float ldsf(uint32_t a) { float v; asm volatile("ld.shared.f32 %0, [%1];" : "=f"(v) : "r"(a)); return v; }
__device__ __forceinline__ void sts128(uint32_t a, uint32_t x, uint32_t y, uint32_t z, uint32_t w) { asm volatile("st.shared.v4.b32 [%0], {%1,%2,%3,%4};" :: "r"(a), "r"(x), "r"(y), "r"(z), "r"(w) : "memory"); }
__device__ __forceinline__ void sts64(uint32_t a, uint32_t x, uint32_t y) { asm volatile("st.shared.v2.b32 [%0], {%1,%2};" :: "r"(a), "r"(x), "r"(y) : "memory"); }
__device__ __forceinline__ void stsf(uint32_t a, float x) { asm volatile("st.shared.f32 [%0], %1;" :: "r"(a), "f"(x) : "memory"); }
__device__ __forceinline__ void sts16(uint32_t a, uint32_t x) { asm volatile("st.shared.b16 [%0], %1;" :: "r"(a), "h"((unsigned short)x) : "memory"); }
__device__ __forceinline__ void stsm4(uint32_t a, uint32_t r0, uint32_t r1, uint32_t r2, uint32_t r3) {
    asm volatile("stmatrix.sync.aligned.m8n8.x4.shared.b16 [%0], {%1,%2,%3,%4};" :: "r"(a), "r"(r0), "r"(r1), "r"(r2), "r"(r3) : "memory");
}
__device__ __forceinline__ void ldsm4(uint32_t (&r)[4], uint32_t a) {
    asm volatile("ldmatrix.sync.aligned.m8n8.x4.shared.b16 {%0,%1,%2,%3}, [%4];" : "=r"(r[0]), "=r"(r[1]), "=r"(r[2]), "=r"(r[3]) : "r"(a) : "memory");
}
#define FU(x) __float_as_uint(x)
#define UF(x) __uint_as_float(x)
__device__ __forceinline__ uint32_t wd_slot(int s) { return (uint32_t)((0xb9a9403056201000ull >> (8 * s)) & 0xff) << 10; }
__device__ __forceinline__ uint32_t h_slot(int s) { return (uint32_t)((0xd1c9d98c847c746cull >> (8 * s)) & 0xff) << 10; }

template<int N> __device__ __forceinline__ void wg_rs(float (&d)[64], uint32_t a0, uint32_t a1, uint32_t a2, uint32_t a3, uint64_t db);
template<> __device__ __forceinline__ void wg_rs<128>(float (&d)[64], uint32_t a0, uint32_t a1, uint32_t a2, uint32_t a3, uint64_t db) {
  asm volatile("{.reg .pred p; setp.ne.b32 p, 1, 0; wgmma.mma_async.sync.aligned.m64n128k16.f32.bf16.bf16 {%0,%1,%2,%3,%4,%5,%6,%7,%8,%9,%10,%11,%12,%13,%14,%15,%16,%17,%18,%19,%20,%21,%22,%23,%24,%25,%26,%27,%28,%29,%30,%31,%32,%33,%34,%35,%36,%37,%38,%39,%40,%41,%42,%43,%44,%45,%46,%47,%48,%49,%50,%51,%52,%53,%54,%55,%56,%57,%58,%59,%60,%61,%62,%63}, {%64,%65,%66,%67}, %68, p, 1, 1, 0;}"
    : "+f"(d[0]),"+f"(d[1]),"+f"(d[2]),"+f"(d[3]),"+f"(d[4]),"+f"(d[5]),"+f"(d[6]),"+f"(d[7]),"+f"(d[8]),"+f"(d[9]),"+f"(d[10]),"+f"(d[11]),"+f"(d[12]),"+f"(d[13]),"+f"(d[14]),"+f"(d[15]),"+f"(d[16]),"+f"(d[17]),"+f"(d[18]),"+f"(d[19]),"+f"(d[20]),"+f"(d[21]),"+f"(d[22]),"+f"(d[23]),"+f"(d[24]),"+f"(d[25]),"+f"(d[26]),"+f"(d[27]),"+f"(d[28]),"+f"(d[29]),"+f"(d[30]),"+f"(d[31]),"+f"(d[32]),"+f"(d[33]),"+f"(d[34]),"+f"(d[35]),"+f"(d[36]),"+f"(d[37]),"+f"(d[38]),"+f"(d[39]),"+f"(d[40]),"+f"(d[41]),"+f"(d[42]),"+f"(d[43]),"+f"(d[44]),"+f"(d[45]),"+f"(d[46]),"+f"(d[47]),"+f"(d[48]),"+f"(d[49]),"+f"(d[50]),"+f"(d[51]),"+f"(d[52]),"+f"(d[53]),"+f"(d[54]),"+f"(d[55]),"+f"(d[56]),"+f"(d[57]),"+f"(d[58]),"+f"(d[59]),"+f"(d[60]),"+f"(d[61]),"+f"(d[62]),"+f"(d[63]) : "r"(a0), "r"(a1), "r"(a2), "r"(a3), "l"(db));
}
template<> __device__ __forceinline__ void wg_rs<120>(float (&d)[64], uint32_t a0, uint32_t a1, uint32_t a2, uint32_t a3, uint64_t db) {
  asm volatile("{.reg .pred p; setp.ne.b32 p, 1, 0; wgmma.mma_async.sync.aligned.m64n120k16.f32.bf16.bf16 {%0,%1,%2,%3,%4,%5,%6,%7,%8,%9,%10,%11,%12,%13,%14,%15,%16,%17,%18,%19,%20,%21,%22,%23,%24,%25,%26,%27,%28,%29,%30,%31,%32,%33,%34,%35,%36,%37,%38,%39,%40,%41,%42,%43,%44,%45,%46,%47,%48,%49,%50,%51,%52,%53,%54,%55,%56,%57,%58,%59}, {%60,%61,%62,%63}, %64, p, 1, 1, 0;}"
    : "+f"(d[0]),"+f"(d[1]),"+f"(d[2]),"+f"(d[3]),"+f"(d[4]),"+f"(d[5]),"+f"(d[6]),"+f"(d[7]),"+f"(d[8]),"+f"(d[9]),"+f"(d[10]),"+f"(d[11]),"+f"(d[12]),"+f"(d[13]),"+f"(d[14]),"+f"(d[15]),"+f"(d[16]),"+f"(d[17]),"+f"(d[18]),"+f"(d[19]),"+f"(d[20]),"+f"(d[21]),"+f"(d[22]),"+f"(d[23]),"+f"(d[24]),"+f"(d[25]),"+f"(d[26]),"+f"(d[27]),"+f"(d[28]),"+f"(d[29]),"+f"(d[30]),"+f"(d[31]),"+f"(d[32]),"+f"(d[33]),"+f"(d[34]),"+f"(d[35]),"+f"(d[36]),"+f"(d[37]),"+f"(d[38]),"+f"(d[39]),"+f"(d[40]),"+f"(d[41]),"+f"(d[42]),"+f"(d[43]),"+f"(d[44]),"+f"(d[45]),"+f"(d[46]),"+f"(d[47]),"+f"(d[48]),"+f"(d[49]),"+f"(d[50]),"+f"(d[51]),"+f"(d[52]),"+f"(d[53]),"+f"(d[54]),"+f"(d[55]),"+f"(d[56]),"+f"(d[57]),"+f"(d[58]),"+f"(d[59]) : "r"(a0), "r"(a1), "r"(a2), "r"(a3), "l"(db));
}
template<> __device__ __forceinline__ void wg_rs<112>(float (&d)[64], uint32_t a0, uint32_t a1, uint32_t a2, uint32_t a3, uint64_t db) {
  asm volatile("{.reg .pred p; setp.ne.b32 p, 1, 0; wgmma.mma_async.sync.aligned.m64n112k16.f32.bf16.bf16 {%0,%1,%2,%3,%4,%5,%6,%7,%8,%9,%10,%11,%12,%13,%14,%15,%16,%17,%18,%19,%20,%21,%22,%23,%24,%25,%26,%27,%28,%29,%30,%31,%32,%33,%34,%35,%36,%37,%38,%39,%40,%41,%42,%43,%44,%45,%46,%47,%48,%49,%50,%51,%52,%53,%54,%55}, {%56,%57,%58,%59}, %60, p, 1, 1, 0;}"
    : "+f"(d[0]),"+f"(d[1]),"+f"(d[2]),"+f"(d[3]),"+f"(d[4]),"+f"(d[5]),"+f"(d[6]),"+f"(d[7]),"+f"(d[8]),"+f"(d[9]),"+f"(d[10]),"+f"(d[11]),"+f"(d[12]),"+f"(d[13]),"+f"(d[14]),"+f"(d[15]),"+f"(d[16]),"+f"(d[17]),"+f"(d[18]),"+f"(d[19]),"+f"(d[20]),"+f"(d[21]),"+f"(d[22]),"+f"(d[23]),"+f"(d[24]),"+f"(d[25]),"+f"(d[26]),"+f"(d[27]),"+f"(d[28]),"+f"(d[29]),"+f"(d[30]),"+f"(d[31]),"+f"(d[32]),"+f"(d[33]),"+f"(d[34]),"+f"(d[35]),"+f"(d[36]),"+f"(d[37]),"+f"(d[38]),"+f"(d[39]),"+f"(d[40]),"+f"(d[41]),"+f"(d[42]),"+f"(d[43]),"+f"(d[44]),"+f"(d[45]),"+f"(d[46]),"+f"(d[47]),"+f"(d[48]),"+f"(d[49]),"+f"(d[50]),"+f"(d[51]),"+f"(d[52]),"+f"(d[53]),"+f"(d[54]),"+f"(d[55]) : "r"(a0), "r"(a1), "r"(a2), "r"(a3), "l"(db));
}
template<> __device__ __forceinline__ void wg_rs<104>(float (&d)[64], uint32_t a0, uint32_t a1, uint32_t a2, uint32_t a3, uint64_t db) {
  asm volatile("{.reg .pred p; setp.ne.b32 p, 1, 0; wgmma.mma_async.sync.aligned.m64n104k16.f32.bf16.bf16 {%0,%1,%2,%3,%4,%5,%6,%7,%8,%9,%10,%11,%12,%13,%14,%15,%16,%17,%18,%19,%20,%21,%22,%23,%24,%25,%26,%27,%28,%29,%30,%31,%32,%33,%34,%35,%36,%37,%38,%39,%40,%41,%42,%43,%44,%45,%46,%47,%48,%49,%50,%51}, {%52,%53,%54,%55}, %56, p, 1, 1, 0;}"
    : "+f"(d[0]),"+f"(d[1]),"+f"(d[2]),"+f"(d[3]),"+f"(d[4]),"+f"(d[5]),"+f"(d[6]),"+f"(d[7]),"+f"(d[8]),"+f"(d[9]),"+f"(d[10]),"+f"(d[11]),"+f"(d[12]),"+f"(d[13]),"+f"(d[14]),"+f"(d[15]),"+f"(d[16]),"+f"(d[17]),"+f"(d[18]),"+f"(d[19]),"+f"(d[20]),"+f"(d[21]),"+f"(d[22]),"+f"(d[23]),"+f"(d[24]),"+f"(d[25]),"+f"(d[26]),"+f"(d[27]),"+f"(d[28]),"+f"(d[29]),"+f"(d[30]),"+f"(d[31]),"+f"(d[32]),"+f"(d[33]),"+f"(d[34]),"+f"(d[35]),"+f"(d[36]),"+f"(d[37]),"+f"(d[38]),"+f"(d[39]),"+f"(d[40]),"+f"(d[41]),"+f"(d[42]),"+f"(d[43]),"+f"(d[44]),"+f"(d[45]),"+f"(d[46]),"+f"(d[47]),"+f"(d[48]),"+f"(d[49]),"+f"(d[50]),"+f"(d[51]) : "r"(a0), "r"(a1), "r"(a2), "r"(a3), "l"(db));
}
template<> __device__ __forceinline__ void wg_rs<96>(float (&d)[64], uint32_t a0, uint32_t a1, uint32_t a2, uint32_t a3, uint64_t db) {
  asm volatile("{.reg .pred p; setp.ne.b32 p, 1, 0; wgmma.mma_async.sync.aligned.m64n96k16.f32.bf16.bf16 {%0,%1,%2,%3,%4,%5,%6,%7,%8,%9,%10,%11,%12,%13,%14,%15,%16,%17,%18,%19,%20,%21,%22,%23,%24,%25,%26,%27,%28,%29,%30,%31,%32,%33,%34,%35,%36,%37,%38,%39,%40,%41,%42,%43,%44,%45,%46,%47}, {%48,%49,%50,%51}, %52, p, 1, 1, 0;}"
    : "+f"(d[0]),"+f"(d[1]),"+f"(d[2]),"+f"(d[3]),"+f"(d[4]),"+f"(d[5]),"+f"(d[6]),"+f"(d[7]),"+f"(d[8]),"+f"(d[9]),"+f"(d[10]),"+f"(d[11]),"+f"(d[12]),"+f"(d[13]),"+f"(d[14]),"+f"(d[15]),"+f"(d[16]),"+f"(d[17]),"+f"(d[18]),"+f"(d[19]),"+f"(d[20]),"+f"(d[21]),"+f"(d[22]),"+f"(d[23]),"+f"(d[24]),"+f"(d[25]),"+f"(d[26]),"+f"(d[27]),"+f"(d[28]),"+f"(d[29]),"+f"(d[30]),"+f"(d[31]),"+f"(d[32]),"+f"(d[33]),"+f"(d[34]),"+f"(d[35]),"+f"(d[36]),"+f"(d[37]),"+f"(d[38]),"+f"(d[39]),"+f"(d[40]),"+f"(d[41]),"+f"(d[42]),"+f"(d[43]),"+f"(d[44]),"+f"(d[45]),"+f"(d[46]),"+f"(d[47]) : "r"(a0), "r"(a1), "r"(a2), "r"(a3), "l"(db));
}
template<> __device__ __forceinline__ void wg_rs<88>(float (&d)[64], uint32_t a0, uint32_t a1, uint32_t a2, uint32_t a3, uint64_t db) {
  asm volatile("{.reg .pred p; setp.ne.b32 p, 1, 0; wgmma.mma_async.sync.aligned.m64n88k16.f32.bf16.bf16 {%0,%1,%2,%3,%4,%5,%6,%7,%8,%9,%10,%11,%12,%13,%14,%15,%16,%17,%18,%19,%20,%21,%22,%23,%24,%25,%26,%27,%28,%29,%30,%31,%32,%33,%34,%35,%36,%37,%38,%39,%40,%41,%42,%43}, {%44,%45,%46,%47}, %48, p, 1, 1, 0;}"
    : "+f"(d[0]),"+f"(d[1]),"+f"(d[2]),"+f"(d[3]),"+f"(d[4]),"+f"(d[5]),"+f"(d[6]),"+f"(d[7]),"+f"(d[8]),"+f"(d[9]),"+f"(d[10]),"+f"(d[11]),"+f"(d[12]),"+f"(d[13]),"+f"(d[14]),"+f"(d[15]),"+f"(d[16]),"+f"(d[17]),"+f"(d[18]),"+f"(d[19]),"+f"(d[20]),"+f"(d[21]),"+f"(d[22]),"+f"(d[23]),"+f"(d[24]),"+f"(d[25]),"+f"(d[26]),"+f"(d[27]),"+f"(d[28]),"+f"(d[29]),"+f"(d[30]),"+f"(d[31]),"+f"(d[32]),"+f"(d[33]),"+f"(d[34]),"+f"(d[35]),"+f"(d[36]),"+f"(d[37]),"+f"(d[38]),"+f"(d[39]),"+f"(d[40]),"+f"(d[41]),"+f"(d[42]),"+f"(d[43]) : "r"(a0), "r"(a1), "r"(a2), "r"(a3), "l"(db));
}
template<> __device__ __forceinline__ void wg_rs<80>(float (&d)[64], uint32_t a0, uint32_t a1, uint32_t a2, uint32_t a3, uint64_t db) {
  asm volatile("{.reg .pred p; setp.ne.b32 p, 1, 0; wgmma.mma_async.sync.aligned.m64n80k16.f32.bf16.bf16 {%0,%1,%2,%3,%4,%5,%6,%7,%8,%9,%10,%11,%12,%13,%14,%15,%16,%17,%18,%19,%20,%21,%22,%23,%24,%25,%26,%27,%28,%29,%30,%31,%32,%33,%34,%35,%36,%37,%38,%39}, {%40,%41,%42,%43}, %44, p, 1, 1, 0;}"
    : "+f"(d[0]),"+f"(d[1]),"+f"(d[2]),"+f"(d[3]),"+f"(d[4]),"+f"(d[5]),"+f"(d[6]),"+f"(d[7]),"+f"(d[8]),"+f"(d[9]),"+f"(d[10]),"+f"(d[11]),"+f"(d[12]),"+f"(d[13]),"+f"(d[14]),"+f"(d[15]),"+f"(d[16]),"+f"(d[17]),"+f"(d[18]),"+f"(d[19]),"+f"(d[20]),"+f"(d[21]),"+f"(d[22]),"+f"(d[23]),"+f"(d[24]),"+f"(d[25]),"+f"(d[26]),"+f"(d[27]),"+f"(d[28]),"+f"(d[29]),"+f"(d[30]),"+f"(d[31]),"+f"(d[32]),"+f"(d[33]),"+f"(d[34]),"+f"(d[35]),"+f"(d[36]),"+f"(d[37]),"+f"(d[38]),"+f"(d[39]) : "r"(a0), "r"(a1), "r"(a2), "r"(a3), "l"(db));
}
template<> __device__ __forceinline__ void wg_rs<72>(float (&d)[64], uint32_t a0, uint32_t a1, uint32_t a2, uint32_t a3, uint64_t db) {
  asm volatile("{.reg .pred p; setp.ne.b32 p, 1, 0; wgmma.mma_async.sync.aligned.m64n72k16.f32.bf16.bf16 {%0,%1,%2,%3,%4,%5,%6,%7,%8,%9,%10,%11,%12,%13,%14,%15,%16,%17,%18,%19,%20,%21,%22,%23,%24,%25,%26,%27,%28,%29,%30,%31,%32,%33,%34,%35}, {%36,%37,%38,%39}, %40, p, 1, 1, 0;}"
    : "+f"(d[0]),"+f"(d[1]),"+f"(d[2]),"+f"(d[3]),"+f"(d[4]),"+f"(d[5]),"+f"(d[6]),"+f"(d[7]),"+f"(d[8]),"+f"(d[9]),"+f"(d[10]),"+f"(d[11]),"+f"(d[12]),"+f"(d[13]),"+f"(d[14]),"+f"(d[15]),"+f"(d[16]),"+f"(d[17]),"+f"(d[18]),"+f"(d[19]),"+f"(d[20]),"+f"(d[21]),"+f"(d[22]),"+f"(d[23]),"+f"(d[24]),"+f"(d[25]),"+f"(d[26]),"+f"(d[27]),"+f"(d[28]),"+f"(d[29]),"+f"(d[30]),"+f"(d[31]),"+f"(d[32]),"+f"(d[33]),"+f"(d[34]),"+f"(d[35]) : "r"(a0), "r"(a1), "r"(a2), "r"(a3), "l"(db));
}
template<> __device__ __forceinline__ void wg_rs<64>(float (&d)[64], uint32_t a0, uint32_t a1, uint32_t a2, uint32_t a3, uint64_t db) {
  asm volatile("{.reg .pred p; setp.ne.b32 p, 1, 0; wgmma.mma_async.sync.aligned.m64n64k16.f32.bf16.bf16 {%0,%1,%2,%3,%4,%5,%6,%7,%8,%9,%10,%11,%12,%13,%14,%15,%16,%17,%18,%19,%20,%21,%22,%23,%24,%25,%26,%27,%28,%29,%30,%31}, {%32,%33,%34,%35}, %36, p, 1, 1, 0;}"
    : "+f"(d[0]),"+f"(d[1]),"+f"(d[2]),"+f"(d[3]),"+f"(d[4]),"+f"(d[5]),"+f"(d[6]),"+f"(d[7]),"+f"(d[8]),"+f"(d[9]),"+f"(d[10]),"+f"(d[11]),"+f"(d[12]),"+f"(d[13]),"+f"(d[14]),"+f"(d[15]),"+f"(d[16]),"+f"(d[17]),"+f"(d[18]),"+f"(d[19]),"+f"(d[20]),"+f"(d[21]),"+f"(d[22]),"+f"(d[23]),"+f"(d[24]),"+f"(d[25]),"+f"(d[26]),"+f"(d[27]),"+f"(d[28]),"+f"(d[29]),"+f"(d[30]),"+f"(d[31]) : "r"(a0), "r"(a1), "r"(a2), "r"(a3), "l"(db));
}
__device__ __forceinline__ void wg_rs_first(float (&d)[64], uint32_t a0, uint32_t a1, uint32_t a2, uint32_t a3, uint64_t db) {
  asm volatile("{.reg .pred p; setp.ne.b32 p, 0, 0; wgmma.mma_async.sync.aligned.m64n128k16.f32.bf16.bf16 {%0,%1,%2,%3,%4,%5,%6,%7,%8,%9,%10,%11,%12,%13,%14,%15,%16,%17,%18,%19,%20,%21,%22,%23,%24,%25,%26,%27,%28,%29,%30,%31,%32,%33,%34,%35,%36,%37,%38,%39,%40,%41,%42,%43,%44,%45,%46,%47,%48,%49,%50,%51,%52,%53,%54,%55,%56,%57,%58,%59,%60,%61,%62,%63}, {%64,%65,%66,%67}, %68, p, 1, 1, 0;}"
    : "=f"(d[0]),"=f"(d[1]),"=f"(d[2]),"=f"(d[3]),"=f"(d[4]),"=f"(d[5]),"=f"(d[6]),"=f"(d[7]),"=f"(d[8]),"=f"(d[9]),"=f"(d[10]),"=f"(d[11]),"=f"(d[12]),"=f"(d[13]),"=f"(d[14]),"=f"(d[15]),"=f"(d[16]),"=f"(d[17]),"=f"(d[18]),"=f"(d[19]),"=f"(d[20]),"=f"(d[21]),"=f"(d[22]),"=f"(d[23]),"=f"(d[24]),"=f"(d[25]),"=f"(d[26]),"=f"(d[27]),"=f"(d[28]),"=f"(d[29]),"=f"(d[30]),"=f"(d[31]),"=f"(d[32]),"=f"(d[33]),"=f"(d[34]),"=f"(d[35]),"=f"(d[36]),"=f"(d[37]),"=f"(d[38]),"=f"(d[39]),"=f"(d[40]),"=f"(d[41]),"=f"(d[42]),"=f"(d[43]),"=f"(d[44]),"=f"(d[45]),"=f"(d[46]),"=f"(d[47]),"=f"(d[48]),"=f"(d[49]),"=f"(d[50]),"=f"(d[51]),"=f"(d[52]),"=f"(d[53]),"=f"(d[54]),"=f"(d[55]),"=f"(d[56]),"=f"(d[57]),"=f"(d[58]),"=f"(d[59]),"=f"(d[60]),"=f"(d[61]),"=f"(d[62]),"=f"(d[63]) : "r"(a0), "r"(a1), "r"(a2), "r"(a3), "l"(db));
}
__device__ __forceinline__ void wg_tt128(float (&d)[64], uint64_t da, uint64_t db, int sc) {
  asm volatile("{.reg .pred p; setp.ne.b32 p, %66, 0; wgmma.mma_async.sync.aligned.m64n128k16.f32.bf16.bf16 {%0,%1,%2,%3,%4,%5,%6,%7,%8,%9,%10,%11,%12,%13,%14,%15,%16,%17,%18,%19,%20,%21,%22,%23,%24,%25,%26,%27,%28,%29,%30,%31,%32,%33,%34,%35,%36,%37,%38,%39,%40,%41,%42,%43,%44,%45,%46,%47,%48,%49,%50,%51,%52,%53,%54,%55,%56,%57,%58,%59,%60,%61,%62,%63}, %64, %65, p, 1, 1, 1, 1;}"
    : "+f"(d[0]),"+f"(d[1]),"+f"(d[2]),"+f"(d[3]),"+f"(d[4]),"+f"(d[5]),"+f"(d[6]),"+f"(d[7]),"+f"(d[8]),"+f"(d[9]),"+f"(d[10]),"+f"(d[11]),"+f"(d[12]),"+f"(d[13]),"+f"(d[14]),"+f"(d[15]),"+f"(d[16]),"+f"(d[17]),"+f"(d[18]),"+f"(d[19]),"+f"(d[20]),"+f"(d[21]),"+f"(d[22]),"+f"(d[23]),"+f"(d[24]),"+f"(d[25]),"+f"(d[26]),"+f"(d[27]),"+f"(d[28]),"+f"(d[29]),"+f"(d[30]),"+f"(d[31]),"+f"(d[32]),"+f"(d[33]),"+f"(d[34]),"+f"(d[35]),"+f"(d[36]),"+f"(d[37]),"+f"(d[38]),"+f"(d[39]),"+f"(d[40]),"+f"(d[41]),"+f"(d[42]),"+f"(d[43]),"+f"(d[44]),"+f"(d[45]),"+f"(d[46]),"+f"(d[47]),"+f"(d[48]),"+f"(d[49]),"+f"(d[50]),"+f"(d[51]),"+f"(d[52]),"+f"(d[53]),"+f"(d[54]),"+f"(d[55]),"+f"(d[56]),"+f"(d[57]),"+f"(d[58]),"+f"(d[59]),"+f"(d[60]),"+f"(d[61]),"+f"(d[62]),"+f"(d[63]) : "l"(da), "l"(db), "r"(sc));
}
__device__ __forceinline__ void wg_tt64(float (&d)[64], uint64_t da, uint64_t db, int sc) {
  asm volatile("{.reg .pred p; setp.ne.b32 p, %34, 0; wgmma.mma_async.sync.aligned.m64n64k16.f32.bf16.bf16 {%0,%1,%2,%3,%4,%5,%6,%7,%8,%9,%10,%11,%12,%13,%14,%15,%16,%17,%18,%19,%20,%21,%22,%23,%24,%25,%26,%27,%28,%29,%30,%31}, %32, %33, p, 1, 1, 1, 1;}"
    : "+f"(d[0]),"+f"(d[1]),"+f"(d[2]),"+f"(d[3]),"+f"(d[4]),"+f"(d[5]),"+f"(d[6]),"+f"(d[7]),"+f"(d[8]),"+f"(d[9]),"+f"(d[10]),"+f"(d[11]),"+f"(d[12]),"+f"(d[13]),"+f"(d[14]),"+f"(d[15]),"+f"(d[16]),"+f"(d[17]),"+f"(d[18]),"+f"(d[19]),"+f"(d[20]),"+f"(d[21]),"+f"(d[22]),"+f"(d[23]),"+f"(d[24]),"+f"(d[25]),"+f"(d[26]),"+f"(d[27]),"+f"(d[28]),"+f"(d[29]),"+f"(d[30]),"+f"(d[31]) : "l"(da), "l"(db), "r"(sc));
}
__device__ __forceinline__ void wg_tt32(float (&d)[64], uint64_t da, uint64_t db, int sc) {
  asm volatile("{.reg .pred p; setp.ne.b32 p, %18, 0; wgmma.mma_async.sync.aligned.m64n32k16.f32.bf16.bf16 {%0,%1,%2,%3,%4,%5,%6,%7,%8,%9,%10,%11,%12,%13,%14,%15}, %16, %17, p, 1, 1, 1, 1;}"
    : "+f"(d[0]),"+f"(d[1]),"+f"(d[2]),"+f"(d[3]),"+f"(d[4]),"+f"(d[5]),"+f"(d[6]),"+f"(d[7]),"+f"(d[8]),"+f"(d[9]),"+f"(d[10]),"+f"(d[11]),"+f"(d[12]),"+f"(d[13]),"+f"(d[14]),"+f"(d[15]) : "l"(da), "l"(db), "r"(sc));
}
__device__ __forceinline__ void wg_g1(float (&d)[88], uint64_t da, uint64_t db, int sc) {
  asm volatile("{.reg .pred p; setp.ne.b32 p, %90, 0; wgmma.mma_async.sync.aligned.m64n176k16.f32.bf16.bf16 {%0,%1,%2,%3,%4,%5,%6,%7,%8,%9,%10,%11,%12,%13,%14,%15,%16,%17,%18,%19,%20,%21,%22,%23,%24,%25,%26,%27,%28,%29,%30,%31,%32,%33,%34,%35,%36,%37,%38,%39,%40,%41,%42,%43,%44,%45,%46,%47,%48,%49,%50,%51,%52,%53,%54,%55,%56,%57,%58,%59,%60,%61,%62,%63,%64,%65,%66,%67,%68,%69,%70,%71,%72,%73,%74,%75,%76,%77,%78,%79,%80,%81,%82,%83,%84,%85,%86,%87}, %88, %89, p, 1, 1, 1, 0;}"
    : "+f"(d[0]),"+f"(d[1]),"+f"(d[2]),"+f"(d[3]),"+f"(d[4]),"+f"(d[5]),"+f"(d[6]),"+f"(d[7]),"+f"(d[8]),"+f"(d[9]),"+f"(d[10]),"+f"(d[11]),"+f"(d[12]),"+f"(d[13]),"+f"(d[14]),"+f"(d[15]),"+f"(d[16]),"+f"(d[17]),"+f"(d[18]),"+f"(d[19]),"+f"(d[20]),"+f"(d[21]),"+f"(d[22]),"+f"(d[23]),"+f"(d[24]),"+f"(d[25]),"+f"(d[26]),"+f"(d[27]),"+f"(d[28]),"+f"(d[29]),"+f"(d[30]),"+f"(d[31]),"+f"(d[32]),"+f"(d[33]),"+f"(d[34]),"+f"(d[35]),"+f"(d[36]),"+f"(d[37]),"+f"(d[38]),"+f"(d[39]),"+f"(d[40]),"+f"(d[41]),"+f"(d[42]),"+f"(d[43]),"+f"(d[44]),"+f"(d[45]),"+f"(d[46]),"+f"(d[47]),"+f"(d[48]),"+f"(d[49]),"+f"(d[50]),"+f"(d[51]),"+f"(d[52]),"+f"(d[53]),"+f"(d[54]),"+f"(d[55]),"+f"(d[56]),"+f"(d[57]),"+f"(d[58]),"+f"(d[59]),"+f"(d[60]),"+f"(d[61]),"+f"(d[62]),"+f"(d[63]),"+f"(d[64]),"+f"(d[65]),"+f"(d[66]),"+f"(d[67]),"+f"(d[68]),"+f"(d[69]),"+f"(d[70]),"+f"(d[71]),"+f"(d[72]),"+f"(d[73]),"+f"(d[74]),"+f"(d[75]),"+f"(d[76]),"+f"(d[77]),"+f"(d[78]),"+f"(d[79]),"+f"(d[80]),"+f"(d[81]),"+f"(d[82]),"+f"(d[83]),"+f"(d[84]),"+f"(d[85]),"+f"(d[86]),"+f"(d[87]) : "l"(da), "l"(db), "r"(sc));
}

struct Params { const __nv_bfloat16 *x, *logA, *Aim, *Cr, *Ci, *logdt, *Dskip, *Wd; uint4* xnT; float2* st; uint2* S; unsigned* flags; };
struct Maps { CUtensorMap x[2], xo, out, wg, wu, wd, hst[2], hld, xt, sld; };

__device__ __forceinline__ void conv_channel(uint32_t cb, int w, int lane, uint32_t (&res)[8], uint32_t bar_free) {
    const int q = lane & 3, g = lane >> 2, gam = g >> 2;
    float acc[64];
    uint4 a[4][4];
    const uint32_t t0 = cb + CH_T + (uint32_t)(14 + 4 * w + (g & 3) + 32 * gam - 2 * q) * 80u;
    #pragma unroll
    for (int s4 = 0; s4 < 4; s4++) {
        a[s4][0] = lds128(t0 + s4 * 16);
        a[s4][1] = lds128(t0 + 16 * 80 + s4 * 16);
        a[s4][2] = lds128(t0 - 8 * 80 + s4 * 16);
        a[s4][3] = lds128(t0 + 8 * 80 + s4 * 16);
    }
    const uint32_t l0 = FU(ldsf(t0 + 64)), l1 = FU(ldsf(t0 + 16 * 80 + 64)), l2 = FU(ldsf(t0 - 8 * 80 + 64)), l3 = FU(ldsf(t0 + 8 * 80 + 64));
    const uint64_t dU = mkdesc(cb + CH_U, UPLANE, 128, 0);
    WG_FENCE();
#define CT(N, s, c) wg_rs<N>(acc, a[(s) >> 2][0].c, a[(s) >> 2][1].c, a[(s) >> 2][2].c, a[(s) >> 2][3].c, dU + 4 * (s))
    wg_rs_first(acc, a[0][0].x, a[0][1].x, a[0][2].x, a[0][3].x, dU);
    CT(128, 1, y); CT(120, 2, z); CT(120, 3, w);
    CT(112, 4, x); CT(112, 5, y); CT(104, 6, z); CT(104, 7, w);
    CT(96, 8, x);  CT(96, 9, y);  CT(88, 10, z); CT(88, 11, w);
    CT(80, 12, x); CT(80, 13, y); CT(72, 14, z); CT(72, 15, w);
#undef CT
    wg_rs<64>(acc, l0, l1, l2, l3, dU + 64);
    wg_tt64(acc, mkdesc(cb + CH_A3, 128, 512, 0), mkdesc(cb + CH_B3, 128, 256, 0), 1);
    wg_tt32(acc, mkdesc(cb + CH_A3 + 256, 128, 512, 0), mkdesc(cb + CH_B3 + 1024, 128, 256, 0), 1);
    WG_COMMIT();
    WG_WAIT(0);
    fence_acc(acc);
    if (bar_free && lane == 0) mbar_arrive(bar_free);
    const int src1 = (lane & ~3) | ((q + 1) & 3);
    float E[16][2];
    #pragma unroll
    for (int j = 0; j < 16; j++) {
        const float nxt = (j < 15) ? acc[4 * (j + 1) + 2] : 0.f;
        const float sup = (q == 0) ? nxt : acc[4 * j + 2];
        const float v = __shfl_sync(0xffffffffu, sup, src1);
        E[j][0] = acc[4 * j] + acc[4 * j + 3];
        E[j][1] = acc[4 * j + 1] + v;
    }
    const int src2 = gam ? ((lane & 12) | ((q + 3) & 3)) : (16 | (lane & 12) | ((q + 1) & 3));
    const bool c1 = gam && q != 0, c2 = gam && q == 0;
    #pragma unroll
    for (int a2 = 0; a2 < 8; a2++) {
        float y[2];
        #pragma unroll
        for (int e = 0; e < 2; e++) {
            const float sup = c1 ? E[2 * a2][e] : E[2 * a2 + 1][e];
            const float nxt = (a2 < 7) ? E[2 * a2 + 2][e] : 0.f;
            const float keep = c2 ? nxt : (c1 ? E[2 * a2 + 1][e] : E[2 * a2][e]);
            y[e] = keep + __shfl_sync(0xffffffffu, sup, src2);
        }
        res[a2] = pack2(y[1], y[0]);
    }
}

__device__ __forceinline__ void layer_norm(uint32_t sb, int w, int lane, const __nv_bfloat16* x) {
    const uint32_t bars = sb + OFF_BAR;
    const int c = blockIdx.x;
    {
        if (elect_one()) {
            mbar_expect(bars + 8 * B_LNX, 4096);
            #pragma unroll
            for (int i = 0; i < 4; i++)
                bulk_load(sb + OFF_LN + (w + 4 * i) * 1040, x + (16 * (c & ~1) + 8 * (c & 1) + 16 + w + 4 * (i & 1) - 8 * (i & 2)) * DM, 1024, bars + 8 * B_LNX);
        }
        mbar_wait(bars + 8 * B_LNX, 0);
        STAMP(34);
        {
            const int r = w + 4 * (lane >> 3);
            const uint32_t r0 = sb + OFF_LN + r * 1040, ra = r0 + (lane & 7) * 16;
            const float pv = bf_lo(FU(ldsf(r0)));
            float s0 = 0.f, s1 = 0.f, a0 = 0.f, a1 = 0.f;
            uint4 nx = lds128(ra), ny = lds128(ra + 128);
            #pragma unroll 1
            for (int k = 128; k <= 1024; k += 128) {
                const uint32_t v[4] = {nx.x, nx.y, nx.z, nx.w};
                nx = ny; ny = lds128(ra + ((k + 128) & 1023));
                #pragma unroll
                for (int i = 0; i < 4; i++) { const float t0 = bf_lo(v[i]) - pv, t1 = bf_hi(v[i]) - pv; s0 += t0; s1 += t1; a0 = fmaf(t0, t0, a0); a1 = fmaf(t1, t1, a1); }
            }
            s0 += s1; a0 += a1;
            #pragma unroll
            for (int o = 4; o; o >>= 1) { s0 += __shfl_xor_sync(0xffffffffu, s0, o); a0 += __shfl_xor_sync(0xffffffffu, a0, o); }
            s0 *= 1.f / DM;
            const float m = pv + s0, var = fmaxf(fmaf(-s0, s0, a0 * (1.f / DM)), 0.f);
            float sd, ri;
            asm("sqrt.approx.ftz.f32 %0, %1;" : "=f"(sd) : "f"(bf_round(bf_round(var) + 1e-5f)));
            asm("rcp.approx.ftz.f32 %0, %1;" : "=f"(ri) : "f"(bf_round(sd)));
            const uint32_t m2 = pack2(m, m);
            if ((lane & 7) == 0) {
                sts64(sb + OFF_CSUM + r * 8, m2 & 0xffff0000u, FU(0.5f * ri));
            }
            #pragma unroll 1
            for (int k = 128; k <= 1024; k += 128) {
                uint32_t v[4] = {nx.x, nx.y, nx.z, nx.w};
                nx = ny; ny = lds128(ra + ((k + 128) & 1023));
                #pragma unroll
                for (int i = 0; i < 4; i++) {
                    uint32_t dv; asm("sub.rn.bf16x2 %0, %1, %2;" : "=r"(dv) : "r"(v[i]), "r"(m2));
                    v[i] = pack2(bf_lo(dv) * ri, bf_hi(dv) * ri);
                }
                sts128(ra + k - 128, v[0], v[1], v[2], v[3]);
            }
        }
        STAMP(62);
        bar_sync(4);
        {
            const uint32_t ad = sb + OFF_LN + (4 * ((lane & 7) >> 1) + (lane & 1) + 2 * ((lane >> 3) & 1)) * 1040 + (16 * w + (lane >> 4)) * 16;
            uint32_t r[8][4];
            #pragma unroll
            for (int i = 0; i < 8; i++)
                asm volatile("ldmatrix.sync.aligned.m8n8.x4.trans.shared.b16 {%0,%1,%2,%3}, [%4];" : "=r"(r[i][0]), "=r"(r[i][1]), "=r"(r[i][2]), "=r"(r[i][3]) : "r"(ad + 32 * i) : "memory");
            bar_sync(4);
            const uint32_t od = sb + OFF_LN + w * 4096 + lane * 8;
            #pragma unroll
            for (int i = 0; i < 8; i++) { sts64(od + i * 512, r[i][0], r[i][1]); sts64(od + i * 512 + 256, r[i][2], r[i][3]); }
        }
        fence_async_smem();
        mbar_arrive(bars + 8 * B_LN);
        STAMP(16);
    }
}

__device__ __forceinline__ void consumer(uint32_t sb, int warp, const Params& P, const Maps& M) {
    const int V = warp >> 2, w = warp & 3, lane = threadIdx.x & 31, q = lane & 3, g = lane >> 2;
    const int c = blockIdx.x;
    const uint32_t bars = sb + OFF_BAR, xb = sb + OFF_X + V * 2 * XBUF;
    {
        float ag[88], au[88];
        if (V == 0) {
            sts128(xb + (w >> 1) * XBUF + 168 * 128 + (threadIdx.x & 63) * 16, 0x3f803f80u, 0x3f803f80u, 0x3f803f80u, 0x3f803f80u);
            fence_async_smem();
            bar_sync(1);
        } else {
            if (c < 128) layer_norm(sb, w, lane, P.x); else mbar_arrive(bars + 8 * B_LN);
            mbar_wait(bars + 8 * B_GO, 0);
        }
        define_acc(ag); define_acc(au);
        #pragma unroll 1
        for (int st = 0; st < 8; st++) {
            if (st + LAG * V == HOLD0 || st + LAG * V == HOLD1) mbar_wait(bars + 8 * (B_K + (st + LAG * V == HOLD1)), 0);
            mbar_wait(bars + 8 * (B_FULLW + (st & 3)), st >> 2);
            mbar_wait(bars + 8 * (B_FULLX + 2 * V + (st & 1)), (st >> 1) & 1);
            STAMP(40 + 8 * V + st);
            const uint64_t dG = mkdesc(sb + OFF_W + (st & 3) * 16384, 0, 1024, 1);
            const uint64_t dX = mkdesc(xb + (st & 1) * XBUF, 16, 1024, 1);
            WG_FENCE();
            #pragma unroll
            for (int k = 0; k < 4; k++) {
                wg_g1(ag, dG + k * 128, dX + k * 2, k ? 1 : st);
                wg_g1(au, dG + 512 + k * 128, dX + k * 2, k ? 1 : st);
            }
            WG_COMMIT();
            WG_WAIT(1);
            if (lane == 0 && st > 0) {
                mbar_arrive(bars + 8 * (B_EMPTYW + ((st - 1) & 3)));
                mbar_arrive(bars + 8 * (B_EMPTYX + 2 * V + ((st - 1) & 1)));
                if (warp < 4 && st == LAG) mbar_arrive(bars + 8 * B_GO);
            }
        }
        WG_WAIT(0);
        fence_acc(ag); fence_acc(au);
        if (lane == 0) { mbar_arrive(bars + 8 * (B_EMPTYW + 3)); mbar_arrive(bars + 8 * (B_EMPTYX + 2 * V + 1)); }
        STAMP(8 * V + 1);
        float cg0 = ag[84], cg1 = ag[86], cu0 = au[84], cu1 = au[86];
        const uint32_t ca = sb + OFF_CSUM + (8 * w + g) * 16;
        if (V == 0) { sts128(ca, FU(cg0), FU(cg1), FU(cu0), FU(cu1)); mbar_arrive(bars + 8 * B_CS); }
        else { mbar_wait(bars + 8 * B_CS, 0); const uint4 t = lds128(ca); cg0 = UF(t.x); cg1 = UF(t.y); cu0 = UF(t.z); cu1 = UF(t.w); }
        mbar_wait(bars + 8 * B_STATS, 0);
        mbar_wait(bars + 8 * (B_EMPTYX + 2 * V), 1);
        STAMP(13 + V);
        const uint32_t hs = xb + (2 * w + ((lane >> 3) & 1)) * (2688 + 128 * V) + (lane >> 4) * 128 + (lane & 7) * 16;
        const uint32_t sa = sb + OFF_ST + (168 * V + 2 * q) * 8;
        uint4 sq[22];
        #pragma unroll
        for (int j = 0; j < 3; j++) sq[j] = lds128(sa + j * 64);
        #pragma unroll
        for (int j = 0; j < 22; j += 2) {
            uint32_t o[4];
            #pragma unroll
            for (int jj = 0; jj < 2; jj++) {
                const uint4 sv = sq[j + jj];
                float hv[4];
                #pragma unroll
                for (int i = 0; i < 4; i++) {
                    const float m = UF((i & 1) ? sv.z : sv.x);
                    const float gh = fmaf(-m, (i & 2) ? cg1 : cg0, ag[4 * (j + jj) + i]) * UF((i & 1) ? sv.w : sv.y);
                    const float p = gh * fmaf(-m, (i & 2) ? cu1 : cu0, au[4 * (j + jj) + i]);
                    hv[i] = fmaf(p, tanh_fast(gh), p);
                }
                o[2 * jj] = pack2(hv[0], hv[1]); o[2 * jj + 1] = pack2(hv[2], hv[3]);
            }
            #pragma unroll
            for (int k = (j ? 3 + 3 * j / 2 : 3); k < 6 + 3 * j / 2 && k < 22; k++) sq[k] = lds128(sa + k * 64);
            uint32_t ad = hs + j * 128;
            if (j == 20 && V == 0 && lane >= 16) ad = xb + 21504 + (lane & 7) * 16;
            stsm4(ad, o[0], o[1], o[2], o[3]);
        }
        fence_async_smem();
        mbar_arrive(bars + 8 * (B_EPI + V));
        STAMP(8 * V + 2);
    }
    if (c >= 128) return;
    {
        uint32_t r0[8], r1[8];
        #pragma unroll
        for (int i = 0; i < 8; i++) asm volatile("" : "=r"(r1[i]));
        #pragma unroll 1
        for (int e = 0; e < 2; e++) {
            #pragma unroll
            for (int i = 0; i < 8; i++) r0[i] = r1[i];
            mbar_wait(bars + 8 * (B_CONV + 2 * V + e), 0);
            conv_channel(sb + OFF_CONV + (2 * V + e) * CH_STRIDE, w, lane, r1, (V + e == 0) ? bars + 8 * B_CH0 : 0);
            if (e == 0) STAMP(8 * V + 3);
        }
        const int gam = g >> 2, qq = gam ? ((q + 3) & 3) : q;
        const uint32_t sp = sb + OFF_CONV + (2 * V + 1) * CH_STRIDE + ((63 - 4 * gam - qq) * 16 + 4 * w + (g & 3)) * 8;
        bar_sync(3 + V);
        #pragma unroll
        for (int a2 = 0; a2 < 8; a2++) sts64(sp - a2 * 1024, r0[a2], r1[a2]);
        fence_async_smem();
        mbar_arrive(bars + 8 * (B_SIG + V));
        STAMP(8 * V + 4);
    }
    if (V == 1) return;
    {
        const int tau = 2 * (c >> 3) + (c & 1), dg = (c >> 1) & 3;
        const uint32_t row = 8 * (w & 1) + 32 * (w >> 1);
        float acc[64];
        define_acc(acc);
        const float rr0 = __ldcg(&P.st[64 * tau + row + g].y), rr1 = __ldcg(&P.st[64 * tau + row + g + 16].y);
        mbar_wait(bars + 8 * B_FULLD, 0);
        STAMP(5);
        uint64_t dB = mkdesc(sb + wd_slot(0), 8192, 1024, 1), dA = mkdesc(sb + h_slot(0), 1024, 128, 0);
        #pragma unroll 1
        for (int st = 0; st < 21; st++) {
            WG_FENCE();
            wg_tt128(acc, dA, dB, st);
            wg_tt128(acc, dA + 128, dB + 128, 1);
            wg_tt128(acc, dA + 256, dB + 256, 1);
            wg_tt128(acc, dA + 384, dB + 384, 1);
            WG_COMMIT();
            const int sd = (st + 1) & 7;
            const uint32_t nb = bars + 8 * (B_FULLD + sd), np = ((st + 1) >> 3) & 1;
            uint32_t ok;
            asm volatile("{.reg .pred p; mbarrier.test_wait.parity.shared::cta.b64 p, [%1], %2; selp.u32 %0, 1, 0, p;}" : "=r"(ok) : "r"(nb), "r"(np) : "memory");
            dB = mkdesc(sb + wd_slot(sd), 8192, 1024, 1); dA = mkdesc(sb + h_slot(sd), 1024, 128, 0);
            WG_WAIT(1);
            if (lane == 0 && st > 0) {
                if (st < 15) mbar_arrive_pair(bars + 8 * (B_EMPTYD + ((st - 1) & 7))); else if (st == 15) mbar_arrive(bars + 8 * B_CH0);
            }
            if (!ok) mbar_wait(nb, np);
            if (w == 0) STAMP2(20 + st);
        }
        WG_FENCE();
        wg_tt128(acc, dA, dB, 1);
        wg_tt128(acc, dA + 128, dB + 128, 1);
        WG_COMMIT();
        mbar_wait(bars + 8 * B_XO, 0);
        mbar_wait(bars + 8 * B_S, 0);
        const uint32_t xo = sb + OFF_CONV + (row + (lane & 7) + 16 * ((lane >> 3) & 1)) * 128;
        const uint32_t so = sb + wd_slot(6) + (w >> 1) * 8192 + q * 256 + (g & 1) * 8;
        uint32_t xr[8][4];
        uint2 sv[16];
        #pragma unroll
        for (int j = 0; j < 16; j += 2) {
            ldsm4(xr[j >> 1], xo + (j >> 3) * 8192 + ((((j & 7) + (lane >> 4)) ^ (lane & 7)) << 4));
            sv[j] = lds64(so + j * 512 + (((4 * (w & 1) + (g >> 1)) ^ (2 * q)) << 4));
            sv[j + 1] = lds64(so + j * 512 + 128 + (((4 * (w & 1) + (g >> 1)) ^ (2 * q + 1)) << 4));
        }
        WG_WAIT(0);
        fence_acc(acc);
        STAMP(6);
        #pragma unroll
        for (int j = 0; j < 16; j += 2) {
            #pragma unroll
            for (int i = 0; i < 4; i++) {
                const int jj = j + (i >> 1), hh = i & 1;
                const float f0 = acc[4 * jj + 2 * hh] * (hh ? rr1 : rr0), f1 = acc[4 * jj + 2 * hh + 1] * (hh ? rr1 : rr0);
                const uint32_t G = pack2(fmaf(f0, tanh_fast(f0), f0), fmaf(f1, tanh_fast(f1), f1));
                const uint32_t s2 = __byte_perm(sv[jj].x, sv[jj].y, hh ? 0x7632 : 0x5410);
                asm("fma.rn.bf16x2 %0, %1, %2, %0;" : "+r"(xr[j >> 1][i]) : "r"(s2), "r"(G));
            }
            stsm4(xo + (j >> 3) * 8192 + ((((j & 7) + (lane >> 4)) ^ (lane & 7)) << 4), xr[j >> 1][0], xr[j >> 1][1], xr[j >> 1][2], xr[j >> 1][3]);
        }
        fence_async_smem();
        bar_sync(1);
        if (w == 0 && elect_one()) {
            #pragma unroll
            for (int i = 0; i < 2; i++)
                asm volatile("cp.async.bulk.tensor.2d.global.shared::cta.bulk_group [%0, {%2, %3}], [%1];"
                    :: "l"(&M.out), "r"(sb + OFF_CONV + i * 8192), "r"(dg * 128 + 64 * i), "r"(tau * 64) : "memory");
            asm volatile("cp.async.bulk.commit_group; cp.async.bulk.wait_group.read 0;" ::: "memory");
        }
        STAMP(7); GSTAMP(23);
    }
}

__device__ __forceinline__ float2 cexp_p(float re2, float im, float p) {
    float sn, cs;
    const float mag = ex2(re2 * p), th = im * p;
    asm("sin.approx.ftz.f32 %0, %1;" : "=f"(sn) : "f"(th));
    asm("cos.approx.ftz.f32 %0, %1;" : "=f"(cs) : "f"(th));
    return make_float2(mag * cs, mag * sn);
}
__device__ __forceinline__ unsigned short ldu16(const void* p) { unsigned short v; asm volatile("ld.global.nc.u16 %0, [%1];" : "=h"(v) : "l"(p)); return v; }
__device__ __forceinline__ float2 cmul(float2 a, float2 b) { return make_float2(fmaf(a.x, b.x, -a.y * b.y), fmaf(a.x, b.y, a.y * b.x)); }
__device__ __forceinline__ float2 csqr(float2 a) { const float t = a.x * a.y; return make_float2(fmaf(a.x, a.x, -a.y * a.y), t + t); }
__device__ __forceinline__ void mma16816(float (&d)[4], const uint32_t (&a)[4], uint32_t b0, uint32_t b1) {
    asm volatile("mma.sync.aligned.m16n8k16.row.col.f32.bf16.bf16.f32 {%0,%1,%2,%3}, {%4,%5,%6,%7}, {%8,%9}, {%0,%1,%2,%3};"
        : "+f"(d[0]), "+f"(d[1]), "+f"(d[2]), "+f"(d[3]) : "r"(a[0]), "r"(a[1]), "r"(a[2]), "r"(a[3]), "r"(b0), "r"(b1));
}

__device__ __forceinline__ void aux_role(uint32_t sb, int w, const Params& P) {
    const int lane = threadIdx.x & 31, q = lane & 3, g = lane >> 2;
    const int c = blockIdx.x;
    const uint32_t bars = sb + OFF_BAR;
    if (c >= 128) {
        if (lane == 0) { mbar_arrive(bars + 8 * B_K); mbar_arrive(bars + 8 * (B_K + 1)); }
        return;
    }
    {
        const uint32_t cb = sb + OFF_CONV + w * CH_STRIDE;
        const uint32_t sF = cb + CH_A3;
        const int d = 4 * c + w;
        const int po = d * 128 + lane;
        unsigned short la = ldu16(P.logA + po), ai = ldu16(P.Aim + po), cr = ldu16(P.Cr + po), ci = ldu16(P.Ci + po);
        const float ldt = __bfloat162float(P.logdt[d]), dsk = __bfloat162float(P.Dskip[d]);
        float dacc[2][3][4];
        #pragma unroll
        for (int i = 0; i < 24; i++) (&dacc[0][0][0])[i] = 0.f;
        const float dt = bf_round(ex2(ldt * 1.4426950408889634f));
        #pragma unroll 1
        for (int ck = 0; ck < 4; ck++) {
            const uint32_t fa = cb + lane * 4 + (ck & 1) * 8064;
            const float re2 = bf_round(ex2(bf_lo((uint32_t)la) * 1.4426950408889634f)) * dt * -1.4426950408889634f, im = bf_lo((uint32_t)ai) * dt;
            const float2 C = make_float2(bf_lo((uint32_t)cr) * (dt + dt), bf_lo((uint32_t)ci) * -(dt + dt));
            {
                const int pn = po + 32 * min(ck + 1, 3);
                la = ldu16(P.logA + pn); ai = ldu16(P.Aim + pn); cr = ldu16(P.Cr + pn); ci = ldu16(P.Ci + pn);
            }
            const float2 z8 = cexp_p(re2, im, 8.f), y1 = cexp_p(re2, -im, 1.f);
            float2 b0 = make_float2(1.f, 0.f), b1 = cexp_p(re2, im, 64.f), b2 = csqr(b1), b3 = cmul(b2, b1), l0 = C;
            const uint32_t fm = cb + (ck & 1) * 8064 + (lane >> 3) * 144 + (lane & 7) * 16;
#define PK(v) pack2((v).x, (v).y)
            #pragma unroll 1
            for (uint32_t ro = 0; ro < 8 * 144; ro += 144) {
                stsm4(fm + (lane >> 3) * 7 * 144 + ro, PK(b0), PK(b1), PK(b2), PK(b3));
                stsf(fa + 32 * 144 + ro, UF(PK(l0)));
                b0 = cmul(b0, z8); b1 = cmul(b1, z8); b2 = cmul(b2, z8); b3 = cmul(b3, z8); l0 = cmul(l0, y1);
            }
            if (ck < 2) STAMP(56 + 3 * ck);
            const float2 y256 = cexp_p(re2, -im, 256.f), y2 = csqr(y1), y4 = csqr(y2), y8 = make_float2(z8.x, -z8.y);
            const float2 t0 = cmul(C, y256), t1 = cmul(t0, y256), t2 = cmul(t1, y256), t3_ = cmul(t2, y256);
            const float2 u1 = cmul(t0, y2), u2 = cmul(u1, y2), u3 = cmul(u2, y2);
            stsm4(fm + 40 * 144, PK(t0), PK(u1), PK(u2), PK(u3));
            stsm4(fm + 44 * 144, PK(t1), PK(cmul(t1, y4)), PK(t2), PK(cmul(t2, y4)));
            const float2 v0 = cmul(t3_, y8), v1 = cmul(v0, y256), v2 = cmul(v1, y256), v3 = cmul(v2, y256);
            stsm4(fm + 48 * 144, PK(v0), PK(v1), PK(v2), PK(v3));
            stsf(fa + 52 * 144, UF(PK(t3_)));
#undef PK
            if (ck < 2) STAMP(57 + 3 * ck);
            if (ck & 1) {
                uint32_t ln_; asm volatile("mov.u32 %0, %%laneid;" : "=r"(ln_));
                const uint32_t lda = cb + (ln_ & 15) * 144 + (ln_ & 16);
                const uint32_t ldb = cb + (32 + (ln_ & 7)) * 144 + (ln_ >> 3) * 16;
                __syncwarp();
                #pragma unroll
                for (int k2 = 0; k2 < 4; k2++) {
                    const uint32_t ko = (k2 >> 1) * 8064 + (k2 & 1) * 64;
                    uint32_t b[3][4];
                    #pragma unroll
                    for (int t3 = 0; t3 < 3; t3++) ldsm4(b[t3], ldb + t3 * 8 * 144 + ko);
                    #pragma unroll
                    for (int k = 0; k < 2; k++)
                        #pragma unroll
                        for (int mu = 0; mu < 2; mu++) {
                            uint32_t a[4];
                            ldsm4(a, lda + mu * 16 * 144 + ko + k * 32);
                            #pragma unroll
                            for (int t3 = 0; t3 < 3; t3++) mma16816(dacc[mu][t3], a, b[t3][2 * k], b[t3][2 * k + 1]);
                        }
                }
                __syncwarp();
                if (lane == 0) mbar_arrive(bars + 8 * (B_K + (ck >> 1)));
                STAMP(58 + 3 * (ck >> 1));
            }
        }
        STAMP(18);
        const uint32_t sG = cb + CH_G;
        if (lane == 0) dacc[0][0][0] += dsk;
        if (lane < 16) sts128(((lane & 8) ? cb + CH_U + 2048 + (lane & 4) * (UPLANE / 4) : sG + 128 + (lane & 4) * 48) + (lane & 3) * 16, 0, 0, 0, 0);
        {
            const uint32_t f0 = sF + (8 * g + 2 * q) * 4, f1 = sF + ((q < 2) ? 256 + 4 * g + 2 * q : 256 + 2 * g + 64 * q) * 4, st1 = (q < 2) ? 128 : 64;
            const uint32_t ga = sG + ((g & 1) ? 0 : 192) + (63 - (g >> 1) - 32 * q) * 2;
            #pragma unroll
            for (int i = 0; i < 4; i++) {
                const int mu = i >> 1, hh = i & 1;
                sts64(f0 + i * 256, FU(dacc[mu][0][2 * hh]), FU(dacc[mu][0][2 * hh + 1]));
                sts64(f1 + i * st1, FU(dacc[mu][1][2 * hh]), FU(dacc[mu][1][2 * hh + 1]));
                const uint32_t pk = pack2(dacc[mu][2][2 * hh], dacc[mu][2][2 * hh + 1]);
                if (q < 2) { sts16(ga - 8 * i, pk & 0xffff); sts16(ga - 8 * i - 32, pk >> 16); }
            }
            if (lane == 2) stsf(sF + 2048, dacc[0][2][0]);
        }
    }
    bar_sync(2);
    STAMP(19);
    const int rw = lane - 1 + 31 * w, u = min(rw, 77) - 14;
    const uint32_t o0 = CH_A3 + u * 4, o1 = CH_A3 + (128 + ((u + ((u >> 1) & 1)) >> 1)) * 4, o2 = CH_A3 + (256 + ((u + 1 + ((u >> 2) & 1)) >> 2)) * 4;
    const int kap = (lane >> 4) * 8 + ((lane >> 1) & 7), gam = lane & 1, hh = w >> 1, wp = w & 1;
    const uint32_t oa = CH_U + wp * UPLANE + (127 - 4 * kap - 2 * gam - hh) * 16;
    const uint32_t ob = CH_U + (wp ^ 1) * UPLANE + (128 - wp - 4 * kap - 2 * gam - hh) * 16;
    const uint32_t od = CH_A3 + (4 * wp + hh) * 512 + (kap >> 3) * 256 + (kap & 7) * 16 + gam * 8;
    #pragma unroll 1
    for (int k = 0; k < 4; k++) {
        const int ch = 2 * (k & 1) + (k >> 1);
        const uint32_t cb = sb + OFF_CONV + ch * CH_STRIDE;
        if (w < 3) {
            const uint32_t f0 = cb + o0, f1 = cb + o1, f2 = cb + o2;
            float kv[17];
            kv[0] = ldsf(u < 0 ? f1 : f0); if (u < 0) kv[0] = 0.f;
            #pragma unroll
            for (int s = 1; s < 4; s++) kv[s] = ldsf(f0 + s * 256);
            kv[4] = ldsf(u < 0 ? f0 + 1024 : f1 + 512);
            #pragma unroll
            for (int s = 5; s < 8; s++) kv[s] = ldsf(f1 + s * 128);
            kv[8] = ldsf(u < 0 ? f1 + 1024 : f2 + 512);
            #pragma unroll
            for (int s = 9; s < 16; s++) kv[s] = ldsf(f2 + s * 64);
            kv[16] = ldsf(u < 0 ? f2 + 1024 : cb + CH_A3 + 2048); if (u > 4) kv[16] = 0.f;
            uint32_t o[17];
            #pragma unroll
            for (int s = 0; s < 17; s++) o[s] = pack2(kv[s], __shfl_up_sync(0xffffffffu, kv[s], 1));
            if (lane > 0 && rw < 78) {
                const uint32_t ta = cb + CH_T + rw * 80;
                #pragma unroll
                for (int s4 = 0; s4 < 4; s4++) sts128(ta + s4 * 16, o[4 * s4], o[4 * s4 + 1], o[4 * s4 + 2], o[4 * s4 + 3]);
                stsf(ta + 64, UF(o[16]));
            }
        } else {
            const uint32_t ga = cb + CH_G + ((lane >> 3) & 1) * 192 + (lane >> 4) * 16 + (lane & 7) * 8;
            #pragma unroll
            for (int i = 0; i < 4; i++) {
                const uint2 x0 = lds64(ga + 32 * i), x1 = lds64(ga + 32 * i + 8);
                sts128(cb + CH_B3 + lane * 16 + 512 * i, x0.x, x0.y, x1.x, x1.y);
            }
        }
        mbar_wait(bars + 8 * B_U, 0);
        float p[24];
        const uint2 r0 = lds64(cb + ob + 24), r3 = lds64(cb + oa);
        uint32_t r[8];
        *(uint4*)&r[0] = lds128(cb + oa + 16); *(uint4*)&r[4] = lds128(cb + ob);
        p[0] = 0.f;
        p[1] = bf_lo(r0.x); p[2] = p[1] + bf_hi(r0.x); p[3] = p[2] + bf_lo(r0.y); p[4] = p[3] + bf_hi(r0.y);
        #pragma unroll
        for (int i = 0; i < 8; i++) { p[5 + 2 * i] = p[4 + 2 * i] + bf_lo(r[i]); p[6 + 2 * i] = p[5 + 2 * i] + bf_hi(r[i]); }
        p[21] = p[20] + bf_lo(r3.x); p[22] = p[21] + bf_hi(r3.x); p[23] = p[22] + bf_lo(r3.y);
        bar_sync(2);
        #pragma unroll
        for (int i = 0; i < 8; i += 4) {
            sts64(cb + od + i * 256, pack2(p[i + 9] - p[i], p[i + 10] - p[i + 1]), pack2(p[i + 11] - p[i + 2], p[i + 12] - p[i + 3]));
            sts64(cb + od + i * 256 + 128, pack2(p[i + 16] - p[i + 9], p[i + 17] - p[i + 10]), pack2(p[i + 18] - p[i + 11], p[i + 19] - p[i + 12]));
        }
        fence_async_smem();
        mbar_arrive(bars + 8 * (B_CONV + ch));
        if (k == 0) STAMP(17);
    }
    STAMP(21);
}

__global__ void __cluster_dims__(2, 1, 1) __launch_bounds__(512, 1)
fused_kernel(const __grid_constant__ Params P, const __grid_constant__ Maps M) {
    extern __shared__ __align__(1024) uint8_t smem_raw[];
    const uint32_t sb = smem_u32(smem_raw);
    const uint32_t bars = sb + OFF_BAR;
    const int warp = __shfl_sync(0xffffffffu, threadIdx.x >> 5, 0);
    const int c = blockIdx.x, tg = c / 22, fb = c - 22 * tg;
    if (elect_one()) {
        if (warp == 0) { STAMP(24); GSTAMP(22); }
        asm volatile("" :: "l"(((const uint64_t*)&P)[warp < 12 ? warp : 0]));
        if (warp < 12) asm volatile("prefetch.tensormap [%0];" :: "l"(&M.x[0] + warp) : "memory");
        #pragma unroll
        for (int k = 0; k < 4; k++) {
            const int i = 16 * k + ((warp + 4) & 15);
            const uint32_t cnt = ((0xff00000000ff0000ull >> i) & 1) ? 2 : i >= B_CONV ? 128 : ((0xff0000f0ull >> i) & 1) ? 8 : ((0x3e000000f000ull >> i) & 1) ? 4 : 1;
            asm volatile("mbarrier.init.shared::cta.b64 [%0], %1;" :: "r"(bars + 8 * i), "r"(cnt) : "memory");
        }
        asm volatile("fence.mbarrier_init.release.cluster; fence.proxy.async.shared::cta;" ::: "memory");
        if (warp == 12) {
            mbar_expect(bars + 8 * B_FULLW, 16384);
            tma2d(sb + OFF_W, &M.wg, 64 * fb, 0, bars + 8 * B_FULLW);
            tma2d(sb + OFF_W + 8192, &M.wu, 64 * fb, 0, bars + 8 * B_FULLW);
            STAMP(31);
        } else if (warp == 4) {
            mbar_expect(bars + 8 * B_FULLX, 168 * 128);
            tma2d(sb + OFF_X, &M.x[0], 0, TOKG * tg, bars + 8 * B_FULLX);
        }
        if (sb & 1023) __trap();
    }
    __syncthreads();
    asm volatile("barrier.cluster.arrive.relaxed.aligned;" ::: "memory");
    if (warp < 8) {
        asm volatile("setmaxnreg.inc.sync.aligned.u32 208;");
        consumer(sb, warp, P, M);
    } else if (warp < 12) {
        asm volatile("setmaxnreg.dec.sync.aligned.u32 72;");
        STAMP(32);
        aux_role(sb, warp - 8, P);
    } else {
        asm volatile("setmaxnreg.dec.sync.aligned.u32 24;");
        const int tau = 2 * (c >> 3) + (c & 1), dg = (c >> 1) & 3;
        if (elect_one()) {
            if (warp == 12) {
                #pragma unroll 1
                for (int st = 1; st < 8; st++) {
                    const uint32_t s = st & 3, fb_ = bars + 8 * (B_FULLW + s);
                    if (st == 2) mbar_wait(bars + 8 * B_FULLW, 0);
                    mbar_wait(bars + 8 * (B_EMPTYW + s), (st >> 2) ^ 1);
                    mbar_expect(fb_, 16384);
                    tma2d(sb + OFF_W + s * 16384, &M.wg, 64 * fb, 64 * st, fb_);
                    tma2d(sb + OFF_W + s * 16384 + 8192, &M.wu, 64 * fb, 64 * st, fb_);
                }
                if (c < 128) {
                    asm volatile("barrier.cluster.wait;" ::: "memory");
                    #pragma unroll 1
                    for (int st = 0; st < 22; st++) {
                        const int sd = st & 7;
                        if (st < 8) {
                            mbar_wait(bars + 8 * (uint32_t)((0x282823070d060504ull >> (8 * st)) & 0xff), st < 5);
                            mbar_arrive_pair(bars + 8 * (B_RDY + st));
                            mbar_wait(bars + 8 * (B_RDY + st), 0);
                        } else mbar_wait(bars + 8 * (B_EMPTYD + sd), ((st >> 3) & 1) ^ 1);
                        const uint32_t fb_ = bars + 8 * (B_FULLD + sd);
                        mbar_expect(fb_, 16384);
                        asm volatile("cp.async.bulk.tensor.2d.shared::cluster.global.mbarrier::complete_tx::bytes.multicast::cluster [%0], [%1, {%3, %4}], [%2], %5;"
                            :: "r"(sb + wd_slot(sd) + (c & 1) * 8192), "l"(&M.wd), "r"(fb_), "r"(128 * dg + 64 * (c & 1)), "r"(64 * st), "h"((unsigned short)3) : "memory");
                    }
                }
            } else if (warp < 15) {
                const int V = warp - 13;
                #pragma unroll 1
                for (int st = 1 - V; st < 8; st++) {
                    const uint32_t s = 2 * V + (st & 1);
                    if (s == 3 && st == 1) mbar_wait(bars + 8 * B_LNS, 0);
                    mbar_wait(bars + 8 * (B_EMPTYX + s), ((st >> 1) & 1) ^ 1);
                    mbar_expect(bars + 8 * (B_FULLX + s), (168 + 8 * V) * 128);
                    tma2d(sb + OFF_X + s * XBUF, &M.x[V], 64 * st, TOKG * tg + 168 * V, bars + 8 * (B_FULLX + s));
                }
                if (c < 128) {
                    if (V == 0) {
                        mbar_wait(bars + 8 * (B_STG + 1), 0);
                        #pragma unroll 1
                        for (int o = 8 * tau; o < 8 * tau + 8; o += 7) flag_wait(P.flags, F_H + 2 * (o / 43) + ((o % 43) >= 21), 22);
                        mbar_arrive(bars + 8 * B_HF);
                        STAMP(25);
                        #pragma unroll 1
                        for (int st = 0; st < 22; st++) {
                            const uint32_t fb_ = bars + 8 * (B_FULLD + (st & 7));
                            if (st == 6) mbar_wait(bars + 8 * B_SST, 0);
                            mbar_wait(bars + 8 * (B_EMPTYD + (st & 7)), ((st >> 3) & 1) ^ 1);
                            mbar_expect(fb_, 8192);
                            asm volatile("cp.async.bulk.tensor.5d.shared::cluster.global.mbarrier::complete_tx::bytes [%0], [%1, {%3, %3, %3, %4, %5}], [%2];"
                                :: "r"(sb + h_slot(st & 7)), "l"(&M.hld), "r"(fb_), "r"(0), "r"(2 * tau), "r"(8 * st) : "memory");
                        }
                    } else {
                        mbar_wait(bars + 8 * B_CH0, 0);
                        mbar_expect(bars + 8 * B_XO, 16384);
                        tma2d(sb + OFF_CONV, &M.xo, 128 * dg, 64 * tau, bars + 8 * B_XO);
                        tma2d(sb + OFF_CONV + 8192, &M.xo, 128 * dg + 64, 64 * tau, bars + 8 * B_XO);
                        flag_wait(P.flags, F_S + dg, 64);
                        STAMP(26);
                        mbar_wait(bars + 8 * B_CH0, 1);
                        mbar_expect(bars + 8 * B_S, 16384);
                        asm volatile("cp.async.bulk.tensor.5d.shared::cluster.global.mbarrier::complete_tx::bytes [%0], [%1, {%3, %3, %3, %4, %5}], [%2];"
                            :: "r"(sb + wd_slot(6)), "l"(&M.sld), "r"(bars + 8 * B_S), "r"(0), "r"(8 * dg), "r"(2 * tau) : "memory");
                        mbar_wait(bars + 8 * B_HF, 0);
                        exit_count(P.flags);
                    }
                }
            } else {
                mbar_wait(bars + 8 * B_LN, 0);
                STAMP2(0);
                if (c < 128) {
                    #pragma unroll 1
                    for (int i = 0; i < 2; i++)
                        asm volatile("cp.async.bulk.tensor.2d.global.shared::cta.bulk_group [%0, {%2, %3}], [%1];"
                            :: "l"(&M.xt), "r"(sb + OFF_LN + i * 8192), "r"((c & 1) * 1024 + (126 - (c & ~1)) * 8), "r"(256 * i) : "memory");
                    #pragma unroll 1
                    for (int i = 0; i < 2; i++) bulk_store(P.st + 16 * (c & ~1) + 8 * (c & 1) + 16 - 16 * i, sb + OFF_CSUM + 64 * i, 64);
                    asm volatile("cp.async.bulk.prefetch.L2.global [%0], %1;" :: "l"(P.Wd + c * (FF * DM / 128)), "r"(FF * DM / 64) : "memory");
                }
                asm volatile("cp.async.bulk.commit_group; cp.async.bulk.wait_group.read 0;" ::: "memory");
                mbar_arrive(bars + 8 * B_LNS);
                STAMP2(1);
                flag_signal(P.flags, F_A);
                STAMP2(2);
                flag_wait(P.flags, F_A, NCTA);
                STAMP(20);
                mbar_expect(bars + 8 * B_STATS, TOKG * 8);
                bulk_load(sb + OFF_ST, P.st + TOKG * tg, TOKG * 8, bars + 8 * B_STATS);
                if (c < 128) {
                    mbar_wait(bars + 8 * (B_K + 1), 0);
                    fence_async_smem();
                    mbar_expect(bars + 8 * B_U, 8 * 2048);
                    #pragma unroll 1
                    for (int i = 0; i < 8; i++)
                        bulk_load(sb + OFF_CONV + (i >> 1) * CH_STRIDE + CH_U + (i & 1) * UPLANE, P.xnT + 4 * c * 256 + i * 128, 2048, bars + 8 * B_U);
                } else exit_count(P.flags);
                #pragma unroll 1
                for (int V = 0; V < 2; V++) {
                    mbar_wait(bars + 8 * (B_EPI + V), 0);
                    STAMP2(3 + 2 * V);
                    asm volatile("cp.async.bulk.tensor.3d.global.shared::cta.bulk_group [%0, {%2, %3, %4}], [%1];"
                        :: "l"(&M.hst[V]), "r"(sb + OFF_X + V * 2 * XBUF), "r"(0), "r"(43 * tg + 21 * V), "r"(8 * fb) : "memory");
                    flag_signal(P.flags, F_H + 2 * tg + V);
                    mbar_arrive(bars + 8 * (B_STG + V));
                    STAMP2(4 + 2 * V);
                }
                if (c < 128) {
                    #pragma unroll 1
                    for (int V = 0; V < 2; V++) {
                        mbar_wait(bars + 8 * (B_SIG + V), 0);
                        STAMP2(7 + 2 * V);
                        bulk_store(P.S + (2 * c + V) * 1024, sb + OFF_CONV + (2 * V + 1) * CH_STRIDE, 8192);
                        flag_signal(P.flags, F_S + (c >> 5));
                        STAMP2(8 + 2 * V);
                    }
                    mbar_arrive(bars + 8 * B_SST);
                }
            }
        }
    }
    asm volatile("nanosleep.u32 0;");
}

typedef CUresult (*EncodeFn)(CUtensorMap*, CUtensorMapDataType, cuuint32_t, void*, const cuuint64_t*, const cuuint64_t*, const cuuint32_t*,
                             const cuuint32_t*, CUtensorMapInterleave, CUtensorMapSwizzle, CUtensorMapL2promotion, CUtensorMapFloatOOBfill);

void make_map(EncodeFn enc, CUtensorMap* m, const void* ptr, int rank, const cuuint64_t* dims, const cuuint64_t* strides, const cuuint32_t* box, bool swz) {
    const cuuint32_t es[5] = {1, 1, 1, 1, 1};
    enc(m, CU_TENSOR_MAP_DATA_TYPE_BFLOAT16, rank, (void*)ptr, dims, strides, box, es, CU_TENSOR_MAP_INTERLEAVE_NONE,
        swz ? CU_TENSOR_MAP_SWIZZLE_128B : CU_TENSOR_MAP_SWIZZLE_NONE, CU_TENSOR_MAP_L2_PROMOTION_L2_128B, CU_TENSOR_MAP_FLOAT_OOB_FILL_NONE);
}
void make_map2(EncodeFn enc, CUtensorMap* m, const void* ptr, cuuint64_t inner, cuuint64_t outer, cuuint32_t rows) {
    const cuuint64_t dims[2] = {inner, outer}, strides[1] = {inner * 2};
    const cuuint32_t box[2] = {64, rows};
    make_map(enc, m, ptr, 2, dims, strides, box, true);
}

}

extern "C" void kernel_launch(void* const* d_in, const int* in_sizes, int n_in, void* d_out, int out_size) {
    (void)in_sizes; (void)n_in; (void)out_size;
    static EncodeFn enc = nullptr;
    static void *hptr, *p_xnT, *p_st, *p_S, *p_flags;
    if (!enc) {
        cudaDriverEntryPointQueryResult qr;
        cudaGetDriverEntryPoint("cuTensorMapEncodeTiled", (void**)&enc, cudaEnableDefault, &qr);
        cudaFuncSetAttribute(fused_kernel, cudaFuncAttributeMaxDynamicSharedMemorySize, SMEM_BYTES);
        cudaGetSymbolAddress(&hptr, g_H); cudaGetSymbolAddress(&p_xnT, g_xnT); cudaGetSymbolAddress(&p_st, g_st);
        cudaGetSymbolAddress(&p_S, g_S); cudaGetSymbolAddress(&p_flags, g_flags);
    }
    Params P;
    P.x = (const __nv_bfloat16*)d_in[0]; P.logA = (const __nv_bfloat16*)d_in[1]; P.Aim = (const __nv_bfloat16*)d_in[2];
    P.Cr = (const __nv_bfloat16*)d_in[3]; P.Ci = (const __nv_bfloat16*)d_in[4]; P.logdt = (const __nv_bfloat16*)d_in[5];
    P.Dskip = (const __nv_bfloat16*)d_in[6];
    P.Wd = (const __nv_bfloat16*)d_in[10]; P.xnT = (uint4*)p_xnT; P.st = (float2*)p_st; P.S = (uint2*)p_S; P.flags = (unsigned*)p_flags;
    Maps M;
    make_map2(enc, &M.x[0], d_in[0], DM, SEQ, 168); make_map2(enc, &M.x[1], d_in[0], DM, SEQ, 176);
    make_map2(enc, &M.xo, d_in[0], DM, SEQ, 64);    make_map2(enc, &M.out, d_out, DM, SEQ, 64);
    make_map2(enc, &M.wg, d_in[8], FF, DM, 64);     make_map2(enc, &M.wu, d_in[9], FF, DM, 64);
    make_map2(enc, &M.wd, d_in[10], DM, FF, 64);
    for (int v = 0; v < 2; v++) {
        const cuuint64_t dims[3] = {64, 256, 172}, strides[2] = {128, 32768};
        const cuuint32_t box[3] = {64, (cuuint32_t)(21 + v), 8};
        make_map(enc, &M.hst[v], hptr, 3, dims, strides, box, false);
    }
    {
        const cuuint64_t dims[2] = {2048, 512}, strides[1] = {4096};
        const cuuint32_t box[2] = {16, 256};
        make_map(enc, &M.xt, p_xnT, 2, dims, strides, box, false);
    }
    {
        const cuuint64_t dims[5] = {64, 2, 4, 32, 64}, strides[4] = {4 * 8192, 8192, 8 * 8192, 128};
        const cuuint32_t box[5] = {64, 2, 4, 8, 2};
        make_map(enc, &M.sld, p_S, 5, dims, strides, box, true);
    }
    {
        const cuuint64_t dims[5] = {64, 2, 2, 64, 172}, strides[4] = {256, 128, 512, 32768};
        const cuuint32_t box[5] = {64, 2, 2, 2, 8};
        make_map(enc, &M.hld, hptr, 5, dims, strides, box, false);
    }
    fused_kernel<<<NCTA, 512, SMEM_BYTES>>>(P, M);
}
```

```cpp
#include <cuda_runtime.h>
#include <cuda_bf16.h>
#include <cuda.h>
#include <stdint.h>

#define PROF 0

namespace {

constexpr int SEQ = 2048, DM = 512, FF = 1376;
constexpr int NCTA = 132;
#define HOLD0 4
#define HOLD1 7
#define LAG 2
constexpr int TOKG = 344;

constexpr uint32_t OFF_W = 0;
constexpr uint32_t XBUF = 22528;
constexpr uint32_t OFF_X = 65536;
constexpr uint32_t OFF_CONV = 155648;
constexpr uint32_t CH_STRIDE = 16640;
constexpr uint32_t CH_T = 0;
constexpr uint32_t CH_A3 = 6272;
constexpr uint32_t CH_B3 = 10368;
constexpr uint32_t CH_U = 12416;
constexpr uint32_t CH_G = CH_A3 + 2064;
constexpr uint32_t UPLANE = 2112;
constexpr uint32_t OFF_LN = OFF_X + 3 * XBUF;
constexpr uint32_t OFF_ST = 222208;
constexpr uint32_t OFF_CSUM = 230400;
constexpr uint32_t OFF_BAR = 231168;
constexpr uint32_t SMEM_BYTES = 231680;

enum {
    B_FULLW = 0, B_EMPTYW = 4, B_FULLX = 8, B_EMPTYX = 12, B_FULLD = 16, B_EMPTYD = 24,
    B_U = 32, B_XO = 33, B_S = 34, B_STG = 35, B_HF = 37, B_STATS = 38, B_LNS = 39, B_SST = 40,
    B_LNX = 41, B_GO = 42, B_CH0 = 43, B_K = 44,
    B_CONV = 46, B_LN = 50, B_CS = 51, B_EPI = 52, B_SIG = 54,
    B_RDY = 56,
    B_COUNT = 64
};
enum { F_A = 0, F_H = 1, F_S = 13, F_EXIT = 17, F_COUNT = 18 };

__device__ uint4 g_xnT[DM * 256];
__device__ float2 g_st[6 * TOKG];
__device__ uint4 g_H[172 * 256 * 8];
__device__ uint2 g_S[256 * 1024];
__device__ unsigned g_flags[F_COUNT * 32];
#define STAMP(i) do {} while (0)
#define GSTAMP(i) do {} while (0)
#define STAMP2(i) do {} while (0)

__device__ __forceinline__ uint32_t smem_u32(const void* p) { return (uint32_t)__cvta_generic_to_shared(p); }
__device__ __forceinline__ void mbar_expect(uint32_t bar, uint32_t bytes) { asm volatile("mbarrier.arrive.expect_tx.shared::cta.b64 _, [%0], %1;" :: "r"(bar), "r"(bytes) : "memory"); }
__device__ __forceinline__ void mbar_arrive(uint32_t bar) { asm volatile("mbarrier.arrive.shared::cta.b64 _, [%0];" :: "r"(bar) : "memory"); }
__device__ __forceinline__ void mbar_wait(uint32_t bar, uint32_t parity) {
    asm volatile("{.reg .pred p; .reg .u32 n; mov.u32 n, 0x20000;\n"
                 "LW: mbarrier.try_wait.parity.shared::cta.b64 p, [%0], %1;\n"
                 "sub.u32 n, n, 1; setp.eq.or.u32 p, n, 0, p; @!p bra LW;}" :: "r"(bar), "r"(parity) : "memory");
}
__device__ __forceinline__ void mbar_arrive_pair(uint32_t bar) {
    asm volatile("{.reg .b32 r, p; mov.u32 p, %%cluster_ctarank; xor.b32 p, p, 1; mapa.shared::cluster.u32 r, %0, p;\n"
                 "mbarrier.arrive.shared::cta.b64 _, [%0]; mbarrier.arrive.shared::cluster.b64 _, [r];}" :: "r"(bar) : "memory");
}
__device__ __forceinline__ bool elect_one() { uint32_t p; asm volatile("{.reg .pred P; elect.sync _|P, 0xffffffff; selp.u32 %0, 1, 0, P;}" : "=r"(p)); return p; }
__device__ __forceinline__ void tma2d(uint32_t dst, const CUtensorMap* m, int c0, int c1, uint32_t bar) {
    asm volatile("cp.async.bulk.tensor.2d.shared::cluster.global.mbarrier::complete_tx::bytes [%0], [%1, {%3, %4}], [%2];"
        :: "r"(dst), "l"(m), "r"(bar), "r"(c0), "r"(c1) : "memory");
}
__device__ __forceinline__ void bulk_load(uint32_t dst, const void* src, uint32_t bytes, uint32_t bar) {
    asm volatile("cp.async.bulk.shared::cluster.global.mbarrier::complete_tx::bytes [%0], [%1], %2, [%3];" :: "r"(dst), "l"(src), "r"(bytes), "r"(bar) : "memory");
}
__device__ __forceinline__ void bulk_store(void* dst, uint32_t src, uint32_t bytes) {
    asm volatile("cp.async.bulk.global.shared::cta.bulk_group [%0], [%1], %2;" :: "l"(dst), "r"(src), "r"(bytes) : "memory");
}
__device__ __forceinline__ void fence_async_smem() { asm volatile("fence.proxy.async.shared::cta;" ::: "memory"); }
__device__ __forceinline__ void flag_wait(unsigned* g_flags, int f, unsigned target) {
    asm volatile("{.reg .pred p; .reg .u32 n, v; mov.u32 n, 0x40000;\n"
                 "LF: ld.acquire.gpu.global.u32 v, [%0]; setp.ge.u32 p, v, %1; @p bra LD;\n"
                 "sub.u32 n, n, 1; setp.ne.u32 p, n, 0; @p bra LF; trap;\nLD: }"
                 :: "l"(g_flags + f * 32), "r"(target) : "memory");
}
__device__ __forceinline__ void flag_signal(unsigned* g_flags, int f) {
    asm volatile("cp.async.bulk.commit_group; cp.async.bulk.wait_group 0; red.relaxed.gpu.global.add.u32 [%0], 1;" :: "l"(g_flags + f * 32) : "memory");
}
__device__ __forceinline__ void exit_count(unsigned* g_flags) {
    if (atomicAdd(g_flags + F_EXIT * 32, 1u) == NCTA - 1) {
        #pragma unroll 1
        for (int i = 0; i < F_COUNT; i++) g_flags[i * 32] = 0;
    }
}
__device__ __forceinline__ void bar_sync(int id) { asm volatile("bar.sync %0, 128;" :: "r"(id) : "memory"); }
__device__ __forceinline__ uint64_t mkdesc(uint32_t addr, uint32_t lbo, uint32_t sbo, uint32_t swz) {
    return (uint64_t)(((addr & 0x3FFFF) >> 4) | ((lbo >> 4) << 16)) | ((uint64_t)((sbo >> 4) | (swz << 30)) << 32);
}
#define WG_FENCE() asm volatile("wgmma.fence.sync.aligned;" ::: "memory")
#define WG_COMMIT() asm volatile("wgmma.commit_group.sync.aligned;" ::: "memory")
#define WG_WAIT(n) asm volatile("wgmma.wait_group.sync.aligned " #n ";" ::: "memory")
template <int N> __device__ __forceinline__ void fence_acc(float (&d)[N]) {
    #pragma unroll
    for (int i = 0; i < N; i++) asm volatile("" : "+f"(d[i]) :: "memory");
}
template <int N> __device__ __forceinline__ void define_acc(float (&d)[N]) {
    #pragma unroll
    for (int i = 0; i < N; i++) asm volatile("" : "=f"(d[i]));
}
__device__ __forceinline__ uint32_t pack2(float lo, float hi) { uint32_t r; asm("cvt.rn.bf16x2.f32 %0, %1, %2;" : "=r"(r) : "f"(hi), "f"(lo)); return r; }
__device__ __forceinline__ float bf_lo(uint32_t v) { return __uint_as_float(v << 16); }
__device__ __forceinline__ float bf_hi(uint32_t v) { return __uint_as_float(v & 0xffff0000u); }
__device__ __forceinline__ float bf_round(float v) { return bf_hi(pack2(0.f, v)); }
__device__ __forceinline__ float tanh_fast(float v) { float r; asm("tanh.approx.f32 %0, %1;" : "=f"(r) : "f"(v)); return r; }
__device__ __forceinline__ float ex2(float v) { float r; asm("ex2.approx.ftz.f32 %0, %1;" : "=f"(r) : "f"(v)); return r; }
__device__ __forceinline__ uint4 lds128(uint32_t a) { uint4 v; asm volatile("ld.shared.v4.b32 {%0,%1,%2,%3}, [%4];" : "=r"(v.x), "=r"(v.y), "=r"(v.z), "=r"(v.w) : "r"(a)); return v; }
__device__ __forceinline__ uint2 lds64(uint32_t a) { uint2 v; asm volatile("ld.shared.v2.b32 {%0,%1}, [%2];" : "=r"(v.x), "=r"(v.y) : "r"(a)); return v; }
__device__ __forceinline__ float ldsf(uint32_t a) { float v; asm volatile("ld.shared.f32 %0, [%1];" : "=f"(v) : "r"(a)); return v; }
__device__ __forceinline__ void sts128(uint32_t a, uint32_t x, uint32_t y, uint32_t z, uint32_t w) { asm volatile("st.shared.v4.b32 [%0], {%1,%2,%3,%4};" :: "r"(a), "r"(x), "r"(y), "r"(z), "r"(w) : "memory"); }
__device__ __forceinline__ void sts64(uint32_t a, uint32_t x, uint32_t y) { asm volatile("st.shared.v2.b32 [%0], {%1,%2};" :: "r"(a), "r"(x), "r"(y) : "memory"); }
__device__ __forceinline__ void stsf(uint32_t a, float x) { asm volatile("st.shared.f32 [%0], %1;" :: "r"(a), "f"(x) : "memory"); }
__device__ __forceinline__ void sts16(uint32_t a, uint32_t x) { asm volatile("st.shared.b16 [%0], %1;" :: "r"(a), "h"((unsigned short)x) : "memory"); }
__device__ __forceinline__ void stsm4(uint32_t a, uint32_t r0, uint32_t r1, uint32_t r2, uint32_t r3) {
    asm volatile("stmatrix.sync.aligned.m8n8.x4.shared.b16 [%0], {%1,%2,%3,%4};" :: "r"(a), "r"(r0), "r"(r1), "r"(r2), "r"(r3) : "memory");
}
__device__ __forceinline__ void ldsm4(uint32_t (&r)[4], uint32_t a) {
    asm volatile("ldmatrix.sync.aligned.m8n8.x4.shared.b16 {%0,%1,%2,%3}, [%4];" : "=r"(r[0]), "=r"(r[1]), "=r"(r[2]), "=r"(r[3]) : "r"(a) : "memory");
}
#define FU(x) __float_as_uint(x)
#define UF(x) __uint_as_float(x)
__device__ __forceinline__ uint32_t wd_slot(int s) { return (uint32_t)((0xb9a8403056201000ull >> (8 * s)) & 0xff) << 10; }
__device__ __forceinline__ uint32_t h_slot(int s) { return (uint32_t)((0xc9a0d98c847c746cull >> (8 * s)) & 0xff) << 10; }

template<int N> __device__ __forceinline__ void wg_rs(float (&d)[64], uint32_t a0, uint32_t a1, uint32_t a2, uint32_t a3, uint64_t db);
template<> __device__ __forceinline__ void wg_rs<128>(float (&d)[64], uint32_t a0, uint32_t a1, uint32_t a2, uint32_t a3, uint64_t db) {
  asm volatile("{.reg .pred p; setp.ne.b32 p, 1, 0; wgmma.mma_async.sync.aligned.m64n128k16.f32.bf16.bf16 {%0,%1,%2,%3,%4,%5,%6,%7,%8,%9,%10,%11,%12,%13,%14,%15,%16,%17,%18,%19,%20,%21,%22,%23,%24,%25,%26,%27,%28,%29,%30,%31,%32,%33,%34,%35,%36,%37,%38,%39,%40,%41,%42,%43,%44,%45,%46,%47,%48,%49,%50,%51,%52,%53,%54,%55,%56,%57,%58,%59,%60,%61,%62,%63}, {%64,%65,%66,%67}, %68, p, 1, 1, 0;}"
    : "+f"(d[0]),"+f"(d[1]),"+f"(d[2]),"+f"(d[3]),"+f"(d[4]),"+f"(d[5]),"+f"(d[6]),"+f"(d[7]),"+f"(d[8]),"+f"(d[9]),"+f"(d[10]),"+f"(d[11]),"+f"(d[12]),"+f"(d[13]),"+f"(d[14]),"+f"(d[15]),"+f"(d[16]),"+f"(d[17]),"+f"(d[18]),"+f"(d[19]),"+f"(d[20]),"+f"(d[21]),"+f"(d[22]),"+f"(d[23]),"+f"(d[24]),"+f"(d[25]),"+f"(d[26]),"+f"(d[27]),"+f"(d[28]),"+f"(d[29]),"+f"(d[30]),"+f"(d[31]),"+f"(d[32]),"+f"(d[33]),"+f"(d[34]),"+f"(d[35]),"+f"(d[36]),"+f"(d[37]),"+f"(d[38]),"+f"(d[39]),"+f"(d[40]),"+f"(d[41]),"+f"(d[42]),"+f"(d[43]),"+f"(d[44]),"+f"(d[45]),"+f"(d[46]),"+f"(d[47]),"+f"(d[48]),"+f"(d[49]),"+f"(d[50]),"+f"(d[51]),"+f"(d[52]),"+f"(d[53]),"+f"(d[54]),"+f"(d[55]),"+f"(d[56]),"+f"(d[57]),"+f"(d[58]),"+f"(d[59]),"+f"(d[60]),"+f"(d[61]),"+f"(d[62]),"+f"(d[63]) : "r"(a0), "r"(a1), "r"(a2), "r"(a3), "l"(db));
}
template<> __device__ __forceinline__ void wg_rs<120>(float (&d)[64], uint32_t a0, uint32_t a1, uint32_t a2, uint32_t a3, uint64_t db) {
  asm volatile("{.reg .pred p; setp.ne.b32 p, 1, 0; wgmma.mma_async.sync.aligned.m64n120k16.f32.bf16.bf16 {%0,%1,%2,%3,%4,%5,%6,%7,%8,%9,%10,%11,%12,%13,%14,%15,%16,%17,%18,%19,%20,%21,%22,%23,%24,%25,%26,%27,%28,%29,%30,%31,%32,%33,%34,%35,%36,%37,%38,%39,%40,%41,%42,%43,%44,%45,%46,%47,%48,%49,%50,%51,%52,%53,%54,%55,%56,%57,%58,%59}, {%60,%61,%62,%63}, %64, p, 1, 1, 0;}"
    : "+f"(d[0]),"+f"(d[1]),"+f"(d[2]),"+f"(d[3]),"+f"(d[4]),"+f"(d[5]),"+f"(d[6]),"+f"(d[7]),"+f"(d[8]),"+f"(d[9]),"+f"(d[10]),"+f"(d[11]),"+f"(d[12]),"+f"(d[13]),"+f"(d[14]),"+f"(d[15]),"+f"(d[16]),"+f"(d[17]),"+f"(d[18]),"+f"(d[19]),"+f"(d[20]),"+f"(d[21]),"+f"(d[22]),"+f"(d[23]),"+f"(d[24]),"+f"(d[25]),"+f"(d[26]),"+f"(d[27]),"+f"(d[28]),"+f"(d[29]),"+f"(d[30]),"+f"(d[31]),"+f"(d[32]),"+f"(d[33]),"+f"(d[34]),"+f"(d[35]),"+f"(d[36]),"+f"(d[37]),"+f"(d[38]),"+f"(d[39]),"+f"(d[40]),"+f"(d[41]),"+f"(d[42]),"+f"(d[43]),"+f"(d[44]),"+f"(d[45]),"+f"(d[46]),"+f"(d[47]),"+f"(d[48]),"+f"(d[49]),"+f"(d[50]),"+f"(d[51]),"+f"(d[52]),"+f"(d[53]),"+f"(d[54]),"+f"(d[55]),"+f"(d[56]),"+f"(d[57]),"+f"(d[58]),"+f"(d[59]) : "r"(a0), "r"(a1), "r"(a2), "r"(a3), "l"(db));
}
template<> __device__ __forceinline__ void wg_rs<112>(float (&d)[64], uint32_t a0, uint32_t a1, uint32_t a2, uint32_t a3, uint64_t db) {
  asm volatile("{.reg .pred p; setp.ne.b32 p, 1, 0; wgmma.mma_async.sync.aligned.m64n112k16.f32.bf16.bf16 {%0,%1,%2,%3,%4,%5,%6,%7,%8,%9,%10,%11,%12,%13,%14,%15,%16,%17,%18,%19,%20,%21,%22,%23,%24,%25,%26,%27,%28,%29,%30,%31,%32,%33,%34,%35,%36,%37,%38,%39,%40,%41,%42,%43,%44,%45,%46,%47,%48,%49,%50,%51,%52,%53,%54,%55}, {%56,%57,%58,%59}, %60, p, 1, 1, 0;}"
    : "+f"(d[0]),"+f"(d[1]),"+f"(d[2]),"+f"(d[3]),"+f"(d[4]),"+f"(d[5]),"+f"(d[6]),"+f"(d[7]),"+f"(d[8]),"+f"(d[9]),"+f"(d[10]),"+f"(d[11]),"+f"(d[12]),"+f"(d[13]),"+f"(d[14]),"+f"(d[15]),"+f"(d[16]),"+f"(d[17]),"+f"(d[18]),"+f"(d[19]),"+f"(d[20]),"+f"(d[21]),"+f"(d[22]),"+f"(d[23]),"+f"(d[24]),"+f"(d[25]),"+f"(d[26]),"+f"(d[27]),"+f"(d[28]),"+f"(d[29]),"+f"(d[30]),"+f"(d[31]),"+f"(d[32]),"+f"(d[33]),"+f"(d[34]),"+f"(d[35]),"+f"(d[36]),"+f"(d[37]),"+f"(d[38]),"+f"(d[39]),"+f"(d[40]),"+f"(d[41]),"+f"(d[42]),"+f"(d[43]),"+f"(d[44]),"+f"(d[45]),"+f"(d[46]),"+f"(d[47]),"+f"(d[48]),"+f"(d[49]),"+f"(d[50]),"+f"(d[51]),"+f"(d[52]),"+f"(d[53]),"+f"(d[54]),"+f"(d[55]) : "r"(a0), "r"(a1), "r"(a2), "r"(a3), "l"(db));
}
template<> __device__ __forceinline__ void wg_rs<104>(float (&d)[64], uint32_t a0, uint32_t a1, uint32_t a2, uint32_t a3, uint64_t db) {
  asm volatile("{.reg .pred p; setp.ne.b32 p, 1, 0; wgmma.mma_async.sync.aligned.m64n104k16.f32.bf16.bf16 {%0,%1,%2,%3,%4,%5,%6,%7,%8,%9,%10,%11,%12,%13,%14,%15,%16,%17,%18,%19,%20,%21,%22,%23,%24,%25,%26,%27,%28,%29,%30,%31,%32,%33,%34,%35,%36,%37,%38,%39,%40,%41,%42,%43,%44,%45,%46,%47,%48,%49,%50,%51}, {%52,%53,%54,%55}, %56, p, 1, 1, 0;}"
    : "+f"(d[0]),"+f"(d[1]),"+f"(d[2]),"+f"(d[3]),"+f"(d[4]),"+f"(d[5]),"+f"(d[6]),"+f"(d[7]),"+f"(d[8]),"+f"(d[9]),"+f"(d[10]),"+f"(d[11]),"+f"(d[12]),"+f"(d[13]),"+f"(d[14]),"+f"(d[15]),"+f"(d[16]),"+f"(d[17]),"+f"(d[18]),"+f"(d[19]),"+f"(d[20]),"+f"(d[21]),"+f"(d[22]),"+f"(d[23]),"+f"(d[24]),"+f"(d[25]),"+f"(d[26]),"+f"(d[27]),"+f"(d[28]),"+f"(d[29]),"+f"(d[30]),"+f"(d[31]),"+f"(d[32]),"+f"(d[33]),"+f"(d[34]),"+f"(d[35]),"+f"(d[36]),"+f"(d[37]),"+f"(d[38]),"+f"(d[39]),"+f"(d[40]),"+f"(d[41]),"+f"(d[42]),"+f"(d[43]),"+f"(d[44]),"+f"(d[45]),"+f"(d[46]),"+f"(d[47]),"+f"(d[48]),"+f"(d[49]),"+f"(d[50]),"+f"(d[51]) : "r"(a0), "r"(a1), "r"(a2), "r"(a3), "l"(db));
}
template<> __device__ __forceinline__ void wg_rs<96>(float (&d)[64], uint32_t a0, uint32_t a1, uint32_t a2, uint32_t a3, uint64_t db) {
  asm volatile("{.reg .pred p; setp.ne.b32 p, 1, 0; wgmma.mma_async.sync.aligned.m64n96k16.f32.bf16.bf16 {%0,%1,%2,%3,%4,%5,%6,%7,%8,%9,%10,%11,%12,%13,%14,%15,%16,%17,%18,%19,%20,%21,%22,%23,%24,%25,%26,%27,%28,%29,%30,%31,%32,%33,%34,%35,%36,%37,%38,%39,%40,%41,%42,%43,%44,%45,%46,%47}, {%48,%49,%50,%51}, %52, p, 1, 1, 0;}"
    : "+f"(d[0]),"+f"(d[1]),"+f"(d[2]),"+f"(d[3]),"+f"(d[4]),"+f"(d[5]),"+f"(d[6]),"+f"(d[7]),"+f"(d[8]),"+f"(d[9]),"+f"(d[10]),"+f"(d[11]),"+f"(d[12]),"+f"(d[13]),"+f"(d[14]),"+f"(d[15]),"+f"(d[16]),"+f"(d[17]),"+f"(d[18]),"+f"(d[19]),"+f"(d[20]),"+f"(d[21]),"+f"(d[22]),"+f"(d[23]),"+f"(d[24]),"+f"(d[25]),"+f"(d[26]),"+f"(d[27]),"+f"(d[28]),"+f"(d[29]),"+f"(d[30]),"+f"(d[31]),"+f"(d[32]),"+f"(d[33]),"+f"(d[34]),"+f"(d[35]),"+f"(d[36]),"+f"(d[37]),"+f"(d[38]),"+f"(d[39]),"+f"(d[40]),"+f"(d[41]),"+f"(d[42]),"+f"(d[43]),"+f"(d[44]),"+f"(d[45]),"+f"(d[46]),"+f"(d[47]) : "r"(a0), "r"(a1), "r"(a2), "r"(a3), "l"(db));
}
template<> __device__ __forceinline__ void wg_rs<88>(float (&d)[64], uint32_t a0, uint32_t a1, uint32_t a2, uint32_t a3, uint64_t db) {
  asm volatile("{.reg .pred p; setp.ne.b32 p, 1, 0; wgmma.mma_async.sync.aligned.m64n88k16.f32.bf16.bf16 {%0,%1,%2,%3,%4,%5,%6,%7,%8,%9,%10,%11,%12,%13,%14,%15,%16,%17,%18,%19,%20,%21,%22,%23,%24,%25,%26,%27,%28,%29,%30,%31,%32,%33,%34,%35,%36,%37,%38,%39,%40,%41,%42,%43}, {%44,%45,%46,%47}, %48, p, 1, 1, 0;}"
    : "+f"(d[0]),"+f"(d[1]),"+f"(d[2]),"+f"(d[3]),"+f"(d[4]),"+f"(d[5]),"+f"(d[6]),"+f"(d[7]),"+f"(d[8]),"+f"(d[9]),"+f"(d[10]),"+f"(d[11]),"+f"(d[12]),"+f"(d[13]),"+f"(d[14]),"+f"(d[15]),"+f"(d[16]),"+f"(d[17]),"+f"(d[18]),"+f"(d[19]),"+f"(d[20]),"+f"(d[21]),"+f"(d[22]),"+f"(d[23]),"+f"(d[24]),"+f"(d[25]),"+f"(d[26]),"+f"(d[27]),"+f"(d[28]),"+f"(d[29]),"+f"(d[30]),"+f"(d[31]),"+f"(d[32]),"+f"(d[33]),"+f"(d[34]),"+f"(d[35]),"+f"(d[36]),"+f"(d[37]),"+f"(d[38]),"+f"(d[39]),"+f"(d[40]),"+f"(d[41]),"+f"(d[42]),"+f"(d[43]) : "r"(a0), "r"(a1), "r"(a2), "r"(a3), "l"(db));
}
template<> __device__ __forceinline__ void wg_rs<80>(float (&d)[64], uint32_t a0, uint32_t a1, uint32_t a2, uint32_t a3, uint64_t db) {
  asm volatile("{.reg .pred p; setp.ne.b32 p, 1, 0; wgmma.mma_async.sync.aligned.m64n80k16.f32.bf16.bf16 {%0,%1,%2,%3,%4,%5,%6,%7,%8,%9,%10,%11,%12,%13,%14,%15,%16,%17,%18,%19,%20,%21,%22,%23,%24,%25,%26,%27,%28,%29,%30,%31,%32,%33,%34,%35,%36,%37,%38,%39}, {%40,%41,%42,%43}, %44, p, 1, 1, 0;}"
    : "+f"(d[0]),"+f"(d[1]),"+f"(d[2]),"+f"(d[3]),"+f"(d[4]),"+f"(d[5]),"+f"(d[6]),"+f"(d[7]),"+f"(d[8]),"+f"(d[9]),"+f"(d[10]),"+f"(d[11]),"+f"(d[12]),"+f"(d[13]),"+f"(d[14]),"+f"(d[15]),"+f"(d[16]),"+f"(d[17]),"+f"(d[18]),"+f"(d[19]),"+f"(d[20]),"+f"(d[21]),"+f"(d[22]),"+f"(d[23]),"+f"(d[24]),"+f"(d[25]),"+f"(d[26]),"+f"(d[27]),"+f"(d[28]),"+f"(d[29]),"+f"(d[30]),"+f"(d[31]),"+f"(d[32]),"+f"(d[33]),"+f"(d[34]),"+f"(d[35]),"+f"(d[36]),"+f"(d[37]),"+f"(d[38]),"+f"(d[39]) : "r"(a0), "r"(a1), "r"(a2), "r"(a3), "l"(db));
}
template<> __device__ __forceinline__ void wg_rs<72>(float (&d)[64], uint32_t a0, uint32_t a1, uint32_t a2, uint32_t a3, uint64_t db) {
  asm volatile("{.reg .pred p; setp.ne.b32 p, 1, 0; wgmma.mma_async.sync.aligned.m64n72k16.f32.bf16.bf16 {%0,%1,%2,%3,%4,%5,%6,%7,%8,%9,%10,%11,%12,%13,%14,%15,%16,%17,%18,%19,%20,%21,%22,%23,%24,%25,%26,%27,%28,%29,%30,%31,%32,%33,%34,%35}, {%36,%37,%38,%39}, %40, p, 1, 1, 0;}"
    : "+f"(d[0]),"+f"(d[1]),"+f"(d[2]),"+f"(d[3]),"+f"(d[4]),"+f"(d[5]),"+f"(d[6]),"+f"(d[7]),"+f"(d[8]),"+f"(d[9]),"+f"(d[10]),"+f"(d[11]),"+f"(d[12]),"+f"(d[13]),"+f"(d[14]),"+f"(d[15]),"+f"(d[16]),"+f"(d[17]),"+f"(d[18]),"+f"(d[19]),"+f"(d[20]),"+f"(d[21]),"+f"(d[22]),"+f"(d[23]),"+f"(d[24]),"+f"(d[25]),"+f"(d[26]),"+f"(d[27]),"+f"(d[28]),"+f"(d[29]),"+f"(d[30]),"+f"(d[31]),"+f"(d[32]),"+f"(d[33]),"+f"(d[34]),"+f"(d[35]) : "r"(a0), "r"(a1), "r"(a2), "r"(a3), "l"(db));
}
template<> __device__ __forceinline__ void wg_rs<64>(float (&d)[64], uint32_t a0, uint32_t a1, uint32_t a2, uint32_t a3, uint64_t db) {
  asm volatile("{.reg .pred p; setp.ne.b32 p, 1, 0; wgmma.mma_async.sync.aligned.m64n64k16.f32.bf16.bf16 {%0,%1,%2,%3,%4,%5,%6,%7,%8,%9,%10,%11,%12,%13,%14,%15,%16,%17,%18,%19,%20,%21,%22,%23,%24,%25,%26,%27,%28,%29,%30,%31}, {%32,%33,%34,%35}, %36, p, 1, 1, 0;}"
    : "+f"(d[0]),"+f"(d[1]),"+f"(d[2]),"+f"(d[3]),"+f"(d[4]),"+f"(d[5]),"+f"(d[6]),"+f"(d[7]),"+f"(d[8]),"+f"(d[9]),"+f"(d[10]),"+f"(d[11]),"+f"(d[12]),"+f"(d[13]),"+f"(d[14]),"+f"(d[15]),"+f"(d[16]),"+f"(d[17]),"+f"(d[18]),"+f"(d[19]),"+f"(d[20]),"+f"(d[21]),"+f"(d[22]),"+f"(d[23]),"+f"(d[24]),"+f"(d[25]),"+f"(d[26]),"+f"(d[27]),"+f"(d[28]),"+f"(d[29]),"+f"(d[30]),"+f"(d[31]) : "r"(a0), "r"(a1), "r"(a2), "r"(a3), "l"(db));
}
__device__ __forceinline__ void wg_rs_first(float (&d)[64], uint32_t a0, uint32_t a1, uint32_t a2, uint32_t a3, uint64_t db) {
  asm volatile("{.reg .pred p; setp.ne.b32 p, 0, 0; wgmma.mma_async.sync.aligned.m64n128k16.f32.bf16.bf16 {%0,%1,%2,%3,%4,%5,%6,%7,%8,%9,%10,%11,%12,%13,%14,%15,%16,%17,%18,%19,%20,%21,%22,%23,%24,%25,%26,%27,%28,%29,%30,%31,%32,%33,%34,%35,%36,%37,%38,%39,%40,%41,%42,%43,%44,%45,%46,%47,%48,%49,%50,%51,%52,%53,%54,%55,%56,%57,%58,%59,%60,%61,%62,%63}, {%64,%65,%66,%67}, %68, p, 1, 1, 0;}"
    : "=f"(d[0]),"=f"(d[1]),"=f"(d[2]),"=f"(d[3]),"=f"(d[4]),"=f"(d[5]),"=f"(d[6]),"=f"(d[7]),"=f"(d[8]),"=f"(d[9]),"=f"(d[10]),"=f"(d[11]),"=f"(d[12]),"=f"(d[13]),"=f"(d[14]),"=f"(d[15]),"=f"(d[16]),"=f"(d[17]),"=f"(d[18]),"=f"(d[19]),"=f"(d[20]),"=f"(d[21]),"=f"(d[22]),"=f"(d[23]),"=f"(d[24]),"=f"(d[25]),"=f"(d[26]),"=f"(d[27]),"=f"(d[28]),"=f"(d[29]),"=f"(d[30]),"=f"(d[31]),"=f"(d[32]),"=f"(d[33]),"=f"(d[34]),"=f"(d[35]),"=f"(d[36]),"=f"(d[37]),"=f"(d[38]),"=f"(d[39]),"=f"(d[40]),"=f"(d[41]),"=f"(d[42]),"=f"(d[43]),"=f"(d[44]),"=f"(d[45]),"=f"(d[46]),"=f"(d[47]),"=f"(d[48]),"=f"(d[49]),"=f"(d[50]),"=f"(d[51]),"=f"(d[52]),"=f"(d[53]),"=f"(d[54]),"=f"(d[55]),"=f"(d[56]),"=f"(d[57]),"=f"(d[58]),"=f"(d[59]),"=f"(d[60]),"=f"(d[61]),"=f"(d[62]),"=f"(d[63]) : "r"(a0), "r"(a1), "r"(a2), "r"(a3), "l"(db));
}
__device__ __forceinline__ void wg_tt128(float (&d)[64], uint64_t da, uint64_t db, int sc) {
  asm volatile("{.reg .pred p; setp.ne.b32 p, %66, 0; wgmma.mma_async.sync.aligned.m64n128k16.f32.bf16.bf16 {%0,%1,%2,%3,%4,%5,%6,%7,%8,%9,%10,%11,%12,%13,%14,%15,%16,%17,%18,%19,%20,%21,%22,%23,%24,%25,%26,%27,%28,%29,%30,%31,%32,%33,%34,%35,%36,%37,%38,%39,%40,%41,%42,%43,%44,%45,%46,%47,%48,%49,%50,%51,%52,%53,%54,%55,%56,%57,%58,%59,%60,%61,%62,%63}, %64, %65, p, 1, 1, 1, 1;}"
    : "+f"(d[0]),"+f"(d[1]),"+f"(d[2]),"+f"(d[3]),"+f"(d[4]),"+f"(d[5]),"+f"(d[6]),"+f"(d[7]),"+f"(d[8]),"+f"(d[9]),"+f"(d[10]),"+f"(d[11]),"+f"(d[12]),"+f"(d[13]),"+f"(d[14]),"+f"(d[15]),"+f"(d[16]),"+f"(d[17]),"+f"(d[18]),"+f"(d[19]),"+f"(d[20]),"+f"(d[21]),"+f"(d[22]),"+f"(d[23]),"+f"(d[24]),"+f"(d[25]),"+f"(d[26]),"+f"(d[27]),"+f"(d[28]),"+f"(d[29]),"+f"(d[30]),"+f"(d[31]),"+f"(d[32]),"+f"(d[33]),"+f"(d[34]),"+f"(d[35]),"+f"(d[36]),"+f"(d[37]),"+f"(d[38]),"+f"(d[39]),"+f"(d[40]),"+f"(d[41]),"+f"(d[42]),"+f"(d[43]),"+f"(d[44]),"+f"(d[45]),"+f"(d[46]),"+f"(d[47]),"+f"(d[48]),"+f"(d[49]),"+f"(d[50]),"+f"(d[51]),"+f"(d[52]),"+f"(d[53]),"+f"(d[54]),"+f"(d[55]),"+f"(d[56]),"+f"(d[57]),"+f"(d[58]),"+f"(d[59]),"+f"(d[60]),"+f"(d[61]),"+f"(d[62]),"+f"(d[63]) : "l"(da), "l"(db), "r"(sc));
}
__device__ __forceinline__ void wg_tt64(float (&d)[64], uint64_t da, uint64_t db, int sc) {
  asm volatile("{.reg .pred p; setp.ne.b32 p, %34, 0; wgmma.mma_async.sync.aligned.m64n64k16.f32.bf16.bf16 {%0,%1,%2,%3,%4,%5,%6,%7,%8,%9,%10,%11,%12,%13,%14,%15,%16,%17,%18,%19,%20,%21,%22,%23,%24,%25,%26,%27,%28,%29,%30,%31}, %32, %33, p, 1, 1, 1, 1;}"
    : "+f"(d[0]),"+f"(d[1]),"+f"(d[2]),"+f"(d[3]),"+f"(d[4]),"+f"(d[5]),"+f"(d[6]),"+f"(d[7]),"+f"(d[8]),"+f"(d[9]),"+f"(d[10]),"+f"(d[11]),"+f"(d[12]),"+f"(d[13]),"+f"(d[14]),"+f"(d[15]),"+f"(d[16]),"+f"(d[17]),"+f"(d[18]),"+f"(d[19]),"+f"(d[20]),"+f"(d[21]),"+f"(d[22]),"+f"(d[23]),"+f"(d[24]),"+f"(d[25]),"+f"(d[26]),"+f"(d[27]),"+f"(d[28]),"+f"(d[29]),"+f"(d[30]),"+f"(d[31]) : "l"(da), "l"(db), "r"(sc));
}
__device__ __forceinline__ void wg_tt32(float (&d)[64], uint64_t da, uint64_t db, int sc) {
  asm volatile("{.reg .pred p; setp.ne.b32 p, %18, 0; wgmma.mma_async.sync.aligned.m64n32k16.f32.bf16.bf16 {%0,%1,%2,%3,%4,%5,%6,%7,%8,%9,%10,%11,%12,%13,%14,%15}, %16, %17, p, 1, 1, 1, 1;}"
    : "+f"(d[0]),"+f"(d[1]),"+f"(d[2]),"+f"(d[3]),"+f"(d[4]),"+f"(d[5]),"+f"(d[6]),"+f"(d[7]),"+f"(d[8]),"+f"(d[9]),"+f"(d[10]),"+f"(d[11]),"+f"(d[12]),"+f"(d[13]),"+f"(d[14]),"+f"(d[15]) : "l"(da), "l"(db), "r"(sc));
}
__device__ __forceinline__ void wg_g1(float (&d)[88], uint64_t da, uint64_t db, int sc) {
  asm volatile("{.reg .pred p; setp.ne.b32 p, %90, 0; wgmma.mma_async.sync.aligned.m64n176k16.f32.bf16.bf16 {%0,%1,%2,%3,%4,%5,%6,%7,%8,%9,%10,%11,%12,%13,%14,%15,%16,%17,%18,%19,%20,%21,%22,%23,%24,%25,%26,%27,%28,%29,%30,%31,%32,%33,%34,%35,%36,%37,%38,%39,%40,%41,%42,%43,%44,%45,%46,%47,%48,%49,%50,%51,%52,%53,%54,%55,%56,%57,%58,%59,%60,%61,%62,%63,%64,%65,%66,%67,%68,%69,%70,%71,%72,%73,%74,%75,%76,%77,%78,%79,%80,%81,%82,%83,%84,%85,%86,%87}, %88, %89, p, 1, 1, 1, 0;}"
    : "+f"(d[0]),"+f"(d[1]),"+f"(d[2]),"+f"(d[3]),"+f"(d[4]),"+f"(d[5]),"+f"(d[6]),"+f"(d[7]),"+f"(d[8]),"+f"(d[9]),"+f"(d[10]),"+f"(d[11]),"+f"(d[12]),"+f"(d[13]),"+f"(d[14]),"+f"(d[15]),"+f"(d[16]),"+f"(d[17]),"+f"(d[18]),"+f"(d[19]),"+f"(d[20]),"+f"(d[21]),"+f"(d[22]),"+f"(d[23]),"+f"(d[24]),"+f"(d[25]),"+f"(d[26]),"+f"(d[27]),"+f"(d[28]),"+f"(d[29]),"+f"(d[30]),"+f"(d[31]),"+f"(d[32]),"+f"(d[33]),"+f"(d[34]),"+f"(d[35]),"+f"(d[36]),"+f"(d[37]),"+f"(d[38]),"+f"(d[39]),"+f"(d[40]),"+f"(d[41]),"+f"(d[42]),"+f"(d[43]),"+f"(d[44]),"+f"(d[45]),"+f"(d[46]),"+f"(d[47]),"+f"(d[48]),"+f"(d[49]),"+f"(d[50]),"+f"(d[51]),"+f"(d[52]),"+f"(d[53]),"+f"(d[54]),"+f"(d[55]),"+f"(d[56]),"+f"(d[57]),"+f"(d[58]),"+f"(d[59]),"+f"(d[60]),"+f"(d[61]),"+f"(d[62]),"+f"(d[63]),"+f"(d[64]),"+f"(d[65]),"+f"(d[66]),"+f"(d[67]),"+f"(d[68]),"+f"(d[69]),"+f"(d[70]),"+f"(d[71]),"+f"(d[72]),"+f"(d[73]),"+f"(d[74]),"+f"(d[75]),"+f"(d[76]),"+f"(d[77]),"+f"(d[78]),"+f"(d[79]),"+f"(d[80]),"+f"(d[81]),"+f"(d[82]),"+f"(d[83]),"+f"(d[84]),"+f"(d[85]),"+f"(d[86]),"+f"(d[87]) : "l"(da), "l"(db), "r"(sc));
}

struct Params { const __nv_bfloat16 *x, *logA, *Aim, *Cr, *Ci, *logdt, *Dskip, *Wd; uint4* xnT; float2* st; uint2* S; unsigned* flags; };
struct Maps { CUtensorMap x[2], xo, out, wg, wu, wd, hst[2], hld, xt, sld; };

__device__ __forceinline__ void conv_channel(uint32_t cb, int w, int lane, uint32_t (&res)[8]) {
    const int q = lane & 3, g = lane >> 2, gam = g >> 2;
    float acc[64];
    uint4 a[4][4];
    const uint32_t t0 = cb + CH_T + (uint32_t)(14 + 4 * w + (g & 3) + 32 * gam - 2 * q) * 80u;
    #pragma unroll
    for (int s4 = 0; s4 < 4; s4++) {
        a[s4][0] = lds128(t0 + s4 * 16);
        a[s4][1] = lds128(t0 + 16 * 80 + s4 * 16);
        a[s4][2] = lds128(t0 - 8 * 80 + s4 * 16);
        a[s4][3] = lds128(t0 + 8 * 80 + s4 * 16);
    }
    const uint32_t l0 = FU(ldsf(t0 + 64)), l1 = FU(ldsf(t0 + 16 * 80 + 64)), l2 = FU(ldsf(t0 - 8 * 80 + 64)), l3 = FU(ldsf(t0 + 8 * 80 + 64));
    const uint64_t dU = mkdesc(cb + CH_U, UPLANE, 128, 0);
    WG_FENCE();
#define CT(N, s, c) wg_rs<N>(acc, a[(s) >> 2][0].c, a[(s) >> 2][1].c, a[(s) >> 2][2].c, a[(s) >> 2][3].c, dU + 4 * (s))
    wg_rs_first(acc, a[0][0].x, a[0][1].x, a[0][2].x, a[0][3].x, dU);
    CT(128, 1, y); CT(120, 2, z); CT(120, 3, w);
    CT(112, 4, x); CT(112, 5, y); CT(104, 6, z); CT(104, 7, w);
    CT(96, 8, x);  CT(96, 9, y);  CT(88, 10, z); CT(88, 11, w);
    CT(80, 12, x); CT(80, 13, y); CT(72, 14, z); CT(72, 15, w);
#undef CT
    wg_rs<64>(acc, l0, l1, l2, l3, dU + 64);
    wg_tt64(acc, mkdesc(cb + CH_A3, 128, 512, 0), mkdesc(cb + CH_B3, 128, 256, 0), 1);
    wg_tt32(acc, mkdesc(cb + CH_A3 + 256, 128, 512, 0), mkdesc(cb + CH_B3 + 1024, 128, 256, 0), 1);
    WG_COMMIT();
    WG_WAIT(0);
    fence_acc(acc);
    const int src1 = (lane & ~3) | ((q + 1) & 3);
    float E[16][2];
    #pragma unroll
    for (int j = 0; j < 16; j++) {
        const float nxt = (j < 15) ? acc[4 * (j + 1) + 2] : 0.f;
        const float sup = (q == 0) ? nxt : acc[4 * j + 2];
        const float v = __shfl_sync(0xffffffffu, sup, src1);
        E[j][0] = acc[4 * j] + acc[4 * j + 3];
        E[j][1] = acc[4 * j + 1] + v;
    }
    const int src2 = gam ? ((lane & 12) | ((q + 3) & 3)) : (16 | (lane & 12) | ((q + 1) & 3));
    const bool c1 = gam && q != 0, c2 = gam && q == 0;
    #pragma unroll
    for (int a2 = 0; a2 < 8; a2++) {
        float y[2];
        #pragma unroll
        for (int e = 0; e < 2; e++) {
            const float sup = c1 ? E[2 * a2][e] : E[2 * a2 + 1][e];
            const float nxt = (a2 < 7) ? E[2 * a2 + 2][e] : 0.f;
            const float keep = c2 ? nxt : (c1 ? E[2 * a2 + 1][e] : E[2 * a2][e]);
            y[e] = keep + __shfl_sync(0xffffffffu, sup, src2);
        }
        res[a2] = pack2(y[1], y[0]);
    }
}

__device__ __forceinline__ void layer_norm(uint32_t sb, int w, int lane, const __nv_bfloat16* x) {
    const uint32_t bars = sb + OFF_BAR;
    const int c = blockIdx.x;
    {
        if (elect_one()) {
            mbar_expect(bars + 8 * B_LNX, 4096);
            #pragma unroll
            for (int i = 0; i < 4; i++)
                bulk_load(sb + OFF_LN + (w + 4 * i) * 1040, x + (16 * (c & ~1) + 8 * (c & 1) + 16 + w + 4 * (i & 1) - 8 * (i & 2)) * DM, 1024, bars + 8 * B_LNX);
        }
        mbar_wait(bars + 8 * B_LNX, 0);
        STAMP(34);
        {
            const int r = w + 4 * (lane >> 3);
            const uint32_t r0 = sb + OFF_LN + r * 1040, ra = r0 + (lane & 7) * 16;
            const float pv = bf_lo(FU(ldsf(r0)));
            float s0 = 0.f, s1 = 0.f, a0 = 0.f, a1 = 0.f;
            uint4 nx = lds128(ra), ny = lds128(ra + 128);
            #pragma unroll 1
            for (int k = 128; k <= 1024; k += 128) {
                const uint32_t v[4] = {nx.x, nx.y, nx.z, nx.w};
                nx = ny; ny = lds128(ra + ((k + 128) & 1023));
                #pragma unroll
                for (int i = 0; i < 4; i++) { const float t0 = bf_lo(v[i]) - pv, t1 = bf_hi(v[i]) - pv; s0 += t0; s1 += t1; a0 = fmaf(t0, t0, a0); a1 = fmaf(t1, t1, a1); }
            }
            s0 += s1; a0 += a1;
            #pragma unroll
            for (int o = 4; o; o >>= 1) { s0 += __shfl_xor_sync(0xffffffffu, s0, o); a0 += __shfl_xor_sync(0xffffffffu, a0, o); }
            s0 *= 1.f / DM;
            const float m = pv + s0, var = fmaxf(fmaf(-s0, s0, a0 * (1.f / DM)), 0.f);
            float sd, ri;
            asm("sqrt.approx.ftz.f32 %0, %1;" : "=f"(sd) : "f"(bf_round(bf_round(var) + 1e-5f)));
            asm("rcp.approx.ftz.f32 %0, %1;" : "=f"(ri) : "f"(bf_round(sd)));
            const uint32_t m2 = pack2(m, m);
            if ((lane & 7) == 0) {
                sts64(sb + OFF_CSUM + r * 8, m2 & 0xffff0000u, FU(0.5f * ri));
            }
            #pragma unroll 1
            for (int k = 128; k <= 1024; k += 128) {
                uint32_t v[4] = {nx.x, nx.y, nx.z, nx.w};
                nx = ny; ny = lds128(ra + ((k + 128) & 1023));
                #pragma unroll
                for (int i = 0; i < 4; i++) {
                    uint32_t dv; asm("sub.rn.bf16x2 %0, %1, %2;" : "=r"(dv) : "r"(v[i]), "r"(m2));
                    v[i] = pack2(bf_lo(dv) * ri, bf_hi(dv) * ri);
                }
                sts128(ra + k - 128, v[0], v[1], v[2], v[3]);
            }
        }
        STAMP(62);
        bar_sync(4);
        {
            const uint32_t ad = sb + OFF_LN + (4 * ((lane & 7) >> 1) + (lane & 1) + 2 * ((lane >> 3) & 1)) * 1040 + (16 * w + (lane >> 4)) * 16;
            uint32_t r[8][4];
            #pragma unroll
            for (int i = 0; i < 8; i++)
                asm volatile("ldmatrix.sync.aligned.m8n8.x4.trans.shared.b16 {%0,%1,%2,%3}, [%4];" : "=r"(r[i][0]), "=r"(r[i][1]), "=r"(r[i][2]), "=r"(r[i][3]) : "r"(ad + 32 * i) : "memory");
            bar_sync(4);
            const uint32_t od = sb + OFF_LN + w * 4096 + lane * 8;
            #pragma unroll
            for (int i = 0; i < 8; i++) { sts64(od + i * 512, r[i][0], r[i][1]); sts64(od + i * 512 + 256, r[i][2], r[i][3]); }
        }
        fence_async_smem();
        mbar_arrive(bars + 8 * B_LN);
        STAMP(16);
    }
}

__device__ __forceinline__ void consumer(uint32_t sb, int warp, const Params& P, const Maps& M) {
    const int V = warp >> 2, w = warp & 3, lane = threadIdx.x & 31, q = lane & 3, g = lane >> 2;
    const int c = blockIdx.x;
    const uint32_t bars = sb + OFF_BAR, xb = sb + OFF_X + V * 2 * XBUF;
    {
        float ag[88], au[88];
        if (V == 0) {
            sts128(xb + (w >> 1) * XBUF + 168 * 128 + (threadIdx.x & 63) * 16, 0x3f803f80u, 0x3f803f80u, 0x3f803f80u, 0x3f803f80u);
            fence_async_smem();
            bar_sync(1);
        } else {
            if (c < 128) layer_norm(sb, w, lane, P.x); else mbar_arrive(bars + 8 * B_LN);
            mbar_wait(bars + 8 * B_GO, 0);
        }
        define_acc(ag); define_acc(au);
        #pragma unroll 1
        for (int st = 0; st < 8; st++) {
            if (st + LAG * V == HOLD0 || st + LAG * V == HOLD1) mbar_wait(bars + 8 * (B_K + (st + LAG * V == HOLD1)), 0);
            mbar_wait(bars + 8 * (B_FULLW + (st & 3)), st >> 2);
            mbar_wait(bars + 8 * (B_FULLX + 2 * V + (st & 1)), (st >> 1) & 1);
            STAMP(40 + 8 * V + st);
            const uint64_t dG = mkdesc(sb + OFF_W + (st & 3) * 16384, 0, 1024, 1);
            const uint64_t dX = mkdesc(xb + (st & 1) * XBUF, 16, 1024, 1);
            WG_FENCE();
            #pragma unroll
            for (int k = 0; k < 4; k++) {
                wg_g1(ag, dG + k * 128, dX + k * 2, k ? 1 : st);
                wg_g1(au, dG + 512 + k * 128, dX + k * 2, k ? 1 : st);
            }
            WG_COMMIT();
            WG_WAIT(1);
            if (lane == 0 && st > 0) {
                mbar_arrive(bars + 8 * (B_EMPTYW + ((st - 1) & 3)));
                mbar_arrive(bars + 8 * (B_EMPTYX + 2 * V + ((st - 1) & 1)));
                if (warp < 4 && st == LAG) mbar_arrive(bars + 8 * B_GO);
            }
        }
        WG_WAIT(0);
        fence_acc(ag); fence_acc(au);
        if (lane == 0) { mbar_arrive(bars + 8 * (B_EMPTYW + 3)); mbar_arrive(bars + 8 * (B_EMPTYX + 2 * V + 1)); }
        STAMP(8 * V + 1);
        float cg0 = ag[84], cg1 = ag[86], cu0 = au[84], cu1 = au[86];
        const uint32_t ca = sb + OFF_CSUM + (8 * w + g) * 16;
        if (V == 0) { sts128(ca, FU(cg0), FU(cg1), FU(cu0), FU(cu1)); mbar_arrive(bars + 8 * B_CS); }
        else { mbar_wait(bars + 8 * B_CS, 0); const uint4 t = lds128(ca); cg0 = UF(t.x); cg1 = UF(t.y); cu0 = UF(t.z); cu1 = UF(t.w); }
        mbar_wait(bars + 8 * B_STATS, 0);
        mbar_wait(bars + 8 * (B_EMPTYX + 2 * V), 1);
        STAMP(13 + V);
        const uint32_t hs = xb + (2 * w + ((lane >> 3) & 1)) * (2688 + 128 * V) + (lane >> 4) * 128 + (lane & 7) * 16;
        const uint32_t sa = sb + OFF_ST + (168 * V + 2 * q) * 8;
        uint4 sq[22];
        #pragma unroll
        for (int j = 0; j < 3; j++) sq[j] = lds128(sa + j * 64);
        #pragma unroll
        for (int j = 0; j < 22; j += 2) {
            uint32_t o[4];
            #pragma unroll
            for (int jj = 0; jj < 2; jj++) {
                const uint4 sv = sq[j + jj];
                float hv[4];
                #pragma unroll
                for (int i = 0; i < 4; i++) {
                    const float m = UF((i & 1) ? sv.z : sv.x);
                    const float gh = fmaf(-m, (i & 2) ? cg1 : cg0, ag[4 * (j + jj) + i]) * UF((i & 1) ? sv.w : sv.y);
                    const float p = gh * fmaf(-m, (i & 2) ? cu1 : cu0, au[4 * (j + jj) + i]);
                    hv[i] = fmaf(p, tanh_fast(gh), p);
                }
                o[2 * jj] = pack2(hv[0], hv[1]); o[2 * jj + 1] = pack2(hv[2], hv[3]);
            }
            #pragma unroll
            for (int k = (j ? 3 + 3 * j / 2 : 3); k < 6 + 3 * j / 2 && k < 22; k++) sq[k] = lds128(sa + k * 64);
            uint32_t ad = hs + j * 128;
            if (j == 20 && V == 0 && lane >= 16) ad = xb + 21504 + (lane & 7) * 16;
            stsm4(ad, o[0], o[1], o[2], o[3]);
        }
        fence_async_smem();
        mbar_arrive(bars + 8 * (B_EPI + V));
        STAMP(8 * V + 2);
    }
    if (c >= 128) return;
    {
        uint32_t r0[8], r1[8];
        #pragma unroll
        for (int i = 0; i < 8; i++) asm volatile("" : "=r"(r1[i]));
        #pragma unroll 1
        for (int e = 0; e < 2; e++) {
            #pragma unroll
            for (int i = 0; i < 8; i++) r0[i] = r1[i];
            mbar_wait(bars + 8 * (B_CONV + 2 * V + e), 0);
            conv_channel(sb + OFF_CONV + (2 * V + e) * CH_STRIDE, w, lane, r1);
            if (e == 0) STAMP(8 * V + 3);
        }
        const int gam = g >> 2, qq = gam ? ((q + 3) & 3) : q;
        const uint32_t sp = sb + OFF_CONV + V * 58368 + ((63 - 4 * gam - qq) * 16 + 4 * w + (g & 3)) * 8;
        bar_sync(3 + V);
        #pragma unroll
        for (int a2 = 0; a2 < 8; a2++) sts64(sp - a2 * 1024, r0[a2], r1[a2]);
        fence_async_smem();
        mbar_arrive(bars + 8 * (B_SIG + V));
        STAMP(8 * V + 4);
    }
    if (V == 1) return;
    {
        const int tau = 2 * (c >> 3) + (c & 1), dg = (c >> 1) & 3;
        const uint32_t row = 8 * (w & 1) + 32 * (w >> 1);
        float acc[64];
        define_acc(acc);
        const float rr0 = __ldcg(&P.st[64 * tau + row + g].y), rr1 = __ldcg(&P.st[64 * tau + row + g + 16].y);
        mbar_wait(bars + 8 * B_FULLD, 0);
        STAMP(5);
        uint64_t dB = mkdesc(sb + wd_slot(0), 8192, 1024, 1), dA = mkdesc(sb + h_slot(0), 1024, 128, 0);
        uint32_t peer;
        asm volatile("{.reg .b32 p; mov.u32 p, %%cluster_ctarank; xor.b32 p, p, 1; mapa.shared::cluster.u32 %0, %1, p;}" : "=r"(peer) : "r"(bars));
        #pragma unroll 1
        for (int st = 0; st < 21; st++) {
            WG_FENCE();
            wg_tt128(acc, dA, dB, st);
            wg_tt128(acc, dA + 128, dB + 128, 1);
            wg_tt128(acc, dA + 256, dB + 256, 1);
            wg_tt128(acc, dA + 384, dB + 384, 1);
            WG_COMMIT();
            const int sd = (st + 1) & 7;
            const uint32_t nb = bars + 8 * (B_FULLD + sd), np = ((st + 1) >> 3) & 1;
            uint32_t ro = st == 15 ? 8 * B_CH0 : 8 * (B_EMPTYD + ((st - 1) & 7)), m = (lane == 0 && st > 0) ? (st < 15 ? 3 : st == 15) : 0, ok;
            dB = mkdesc(sb + wd_slot(sd), 8192, 1024, 1); dA = mkdesc(sb + h_slot(sd), 1024, 128, 0);
            asm volatile("{.reg .pred p; mbarrier.test_wait.parity.shared::cta.b64 p, [%5], %6; vote.sync.all.pred p, p, -1; selp.u32 %0, 1, 0, p;}"
                : "=r"(ok), "+l"(dA), "+l"(dB), "+r"(ro), "+r"(m) : "r"(nb), "r"(np) : "memory");
            WG_WAIT(1);
            asm volatile("{.reg .pred p, q; setp.ne.u32 p, %2, 0; setp.eq.u32 q, %2, 3; @p mbarrier.arrive.shared::cta.b64 _, [%0]; @q mbarrier.arrive.shared::cluster.b64 _, [%1];}"
                :: "r"(bars + ro), "r"(peer + ro), "r"(m) : "memory");
            if (!ok) mbar_wait(nb, np);
            if (w == 0) STAMP2(20 + st);
        }
        WG_FENCE();
        wg_tt128(acc, dA, dB, 1);
        wg_tt128(acc, dA + 128, dB + 128, 1);
        WG_COMMIT();
        mbar_wait(bars + 8 * B_XO, 0);
        mbar_wait(bars + 8 * B_S, 0);
        const uint32_t xo = sb + OFF_CONV + (row + (lane & 7) + 16 * ((lane >> 3) & 1)) * 128;
        const uint32_t so = sb + wd_slot(6) + (w >> 1) * 8192 + q * 256 + (g & 1) * 8;
        uint32_t xr[8][4];
        uint2 sv[16];
        #pragma unroll
        for (int j = 0; j < 16; j += 2) {
            ldsm4(xr[j >> 1], xo + (j >> 3) * 8192 + ((((j & 7) + (lane >> 4)) ^ (lane & 7)) << 4));
            sv[j] = lds64(so + j * 512 + (((4 * (w & 1) + (g >> 1)) ^ (2 * q)) << 4));
            sv[j + 1] = lds64(so + j * 512 + 128 + (((4 * (w & 1) + (g >> 1)) ^ (2 * q + 1)) << 4));
        }
        WG_WAIT(0);
        fence_acc(acc);
        STAMP(6);
        #pragma unroll
        for (int j = 0; j < 16; j += 2) {
            #pragma unroll
            for (int i = 0; i < 4; i++) {
                const int jj = j + (i >> 1), hh = i & 1;
                const float f0 = acc[4 * jj + 2 * hh] * (hh ? rr1 : rr0), f1 = acc[4 * jj + 2 * hh + 1] * (hh ? rr1 : rr0);
                const uint32_t G = pack2(fmaf(f0, tanh_fast(f0), f0), fmaf(f1, tanh_fast(f1), f1));
                const uint32_t s2 = __byte_perm(sv[jj].x, sv[jj].y, hh ? 0x7632 : 0x5410);
                asm("fma.rn.bf16x2 %0, %1, %2, %0;" : "+r"(xr[j >> 1][i]) : "r"(s2), "r"(G));
            }
            stsm4(xo + (j >> 3) * 8192 + ((((j & 7) + (lane >> 4)) ^ (lane & 7)) << 4), xr[j >> 1][0], xr[j >> 1][1], xr[j >> 1][2], xr[j >> 1][3]);
        }
        fence_async_smem();
        bar_sync(1);
        if (w == 0 && elect_one()) {
            #pragma unroll
            for (int i = 0; i < 2; i++)
                asm volatile("cp.async.bulk.tensor.2d.global.shared::cta.bulk_group [%0, {%2, %3}], [%1];"
                    :: "l"(&M.out), "r"(sb + OFF_CONV + i * 8192), "r"(dg * 128 + 64 * i), "r"(tau * 64) : "memory");
            asm volatile("cp.async.bulk.commit_group; cp.async.bulk.wait_group.read 0;" ::: "memory");
        }
        STAMP(7); GSTAMP(23);
    }
}

__device__ __forceinline__ float2 cexp_p(float re2, float im, float p) {
    float sn, cs;
    const float mag = ex2(re2 * p), th = im * p;
    asm("sin.approx.ftz.f32 %0, %1;" : "=f"(sn) : "f"(th));
    asm("cos.approx.ftz.f32 %0, %1;" : "=f"(cs) : "f"(th));
    return make_float2(mag * cs, mag * sn);
}
__device__ __forceinline__ unsigned short ldu16(const void* p) { unsigned short v; asm volatile("ld.global.nc.u16 %0, [%1];" : "=h"(v) : "l"(p)); return v; }
__device__ __forceinline__ float2 cmul(float2 a, float2 b) { return make_float2(fmaf(a.x, b.x, -a.y * b.y), fmaf(a.x, b.y, a.y * b.x)); }
__device__ __forceinline__ float2 csqr(float2 a) { const float t = a.x * a.y; return make_float2(fmaf(a.x, a.x, -a.y * a.y), t + t); }
__device__ __forceinline__ void mma16816(float (&d)[4], const uint32_t (&a)[4], uint32_t b0, uint32_t b1) {
    asm volatile("mma.sync.aligned.m16n8k16.row.col.f32.bf16.bf16.f32 {%0,%1,%2,%3}, {%4,%5,%6,%7}, {%8,%9}, {%0,%1,%2,%3};"
        : "+f"(d[0]), "+f"(d[1]), "+f"(d[2]), "+f"(d[3]) : "r"(a[0]), "r"(a[1]), "r"(a[2]), "r"(a[3]), "r"(b0), "r"(b1));
}

__device__ __forceinline__ void aux_role(uint32_t sb, int w, const Params& P) {
    const int lane = threadIdx.x & 31, q = lane & 3, g = lane >> 2;
    const int c = blockIdx.x;
    const uint32_t bars = sb + OFF_BAR;
    if (c >= 128) {
        if (lane == 0) { mbar_arrive(bars + 8 * B_K); mbar_arrive(bars + 8 * (B_K + 1)); }
        return;
    }
    {
        const uint32_t cb = sb + OFF_CONV + w * CH_STRIDE;
        const uint32_t sF = cb + CH_A3;
        const int d = 4 * c + w;
        const int po = d * 128 + lane;
        unsigned short la = ldu16(P.logA + po), ai = ldu16(P.Aim + po), cr = ldu16(P.Cr + po), ci = ldu16(P.Ci + po);
        const float ldt = __bfloat162float(P.logdt[d]), dsk = __bfloat162float(P.Dskip[d]);
        float dacc[2][3][4];
        #pragma unroll
        for (int i = 0; i < 24; i++) (&dacc[0][0][0])[i] = 0.f;
        const float dt = bf_round(ex2(ldt * 1.4426950408889634f));
        #pragma unroll 1
        for (int ck = 0; ck < 4; ck++) {
            const uint32_t fa = cb + lane * 4 + (ck & 1) * 8064;
            const float re2 = bf_round(ex2(bf_lo((uint32_t)la) * 1.4426950408889634f)) * dt * -1.4426950408889634f, im = bf_lo((uint32_t)ai) * dt;
            const float2 C = make_float2(bf_lo((uint32_t)cr) * (dt + dt), bf_lo((uint32_t)ci) * -(dt + dt));
            {
                const int pn = po + 32 * min(ck + 1, 3);
                la = ldu16(P.logA + pn); ai = ldu16(P.Aim + pn); cr = ldu16(P.Cr + pn); ci = ldu16(P.Ci + pn);
            }
            const float2 z8 = cexp_p(re2, im, 8.f), y1 = cexp_p(re2, -im, 1.f);
            float2 b0 = make_float2(1.f, 0.f), b1 = cexp_p(re2, im, 64.f), b2 = csqr(b1), b3 = cmul(b2, b1), l0 = C;
            const uint32_t fm = cb + (ck & 1) * 8064 + (lane >> 3) * 144 + (lane & 7) * 16;
#define PK(v) pack2((v).x, (v).y)
            #pragma unroll 1
            for (uint32_t ro = 0; ro < 8 * 144; ro += 144) {
                stsm4(fm + (lane >> 3) * 7 * 144 + ro, PK(b0), PK(b1), PK(b2), PK(b3));
                stsf(fa + 32 * 144 + ro, UF(PK(l0)));
                b0 = cmul(b0, z8); b1 = cmul(b1, z8); b2 = cmul(b2, z8); b3 = cmul(b3, z8); l0 = cmul(l0, y1);
            }
            if (ck < 2) STAMP(56 + 3 * ck);
            const float2 y256 = cexp_p(re2, -im, 256.f), y2 = csqr(y1), y4 = csqr(y2), y8 = make_float2(z8.x, -z8.y);
            const float2 t0 = cmul(C, y256), t1 = cmul(t0, y256), t2 = cmul(t1, y256), t3_ = cmul(t2, y256);
            const float2 u1 = cmul(t0, y2), u2 = cmul(u1, y2), u3 = cmul(u2, y2);
            stsm4(fm + 40 * 144, PK(t0), PK(u1), PK(u2), PK(u3));
            stsm4(fm + 44 * 144, PK(t1), PK(cmul(t1, y4)), PK(t2), PK(cmul(t2, y4)));
            const float2 v0 = cmul(t3_, y8), v1 = cmul(v0, y256), v2 = cmul(v1, y256), v3 = cmul(v2, y256);
            stsm4(fm + 48 * 144, PK(v0), PK(v1), PK(v2), PK(v3));
            stsf(fa + 52 * 144, UF(PK(t3_)));
#undef PK
            if (ck < 2) STAMP(57 + 3 * ck);
            if (ck & 1) {
                uint32_t ln_; asm volatile("mov.u32 %0, %%laneid;" : "=r"(ln_));
                const uint32_t lda = cb + (ln_ & 15) * 144 + (ln_ & 16);
                const uint32_t ldb = cb + (32 + (ln_ & 7)) * 144 + (ln_ >> 3) * 16;
                __syncwarp();
                #pragma unroll
                for (int k2 = 0; k2 < 4; k2++) {
                    const uint32_t ko = (k2 >> 1) * 8064 + (k2 & 1) * 64;
                    uint32_t b[3][4];
                    #pragma unroll
                    for (int t3 = 0; t3 < 3; t3++) ldsm4(b[t3], ldb + t3 * 8 * 144 + ko);
                    #pragma unroll
                    for (int k = 0; k < 2; k++)
                        #pragma unroll
                        for (int mu = 0; mu < 2; mu++) {
                            uint32_t a[4];
                            ldsm4(a, lda + mu * 16 * 144 + ko + k * 32);
                            #pragma unroll
                            for (int t3 = 0; t3 < 3; t3++) mma16816(dacc[mu][t3], a, b[t3][2 * k], b[t3][2 * k + 1]);
                        }
                }
                __syncwarp();
                if (lane == 0) mbar_arrive(bars + 8 * (B_K + (ck >> 1)));
                STAMP(58 + 3 * (ck >> 1));
            }
        }
        STAMP(18);
        const uint32_t sG = cb + CH_G;
        if (lane == 0) dacc[0][0][0] += dsk;
        if (lane < 16) sts128(((lane & 8) ? cb + CH_U + 2048 + (lane & 4) * (UPLANE / 4) : sG + 128 + (lane & 4) * 48) + (lane & 3) * 16, 0, 0, 0, 0);
        {
            const uint32_t f0 = sF + (8 * g + 2 * q) * 4, f1 = sF + ((q < 2) ? 256 + 4 * g + 2 * q : 256 + 2 * g + 64 * q) * 4, st1 = (q < 2) ? 128 : 64;
            const uint32_t ga = sG + ((g & 1) ? 0 : 192) + (63 - (g >> 1) - 32 * q) * 2;
            #pragma unroll
            for (int i = 0; i < 4; i++) {
                const int mu = i >> 1, hh = i & 1;
                sts64(f0 + i * 256, FU(dacc[mu][0][2 * hh]), FU(dacc[mu][0][2 * hh + 1]));
                sts64(f1 + i * st1, FU(dacc[mu][1][2 * hh]), FU(dacc[mu][1][2 * hh + 1]));
                const uint32_t pk = pack2(dacc[mu][2][2 * hh], dacc[mu][2][2 * hh + 1]);
                if (q < 2) { sts16(ga - 8 * i, pk & 0xffff); sts16(ga - 8 * i - 32, pk >> 16); }
            }
            if (lane == 2) stsf(sF + 2048, dacc[0][2][0]);
        }
    }
    bar_sync(2);
    STAMP(19);
    const int rw = lane - 1 + 31 * w, u = min(rw, 77) - 14;
    const uint32_t o0 = CH_A3 + u * 4, o1 = CH_A3 + (128 + ((u + ((u >> 1) & 1)) >> 1)) * 4, o2 = CH_A3 + (256 + ((u + 1 + ((u >> 2) & 1)) >> 2)) * 4;
    const int kap = (lane >> 4) * 8 + ((lane >> 1) & 7), gam = lane & 1, hh = w >> 1, wp = w & 1;
    const uint32_t oa = CH_U + wp * UPLANE + (127 - 4 * kap - 2 * gam - hh) * 16;
    const uint32_t ob = CH_U + (wp ^ 1) * UPLANE + (128 - wp - 4 * kap - 2 * gam - hh) * 16;
    const uint32_t od = CH_A3 + (4 * wp + hh) * 512 + (kap >> 3) * 256 + (kap & 7) * 16 + gam * 8;
    #pragma unroll 1
    for (int k = 0; k < 4; k++) {
        const int ch = 2 * (k & 1) + (k >> 1);
        const uint32_t cb = sb + OFF_CONV + ch * CH_STRIDE;
        if (w < 3) {
            const uint32_t f0 = cb + o0, f1 = cb + o1, f2 = cb + o2;
            float kv[17];
            kv[0] = ldsf(u < 0 ? f1 : f0); if (u < 0) kv[0] = 0.f;
            #pragma unroll
            for (int s = 1; s < 4; s++) kv[s] = ldsf(f0 + s * 256);
            kv[4] = ldsf(u < 0 ? f0 + 1024 : f1 + 512);
            #pragma unroll
            for (int s = 5; s < 8; s++) kv[s] = ldsf(f1 + s * 128);
            kv[8] = ldsf(u < 0 ? f1 + 1024 : f2 + 512);
            #pragma unroll
            for (int s = 9; s < 16; s++) kv[s] = ldsf(f2 + s * 64);
            kv[16] = ldsf(u < 0 ? f2 + 1024 : cb + CH_A3 + 2048); if (u > 4) kv[16] = 0.f;
            uint32_t o[17];
            #pragma unroll
            for (int s = 0; s < 17; s++) o[s] = pack2(kv[s], __shfl_up_sync(0xffffffffu, kv[s], 1));
            if (lane > 0 && rw < 78) {
                const uint32_t ta = cb + CH_T + rw * 80;
                #pragma unroll
                for (int s4 = 0; s4 < 4; s4++) sts128(ta + s4 * 16, o[4 * s4], o[4 * s4 + 1], o[4 * s4 + 2], o[4 * s4 + 3]);
                stsf(ta + 64, UF(o[16]));
            }
        } else {
            const uint32_t ga = cb + CH_G + ((lane >> 3) & 1) * 192 + (lane >> 4) * 16 + (lane & 7) * 8;
            #pragma unroll
            for (int i = 0; i < 4; i++) {
                const uint2 x0 = lds64(ga + 32 * i), x1 = lds64(ga + 32 * i + 8);
                sts128(cb + CH_B3 + lane * 16 + 512 * i, x0.x, x0.y, x1.x, x1.y);
            }
        }
        mbar_wait(bars + 8 * B_U, 0);
        float p[24];
        const uint2 r0 = lds64(cb + ob + 24), r3 = lds64(cb + oa);
        uint32_t r[8];
        *(uint4*)&r[0] = lds128(cb + oa + 16); *(uint4*)&r[4] = lds128(cb + ob);
        p[0] = 0.f;
        p[1] = bf_lo(r0.x); p[2] = p[1] + bf_hi(r0.x); p[3] = p[2] + bf_lo(r0.y); p[4] = p[3] + bf_hi(r0.y);
        #pragma unroll
        for (int i = 0; i < 8; i++) { p[5 + 2 * i] = p[4 + 2 * i] + bf_lo(r[i]); p[6 + 2 * i] = p[5 + 2 * i] + bf_hi(r[i]); }
        p[21] = p[20] + bf_lo(r3.x); p[22] = p[21] + bf_hi(r3.x); p[23] = p[22] + bf_lo(r3.y);
        bar_sync(2);
        #pragma unroll
        for (int i = 0; i < 8; i += 4) {
            sts64(cb + od + i * 256, pack2(p[i + 9] - p[i], p[i + 10] - p[i + 1]), pack2(p[i + 11] - p[i + 2], p[i + 12] - p[i + 3]));
            sts64(cb + od + i * 256 + 128, pack2(p[i + 16] - p[i + 9], p[i + 17] - p[i + 10]), pack2(p[i + 18] - p[i + 11], p[i + 19] - p[i + 12]));
        }
        fence_async_smem();
        mbar_arrive(bars + 8 * (B_CONV + ch));
        if (k == 0) STAMP(17);
    }
    STAMP(21);
}

__global__ void __cluster_dims__(2, 1, 1) __launch_bounds__(512, 1)
fused_kernel(const __grid_constant__ Params P, const __grid_constant__ Maps M) {
    extern __shared__ __align__(1024) uint8_t smem_raw[];
    const uint32_t sb = smem_u32(smem_raw);
    const uint32_t bars = sb + OFF_BAR;
    const int warp = __shfl_sync(0xffffffffu, threadIdx.x >> 5, 0);
    const int c = blockIdx.x, tg = c / 22, fb = c - 22 * tg;
    if (elect_one()) {
        if (warp == 0) { STAMP(24); GSTAMP(22); }
        asm volatile("" :: "l"(((const uint64_t*)&P)[warp < 12 ? warp : 0]));
        if (warp < 12) asm volatile("prefetch.tensormap [%0];" :: "l"(&M.x[0] + warp) : "memory");
        #pragma unroll
        for (int k = 0; k < 4; k++) {
            const int i = 16 * k + ((warp + 4) & 15);
            const uint32_t cnt = ((0xff00000000ff0000ull >> i) & 1) ? 2 : i >= B_CONV ? 128 : ((0xff0000f0ull >> i) & 1) ? 8 : ((0x3e000000f000ull >> i) & 1) ? 4 : 1;
            asm volatile("mbarrier.init.shared::cta.b64 [%0], %1;" :: "r"(bars + 8 * i), "r"(cnt) : "memory");
        }
        asm volatile("fence.mbarrier_init.release.cluster; fence.proxy.async.shared::cta;" ::: "memory");
        if (warp == 12) {
            mbar_expect(bars + 8 * B_FULLW, 16384);
            tma2d(sb + OFF_W, &M.wg, 64 * fb, 0, bars + 8 * B_FULLW);
            tma2d(sb + OFF_W + 8192, &M.wu, 64 * fb, 0, bars + 8 * B_FULLW);
            STAMP(31);
        } else if (warp == 4) {
            mbar_expect(bars + 8 * B_FULLX, 168 * 128);
            tma2d(sb + OFF_X, &M.x[0], 0, TOKG * tg, bars + 8 * B_FULLX);
        }
        if (sb & 1023) __trap();
    }
    __syncthreads();
    asm volatile("barrier.cluster.arrive.relaxed.aligned;" ::: "memory");
    if (warp < 8) {
        asm volatile("setmaxnreg.inc.sync.aligned.u32 208;");
        consumer(sb, warp, P, M);
    } else if (warp < 12) {
        asm volatile("setmaxnreg.dec.sync.aligned.u32 72;");
        STAMP(32);
        aux_role(sb, warp - 8, P);
    } else {
        asm volatile("setmaxnreg.dec.sync.aligned.u32 24;");
        const int tau = 2 * (c >> 3) + (c & 1), dg = (c >> 1) & 3;
        if (elect_one()) {
            if (warp == 12) {
                #pragma unroll 1
                for (int st = 1; st < 8; st++) {
                    const uint32_t s = st & 3, fb_ = bars + 8 * (B_FULLW + s);
                    if (st == 2) mbar_wait(bars + 8 * B_FULLW, 0);
                    mbar_wait(bars + 8 * (B_EMPTYW + s), (st >> 2) ^ 1);
                    mbar_expect(fb_, 16384);
                    tma2d(sb + OFF_W + s * 16384, &M.wg, 64 * fb, 64 * st, fb_);
                    tma2d(sb + OFF_W + s * 16384 + 8192, &M.wu, 64 * fb, 64 * st, fb_);
                }
                if (c < 128) {
                    asm volatile("barrier.cluster.wait;" ::: "memory");
                    #pragma unroll 1
                    for (int st = 0; st < 22; st++) {
                        const int sd = st & 7;
                        if (st < 8) {
                            mbar_wait(bars + 8 * (uint32_t)((0x373623070d060504ull >> (8 * st)) & 0xff), st < 5);
                            mbar_arrive_pair(bars + 8 * (B_RDY + st));
                            mbar_wait(bars + 8 * (B_RDY + st), 0);
                        } else mbar_wait(bars + 8 * (B_EMPTYD + sd), ((st >> 3) & 1) ^ 1);
                        const uint32_t fb_ = bars + 8 * (B_FULLD + sd);
                        mbar_expect(fb_, 16384);
                        asm volatile("cp.async.bulk.tensor.2d.shared::cluster.global.mbarrier::complete_tx::bytes.multicast::cluster [%0], [%1, {%3, %4}], [%2], %5;"
                            :: "r"(sb + wd_slot(sd) + (c & 1) * 8192), "l"(&M.wd), "r"(fb_), "r"(128 * dg + 64 * (c & 1)), "r"(64 * st), "h"((unsigned short)3) : "memory");
                    }
                }
            } else if (warp < 15) {
                const int V = warp - 13;
                #pragma unroll 1
                for (int st = 1 - V; st < 8; st++) {
                    const uint32_t s = 2 * V + (st & 1);
                    if (s == 3 && st == 1) mbar_wait(bars + 8 * B_LNS, 0);
                    mbar_wait(bars + 8 * (B_EMPTYX + s), ((st >> 1) & 1) ^ 1);
                    mbar_expect(bars + 8 * (B_FULLX + s), (168 + 8 * V) * 128);
                    tma2d(sb + OFF_X + s * XBUF, &M.x[V], 64 * st, TOKG * tg + 168 * V, bars + 8 * (B_FULLX + s));
                }
                if (c < 128) {
                    if (V == 0) {
                        mbar_wait(bars + 8 * (B_STG + 1), 0);
                        #pragma unroll 1
                        for (int o = 8 * tau; o < 8 * tau + 8; o += 7) flag_wait(P.flags, F_H + 2 * (o / 43) + ((o % 43) >= 21), 22);
                        mbar_arrive(bars + 8 * B_HF);
                        STAMP(25);
                        #pragma unroll 1
                        for (int st = 0; st < 22; st++) {
                            const uint32_t fb_ = bars + 8 * (B_FULLD + (st & 7));
                            if (st == 6 || st == 7) mbar_wait(bars + 8 * (B_SIG - 6 + st), 0);
                            mbar_wait(bars + 8 * (B_EMPTYD + (st & 7)), ((st >> 3) & 1) ^ 1);
                            mbar_expect(fb_, 8192);
                            asm volatile("cp.async.bulk.tensor.5d.shared::cluster.global.mbarrier::complete_tx::bytes [%0], [%1, {%3, %3, %3, %4, %5}], [%2];"
                                :: "r"(sb + h_slot(st & 7)), "l"(&M.hld), "r"(fb_), "r"(0), "r"(2 * tau), "r"(8 * st) : "memory");
                        }
                    } else {
                        mbar_wait(bars + 8 * B_SST, 0);
                        mbar_wait(bars + 8 * B_CH0, 0);
                        mbar_expect(bars + 8 * B_XO, 16384);
                        tma2d(sb + OFF_CONV, &M.xo, 128 * dg, 64 * tau, bars + 8 * B_XO);
                        tma2d(sb + OFF_CONV + 8192, &M.xo, 128 * dg + 64, 64 * tau, bars + 8 * B_XO);
                        flag_wait(P.flags, F_S + dg, 64);
                        STAMP(26);
                        mbar_expect(bars + 8 * B_S, 16384);
                        asm volatile("cp.async.bulk.tensor.5d.shared::cluster.global.mbarrier::complete_tx::bytes [%0], [%1, {%3, %3, %3, %4, %5}], [%2];"
                            :: "r"(sb + wd_slot(6)), "l"(&M.sld), "r"(bars + 8 * B_S), "r"(0), "r"(8 * dg), "r"(2 * tau) : "memory");
                        mbar_wait(bars + 8 * B_HF, 0);
                        exit_count(P.flags);
                    }
                }
            } else {
                mbar_wait(bars + 8 * B_LN, 0);
                STAMP2(0);
                if (c < 128) {
                    #pragma unroll 1
                    for (int i = 0; i < 2; i++)
                        asm volatile("cp.async.bulk.tensor.2d.global.shared::cta.bulk_group [%0, {%2, %3}], [%1];"
                            :: "l"(&M.xt), "r"(sb + OFF_LN + i * 8192), "r"((c & 1) * 1024 + (126 - (c & ~1)) * 8), "r"(256 * i) : "memory");
                    #pragma unroll 1
                    for (int i = 0; i < 2; i++) bulk_store(P.st + 16 * (c & ~1) + 8 * (c & 1) + 16 - 16 * i, sb + OFF_CSUM + 64 * i, 64);
                    asm volatile("cp.async.bulk.prefetch.L2.global [%0], %1;" :: "l"(P.Wd + c * (FF * DM / 128)), "r"(FF * DM / 64) : "memory");
                }
                asm volatile("cp.async.bulk.commit_group; cp.async.bulk.wait_group.read 0;" ::: "memory");
                mbar_arrive(bars + 8 * B_LNS);
                STAMP2(1);
                flag_signal(P.flags, F_A);
                STAMP2(2);
                flag_wait(P.flags, F_A, NCTA);
                STAMP(20);
                mbar_expect(bars + 8 * B_STATS, TOKG * 8);
                bulk_load(sb + OFF_ST, P.st + TOKG * tg, TOKG * 8, bars + 8 * B_STATS);
                if (c < 128) {
                    mbar_wait(bars + 8 * (B_K + 1), 0);
                    fence_async_smem();
                    mbar_expect(bars + 8 * B_U, 8 * 2048);
                    #pragma unroll 1
                    for (int i = 0; i < 8; i++)
                        bulk_load(sb + OFF_CONV + (i >> 1) * CH_STRIDE + CH_U + (i & 1) * UPLANE, P.xnT + 4 * c * 256 + i * 128, 2048, bars + 8 * B_U);
                } else exit_count(P.flags);
                #pragma unroll 1
                for (int V = 0; V < 2; V++) {
                    mbar_wait(bars + 8 * (B_EPI + V), 0);
                    STAMP2(3 + 2 * V);
                    asm volatile("cp.async.bulk.tensor.3d.global.shared::cta.bulk_group [%0, {%2, %3, %4}], [%1];"
                        :: "l"(&M.hst[V]), "r"(sb + OFF_X + V * 2 * XBUF), "r"(0), "r"(43 * tg + 21 * V), "r"(8 * fb) : "memory");
                    flag_signal(P.flags, F_H + 2 * tg + V);
                    mbar_arrive(bars + 8 * (B_STG + V));
                    STAMP2(4 + 2 * V);
                }
                if (c < 128) {
                    #pragma unroll 1
                    for (int V = 0; V < 2; V++) {
                        mbar_wait(bars + 8 * (B_SIG + V), 0);
                        STAMP2(7 + 2 * V);
                        bulk_store(P.S + (2 * c + V) * 1024, sb + OFF_CONV + V * 58368, 8192);
                        flag_signal(P.flags, F_S + (c >> 5));
                        STAMP2(8 + 2 * V);
                    }
                    mbar_arrive(bars + 8 * B_SST);
                }
            }
        }
    }
    asm volatile("nanosleep.u32 0;");
}

typedef CUresult (*EncodeFn)(CUtensorMap*, CUtensorMapDataType, cuuint32_t, void*, const cuuint64_t*, const cuuint64_t*, const cuuint32_t*,
                             const cuuint32_t*, CUtensorMapInterleave, CUtensorMapSwizzle, CUtensorMapL2promotion, CUtensorMapFloatOOBfill);

void make_map(EncodeFn enc, CUtensorMap* m, const void* ptr, int rank, const cuuint64_t* dims, const cuuint64_t* strides, const cuuint32_t* box, bool swz) {
    const cuuint32_t es[5] = {1, 1, 1, 1, 1};
    enc(m, CU_TENSOR_MAP_DATA_TYPE_BFLOAT16, rank, (void*)ptr, dims, strides, box, es, CU_TENSOR_MAP_INTERLEAVE_NONE,
        swz ? CU_TENSOR_MAP_SWIZZLE_128B : CU_TENSOR_MAP_SWIZZLE_NONE, CU_TENSOR_MAP_L2_PROMOTION_L2_128B, CU_TENSOR_MAP_FLOAT_OOB_FILL_NONE);
}
void make_map2(EncodeFn enc, CUtensorMap* m, const void* ptr, cuuint64_t inner, cuuint64_t outer, cuuint32_t rows) {
    const cuuint64_t dims[2] = {inner, outer}, strides[1] = {inner * 2};
    const cuuint32_t box[2] = {64, rows};
    make_map(enc, m, ptr, 2, dims, strides, box, true);
}

}

extern "C" void kernel_launch(void* const* d_in, const int* in_sizes, int n_in, void* d_out, int out_size) {
    (void)in_sizes; (void)n_in; (void)out_size;
    static EncodeFn enc = nullptr;
    static void *hptr, *p_xnT, *p_st, *p_S, *p_flags;
    if (!enc) {
        cudaDriverEntryPointQueryResult qr;
        cudaGetDriverEntryPoint("cuTensorMapEncodeTiled", (void**)&enc, cudaEnableDefault, &qr);
        cudaFuncSetAttribute(fused_kernel, cudaFuncAttributeMaxDynamicSharedMemorySize, SMEM_BYTES);
        cudaGetSymbolAddress(&hptr, g_H); cudaGetSymbolAddress(&p_xnT, g_xnT); cudaGetSymbolAddress(&p_st, g_st);
        cudaGetSymbolAddress(&p_S, g_S); cudaGetSymbolAddress(&p_flags, g_flags);
    }
    Params P;
    P.x = (const __nv_bfloat16*)d_in[0]; P.logA = (const __nv_bfloat16*)d_in[1]; P.Aim = (const __nv_bfloat16*)d_in[2];
    P.Cr = (const __nv_bfloat16*)d_in[3]; P.Ci = (const __nv_bfloat16*)d_in[4]; P.logdt = (const __nv_bfloat16*)d_in[5];
    P.Dskip = (const __nv_bfloat16*)d_in[6];
    P.Wd = (const __nv_bfloat16*)d_in[10]; P.xnT = (uint4*)p_xnT; P.st = (float2*)p_st; P.S = (uint2*)p_S; P.flags = (unsigned*)p_flags;
    Maps M;
    make_map2(enc, &M.x[0], d_in[0], DM, SEQ, 168); make_map2(enc, &M.x[1], d_in[0], DM, SEQ, 176);
    make_map2(enc, &M.xo, d_in[0], DM, SEQ, 64);    make_map2(enc, &M.out, d_out, DM, SEQ, 64);
    make_map2(enc, &M.wg, d_in[8], FF, DM, 64);     make_map2(enc, &M.wu, d_in[9], FF, DM, 64);
    make_map2(enc, &M.wd, d_in[10], DM, FF, 64);
    for (int v = 0; v < 2; v++) {
        const cuuint64_t dims[3] = {64, 256, 172}, strides[2] = {128, 32768};
        const cuuint32_t box[3] = {64, (cuuint32_t)(21 + v), 8};
        make_map(enc, &M.hst[v], hptr, 3, dims, strides, box, false);
    }
    {
        const cuuint64_t dims[2] = {2048, 512}, strides[1] = {4096};
        const cuuint32_t box[2] = {16, 256};
        make_map(enc, &M.xt, p_xnT, 2, dims, strides, box, false);
    }
    {
        const cuuint64_t dims[5] = {64, 2, 4, 32, 64}, strides[4] = {4 * 8192, 8192, 8 * 8192, 128};
        const cuuint32_t box[5] = {64, 2, 4, 8, 2};
        make_map(enc, &M.sld, p_S, 5, dims, strides, box, true);
    }
    {
        const cuuint64_t dims[5] = {64, 2, 2, 64, 172}, strides[4] = {256, 128, 512, 32768};
        const cuuint32_t box[5] = {64, 2, 2, 2, 8};
        make_map(enc, &M.hld, hptr, 5, dims, strides, box, false);
    }
    fused_kernel<<<NCTA, 512, SMEM_BYTES>>>(P, M);
}
```

```cpp
#include <cuda_runtime.h>
#include <cuda_bf16.h>
#include <cuda.h>
#include <stdint.h>

#define PROF 0

namespace {

constexpr int SEQ = 2048, DM = 512, FF = 1376;
constexpr int NCTA = 132;
#define HOLD0 4
#define HOLD1 7
#define LAG 2
constexpr int TOKG = 344;

constexpr uint32_t OFF_W = 0;
constexpr uint32_t XBUF = 22528;
constexpr uint32_t OFF_X = 65536;
constexpr uint32_t OFF_CONV = 155648;
constexpr uint32_t CH_STRIDE = 16640;
constexpr uint32_t CH_T = 0;
constexpr uint32_t CH_A3 = 6272;
constexpr uint32_t CH_B3 = 10368;
constexpr uint32_t CH_U = 12416;
constexpr uint32_t CH_G = CH_A3 + 2064;
constexpr uint32_t UPLANE = 2112;
constexpr uint32_t OFF_LN = OFF_X + 3 * XBUF;
constexpr uint32_t OFF_ST = 222208;
constexpr uint32_t OFF_CSUM = 230400;
constexpr uint32_t OFF_BAR = 231168;
constexpr uint32_t SMEM_BYTES = 231680;

enum {
    B_FULLW = 0, B_EMPTYW = 4, B_FULLX = 8, B_EMPTYX = 12, B_FULLD = 16, B_EMPTYD = 24,
    B_U = 32, B_XO = 33, B_S = 34, B_STG = 35, B_HF = 37, B_STATS = 38, B_LNS = 39, B_SST = 40,
    B_LNX = 41, B_GO = 42, B_CH0 = 43, B_K = 44,
    B_CONV = 46, B_LN = 50, B_CS = 51, B_EPI = 52, B_SIG = 54,
    B_COUNT = 56
};
enum { F_A = 0, F_H = 1, F_S = 13, F_EXIT = 17, F_COUNT = 18 };

__device__ uint4 g_xnT[DM * 256];
__device__ float2 g_st[6 * TOKG];
__device__ uint4 g_H[172 * 256 * 8];
__device__ uint2 g_S[256 * 1024];
__device__ unsigned g_flags[F_COUNT * 32];
#define STAMP(i) do {} while (0)
#define GSTAMP(i) do {} while (0)
#define STAMP2(i) do {} while (0)

__device__ __forceinline__ uint32_t smem_u32(const void* p) { return (uint32_t)__cvta_generic_to_shared(p); }
__device__ __forceinline__ void mbar_expect(uint32_t bar, uint32_t bytes) { asm volatile("mbarrier.arrive.expect_tx.shared::cta.b64 _, [%0], %1;" :: "r"(bar), "r"(bytes) : "memory"); }
__device__ __forceinline__ void mbar_arrive(uint32_t bar) { asm volatile("mbarrier.arrive.shared::cta.b64 _, [%0];" :: "r"(bar) : "memory"); }
__device__ __forceinline__ void mbar_wait(uint32_t bar, uint32_t parity) {
    asm volatile("{.reg .pred p; .reg .u32 n; mov.u32 n, 0x20000;\n"
                 "LW: mbarrier.try_wait.parity.shared::cta.b64 p, [%0], %1;\n"
                 "sub.u32 n, n, 1; setp.eq.or.u32 p, n, 0, p; @!p bra LW;}" :: "r"(bar), "r"(parity) : "memory");
}
__device__ __forceinline__ bool elect_one() { uint32_t p; asm volatile("{.reg .pred P; elect.sync _|P, 0xffffffff; selp.u32 %0, 1, 0, P;}" : "=r"(p)); return p; }
__device__ __forceinline__ void tma2d(uint32_t dst, const CUtensorMap* m, int c0, int c1, uint32_t bar) {
    asm volatile("cp.async.bulk.tensor.2d.shared::cluster.global.mbarrier::complete_tx::bytes [%0], [%1, {%3, %4}], [%2];"
        :: "r"(dst), "l"(m), "r"(bar), "r"(c0), "r"(c1) : "memory");
}
__device__ __forceinline__ void bulk_load(uint32_t dst, const void* src, uint32_t bytes, uint32_t bar) {
    asm volatile("cp.async.bulk.shared::cluster.global.mbarrier::complete_tx::bytes [%0], [%1], %2, [%3];" :: "r"(dst), "l"(src), "r"(bytes), "r"(bar) : "memory");
}
__device__ __forceinline__ void bulk_store(void* dst, uint32_t src, uint32_t bytes) {
    asm volatile("cp.async.bulk.global.shared::cta.bulk_group [%0], [%1], %2;" :: "l"(dst), "r"(src), "r"(bytes) : "memory");
}
__device__ __forceinline__ void fence_async_smem() { asm volatile("fence.proxy.async.shared::cta;" ::: "memory"); }
__device__ __forceinline__ void flag_wait(unsigned* g_flags, int f, unsigned target) {
    asm volatile("{.reg .pred p; .reg .u32 n, v; mov.u32 n, 0x40000;\n"
                 "LF: ld.acquire.gpu.global.u32 v, [%0]; setp.ge.u32 p, v, %1; @p bra LD;\n"
                 "sub.u32 n, n, 1; setp.ne.u32 p, n, 0; @p bra LF; trap;\nLD: }"
                 :: "l"(g_flags + f * 32), "r"(target) : "memory");
}
__device__ __forceinline__ void flag_signal(unsigned* g_flags, int f) {
    asm volatile("cp.async.bulk.commit_group; cp.async.bulk.wait_group 0; red.relaxed.gpu.global.add.u32 [%0], 1;" :: "l"(g_flags + f * 32) : "memory");
}
__device__ __forceinline__ void exit_count(unsigned* g_flags) {
    if (atomicAdd(g_flags + F_EXIT * 32, 1u) == NCTA - 1) {
        #pragma unroll 1
        for (int i = 0; i < F_COUNT; i++) g_flags[i * 32] = 0;
    }
}
__device__ __forceinline__ void bar_sync(int id) { asm volatile("bar.sync %0, 128;" :: "r"(id) : "memory"); }
__device__ __forceinline__ uint64_t mkdesc(uint32_t addr, uint32_t lbo, uint32_t sbo, uint32_t swz) {
    return (uint64_t)((addr >> 4) | ((lbo >> 4) << 16)) | ((uint64_t)((sbo >> 4) | (swz << 30)) << 32);
}
#define WG_FENCE() asm volatile("wgmma.fence.sync.aligned;" ::: "memory")
#define WG_COMMIT() asm volatile("wgmma.commit_group.sync.aligned;" ::: "memory")
#define WG_WAIT(n) asm volatile("wgmma.wait_group.sync.aligned " #n ";" ::: "memory")
template <int N> __device__ __forceinline__ void fence_acc(float (&d)[N]) {
    #pragma unroll
    for (int i = 0; i < N; i++) asm volatile("" : "+f"(d[i]) :: "memory");
}
template <int N> __device__ __forceinline__ void define_acc(float (&d)[N]) {
    #pragma unroll
    for (int i = 0; i < N; i++) asm volatile("" : "=f"(d[i]));
}
__device__ __forceinline__ uint32_t pack2(float lo, float hi) { uint32_t r; asm("cvt.rn.bf16x2.f32 %0, %1, %2;" : "=r"(r) : "f"(hi), "f"(lo)); return r; }
__device__ __forceinline__ float bf_lo(uint32_t v) { return __uint_as_float(v << 16); }
__device__ __forceinline__ float bf_hi(uint32_t v) { return __uint_as_float(v & 0xffff0000u); }
__device__ __forceinline__ float bf_round(float v) { return bf_hi(pack2(0.f, v)); }
__device__ __forceinline__ float tanh_fast(float v) { float r; asm("tanh.approx.f32 %0, %1;" : "=f"(r) : "f"(v)); return r; }
__device__ __forceinline__ float ex2(float v) { float r; asm("ex2.approx.ftz.f32 %0, %1;" : "=f"(r) : "f"(v)); return r; }
__device__ __forceinline__ uint4 lds128(uint32_t a) { uint4 v; asm volatile("ld.shared.v4.b32 {%0,%1,%2,%3}, [%4];" : "=r"(v.x), "=r"(v.y), "=r"(v.z), "=r"(v.w) : "r"(a)); return v; }
__device__ __forceinline__ uint2 lds64(uint32_t a) { uint2 v; asm volatile("ld.shared.v2.b32 {%0,%1}, [%2];" : "=r"(v.x), "=r"(v.y) : "r"(a)); return v; }
__device__ __forceinline__ float ldsf(uint32_t a) { float v; asm volatile("ld.shared.f32 %0, [%1];" : "=f"(v) : "r"(a)); return v; }
__device__ __forceinline__ void sts128(uint32_t a, uint32_t x, uint32_t y, uint32_t z, uint32_t w) { asm volatile("st.shared.v4.b32 [%0], {%1,%2,%3,%4};" :: "r"(a), "r"(x), "r"(y), "r"(z), "r"(w) : "memory"); }
__device__ __forceinline__ void sts64(uint32_t a, uint32_t x, uint32_t y) { asm volatile("st.shared.v2.b32 [%0], {%1,%2};" :: "r"(a), "r"(x), "r"(y) : "memory"); }
__device__ __forceinline__ void stsf(uint32_t a, float x) { asm volatile("st.shared.f32 [%0], %1;" :: "r"(a), "f"(x) : "memory"); }
__device__ __forceinline__ void sts16(uint32_t a, uint32_t x) { asm volatile("st.shared.b16 [%0], %1;" :: "r"(a), "h"((unsigned short)x) : "memory"); }
__device__ __forceinline__ void stsm4(uint32_t a, uint32_t r0, uint32_t r1, uint32_t r2, uint32_t r3) {
    asm volatile("stmatrix.sync.aligned.m8n8.x4.shared.b16 [%0], {%1,%2,%3,%4};" :: "r"(a), "r"(r0), "r"(r1), "r"(r2), "r"(r3) : "memory");
}
__device__ __forceinline__ void ldsm4(uint32_t (&r)[4], uint32_t a) {
    asm volatile("ldmatrix.sync.aligned.m8n8.x4.shared.b16 {%0,%1,%2,%3}, [%4];" : "=r"(r[0]), "=r"(r[1]), "=r"(r[2]), "=r"(r[3]) : "r"(a) : "memory");
}
#define FU(x) __float_as_uint(x)
#define UF(x) __uint_as_float(x)
__device__ __forceinline__ uint32_t wd_slot(int s) { return (uint32_t)((0xb9a8403056201000ull >> (8 * s)) & 0xff) << 10; }
__device__ __forceinline__ uint32_t h_slot(int s) { return (uint32_t)((0xc9a0d98c847c746cull >> (8 * s)) & 0xff) << 10; }

template<int N> __device__ __forceinline__ void wg_rs(float (&d)[64], uint32_t a0, uint32_t a1, uint32_t a2, uint32_t a3, uint64_t db);
template<> __device__ __forceinline__ void wg_rs<128>(float (&d)[64], uint32_t a0, uint32_t a1, uint32_t a2, uint32_t a3, uint64_t db) {
  asm volatile("{.reg .pred p; setp.ne.b32 p, 1, 0; wgmma.mma_async.sync.aligned.m64n128k16.f32.bf16.bf16 {%0,%1,%2,%3,%4,%5,%6,%7,%8,%9,%10,%11,%12,%13,%14,%15,%16,%17,%18,%19,%20,%21,%22,%23,%24,%25,%26,%27,%28,%29,%30,%31,%32,%33,%34,%35,%36,%37,%38,%39,%40,%41,%42,%43,%44,%45,%46,%47,%48,%49,%50,%51,%52,%53,%54,%55,%56,%57,%58,%59,%60,%61,%62,%63}, {%64,%65,%66,%67}, %68, p, 1, 1, 0;}"
    : "+f"(d[0]),"+f"(d[1]),"+f"(d[2]),"+f"(d[3]),"+f"(d[4]),"+f"(d[5]),"+f"(d[6]),"+f"(d[7]),"+f"(d[8]),"+f"(d[9]),"+f"(d[10]),"+f"(d[11]),"+f"(d[12]),"+f"(d[13]),"+f"(d[14]),"+f"(d[15]),"+f"(d[16]),"+f"(d[17]),"+f"(d[18]),"+f"(d[19]),"+f"(d[20]),"+f"(d[21]),"+f"(d[22]),"+f"(d[23]),"+f"(d[24]),"+f"(d[25]),"+f"(d[26]),"+f"(d[27]),"+f"(d[28]),"+f"(d[29]),"+f"(d[30]),"+f"(d[31]),"+f"(d[32]),"+f"(d[33]),"+f"(d[34]),"+f"(d[35]),"+f"(d[36]),"+f"(d[37]),"+f"(d[38]),"+f"(d[39]),"+f"(d[40]),"+f"(d[41]),"+f"(d[42]),"+f"(d[43]),"+f"(d[44]),"+f"(d[45]),"+f"(d[46]),"+f"(d[47]),"+f"(d[48]),"+f"(d[49]),"+f"(d[50]),"+f"(d[51]),"+f"(d[52]),"+f"(d[53]),"+f"(d[54]),"+f"(d[55]),"+f"(d[56]),"+f"(d[57]),"+f"(d[58]),"+f"(d[59]),"+f"(d[60]),"+f"(d[61]),"+f"(d[62]),"+f"(d[63]) : "r"(a0), "r"(a1), "r"(a2), "r"(a3), "l"(db));
}
template<> __device__ __forceinline__ void wg_rs<120>(float (&d)[64], uint32_t a0, uint32_t a1, uint32_t a2, uint32_t a3, uint64_t db) {
  asm volatile("{.reg .pred p; setp.ne.b32 p, 1, 0; wgmma.mma_async.sync.aligned.m64n120k16.f32.bf16.bf16 {%0,%1,%2,%3,%4,%5,%6,%7,%8,%9,%10,%11,%12,%13,%14,%15,%16,%17,%18,%19,%20,%21,%22,%23,%24,%25,%26,%27,%28,%29,%30,%31,%32,%33,%34,%35,%36,%37,%38,%39,%40,%41,%42,%43,%44,%45,%46,%47,%48,%49,%50,%51,%52,%53,%54,%55,%56,%57,%58,%59}, {%60,%61,%62,%63}, %64, p, 1, 1, 0;}"
    : "+f"(d[0]),"+f"(d[1]),"+f"(d[2]),"+f"(d[3]),"+f"(d[4]),"+f"(d[5]),"+f"(d[6]),"+f"(d[7]),"+f"(d[8]),"+f"(d[9]),"+f"(d[10]),"+f"(d[11]),"+f"(d[12]),"+f"(d[13]),"+f"(d[14]),"+f"(d[15]),"+f"(d[16]),"+f"(d[17]),"+f"(d[18]),"+f"(d[19]),"+f"(d[20]),"+f"(d[21]),"+f"(d[22]),"+f"(d[23]),"+f"(d[24]),"+f"(d[25]),"+f"(d[26]),"+f"(d[27]),"+f"(d[28]),"+f"(d[29]),"+f"(d[30]),"+f"(d[31]),"+f"(d[32]),"+f"(d[33]),"+f"(d[34]),"+f"(d[35]),"+f"(d[36]),"+f"(d[37]),"+f"(d[38]),"+f"(d[39]),"+f"(d[40]),"+f"(d[41]),"+f"(d[42]),"+f"(d[43]),"+f"(d[44]),"+f"(d[45]),"+f"(d[46]),"+f"(d[47]),"+f"(d[48]),"+f"(d[49]),"+f"(d[50]),"+f"(d[51]),"+f"(d[52]),"+f"(d[53]),"+f"(d[54]),"+f"(d[55]),"+f"(d[56]),"+f"(d[57]),"+f"(d[58]),"+f"(d[59]) : "r"(a0), "r"(a1), "r"(a2), "r"(a3), "l"(db));
}
template<> __device__ __forceinline__ void wg_rs<112>(float (&d)[64], uint32_t a0, uint32_t a1, uint32_t a2, uint32_t a3, uint64_t db) {
  asm volatile("{.reg .pred p; setp.ne.b32 p, 1, 0; wgmma.mma_async.sync.aligned.m64n112k16.f32.bf16.bf16 {%0,%1,%2,%3,%4,%5,%6,%7,%8,%9,%10,%11,%12,%13,%14,%15,%16,%17,%18,%19,%20,%21,%22,%23,%24,%25,%26,%27,%28,%29,%30,%31,%32,%33,%34,%35,%36,%37,%38,%39,%40,%41,%42,%43,%44,%45,%46,%47,%48,%49,%50,%51,%52,%53,%54,%55}, {%56,%57,%58,%59}, %60, p, 1, 1, 0;}"
    : "+f"(d[0]),"+f"(d[1]),"+f"(d[2]),"+f"(d[3]),"+f"(d[4]),"+f"(d[5]),"+f"(d[6]),"+f"(d[7]),"+f"(d[8]),"+f"(d[9]),"+f"(d[10]),"+f"(d[11]),"+f"(d[12]),"+f"(d[13]),"+f"(d[14]),"+f"(d[15]),"+f"(d[16]),"+f"(d[17]),"+f"(d[18]),"+f"(d[19]),"+f"(d[20]),"+f"(d[21]),"+f"(d[22]),"+f"(d[23]),"+f"(d[24]),"+f"(d[25]),"+f"(d[26]),"+f"(d[27]),"+f"(d[28]),"+f"(d[29]),"+f"(d[30]),"+f"(d[31]),"+f"(d[32]),"+f"(d[33]),"+f"(d[34]),"+f"(d[35]),"+f"(d[36]),"+f"(d[37]),"+f"(d[38]),"+f"(d[39]),"+f"(d[40]),"+f"(d[41]),"+f"(d[42]),"+f"(d[43]),"+f"(d[44]),"+f"(d[45]),"+f"(d[46]),"+f"(d[47]),"+f"(d[48]),"+f"(d[49]),"+f"(d[50]),"+f"(d[51]),"+f"(d[52]),"+f"(d[53]),"+f"(d[54]),"+f"(d[55]) : "r"(a0), "r"(a1), "r"(a2), "r"(a3), "l"(db));
}
template<> __device__ __forceinline__ void wg_rs<104>(float (&d)[64], uint32_t a0, uint32_t a1, uint32_t a2, uint32_t a3, uint64_t db) {
  asm volatile("{.reg .pred p; setp.ne.b32 p, 1, 0; wgmma.mma_async.sync.aligned.m64n104k16.f32.bf16.bf16 {%0,%1,%2,%3,%4,%5,%6,%7,%8,%9,%10,%11,%12,%13,%14,%15,%16,%17,%18,%19,%20,%21,%22,%23,%24,%25,%26,%27,%28,%29,%30,%31,%32,%33,%34,%35,%36,%37,%38,%39,%40,%41,%42,%43,%44,%45,%46,%47,%48,%49,%50,%51}, {%52,%53,%54,%55}, %56, p, 1, 1, 0;}"
    : "+f"(d[0]),"+f"(d[1]),"+f"(d[2]),"+f"(d[3]),"+f"(d[4]),"+f"(d[5]),"+f"(d[6]),"+f"(d[7]),"+f"(d[8]),"+f"(d[9]),"+f"(d[10]),"+f"(d[11]),"+f"(d[12]),"+f"(d[13]),"+f"(d[14]),"+f"(d[15]),"+f"(d[16]),"+f"(d[17]),"+f"(d[18]),"+f"(d[19]),"+f"(d[20]),"+f"(d[21]),"+f"(d[22]),"+f"(d[23]),"+f"(d[24]),"+f"(d[25]),"+f"(d[26]),"+f"(d[27]),"+f"(d[28]),"+f"(d[29]),"+f"(d[30]),"+f"(d[31]),"+f"(d[32]),"+f"(d[33]),"+f"(d[34]),"+f"(d[35]),"+f"(d[36]),"+f"(d[37]),"+f"(d[38]),"+f"(d[39]),"+f"(d[40]),"+f"(d[41]),"+f"(d[42]),"+f"(d[43]),"+f"(d[44]),"+f"(d[45]),"+f"(d[46]),"+f"(d[47]),"+f"(d[48]),"+f"(d[49]),"+f"(d[50]),"+f"(d[51]) : "r"(a0), "r"(a1), "r"(a2), "r"(a3), "l"(db));
}
template<> __device__ __forceinline__ void wg_rs<96>(float (&d)[64], uint32_t a0, uint32_t a1, uint32_t a2, uint32_t a3, uint64_t db) {
  asm volatile("{.reg .pred p; setp.ne.b32 p, 1, 0; wgmma.mma_async.sync.aligned.m64n96k16.f32.bf16.bf16 {%0,%1,%2,%3,%4,%5,%6,%7,%8,%9,%10,%11,%12,%13,%14,%15,%16,%17,%18,%19,%20,%21,%22,%23,%24,%25,%26,%27,%28,%29,%30,%31,%32,%33,%34,%35,%36,%37,%38,%39,%40,%41,%42,%43,%44,%45,%46,%47}, {%48,%49,%50,%51}, %52, p, 1, 1, 0;}"
    : "+f"(d[0]),"+f"(d[1]),"+f"(d[2]),"+f"(d[3]),"+f"(d[4]),"+f"(d[5]),"+f"(d[6]),"+f"(d[7]),"+f"(d[8]),"+f"(d[9]),"+f"(d[10]),"+f"(d[11]),"+f"(d[12]),"+f"(d[13]),"+f"(d[14]),"+f"(d[15]),"+f"(d[16]),"+f"(d[17]),"+f"(d[18]),"+f"(d[19]),"+f"(d[20]),"+f"(d[21]),"+f"(d[22]),"+f"(d[23]),"+f"(d[24]),"+f"(d[25]),"+f"(d[26]),"+f"(d[27]),"+f"(d[28]),"+f"(d[29]),"+f"(d[30]),"+f"(d[31]),"+f"(d[32]),"+f"(d[33]),"+f"(d[34]),"+f"(d[35]),"+f"(d[36]),"+f"(d[37]),"+f"(d[38]),"+f"(d[39]),"+f"(d[40]),"+f"(d[41]),"+f"(d[42]),"+f"(d[43]),"+f"(d[44]),"+f"(d[45]),"+f"(d[46]),"+f"(d[47]) : "r"(a0), "r"(a1), "r"(a2), "r"(a3), "l"(db));
}
template<> __device__ __forceinline__ void wg_rs<88>(float (&d)[64], uint32_t a0, uint32_t a1, uint32_t a2, uint32_t a3, uint64_t db) {
  asm volatile("{.reg .pred p; setp.ne.b32 p, 1, 0; wgmma.mma_async.sync.aligned.m64n88k16.f32.bf16.bf16 {%0,%1,%2,%3,%4,%5,%6,%7,%8,%9,%10,%11,%12,%13,%14,%15,%16,%17,%18,%19,%20,%21,%22,%23,%24,%25,%26,%27,%28,%29,%30,%31,%32,%33,%34,%35,%36,%37,%38,%39,%40,%41,%42,%43}, {%44,%45,%46,%47}, %48, p, 1, 1, 0;}"
    : "+f"(d[0]),"+f"(d[1]),"+f"(d[2]),"+f"(d[3]),"+f"(d[4]),"+f"(d[5]),"+f"(d[6]),"+f"(d[7]),"+f"(d[8]),"+f"(d[9]),"+f"(d[10]),"+f"(d[11]),"+f"(d[12]),"+f"(d[13]),"+f"(d[14]),"+f"(d[15]),"+f"(d[16]),"+f"(d[17]),"+f"(d[18]),"+f"(d[19]),"+f"(d[20]),"+f"(d[21]),"+f"(d[22]),"+f"(d[23]),"+f"(d[24]),"+f"(d[25]),"+f"(d[26]),"+f"(d[27]),"+f"(d[28]),"+f"(d[29]),"+f"(d[30]),"+f"(d[31]),"+f"(d[32]),"+f"(d[33]),"+f"(d[34]),"+f"(d[35]),"+f"(d[36]),"+f"(d[37]),"+f"(d[38]),"+f"(d[39]),"+f"(d[40]),"+f"(d[41]),"+f"(d[42]),"+f"(d[43]) : "r"(a0), "r"(a1), "r"(a2), "r"(a3), "l"(db));
}
template<> __device__ __forceinline__ void wg_rs<80>(float (&d)[64], uint32_t a0, uint32_t a1, uint32_t a2, uint32_t a3, uint64_t db) {
  asm volatile("{.reg .pred p; setp.ne.b32 p, 1, 0; wgmma.mma_async.sync.aligned.m64n80k16.f32.bf16.bf16 {%0,%1,%2,%3,%4,%5,%6,%7,%8,%9,%10,%11,%12,%13,%14,%15,%16,%17,%18,%19,%20,%21,%22,%23,%24,%25,%26,%27,%28,%29,%30,%31,%32,%33,%34,%35,%36,%37,%38,%39}, {%40,%41,%42,%43}, %44, p, 1, 1, 0;}"
    : "+f"(d[0]),"+f"(d[1]),"+f"(d[2]),"+f"(d[3]),"+f"(d[4]),"+f"(d[5]),"+f"(d[6]),"+f"(d[7]),"+f"(d[8]),"+f"(d[9]),"+f"(d[10]),"+f"(d[11]),"+f"(d[12]),"+f"(d[13]),"+f"(d[14]),"+f"(d[15]),"+f"(d[16]),"+f"(d[17]),"+f"(d[18]),"+f"(d[19]),"+f"(d[20]),"+f"(d[21]),"+f"(d[22]),"+f"(d[23]),"+f"(d[24]),"+f"(d[25]),"+f"(d[26]),"+f"(d[27]),"+f"(d[28]),"+f"(d[29]),"+f"(d[30]),"+f"(d[31]),"+f"(d[32]),"+f"(d[33]),"+f"(d[34]),"+f"(d[35]),"+f"(d[36]),"+f"(d[37]),"+f"(d[38]),"+f"(d[39]) : "r"(a0), "r"(a1), "r"(a2), "r"(a3), "l"(db));
}
template<> __device__ __forceinline__ void wg_rs<72>(float (&d)[64], uint32_t a0, uint32_t a1, uint32_t a2, uint32_t a3, uint64_t db) {
  asm volatile("{.reg .pred p; setp.ne.b32 p, 1, 0; wgmma.mma_async.sync.aligned.m64n72k16.f32.bf16.bf16 {%0,%1,%2,%3,%4,%5,%6,%7,%8,%9,%10,%11,%12,%13,%14,%15,%16,%17,%18,%19,%20,%21,%22,%23,%24,%25,%26,%27,%28,%29,%30,%31,%32,%33,%34,%35}, {%36,%37,%38,%39}, %40, p, 1, 1, 0;}"
    : "+f"(d[0]),"+f"(d[1]),"+f"(d[2]),"+f"(d[3]),"+f"(d[4]),"+f"(d[5]),"+f"(d[6]),"+f"(d[7]),"+f"(d[8]),"+f"(d[9]),"+f"(d[10]),"+f"(d[11]),"+f"(d[12]),"+f"(d[13]),"+f"(d[14]),"+f"(d[15]),"+f"(d[16]),"+f"(d[17]),"+f"(d[18]),"+f"(d[19]),"+f"(d[20]),"+f"(d[21]),"+f"(d[22]),"+f"(d[23]),"+f"(d[24]),"+f"(d[25]),"+f"(d[26]),"+f"(d[27]),"+f"(d[28]),"+f"(d[29]),"+f"(d[30]),"+f"(d[31]),"+f"(d[32]),"+f"(d[33]),"+f"(d[34]),"+f"(d[35]) : "r"(a0), "r"(a1), "r"(a2), "r"(a3), "l"(db));
}
template<> __device__ __forceinline__ void wg_rs<64>(float (&d)[64], uint32_t a0, uint32_t a1, uint32_t a2, uint32_t a3, uint64_t db) {
  asm volatile("{.reg .pred p; setp.ne.b32 p, 1, 0; wgmma.mma_async.sync.aligned.m64n64k16.f32.bf16.bf16 {%0,%1,%2,%3,%4,%5,%6,%7,%8,%9,%10,%11,%12,%13,%14,%15,%16,%17,%18,%19,%20,%21,%22,%23,%24,%25,%26,%27,%28,%29,%30,%31}, {%32,%33,%34,%35}, %36, p, 1, 1, 0;}"
    : "+f"(d[0]),"+f"(d[1]),"+f"(d[2]),"+f"(d[3]),"+f"(d[4]),"+f"(d[5]),"+f"(d[6]),"+f"(d[7]),"+f"(d[8]),"+f"(d[9]),"+f"(d[10]),"+f"(d[11]),"+f"(d[12]),"+f"(d[13]),"+f"(d[14]),"+f"(d[15]),"+f"(d[16]),"+f"(d[17]),"+f"(d[18]),"+f"(d[19]),"+f"(d[20]),"+f"(d[21]),"+f"(d[22]),"+f"(d[23]),"+f"(d[24]),"+f"(d[25]),"+f"(d[26]),"+f"(d[27]),"+f"(d[28]),"+f"(d[29]),"+f"(d[30]),"+f"(d[31]) : "r"(a0), "r"(a1), "r"(a2), "r"(a3), "l"(db));
}
__device__ __forceinline__ void wg_rs_first(float (&d)[64], uint32_t a0, uint32_t a1, uint32_t a2, uint32_t a3, uint64_t db) {
  asm volatile("{.reg .pred p; setp.ne.b32 p, 0, 0; wgmma.mma_async.sync.aligned.m64n128k16.f32.bf16.bf16 {%0,%1,%2,%3,%4,%5,%6,%7,%8,%9,%10,%11,%12,%13,%14,%15,%16,%17,%18,%19,%20,%21,%22,%23,%24,%25,%26,%27,%28,%29,%30,%31,%32,%33,%34,%35,%36,%37,%38,%39,%40,%41,%42,%43,%44,%45,%46,%47,%48,%49,%50,%51,%52,%53,%54,%55,%56,%57,%58,%59,%60,%61,%62,%63}, {%64,%65,%66,%67}, %68, p, 1, 1, 0;}"
    : "=f"(d[0]),"=f"(d[1]),"=f"(d[2]),"=f"(d[3]),"=f"(d[4]),"=f"(d[5]),"=f"(d[6]),"=f"(d[7]),"=f"(d[8]),"=f"(d[9]),"=f"(d[10]),"=f"(d[11]),"=f"(d[12]),"=f"(d[13]),"=f"(d[14]),"=f"(d[15]),"=f"(d[16]),"=f"(d[17]),"=f"(d[18]),"=f"(d[19]),"=f"(d[20]),"=f"(d[21]),"=f"(d[22]),"=f"(d[23]),"=f"(d[24]),"=f"(d[25]),"=f"(d[26]),"=f"(d[27]),"=f"(d[28]),"=f"(d[29]),"=f"(d[30]),"=f"(d[31]),"=f"(d[32]),"=f"(d[33]),"=f"(d[34]),"=f"(d[35]),"=f"(d[36]),"=f"(d[37]),"=f"(d[38]),"=f"(d[39]),"=f"(d[40]),"=f"(d[41]),"=f"(d[42]),"=f"(d[43]),"=f"(d[44]),"=f"(d[45]),"=f"(d[46]),"=f"(d[47]),"=f"(d[48]),"=f"(d[49]),"=f"(d[50]),"=f"(d[51]),"=f"(d[52]),"=f"(d[53]),"=f"(d[54]),"=f"(d[55]),"=f"(d[56]),"=f"(d[57]),"=f"(d[58]),"=f"(d[59]),"=f"(d[60]),"=f"(d[61]),"=f"(d[62]),"=f"(d[63]) : "r"(a0), "r"(a1), "r"(a2), "r"(a3), "l"(db));
}
__device__ __forceinline__ void wg_tt128(float (&d)[64], uint64_t da, uint64_t db, int sc) {
  asm volatile("{.reg .pred p; setp.ne.b32 p, %66, 0; wgmma.mma_async.sync.aligned.m64n128k16.f32.bf16.bf16 {%0,%1,%2,%3,%4,%5,%6,%7,%8,%9,%10,%11,%12,%13,%14,%15,%16,%17,%18,%19,%20,%21,%22,%23,%24,%25,%26,%27,%28,%29,%30,%31,%32,%33,%34,%35,%36,%37,%38,%39,%40,%41,%42,%43,%44,%45,%46,%47,%48,%49,%50,%51,%52,%53,%54,%55,%56,%57,%58,%59,%60,%61,%62,%63}, %64, %65, p, 1, 1, 1, 1;}"
    : "+f"(d[0]),"+f"(d[1]),"+f"(d[2]),"+f"(d[3]),"+f"(d[4]),"+f"(d[5]),"+f"(d[6]),"+f"(d[7]),"+f"(d[8]),"+f"(d[9]),"+f"(d[10]),"+f"(d[11]),"+f"(d[12]),"+f"(d[13]),"+f"(d[14]),"+f"(d[15]),"+f"(d[16]),"+f"(d[17]),"+f"(d[18]),"+f"(d[19]),"+f"(d[20]),"+f"(d[21]),"+f"(d[22]),"+f"(d[23]),"+f"(d[24]),"+f"(d[25]),"+f"(d[26]),"+f"(d[27]),"+f"(d[28]),"+f"(d[29]),"+f"(d[30]),"+f"(d[31]),"+f"(d[32]),"+f"(d[33]),"+f"(d[34]),"+f"(d[35]),"+f"(d[36]),"+f"(d[37]),"+f"(d[38]),"+f"(d[39]),"+f"(d[40]),"+f"(d[41]),"+f"(d[42]),"+f"(d[43]),"+f"(d[44]),"+f"(d[45]),"+f"(d[46]),"+f"(d[47]),"+f"(d[48]),"+f"(d[49]),"+f"(d[50]),"+f"(d[51]),"+f"(d[52]),"+f"(d[53]),"+f"(d[54]),"+f"(d[55]),"+f"(d[56]),"+f"(d[57]),"+f"(d[58]),"+f"(d[59]),"+f"(d[60]),"+f"(d[61]),"+f"(d[62]),"+f"(d[63]) : "l"(da), "l"(db), "r"(sc));
}
__device__ __forceinline__ void wg_tt64(float (&d)[64], uint64_t da, uint64_t db, int sc) {
  asm volatile("{.reg .pred p; setp.ne.b32 p, %34, 0; wgmma.mma_async.sync.aligned.m64n64k16.f32.bf16.bf16 {%0,%1,%2,%3,%4,%5,%6,%7,%8,%9,%10,%11,%12,%13,%14,%15,%16,%17,%18,%19,%20,%21,%22,%23,%24,%25,%26,%27,%28,%29,%30,%31}, %32, %33, p, 1, 1, 1, 1;}"
    : "+f"(d[0]),"+f"(d[1]),"+f"(d[2]),"+f"(d[3]),"+f"(d[4]),"+f"(d[5]),"+f"(d[6]),"+f"(d[7]),"+f"(d[8]),"+f"(d[9]),"+f"(d[10]),"+f"(d[11]),"+f"(d[12]),"+f"(d[13]),"+f"(d[14]),"+f"(d[15]),"+f"(d[16]),"+f"(d[17]),"+f"(d[18]),"+f"(d[19]),"+f"(d[20]),"+f"(d[21]),"+f"(d[22]),"+f"(d[23]),"+f"(d[24]),"+f"(d[25]),"+f"(d[26]),"+f"(d[27]),"+f"(d[28]),"+f"(d[29]),"+f"(d[30]),"+f"(d[31]) : "l"(da), "l"(db), "r"(sc));
}
__device__ __forceinline__ void wg_tt32(float (&d)[64], uint64_t da, uint64_t db, int sc) {
  asm volatile("{.reg .pred p; setp.ne.b32 p, %18, 0; wgmma.mma_async.sync.aligned.m64n32k16.f32.bf16.bf16 {%0,%1,%2,%3,%4,%5,%6,%7,%8,%9,%10,%11,%12,%13,%14,%15}, %16, %17, p, 1, 1, 1, 1;}"
    : "+f"(d[0]),"+f"(d[1]),"+f"(d[2]),"+f"(d[3]),"+f"(d[4]),"+f"(d[5]),"+f"(d[6]),"+f"(d[7]),"+f"(d[8]),"+f"(d[9]),"+f"(d[10]),"+f"(d[11]),"+f"(d[12]),"+f"(d[13]),"+f"(d[14]),"+f"(d[15]) : "l"(da), "l"(db), "r"(sc));
}
__device__ __forceinline__ void wg_g1(float (&d)[88], uint64_t da, uint64_t db, int sc) {
  asm volatile("{.reg .pred p; setp.ne.b32 p, %90, 0; wgmma.mma_async.sync.aligned.m64n176k16.f32.bf16.bf16 {%0,%1,%2,%3,%4,%5,%6,%7,%8,%9,%10,%11,%12,%13,%14,%15,%16,%17,%18,%19,%20,%21,%22,%23,%24,%25,%26,%27,%28,%29,%30,%31,%32,%33,%34,%35,%36,%37,%38,%39,%40,%41,%42,%43,%44,%45,%46,%47,%48,%49,%50,%51,%52,%53,%54,%55,%56,%57,%58,%59,%60,%61,%62,%63,%64,%65,%66,%67,%68,%69,%70,%71,%72,%73,%74,%75,%76,%77,%78,%79,%80,%81,%82,%83,%84,%85,%86,%87}, %88, %89, p, 1, 1, 1, 0;}"
    : "+f"(d[0]),"+f"(d[1]),"+f"(d[2]),"+f"(d[3]),"+f"(d[4]),"+f"(d[5]),"+f"(d[6]),"+f"(d[7]),"+f"(d[8]),"+f"(d[9]),"+f"(d[10]),"+f"(d[11]),"+f"(d[12]),"+f"(d[13]),"+f"(d[14]),"+f"(d[15]),"+f"(d[16]),"+f"(d[17]),"+f"(d[18]),"+f"(d[19]),"+f"(d[20]),"+f"(d[21]),"+f"(d[22]),"+f"(d[23]),"+f"(d[24]),"+f"(d[25]),"+f"(d[26]),"+f"(d[27]),"+f"(d[28]),"+f"(d[29]),"+f"(d[30]),"+f"(d[31]),"+f"(d[32]),"+f"(d[33]),"+f"(d[34]),"+f"(d[35]),"+f"(d[36]),"+f"(d[37]),"+f"(d[38]),"+f"(d[39]),"+f"(d[40]),"+f"(d[41]),"+f"(d[42]),"+f"(d[43]),"+f"(d[44]),"+f"(d[45]),"+f"(d[46]),"+f"(d[47]),"+f"(d[48]),"+f"(d[49]),"+f"(d[50]),"+f"(d[51]),"+f"(d[52]),"+f"(d[53]),"+f"(d[54]),"+f"(d[55]),"+f"(d[56]),"+f"(d[57]),"+f"(d[58]),"+f"(d[59]),"+f"(d[60]),"+f"(d[61]),"+f"(d[62]),"+f"(d[63]),"+f"(d[64]),"+f"(d[65]),"+f"(d[66]),"+f"(d[67]),"+f"(d[68]),"+f"(d[69]),"+f"(d[70]),"+f"(d[71]),"+f"(d[72]),"+f"(d[73]),"+f"(d[74]),"+f"(d[75]),"+f"(d[76]),"+f"(d[77]),"+f"(d[78]),"+f"(d[79]),"+f"(d[80]),"+f"(d[81]),"+f"(d[82]),"+f"(d[83]),"+f"(d[84]),"+f"(d[85]),"+f"(d[86]),"+f"(d[87]) : "l"(da), "l"(db), "r"(sc));
}

struct Params { const __nv_bfloat16 *x, *logA, *Aim, *Cr, *Ci, *logdt, *Dskip, *Wd; uint4* xnT; float2* st; uint2* S; unsigned* flags; };
struct Maps { CUtensorMap x[2], xo, out, wg, wu, wd, hst[2], hld, xt, sld; };

__device__ __forceinline__ void conv_channel(uint32_t cb, int w, int lane, uint32_t (&res)[8]) {
    const int q = lane & 3, g = lane >> 2, gam = g >> 2;
    float acc[64];
    uint4 a[4][4];
    const uint32_t t0 = cb + CH_T + (uint32_t)(14 + 4 * w + (g & 3) + 32 * gam - 2 * q) * 80u;
    #pragma unroll
    for (int s4 = 0; s4 < 4; s4++) {
        a[s4][0] = lds128(t0 + s4 * 16);
        a[s4][1] = lds128(t0 + 16 * 80 + s4 * 16);
        a[s4][2] = lds128(t0 - 8 * 80 + s4 * 16);
        a[s4][3] = lds128(t0 + 8 * 80 + s4 * 16);
    }
    const uint32_t l0 = FU(ldsf(t0 + 64)), l1 = FU(ldsf(t0 + 16 * 80 + 64)), l2 = FU(ldsf(t0 - 8 * 80 + 64)), l3 = FU(ldsf(t0 + 8 * 80 + 64));
    const uint64_t dU = mkdesc(cb + CH_U, UPLANE, 128, 0);
    WG_FENCE();
#define CT(N, s, c) wg_rs<N>(acc, a[(s) >> 2][0].c, a[(s) >> 2][1].c, a[(s) >> 2][2].c, a[(s) >> 2][3].c, dU + 4 * (s))
    wg_rs_first(acc, a[0][0].x, a[0][1].x, a[0][2].x, a[0][3].x, dU);
    CT(128, 1, y); CT(120, 2, z); CT(120, 3, w);
    CT(112, 4, x); CT(112, 5, y); CT(104, 6, z); CT(104, 7, w);
    CT(96, 8, x);  CT(96, 9, y);  CT(88, 10, z); CT(88, 11, w);
    CT(80, 12, x); CT(80, 13, y); CT(72, 14, z); CT(72, 15, w);
#undef CT
    wg_rs<64>(acc, l0, l1, l2, l3, dU + 64);
    wg_tt64(acc, mkdesc(cb + CH_A3, 128, 512, 0), mkdesc(cb + CH_B3, 128, 256, 0), 1);
    wg_tt32(acc, mkdesc(cb + CH_A3 + 256, 128, 512, 0), mkdesc(cb + CH_B3 + 1024, 128, 256, 0), 1);
    WG_COMMIT();
    WG_WAIT(0);
    fence_acc(acc);
    const int src1 = (lane & ~3) | ((q + 1) & 3);
    float E[16][2];
    #pragma unroll
    for (int j = 0; j < 16; j++) {
        const float nxt = (j < 15) ? acc[4 * (j + 1) + 2] : 0.f;
        const float sup = (q == 0) ? nxt : acc[4 * j + 2];
        const float v = __shfl_sync(0xffffffffu, sup, src1);
        E[j][0] = acc[4 * j] + acc[4 * j + 3];
        E[j][1] = acc[4 * j + 1] + v;
    }
    const int src2 = gam ? ((lane & 12) | ((q + 3) & 3)) : (16 | (lane & 12) | ((q + 1) & 3));
    const bool c1 = gam && q != 0, c2 = gam && q == 0;
    #pragma unroll
    for (int a2 = 0; a2 < 8; a2++) {
        float y[2];
        #pragma unroll
        for (int e = 0; e < 2; e++) {
            const float sup = c1 ? E[2 * a2][e] : E[2 * a2 + 1][e];
            const float nxt = (a2 < 7) ? E[2 * a2 + 2][e] : 0.f;
            const float keep = c2 ? nxt : (c1 ? E[2 * a2 + 1][e] : E[2 * a2][e]);
            y[e] = keep + __shfl_sync(0xffffffffu, sup, src2);
        }
        res[a2] = pack2(y[1], y[0]);
    }
}

__device__ __forceinline__ void layer_norm(uint32_t sb, int w, int lane, const __nv_bfloat16* x) {
    const uint32_t bars = sb + OFF_BAR;
    const int c = blockIdx.x;
    {
        if (elect_one()) {
            mbar_expect(bars + 8 * B_LNX, 4096);
            #pragma unroll
            for (int i = 0; i < 4; i++)
                bulk_load(sb + OFF_LN + (w + 4 * i) * 1040, x + (16 * (c & ~1) + 8 * (c & 1) + 16 + w + 4 * (i & 1) - 8 * (i & 2)) * DM, 1024, bars + 8 * B_LNX);
        }
        mbar_wait(bars + 8 * B_LNX, 0);
        STAMP(34);
        {
            const int r = w + 4 * (lane >> 3);
            const uint32_t r0 = sb + OFF_LN + r * 1040, ra = r0 + (lane & 7) * 16;
            const float pv = bf_lo(FU(ldsf(r0)));
            float s0 = 0.f, s1 = 0.f, a0 = 0.f, a1 = 0.f;
            uint4 nx = lds128(ra), ny = lds128(ra + 128);
            #pragma unroll 1
            for (int k = 128; k <= 1024; k += 128) {
                const uint32_t v[4] = {nx.x, nx.y, nx.z, nx.w};
                nx = ny; ny = lds128(ra + ((k + 128) & 1023));
                #pragma unroll
                for (int i = 0; i < 4; i++) { const float t0 = bf_lo(v[i]) - pv, t1 = bf_hi(v[i]) - pv; s0 += t0; s1 += t1; a0 = fmaf(t0, t0, a0); a1 = fmaf(t1, t1, a1); }
            }
            s0 += s1; a0 += a1;
            #pragma unroll
            for (int o = 4; o; o >>= 1) { s0 += __shfl_xor_sync(0xffffffffu, s0, o); a0 += __shfl_xor_sync(0xffffffffu, a0, o); }
            s0 *= 1.f / DM;
            const float m = pv + s0, var = fmaxf(fmaf(-s0, s0, a0 * (1.f / DM)), 0.f);
            float sd, ri;
            asm("sqrt.approx.ftz.f32 %0, %1;" : "=f"(sd) : "f"(bf_round(bf_round(var) + 1e-5f)));
            asm("rcp.approx.ftz.f32 %0, %1;" : "=f"(ri) : "f"(bf_round(sd)));
            const uint32_t m2 = pack2(m, m);
            if ((lane & 7) == 0) {
                sts64(sb + OFF_CSUM + r * 8, m2 & 0xffff0000u, FU(0.5f * ri));
            }
            #pragma unroll 1
            for (int k = 128; k <= 1024; k += 128) {
                uint32_t v[4] = {nx.x, nx.y, nx.z, nx.w};
                nx = ny; ny = lds128(ra + ((k + 128) & 1023));
                #pragma unroll
                for (int i = 0; i < 4; i++) {
                    uint32_t dv; asm("sub.rn.bf16x2 %0, %1, %2;" : "=r"(dv) : "r"(v[i]), "r"(m2));
                    v[i] = pack2(bf_lo(dv) * ri, bf_hi(dv) * ri);
                }
                sts128(ra + k - 128, v[0], v[1], v[2], v[3]);
            }
        }
        STAMP(62);
        bar_sync(4);
        {
            const uint32_t ad = sb + OFF_LN + (4 * ((lane & 7) >> 1) + (lane & 1) + 2 * ((lane >> 3) & 1)) * 1040 + (16 * w + (lane >> 4)) * 16;
            uint32_t r[8][4];
            #pragma unroll
            for (int i = 0; i < 8; i++)
                asm volatile("ldmatrix.sync.aligned.m8n8.x4.trans.shared.b16 {%0,%1,%2,%3}, [%4];" : "=r"(r[i][0]), "=r"(r[i][1]), "=r"(r[i][2]), "=r"(r[i][3]) : "r"(ad + 32 * i) : "memory");
            bar_sync(4);
            const uint32_t od = sb + OFF_LN + w * 4096 + lane * 8;
            #pragma unroll
            for (int i = 0; i < 8; i++) { sts64(od + i * 512, r[i][0], r[i][1]); sts64(od + i * 512 + 256, r[i][2], r[i][3]); }
        }
        fence_async_smem();
        mbar_arrive(bars + 8 * B_LN);
        STAMP(16);
    }
}

__device__ __forceinline__ void consumer(uint32_t sb, int warp, const Params& P, const Maps& M) {
    const int V = warp >> 2, w = warp & 3, lane = threadIdx.x & 31, q = lane & 3, g = lane >> 2;
    const int c = blockIdx.x;
    const uint32_t bars = sb + OFF_BAR, xb = sb + OFF_X + V * 2 * XBUF;
    {
        float ag[88], au[88];
        if (V == 0) {
            sts128(xb + (w >> 1) * XBUF + 168 * 128 + (threadIdx.x & 63) * 16, 0x3f803f80u, 0x3f803f80u, 0x3f803f80u, 0x3f803f80u);
            fence_async_smem();
            bar_sync(1);
        } else {
            if (c < 128) layer_norm(sb, w, lane, P.x); else mbar_arrive(bars + 8 * B_LN);
            mbar_wait(bars + 8 * B_GO, 0);
        }
        define_acc(ag); define_acc(au);
        #pragma unroll 1
        for (int st = 0; st < 8; st++) {
            if (st + LAG * V == HOLD0 || st + LAG * V == HOLD1) mbar_wait(bars + 8 * (B_K + (st + LAG * V == HOLD1)), 0);
            mbar_wait(bars + 8 * (B_FULLW + (st & 3)), st >> 2);
            mbar_wait(bars + 8 * (B_FULLX + 2 * V + (st & 1)), (st >> 1) & 1);
            STAMP(40 + 8 * V + st);
            const uint64_t dG = mkdesc(sb + OFF_W + (st & 3) * 16384, 0, 1024, 1);
            const uint64_t dX = mkdesc(xb + (st & 1) * XBUF, 16, 1024, 1);
            WG_FENCE();
            #pragma unroll
            for (int k = 0; k < 4; k++) {
                wg_g1(ag, dG + k * 128, dX + k * 2, k ? 1 : st);
                wg_g1(au, dG + 512 + k * 128, dX + k * 2, k ? 1 : st);
            }
            WG_COMMIT();
            WG_WAIT(1);
            if (lane == 0 && st > 0) {
                mbar_arrive(bars + 8 * (B_EMPTYW + ((st - 1) & 3)));
                mbar_arrive(bars + 8 * (B_EMPTYX + 2 * V + ((st - 1) & 1)));
                if (warp < 4 && st == LAG) mbar_arrive(bars + 8 * B_GO);
            }
        }
        WG_WAIT(0);
        fence_acc(ag); fence_acc(au);
        if (lane == 0) { mbar_arrive(bars + 8 * (B_EMPTYW + 3)); mbar_arrive(bars + 8 * (B_EMPTYX + 2 * V + 1)); }
        STAMP(8 * V + 1);
        float cg0 = ag[84], cg1 = ag[86], cu0 = au[84], cu1 = au[86];
        const uint32_t ca = sb + OFF_CSUM + (8 * w + g) * 16;
        if (V == 0) { sts128(ca, FU(cg0), FU(cg1), FU(cu0), FU(cu1)); mbar_arrive(bars + 8 * B_CS); }
        else { mbar_wait(bars + 8 * B_CS, 0); const uint4 t = lds128(ca); cg0 = UF(t.x); cg1 = UF(t.y); cu0 = UF(t.z); cu1 = UF(t.w); }
        mbar_wait(bars + 8 * B_STATS, 0);
        mbar_wait(bars + 8 * (B_EMPTYX + 2 * V), 1);
        STAMP(13 + V);
        const uint32_t hs = xb + (2 * w + ((lane >> 3) & 1)) * (2688 + 128 * V) + (lane >> 4) * 128 + (lane & 7) * 16;
        const uint32_t sa = sb + OFF_ST + (168 * V + 2 * q) * 8;
        uint4 sq[22];
        #pragma unroll
        for (int j = 0; j < 3; j++) sq[j] = lds128(sa + j * 64);
        #pragma unroll
        for (int j = 0; j < 22; j += 2) {
            uint32_t o[4];
            #pragma unroll
            for (int jj = 0; jj < 2; jj++) {
                const uint4 sv = sq[j + jj];
                float hv[4];
                #pragma unroll
                for (int i = 0; i < 4; i++) {
                    const float m = UF((i & 1) ? sv.z : sv.x);
                    const float gh = fmaf(-m, (i & 2) ? cg1 : cg0, ag[4 * (j + jj) + i]) * UF((i & 1) ? sv.w : sv.y);
                    const float p = gh * fmaf(-m, (i & 2) ? cu1 : cu0, au[4 * (j + jj) + i]);
                    hv[i] = fmaf(p, tanh_fast(gh), p);
                }
                o[2 * jj] = pack2(hv[0], hv[1]); o[2 * jj + 1] = pack2(hv[2], hv[3]);
            }
            #pragma unroll
            for (int k = (j ? 3 + 3 * j / 2 : 3); k < 6 + 3 * j / 2 && k < 22; k++) sq[k] = lds128(sa + k * 64);
            uint32_t ad = hs + j * 128;
            if (j == 20 && V == 0 && lane >= 16) ad = xb + 21504 + (lane & 7) * 16;
            stsm4(ad, o[0], o[1], o[2], o[3]);
        }
        fence_async_smem();
        mbar_arrive(bars + 8 * (B_EPI + V));
        STAMP(8 * V + 2);
    }
    if (c >= 128) return;
    {
        uint32_t r0[8], r1[8];
        #pragma unroll
        for (int i = 0; i < 8; i++) asm volatile("" : "=r"(r1[i]));
        #pragma unroll 1
        for (int e = 0; e < 2; e++) {
            #pragma unroll
            for (int i = 0; i < 8; i++) r0[i] = r1[i];
            mbar_wait(bars + 8 * (B_CONV + 2 * V + e), 0);
            conv_channel(sb + OFF_CONV + (2 * V + e) * CH_STRIDE, w, lane, r1);
            if (e == 0) STAMP(8 * V + 3);
        }
        const int gam = g >> 2, qq = gam ? ((q + 3) & 3) : q;
        const uint32_t sp = sb + OFF_CONV + V * 58368 + ((63 - 4 * gam - qq) * 16 + 4 * w + (g & 3)) * 8;
        bar_sync(3 + V);
        #pragma unroll
        for (int a2 = 0; a2 < 8; a2++) sts64(sp - a2 * 1024, r0[a2], r1[a2]);
        fence_async_smem();
        mbar_arrive(bars + 8 * (B_SIG + V));
        STAMP(8 * V + 4);
    }
    if (V == 1) return;
    {
        const int tau = c >> 2, dg = c & 3;
        const uint32_t row = 8 * (w & 1) + 32 * (w >> 1);
        float acc[64];
        define_acc(acc);
        const float rr0 = __ldcg(&P.st[64 * tau + row + g].y), rr1 = __ldcg(&P.st[64 * tau + row + g + 16].y);
        mbar_wait(bars + 8 * B_FULLD, 0);
        STAMP(5);
        uint64_t dB = mkdesc(sb + wd_slot(0), 8192, 1024, 1), dA = mkdesc(sb + h_slot(0), 1024, 128, 0);
        #pragma unroll 1
        for (int st = 0; st < 21; st++) {
            WG_FENCE();
            wg_tt128(acc, dA, dB, st);
            wg_tt128(acc, dA + 128, dB + 128, 1);
            wg_tt128(acc, dA + 256, dB + 256, 1);
            wg_tt128(acc, dA + 384, dB + 384, 1);
            WG_COMMIT();
            const int sd = (st + 1) & 7;
            const uint32_t nb = bars + 8 * (B_FULLD + sd), np = ((st + 1) >> 3) & 1;
            uint32_t ro = st == 15 ? 8 * B_CH0 : 8 * (B_EMPTYD + ((st - 1) & 7)), m = lane == 0 && st > 0, ok;
            dB = mkdesc(sb + wd_slot(sd), 8192, 1024, 1); dA = mkdesc(sb + h_slot(sd), 1024, 128, 0);
            asm volatile("{.reg .pred p; mbarrier.test_wait.parity.shared::cta.b64 p, [%5], %6; vote.sync.all.pred p, p, -1; selp.u32 %0, 1, 0, p;}"
                : "=r"(ok), "+l"(dA), "+l"(dB), "+r"(ro), "+r"(m) : "r"(nb), "r"(np) : "memory");
            WG_WAIT(1);
            asm volatile("{.reg .pred p; setp.ne.u32 p, %1, 0; @p mbarrier.arrive.shared::cta.b64 _, [%0];}" :: "r"(bars + ro), "r"(m) : "memory");
            if (!ok) mbar_wait(nb, np);
            if (w == 0) STAMP2(20 + st);
        }
        WG_FENCE();
        wg_tt128(acc, dA, dB, 1);
        wg_tt128(acc, dA + 128, dB + 128, 1);
        WG_COMMIT();
        mbar_wait(bars + 8 * B_XO, 0);
        mbar_wait(bars + 8 * B_S, 0);
        const uint32_t xo = sb + OFF_CONV + (row + (lane & 7) + 16 * ((lane >> 3) & 1)) * 128;
        const uint32_t so = sb + wd_slot(6) + (w >> 1) * 8192 + q * 256 + (g & 1) * 8;
        uint32_t xr[8][4];
        uint2 sv[16];
        #pragma unroll
        for (int j = 0; j < 16; j += 2) {
            ldsm4(xr[j >> 1], xo + (j >> 3) * 8192 + ((((j & 7) + (lane >> 4)) ^ (lane & 7)) << 4));
            sv[j] = lds64(so + j * 512 + (((4 * (w & 1) + (g >> 1)) ^ (2 * q)) << 4));
            sv[j + 1] = lds64(so + j * 512 + 128 + (((4 * (w & 1) + (g >> 1)) ^ (2 * q + 1)) << 4));
        }
        WG_WAIT(0);
        fence_acc(acc);
        STAMP(6);
        #pragma unroll
        for (int j = 0; j < 16; j += 2) {
            #pragma unroll
            for (int i = 0; i < 4; i++) {
                const int jj = j + (i >> 1), hh = i & 1;
                const float f0 = acc[4 * jj + 2 * hh] * (hh ? rr1 : rr0), f1 = acc[4 * jj + 2 * hh + 1] * (hh ? rr1 : rr0);
                const uint32_t G = pack2(fmaf(f0, tanh_fast(f0), f0), fmaf(f1, tanh_fast(f1), f1));
                const uint32_t s2 = __byte_perm(sv[jj].x, sv[jj].y, hh ? 0x7632 : 0x5410);
                asm("fma.rn.bf16x2 %0, %1, %2, %0;" : "+r"(xr[j >> 1][i]) : "r"(s2), "r"(G));
            }
            stsm4(xo + (j >> 3) * 8192 + ((((j & 7) + (lane >> 4)) ^ (lane & 7)) << 4), xr[j >> 1][0], xr[j >> 1][1], xr[j >> 1][2], xr[j >> 1][3]);
        }
        fence_async_smem();
        bar_sync(1);
        if (w == 0 && elect_one()) {
            #pragma unroll
            for (int i = 0; i < 2; i++)
                asm volatile("cp.async.bulk.tensor.2d.global.shared::cta.bulk_group [%0, {%2, %3}], [%1];"
                    :: "l"(&M.out), "r"(sb + OFF_CONV + i * 8192), "r"(dg * 128 + 64 * i), "r"(tau * 64) : "memory");
            asm volatile("cp.async.bulk.commit_group; cp.async.bulk.wait_group.read 0;" ::: "memory");
        }
        STAMP(7); GSTAMP(23);
    }
}

__device__ __forceinline__ float2 cexp_p(float re2, float im, float p) {
    float sn, cs;
    const float mag = ex2(re2 * p), th = im * p;
    asm("sin.approx.ftz.f32 %0, %1;" : "=f"(sn) : "f"(th));
    asm("cos.approx.ftz.f32 %0, %1;" : "=f"(cs) : "f"(th));
    return make_float2(mag * cs, mag * sn);
}
__device__ __forceinline__ unsigned short ldu16(const void* p) { unsigned short v; asm volatile("ld.global.nc.u16 %0, [%1];" : "=h"(v) : "l"(p)); return v; }
__device__ __forceinline__ float2 cmul(float2 a, float2 b) { return make_float2(fmaf(a.x, b.x, -a.y * b.y), fmaf(a.x, b.y, a.y * b.x)); }
__device__ __forceinline__ float2 csqr(float2 a) { const float t = a.x * a.y; return make_float2(fmaf(a.x, a.x, -a.y * a.y), t + t); }
__device__ __forceinline__ void mma16816(float (&d)[4], const uint32_t (&a)[4], uint32_t b0, uint32_t b1) {
    asm volatile("mma.sync.aligned.m16n8k16.row.col.f32.bf16.bf16.f32 {%0,%1,%2,%3}, {%4,%5,%6,%7}, {%8,%9}, {%0,%1,%2,%3};"
        : "+f"(d[0]), "+f"(d[1]), "+f"(d[2]), "+f"(d[3]) : "r"(a[0]), "r"(a[1]), "r"(a[2]), "r"(a[3]), "r"(b0), "r"(b1));
}

__device__ __forceinline__ void aux_role(uint32_t sb, int w, const Params& P) {
    const int lane = threadIdx.x & 31, q = lane & 3, g = lane >> 2;
    const int c = blockIdx.x;
    const uint32_t bars = sb + OFF_BAR;
    if (c >= 128) {
        if (lane == 0) { mbar_arrive(bars + 8 * B_K); mbar_arrive(bars + 8 * (B_K + 1)); }
        return;
    }
    {
        const uint32_t cb = sb + OFF_CONV + w * CH_STRIDE;
        const uint32_t sF = cb + CH_A3;
        const int d = 4 * c + w;
        const int po = d * 128 + lane;
        unsigned short la = ldu16(P.logA + po), ai = ldu16(P.Aim + po), cr = ldu16(P.Cr + po), ci = ldu16(P.Ci + po);
        const float ldt = __bfloat162float(P.logdt[d]), dsk = __bfloat162float(P.Dskip[d]);
        float dacc[2][3][4];
        #pragma unroll
        for (int i = 0; i < 24; i++) (&dacc[0][0][0])[i] = 0.f;
        const float dt = bf_round(ex2(ldt * 1.4426950408889634f));
        #pragma unroll 1
        for (int ck = 0; ck < 4; ck++) {
            const uint32_t fa = cb + lane * 4 + (ck & 1) * 8064;
            const float re2 = bf_round(ex2(bf_lo((uint32_t)la) * 1.4426950408889634f)) * dt * -1.4426950408889634f, im = bf_lo((uint32_t)ai) * dt;
            const float2 C = make_float2(bf_lo((uint32_t)cr) * (dt + dt), bf_lo((uint32_t)ci) * -(dt + dt));
            {
                const int pn = po + 32 * min(ck + 1, 3);
                la = ldu16(P.logA + pn); ai = ldu16(P.Aim + pn); cr = ldu16(P.Cr + pn); ci = ldu16(P.Ci + pn);
            }
            const float2 z8 = cexp_p(re2, im, 8.f), y1 = cexp_p(re2, -im, 1.f);
            float2 b0 = make_float2(1.f, 0.f), b1 = cexp_p(re2, im, 64.f), b2 = csqr(b1), b3 = cmul(b2, b1), l0 = C;
            const uint32_t fm = cb + (ck & 1) * 8064 + (lane >> 3) * 144 + (lane & 7) * 16;
#define PK(v) pack2((v).x, (v).y)
            #pragma unroll 1
            for (uint32_t ro = 0; ro < 8 * 144; ro += 144) {
                stsm4(fm + (lane >> 3) * 7 * 144 + ro, PK(b0), PK(b1), PK(b2), PK(b3));
                stsf(fa + 32 * 144 + ro, UF(PK(l0)));
                b0 = cmul(b0, z8); b1 = cmul(b1, z8); b2 = cmul(b2, z8); b3 = cmul(b3, z8); l0 = cmul(l0, y1);
            }
            if (ck < 2) STAMP(56 + 3 * ck);
            const float2 y256 = cexp_p(re2, -im, 256.f), y2 = csqr(y1), y4 = csqr(y2), y8 = make_float2(z8.x, -z8.y);
            const float2 t0 = cmul(C, y256), t1 = cmul(t0, y256), t2 = cmul(t1, y256), t3_ = cmul(t2, y256);
            const float2 u1 = cmul(t0, y2), u2 = cmul(u1, y2), u3 = cmul(u2, y2);
            stsm4(fm + 40 * 144, PK(t0), PK(u1), PK(u2), PK(u3));
            stsm4(fm + 44 * 144, PK(t1), PK(cmul(t1, y4)), PK(t2), PK(cmul(t2, y4)));
            const float2 v0 = cmul(t3_, y8), v1 = cmul(v0, y256), v2 = cmul(v1, y256), v3 = cmul(v2, y256);
            stsm4(fm + 48 * 144, PK(v0), PK(v1), PK(v2), PK(v3));
            stsf(fa + 52 * 144, UF(PK(t3_)));
#undef PK
            if (ck < 2) STAMP(57 + 3 * ck);
            if (ck & 1) {
                uint32_t ln_; asm volatile("mov.u32 %0, %%laneid;" : "=r"(ln_));
                const uint32_t lda = cb + (ln_ & 15) * 144 + (ln_ & 16);
                const uint32_t ldb = cb + (32 + (ln_ & 7)) * 144 + (ln_ >> 3) * 16;
                __syncwarp();
                #pragma unroll
                for (int k2 = 0; k2 < 4; k2++) {
                    const uint32_t ko = (k2 >> 1) * 8064 + (k2 & 1) * 64;
                    uint32_t b[3][4];
                    #pragma unroll
                    for (int t3 = 0; t3 < 3; t3++) ldsm4(b[t3], ldb + t3 * 8 * 144 + ko);
                    #pragma unroll
                    for (int k = 0; k < 2; k++)
                        #pragma unroll
                        for (int mu = 0; mu < 2; mu++) {
                            uint32_t a[4];
                            ldsm4(a, lda + mu * 16 * 144 + ko + k * 32);
                            #pragma unroll
                            for (int t3 = 0; t3 < 3; t3++) mma16816(dacc[mu][t3], a, b[t3][2 * k], b[t3][2 * k + 1]);
                        }
                }
                __syncwarp();
                if (lane == 0) mbar_arrive(bars + 8 * (B_K + (ck >> 1)));
                STAMP(58 + 3 * (ck >> 1));
            }
        }
        STAMP(18);
        const uint32_t sG = cb + CH_G;
        if (lane == 0) dacc[0][0][0] += dsk;
        if (lane < 16) sts128(((lane & 8) ? cb + CH_U + 2048 + (lane & 4) * (UPLANE / 4) : sG + 128 + (lane & 4) * 48) + (lane & 3) * 16, 0, 0, 0, 0);
        {
            const uint32_t f0 = sF + (8 * g + 2 * q) * 4, f1 = sF + ((q < 2) ? 256 + 4 * g + 2 * q : 256 + 2 * g + 64 * q) * 4, st1 = (q < 2) ? 128 : 64;
            const uint32_t ga = sG + ((g & 1) ? 0 : 192) + (63 - (g >> 1) - 32 * q) * 2;
            #pragma unroll
            for (int i = 0; i < 4; i++) {
                const int mu = i >> 1, hh = i & 1;
                sts64(f0 + i * 256, FU(dacc[mu][0][2 * hh]), FU(dacc[mu][0][2 * hh + 1]));
                sts64(f1 + i * st1, FU(dacc[mu][1][2 * hh]), FU(dacc[mu][1][2 * hh + 1]));
                const uint32_t pk = pack2(dacc[mu][2][2 * hh], dacc[mu][2][2 * hh + 1]);
                if (q < 2) { sts16(ga - 8 * i, pk & 0xffff); sts16(ga - 8 * i - 32, pk >> 16); }
            }
            if (lane == 2) stsf(sF + 2048, dacc[0][2][0]);
        }
    }
    bar_sync(2);
    STAMP(19);
    const int rw = lane - 1 + 31 * w, u = min(rw, 77) - 14;
    const uint32_t o0 = CH_A3 + u * 4, o1 = CH_A3 + (128 + ((u + ((u >> 1) & 1)) >> 1)) * 4, o2 = CH_A3 + (256 + ((u + 1 + ((u >> 2) & 1)) >> 2)) * 4;
    const int kap = (lane >> 4) * 8 + ((lane >> 1) & 7), gam = lane & 1, hh = w >> 1, wp = w & 1;
    const uint32_t oa = CH_U + wp * UPLANE + (127 - 4 * kap - 2 * gam - hh) * 16;
    const uint32_t ob = CH_U + (wp ^ 1) * UPLANE + (128 - wp - 4 * kap - 2 * gam - hh) * 16;
    const uint32_t od = CH_A3 + (4 * wp + hh) * 512 + (kap >> 3) * 256 + (kap & 7) * 16 + gam * 8;
    #pragma unroll 1
    for (int k = 0; k < 4; k++) {
        const int ch = 2 * (k & 1) + (k >> 1);
        const uint32_t cb = sb + OFF_CONV + ch * CH_STRIDE;
        if (w < 3) {
            const uint32_t f0 = cb + o0, f1 = cb + o1, f2 = cb + o2;
            float kv[17];
            kv[0] = ldsf(u < 0 ? f1 : f0); if (u < 0) kv[0] = 0.f;
            #pragma unroll
            for (int s = 1; s < 4; s++) kv[s] = ldsf(f0 + s * 256);
            kv[4] = ldsf(u < 0 ? f0 + 1024 : f1 + 512);
            #pragma unroll
            for (int s = 5; s < 8; s++) kv[s] = ldsf(f1 + s * 128);
            kv[8] = ldsf(u < 0 ? f1 + 1024 : f2 + 512);
            #pragma unroll
            for (int s = 9; s < 16; s++) kv[s] = ldsf(f2 + s * 64);
            kv[16] = ldsf(u < 0 ? f2 + 1024 : cb + CH_A3 + 2048); if (u > 4) kv[16] = 0.f;
            uint32_t o[17];
            #pragma unroll
            for (int s = 0; s < 17; s++) o[s] = pack2(kv[s], __shfl_up_sync(0xffffffffu, kv[s], 1));
            if (lane > 0 && rw < 78) {
                const uint32_t ta = cb + CH_T + rw * 80;
                #pragma unroll
                for (int s4 = 0; s4 < 4; s4++) sts128(ta + s4 * 16, o[4 * s4], o[4 * s4 + 1], o[4 * s4 + 2], o[4 * s4 + 3]);
                stsf(ta + 64, UF(o[16]));
            }
        } else {
            const uint32_t ga = cb + CH_G + ((lane >> 3) & 1) * 192 + (lane >> 4) * 16 + (lane & 7) * 8;
            #pragma unroll
            for (int i = 0; i < 4; i++) {
                const uint2 x0 = lds64(ga + 32 * i), x1 = lds64(ga + 32 * i + 8);
                sts128(cb + CH_B3 + lane * 16 + 512 * i, x0.x, x0.y, x1.x, x1.y);
            }
        }
        mbar_wait(bars + 8 * B_U, 0);
        float p[24];
        const uint2 r0 = lds64(cb + ob + 24), r3 = lds64(cb + oa);
        uint32_t r[8];
        *(uint4*)&r[0] = lds128(cb + oa + 16); *(uint4*)&r[4] = lds128(cb + ob);
        p[0] = 0.f;
        p[1] = bf_lo(r0.x); p[2] = p[1] + bf_hi(r0.x); p[3] = p[2] + bf_lo(r0.y); p[4] = p[3] + bf_hi(r0.y);
        #pragma unroll
        for (int i = 0; i < 8; i++) { p[5 + 2 * i] = p[4 + 2 * i] + bf_lo(r[i]); p[6 + 2 * i] = p[5 + 2 * i] + bf_hi(r[i]); }
        p[21] = p[20] + bf_lo(r3.x); p[22] = p[21] + bf_hi(r3.x); p[23] = p[22] + bf_lo(r3.y);
        bar_sync(2);
        #pragma unroll
        for (int i = 0; i < 8; i += 4) {
            sts64(cb + od + i * 256, pack2(p[i + 9] - p[i], p[i + 10] - p[i + 1]), pack2(p[i + 11] - p[i + 2], p[i + 12] - p[i + 3]));
            sts64(cb + od + i * 256 + 128, pack2(p[i + 16] - p[i + 9], p[i + 17] - p[i + 10]), pack2(p[i + 18] - p[i + 11], p[i + 19] - p[i + 12]));
        }
        fence_async_smem();
        mbar_arrive(bars + 8 * (B_CONV + ch));
        if (k == 0) STAMP(17);
    }
    STAMP(21);
}

__global__ void __launch_bounds__(512, 1)
fused_kernel(const __grid_constant__ Params P, const __grid_constant__ Maps M) {
    extern __shared__ __align__(1024) uint8_t smem_raw[];
    const uint32_t sb = smem_u32(smem_raw);
    const uint32_t bars = sb + OFF_BAR;
    const int warp = __shfl_sync(0xffffffffu, threadIdx.x >> 5, 0);
    const int c = blockIdx.x, tg = c / 22, fb = c - 22 * tg;
    if (elect_one()) {
        if (warp == 0) { STAMP(24); GSTAMP(22); }
        asm volatile("" :: "l"(((const uint64_t*)&P)[warp < 12 ? warp : 0]));
        if (warp < 12) asm volatile("prefetch.tensormap [%0];" :: "l"(&M.x[0] + warp) : "memory");
        #pragma unroll
        for (int k = 0; k < 4; k++) {
            const int i = 16 * k + ((warp + 4) & 15);
            const uint32_t cnt = i >= B_CONV ? 128 : ((0xf0ull >> i) & 1) ? 8 : ((0xff0000ull >> i) & 1) ? 2 : ((0x3e00ff00f000ull >> i) & 1) ? 4 : 1;
            asm volatile("mbarrier.init.shared::cta.b64 [%0], %1;" :: "r"(bars + 8 * i), "r"(cnt) : "memory");
        }
        asm volatile("fence.mbarrier_init.release.cluster; fence.proxy.async.shared::cta;" ::: "memory");
        if (warp == 12) {
            mbar_expect(bars + 8 * B_FULLW, 16384);
            tma2d(sb + OFF_W, &M.wg, 64 * fb, 0, bars + 8 * B_FULLW);
            tma2d(sb + OFF_W + 8192, &M.wu, 64 * fb, 0, bars + 8 * B_FULLW);
            STAMP(31);
        } else if (warp == 4) {
            mbar_expect(bars + 8 * B_FULLX, 168 * 128);
            tma2d(sb + OFF_X, &M.x[0], 0, TOKG * tg, bars + 8 * B_FULLX);
        }
        if (sb & 1023) __trap();
    }
    __syncthreads();
    if (warp < 8) {
        asm volatile("setmaxnreg.inc.sync.aligned.u32 208;");
        consumer(sb, warp, P, M);
    } else if (warp < 12) {
        asm volatile("setmaxnreg.dec.sync.aligned.u32 72;");
        STAMP(32);
        aux_role(sb, warp - 8, P);
    } else {
        asm volatile("setmaxnreg.dec.sync.aligned.u32 24;");
        const int tau = c >> 2, dg = c & 3;
        if (elect_one()) {
            if (warp == 12) {
                #pragma unroll 1
                for (int st = 1; st < 8; st++) {
                    const uint32_t s = st & 3, fb_ = bars + 8 * (B_FULLW + s);
                    if (st == 2) mbar_wait(bars + 8 * B_FULLW, 0);
                    mbar_wait(bars + 8 * (B_EMPTYW + s), (st >> 2) ^ 1);
                    mbar_expect(fb_, 16384);
                    tma2d(sb + OFF_W + s * 16384, &M.wg, 64 * fb, 64 * st, fb_);
                    tma2d(sb + OFF_W + s * 16384 + 8192, &M.wu, 64 * fb, 64 * st, fb_);
                }
                if (c < 128) {
                    #pragma unroll 1
                    for (int st = 0; st < 22; st++) {
                        const int sd = st & 7;
                        if (st < 8) mbar_wait(bars + 8 * (uint32_t)((0x373623070d060504ull >> (8 * st)) & 0xff), st < 5);
                        else mbar_wait(bars + 8 * (B_EMPTYD + sd), ((st >> 3) & 1) ^ 1);
                        const uint32_t da = sb + wd_slot(sd), fb_ = bars + 8 * (B_FULLD + sd);
                        if (st >= 10 && st < 21) STAMP2(31 + st);
                        mbar_expect(fb_, 16384);
                        tma2d(da, &M.wd, 128 * dg, 64 * st, fb_);
                        tma2d(da + 8192, &M.wd, 128 * dg + 64, 64 * st, fb_);
                    }
                }
            } else if (warp < 15) {
                const int V = warp - 13;
                #pragma unroll 1
                for (int st = 1 - V; st < 8; st++) {
                    const uint32_t s = 2 * V + (st & 1);
                    if (s == 3 && st == 1) mbar_wait(bars + 8 * B_LNS, 0);
                    mbar_wait(bars + 8 * (B_EMPTYX + s), ((st >> 1) & 1) ^ 1);
                    mbar_expect(bars + 8 * (B_FULLX + s), (168 + 8 * V) * 128);
                    tma2d(sb + OFF_X + s * XBUF, &M.x[V], 64 * st, TOKG * tg + 168 * V, bars + 8 * (B_FULLX + s));
                }
                if (c < 128) {
                    if (V == 0) {
                        mbar_wait(bars + 8 * (B_STG + 1), 0);
                        #pragma unroll 1
                        for (int o = 8 * tau; o < 8 * tau + 8; o += 7) flag_wait(P.flags, F_H + 2 * (o / 43) + ((o % 43) >= 21), 22);
                        mbar_arrive(bars + 8 * B_HF);
                        STAMP(25);
                        #pragma unroll 1
                        for (int st = 0; st < 22; st++) {
                            const uint32_t fb_ = bars + 8 * (B_FULLD + (st & 7));
                            if (st == 6 || st == 7) mbar_wait(bars + 8 * (B_SIG - 6 + st), 0);
                            mbar_wait(bars + 8 * (B_EMPTYD + (st & 7)), ((st >> 3) & 1) ^ 1);
                            if (st >= 10 && st < 21) STAMP2(42 + st);
                            mbar_expect(fb_, 8192);
                            asm volatile("cp.async.bulk.tensor.5d.shared::cluster.global.mbarrier::complete_tx::bytes [%0], [%1, {%3, %3, %3, %4, %5}], [%2];"
                                :: "r"(sb + h_slot(st & 7)), "l"(&M.hld), "r"(fb_), "r"(0), "r"(2 * tau), "r"(8 * st) : "memory");
                        }
                    } else {
                        mbar_wait(bars + 8 * B_SST, 0);
                        mbar_wait(bars + 8 * B_CH0, 0);
                        mbar_expect(bars + 8 * B_XO, 16384);
                        tma2d(sb + OFF_CONV, &M.xo, 128 * dg, 64 * tau, bars + 8 * B_XO);
                        tma2d(sb + OFF_CONV + 8192, &M.xo, 128 * dg + 64, 64 * tau, bars + 8 * B_XO);
                        flag_wait(P.flags, F_S + dg, 64);
                        STAMP(26);
                        mbar_expect(bars + 8 * B_S, 16384);
                        asm volatile("cp.async.bulk.tensor.5d.shared::cluster.global.mbarrier::complete_tx::bytes [%0], [%1, {%3, %3, %3, %4, %5}], [%2];"
                            :: "r"(sb + wd_slot(6)), "l"(&M.sld), "r"(bars + 8 * B_S), "r"(0), "r"(8 * dg), "r"(2 * tau) : "memory");
                        mbar_wait(bars + 8 * B_HF, 0);
                        exit_count(P.flags);
                    }
                }
            } else {
                mbar_wait(bars + 8 * B_LN, 0);
                STAMP2(0);
                if (c < 128) {
                    #pragma unroll 1
                    for (int i = 0; i < 2; i++)
                        asm volatile("cp.async.bulk.tensor.2d.global.shared::cta.bulk_group [%0, {%2, %3}], [%1];"
                            :: "l"(&M.xt), "r"(sb + OFF_LN + i * 8192), "r"((c & 1) * 1024 + (126 - (c & ~1)) * 8), "r"(256 * i) : "memory");
                    #pragma unroll 1
                    for (int i = 0; i < 2; i++) bulk_store(P.st + 16 * (c & ~1) + 8 * (c & 1) + 16 - 16 * i, sb + OFF_CSUM + 64 * i, 64);
                    asm volatile("cp.async.bulk.prefetch.L2.global [%0], %1;" :: "l"(P.Wd + c * (FF * DM / 128)), "r"(FF * DM / 64) : "memory");
                }
                asm volatile("cp.async.bulk.commit_group; cp.async.bulk.wait_group.read 0;" ::: "memory");
                mbar_arrive(bars + 8 * B_LNS);
                STAMP2(1);
                flag_signal(P.flags, F_A);
                STAMP2(2);
                flag_wait(P.flags, F_A, NCTA);
                STAMP(20);
                mbar_expect(bars + 8 * B_STATS, TOKG * 8);
                bulk_load(sb + OFF_ST, P.st + TOKG * tg, TOKG * 8, bars + 8 * B_STATS);
                if (c < 128) {
                    mbar_wait(bars + 8 * (B_K + 1), 0);
                    fence_async_smem();
                    mbar_expect(bars + 8 * B_U, 8 * 2048);
                    #pragma unroll 1
                    for (int i = 0; i < 8; i++)
                        bulk_load(sb + OFF_CONV + (i >> 1) * CH_STRIDE + CH_U + (i & 1) * UPLANE, P.xnT + 4 * c * 256 + i * 128, 2048, bars + 8 * B_U);
                } else exit_count(P.flags);
                #pragma unroll 1
                for (int V = 0; V < 2; V++) {
                    mbar_wait(bars + 8 * (B_EPI + V), 0);
                    STAMP2(3 + 2 * V);
                    asm volatile("cp.async.bulk.tensor.3d.global.shared::cta.bulk_group [%0, {%2, %3, %4}], [%1];"
                        :: "l"(&M.hst[V]), "r"(sb + OFF_X + V * 2 * XBUF), "r"(0), "r"(43 * tg + 21 * V), "r"(8 * fb) : "memory");
                    flag_signal(P.flags, F_H + 2 * tg + V);
                    mbar_arrive(bars + 8 * (B_STG + V));
                    STAMP2(4 + 2 * V);
                }
                if (c < 128) {
                    #pragma unroll 1
                    for (int V = 0; V < 2; V++) {
                        mbar_wait(bars + 8 * (B_SIG + V), 0);
                        STAMP2(7 + 2 * V);
                        bulk_store(P.S + (2 * c + V) * 1024, sb + OFF_CONV + V * 58368, 8192);
                        flag_signal(P.flags, F_S + (c >> 5));
                        STAMP2(8 + 2 * V);
                    }
                    mbar_arrive(bars + 8 * B_SST);
                }
            }
        }
    }
    asm volatile("nanosleep.u32 0;");
}

typedef CUresult (*EncodeFn)(CUtensorMap*, CUtensorMapDataType, cuuint32_t, void*, const cuuint64_t*, const cuuint64_t*, const cuuint32_t*,
                             const cuuint32_t*, CUtensorMapInterleave, CUtensorMapSwizzle, CUtensorMapL2promotion, CUtensorMapFloatOOBfill);

void make_map(EncodeFn enc, CUtensorMap* m, const void* ptr, int rank, const cuuint64_t* dims, const cuuint64_t* strides, const cuuint32_t* box, bool swz) {
    const cuuint32_t es[5] = {1, 1, 1, 1, 1};
    enc(m, CU_TENSOR_MAP_DATA_TYPE_BFLOAT16, rank, (void*)ptr, dims, strides, box, es, CU_TENSOR_MAP_INTERLEAVE_NONE,
        swz ? CU_TENSOR_MAP_SWIZZLE_128B : CU_TENSOR_MAP_SWIZZLE_NONE, CU_TENSOR_MAP_L2_PROMOTION_L2_128B, CU_TENSOR_MAP_FLOAT_OOB_FILL_NONE);
}
void make_map2(EncodeFn enc, CUtensorMap* m, const void* ptr, cuuint64_t inner, cuuint64_t outer, cuuint32_t rows) {
    const cuuint64_t dims[2] = {inner, outer}, strides[1] = {inner * 2};
    const cuuint32_t box[2] = {64, rows};
    make_map(enc, m, ptr, 2, dims, strides, box, true);
}

}

extern "C" void kernel_launch(void* const* d_in, const int* in_sizes, int n_in, void* d_out, int out_size) {
    (void)in_sizes; (void)n_in; (void)out_size;
    static EncodeFn enc = nullptr;
    static void *hptr, *p_xnT, *p_st, *p_S, *p_flags;
    if (!enc) {
        cudaDriverEntryPointQueryResult qr;
        cudaGetDriverEntryPoint("cuTensorMapEncodeTiled", (void**)&enc, cudaEnableDefault, &qr);
        cudaFuncSetAttribute(fused_kernel, cudaFuncAttributeMaxDynamicSharedMemorySize, SMEM_BYTES);
        cudaGetSymbolAddress(&hptr, g_H); cudaGetSymbolAddress(&p_xnT, g_xnT); cudaGetSymbolAddress(&p_st, g_st);
        cudaGetSymbolAddress(&p_S, g_S); cudaGetSymbolAddress(&p_flags, g_flags);
    }
    Params P;
    P.x = (const __nv_bfloat16*)d_in[0]; P.logA = (const __nv_bfloat16*)d_in[1]; P.Aim = (const __nv_bfloat16*)d_in[2];
    P.Cr = (const __nv_bfloat16*)d_in[3]; P.Ci = (const __nv_bfloat16*)d_in[4]; P.logdt = (const __nv_bfloat16*)d_in[5];
    P.Dskip = (const __nv_bfloat16*)d_in[6];
    P.Wd = (const __nv_bfloat16*)d_in[10]; P.xnT = (uint4*)p_xnT; P.st = (float2*)p_st; P.S = (uint2*)p_S; P.flags = (unsigned*)p_flags;
    Maps M;
    make_map2(enc, &M.x[0], d_in[0], DM, SEQ, 168); make_map2(enc, &M.x[1], d_in[0], DM, SEQ, 176);
    make_map2(enc, &M.xo, d_in[0], DM, SEQ, 64);    make_map2(enc, &M.out, d_out, DM, SEQ, 64);
    make_map2(enc, &M.wg, d_in[8], FF, DM, 64);     make_map2(enc, &M.wu, d_in[9], FF, DM, 64);
    make_map2(enc, &M.wd, d_in[10], DM, FF, 64);
    for (int v = 0; v < 2; v++) {
        const cuuint64_t dims[3] = {64, 256, 172}, strides[2] = {128, 32768};
        const cuuint32_t box[3] = {64, (cuuint32_t)(21 + v), 8};
        make_map(enc, &M.hst[v], hptr, 3, dims, strides, box, false);
    }
    {
        const cuuint64_t dims[2] = {2048, 512}, strides[1] = {4096};
        const cuuint32_t box[2] = {16, 256};
        make_map(enc, &M.xt, p_xnT, 2, dims, strides, box, false);
    }
    {
        const cuuint64_t dims[5] = {64, 2, 4, 32, 64}, strides[4] = {4 * 8192, 8192, 8 * 8192, 128};
        const cuuint32_t box[5] = {64, 2, 4, 8, 2};
        make_map(enc, &M.sld, p_S, 5, dims, strides, box, true);
    }
    {
        const cuuint64_t dims[5] = {64, 2, 2, 64, 172}, strides[4] = {256, 128, 512, 32768};
        const cuuint32_t box[5] = {64, 2, 2, 2, 8};
        make_map(enc, &M.hld, hptr, 5, dims, strides, box, false);
    }
    fused_kernel<<<NCTA, 512, SMEM_BYTES>>>(P, M);
}
```

```cpp
#include <cuda_runtime.h>
#include <cuda_bf16.h>
#include <cuda.h>
#include <stdint.h>

#define PROF 0

namespace {

constexpr int SEQ = 2048, DM = 512, FF = 1376;
constexpr int NCTA = 132;
#define HOLD0 4
#define HOLD1 7
#define LAG 2
constexpr int TOKG = 344;

constexpr uint32_t OFF_W = 0;
constexpr uint32_t XBUF = 22528;
constexpr uint32_t OFF_X = 65536;
constexpr uint32_t OFF_CONV = 155648;
constexpr uint32_t CH_STRIDE = 16640;
constexpr uint32_t CH_T = 0;
constexpr uint32_t CH_A3 = 6272;
constexpr uint32_t CH_B3 = 10368;
constexpr uint32_t CH_U = 12416;
constexpr uint32_t CH_G = CH_A3 + 2064;
constexpr uint32_t UPLANE = 2112;
constexpr uint32_t OFF_LN = OFF_X + 3 * XBUF;
constexpr uint32_t OFF_ST = 222208;
constexpr uint32_t OFF_CSUM = 230400;
constexpr uint32_t OFF_BAR = 231168;
constexpr uint32_t SMEM_BYTES = 231680;

enum {
    B_FULLW = 0, B_EMPTYW = 4, B_FULLX = 8, B_EMPTYX = 12, B_FULLD = 16, B_EMPTYD = 24,
    B_U = 32, B_XO = 33, B_S = 34, B_STG = 35, B_HF = 37, B_STATS = 38, B_LNS = 39, B_SST = 40,
    B_LNX = 41, B_GO = 42, B_CH0 = 43, B_K = 44,
    B_CONV = 46, B_LN = 50, B_CS = 51, B_EPI = 52, B_SIG = 54,
    B_COUNT = 56
};
enum { F_A = 0, F_H = 1, F_S = 13, F_EXIT = 17, F_COUNT = 18 };

__device__ uint4 g_xnT[DM * 256];
__device__ float2 g_st[6 * TOKG];
__device__ uint4 g_H[172 * 256 * 8];
__device__ uint2 g_S[256 * 1024];
__device__ unsigned g_flags[F_COUNT * 32];
#define STAMP(i) do {} while (0)
#define GSTAMP(i) do {} while (0)
#define STAMP2(i) do {} while (0)

__device__ __forceinline__ uint32_t smem_u32(const void* p) { return (uint32_t)__cvta_generic_to_shared(p); }
__device__ __forceinline__ void mbar_expect(uint32_t bar, uint32_t bytes) { asm volatile("mbarrier.arrive.expect_tx.shared::cta.b64 _, [%0], %1;" :: "r"(bar), "r"(bytes) : "memory"); }
__device__ __forceinline__ void mbar_arrive(uint32_t bar) { asm volatile("mbarrier.arrive.shared::cta.b64 _, [%0];" :: "r"(bar) : "memory"); }
__device__ __forceinline__ void mbar_wait(uint32_t bar, uint32_t parity) {
    asm volatile("{.reg .pred p; .reg .u32 n; mov.u32 n, 0x20000;\n"
                 "LW: mbarrier.try_wait.parity.shared::cta.b64 p, [%0], %1;\n"
                 "sub.u32 n, n, 1; setp.eq.or.u32 p, n, 0, p; @!p bra LW;}" :: "r"(bar), "r"(parity) : "memory");
}
__device__ __forceinline__ bool elect_one() { uint32_t p; asm volatile("{.reg .pred P; elect.sync _|P, 0xffffffff; selp.u32 %0, 1, 0, P;}" : "=r"(p)); return p; }
__device__ __forceinline__ void tma2d(uint32_t dst, const CUtensorMap* m, int c0, int c1, uint32_t bar) {
    asm volatile("cp.async.bulk.tensor.2d.shared::cluster.global.mbarrier::complete_tx::bytes [%0], [%1, {%3, %4}], [%2];"
        :: "r"(dst), "l"(m), "r"(bar), "r"(c0), "r"(c1) : "memory");
}
__device__ __forceinline__ void bulk_load(uint32_t dst, const void* src, uint32_t bytes, uint32_t bar) {
    asm volatile("cp.async.bulk.shared::cluster.global.mbarrier::complete_tx::bytes [%0], [%1], %2, [%3];" :: "r"(dst), "l"(src), "r"(bytes), "r"(bar) : "memory");
}
__device__ __forceinline__ void bulk_store(void* dst, uint32_t src, uint32_t bytes) {
    asm volatile("cp.async.bulk.global.shared::cta.bulk_group [%0], [%1], %2;" :: "l"(dst), "r"(src), "r"(bytes) : "memory");
}
__device__ __forceinline__ void fence_async_smem() { asm volatile("fence.proxy.async.shared::cta;" ::: "memory"); }
__device__ __forceinline__ void flag_wait(unsigned* g_flags, int f, unsigned target) {
    asm volatile("{.reg .pred p; .reg .u32 n, v; mov.u32 n, 0x40000;\n"
                 "LF: ld.acquire.gpu.global.u32 v, [%0]; setp.ge.u32 p, v, %1; @p bra LD;\n"
                 "sub.u32 n, n, 1; setp.ne.u32 p, n, 0; @p bra LF; trap;\nLD: }"
                 :: "l"(g_flags + f * 32), "r"(target) : "memory");
}
__device__ __forceinline__ void flag_signal(unsigned* g_flags, int f) {
    asm volatile("cp.async.bulk.commit_group; cp.async.bulk.wait_group 0; red.relaxed.gpu.global.add.u32 [%0], 1;" :: "l"(g_flags + f * 32) : "memory");
}
__device__ __forceinline__ void exit_count(unsigned* g_flags) {
    if (atomicAdd(g_flags + F_EXIT * 32, 1u) == NCTA - 1) {
        #pragma unroll 1
        for (int i = 0; i < F_COUNT; i++) g_flags[i * 32] = 0;
    }
}
__device__ __forceinline__ void bar_sync(int id) { asm volatile("bar.sync %0, 128;" :: "r"(id) : "memory"); }
__device__ __forceinline__ uint64_t mkdesc(uint32_t addr, uint32_t lbo, uint32_t sbo, uint32_t swz) {
    return (uint64_t)((addr >> 4) | ((lbo >> 4) << 16)) | ((uint64_t)((sbo >> 4) | (swz << 30)) << 32);
}
#define WG_FENCE() asm volatile("wgmma.fence.sync.aligned;" ::: "memory")
#define WG_COMMIT() asm volatile("wgmma.commit_group.sync.aligned;" ::: "memory")
#define WG_WAIT(n) asm volatile("wgmma.wait_group.sync.aligned " #n ";" ::: "memory")
template <int N> __device__ __forceinline__ void fence_acc(float (&d)[N]) {
    #pragma unroll
    for (int i = 0; i < N; i++) asm volatile("" : "+f"(d[i]) :: "memory");
}
template <int N> __device__ __forceinline__ void define_acc(float (&d)[N]) {
    #pragma unroll
    for (int i = 0; i < N; i++) asm volatile("" : "=f"(d[i]));
}
__device__ __forceinline__ uint32_t pack2(float lo, float hi) { uint32_t r; asm("cvt.rn.bf16x2.f32 %0, %1, %2;" : "=r"(r) : "f"(hi), "f"(lo)); return r; }
__device__ __forceinline__ float bf_lo(uint32_t v) { return __uint_as_float(v << 16); }
__device__ __forceinline__ float bf_hi(uint32_t v) { return __uint_as_float(v & 0xffff0000u); }
__device__ __forceinline__ float bf_round(float v) { return bf_hi(pack2(0.f, v)); }
__device__ __forceinline__ float tanh_fast(float v) { float r; asm("tanh.approx.f32 %0, %1;" : "=f"(r) : "f"(v)); return r; }
__device__ __forceinline__ float ex2(float v) { float r; asm("ex2.approx.ftz.f32 %0, %1;" : "=f"(r) : "f"(v)); return r; }
__device__ __forceinline__ uint4 lds128(uint32_t a) { uint4 v; asm volatile("ld.shared.v4.b32 {%0,%1,%2,%3}, [%4];" : "=r"(v.x), "=r"(v.y), "=r"(v.z), "=r"(v.w) : "r"(a)); return v; }
__device__ __forceinline__ uint2 lds64(uint32_t a) { uint2 v; asm volatile("ld.shared.v2.b32 {%0,%1}, [%2];" : "=r"(v.x), "=r"(v.y) : "r"(a)); return v; }
__device__ __forceinline__ float ldsf(uint32_t a) { float v; asm volatile("ld.shared.f32 %0, [%1];" : "=f"(v) : "r"(a)); return v; }
__device__ __forceinline__ void sts128(uint32_t a, uint32_t x, uint32_t y, uint32_t z, uint32_t w) { asm volatile("st.shared.v4.b32 [%0], {%1,%2,%3,%4};" :: "r"(a), "r"(x), "r"(y), "r"(z), "r"(w) : "memory"); }
__device__ __forceinline__ void sts64(uint32_t a, uint32_t x, uint32_t y) { asm volatile("st.shared.v2.b32 [%0], {%1,%2};" :: "r"(a), "r"(x), "r"(y) : "memory"); }
__device__ __forceinline__ void stsf(uint32_t a, float x) { asm volatile("st.shared.f32 [%0], %1;" :: "r"(a), "f"(x) : "memory"); }
__device__ __forceinline__ void sts16(uint32_t a, uint32_t x) { asm volatile("st.shared.b16 [%0], %1;" :: "r"(a), "h"((unsigned short)x) : "memory"); }
__device__ __forceinline__ void stsm4(uint32_t a, uint32_t r0, uint32_t r1, uint32_t r2, uint32_t r3) {
    asm volatile("stmatrix.sync.aligned.m8n8.x4.shared.b16 [%0], {%1,%2,%3,%4};" :: "r"(a), "r"(r0), "r"(r1), "r"(r2), "r"(r3) : "memory");
}
__device__ __forceinline__ void ldsm4(uint32_t (&r)[4], uint32_t a) {
    asm volatile("ldmatrix.sync.aligned.m8n8.x4.shared.b16 {%0,%1,%2,%3}, [%4];" : "=r"(r[0]), "=r"(r[1]), "=r"(r[2]), "=r"(r[3]) : "r"(a) : "memory");
}
#define FU(x) __float_as_uint(x)
#define UF(x) __uint_as_float(x)
__device__ __forceinline__ uint32_t wd_slot(int s) { return (uint32_t)((0xb9a8403056201000ull >> (8 * s)) & 0xff) << 10; }
__device__ __forceinline__ uint32_t h_slot(int s) { return (uint32_t)((0xc9a0d98c847c746cull >> (8 * s)) & 0xff) << 10; }

template<int N> __device__ __forceinline__ void wg_rs(float (&d)[64], uint32_t a0, uint32_t a1, uint32_t a2, uint32_t a3, uint64_t db);
template<> __device__ __forceinline__ void wg_rs<128>(float (&d)[64], uint32_t a0, uint32_t a1, uint32_t a2, uint32_t a3, uint64_t db) {
  asm volatile("{.reg .pred p; setp.ne.b32 p, 1, 0; wgmma.mma_async.sync.aligned.m64n128k16.f32.bf16.bf16 {%0,%1,%2,%3,%4,%5,%6,%7,%8,%9,%10,%11,%12,%13,%14,%15,%16,%17,%18,%19,%20,%21,%22,%23,%24,%25,%26,%27,%28,%29,%30,%31,%32,%33,%34,%35,%36,%37,%38,%39,%40,%41,%42,%43,%44,%45,%46,%47,%48,%49,%50,%51,%52,%53,%54,%55,%56,%57,%58,%59,%60,%61,%62,%63}, {%64,%65,%66,%67}, %68, p, 1, 1, 0;}"
    : "+f"(d[0]),"+f"(d[1]),"+f"(d[2]),"+f"(d[3]),"+f"(d[4]),"+f"(d[5]),"+f"(d[6]),"+f"(d[7]),"+f"(d[8]),"+f"(d[9]),"+f"(d[10]),"+f"(d[11]),"+f"(d[12]),"+f"(d[13]),"+f"(d[14]),"+f"(d[15]),"+f"(d[16]),"+f"(d[17]),"+f"(d[18]),"+f"(d[19]),"+f"(d[20]),"+f"(d[21]),"+f"(d[22]),"+f"(d[23]),"+f"(d[24]),"+f"(d[25]),"+f"(d[26]),"+f"(d[27]),"+f"(d[28]),"+f"(d[29]),"+f"(d[30]),"+f"(d[31]),"+f"(d[32]),"+f"(d[33]),"+f"(d[34]),"+f"(d[35]),"+f"(d[36]),"+f"(d[37]),"+f"(d[38]),"+f"(d[39]),"+f"(d[40]),"+f"(d[41]),"+f"(d[42]),"+f"(d[43]),"+f"(d[44]),"+f"(d[45]),"+f"(d[46]),"+f"(d[47]),"+f"(d[48]),"+f"(d[49]),"+f"(d[50]),"+f"(d[51]),"+f"(d[52]),"+f"(d[53]),"+f"(d[54]),"+f"(d[55]),"+f"(d[56]),"+f"(d[57]),"+f"(d[58]),"+f"(d[59]),"+f"(d[60]),"+f"(d[61]),"+f"(d[62]),"+f"(d[63]) : "r"(a0), "r"(a1), "r"(a2), "r"(a3), "l"(db));
}
template<> __device__ __forceinline__ void wg_rs<120>(float (&d)[64], uint32_t a0, uint32_t a1, uint32_t a2, uint32_t a3, uint64_t db) {
  asm volatile("{.reg .pred p; setp.ne.b32 p, 1, 0; wgmma.mma_async.sync.aligned.m64n120k16.f32.bf16.bf16 {%0,%1,%2,%3,%4,%5,%6,%7,%8,%9,%10,%11,%12,%13,%14,%15,%16,%17,%18,%19,%20,%21,%22,%23,%24,%25,%26,%27,%28,%29,%30,%31,%32,%33,%34,%35,%36,%37,%38,%39,%40,%41,%42,%43,%44,%45,%46,%47,%48,%49,%50,%51,%52,%53,%54,%55,%56,%57,%58,%59}, {%60,%61,%62,%63}, %64, p, 1, 1, 0;}"
    : "+f"(d[0]),"+f"(d[1]),"+f"(d[2]),"+f"(d[3]),"+f"(d[4]),"+f"(d[5]),"+f"(d[6]),"+f"(d[7]),"+f"(d[8]),"+f"(d[9]),"+f"(d[10]),"+f"(d[11]),"+f"(d[12]),"+f"(d[13]),"+f"(d[14]),"+f"(d[15]),"+f"(d[16]),"+f"(d[17]),"+f"(d[18]),"+f"(d[19]),"+f"(d[20]),"+f"(d[21]),"+f"(d[22]),"+f"(d[23]),"+f"(d[24]),"+f"(d[25]),"+f"(d[26]),"+f"(d[27]),"+f"(d[28]),"+f"(d[29]),"+f"(d[30]),"+f"(d[31]),"+f"(d[32]),"+f"(d[33]),"+f"(d[34]),"+f"(d[35]),"+f"(d[36]),"+f"(d[37]),"+f"(d[38]),"+f"(d[39]),"+f"(d[40]),"+f"(d[41]),"+f"(d[42]),"+f"(d[43]),"+f"(d[44]),"+f"(d[45]),"+f"(d[46]),"+f"(d[47]),"+f"(d[48]),"+f"(d[49]),"+f"(d[50]),"+f"(d[51]),"+f"(d[52]),"+f"(d[53]),"+f"(d[54]),"+f"(d[55]),"+f"(d[56]),"+f"(d[57]),"+f"(d[58]),"+f"(d[59]) : "r"(a0), "r"(a1), "r"(a2), "r"(a3), "l"(db));
}
template<> __device__ __forceinline__ void wg_rs<112>(float (&d)[64], uint32_t a0, uint32_t a1, uint32_t a2, uint32_t a3, uint64_t db) {
  asm volatile("{.reg .pred p; setp.ne.b32 p, 1, 0; wgmma.mma_async.sync.aligned.m64n112k16.f32.bf16.bf16 {%0,%1,%2,%3,%4,%5,%6,%7,%8,%9,%10,%11,%12,%13,%14,%15,%16,%17,%18,%19,%20,%21,%22,%23,%24,%25,%26,%27,%28,%29,%30,%31,%32,%33,%34,%35,%36,%37,%38,%39,%40,%41,%42,%43,%44,%45,%46,%47,%48,%49,%50,%51,%52,%53,%54,%55}, {%56,%57,%58,%59}, %60, p, 1, 1, 0;}"
    : "+f"(d[0]),"+f"(d[1]),"+f"(d[2]),"+f"(d[3]),"+f"(d[4]),"+f"(d[5]),"+f"(d[6]),"+f"(d[7]),"+f"(d[8]),"+f"(d[9]),"+f"(d[10]),"+f"(d[11]),"+f"(d[12]),"+f"(d[13]),"+f"(d[14]),"+f"(d[15]),"+f"(d[16]),"+f"(d[17]),"+f"(d[18]),"+f"(d[19]),"+f"(d[20]),"+f"(d[21]),"+f"(d[22]),"+f"(d[23]),"+f"(d[24]),"+f"(d[25]),"+f"(d[26]),"+f"(d[27]),"+f"(d[28]),"+f"(d[29]),"+f"(d[30]),"+f"(d[31]),"+f"(d[32]),"+f"(d[33]),"+f"(d[34]),"+f"(d[35]),"+f"(d[36]),"+f"(d[37]),"+f"(d[38]),"+f"(d[39]),"+f"(d[40]),"+f"(d[41]),"+f"(d[42]),"+f"(d[43]),"+f"(d[44]),"+f"(d[45]),"+f"(d[46]),"+f"(d[47]),"+f"(d[48]),"+f"(d[49]),"+f"(d[50]),"+f"(d[51]),"+f"(d[52]),"+f"(d[53]),"+f"(d[54]),"+f"(d[55]) : "r"(a0), "r"(a1), "r"(a2), "r"(a3), "l"(db));
}
template<> __device__ __forceinline__ void wg_rs<104>(float (&d)[64], uint32_t a0, uint32_t a1, uint32_t a2, uint32_t a3, uint64_t db) {
  asm volatile("{.reg .pred p; setp.ne.b32 p, 1, 0; wgmma.mma_async.sync.aligned.m64n104k16.f32.bf16.bf16 {%0,%1,%2,%3,%4,%5,%6,%7,%8,%9,%10,%11,%12,%13,%14,%15,%16,%17,%18,%19,%20,%21,%22,%23,%24,%25,%26,%27,%28,%29,%30,%31,%32,%33,%34,%35,%36,%37,%38,%39,%40,%41,%42,%43,%44,%45,%46,%47,%48,%49,%50,%51}, {%52,%53,%54,%55}, %56, p, 1, 1, 0;}"
    : "+f"(d[0]),"+f"(d[1]),"+f"(d[2]),"+f"(d[3]),"+f"(d[4]),"+f"(d[5]),"+f"(d[6]),"+f"(d[7]),"+f"(d[8]),"+f"(d[9]),"+f"(d[10]),"+f"(d[11]),"+f"(d[12]),"+f"(d[13]),"+f"(d[14]),"+f"(d[15]),"+f"(d[16]),"+f"(d[17]),"+f"(d[18]),"+f"(d[19]),"+f"(d[20]),"+f"(d[21]),"+f"(d[22]),"+f"(d[23]),"+f"(d[24]),"+f"(d[25]),"+f"(d[26]),"+f"(d[27]),"+f"(d[28]),"+f"(d[29]),"+f"(d[30]),"+f"(d[31]),"+f"(d[32]),"+f"(d[33]),"+f"(d[34]),"+f"(d[35]),"+f"(d[36]),"+f"(d[37]),"+f"(d[38]),"+f"(d[39]),"+f"(d[40]),"+f"(d[41]),"+f"(d[42]),"+f"(d[43]),"+f"(d[44]),"+f"(d[45]),"+f"(d[46]),"+f"(d[47]),"+f"(d[48]),"+f"(d[49]),"+f"(d[50]),"+f"(d[51]) : "r"(a0), "r"(a1), "r"(a2), "r"(a3), "l"(db));
}
template<> __device__ __forceinline__ void wg_rs<96>(float (&d)[64], uint32_t a0, uint32_t a1, uint32_t a2, uint32_t a3, uint64_t db) {
  asm volatile("{.reg .pred p; setp.ne.b32 p, 1, 0; wgmma.mma_async.sync.aligned.m64n96k16.f32.bf16.bf16 {%0,%1,%2,%3,%4,%5,%6,%7,%8,%9,%10,%11,%12,%13,%14,%15,%16,%17,%18,%19,%20,%21,%22,%23,%24,%25,%26,%27,%28,%29,%30,%31,%32,%33,%34,%35,%36,%37,%38,%39,%40,%41,%42,%43,%44,%45,%46,%47}, {%48,%49,%50,%51}, %52, p, 1, 1, 0;}"
    : "+f"(d[0]),"+f"(d[1]),"+f"(d[2]),"+f"(d[3]),"+f"(d[4]),"+f"(d[5]),"+f"(d[6]),"+f"(d[7]),"+f"(d[8]),"+f"(d[9]),"+f"(d[10]),"+f"(d[11]),"+f"(d[12]),"+f"(d[13]),"+f"(d[14]),"+f"(d[15]),"+f"(d[16]),"+f"(d[17]),"+f"(d[18]),"+f"(d[19]),"+f"(d[20]),"+f"(d[21]),"+f"(d[22]),"+f"(d[23]),"+f"(d[24]),"+f"(d[25]),"+f"(d[26]),"+f"(d[27]),"+f"(d[28]),"+f"(d[29]),"+f"(d[30]),"+f"(d[31]),"+f"(d[32]),"+f"(d[33]),"+f"(d[34]),"+f"(d[35]),"+f"(d[36]),"+f"(d[37]),"+f"(d[38]),"+f"(d[39]),"+f"(d[40]),"+f"(d[41]),"+f"(d[42]),"+f"(d[43]),"+f"(d[44]),"+f"(d[45]),"+f"(d[46]),"+f"(d[47]) : "r"(a0), "r"(a1), "r"(a2), "r"(a3), "l"(db));
}
template<> __device__ __forceinline__ void wg_rs<88>(float (&d)[64], uint32_t a0, uint32_t a1, uint32_t a2, uint32_t a3, uint64_t db) {
  asm volatile("{.reg .pred p; setp.ne.b32 p, 1, 0; wgmma.mma_async.sync.aligned.m64n88k16.f32.bf16.bf16 {%0,%1,%2,%3,%4,%5,%6,%7,%8,%9,%10,%11,%12,%13,%14,%15,%16,%17,%18,%19,%20,%21,%22,%23,%24,%25,%26,%27,%28,%29,%30,%31,%32,%33,%34,%35,%36,%37,%38,%39,%40,%41,%42,%43}, {%44,%45,%46,%47}, %48, p, 1, 1, 0;}"
    : "+f"(d[0]),"+f"(d[1]),"+f"(d[2]),"+f"(d[3]),"+f"(d[4]),"+f"(d[5]),"+f"(d[6]),"+f"(d[7]),"+f"(d[8]),"+f"(d[9]),"+f"(d[10]),"+f"(d[11]),"+f"(d[12]),"+f"(d[13]),"+f"(d[14]),"+f"(d[15]),"+f"(d[16]),"+f"(d[17]),"+f"(d[18]),"+f"(d[19]),"+f"(d[20]),"+f"(d[21]),"+f"(d[22]),"+f"(d[23]),"+f"(d[24]),"+f"(d[25]),"+f"(d[26]),"+f"(d[27]),"+f"(d[28]),"+f"(d[29]),"+f"(d[30]),"+f"(d[31]),"+f"(d[32]),"+f"(d[33]),"+f"(d[34]),"+f"(d[35]),"+f"(d[36]),"+f"(d[37]),"+f"(d[38]),"+f"(d[39]),"+f"(d[40]),"+f"(d[41]),"+f"(d[42]),"+f"(d[43]) : "r"(a0), "r"(a1), "r"(a2), "r"(a3), "l"(db));
}
template<> __device__ __forceinline__ void wg_rs<80>(float (&d)[64], uint32_t a0, uint32_t a1, uint32_t a2, uint32_t a3, uint64_t db) {
  asm volatile("{.reg .pred p; setp.ne.b32 p, 1, 0; wgmma.mma_async.sync.aligned.m64n80k16.f32.bf16.bf16 {%0,%1,%2,%3,%4,%5,%6,%7,%8,%9,%10,%11,%12,%13,%14,%15,%16,%17,%18,%19,%20,%21,%22,%23,%24,%25,%26,%27,%28,%29,%30,%31,%32,%33,%34,%35,%36,%37,%38,%39}, {%40,%41,%42,%43}, %44, p, 1, 1, 0;}"
    : "+f"(d[0]),"+f"(d[1]),"+f"(d[2]),"+f"(d[3]),"+f"(d[4]),"+f"(d[5]),"+f"(d[6]),"+f"(d[7]),"+f"(d[8]),"+f"(d[9]),"+f"(d[10]),"+f"(d[11]),"+f"(d[12]),"+f"(d[13]),"+f"(d[14]),"+f"(d[15]),"+f"(d[16]),"+f"(d[17]),"+f"(d[18]),"+f"(d[19]),"+f"(d[20]),"+f"(d[21]),"+f"(d[22]),"+f"(d[23]),"+f"(d[24]),"+f"(d[25]),"+f"(d[26]),"+f"(d[27]),"+f"(d[28]),"+f"(d[29]),"+f"(d[30]),"+f"(d[31]),"+f"(d[32]),"+f"(d[33]),"+f"(d[34]),"+f"(d[35]),"+f"(d[36]),"+f"(d[37]),"+f"(d[38]),"+f"(d[39]) : "r"(a0), "r"(a1), "r"(a2), "r"(a3), "l"(db));
}
template<> __device__ __forceinline__ void wg_rs<72>(float (&d)[64], uint32_t a0, uint32_t a1, uint32_t a2, uint32_t a3, uint64_t db) {
  asm volatile("{.reg .pred p; setp.ne.b32 p, 1, 0; wgmma.mma_async.sync.aligned.m64n72k16.f32.bf16.bf16 {%0,%1,%2,%3,%4,%5,%6,%7,%8,%9,%10,%11,%12,%13,%14,%15,%16,%17,%18,%19,%20,%21,%22,%23,%24,%25,%26,%27,%28,%29,%30,%31,%32,%33,%34,%35}, {%36,%37,%38,%39}, %40, p, 1, 1, 0;}"
    : "+f"(d[0]),"+f"(d[1]),"+f"(d[2]),"+f"(d[3]),"+f"(d[4]),"+f"(d[5]),"+f"(d[6]),"+f"(d[7]),"+f"(d[8]),"+f"(d[9]),"+f"(d[10]),"+f"(d[11]),"+f"(d[12]),"+f"(d[13]),"+f"(d[14]),"+f"(d[15]),"+f"(d[16]),"+f"(d[17]),"+f"(d[18]),"+f"(d[19]),"+f"(d[20]),"+f"(d[21]),"+f"(d[22]),"+f"(d[23]),"+f"(d[24]),"+f"(d[25]),"+f"(d[26]),"+f"(d[27]),"+f"(d[28]),"+f"(d[29]),"+f"(d[30]),"+f"(d[31]),"+f"(d[32]),"+f"(d[33]),"+f"(d[34]),"+f"(d[35]) : "r"(a0), "r"(a1), "r"(a2), "r"(a3), "l"(db));
}
template<> __device__ __forceinline__ void wg_rs<64>(float (&d)[64], uint32_t a0, uint32_t a1, uint32_t a2, uint32_t a3, uint64_t db) {
  asm volatile("{.reg .pred p; setp.ne.b32 p, 1, 0; wgmma.mma_async.sync.aligned.m64n64k16.f32.bf16.bf16 {%0,%1,%2,%3,%4,%5,%6,%7,%8,%9,%10,%11,%12,%13,%14,%15,%16,%17,%18,%19,%20,%21,%22,%23,%24,%25,%26,%27,%28,%29,%30,%31}, {%32,%33,%34,%35}, %36, p, 1, 1, 0;}"
    : "+f"(d[0]),"+f"(d[1]),"+f"(d[2]),"+f"(d[3]),"+f"(d[4]),"+f"(d[5]),"+f"(d[6]),"+f"(d[7]),"+f"(d[8]),"+f"(d[9]),"+f"(d[10]),"+f"(d[11]),"+f"(d[12]),"+f"(d[13]),"+f"(d[14]),"+f"(d[15]),"+f"(d[16]),"+f"(d[17]),"+f"(d[18]),"+f"(d[19]),"+f"(d[20]),"+f"(d[21]),"+f"(d[22]),"+f"(d[23]),"+f"(d[24]),"+f"(d[25]),"+f"(d[26]),"+f"(d[27]),"+f"(d[28]),"+f"(d[29]),"+f"(d[30]),"+f"(d[31]) : "r"(a0), "r"(a1), "r"(a2), "r"(a3), "l"(db));
}
__device__ __forceinline__ void wg_rs_first(float (&d)[64], uint32_t a0, uint32_t a1, uint32_t a2, uint32_t a3, uint64_t db) {
  asm volatile("{.reg .pred p; setp.ne.b32 p, 0, 0; wgmma.mma_async.sync.aligned.m64n128k16.f32.bf16.bf16 {%0,%1,%2,%3,%4,%5,%6,%7,%8,%9,%10,%11,%12,%13,%14,%15,%16,%17,%18,%19,%20,%21,%22,%23,%24,%25,%26,%27,%28,%29,%30,%31,%32,%33,%34,%35,%36,%37,%38,%39,%40,%41,%42,%43,%44,%45,%46,%47,%48,%49,%50,%51,%52,%53,%54,%55,%56,%57,%58,%59,%60,%61,%62,%63}, {%64,%65,%66,%67}, %68, p, 1, 1, 0;}"
    : "=f"(d[0]),"=f"(d[1]),"=f"(d[2]),"=f"(d[3]),"=f"(d[4]),"=f"(d[5]),"=f"(d[6]),"=f"(d[7]),"=f"(d[8]),"=f"(d[9]),"=f"(d[10]),"=f"(d[11]),"=f"(d[12]),"=f"(d[13]),"=f"(d[14]),"=f"(d[15]),"=f"(d[16]),"=f"(d[17]),"=f"(d[18]),"=f"(d[19]),"=f"(d[20]),"=f"(d[21]),"=f"(d[22]),"=f"(d[23]),"=f"(d[24]),"=f"(d[25]),"=f"(d[26]),"=f"(d[27]),"=f"(d[28]),"=f"(d[29]),"=f"(d[30]),"=f"(d[31]),"=f"(d[32]),"=f"(d[33]),"=f"(d[34]),"=f"(d[35]),"=f"(d[36]),"=f"(d[37]),"=f"(d[38]),"=f"(d[39]),"=f"(d[40]),"=f"(d[41]),"=f"(d[42]),"=f"(d[43]),"=f"(d[44]),"=f"(d[45]),"=f"(d[46]),"=f"(d[47]),"=f"(d[48]),"=f"(d[49]),"=f"(d[50]),"=f"(d[51]),"=f"(d[52]),"=f"(d[53]),"=f"(d[54]),"=f"(d[55]),"=f"(d[56]),"=f"(d[57]),"=f"(d[58]),"=f"(d[59]),"=f"(d[60]),"=f"(d[61]),"=f"(d[62]),"=f"(d[63]) : "r"(a0), "r"(a1), "r"(a2), "r"(a3), "l"(db));
}
__device__ __forceinline__ void wg_tt128(float (&d)[64], uint64_t da, uint64_t db, int sc) {
  asm volatile("{.reg .pred p; setp.ne.b32 p, %66, 0; wgmma.mma_async.sync.aligned.m64n128k16.f32.bf16.bf16 {%0,%1,%2,%3,%4,%5,%6,%7,%8,%9,%10,%11,%12,%13,%14,%15,%16,%17,%18,%19,%20,%21,%22,%23,%24,%25,%26,%27,%28,%29,%30,%31,%32,%33,%34,%35,%36,%37,%38,%39,%40,%41,%42,%43,%44,%45,%46,%47,%48,%49,%50,%51,%52,%53,%54,%55,%56,%57,%58,%59,%60,%61,%62,%63}, %64, %65, p, 1, 1, 1, 1;}"
    : "+f"(d[0]),"+f"(d[1]),"+f"(d[2]),"+f"(d[3]),"+f"(d[4]),"+f"(d[5]),"+f"(d[6]),"+f"(d[7]),"+f"(d[8]),"+f"(d[9]),"+f"(d[10]),"+f"(d[11]),"+f"(d[12]),"+f"(d[13]),"+f"(d[14]),"+f"(d[15]),"+f"(d[16]),"+f"(d[17]),"+f"(d[18]),"+f"(d[19]),"+f"(d[20]),"+f"(d[21]),"+f"(d[22]),"+f"(d[23]),"+f"(d[24]),"+f"(d[25]),"+f"(d[26]),"+f"(d[27]),"+f"(d[28]),"+f"(d[29]),"+f"(d[30]),"+f"(d[31]),"+f"(d[32]),"+f"(d[33]),"+f"(d[34]),"+f"(d[35]),"+f"(d[36]),"+f"(d[37]),"+f"(d[38]),"+f"(d[39]),"+f"(d[40]),"+f"(d[41]),"+f"(d[42]),"+f"(d[43]),"+f"(d[44]),"+f"(d[45]),"+f"(d[46]),"+f"(d[47]),"+f"(d[48]),"+f"(d[49]),"+f"(d[50]),"+f"(d[51]),"+f"(d[52]),"+f"(d[53]),"+f"(d[54]),"+f"(d[55]),"+f"(d[56]),"+f"(d[57]),"+f"(d[58]),"+f"(d[59]),"+f"(d[60]),"+f"(d[61]),"+f"(d[62]),"+f"(d[63]) : "l"(da), "l"(db), "r"(sc));
}
__device__ __forceinline__ void wg_tt64(float (&d)[64], uint64_t da, uint64_t db, int sc) {
  asm volatile("{.reg .pred p; setp.ne.b32 p, %34, 0; wgmma.mma_async.sync.aligned.m64n64k16.f32.bf16.bf16 {%0,%1,%2,%3,%4,%5,%6,%7,%8,%9,%10,%11,%12,%13,%14,%15,%16,%17,%18,%19,%20,%21,%22,%23,%24,%25,%26,%27,%28,%29,%30,%31}, %32, %33, p, 1, 1, 1, 1;}"
    : "+f"(d[0]),"+f"(d[1]),"+f"(d[2]),"+f"(d[3]),"+f"(d[4]),"+f"(d[5]),"+f"(d[6]),"+f"(d[7]),"+f"(d[8]),"+f"(d[9]),"+f"(d[10]),"+f"(d[11]),"+f"(d[12]),"+f"(d[13]),"+f"(d[14]),"+f"(d[15]),"+f"(d[16]),"+f"(d[17]),"+f"(d[18]),"+f"(d[19]),"+f"(d[20]),"+f"(d[21]),"+f"(d[22]),"+f"(d[23]),"+f"(d[24]),"+f"(d[25]),"+f"(d[26]),"+f"(d[27]),"+f"(d[28]),"+f"(d[29]),"+f"(d[30]),"+f"(d[31]) : "l"(da), "l"(db), "r"(sc));
}
__device__ __forceinline__ void wg_tt32(float (&d)[64], uint64_t da, uint64_t db, int sc) {
  asm volatile("{.reg .pred p; setp.ne.b32 p, %18, 0; wgmma.mma_async.sync.aligned.m64n32k16.f32.bf16.bf16 {%0,%1,%2,%3,%4,%5,%6,%7,%8,%9,%10,%11,%12,%13,%14,%15}, %16, %17, p, 1, 1, 1, 1;}"
    : "+f"(d[0]),"+f"(d[1]),"+f"(d[2]),"+f"(d[3]),"+f"(d[4]),"+f"(d[5]),"+f"(d[6]),"+f"(d[7]),"+f"(d[8]),"+f"(d[9]),"+f"(d[10]),"+f"(d[11]),"+f"(d[12]),"+f"(d[13]),"+f"(d[14]),"+f"(d[15]) : "l"(da), "l"(db), "r"(sc));
}
__device__ __forceinline__ void wg_g1(float (&d)[88], uint64_t da, uint64_t db, int sc) {
  asm volatile("{.reg .pred p; setp.ne.b32 p, %90, 0; wgmma.mma_async.sync.aligned.m64n176k16.f32.bf16.bf16 {%0,%1,%2,%3,%4,%5,%6,%7,%8,%9,%10,%11,%12,%13,%14,%15,%16,%17,%18,%19,%20,%21,%22,%23,%24,%25,%26,%27,%28,%29,%30,%31,%32,%33,%34,%35,%36,%37,%38,%39,%40,%41,%42,%43,%44,%45,%46,%47,%48,%49,%50,%51,%52,%53,%54,%55,%56,%57,%58,%59,%60,%61,%62,%63,%64,%65,%66,%67,%68,%69,%70,%71,%72,%73,%74,%75,%76,%77,%78,%79,%80,%81,%82,%83,%84,%85,%86,%87}, %88, %89, p, 1, 1, 1, 0;}"
    : "+f"(d[0]),"+f"(d[1]),"+f"(d[2]),"+f"(d[3]),"+f"(d[4]),"+f"(d[5]),"+f"(d[6]),"+f"(d[7]),"+f"(d[8]),"+f"(d[9]),"+f"(d[10]),"+f"(d[11]),"+f"(d[12]),"+f"(d[13]),"+f"(d[14]),"+f"(d[15]),"+f"(d[16]),"+f"(d[17]),"+f"(d[18]),"+f"(d[19]),"+f"(d[20]),"+f"(d[21]),"+f"(d[22]),"+f"(d[23]),"+f"(d[24]),"+f"(d[25]),"+f"(d[26]),"+f"(d[27]),"+f"(d[28]),"+f"(d[29]),"+f"(d[30]),"+f"(d[31]),"+f"(d[32]),"+f"(d[33]),"+f"(d[34]),"+f"(d[35]),"+f"(d[36]),"+f"(d[37]),"+f"(d[38]),"+f"(d[39]),"+f"(d[40]),"+f"(d[41]),"+f"(d[42]),"+f"(d[43]),"+f"(d[44]),"+f"(d[45]),"+f"(d[46]),"+f"(d[47]),"+f"(d[48]),"+f"(d[49]),"+f"(d[50]),"+f"(d[51]),"+f"(d[52]),"+f"(d[53]),"+f"(d[54]),"+f"(d[55]),"+f"(d[56]),"+f"(d[57]),"+f"(d[58]),"+f"(d[59]),"+f"(d[60]),"+f"(d[61]),"+f"(d[62]),"+f"(d[63]),"+f"(d[64]),"+f"(d[65]),"+f"(d[66]),"+f"(d[67]),"+f"(d[68]),"+f"(d[69]),"+f"(d[70]),"+f"(d[71]),"+f"(d[72]),"+f"(d[73]),"+f"(d[74]),"+f"(d[75]),"+f"(d[76]),"+f"(d[77]),"+f"(d[78]),"+f"(d[79]),"+f"(d[80]),"+f"(d[81]),"+f"(d[82]),"+f"(d[83]),"+f"(d[84]),"+f"(d[85]),"+f"(d[86]),"+f"(d[87]) : "l"(da), "l"(db), "r"(sc));
}

struct Params { const __nv_bfloat16 *x, *logA, *Aim, *Cr, *Ci, *logdt, *Dskip, *Wd; uint4* xnT; float2* st; uint2* S; unsigned* flags; };
struct Maps { CUtensorMap x[2], xo, out, wg, wu, wd, hst[2], hld, xt, sld; };

__device__ __forceinline__ void conv_channel(uint32_t cb, int w, int lane, uint32_t (&res)[8], int sidx) {
    const int q = lane & 3, g = lane >> 2, gam = g >> 2;
    float acc[64];
    uint4 a[4][4];
    const uint32_t t0 = cb + CH_T + (uint32_t)(14 + 4 * w + (g & 3) + 32 * gam - 2 * q) * 80u;
    #pragma unroll
    for (int s4 = 0; s4 < 4; s4++) {
        a[s4][0] = lds128(t0 + s4 * 16);
        a[s4][1] = lds128(t0 + 16 * 80 + s4 * 16);
        a[s4][2] = lds128(t0 - 8 * 80 + s4 * 16);
        a[s4][3] = lds128(t0 + 8 * 80 + s4 * 16);
    }
    const uint32_t l0 = FU(ldsf(t0 + 64)), l1 = FU(ldsf(t0 + 16 * 80 + 64)), l2 = FU(ldsf(t0 - 8 * 80 + 64)), l3 = FU(ldsf(t0 + 8 * 80 + 64));
    const uint64_t dU = mkdesc(cb + CH_U, UPLANE, 128, 0);
    WG_FENCE();
    if (w == 0) STAMP2(52 + 3 * sidx);
#define CT(N, s, c) wg_rs<N>(acc, a[(s) >> 2][0].c, a[(s) >> 2][1].c, a[(s) >> 2][2].c, a[(s) >> 2][3].c, dU + 4 * (s))
    wg_rs_first(acc, a[0][0].x, a[0][1].x, a[0][2].x, a[0][3].x, dU);
    CT(128, 1, y); CT(120, 2, z); CT(120, 3, w);
    CT(112, 4, x); CT(112, 5, y); CT(104, 6, z); CT(104, 7, w);
    CT(96, 8, x);  CT(96, 9, y);  CT(88, 10, z); CT(88, 11, w);
    CT(80, 12, x); CT(80, 13, y); CT(72, 14, z); CT(72, 15, w);
#undef CT
    wg_rs<64>(acc, l0, l1, l2, l3, dU + 64);
    wg_tt64(acc, mkdesc(cb + CH_A3, 128, 512, 0), mkdesc(cb + CH_B3, 128, 256, 0), 1);
    wg_tt32(acc, mkdesc(cb + CH_A3 + 256, 128, 512, 0), mkdesc(cb + CH_B3 + 1024, 128, 256, 0), 1);
    WG_COMMIT();
    if (w == 0) STAMP2(53 + 3 * sidx);
    WG_WAIT(0);
    fence_acc(acc);
    if (w == 0) STAMP2(54 + 3 * sidx);
    const int src1 = (lane & ~3) | ((q + 1) & 3);
    float E[16][2];
    #pragma unroll
    for (int j = 0; j < 16; j++) {
        const float nxt = (j < 15) ? acc[4 * (j + 1) + 2] : 0.f;
        const float sup = (q == 0) ? nxt : acc[4 * j + 2];
        const float v = __shfl_sync(0xffffffffu, sup, src1);
        E[j][0] = acc[4 * j] + acc[4 * j + 3];
        E[j][1] = acc[4 * j + 1] + v;
    }
    const int src2 = gam ? ((lane & 12) | ((q + 3) & 3)) : (16 | (lane & 12) | ((q + 1) & 3));
    const bool c1 = gam && q != 0, c2 = gam && q == 0;
    #pragma unroll
    for (int a2 = 0; a2 < 8; a2++) {
        float y[2];
        #pragma unroll
        for (int e = 0; e < 2; e++) {
            const float sup = c1 ? E[2 * a2][e] : E[2 * a2 + 1][e];
            const float nxt = (a2 < 7) ? E[2 * a2 + 2][e] : 0.f;
            const float keep = c2 ? nxt : (c1 ? E[2 * a2 + 1][e] : E[2 * a2][e]);
            y[e] = keep + __shfl_sync(0xffffffffu, sup, src2);
        }
        res[a2] = pack2(y[1], y[0]);
    }
}

__device__ __forceinline__ void layer_norm(uint32_t sb, int w, int lane, const __nv_bfloat16* x) {
    const uint32_t bars = sb + OFF_BAR;
    const int c = blockIdx.x;
    {
        if (elect_one()) {
            mbar_expect(bars + 8 * B_LNX, 4096);
            #pragma unroll
            for (int i = 0; i < 4; i++)
                bulk_load(sb + OFF_LN + (w + 4 * i) * 1040, x + (16 * (c & ~1) + 8 * (c & 1) + 16 + w + 4 * (i & 1) - 8 * (i & 2)) * DM, 1024, bars + 8 * B_LNX);
        }
        mbar_wait(bars + 8 * B_LNX, 0);
        STAMP(34);
        {
            const int r = w + 4 * (lane >> 3);
            const uint32_t r0 = sb + OFF_LN + r * 1040, ra = r0 + (lane & 7) * 16;
            const float pv = bf_lo(FU(ldsf(r0)));
            float s0 = 0.f, s1 = 0.f, a0 = 0.f, a1 = 0.f;
            uint4 nx = lds128(ra), ny = lds128(ra + 128);
            #pragma unroll 1
            for (int k = 128; k <= 1024; k += 128) {
                const uint32_t v[4] = {nx.x, nx.y, nx.z, nx.w};
                nx = ny; ny = lds128(ra + ((k + 128) & 1023));
                #pragma unroll
                for (int i = 0; i < 4; i++) { const float t0 = bf_lo(v[i]) - pv, t1 = bf_hi(v[i]) - pv; s0 += t0; s1 += t1; a0 = fmaf(t0, t0, a0); a1 = fmaf(t1, t1, a1); }
            }
            s0 += s1; a0 += a1;
            #pragma unroll
            for (int o = 4; o; o >>= 1) { s0 += __shfl_xor_sync(0xffffffffu, s0, o); a0 += __shfl_xor_sync(0xffffffffu, a0, o); }
            s0 *= 1.f / DM;
            const float m = pv + s0, var = fmaxf(fmaf(-s0, s0, a0 * (1.f / DM)), 0.f);
            float sd, ri;
            asm("sqrt.approx.ftz.f32 %0, %1;" : "=f"(sd) : "f"(bf_round(bf_round(var) + 1e-5f)));
            asm("rcp.approx.ftz.f32 %0, %1;" : "=f"(ri) : "f"(bf_round(sd)));
            const uint32_t m2 = pack2(m, m);
            if ((lane & 7) == 0) {
                sts64(sb + OFF_CSUM + r * 8, m2 & 0xffff0000u, FU(0.5f * ri));
            }
            #pragma unroll 1
            for (int k = 128; k <= 1024; k += 128) {
                uint32_t v[4] = {nx.x, nx.y, nx.z, nx.w};
                nx = ny; ny = lds128(ra + ((k + 128) & 1023));
                #pragma unroll
                for (int i = 0; i < 4; i++) {
                    uint32_t dv; asm("sub.rn.bf16x2 %0, %1, %2;" : "=r"(dv) : "r"(v[i]), "r"(m2));
                    v[i] = pack2(bf_lo(dv) * ri, bf_hi(dv) * ri);
                }
                sts128(ra + k - 128, v[0], v[1], v[2], v[3]);
            }
        }
        STAMP(62);
        bar_sync(4);
        {
            const uint32_t ad = sb + OFF_LN + (4 * ((lane & 7) >> 1) + (lane & 1) + 2 * ((lane >> 3) & 1)) * 1040 + (16 * w + (lane >> 4)) * 16;
            uint32_t r[8][4];
            #pragma unroll
            for (int i = 0; i < 8; i++)
                asm volatile("ldmatrix.sync.aligned.m8n8.x4.trans.shared.b16 {%0,%1,%2,%3}, [%4];" : "=r"(r[i][0]), "=r"(r[i][1]), "=r"(r[i][2]), "=r"(r[i][3]) : "r"(ad + 32 * i) : "memory");
            bar_sync(4);
            const uint32_t od = sb + OFF_LN + w * 4096 + lane * 8;
            #pragma unroll
            for (int i = 0; i < 8; i++) { sts64(od + i * 512, r[i][0], r[i][1]); sts64(od + i * 512 + 256, r[i][2], r[i][3]); }
        }
        fence_async_smem();
        mbar_arrive(bars + 8 * B_LN);
        STAMP(16);
    }
}

__device__ __forceinline__ void consumer(uint32_t sb, int warp, const Params& P, const Maps& M) {
    const int V = warp >> 2, w = warp & 3, lane = threadIdx.x & 31, q = lane & 3, g = lane >> 2;
    const int c = blockIdx.x;
    const uint32_t bars = sb + OFF_BAR, xb = sb + OFF_X + V * 2 * XBUF;
    {
        float ag[88], au[88];
        if (V == 0) {
            sts128(xb + (w >> 1) * XBUF + 168 * 128 + (threadIdx.x & 63) * 16, 0x3f803f80u, 0x3f803f80u, 0x3f803f80u, 0x3f803f80u);
            fence_async_smem();
            bar_sync(1);
        } else {
            if (c < 128) layer_norm(sb, w, lane, P.x); else mbar_arrive(bars + 8 * B_LN);
            mbar_wait(bars + 8 * B_GO, 0);
        }
        define_acc(ag); define_acc(au);
        #pragma unroll 1
        for (int st = 0; st < 8; st++) {
            if (st + LAG * V == HOLD0 || st + LAG * V == HOLD1) mbar_wait(bars + 8 * (B_K + (st + LAG * V == HOLD1)), 0);
            mbar_wait(bars + 8 * (B_FULLW + (st & 3)), st >> 2);
            mbar_wait(bars + 8 * (B_FULLX + 2 * V + (st & 1)), (st >> 1) & 1);
            STAMP(40 + 8 * V + st);
            const uint64_t dG = mkdesc(sb + OFF_W + (st & 3) * 16384, 0, 1024, 1);
            const uint64_t dX = mkdesc(xb + (st & 1) * XBUF, 16, 1024, 1);
            WG_FENCE();
            #pragma unroll
            for (int k = 0; k < 4; k++) {
                wg_g1(ag, dG + k * 128, dX + k * 2, k ? 1 : st);
                wg_g1(au, dG + 512 + k * 128, dX + k * 2, k ? 1 : st);
            }
            WG_COMMIT();
            WG_WAIT(1);
            if (lane == 0 && st > 0) {
                mbar_arrive(bars + 8 * (B_EMPTYW + ((st - 1) & 3)));
                mbar_arrive(bars + 8 * (B_EMPTYX + 2 * V + ((st - 1) & 1)));
                if (warp < 4 && st == LAG) mbar_arrive(bars + 8 * B_GO);
            }
        }
        WG_WAIT(0);
        fence_acc(ag); fence_acc(au);
        if (lane == 0) { mbar_arrive(bars + 8 * (B_EMPTYW + 3)); mbar_arrive(bars + 8 * (B_EMPTYX + 2 * V + 1)); }
        STAMP(8 * V + 1);
        float cg0 = ag[84], cg1 = ag[86], cu0 = au[84], cu1 = au[86];
        const uint32_t ca = sb + OFF_CSUM + (8 * w + g) * 16;
        if (V == 0) { sts128(ca, FU(cg0), FU(cg1), FU(cu0), FU(cu1)); mbar_arrive(bars + 8 * B_CS); }
        else { mbar_wait(bars + 8 * B_CS, 0); const uint4 t = lds128(ca); cg0 = UF(t.x); cg1 = UF(t.y); cu0 = UF(t.z); cu1 = UF(t.w); }
        mbar_wait(bars + 8 * B_STATS, 0);
        mbar_wait(bars + 8 * (B_EMPTYX + 2 * V), 1);
        STAMP(13 + V);
        const uint32_t hs = xb + (2 * w + ((lane >> 3) & 1)) * (2688 + 128 * V) + (lane >> 4) * 128 + (lane & 7) * 16;
        const uint32_t sa = sb + OFF_ST + (168 * V + 2 * q) * 8;
        uint4 sq[22];
        #pragma unroll
        for (int j = 0; j < 3; j++) sq[j] = lds128(sa + j * 64);
        #pragma unroll
        for (int j = 0; j < 22; j += 2) {
            uint32_t o[4];
            #pragma unroll
            for (int jj = 0; jj < 2; jj++) {
                const uint4 sv = sq[j + jj];
                float hv[4];
                #pragma unroll
                for (int i = 0; i < 4; i++) {
                    const float m = UF((i & 1) ? sv.z : sv.x);
                    const float gh = fmaf(-m, (i & 2) ? cg1 : cg0, ag[4 * (j + jj) + i]) * UF((i & 1) ? sv.w : sv.y);
                    const float p = gh * fmaf(-m, (i & 2) ? cu1 : cu0, au[4 * (j + jj) + i]);
                    hv[i] = fmaf(p, tanh_fast(gh), p);
                }
                o[2 * jj] = pack2(hv[0], hv[1]); o[2 * jj + 1] = pack2(hv[2], hv[3]);
            }
            #pragma unroll
            for (int k = (j ? 3 + 3 * j / 2 : 3); k < 6 + 3 * j / 2 && k < 22; k++) sq[k] = lds128(sa + k * 64);
            uint32_t ad = hs + j * 128;
            if (j == 20 && V == 0 && lane >= 16) ad = xb + 21504 + (lane & 7) * 16;
            stsm4(ad, o[0], o[1], o[2], o[3]);
        }
        fence_async_smem();
        mbar_arrive(bars + 8 * (B_EPI + V));
        STAMP(8 * V + 2);
    }
    if (c >= 128) return;
    {
        uint32_t r0[8], r1[8];
        #pragma unroll
        for (int i = 0; i < 8; i++) asm volatile("" : "=r"(r1[i]));
        #pragma unroll 1
        for (int e = 0; e < 2; e++) {
            #pragma unroll
            for (int i = 0; i < 8; i++) r0[i] = r1[i];
            mbar_wait(bars + 8 * (B_CONV + 2 * V + e), 0);
            conv_channel(sb + OFF_CONV + (2 * V + e) * CH_STRIDE, w, lane, r1, 2 * V + e);
            if (e == 0) STAMP(8 * V + 3);
        }
        const int gam = g >> 2, qq = gam ? ((q + 3) & 3) : q;
        const uint32_t sp = sb + OFF_CONV + V * 58368 + ((63 - 4 * gam - qq) * 16 + 4 * w + (g & 3)) * 8;
        bar_sync(3 + V);
        #pragma unroll
        for (int a2 = 0; a2 < 8; a2++) sts64(sp - a2 * 1024, r0[a2], r1[a2]);
        fence_async_smem();
        mbar_arrive(bars + 8 * (B_SIG + V));
        STAMP(8 * V + 4);
    }
    if (V == 1) return;
    {
        const int tau = c >> 2, dg = c & 3;
        const uint32_t row = 8 * (w & 1) + 32 * (w >> 1);
        float acc[64];
        define_acc(acc);
        const float rr0 = __ldcg(&P.st[64 * tau + row + g].y), rr1 = __ldcg(&P.st[64 * tau + row + g + 16].y);
        mbar_wait(bars + 8 * B_FULLD, 0);
        STAMP(5);
        uint64_t dB = mkdesc(sb + wd_slot(0), 8192, 1024, 1), dA = mkdesc(sb + h_slot(0), 1024, 128, 0);
        #pragma unroll 1
        for (int st = 0; st < 21; st++) {
            WG_FENCE();
            wg_tt128(acc, dA, dB, st);
            wg_tt128(acc, dA + 128, dB + 128, 1);
            wg_tt128(acc, dA + 256, dB + 256, 1);
            wg_tt128(acc, dA + 384, dB + 384, 1);
            WG_COMMIT();
            const int sd = (st + 1) & 7;
            const uint32_t nb = bars + 8 * (B_FULLD + sd), np = ((st + 1) >> 3) & 1;
            uint32_t ro = st == 15 ? 8 * B_CH0 : 8 * (B_EMPTYD + ((st - 1) & 7)), m = lane == 0 && st > 0, ok;
            dB = mkdesc(sb + wd_slot(sd), 8192, 1024, 1); dA = mkdesc(sb + h_slot(sd), 1024, 128, 0);
            asm volatile("{.reg .pred p; mbarrier.test_wait.parity.shared::cta.b64 p, [%5], %6; vote.sync.all.pred p, p, -1; selp.u32 %0, 1, 0, p;}"
                : "=r"(ok), "+l"(dA), "+l"(dB), "+r"(ro), "+r"(m) : "r"(nb), "r"(np) : "memory");
            WG_WAIT(1);
            asm volatile("{.reg .pred p; setp.ne.u32 p, %1, 0; @p mbarrier.arrive.shared::cta.b64 _, [%0];}" :: "r"(bars + ro), "r"(m) : "memory");
            if (!ok) mbar_wait(nb, np);
            if (w == 0) STAMP2(20 + st);
        }
        WG_FENCE();
        wg_tt128(acc, dA, dB, 1);
        wg_tt128(acc, dA + 128, dB + 128, 1);
        WG_COMMIT();
        mbar_wait(bars + 8 * B_XO, 0);
        const uint32_t xo = sb + OFF_CONV + (row + (lane & 7) + 16 * ((lane >> 3) & 1)) * 128;
        const uint32_t so = sb + wd_slot(6) + (w >> 1) * 8192 + q * 256 + (g & 1) * 8;
        uint32_t xr[8][4];
        uint2 sv[16];
        #pragma unroll
        for (int j = 0; j < 16; j += 2) {
            ldsm4(xr[j >> 1], xo + (j >> 3) * 8192 + ((((j & 7) + (lane >> 4)) ^ (lane & 7)) << 4));
            sv[j] = lds64(so + j * 512 + (((4 * (w & 1) + (g >> 1)) ^ (2 * q)) << 4));
            sv[j + 1] = lds64(so + j * 512 + 128 + (((4 * (w & 1) + (g >> 1)) ^ (2 * q + 1)) << 4));
        }
        WG_WAIT(0);
        fence_acc(acc);
        STAMP(6);
        #pragma unroll
        for (int j = 0; j < 16; j += 2) {
            #pragma unroll
            for (int i = 0; i < 4; i++) {
                const int jj = j + (i >> 1), hh = i & 1;
                const float f0 = acc[4 * jj + 2 * hh] * (hh ? rr1 : rr0), f1 = acc[4 * jj + 2 * hh + 1] * (hh ? rr1 : rr0);
                const uint32_t G = pack2(fmaf(f0, tanh_fast(f0), f0), fmaf(f1, tanh_fast(f1), f1));
                const uint32_t s2 = __byte_perm(sv[jj].x, sv[jj].y, hh ? 0x7632 : 0x5410);
                asm("fma.rn.bf16x2 %0, %1, %2, %0;" : "+r"(xr[j >> 1][i]) : "r"(s2), "r"(G));
            }
            stsm4(xo + (j >> 3) * 8192 + ((((j & 7) + (lane >> 4)) ^ (lane & 7)) << 4), xr[j >> 1][0], xr[j >> 1][1], xr[j >> 1][2], xr[j >> 1][3]);
        }
        fence_async_smem();
        bar_sync(1);
        if (w == 0 && elect_one()) {
            #pragma unroll
            for (int i = 0; i < 2; i++)
                asm volatile("cp.async.bulk.tensor.2d.global.shared::cta.bulk_group [%0, {%2, %3}], [%1];"
                    :: "l"(&M.out), "r"(sb + OFF_CONV + i * 8192), "r"(dg * 128 + 64 * i), "r"(tau * 64) : "memory");
            asm volatile("cp.async.bulk.commit_group; cp.async.bulk.wait_group.read 0;" ::: "memory");
        }
        STAMP(7); GSTAMP(23);
    }
}

__device__ __forceinline__ float2 cexp_p(float re2, float im, float p) {
    float sn, cs;
    const float mag = ex2(re2 * p), th = im * p;
    asm("sin.approx.ftz.f32 %0, %1;" : "=f"(sn) : "f"(th));
    asm("cos.approx.ftz.f32 %0, %1;" : "=f"(cs) : "f"(th));
    return make_float2(mag * cs, mag * sn);
}
__device__ __forceinline__ unsigned short ldu16(const void* p) { unsigned short v; asm volatile("ld.global.nc.u16 %0, [%1];" : "=h"(v) : "l"(p)); return v; }
__device__ __forceinline__ float2 cmul(float2 a, float2 b) { return make_float2(fmaf(a.x, b.x, -a.y * b.y), fmaf(a.x, b.y, a.y * b.x)); }
__device__ __forceinline__ float2 csqr(float2 a) { const float t = a.x * a.y; return make_float2(fmaf(a.x, a.x, -a.y * a.y), t + t); }
__device__ __forceinline__ void mma16816(float (&d)[4], const uint32_t (&a)[4], uint32_t b0, uint32_t b1) {
    asm volatile("mma.sync.aligned.m16n8k16.row.col.f32.bf16.bf16.f32 {%0,%1,%2,%3}, {%4,%5,%6,%7}, {%8,%9}, {%0,%1,%2,%3};"
        : "+f"(d[0]), "+f"(d[1]), "+f"(d[2]), "+f"(d[3]) : "r"(a[0]), "r"(a[1]), "r"(a[2]), "r"(a[3]), "r"(b0), "r"(b1));
}

__device__ __forceinline__ void aux_role(uint32_t sb, int w, const Params& P) {
    const int lane = threadIdx.x & 31, q = lane & 3, g = lane >> 2;
    const int c = blockIdx.x;
    const uint32_t bars = sb + OFF_BAR;
    if (c >= 128) {
        if (lane == 0) { mbar_arrive(bars + 8 * B_K); mbar_arrive(bars + 8 * (B_K + 1)); }
        return;
    }
    {
        const uint32_t cb = sb + OFF_CONV + w * CH_STRIDE;
        const uint32_t sF = cb + CH_A3;
        const int d = 4 * c + w;
        const int po = d * 128 + lane;
        unsigned short la = ldu16(P.logA + po), ai = ldu16(P.Aim + po), cr = ldu16(P.Cr + po), ci = ldu16(P.Ci + po);
        const float ldt = __bfloat162float(P.logdt[d]), dsk = __bfloat162float(P.Dskip[d]);
        float dacc[2][3][4];
        #pragma unroll
        for (int i = 0; i < 24; i++) (&dacc[0][0][0])[i] = 0.f;
        const float dt = bf_round(ex2(ldt * 1.4426950408889634f));
        #pragma unroll 1
        for (int ck = 0; ck < 4; ck++) {
            const uint32_t fa = cb + lane * 4 + (ck & 1) * 8064;
            const float re2 = bf_round(ex2(bf_lo((uint32_t)la) * 1.4426950408889634f)) * dt * -1.4426950408889634f, im = bf_lo((uint32_t)ai) * dt;
            const float2 C = make_float2(bf_lo((uint32_t)cr) * (dt + dt), bf_lo((uint32_t)ci) * -(dt + dt));
            {
                const int pn = po + 32 * min(ck + 1, 3);
                la = ldu16(P.logA + pn); ai = ldu16(P.Aim + pn); cr = ldu16(P.Cr + pn); ci = ldu16(P.Ci + pn);
            }
            const float2 z8 = cexp_p(re2, im, 8.f), y1 = cexp_p(re2, -im, 1.f);
            float2 b0 = make_float2(1.f, 0.f), b1 = cexp_p(re2, im, 64.f), b2 = csqr(b1), b3 = cmul(b2, b1), l0 = C;
            const uint32_t fm = cb + (ck & 1) * 8064 + (lane >> 3) * 144 + (lane & 7) * 16;
#define PK(v) pack2((v).x, (v).y)
            #pragma unroll 1
            for (uint32_t ro = 0; ro < 8 * 144; ro += 144) {
                stsm4(fm + (lane >> 3) * 7 * 144 + ro, PK(b0), PK(b1), PK(b2), PK(b3));
                stsf(fa + 32 * 144 + ro, UF(PK(l0)));
                b0 = cmul(b0, z8); b1 = cmul(b1, z8); b2 = cmul(b2, z8); b3 = cmul(b3, z8); l0 = cmul(l0, y1);
            }
            if (ck < 2) STAMP(56 + 3 * ck);
            const float2 y256 = cexp_p(re2, -im, 256.f), y2 = csqr(y1), y4 = csqr(y2), y8 = make_float2(z8.x, -z8.y);
            const float2 t0 = cmul(C, y256), t1 = cmul(t0, y256), t2 = cmul(t1, y256), t3_ = cmul(t2, y256);
            const float2 u1 = cmul(t0, y2), u2 = cmul(u1, y2), u3 = cmul(u2, y2);
            stsm4(fm + 40 * 144, PK(t0), PK(u1), PK(u2), PK(u3));
            stsm4(fm + 44 * 144, PK(t1), PK(cmul(t1, y4)), PK(t2), PK(cmul(t2, y4)));
            const float2 v0 = cmul(t3_, y8), v1 = cmul(v0, y256), v2 = cmul(v1, y256), v3 = cmul(v2, y256);
            stsm4(fm + 48 * 144, PK(v0), PK(v1), PK(v2), PK(v3));
            stsf(fa + 52 * 144, UF(PK(t3_)));
#undef PK
            if (ck < 2) STAMP(57 + 3 * ck);
            if (ck & 1) {
                uint32_t ln_; asm volatile("mov.u32 %0, %%laneid;" : "=r"(ln_));
                const uint32_t lda = cb + (ln_ & 15) * 144 + (ln_ & 16);
                const uint32_t ldb = cb + (32 + (ln_ & 7)) * 144 + (ln_ >> 3) * 16;
                __syncwarp();
                #pragma unroll
                for (int k2 = 0; k2 < 4; k2++) {
                    const uint32_t ko = (k2 >> 1) * 8064 + (k2 & 1) * 64;
                    uint32_t b[3][4];
                    #pragma unroll
                    for (int t3 = 0; t3 < 3; t3++) ldsm4(b[t3], ldb + t3 * 8 * 144 + ko);
                    #pragma unroll
                    for (int k = 0; k < 2; k++)
                        #pragma unroll
                        for (int mu = 0; mu < 2; mu++) {
                            uint32_t a[4];
                            ldsm4(a, lda + mu * 16 * 144 + ko + k * 32);
                            #pragma unroll
                            for (int t3 = 0; t3 < 3; t3++) mma16816(dacc[mu][t3], a, b[t3][2 * k], b[t3][2 * k + 1]);
                        }
                }
                __syncwarp();
                if (lane == 0) mbar_arrive(bars + 8 * (B_K + (ck >> 1)));
                STAMP(58 + 3 * (ck >> 1));
            }
        }
        STAMP(18);
        const uint32_t sG = cb + CH_G;
        if (lane == 0) dacc[0][0][0] += dsk;
        if (lane < 16) sts128(((lane & 8) ? cb + CH_U + 2048 + (lane & 4) * (UPLANE / 4) : sG + 128 + (lane & 4) * 48) + (lane & 3) * 16, 0, 0, 0, 0);
        {
            const uint32_t f0 = sF + (8 * g + 2 * q) * 4, f1 = sF + ((q < 2) ? 256 + 4 * g + 2 * q : 256 + 2 * g + 64 * q) * 4, st1 = (q < 2) ? 128 : 64;
            const uint32_t ga = sG + ((g & 1) ? 0 : 192) + (63 - (g >> 1) - 32 * q) * 2;
            #pragma unroll
            for (int i = 0; i < 4; i++) {
                const int mu = i >> 1, hh = i & 1;
                sts64(f0 + i * 256, FU(dacc[mu][0][2 * hh]), FU(dacc[mu][0][2 * hh + 1]));
                sts64(f1 + i * st1, FU(dacc[mu][1][2 * hh]), FU(dacc[mu][1][2 * hh + 1]));
                const uint32_t pk = pack2(dacc[mu][2][2 * hh], dacc[mu][2][2 * hh + 1]);
                if (q < 2) { sts16(ga - 8 * i, pk & 0xffff); sts16(ga - 8 * i - 32, pk >> 16); }
            }
            if (lane == 2) stsf(sF + 2048, dacc[0][2][0]);
        }
    }
    bar_sync(2);
    STAMP(19);
    const int rw = lane - 1 + 31 * w, u = min(rw, 77) - 14;
    const uint32_t o0 = CH_A3 + u * 4, o1 = CH_A3 + (128 + ((u + ((u >> 1) & 1)) >> 1)) * 4, o2 = CH_A3 + (256 + ((u + 1 + ((u >> 2) & 1)) >> 2)) * 4;
    const int kap = (lane >> 4) * 8 + ((lane >> 1) & 7), gam = lane & 1, hh = w >> 1, wp = w & 1;
    const uint32_t oa = CH_U + wp * UPLANE + (127 - 4 * kap - 2 * gam - hh) * 16;
    const uint32_t ob = CH_U + (wp ^ 1) * UPLANE + (128 - wp - 4 * kap - 2 * gam - hh) * 16;
    const uint32_t od = CH_A3 + (4 * wp + hh) * 512 + (kap >> 3) * 256 + (kap & 7) * 16 + gam * 8;
    #pragma unroll 1
    for (int k = 0; k < 4; k++) {
        const int ch = 2 * (k & 1) + (k >> 1);
        const uint32_t cb = sb + OFF_CONV + ch * CH_STRIDE;
        if (w < 3) {
            const uint32_t f0 = cb + o0, f1 = cb + o1, f2 = cb + o2;
            float kv[17];
            kv[0] = ldsf(u < 0 ? f1 : f0); if (u < 0) kv[0] = 0.f;
            #pragma unroll
            for (int s = 1; s < 4; s++) kv[s] = ldsf(f0 + s * 256);
            kv[4] = ldsf(u < 0 ? f0 + 1024 : f1 + 512);
            #pragma unroll
            for (int s = 5; s < 8; s++) kv[s] = ldsf(f1 + s * 128);
            kv[8] = ldsf(u < 0 ? f1 + 1024 : f2 + 512);
            #pragma unroll
            for (int s = 9; s < 16; s++) kv[s] = ldsf(f2 + s * 64);
            kv[16] = ldsf(u < 0 ? f2 + 1024 : cb + CH_A3 + 2048); if (u > 4) kv[16] = 0.f;
            uint32_t o[17];
            #pragma unroll
            for (int s = 0; s < 17; s++) o[s] = pack2(kv[s], __shfl_up_sync(0xffffffffu, kv[s], 1));
            if (lane > 0 && rw < 78) {
                const uint32_t ta = cb + CH_T + rw * 80;
                #pragma unroll
                for (int s4 = 0; s4 < 4; s4++) sts128(ta + s4 * 16, o[4 * s4], o[4 * s4 + 1], o[4 * s4 + 2], o[4 * s4 + 3]);
                stsf(ta + 64, UF(o[16]));
            }
        } else {
            const uint32_t ga = cb + CH_G + ((lane >> 3) & 1) * 192 + (lane >> 4) * 16 + (lane & 7) * 8;
            #pragma unroll
            for (int i = 0; i < 4; i++) {
                const uint2 x0 = lds64(ga + 32 * i), x1 = lds64(ga + 32 * i + 8);
                sts128(cb + CH_B3 + lane * 16 + 512 * i, x0.x, x0.y, x1.x, x1.y);
            }
        }
        mbar_wait(bars + 8 * B_U, 0);
        float p[24];
        const uint2 r0 = lds64(cb + ob + 24), r3 = lds64(cb + oa);
        uint32_t r[8];
        *(uint4*)&r[0] = lds128(cb + oa + 16); *(uint4*)&r[4] = lds128(cb + ob);
        p[0] = 0.f;
        p[1] = bf_lo(r0.x); p[2] = p[1] + bf_hi(r0.x); p[3] = p[2] + bf_lo(r0.y); p[4] = p[3] + bf_hi(r0.y);
        #pragma unroll
        for (int i = 0; i < 8; i++) { p[5 + 2 * i] = p[4 + 2 * i] + bf_lo(r[i]); p[6 + 2 * i] = p[5 + 2 * i] + bf_hi(r[i]); }
        p[21] = p[20] + bf_lo(r3.x); p[22] = p[21] + bf_hi(r3.x); p[23] = p[22] + bf_lo(r3.y);
        bar_sync(2);
        #pragma unroll
        for (int i = 0; i < 8; i += 4) {
            sts64(cb + od + i * 256, pack2(p[i + 9] - p[i], p[i + 10] - p[i + 1]), pack2(p[i + 11] - p[i + 2], p[i + 12] - p[i + 3]));
            sts64(cb + od + i * 256 + 128, pack2(p[i + 16] - p[i + 9], p[i + 17] - p[i + 10]), pack2(p[i + 18] - p[i + 11], p[i + 19] - p[i + 12]));
        }
        fence_async_smem();
        mbar_arrive(bars + 8 * (B_CONV + ch));
        if (k == 0) STAMP(17);
    }
    STAMP(21);
}

__global__ void __launch_bounds__(512, 1)
fused_kernel(const __grid_constant__ Params P, const __grid_constant__ Maps M) {
    extern __shared__ __align__(1024) uint8_t smem_raw[];
    const uint32_t sb = smem_u32(smem_raw);
    const uint32_t bars = sb + OFF_BAR;
    const int warp = __shfl_sync(0xffffffffu, threadIdx.x >> 5, 0);
    const int c = blockIdx.x, tg = c / 22, fb = c - 22 * tg;
    if (elect_one()) {
        if (warp == 0) { STAMP(24); GSTAMP(22); }
        asm volatile("" :: "l"(((const uint64_t*)&P)[warp < 12 ? warp : 0]));
        if (warp < 12) asm volatile("prefetch.tensormap [%0];" :: "l"(&M.x[0] + warp) : "memory");
        #pragma unroll
        for (int k = 0; k < 4; k++) {
            const int i = 16 * k + ((warp + 4) & 15);
            const uint32_t cnt = i >= B_CONV ? 128 : ((0xf0ull >> i) & 1) ? 8 : ((0xff0000ull >> i) & 1) ? 2 : ((0x3e00ff00f000ull >> i) & 1) ? 4 : 1;
            asm volatile("mbarrier.init.shared::cta.b64 [%0], %1;" :: "r"(bars + 8 * i), "r"(cnt) : "memory");
        }
        asm volatile("fence.mbarrier_init.release.cluster; fence.proxy.async.shared::cta;" ::: "memory");
        if (warp == 12) {
            mbar_expect(bars + 8 * B_FULLW, 16384);
            tma2d(sb + OFF_W, &M.wg, 64 * fb, 0, bars + 8 * B_FULLW);
            tma2d(sb + OFF_W + 8192, &M.wu, 64 * fb, 0, bars + 8 * B_FULLW);
            STAMP(31);
        } else if (warp == 4) {
            mbar_expect(bars + 8 * B_FULLX, 168 * 128);
            tma2d(sb + OFF_X, &M.x[0], 0, TOKG * tg, bars + 8 * B_FULLX);
        }
        if (sb & 1023) __trap();
    }
    __syncthreads();
    if (warp < 8) {
        asm volatile("setmaxnreg.inc.sync.aligned.u32 208;");
        consumer(sb, warp, P, M);
    } else if (warp < 12) {
        asm volatile("setmaxnreg.dec.sync.aligned.u32 72;");
        STAMP(32);
        aux_role(sb, warp - 8, P);
    } else {
        asm volatile("setmaxnreg.dec.sync.aligned.u32 24;");
        const int tau = c >> 2, dg = c & 3;
        if (elect_one()) {
            if (warp < 15) {
                if (warp == 12) {
                    #pragma unroll 1
                    for (int st = 1; st < 8; st++) {
                        const uint32_t s = st & 3, fb_ = bars + 8 * (B_FULLW + s);
                        if (st == 2) mbar_wait(bars + 8 * B_FULLW, 0);
                        mbar_wait(bars + 8 * (B_EMPTYW + s), (st >> 2) ^ 1);
                        mbar_expect(fb_, 16384);
                        tma2d(sb + OFF_W + s * 16384, &M.wg, 64 * fb, 64 * st, fb_);
                        tma2d(sb + OFF_W + s * 16384 + 8192, &M.wu, 64 * fb, 64 * st, fb_);
                    }
                } else {
                    const int V = warp - 13;
                    #pragma unroll 1
                    for (int st = 1 - V; st < 8; st++) {
                        const uint32_t s = 2 * V + (st & 1);
                        if (s == 3 && st == 1) mbar_wait(bars + 8 * B_LNS, 0);
                        mbar_wait(bars + 8 * (B_EMPTYX + s), ((st >> 1) & 1) ^ 1);
                        mbar_expect(bars + 8 * (B_FULLX + s), (168 + 8 * V) * 128);
                        tma2d(sb + OFF_X + s * XBUF, &M.x[V], 64 * st, TOKG * tg + 168 * V, bars + 8 * (B_FULLX + s));
                    }
                }
                if (c < 128 && warp < 14) {
                    if (warp == 13) {
                        mbar_wait(bars + 8 * (B_STG + 1), 0);
                        #pragma unroll 1
                        for (int o = 8 * tau; o < 8 * tau + 8; o += 7) flag_wait(P.flags, F_H + 2 * (o / 43) + ((o % 43) >= 21), 22);
                        mbar_arrive(bars + 8 * B_HF);
                        STAMP(25);
                    }
                    #pragma unroll 1
                    for (int st = 0; st < 22; st += (st < 7 || (st == 7 && warp == 12)) ? 1 : 2) {
                        const int sd = st & 7;
                        const uint32_t fb_ = bars + 8 * (B_FULLD + sd);
                        if (st >= 8) mbar_wait(bars + 8 * (B_EMPTYD + sd), ((st >> 3) & 1) ^ 1);
                        else if (warp == 12 || st >= 6) mbar_wait(bars + 8 * (uint32_t)((0x373623070d060504ull >> (8 * st)) & 0xff), st < 5);
                        if (st >= 10 && st < 21) STAMP2(31 + st);
                        if (st >= 8 || warp == 13) {
                            mbar_expect(fb_, 8192);
                            asm volatile("cp.async.bulk.tensor.5d.shared::cluster.global.mbarrier::complete_tx::bytes [%0], [%1, {%3, %3, %3, %4, %5}], [%2];"
                                :: "r"(sb + h_slot(sd)), "l"(&M.hld), "r"(fb_), "r"(0), "r"(2 * tau), "r"(8 * st) : "memory");
                        }
                        if (st >= 8 || warp == 12) {
                            const uint32_t da = sb + wd_slot(sd);
                            mbar_expect(fb_, 16384);
                            tma2d(da, &M.wd, 128 * dg, 64 * st, fb_);
                            tma2d(da + 8192, &M.wd, 128 * dg + 64, 64 * st, fb_);
                        }
                    }
                } else if (c < 128) {
                    mbar_wait(bars + 8 * B_SST, 0);
                    flag_wait(P.flags, F_S + dg, 64);
                    STAMP(26);
                    mbar_wait(bars + 8 * B_CH0, 0);
                    mbar_expect(bars + 8 * B_XO, 32768);
                    tma2d(sb + OFF_CONV, &M.xo, 128 * dg, 64 * tau, bars + 8 * B_XO);
                    tma2d(sb + OFF_CONV + 8192, &M.xo, 128 * dg + 64, 64 * tau, bars + 8 * B_XO);
                    asm volatile("cp.async.bulk.tensor.5d.shared::cluster.global.mbarrier::complete_tx::bytes [%0], [%1, {%3, %3, %3, %4, %5}], [%2];"
                        :: "r"(sb + wd_slot(6)), "l"(&M.sld), "r"(bars + 8 * B_XO), "r"(0), "r"(8 * dg), "r"(2 * tau) : "memory");
                    mbar_wait(bars + 8 * B_HF, 0);
                    exit_count(P.flags);
                }
            } else {
                mbar_wait(bars + 8 * B_LN, 0);
                STAMP2(0);
                if (c < 128) {
                    #pragma unroll 1
                    for (int i = 0; i < 2; i++)
                        asm volatile("cp.async.bulk.tensor.2d.global.shared::cta.bulk_group [%0, {%2, %3}], [%1];"
                            :: "l"(&M.xt), "r"(sb + OFF_LN + i * 8192), "r"((c & 1) * 1024 + (126 - (c & ~1)) * 8), "r"(256 * i) : "memory");
                    #pragma unroll 1
                    for (int i = 0; i < 2; i++) bulk_store(P.st + 16 * (c & ~1) + 8 * (c & 1) + 16 - 16 * i, sb + OFF_CSUM + 64 * i, 64);
                    asm volatile("cp.async.bulk.prefetch.L2.global [%0], %1;" :: "l"(P.Wd + c * (FF * DM / 128)), "r"(FF * DM / 64) : "memory");
                }
                asm volatile("cp.async.bulk.commit_group; cp.async.bulk.wait_group.read 0;" ::: "memory");
                mbar_arrive(bars + 8 * B_LNS);
                STAMP2(1);
                flag_signal(P.flags, F_A);
                STAMP2(2);
                flag_wait(P.flags, F_A, NCTA);
                STAMP(20);
                mbar_expect(bars + 8 * B_STATS, TOKG * 8);
                bulk_load(sb + OFF_ST, P.st + TOKG * tg, TOKG * 8, bars + 8 * B_STATS);
                if (c < 128) {
                    mbar_wait(bars + 8 * (B_K + 1), 0);
                    fence_async_smem();
                    mbar_expect(bars + 8 * B_U, 8 * 2048);
                    #pragma unroll 1
                    for (int i = 0; i < 8; i++)
                        bulk_load(sb + OFF_CONV + (i >> 1) * CH_STRIDE + CH_U + (i & 1) * UPLANE, P.xnT + 4 * c * 256 + i * 128, 2048, bars + 8 * B_U);
                } else exit_count(P.flags);
                #pragma unroll 1
                for (int V = 0; V < 2; V++) {
                    mbar_wait(bars + 8 * (B_EPI + V), 0);
                    STAMP2(3 + 2 * V);
                    asm volatile("cp.async.bulk.tensor.3d.global.shared::cta.bulk_group [%0, {%2, %3, %4}], [%1];"
                        :: "l"(&M.hst[V]), "r"(sb + OFF_X + V * 2 * XBUF), "r"(0), "r"(43 * tg + 21 * V), "r"(8 * fb) : "memory");
                    flag_signal(P.flags, F_H + 2 * tg + V);
                    mbar_arrive(bars + 8 * (B_STG + V));
                    STAMP2(4 + 2 * V);
                }
                if (c < 128) {
                    #pragma unroll 1
                    for (int V = 0; V < 2; V++) {
                        mbar_wait(bars + 8 * (B_SIG + V), 0);
                        STAMP2(7 + 2 * V);
                        bulk_store(P.S + (2 * c + V) * 1024, sb + OFF_CONV + V * 58368, 8192);
                        flag_signal(P.flags, F_S + (c >> 5));
                        STAMP2(8 + 2 * V);
                    }
                    mbar_arrive(bars + 8 * B_SST);
                }
            }
        }
    }
    asm volatile("nanosleep.u32 0;");
}

typedef CUresult (*EncodeFn)(CUtensorMap*, CUtensorMapDataType, cuuint32_t, void*, const cuuint64_t*, const cuuint64_t*, const cuuint32_t*,
                             const cuuint32_t*, CUtensorMapInterleave, CUtensorMapSwizzle, CUtensorMapL2promotion, CUtensorMapFloatOOBfill);

void make_map(EncodeFn enc, CUtensorMap* m, const void* ptr, int rank, const cuuint64_t* dims, const cuuint64_t* strides, const cuuint32_t* box, bool swz) {
    const cuuint32_t es[5] = {1, 1, 1, 1, 1};
    enc(m, CU_TENSOR_MAP_DATA_TYPE_BFLOAT16, rank, (void*)ptr, dims, strides, box, es, CU_TENSOR_MAP_INTERLEAVE_NONE,
        swz ? CU_TENSOR_MAP_SWIZZLE_128B : CU_TENSOR_MAP_SWIZZLE_NONE, CU_TENSOR_MAP_L2_PROMOTION_L2_128B, CU_TENSOR_MAP_FLOAT_OOB_FILL_NONE);
}
void make_map2(EncodeFn enc, CUtensorMap* m, const void* ptr, cuuint64_t inner, cuuint64_t outer, cuuint32_t rows) {
    const cuuint64_t dims[2] = {inner, outer}, strides[1] = {inner * 2};
    const cuuint32_t box[2] = {64, rows};
    make_map(enc, m, ptr, 2, dims, strides, box, true);
}

}

extern "C" void kernel_launch(void* const* d_in, const int* in_sizes, int n_in, void* d_out, int out_size) {
    (void)in_sizes; (void)n_in; (void)out_size;
    static EncodeFn enc = nullptr;
    static void *hptr, *p_xnT, *p_st, *p_S, *p_flags;
    if (!enc) {
        cudaDriverEntryPointQueryResult qr;
        cudaGetDriverEntryPoint("cuTensorMapEncodeTiled", (void**)&enc, cudaEnableDefault, &qr);
        cudaFuncSetAttribute(fused_kernel, cudaFuncAttributeMaxDynamicSharedMemorySize, SMEM_BYTES);
        cudaGetSymbolAddress(&hptr, g_H); cudaGetSymbolAddress(&p_xnT, g_xnT); cudaGetSymbolAddress(&p_st, g_st);
        cudaGetSymbolAddress(&p_S, g_S); cudaGetSymbolAddress(&p_flags, g_flags);
    }
    Params P;
    P.x = (const __nv_bfloat16*)d_in[0]; P.logA = (const __nv_bfloat16*)d_in[1]; P.Aim = (const __nv_bfloat16*)d_in[2];
    P.Cr = (const __nv_bfloat16*)d_in[3]; P.Ci = (const __nv_bfloat16*)d_in[4]; P.logdt = (const __nv_bfloat16*)d_in[5];
    P.Dskip = (const __nv_bfloat16*)d_in[6];
    P.Wd = (const __nv_bfloat16*)d_in[10]; P.xnT = (uint4*)p_xnT; P.st = (float2*)p_st; P.S = (uint2*)p_S; P.flags = (unsigned*)p_flags;
    Maps M;
    make_map2(enc, &M.x[0], d_in[0], DM, SEQ, 168); make_map2(enc, &M.x[1], d_in[0], DM, SEQ, 176);
    make_map2(enc, &M.xo, d_in[0], DM, SEQ, 64);    make_map2(enc, &M.out, d_out, DM, SEQ, 64);
    make_map2(enc, &M.wg, d_in[8], FF, DM, 64);     make_map2(enc, &M.wu, d_in[9], FF, DM, 64);
    make_map2(enc, &M.wd, d_in[10], DM, FF, 64);
    for (int v = 0; v < 2; v++) {
        const cuuint64_t dims[3] = {64, 256, 172}, strides[2] = {128, 32768};
        const cuuint32_t box[3] = {64, (cuuint32_t)(21 + v), 8};
        make_map(enc, &M.hst[v], hptr, 3, dims, strides, box, false);
    }
    {
        const cuuint64_t dims[2] = {2048, 512}, strides[1] = {4096};
        const cuuint32_t box[2] = {16, 256};
        make_map(enc, &M.xt, p_xnT, 2, dims, strides, box, false);
    }
    {
        const cuuint64_t dims[5] = {64, 2, 4, 32, 64}, strides[4] = {4 * 8192, 8192, 8 * 8192, 128};
        const cuuint32_t box[5] = {64, 2, 4, 8, 2};
        make_map(enc, &M.sld, p_S, 5, dims, strides, box, true);
    }
    {
        const cuuint64_t dims[5] = {64, 2, 2, 64, 172}, strides[4] = {256, 128, 512, 32768};
        const cuuint32_t box[5] = {64, 2, 2, 2, 8};
        make_map(enc, &M.hld, hptr, 5, dims, strides, box, false);
    }
    fused_kernel<<<NCTA, 512, SMEM_BYTES>>>(P, M);
}
```

```cpp
#include <cuda_runtime.h>
#include <cuda_bf16.h>
#include <cuda.h>
#include <stdint.h>

#define PROF 0

namespace {

constexpr int SEQ = 2048, DM = 512, FF = 1376;
constexpr int NCTA = 132;
#define HOLD0 4
#define HOLD1 7
#define LAG 2
constexpr int TOKG = 344;

constexpr uint32_t OFF_W = 0;
constexpr uint32_t XBUF = 22528;
constexpr uint32_t OFF_X = 65536;
constexpr uint32_t OFF_CONV = 155648;
constexpr uint32_t CH_STRIDE = 17536;
constexpr uint32_t CH_T = 0;
constexpr uint32_t CH_A3 = 8448;
constexpr uint32_t CH_B3 = 12544;
constexpr uint32_t CH_U = 13312;
constexpr uint32_t CH_G = CH_A3 + 2064;
constexpr uint32_t UPLANE = 2112;
constexpr uint32_t OFF_LN = OFF_X + 3 * XBUF;
constexpr uint32_t OFF_SST = 60416;
constexpr uint32_t OFF_ST = 225792;
constexpr uint32_t OFF_CSUM = 228544;
constexpr uint32_t OFF_BAR = 229056;
constexpr uint32_t SMEM_BYTES = 229568;

enum {
    B_FULLW = 0, B_EMPTYW = 4, B_FULLX = 8, B_EMPTYX = 12, B_FULLD = 16, B_EMPTYD = 24,
    B_U = 32, B_XO = 33, B_S = 34, B_STG = 35, B_HF = 37, B_STATS = 38, B_LNS = 39, B_SST = 40,
    B_LNX = 41, B_GO = 42, B_CH0 = 43, B_K = 44,
    B_CONV = 46, B_LN = 50, B_CS = 51, B_EPI = 52, B_SIG = 54,
    B_COUNT = 56
};
enum { F_A = 0, F_H = 1, F_S = 13, F_EXIT = 17, F_COUNT = 18 };

__device__ uint4 g_xnT[DM * 256];
__device__ float2 g_st[6 * TOKG];
__device__ uint4 g_H[172 * 256 * 8];
__device__ uint2 g_S[256 * 1024];
__device__ unsigned g_flags[F_COUNT * 32];
#define STAMP(i) do {} while (0)
#define GSTAMP(i) do {} while (0)
#define STAMP2(i) do {} while (0)

__device__ __forceinline__ uint32_t smem_u32(const void* p) { return (uint32_t)__cvta_generic_to_shared(p); }
__device__ __forceinline__ void mbar_expect(uint32_t bar, uint32_t bytes) { asm volatile("mbarrier.arrive.expect_tx.shared::cta.b64 _, [%0], %1;" :: "r"(bar), "r"(bytes) : "memory"); }
__device__ __forceinline__ void mbar_arrive(uint32_t bar) { asm volatile("mbarrier.arrive.shared::cta.b64 _, [%0];" :: "r"(bar) : "memory"); }
__device__ __forceinline__ void mbar_wait(uint32_t bar, uint32_t parity) {
    asm volatile("{.reg .pred p; .reg .u32 n; mov.u32 n, 0x20000;\n"
                 "LW: mbarrier.try_wait.parity.shared::cta.b64 p, [%0], %1;\n"
                 "sub.u32 n, n, 1; setp.eq.or.u32 p, n, 0, p; @!p bra LW;}" :: "r"(bar), "r"(parity) : "memory");
}
__device__ __forceinline__ bool elect_one() { uint32_t p; asm volatile("{.reg .pred P; elect.sync _|P, 0xffffffff; selp.u32 %0, 1, 0, P;}" : "=r"(p)); return p; }
__device__ __forceinline__ void tma2d(uint32_t dst, const CUtensorMap* m, int c0, int c1, uint32_t bar) {
    asm volatile("cp.async.bulk.tensor.2d.shared::cluster.global.mbarrier::complete_tx::bytes [%0], [%1, {%3, %4}], [%2];"
        :: "r"(dst), "l"(m), "r"(bar), "r"(c0), "r"(c1) : "memory");
}
__device__ __forceinline__ void bulk_load(uint32_t dst, const void* src, uint32_t bytes, uint32_t bar) {
    asm volatile("cp.async.bulk.shared::cluster.global.mbarrier::complete_tx::bytes [%0], [%1], %2, [%3];" :: "r"(dst), "l"(src), "r"(bytes), "r"(bar) : "memory");
}
__device__ __forceinline__ void bulk_store(void* dst, uint32_t src, uint32_t bytes) {
    asm volatile("cp.async.bulk.global.shared::cta.bulk_group [%0], [%1], %2;" :: "l"(dst), "r"(src), "r"(bytes) : "memory");
}
__device__ __forceinline__ void fence_async_smem() { asm volatile("fence.proxy.async.shared::cta;" ::: "memory"); }
__device__ __forceinline__ void flag_wait(unsigned* g_flags, int f, unsigned target) {
    asm volatile("{.reg .pred p; .reg .u32 n, v; mov.u32 n, 0x40000;\n"
                 "LF: ld.acquire.gpu.global.u32 v, [%0]; setp.ge.u32 p, v, %1; @p bra LD;\n"
                 "sub.u32 n, n, 1; setp.ne.u32 p, n, 0; @p bra LF; trap;\nLD: }"
                 :: "l"(g_flags + f * 32), "r"(target) : "memory");
}
__device__ __forceinline__ void flag_signal(unsigned* g_flags, int f) {
    asm volatile("cp.async.bulk.commit_group; cp.async.bulk.wait_group 0; red.relaxed.gpu.global.add.u32 [%0], 1;" :: "l"(g_flags + f * 32) : "memory");
}
__device__ __forceinline__ void exit_count(unsigned* g_flags) {
    if (atomicAdd(g_flags + F_EXIT * 32, 1u) == NCTA - 1) {
        #pragma unroll 1
        for (int i = 0; i < F_COUNT; i++) g_flags[i * 32] = 0;
    }
}
__device__ __forceinline__ void bar_sync(int id) { asm volatile("bar.sync %0, 128;" :: "r"(id) : "memory"); }
__device__ __forceinline__ uint64_t mkdesc(uint32_t addr, uint32_t lbo, uint32_t sbo, uint32_t swz) {
    return (uint64_t)((addr >> 4) | ((lbo >> 4) << 16)) | ((uint64_t)((sbo >> 4) | (swz << 30)) << 32);
}
#define WG_FENCE() asm volatile("wgmma.fence.sync.aligned;" ::: "memory")
#define WG_COMMIT() asm volatile("wgmma.commit_group.sync.aligned;" ::: "memory")
#define WG_WAIT(n) asm volatile("wgmma.wait_group.sync.aligned " #n ";" ::: "memory")
template <int N> __device__ __forceinline__ void fence_acc(float (&d)[N]) {
    #pragma unroll
    for (int i = 0; i < N; i++) asm volatile("" : "+f"(d[i]) :: "memory");
}
template <int N> __device__ __forceinline__ void define_acc(float (&d)[N]) {
    #pragma unroll
    for (int i = 0; i < N; i++) asm volatile("" : "=f"(d[i]));
}
__device__ __forceinline__ uint32_t pack2(float lo, float hi) { uint32_t r; asm("cvt.rn.bf16x2.f32 %0, %1, %2;" : "=r"(r) : "f"(hi), "f"(lo)); return r; }
__device__ __forceinline__ float bf_lo(uint32_t v) { return __uint_as_float(v << 16); }
__device__ __forceinline__ float bf_hi(uint32_t v) { return __uint_as_float(v & 0xffff0000u); }
__device__ __forceinline__ float bf_round(float v) { return bf_hi(pack2(0.f, v)); }
__device__ __forceinline__ float tanh_fast(float v) { float r; asm("tanh.approx.f32 %0, %1;" : "=f"(r) : "f"(v)); return r; }
__device__ __forceinline__ float ex2(float v) { float r; asm("ex2.approx.ftz.f32 %0, %1;" : "=f"(r) : "f"(v)); return r; }
__device__ __forceinline__ uint4 lds128(uint32_t a) { uint4 v; asm volatile("ld.shared.v4.b32 {%0,%1,%2,%3}, [%4];" : "=r"(v.x), "=r"(v.y), "=r"(v.z), "=r"(v.w) : "r"(a)); return v; }
__device__ __forceinline__ uint2 lds64(uint32_t a) { uint2 v; asm volatile("ld.shared.v2.b32 {%0,%1}, [%2];" : "=r"(v.x), "=r"(v.y) : "r"(a)); return v; }
__device__ __forceinline__ float ldsf(uint32_t a) { float v; asm volatile("ld.shared.f32 %0, [%1];" : "=f"(v) : "r"(a)); return v; }
__device__ __forceinline__ void sts128(uint32_t a, uint32_t x, uint32_t y, uint32_t z, uint32_t w) { asm volatile("st.shared.v4.b32 [%0], {%1,%2,%3,%4};" :: "r"(a), "r"(x), "r"(y), "r"(z), "r"(w) : "memory"); }
__device__ __forceinline__ void sts64(uint32_t a, uint32_t x, uint32_t y) { asm volatile("st.shared.v2.b32 [%0], {%1,%2};" :: "r"(a), "r"(x), "r"(y) : "memory"); }
__device__ __forceinline__ void stsf(uint32_t a, float x) { asm volatile("st.shared.f32 [%0], %1;" :: "r"(a), "f"(x) : "memory"); }
__device__ __forceinline__ void sts16(uint32_t a, uint32_t x) { asm volatile("st.shared.b16 [%0], %1;" :: "r"(a), "h"((unsigned short)x) : "memory"); }
__device__ __forceinline__ void stsm4(uint32_t a, uint32_t r0, uint32_t r1, uint32_t r2, uint32_t r3) {
    asm volatile("stmatrix.sync.aligned.m8n8.x4.shared.b16 [%0], {%1,%2,%3,%4};" :: "r"(a), "r"(r0), "r"(r1), "r"(r2), "r"(r3) : "memory");
}
__device__ __forceinline__ void ldsm4(uint32_t (&r)[4], uint32_t a) {
    asm volatile("ldmatrix.sync.aligned.m8n8.x4.shared.b16 {%0,%1,%2,%3}, [%4];" : "=r"(r[0]), "=r"(r[1]), "=r"(r[2]), "=r"(r[3]) : "r"(a) : "memory");
}
#define FU(x) __float_as_uint(x)
#define UF(x) __uint_as_float(x)
__device__ __forceinline__ uint32_t wd_slot(int s) { return (uint32_t)((0xbba8403056201000ull >> (8 * s)) & 0xff) << 10; }
__device__ __forceinline__ uint32_t h_slot(int s) { return (uint32_t)((0xcba0908880787068ull >> (8 * s)) & 0xff) << 10; }

template<int N> __device__ __forceinline__ void wg_rs(float (&d)[64], uint32_t a0, uint32_t a1, uint32_t a2, uint32_t a3, uint64_t db);
template<> __device__ __forceinline__ void wg_rs<128>(float (&d)[64], uint32_t a0, uint32_t a1, uint32_t a2, uint32_t a3, uint64_t db) {
  asm volatile("{.reg .pred p; setp.ne.b32 p, 1, 0; wgmma.mma_async.sync.aligned.m64n128k16.f32.bf16.bf16 {%0,%1,%2,%3,%4,%5,%6,%7,%8,%9,%10,%11,%12,%13,%14,%15,%16,%17,%18,%19,%20,%21,%22,%23,%24,%25,%26,%27,%28,%29,%30,%31,%32,%33,%34,%35,%36,%37,%38,%39,%40,%41,%42,%43,%44,%45,%46,%47,%48,%49,%50,%51,%52,%53,%54,%55,%56,%57,%58,%59,%60,%61,%62,%63}, {%64,%65,%66,%67}, %68, p, 1, 1, 0;}"
    : "+f"(d[0]),"+f"(d[1]),"+f"(d[2]),"+f"(d[3]),"+f"(d[4]),"+f"(d[5]),"+f"(d[6]),"+f"(d[7]),"+f"(d[8]),"+f"(d[9]),"+f"(d[10]),"+f"(d[11]),"+f"(d[12]),"+f"(d[13]),"+f"(d[14]),"+f"(d[15]),"+f"(d[16]),"+f"(d[17]),"+f"(d[18]),"+f"(d[19]),"+f"(d[20]),"+f"(d[21]),"+f"(d[22]),"+f"(d[23]),"+f"(d[24]),"+f"(d[25]),"+f"(d[26]),"+f"(d[27]),"+f"(d[28]),"+f"(d[29]),"+f"(d[30]),"+f"(d[31]),"+f"(d[32]),"+f"(d[33]),"+f"(d[34]),"+f"(d[35]),"+f"(d[36]),"+f"(d[37]),"+f"(d[38]),"+f"(d[39]),"+f"(d[40]),"+f"(d[41]),"+f"(d[42]),"+f"(d[43]),"+f"(d[44]),"+f"(d[45]),"+f"(d[46]),"+f"(d[47]),"+f"(d[48]),"+f"(d[49]),"+f"(d[50]),"+f"(d[51]),"+f"(d[52]),"+f"(d[53]),"+f"(d[54]),"+f"(d[55]),"+f"(d[56]),"+f"(d[57]),"+f"(d[58]),"+f"(d[59]),"+f"(d[60]),"+f"(d[61]),"+f"(d[62]),"+f"(d[63]) : "r"(a0), "r"(a1), "r"(a2), "r"(a3), "l"(db));
}
template<> __device__ __forceinline__ void wg_rs<120>(float (&d)[64], uint32_t a0, uint32_t a1, uint32_t a2, uint32_t a3, uint64_t db) {
  asm volatile("{.reg .pred p; setp.ne.b32 p, 1, 0; wgmma.mma_async.sync.aligned.m64n120k16.f32.bf16.bf16 {%0,%1,%2,%3,%4,%5,%6,%7,%8,%9,%10,%11,%12,%13,%14,%15,%16,%17,%18,%19,%20,%21,%22,%23,%24,%25,%26,%27,%28,%29,%30,%31,%32,%33,%34,%35,%36,%37,%38,%39,%40,%41,%42,%43,%44,%45,%46,%47,%48,%49,%50,%51,%52,%53,%54,%55,%56,%57,%58,%59}, {%60,%61,%62,%63}, %64, p, 1, 1, 0;}"
    : "+f"(d[0]),"+f"(d[1]),"+f"(d[2]),"+f"(d[3]),"+f"(d[4]),"+f"(d[5]),"+f"(d[6]),"+f"(d[7]),"+f"(d[8]),"+f"(d[9]),"+f"(d[10]),"+f"(d[11]),"+f"(d[12]),"+f"(d[13]),"+f"(d[14]),"+f"(d[15]),"+f"(d[16]),"+f"(d[17]),"+f"(d[18]),"+f"(d[19]),"+f"(d[20]),"+f"(d[21]),"+f"(d[22]),"+f"(d[23]),"+f"(d[24]),"+f"(d[25]),"+f"(d[26]),"+f"(d[27]),"+f"(d[28]),"+f"(d[29]),"+f"(d[30]),"+f"(d[31]),"+f"(d[32]),"+f"(d[33]),"+f"(d[34]),"+f"(d[35]),"+f"(d[36]),"+f"(d[37]),"+f"(d[38]),"+f"(d[39]),"+f"(d[40]),"+f"(d[41]),"+f"(d[42]),"+f"(d[43]),"+f"(d[44]),"+f"(d[45]),"+f"(d[46]),"+f"(d[47]),"+f"(d[48]),"+f"(d[49]),"+f"(d[50]),"+f"(d[51]),"+f"(d[52]),"+f"(d[53]),"+f"(d[54]),"+f"(d[55]),"+f"(d[56]),"+f"(d[57]),"+f"(d[58]),"+f"(d[59]) : "r"(a0), "r"(a1), "r"(a2), "r"(a3), "l"(db));
}
template<> __device__ __forceinline__ void wg_rs<112>(float (&d)[64], uint32_t a0, uint32_t a1, uint32_t a2, uint32_t a3, uint64_t db) {
  asm volatile("{.reg .pred p; setp.ne.b32 p, 1, 0; wgmma.mma_async.sync.aligned.m64n112k16.f32.bf16.bf16 {%0,%1,%2,%3,%4,%5,%6,%7,%8,%9,%10,%11,%12,%13,%14,%15,%16,%17,%18,%19,%20,%21,%22,%23,%24,%25,%26,%27,%28,%29,%30,%31,%32,%33,%34,%35,%36,%37,%38,%39,%40,%41,%42,%43,%44,%45,%46,%47,%48,%49,%50,%51,%52,%53,%54,%55}, {%56,%57,%58,%59}, %60, p, 1, 1, 0;}"
    : "+f"(d[0]),"+f"(d[1]),"+f"(d[2]),"+f"(d[3]),"+f"(d[4]),"+f"(d[5]),"+f"(d[6]),"+f"(d[7]),"+f"(d[8]),"+f"(d[9]),"+f"(d[10]),"+f"(d[11]),"+f"(d[12]),"+f"(d[13]),"+f"(d[14]),"+f"(d[15]),"+f"(d[16]),"+f"(d[17]),"+f"(d[18]),"+f"(d[19]),"+f"(d[20]),"+f"(d[21]),"+f"(d[22]),"+f"(d[23]),"+f"(d[24]),"+f"(d[25]),"+f"(d[26]),"+f"(d[27]),"+f"(d[28]),"+f"(d[29]),"+f"(d[30]),"+f"(d[31]),"+f"(d[32]),"+f"(d[33]),"+f"(d[34]),"+f"(d[35]),"+f"(d[36]),"+f"(d[37]),"+f"(d[38]),"+f"(d[39]),"+f"(d[40]),"+f"(d[41]),"+f"(d[42]),"+f"(d[43]),"+f"(d[44]),"+f"(d[45]),"+f"(d[46]),"+f"(d[47]),"+f"(d[48]),"+f"(d[49]),"+f"(d[50]),"+f"(d[51]),"+f"(d[52]),"+f"(d[53]),"+f"(d[54]),"+f"(d[55]) : "r"(a0), "r"(a1), "r"(a2), "r"(a3), "l"(db));
}
template<> __device__ __forceinline__ void wg_rs<104>(float (&d)[64], uint32_t a0, uint32_t a1, uint32_t a2, uint32_t a3, uint64_t db) {
  asm volatile("{.reg .pred p; setp.ne.b32 p, 1, 0; wgmma.mma_async.sync.aligned.m64n104k16.f32.bf16.bf16 {%0,%1,%2,%3,%4,%5,%6,%7,%8,%9,%10,%11,%12,%13,%14,%15,%16,%17,%18,%19,%20,%21,%22,%23,%24,%25,%26,%27,%28,%29,%30,%31,%32,%33,%34,%35,%36,%37,%38,%39,%40,%41,%42,%43,%44,%45,%46,%47,%48,%49,%50,%51}, {%52,%53,%54,%55}, %56, p, 1, 1, 0;}"
    : "+f"(d[0]),"+f"(d[1]),"+f"(d[2]),"+f"(d[3]),"+f"(d[4]),"+f"(d[5]),"+f"(d[6]),"+f"(d[7]),"+f"(d[8]),"+f"(d[9]),"+f"(d[10]),"+f"(d[11]),"+f"(d[12]),"+f"(d[13]),"+f"(d[14]),"+f"(d[15]),"+f"(d[16]),"+f"(d[17]),"+f"(d[18]),"+f"(d[19]),"+f"(d[20]),"+f"(d[21]),"+f"(d[22]),"+f"(d[23]),"+f"(d[24]),"+f"(d[25]),"+f"(d[26]),"+f"(d[27]),"+f"(d[28]),"+f"(d[29]),"+f"(d[30]),"+f"(d[31]),"+f"(d[32]),"+f"(d[33]),"+f"(d[34]),"+f"(d[35]),"+f"(d[36]),"+f"(d[37]),"+f"(d[38]),"+f"(d[39]),"+f"(d[40]),"+f"(d[41]),"+f"(d[42]),"+f"(d[43]),"+f"(d[44]),"+f"(d[45]),"+f"(d[46]),"+f"(d[47]),"+f"(d[48]),"+f"(d[49]),"+f"(d[50]),"+f"(d[51]) : "r"(a0), "r"(a1), "r"(a2), "r"(a3), "l"(db));
}
template<> __device__ __forceinline__ void wg_rs<96>(float (&d)[64], uint32_t a0, uint32_t a1, uint32_t a2, uint32_t a3, uint64_t db) {
  asm volatile("{.reg .pred p; setp.ne.b32 p, 1, 0; wgmma.mma_async.sync.aligned.m64n96k16.f32.bf16.bf16 {%0,%1,%2,%3,%4,%5,%6,%7,%8,%9,%10,%11,%12,%13,%14,%15,%16,%17,%18,%19,%20,%21,%22,%23,%24,%25,%26,%27,%28,%29,%30,%31,%32,%33,%34,%35,%36,%37,%38,%39,%40,%41,%42,%43,%44,%45,%46,%47}, {%48,%49,%50,%51}, %52, p, 1, 1, 0;}"
    : "+f"(d[0]),"+f"(d[1]),"+f"(d[2]),"+f"(d[3]),"+f"(d[4]),"+f"(d[5]),"+f"(d[6]),"+f"(d[7]),"+f"(d[8]),"+f"(d[9]),"+f"(d[10]),"+f"(d[11]),"+f"(d[12]),"+f"(d[13]),"+f"(d[14]),"+f"(d[15]),"+f"(d[16]),"+f"(d[17]),"+f"(d[18]),"+f"(d[19]),"+f"(d[20]),"+f"(d[21]),"+f"(d[22]),"+f"(d[23]),"+f"(d[24]),"+f"(d[25]),"+f"(d[26]),"+f"(d[27]),"+f"(d[28]),"+f"(d[29]),"+f"(d[30]),"+f"(d[31]),"+f"(d[32]),"+f"(d[33]),"+f"(d[34]),"+f"(d[35]),"+f"(d[36]),"+f"(d[37]),"+f"(d[38]),"+f"(d[39]),"+f"(d[40]),"+f"(d[41]),"+f"(d[42]),"+f"(d[43]),"+f"(d[44]),"+f"(d[45]),"+f"(d[46]),"+f"(d[47]) : "r"(a0), "r"(a1), "r"(a2), "r"(a3), "l"(db));
}
template<> __device__ __forceinline__ void wg_rs<88>(float (&d)[64], uint32_t a0, uint32_t a1, uint32_t a2, uint32_t a3, uint64_t db) {
  asm volatile("{.reg .pred p; setp.ne.b32 p, 1, 0; wgmma.mma_async.sync.aligned.m64n88k16.f32.bf16.bf16 {%0,%1,%2,%3,%4,%5,%6,%7,%8,%9,%10,%11,%12,%13,%14,%15,%16,%17,%18,%19,%20,%21,%22,%23,%24,%25,%26,%27,%28,%29,%30,%31,%32,%33,%34,%35,%36,%37,%38,%39,%40,%41,%42,%43}, {%44,%45,%46,%47}, %48, p, 1, 1, 0;}"
    : "+f"(d[0]),"+f"(d[1]),"+f"(d[2]),"+f"(d[3]),"+f"(d[4]),"+f"(d[5]),"+f"(d[6]),"+f"(d[7]),"+f"(d[8]),"+f"(d[9]),"+f"(d[10]),"+f"(d[11]),"+f"(d[12]),"+f"(d[13]),"+f"(d[14]),"+f"(d[15]),"+f"(d[16]),"+f"(d[17]),"+f"(d[18]),"+f"(d[19]),"+f"(d[20]),"+f"(d[21]),"+f"(d[22]),"+f"(d[23]),"+f"(d[24]),"+f"(d[25]),"+f"(d[26]),"+f"(d[27]),"+f"(d[28]),"+f"(d[29]),"+f"(d[30]),"+f"(d[31]),"+f"(d[32]),"+f"(d[33]),"+f"(d[34]),"+f"(d[35]),"+f"(d[36]),"+f"(d[37]),"+f"(d[38]),"+f"(d[39]),"+f"(d[40]),"+f"(d[41]),"+f"(d[42]),"+f"(d[43]) : "r"(a0), "r"(a1), "r"(a2), "r"(a3), "l"(db));
}
template<> __device__ __forceinline__ void wg_rs<80>(float (&d)[64], uint32_t a0, uint32_t a1, uint32_t a2, uint32_t a3, uint64_t db) {
  asm volatile("{.reg .pred p; setp.ne.b32 p, 1, 0; wgmma.mma_async.sync.aligned.m64n80k16.f32.bf16.bf16 {%0,%1,%2,%3,%4,%5,%6,%7,%8,%9,%10,%11,%12,%13,%14,%15,%16,%17,%18,%19,%20,%21,%22,%23,%24,%25,%26,%27,%28,%29,%30,%31,%32,%33,%34,%35,%36,%37,%38,%39}, {%40,%41,%42,%43}, %44, p, 1, 1, 0;}"
    : "+f"(d[0]),"+f"(d[1]),"+f"(d[2]),"+f"(d[3]),"+f"(d[4]),"+f"(d[5]),"+f"(d[6]),"+f"(d[7]),"+f"(d[8]),"+f"(d[9]),"+f"(d[10]),"+f"(d[11]),"+f"(d[12]),"+f"(d[13]),"+f"(d[14]),"+f"(d[15]),"+f"(d[16]),"+f"(d[17]),"+f"(d[18]),"+f"(d[19]),"+f"(d[20]),"+f"(d[21]),"+f"(d[22]),"+f"(d[23]),"+f"(d[24]),"+f"(d[25]),"+f"(d[26]),"+f"(d[27]),"+f"(d[28]),"+f"(d[29]),"+f"(d[30]),"+f"(d[31]),"+f"(d[32]),"+f"(d[33]),"+f"(d[34]),"+f"(d[35]),"+f"(d[36]),"+f"(d[37]),"+f"(d[38]),"+f"(d[39]) : "r"(a0), "r"(a1), "r"(a2), "r"(a3), "l"(db));
}
template<> __device__ __forceinline__ void wg_rs<72>(float (&d)[64], uint32_t a0, uint32_t a1, uint32_t a2, uint32_t a3, uint64_t db) {
  asm volatile("{.reg .pred p; setp.ne.b32 p, 1, 0; wgmma.mma_async.sync.aligned.m64n72k16.f32.bf16.bf16 {%0,%1,%2,%3,%4,%5,%6,%7,%8,%9,%10,%11,%12,%13,%14,%15,%16,%17,%18,%19,%20,%21,%22,%23,%24,%25,%26,%27,%28,%29,%30,%31,%32,%33,%34,%35}, {%36,%37,%38,%39}, %40, p, 1, 1, 0;}"
    : "+f"(d[0]),"+f"(d[1]),"+f"(d[2]),"+f"(d[3]),"+f"(d[4]),"+f"(d[5]),"+f"(d[6]),"+f"(d[7]),"+f"(d[8]),"+f"(d[9]),"+f"(d[10]),"+f"(d[11]),"+f"(d[12]),"+f"(d[13]),"+f"(d[14]),"+f"(d[15]),"+f"(d[16]),"+f"(d[17]),"+f"(d[18]),"+f"(d[19]),"+f"(d[20]),"+f"(d[21]),"+f"(d[22]),"+f"(d[23]),"+f"(d[24]),"+f"(d[25]),"+f"(d[26]),"+f"(d[27]),"+f"(d[28]),"+f"(d[29]),"+f"(d[30]),"+f"(d[31]),"+f"(d[32]),"+f"(d[33]),"+f"(d[34]),"+f"(d[35]) : "r"(a0), "r"(a1), "r"(a2), "r"(a3), "l"(db));
}
template<> __device__ __forceinline__ void wg_rs<64>(float (&d)[64], uint32_t a0, uint32_t a1, uint32_t a2, uint32_t a3, uint64_t db) {
  asm volatile("{.reg .pred p; setp.ne.b32 p, 1, 0; wgmma.mma_async.sync.aligned.m64n64k16.f32.bf16.bf16 {%0,%1,%2,%3,%4,%5,%6,%7,%8,%9,%10,%11,%12,%13,%14,%15,%16,%17,%18,%19,%20,%21,%22,%23,%24,%25,%26,%27,%28,%29,%30,%31}, {%32,%33,%34,%35}, %36, p, 1, 1, 0;}"
    : "+f"(d[0]),"+f"(d[1]),"+f"(d[2]),"+f"(d[3]),"+f"(d[4]),"+f"(d[5]),"+f"(d[6]),"+f"(d[7]),"+f"(d[8]),"+f"(d[9]),"+f"(d[10]),"+f"(d[11]),"+f"(d[12]),"+f"(d[13]),"+f"(d[14]),"+f"(d[15]),"+f"(d[16]),"+f"(d[17]),"+f"(d[18]),"+f"(d[19]),"+f"(d[20]),"+f"(d[21]),"+f"(d[22]),"+f"(d[23]),"+f"(d[24]),"+f"(d[25]),"+f"(d[26]),"+f"(d[27]),"+f"(d[28]),"+f"(d[29]),"+f"(d[30]),"+f"(d[31]) : "r"(a0), "r"(a1), "r"(a2), "r"(a3), "l"(db));
}
__device__ __forceinline__ void wg_rs_first(float (&d)[64], uint32_t a0, uint32_t a1, uint32_t a2, uint32_t a3, uint64_t db) {
  asm volatile("{.reg .pred p; setp.ne.b32 p, 0, 0; wgmma.mma_async.sync.aligned.m64n128k16.f32.bf16.bf16 {%0,%1,%2,%3,%4,%5,%6,%7,%8,%9,%10,%11,%12,%13,%14,%15,%16,%17,%18,%19,%20,%21,%22,%23,%24,%25,%26,%27,%28,%29,%30,%31,%32,%33,%34,%35,%36,%37,%38,%39,%40,%41,%42,%43,%44,%45,%46,%47,%48,%49,%50,%51,%52,%53,%54,%55,%56,%57,%58,%59,%60,%61,%62,%63}, {%64,%65,%66,%67}, %68, p, 1, 1, 0;}"
    : "=f"(d[0]),"=f"(d[1]),"=f"(d[2]),"=f"(d[3]),"=f"(d[4]),"=f"(d[5]),"=f"(d[6]),"=f"(d[7]),"=f"(d[8]),"=f"(d[9]),"=f"(d[10]),"=f"(d[11]),"=f"(d[12]),"=f"(d[13]),"=f"(d[14]),"=f"(d[15]),"=f"(d[16]),"=f"(d[17]),"=f"(d[18]),"=f"(d[19]),"=f"(d[20]),"=f"(d[21]),"=f"(d[22]),"=f"(d[23]),"=f"(d[24]),"=f"(d[25]),"=f"(d[26]),"=f"(d[27]),"=f"(d[28]),"=f"(d[29]),"=f"(d[30]),"=f"(d[31]),"=f"(d[32]),"=f"(d[33]),"=f"(d[34]),"=f"(d[35]),"=f"(d[36]),"=f"(d[37]),"=f"(d[38]),"=f"(d[39]),"=f"(d[40]),"=f"(d[41]),"=f"(d[42]),"=f"(d[43]),"=f"(d[44]),"=f"(d[45]),"=f"(d[46]),"=f"(d[47]),"=f"(d[48]),"=f"(d[49]),"=f"(d[50]),"=f"(d[51]),"=f"(d[52]),"=f"(d[53]),"=f"(d[54]),"=f"(d[55]),"=f"(d[56]),"=f"(d[57]),"=f"(d[58]),"=f"(d[59]),"=f"(d[60]),"=f"(d[61]),"=f"(d[62]),"=f"(d[63]) : "r"(a0), "r"(a1), "r"(a2), "r"(a3), "l"(db));
}
__device__ __forceinline__ void wg_tt128(float (&d)[64], uint64_t da, uint64_t db, int sc) {
  asm volatile("{.reg .pred p; setp.ne.b32 p, %66, 0; wgmma.mma_async.sync.aligned.m64n128k16.f32.bf16.bf16 {%0,%1,%2,%3,%4,%5,%6,%7,%8,%9,%10,%11,%12,%13,%14,%15,%16,%17,%18,%19,%20,%21,%22,%23,%24,%25,%26,%27,%28,%29,%30,%31,%32,%33,%34,%35,%36,%37,%38,%39,%40,%41,%42,%43,%44,%45,%46,%47,%48,%49,%50,%51,%52,%53,%54,%55,%56,%57,%58,%59,%60,%61,%62,%63}, %64, %65, p, 1, 1, 1, 1;}"
    : "+f"(d[0]),"+f"(d[1]),"+f"(d[2]),"+f"(d[3]),"+f"(d[4]),"+f"(d[5]),"+f"(d[6]),"+f"(d[7]),"+f"(d[8]),"+f"(d[9]),"+f"(d[10]),"+f"(d[11]),"+f"(d[12]),"+f"(d[13]),"+f"(d[14]),"+f"(d[15]),"+f"(d[16]),"+f"(d[17]),"+f"(d[18]),"+f"(d[19]),"+f"(d[20]),"+f"(d[21]),"+f"(d[22]),"+f"(d[23]),"+f"(d[24]),"+f"(d[25]),"+f"(d[26]),"+f"(d[27]),"+f"(d[28]),"+f"(d[29]),"+f"(d[30]),"+f"(d[31]),"+f"(d[32]),"+f"(d[33]),"+f"(d[34]),"+f"(d[35]),"+f"(d[36]),"+f"(d[37]),"+f"(d[38]),"+f"(d[39]),"+f"(d[40]),"+f"(d[41]),"+f"(d[42]),"+f"(d[43]),"+f"(d[44]),"+f"(d[45]),"+f"(d[46]),"+f"(d[47]),"+f"(d[48]),"+f"(d[49]),"+f"(d[50]),"+f"(d[51]),"+f"(d[52]),"+f"(d[53]),"+f"(d[54]),"+f"(d[55]),"+f"(d[56]),"+f"(d[57]),"+f"(d[58]),"+f"(d[59]),"+f"(d[60]),"+f"(d[61]),"+f"(d[62]),"+f"(d[63]) : "l"(da), "l"(db), "r"(sc));
}
__device__ __forceinline__ void wg_tt64(float (&d)[64], uint64_t da, uint64_t db, int sc) {
  asm volatile("{.reg .pred p; setp.ne.b32 p, %34, 0; wgmma.mma_async.sync.aligned.m64n64k16.f32.bf16.bf16 {%0,%1,%2,%3,%4,%5,%6,%7,%8,%9,%10,%11,%12,%13,%14,%15,%16,%17,%18,%19,%20,%21,%22,%23,%24,%25,%26,%27,%28,%29,%30,%31}, %32, %33, p, 1, 1, 1, 1;}"
    : "+f"(d[0]),"+f"(d[1]),"+f"(d[2]),"+f"(d[3]),"+f"(d[4]),"+f"(d[5]),"+f"(d[6]),"+f"(d[7]),"+f"(d[8]),"+f"(d[9]),"+f"(d[10]),"+f"(d[11]),"+f"(d[12]),"+f"(d[13]),"+f"(d[14]),"+f"(d[15]),"+f"(d[16]),"+f"(d[17]),"+f"(d[18]),"+f"(d[19]),"+f"(d[20]),"+f"(d[21]),"+f"(d[22]),"+f"(d[23]),"+f"(d[24]),"+f"(d[25]),"+f"(d[26]),"+f"(d[27]),"+f"(d[28]),"+f"(d[29]),"+f"(d[30]),"+f"(d[31]) : "l"(da), "l"(db), "r"(sc));
}
__device__ __forceinline__ void wg_tt32(float (&d)[64], uint64_t da, uint64_t db, int sc) {
  asm volatile("{.reg .pred p; setp.ne.b32 p, %18, 0; wgmma.mma_async.sync.aligned.m64n32k16.f32.bf16.bf16 {%0,%1,%2,%3,%4,%5,%6,%7,%8,%9,%10,%11,%12,%13,%14,%15}, %16, %17, p, 1, 1, 1, 1;}"
    : "+f"(d[0]),"+f"(d[1]),"+f"(d[2]),"+f"(d[3]),"+f"(d[4]),"+f"(d[5]),"+f"(d[6]),"+f"(d[7]),"+f"(d[8]),"+f"(d[9]),"+f"(d[10]),"+f"(d[11]),"+f"(d[12]),"+f"(d[13]),"+f"(d[14]),"+f"(d[15]) : "l"(da), "l"(db), "r"(sc));
}
__device__ __forceinline__ void wg_g1(float (&d)[88], uint64_t da, uint64_t db, int sc) {
  asm volatile("{.reg .pred p; setp.ne.b32 p, %90, 0; wgmma.mma_async.sync.aligned.m64n176k16.f32.bf16.bf16 {%0,%1,%2,%3,%4,%5,%6,%7,%8,%9,%10,%11,%12,%13,%14,%15,%16,%17,%18,%19,%20,%21,%22,%23,%24,%25,%26,%27,%28,%29,%30,%31,%32,%33,%34,%35,%36,%37,%38,%39,%40,%41,%42,%43,%44,%45,%46,%47,%48,%49,%50,%51,%52,%53,%54,%55,%56,%57,%58,%59,%60,%61,%62,%63,%64,%65,%66,%67,%68,%69,%70,%71,%72,%73,%74,%75,%76,%77,%78,%79,%80,%81,%82,%83,%84,%85,%86,%87}, %88, %89, p, 1, 1, 1, 0;}"
    : "+f"(d[0]),"+f"(d[1]),"+f"(d[2]),"+f"(d[3]),"+f"(d[4]),"+f"(d[5]),"+f"(d[6]),"+f"(d[7]),"+f"(d[8]),"+f"(d[9]),"+f"(d[10]),"+f"(d[11]),"+f"(d[12]),"+f"(d[13]),"+f"(d[14]),"+f"(d[15]),"+f"(d[16]),"+f"(d[17]),"+f"(d[18]),"+f"(d[19]),"+f"(d[20]),"+f"(d[21]),"+f"(d[22]),"+f"(d[23]),"+f"(d[24]),"+f"(d[25]),"+f"(d[26]),"+f"(d[27]),"+f"(d[28]),"+f"(d[29]),"+f"(d[30]),"+f"(d[31]),"+f"(d[32]),"+f"(d[33]),"+f"(d[34]),"+f"(d[35]),"+f"(d[36]),"+f"(d[37]),"+f"(d[38]),"+f"(d[39]),"+f"(d[40]),"+f"(d[41]),"+f"(d[42]),"+f"(d[43]),"+f"(d[44]),"+f"(d[45]),"+f"(d[46]),"+f"(d[47]),"+f"(d[48]),"+f"(d[49]),"+f"(d[50]),"+f"(d[51]),"+f"(d[52]),"+f"(d[53]),"+f"(d[54]),"+f"(d[55]),"+f"(d[56]),"+f"(d[57]),"+f"(d[58]),"+f"(d[59]),"+f"(d[60]),"+f"(d[61]),"+f"(d[62]),"+f"(d[63]),"+f"(d[64]),"+f"(d[65]),"+f"(d[66]),"+f"(d[67]),"+f"(d[68]),"+f"(d[69]),"+f"(d[70]),"+f"(d[71]),"+f"(d[72]),"+f"(d[73]),"+f"(d[74]),"+f"(d[75]),"+f"(d[76]),"+f"(d[77]),"+f"(d[78]),"+f"(d[79]),"+f"(d[80]),"+f"(d[81]),"+f"(d[82]),"+f"(d[83]),"+f"(d[84]),"+f"(d[85]),"+f"(d[86]),"+f"(d[87]) : "l"(da), "l"(db), "r"(sc));
}

struct Params { const __nv_bfloat16 *x, *logA, *Aim, *Cr, *Ci, *logdt, *Dskip, *Wd; uint4* xnT; float2* st; uint2* S; unsigned* flags; };
struct Maps { CUtensorMap x[2], xo, out, wg, wu, wd, hst[2], hld, xt, sld; };

__device__ __forceinline__ void conv_channel(uint32_t cb, int w, int lane, uint32_t (&res)[8], uint32_t sig, int sidx) {
    const int q = lane & 3, g = lane >> 2, gam = g >> 2;
    float acc[64];
    uint2 a[17][2];
    const uint32_t t0 = cb + CH_T + (uint32_t)(14 + 4 * w + (g & 3) - 2 * q) * 280u + gam * 8;
#define LDA(s0, s1) _Pragma("unroll") for (int s = s0; s < s1; s++) { a[s][0] = lds64(t0 + s * 16); a[s][1] = lds64(t0 - 8 * 280 + s * 16); }
#define CT(N, s) wg_rs<N>(acc, a[s][0].x, a[s][0].y, a[s][1].x, a[s][1].y, dU + 4 * (s))
    const uint64_t dU = mkdesc(cb + CH_U, UPLANE, 128, 0);
    LDA(0, 17)
    if (sig) { fence_async_smem(); mbar_arrive(sig); }
    WG_FENCE();
    if (w == 0) STAMP2(52 + 3 * sidx);
    wg_rs_first(acc, a[0][0].x, a[0][0].y, a[0][1].x, a[0][1].y, dU);
    CT(128, 1); CT(120, 2); CT(120, 3); CT(112, 4); CT(112, 5); CT(104, 6); CT(104, 7); CT(96, 8);
    CT(96, 9); CT(88, 10); CT(88, 11); CT(80, 12); CT(80, 13); CT(72, 14); CT(72, 15); CT(64, 16);
#undef CT
#undef LDA
    wg_tt64(acc, mkdesc(cb + CH_A3, 128, 512, 0), mkdesc(cb + CH_B3, 384, 32, 0), 1);
    wg_tt32(acc, mkdesc(cb + CH_A3 + 256, 128, 512, 0), mkdesc(cb + CH_B3 + 128, 384, 32, 0), 1);
    WG_COMMIT();
    if (w == 0) STAMP2(53 + 3 * sidx);
    WG_WAIT(0);
    fence_acc(acc);
    if (w == 0) STAMP2(54 + 3 * sidx);
    const int src1 = (lane & ~3) | ((q + 1) & 3);
    float E[16][2];
    #pragma unroll
    for (int j = 0; j < 16; j++) {
        const float nxt = (j < 15) ? acc[4 * (j + 1) + 2] : 0.f;
        const float sup = (q == 0) ? nxt : acc[4 * j + 2];
        const float v = __shfl_sync(0xffffffffu, sup, src1);
        E[j][0] = acc[4 * j] + acc[4 * j + 3];
        E[j][1] = acc[4 * j + 1] + v;
    }
    const int src2 = gam ? ((lane & 12) | ((q + 3) & 3)) : (16 | (lane & 12) | ((q + 1) & 3));
    const bool c1 = gam && q != 0, c2 = gam && q == 0;
    #pragma unroll
    for (int a2 = 0; a2 < 8; a2++) {
        float y[2];
        #pragma unroll
        for (int e = 0; e < 2; e++) {
            const float sup = c1 ? E[2 * a2][e] : E[2 * a2 + 1][e];
            const float nxt = (a2 < 7) ? E[2 * a2 + 2][e] : 0.f;
            const float keep = c2 ? nxt : (c1 ? E[2 * a2 + 1][e] : E[2 * a2][e]);
            y[e] = keep + __shfl_sync(0xffffffffu, sup, src2);
        }
        res[a2] = pack2(y[1], y[0]);
    }
}

__device__ __forceinline__ void layer_norm(uint32_t sb, int w, int lane, const __nv_bfloat16* x) {
    const uint32_t bars = sb + OFF_BAR;
    const int c = blockIdx.x;
    {
        if (elect_one()) {
            mbar_expect(bars + 8 * B_LNX, 4096);
            #pragma unroll
            for (int i = 0; i < 4; i++)
                bulk_load(sb + OFF_LN + (w + 4 * i) * 1152 + ((w & 1) + 2 * i) * 16, x + (16 * (c & ~1) + 8 * (c & 1) + 16 + w + 4 * (i & 1) - 8 * (i & 2)) * DM, 1024, bars + 8 * B_LNX);
        }
        mbar_wait(bars + 8 * B_LNX, 0);
        STAMP(34);
        {
            const int r = w + 4 * (lane >> 3);
            const uint32_t r0 = sb + OFF_LN + r * 1152 + ((w & 1) + 2 * (lane >> 3)) * 16, ra = r0 + (lane & 7) * 16;
            const float pv = bf_lo(FU(ldsf(r0)));
            float s0 = 0.f, s1 = 0.f, a0 = 0.f, a1 = 0.f;
            uint4 nx = lds128(ra), ny = lds128(ra + 128);
            #pragma unroll 2
            for (int k = 128; k <= 1024; k += 128) {
                const uint32_t v[4] = {nx.x, nx.y, nx.z, nx.w};
                nx = ny; ny = lds128(ra + ((k + 128) & 1023));
                #pragma unroll
                for (int i = 0; i < 4; i++) { const float t0 = bf_lo(v[i]) - pv, t1 = bf_hi(v[i]) - pv; s0 += t0; s1 += t1; a0 = fmaf(t0, t0, a0); a1 = fmaf(t1, t1, a1); }
            }
            s0 += s1; a0 += a1;
            #pragma unroll
            for (int o = 4; o; o >>= 1) { s0 += __shfl_xor_sync(0xffffffffu, s0, o); a0 += __shfl_xor_sync(0xffffffffu, a0, o); }
            s0 *= 1.f / DM;
            const float m = pv + s0, var = fmaxf(fmaf(-s0, s0, a0 * (1.f / DM)), 0.f);
            float sd, ri;
            asm("sqrt.approx.ftz.f32 %0, %1;" : "=f"(sd) : "f"(bf_round(bf_round(var) + 1e-5f)));
            asm("rcp.approx.ftz.f32 %0, %1;" : "=f"(ri) : "f"(bf_round(sd)));
            const uint32_t m2 = pack2(m, m);
            if ((lane & 7) == 0) {
                sts64(sb + OFF_CSUM + r * 8, m2 & 0xffff0000u, FU(0.5f * ri));
            }
            #pragma unroll 2
            for (int k = 128; k <= 1024; k += 128) {
                uint32_t v[4] = {nx.x, nx.y, nx.z, nx.w};
                nx = ny; ny = lds128(ra + ((k + 128) & 1023));
                #pragma unroll
                for (int i = 0; i < 4; i++) {
                    uint32_t dv; asm("sub.rn.bf16x2 %0, %1, %2;" : "=r"(dv) : "r"(v[i]), "r"(m2));
                    v[i] = pack2(bf_lo(dv) * ri, bf_hi(dv) * ri);
                }
                sts128(ra + k - 128, v[0], v[1], v[2], v[3]);
            }
        }
        STAMP(62);
        bar_sync(4);
        {
            const uint32_t ad = sb + OFF_LN + (4 * ((lane & 7) >> 1) + (lane & 1) + 2 * ((lane >> 3) & 1)) * 1152 + (16 * w + (lane >> 4) + (lane & 7)) * 16;
            uint32_t r[8][4];
            #pragma unroll
            for (int i = 0; i < 8; i++)
                asm volatile("ldmatrix.sync.aligned.m8n8.x4.trans.shared.b16 {%0,%1,%2,%3}, [%4];" : "=r"(r[i][0]), "=r"(r[i][1]), "=r"(r[i][2]), "=r"(r[i][3]) : "r"(ad + 32 * i) : "memory");
            bar_sync(4);
            const uint32_t od = sb + OFF_LN + w * 4096 + lane * 8;
            #pragma unroll
            for (int i = 0; i < 8; i++) { sts64(od + i * 512, r[i][0], r[i][1]); sts64(od + i * 512 + 256, r[i][2], r[i][3]); }
        }
        fence_async_smem();
        mbar_arrive(bars + 8 * B_LN);
        STAMP(16);
    }
}

__device__ __forceinline__ void consumer(uint32_t sb, int warp, const Params& P, const Maps& M) {
    const int V = warp >> 2, w = warp & 3, lane = threadIdx.x & 31, q = lane & 3, g = lane >> 2;
    const int c = blockIdx.x;
    const uint32_t bars = sb + OFF_BAR, xb = sb + OFF_X + V * 2 * XBUF;
    {
        float ag[88], au[88];
        if (V == 0) {
            sts128(xb + (w >> 1) * XBUF + 168 * 128 + (threadIdx.x & 63) * 16, 0x3f803f80u, 0x3f803f80u, 0x3f803f80u, 0x3f803f80u);
            fence_async_smem();
            bar_sync(1);
        } else {
            if (c < 128) layer_norm(sb, w, lane, P.x); else mbar_arrive(bars + 8 * B_LN);
            mbar_wait(bars + 8 * B_GO, 0);
        }
        define_acc(ag); define_acc(au);
        #pragma unroll 1
        for (int st = 0; st < 8; st++) {
            if (st + LAG * V == HOLD0 || st + LAG * V == HOLD1) mbar_wait(bars + 8 * (B_K + (st + LAG * V == HOLD1)), 0);
            mbar_wait(bars + 8 * (B_FULLW + (st & 3)), st >> 2);
            mbar_wait(bars + 8 * (B_FULLX + 2 * V + (st & 1)), (st >> 1) & 1);
            STAMP(40 + 8 * V + st);
            const uint64_t dG = mkdesc(sb + OFF_W + (st & 3) * 16384, 0, 1024, 1);
            const uint64_t dX = mkdesc(xb + (st & 1) * XBUF, 16, 1024, 1);
            WG_FENCE();
            #pragma unroll
            for (int k = 0; k < 4; k++) {
                wg_g1(ag, dG + k * 128, dX + k * 2, k ? 1 : st);
                wg_g1(au, dG + 512 + k * 128, dX + k * 2, k ? 1 : st);
            }
            WG_COMMIT();
            WG_WAIT(1);
            if (lane == 0 && st > 0) {
                mbar_arrive(bars + 8 * (B_EMPTYW + ((st - 1) & 3)));
                mbar_arrive(bars + 8 * (B_EMPTYX + 2 * V + ((st - 1) & 1)));
                if (warp < 4 && st == LAG) mbar_arrive(bars + 8 * B_GO);
            }
        }
        WG_WAIT(0);
        fence_acc(ag); fence_acc(au);
        if (lane == 0) { mbar_arrive(bars + 8 * (B_EMPTYW + 3)); mbar_arrive(bars + 8 * (B_EMPTYX + 2 * V + 1)); }
        STAMP(8 * V + 1);
        float cg0 = ag[84], cg1 = ag[86], cu0 = au[84], cu1 = au[86];
        const uint32_t ca = sb + OFF_CSUM + (8 * w + g) * 16;
        if (V == 0) { sts128(ca, FU(cg0), FU(cg1), FU(cu0), FU(cu1)); mbar_arrive(bars + 8 * B_CS); }
        else { mbar_wait(bars + 8 * B_CS, 0); const uint4 t = lds128(ca); cg0 = UF(t.x); cg1 = UF(t.y); cu0 = UF(t.z); cu1 = UF(t.w); }
        mbar_wait(bars + 8 * B_STATS, 0);
        mbar_wait(bars + 8 * (B_EMPTYX + 2 * V), 1);
        STAMP(13 + V);
        const uint32_t hs = xb + (2 * w + ((lane >> 3) & 1)) * (2688 + 128 * V) + (lane >> 4) * 128 + (lane & 7) * 16;
        const uint32_t sa = sb + OFF_ST + (168 * V + 2 * q) * 8;
        uint4 sq[22];
        #pragma unroll
        for (int j = 0; j < 3; j++) sq[j] = lds128(sa + j * 64);
        #pragma unroll
        for (int j = 0; j < 22; j += 2) {
            uint32_t o[4];
            #pragma unroll
            for (int jj = 0; jj < 2; jj++) {
                const uint4 sv = sq[j + jj];
                float hv[4];
                #pragma unroll
                for (int i = 0; i < 4; i++) {
                    const float m = UF((i & 1) ? sv.z : sv.x);
                    const float gh = fmaf(-m, (i & 2) ? cg1 : cg0, ag[4 * (j + jj) + i]) * UF((i & 1) ? sv.w : sv.y);
                    const float p = gh * fmaf(-m, (i & 2) ? cu1 : cu0, au[4 * (j + jj) + i]);
                    hv[i] = fmaf(p, tanh_fast(gh), p);
                }
                o[2 * jj] = pack2(hv[0], hv[1]); o[2 * jj + 1] = pack2(hv[2], hv[3]);
            }
            #pragma unroll
            for (int k = (j ? 3 + 3 * j / 2 : 3); k < 6 + 3 * j / 2 && k < 22; k++) sq[k] = lds128(sa + k * 64);
            uint32_t ad = hs + j * 128;
            if (j == 20 && V == 0 && lane >= 16) ad = xb + 21504 + (lane & 7) * 16;
            stsm4(ad, o[0], o[1], o[2], o[3]);
        }
        if (c >= 128) { fence_async_smem(); mbar_arrive(bars + 8 * (B_EPI + V)); }
        STAMP(8 * V + 2);
    }
    if (c >= 128) return;
    {
        uint32_t r0[8], r1[8];
        #pragma unroll
        for (int i = 0; i < 8; i++) asm volatile("" : "=r"(r1[i]));
        #pragma unroll 1
        for (int e = 0; e < 2; e++) {
            #pragma unroll
            for (int i = 0; i < 8; i++) r0[i] = r1[i];
            mbar_wait(bars + 8 * (B_CONV + 2 * V + e), 0);
            conv_channel(sb + OFF_CONV + (2 * V + e) * CH_STRIDE, w, lane, r1, e ? 0 : bars + 8 * (B_EPI + V), 2 * V + e);
            if (e == 0) STAMP(8 * V + 3);
        }
        const int gam = g >> 2, qq = gam ? ((q + 3) & 3) : q;
        const uint32_t sp = sb + OFF_CONV + V * OFF_SST + ((63 - 4 * gam - qq) * 16 + 4 * (w ^ (3 - qq)) + (g & 3)) * 8;
        bar_sync(3 + V);
        #pragma unroll
        for (int a2 = 0; a2 < 8; a2++) sts64(sp - a2 * 1024, r0[a2], r1[a2]);
        fence_async_smem();
        mbar_arrive(bars + 8 * (B_SIG + V));
        STAMP(8 * V + 4);
    }
    if (V == 1) return;
    {
        const int tau = c >> 2, dg = c & 3;
        const uint32_t row = 8 * (w & 1) + 32 * (w >> 1);
        float acc[64];
        define_acc(acc);
        const float rr0 = __ldcg(&P.st[64 * tau + row + g].y), rr1 = __ldcg(&P.st[64 * tau + row + g + 16].y);
        mbar_wait(bars + 8 * B_FULLD, 0);
        STAMP(5);
        uint64_t dB = mkdesc(sb + wd_slot(0), 8192, 1024, 1), dA = mkdesc(sb + h_slot(0), 1024, 128, 0);
        #pragma unroll 1
        for (int st = 0; st < 21; st++) {
            WG_FENCE();
            wg_tt128(acc, dA, dB, st);
            wg_tt128(acc, dA + 128, dB + 128, 1);
            wg_tt128(acc, dA + 256, dB + 256, 1);
            wg_tt128(acc, dA + 384, dB + 384, 1);
            WG_COMMIT();
            const int sd = (st + 1) & 7;
            const uint32_t nb = bars + 8 * (B_FULLD + sd), np = ((st + 1) >> 3) & 1;
            uint32_t ro = st == 15 ? 8 * B_CH0 : 8 * (B_EMPTYD + ((st - 1) & 7)), m = lane == 0 && st > 0, ok;
            dB = mkdesc(sb + wd_slot(sd), 8192, 1024, 1); dA = mkdesc(sb + h_slot(sd), 1024, 128, 0);
            asm volatile("{.reg .pred p; mbarrier.test_wait.parity.shared::cta.b64 p, [%5], %6; vote.sync.all.pred p, p, -1; selp.u32 %0, 1, 0, p;}"
                : "=r"(ok), "+l"(dA), "+l"(dB), "+r"(ro), "+r"(m) : "r"(nb), "r"(np) : "memory");
            WG_WAIT(1);
            asm volatile("{.reg .pred p; setp.ne.u32 p, %1, 0; @p mbarrier.arrive.shared::cta.b64 _, [%0];}" :: "r"(bars + ro), "r"(m) : "memory");
            if (!ok) mbar_wait(nb, np);
            if (w == 0) STAMP2(20 + st);
        }
        WG_FENCE();
        wg_tt128(acc, dA, dB, 1);
        wg_tt128(acc, dA + 128, dB + 128, 1);
        WG_COMMIT();
        mbar_wait(bars + 8 * B_XO, 0);
        const uint32_t xo = sb + OFF_CONV + (row + (lane & 7) + 16 * ((lane >> 3) & 1)) * 128;
        const uint32_t so = sb + wd_slot(6) + (w >> 1) * 8192 + q * 256 + (g & 1) * 8;
        const uint32_t sx = (4 * (w & 1) + (g >> 1)) ^ (2 * q) ^ (2 * ((2 * tau + (w >> 1)) & 3));
        uint32_t xr[8][4];
        uint2 sv[16];
        #pragma unroll
        for (int j = 0; j < 16; j += 2) {
            ldsm4(xr[j >> 1], xo + (j >> 3) * 8192 + ((((j & 7) + (lane >> 4)) ^ (lane & 7)) << 4));
            sv[j] = lds64(so + j * 512 + (sx << 4));
            sv[j + 1] = lds64(so + j * 512 + 128 + ((sx ^ 1) << 4));
        }
        WG_WAIT(0);
        fence_acc(acc);
        STAMP(6);
        #pragma unroll
        for (int j = 0; j < 16; j += 2) {
            #pragma unroll
            for (int i = 0; i < 4; i++) {
                const int jj = j + (i >> 1), hh = i & 1;
                const float f0 = acc[4 * jj + 2 * hh] * (hh ? rr1 : rr0), f1 = acc[4 * jj + 2 * hh + 1] * (hh ? rr1 : rr0);
                const uint32_t G = pack2(fmaf(f0, tanh_fast(f0), f0), fmaf(f1, tanh_fast(f1), f1));
                const uint32_t s2 = __byte_perm(sv[jj].x, sv[jj].y, hh ? 0x7632 : 0x5410);
                asm("fma.rn.bf16x2 %0, %1, %2, %0;" : "+r"(xr[j >> 1][i]) : "r"(s2), "r"(G));
            }
            stsm4(xo + (j >> 3) * 8192 + ((((j & 7) + (lane >> 4)) ^ (lane & 7)) << 4), xr[j >> 1][0], xr[j >> 1][1], xr[j >> 1][2], xr[j >> 1][3]);
        }
        fence_async_smem();
        bar_sync(1);
        if (w == 0 && elect_one()) {
            #pragma unroll
            for (int i = 0; i < 2; i++)
                asm volatile("cp.async.bulk.tensor.2d.global.shared::cta.bulk_group [%0, {%2, %3}], [%1];"
                    :: "l"(&M.out), "r"(sb + OFF_CONV + i * 8192), "r"(dg * 128 + 64 * i), "r"(tau * 64) : "memory");
            asm volatile("cp.async.bulk.commit_group; cp.async.bulk.wait_group.read 0;" ::: "memory");
        }
        STAMP(7); GSTAMP(23);
    }
}

__device__ __forceinline__ float2 cexp_p(float re2, float im, float p) {
    float sn, cs;
    const float mag = ex2(re2 * p), th = im * p;
    asm("sin.approx.ftz.f32 %0, %1;" : "=f"(sn) : "f"(th));
    asm("cos.approx.ftz.f32 %0, %1;" : "=f"(cs) : "f"(th));
    return make_float2(mag * cs, mag * sn);
}
__device__ __forceinline__ unsigned short ldu16(const void* p) { unsigned short v; asm volatile("ld.global.nc.u16 %0, [%1];" : "=h"(v) : "l"(p)); return v; }
__device__ __forceinline__ float2 cmul(float2 a, float2 b) { return make_float2(fmaf(a.x, b.x, -a.y * b.y), fmaf(a.x, b.y, a.y * b.x)); }
__device__ __forceinline__ float2 csqr(float2 a) { const float t = a.x * a.y; return make_float2(fmaf(a.x, a.x, -a.y * a.y), t + t); }
__device__ __forceinline__ void mma16816(float (&d)[4], const uint32_t (&a)[4], uint32_t b0, uint32_t b1) {
    asm volatile("mma.sync.aligned.m16n8k16.row.col.f32.bf16.bf16.f32 {%0,%1,%2,%3}, {%4,%5,%6,%7}, {%8,%9}, {%0,%1,%2,%3};"
        : "+f"(d[0]), "+f"(d[1]), "+f"(d[2]), "+f"(d[3]) : "r"(a[0]), "r"(a[1]), "r"(a[2]), "r"(a[3]), "r"(b0), "r"(b1));
}

__device__ __forceinline__ void aux_role(uint32_t sb, int w, const Params& P) {
    const int lane = threadIdx.x & 31, q = lane & 3, g = lane >> 2;
    const int c = blockIdx.x;
    const uint32_t bars = sb + OFF_BAR;
    if (c >= 128) {
        if (lane == 0) { mbar_arrive(bars + 8 * B_K); mbar_arrive(bars + 8 * (B_K + 1)); }
        return;
    }
    {
        const uint32_t cb = sb + OFF_CONV + w * CH_STRIDE;
        const uint32_t sF = cb + CH_A3;
        const int d = 4 * c + w;
        const int po = d * 128 + lane;
        unsigned short la = ldu16(P.logA + po), ai = ldu16(P.Aim + po), cr = ldu16(P.Cr + po), ci = ldu16(P.Ci + po);
        const float ldt = __bfloat162float(P.logdt[d]), dsk = __bfloat162float(P.Dskip[d]);
        float dacc[2][3][4];
        #pragma unroll
        for (int i = 0; i < 24; i++) (&dacc[0][0][0])[i] = 0.f;
        uint32_t keep = 0;
        const float dt = bf_round(ex2(ldt * 1.4426950408889634f));
        #pragma unroll 1
        for (int ck = 0; ck < 4; ck++) {
            const uint32_t fa = cb + lane * 4 + (ck & 1) * 8064;
            const float re2 = bf_round(ex2(bf_lo((uint32_t)la) * 1.4426950408889634f)) * dt * -1.4426950408889634f, im = bf_lo((uint32_t)ai) * dt;
            const float2 C = make_float2(bf_lo((uint32_t)cr) * (dt + dt), bf_lo((uint32_t)ci) * -(dt + dt));
            {
                const int pn = po + 32 * min(ck + 1, 3);
                la = ldu16(P.logA + pn); ai = ldu16(P.Aim + pn); cr = ldu16(P.Cr + pn); ci = ldu16(P.Ci + pn);
            }
            const float2 z8 = cexp_p(re2, im, 8.f), y1 = cexp_p(re2, -im, 1.f);
            float2 b0 = make_float2(1.f, 0.f), b1 = cexp_p(re2, im, 64.f), b2 = csqr(b1), b3 = cmul(b2, b1), l0 = C;
            const uint32_t fm = cb + (ck & 1) * 8064 + (lane >> 3) * 144 + (lane & 7) * 16;
#define PK(v) pack2((v).x, (v).y)
            #pragma unroll 1
            for (uint32_t ro = 0; ro < 8 * 144; ro += 144) {
                const uint32_t p0 = PK(b0), p1 = PK(b1), p2 = PK(b2), p3 = PK(b3), p4 = PK(l0);
                stsm4(fm + (lane >> 3) * 7 * 144 + ro, p0, p1, p2, p3);
                stsf(fa + 32 * 144 + ro, UF(p4));
                b0 = cmul(b0, z8); b1 = cmul(b1, z8); b2 = cmul(b2, z8); b3 = cmul(b3, z8); l0 = cmul(l0, y1);
                keep = (keep ^ p0 ^ p1 ^ FU(l0.y)) + (p2 ^ p3 ^ p4);
            }
            if (ck < 2) STAMP(56 + 3 * ck);
            const float2 y256 = cexp_p(re2, -im, 256.f), y2 = csqr(y1), y4 = csqr(y2), y8 = make_float2(z8.x, -z8.y);
            const float2 t0 = cmul(C, y256), t1 = cmul(t0, y256), t2 = cmul(t1, y256), t3_ = cmul(t2, y256);
            const float2 u1 = cmul(t0, y2), u2 = cmul(u1, y2), u3 = cmul(u2, y2);
            stsm4(fm + 40 * 144, PK(t0), PK(u1), PK(u2), PK(u3));
            stsm4(fm + 44 * 144, PK(t1), PK(cmul(t1, y4)), PK(t2), PK(cmul(t2, y4)));
            const float2 v0 = cmul(t3_, y8), v1 = cmul(v0, y256), v2 = cmul(v1, y256), v3 = cmul(v2, y256);
            stsm4(fm + 48 * 144, PK(v0), PK(v1), PK(v2), PK(v3));
            stsf(fa + 52 * 144, UF(PK(t3_)));
#undef PK
            if (ck < 2) STAMP(57 + 3 * ck);
            if (ck & 1) {
                uint32_t ln_; asm volatile("mov.u32 %0, %%laneid;" : "=r"(ln_));
                const uint32_t lda = cb + (ln_ & 15) * 144 + (ln_ & 16);
                const uint32_t ldb = cb + (32 + (ln_ & 7)) * 144 + (ln_ >> 3) * 16;
                __syncwarp();
                #pragma unroll
                for (int k2 = 0; k2 < 4; k2++) {
                    const uint32_t ko = (k2 >> 1) * 8064 + (k2 & 1) * 64;
                    uint32_t b[3][4];
                    #pragma unroll
                    for (int t3 = 0; t3 < 3; t3++) ldsm4(b[t3], ldb + t3 * 8 * 144 + ko);
                    #pragma unroll
                    for (int k = 0; k < 2; k++)
                        #pragma unroll
                        for (int mu = 0; mu < 2; mu++) {
                            uint32_t a[4];
                            ldsm4(a, lda + mu * 16 * 144 + ko + k * 32);
                            #pragma unroll
                            for (int t3 = 0; t3 < 3; t3++) mma16816(dacc[mu][t3], a, b[t3][2 * k], b[t3][2 * k + 1]);
                        }
                }
                __syncwarp();
                if (lane == 0) mbar_arrive(bars + 8 * (B_K + (ck >> 1)));
                STAMP(58 + 3 * (ck >> 1));
            }
        }
        STAMP(18);
        stsf(cb + CH_T + 8400 + (lane & 7) * 4, UF(keep));
        const uint32_t sG = cb + CH_G;
        if (lane == 0) dacc[0][0][0] += dsk;
        if (lane < 18) sts128(lane < 8 ? cb + CH_U + 2048 + (lane & 4) * (UPLANE / 4) + (lane & 3) * 16 : sG + 128 + (lane & 1) * 208 + ((lane - 8) >> 1) * 16, 0, 0, 0, 0);
        {
            const uint32_t f0 = sF + (8 * g + 2 * q) * 4, f1 = sF + ((q < 2) ? 256 + 4 * g + 2 * q : 256 + 2 * g + 64 * q) * 4, st1 = (q < 2) ? 128 : 64;
            const uint32_t ga = sG + ((g & 1) ? 0 : 208) + (63 - (g >> 1) - 32 * q) * 2;
            #pragma unroll
            for (int i = 0; i < 4; i++) {
                const int mu = i >> 1, hh = i & 1;
                sts64(f0 + i * 256, FU(dacc[mu][0][2 * hh]), FU(dacc[mu][0][2 * hh + 1]));
                sts64(f1 + i * st1, FU(dacc[mu][1][2 * hh]), FU(dacc[mu][1][2 * hh + 1]));
                const uint32_t pk = pack2(dacc[mu][2][2 * hh], dacc[mu][2][2 * hh + 1]);
                if (q < 2) { sts16(ga - 8 * i, pk & 0xffff); sts16(ga - 8 * i - 32, pk >> 16); }
            }
            if (lane == 2) stsf(sF + 2048, dacc[0][2][0]);
        }
    }
    bar_sync(2);
    STAMP(19);
    const int u = min(lane, 30) - 15, r2 = (u + ((u >> 1) & 1)) >> 1, r4 = (u + 1 + ((u >> 2) & 1)) >> 2, xt = 1024 + 16 * w + u;
    const uint32_t o0 = CH_A3 + 4 * (w == 0 ? u : w == 1 ? 256 + r2 : 256 + 64 * w + r4), ost = w == 0 ? 64 : w == 1 ? 32 : 16;
    const uint32_t oa0 = u >= 0 || w == 3 ? o0 : CH_A3 + 4 * (w == 1 ? 256 + u : w == 2 ? 384 + r2 : 0);
    const uint32_t ot = CH_A3 + 4 * min(512, 256 + ((xt + 1 + ((xt >> 2) & 1)) >> 2));
    const int kap = (lane >> 4) * 8 + ((lane >> 1) & 7), gam = lane & 1, hh = w >> 1, wp = w & 1;
    const uint32_t oa = CH_U + wp * UPLANE + (127 - 4 * kap - 2 * gam - hh) * 16;
    const uint32_t ob = CH_U + (wp ^ 1) * UPLANE + (128 - wp - 4 * kap - 2 * gam - hh) * 16;
    const uint32_t od = CH_A3 + (4 * wp + hh) * 512 + (kap >> 3) * 256 + (kap & 7) * 16 + gam * 8;
    #pragma unroll 1
    for (int k = 0; k < 4; k++) {
        const int ch = 2 * (k & 1) + (k >> 1);
        const uint32_t cb = sb + OFF_CONV + ch * CH_STRIDE;
        {
            float kv[17];
            kv[0] = ldsf(cb + oa0); kv[16] = ldsf(cb + ot);
            #pragma unroll
            for (int s = 1; s < 16; s++) kv[s] = ldsf(cb + o0 + s * ost);
            const int tid = threadIdx.x & 127;
            const uint32_t ga = cb + CH_G + (tid >= 24) * 16 + min(tid, 47) * 8;
            const uint2 x0 = lds64(ga), x1 = lds64(ga + 8);
            if (u < 0 && w == 0) kv[0] = 0.f;
            if (xt > 1028) kv[16] = 0.f;
            uint32_t o[17];
            #pragma unroll
            for (int s = 0; s < 17; s++) o[s] = pack2(kv[s], __shfl_up_sync(0xffffffffu, kv[s], 1));
            if (lane > 0 && lane < 31) {
                const uint32_t ta = cb + CH_T + (lane - 1) * 280;
                #pragma unroll
                for (int s2 = 0; s2 < 8; s2++) sts64(ta + 64 * w + s2 * 8, o[2 * s2], o[2 * s2 + 1]);
                stsf(ta + 256 + 4 * w, UF(o[16]));
            }
            if (tid < 48) sts128(cb + CH_B3 + tid * 16, x0.x, x0.y, x1.x, x1.y);
        }
        mbar_wait(bars + 8 * B_U, 0);
        float p[24];
        const uint2 r0 = lds64(cb + ob + 24), r3 = lds64(cb + oa);
        uint32_t r[8];
        *(uint4*)&r[0] = lds128(cb + oa + 16); *(uint4*)&r[4] = lds128(cb + ob);
        p[0] = 0.f;
        p[1] = bf_lo(r0.x); p[2] = p[1] + bf_hi(r0.x); p[3] = p[2] + bf_lo(r0.y); p[4] = p[3] + bf_hi(r0.y);
        #pragma unroll
        for (int i = 0; i < 8; i++) { p[5 + 2 * i] = p[4 + 2 * i] + bf_lo(r[i]); p[6 + 2 * i] = p[5 + 2 * i] + bf_hi(r[i]); }
        p[21] = p[20] + bf_lo(r3.x); p[22] = p[21] + bf_hi(r3.x); p[23] = p[22] + bf_lo(r3.y);
        bar_sync(2);
        #pragma unroll
        for (int i = 0; i < 8; i += 4) {
            sts64(cb + od + i * 256, pack2(p[i + 9] - p[i], p[i + 10] - p[i + 1]), pack2(p[i + 11] - p[i + 2], p[i + 12] - p[i + 3]));
            sts64(cb + od + i * 256 + 128, pack2(p[i + 16] - p[i + 9], p[i + 17] - p[i + 10]), pack2(p[i + 18] - p[i + 11], p[i + 19] - p[i + 12]));
        }
        fence_async_smem();
        mbar_arrive(bars + 8 * (B_CONV + ch));
        if (k == 0) STAMP(17);
    }
    STAMP(21);
}

__global__ void __launch_bounds__(512, 1)
fused_kernel(const __grid_constant__ Params P, const __grid_constant__ Maps M) {
    extern __shared__ __align__(1024) uint8_t smem_raw[];
    const uint32_t sb = smem_u32(smem_raw);
    const uint32_t bars = sb + OFF_BAR;
    const int warp = __shfl_sync(0xffffffffu, threadIdx.x >> 5, 0);
    const int c = blockIdx.x, tg = c / 22, fb = c - 22 * tg;
    if (elect_one()) {
        if (warp == 0) { STAMP(24); GSTAMP(22); }
        asm volatile("" :: "l"(((const uint64_t*)&P)[warp < 12 ? warp : 0]));
        if (warp < 12) asm volatile("prefetch.tensormap [%0];" :: "l"(&M.x[0] + warp) : "memory");
        #pragma unroll
        for (int k = 0; k < 4; k++) {
            const int i = 16 * k + ((warp + 4) & 15);
            const uint32_t cnt = i >= B_CONV ? 128 : ((0xf0ull >> i) & 1) ? 8 : ((0xff0000ull >> i) & 1) ? 2 : ((0x3e00ff00f000ull >> i) & 1) ? 4 : 1;
            asm volatile("mbarrier.init.shared::cta.b64 [%0], %1;" :: "r"(bars + 8 * i), "r"(cnt) : "memory");
        }
        asm volatile("fence.mbarrier_init.release.cluster; fence.proxy.async.shared::cta;" ::: "memory");
        if (warp == 12 || warp == 13) {
            const uint32_t s = warp - 12;
            mbar_expect(bars + 8 * (B_FULLW + s), 16384);
            tma2d(sb + OFF_W + s * 16384, &M.wg, 64 * fb, 64 * s, bars + 8 * (B_FULLW + s));
            tma2d(sb + OFF_W + s * 16384 + 8192, &M.wu, 64 * fb, 64 * s, bars + 8 * (B_FULLW + s));
            STAMP(31);
        } else if (warp >= 4 && warp < 7) {
            const uint32_t s = warp - 4, V = s >> 1;
            mbar_expect(bars + 8 * (B_FULLX + s), (168 + 8 * V) * 128);
            tma2d(sb + OFF_X + s * XBUF, &M.x[V], 64 * (s & 1), TOKG * tg + 168 * V, bars + 8 * (B_FULLX + s));
        }
        if (sb & 1023) __trap();
    }
    __syncthreads();
    if (warp < 8) {
        asm volatile("setmaxnreg.inc.sync.aligned.u32 208;");
        consumer(sb, warp, P, M);
    } else if (warp < 12) {
        asm volatile("setmaxnreg.dec.sync.aligned.u32 72;");
        STAMP(32);
        aux_role(sb, warp - 8, P);
    } else {
        asm volatile("setmaxnreg.dec.sync.aligned.u32 24;");
        const int tau = c >> 2, dg = c & 3;
        if (elect_one()) {
            if (warp < 15) {
                if (warp == 12) {
                    #pragma unroll 1
                    for (int st = 2; st < 8; st++) {
                        const uint32_t s = st & 3, fb_ = bars + 8 * (B_FULLW + s);
                        if (st == 2) mbar_wait(bars + 8 * B_FULLW, 0);
                        mbar_wait(bars + 8 * (B_EMPTYW + s), (st >> 2) ^ 1);
                        mbar_expect(fb_, 16384);
                        tma2d(sb + OFF_W + s * 16384, &M.wg, 64 * fb, 64 * st, fb_);
                        tma2d(sb + OFF_W + s * 16384 + 8192, &M.wu, 64 * fb, 64 * st, fb_);
                    }
                } else {
                    const int V = warp - 13;
                    #pragma unroll 1
                    for (int st = 2 - V; st < 8; st++) {
                        const uint32_t s = 2 * V + (st & 1);
                        if (s == 3 && st == 1) mbar_wait(bars + 8 * B_LNS, 0);
                        mbar_wait(bars + 8 * (B_EMPTYX + s), ((st >> 1) & 1) ^ 1);
                        mbar_expect(bars + 8 * (B_FULLX + s), (168 + 8 * V) * 128);
                        tma2d(sb + OFF_X + s * XBUF, &M.x[V], 64 * st, TOKG * tg + 168 * V, bars + 8 * (B_FULLX + s));
                    }
                }
                if (c < 128 && warp < 14) {
                    if (warp == 13) {
                        mbar_wait(bars + 8 * (B_STG + 1), 0);
                        #pragma unroll 1
                        for (int o = 8 * tau; o < 8 * tau + 8; o += 7) flag_wait(P.flags, F_H + 2 * (o / 43) + ((o % 43) >= 21), 22);
                        mbar_arrive(bars + 8 * B_HF);
                        STAMP(25);
                    }
                    #pragma unroll 1
                    for (int st = 0; st < 22; st += (st < 7 || (st == 7 && warp == 12)) ? 1 : 2) {
                        const int sd = st & 7;
                        const uint32_t fb_ = bars + 8 * (B_FULLD + sd);
                        if (st >= 8) mbar_wait(bars + 8 * (B_EMPTYD + sd), ((st >> 3) & 1) ^ 1);
                        else if (warp == 12 || st >= 6) mbar_wait(bars + 8 * (uint32_t)((0x373623070d060504ull >> (8 * st)) & 0xff), st < 5);
                        if (st >= 10 && st < 21) STAMP2(31 + st);
                        if (st >= 8 || warp == 13) {
                            mbar_expect(fb_, 8192);
                            asm volatile("cp.async.bulk.tensor.5d.shared::cluster.global.mbarrier::complete_tx::bytes [%0], [%1, {%3, %3, %3, %4, %5}], [%2];"
                                :: "r"(sb + h_slot(sd)), "l"(&M.hld), "r"(fb_), "r"(0), "r"(2 * tau), "r"(8 * st) : "memory");
                        }
                        if (st >= 8 || warp == 12) {
                            const uint32_t da = sb + wd_slot(sd);
                            mbar_expect(fb_, 16384);
                            tma2d(da, &M.wd, 128 * dg, 64 * st, fb_);
                            tma2d(da + 8192, &M.wd, 128 * dg + 64, 64 * st, fb_);
                        }
                    }
                } else if (c < 128) {
                    mbar_wait(bars + 8 * B_SST, 0);
                    flag_wait(P.flags, F_S + dg, 64);
                    STAMP(26);
                    mbar_wait(bars + 8 * B_CH0, 0);
                    mbar_expect(bars + 8 * B_XO, 32768);
                    tma2d(sb + OFF_CONV, &M.xo, 128 * dg, 64 * tau, bars + 8 * B_XO);
                    tma2d(sb + OFF_CONV + 8192, &M.xo, 128 * dg + 64, 64 * tau, bars + 8 * B_XO);
                    asm volatile("cp.async.bulk.tensor.5d.shared::cluster.global.mbarrier::complete_tx::bytes [%0], [%1, {%3, %3, %3, %4, %5}], [%2];"
                        :: "r"(sb + wd_slot(6)), "l"(&M.sld), "r"(bars + 8 * B_XO), "r"(0), "r"(8 * dg), "r"(2 * tau) : "memory");
                    mbar_wait(bars + 8 * B_HF, 0);
                    exit_count(P.flags);
                }
            } else {
                mbar_wait(bars + 8 * B_LN, 0);
                STAMP2(0);
                if (c < 128) {
                    #pragma unroll 1
                    for (int i = 0; i < 2; i++)
                        asm volatile("cp.async.bulk.tensor.2d.global.shared::cta.bulk_group [%0, {%2, %3}], [%1];"
                            :: "l"(&M.xt), "r"(sb + OFF_LN + i * 8192), "r"((c & 1) * 1024 + (126 - (c & ~1)) * 8), "r"(256 * i) : "memory");
                    #pragma unroll 1
                    for (int i = 0; i < 2; i++) bulk_store(P.st + 16 * (c & ~1) + 8 * (c & 1) + 16 - 16 * i, sb + OFF_CSUM + 64 * i, 64);
                    asm volatile("cp.async.bulk.prefetch.L2.global [%0], %1;" :: "l"(P.Wd + c * (FF * DM / 128)), "r"(FF * DM / 64) : "memory");
                }
                asm volatile("cp.async.bulk.commit_group; cp.async.bulk.wait_group.read 0;" ::: "memory");
                mbar_arrive(bars + 8 * B_LNS);
                STAMP2(1);
                flag_signal(P.flags, F_A);
                STAMP2(2);
                flag_wait(P.flags, F_A, NCTA);
                STAMP(20);
                mbar_expect(bars + 8 * B_STATS, TOKG * 8);
                bulk_load(sb + OFF_ST, P.st + TOKG * tg, TOKG * 8, bars + 8 * B_STATS);
                if (c < 128) {
                    mbar_wait(bars + 8 * (B_K + 1), 0);
                    fence_async_smem();
                    mbar_expect(bars + 8 * B_U, 8 * 2048);
                    #pragma unroll 1
                    for (int i = 0; i < 8; i++)
                        bulk_load(sb + OFF_CONV + (i >> 1) * CH_STRIDE + CH_U + (i & 1) * UPLANE, P.xnT + 4 * c * 256 + i * 128, 2048, bars + 8 * B_U);
                } else exit_count(P.flags);
                #pragma unroll 1
                for (int V = 0; V < 2; V++) {
                    mbar_wait(bars + 8 * (B_EPI + V), 0);
                    STAMP2(3 + 2 * V);
                    asm volatile("cp.async.bulk.tensor.3d.global.shared::cta.bulk_group [%0, {%2, %3, %4}], [%1];"
                        :: "l"(&M.hst[V]), "r"(sb + OFF_X + V * 2 * XBUF), "r"(0), "r"(43 * tg + 21 * V), "r"(8 * fb) : "memory");
                    flag_signal(P.flags, F_H + 2 * tg + V);
                    mbar_arrive(bars + 8 * (B_STG + V));
                    STAMP2(4 + 2 * V);
                }
                if (c < 128) {
                    #pragma unroll 1
                    for (int V = 0; V < 2; V++) {
                        mbar_wait(bars + 8 * (B_SIG + V), 0);
                        STAMP2(7 + 2 * V);
                        bulk_store(P.S + (2 * c + V) * 1024, sb + OFF_CONV + V * OFF_SST, 8192);
                        flag_signal(P.flags, F_S + (c >> 5));
                        STAMP2(8 + 2 * V);
                    }
                    mbar_arrive(bars + 8 * B_SST);
                }
            }
        }
    }
    asm volatile("nanosleep.u32 0;");
}

typedef CUresult (*EncodeFn)(CUtensorMap*, CUtensorMapDataType, cuuint32_t, void*, const cuuint64_t*, const cuuint64_t*, const cuuint32_t*,
                             const cuuint32_t*, CUtensorMapInterleave, CUtensorMapSwizzle, CUtensorMapL2promotion, CUtensorMapFloatOOBfill);

void make_map(EncodeFn enc, CUtensorMap* m, const void* ptr, int rank, const cuuint64_t* dims, const cuuint64_t* strides, const cuuint32_t* box, bool swz) {
    const cuuint32_t es[5] = {1, 1, 1, 1, 1};
    enc(m, CU_TENSOR_MAP_DATA_TYPE_BFLOAT16, rank, (void*)ptr, dims, strides, box, es, CU_TENSOR_MAP_INTERLEAVE_NONE,
        swz ? CU_TENSOR_MAP_SWIZZLE_128B : CU_TENSOR_MAP_SWIZZLE_NONE, CU_TENSOR_MAP_L2_PROMOTION_L2_128B, CU_TENSOR_MAP_FLOAT_OOB_FILL_NONE);
}
void make_map2(EncodeFn enc, CUtensorMap* m, const void* ptr, cuuint64_t inner, cuuint64_t outer, cuuint32_t rows) {
    const cuuint64_t dims[2] = {inner, outer}, strides[1] = {inner * 2};
    const cuuint32_t box[2] = {64, rows};
    make_map(enc, m, ptr, 2, dims, strides, box, true);
}

}

extern "C" void kernel_launch(void* const* d_in, const int* in_sizes, int n_in, void* d_out, int out_size) {
    (void)in_sizes; (void)n_in; (void)out_size;
    static EncodeFn enc = nullptr;
    static void *hptr, *p_xnT, *p_st, *p_S, *p_flags;
    if (!enc) {
        cudaDriverEntryPointQueryResult qr;
        cudaGetDriverEntryPoint("cuTensorMapEncodeTiled", (void**)&enc, cudaEnableDefault, &qr);
        cudaFuncSetAttribute(fused_kernel, cudaFuncAttributeMaxDynamicSharedMemorySize, SMEM_BYTES);
        cudaGetSymbolAddress(&hptr, g_H); cudaGetSymbolAddress(&p_xnT, g_xnT); cudaGetSymbolAddress(&p_st, g_st);
        cudaGetSymbolAddress(&p_S, g_S); cudaGetSymbolAddress(&p_flags, g_flags);
    }
    Params P;
    P.x = (const __nv_bfloat16*)d_in[0]; P.logA = (const __nv_bfloat16*)d_in[1]; P.Aim = (const __nv_bfloat16*)d_in[2];
    P.Cr = (const __nv_bfloat16*)d_in[3]; P.Ci = (const __nv_bfloat16*)d_in[4]; P.logdt = (const __nv_bfloat16*)d_in[5];
    P.Dskip = (const __nv_bfloat16*)d_in[6];
    P.Wd = (const __nv_bfloat16*)d_in[10]; P.xnT = (uint4*)p_xnT; P.st = (float2*)p_st; P.S = (uint2*)p_S; P.flags = (unsigned*)p_flags;
    Maps M;
    make_map2(enc, &M.x[0], d_in[0], DM, SEQ, 168); make_map2(enc, &M.x[1], d_in[0], DM, SEQ, 176);
    make_map2(enc, &M.xo, d_in[0], DM, SEQ, 64);    make_map2(enc, &M.out, d_out, DM, SEQ, 64);
    make_map2(enc, &M.wg, d_in[8], FF, DM, 64);     make_map2(enc, &M.wu, d_in[9], FF, DM, 64);
    make_map2(enc, &M.wd, d_in[10], DM, FF, 64);
    for (int v = 0; v < 2; v++) {
        const cuuint64_t dims[3] = {64, 256, 172}, strides[2] = {128, 32768};
        const cuuint32_t box[3] = {64, (cuuint32_t)(21 + v), 8};
        make_map(enc, &M.hst[v], hptr, 3, dims, strides, box, false);
    }
    {
        const cuuint64_t dims[2] = {2048, 512}, strides[1] = {4096};
        const cuuint32_t box[2] = {16, 256};
        make_map(enc, &M.xt, p_xnT, 2, dims, strides, box, false);
    }
    {
        const cuuint64_t dims[5] = {64, 2, 4, 32, 64}, strides[4] = {4 * 8192, 8192, 8 * 8192, 128};
        const cuuint32_t box[5] = {64, 2, 4, 8, 2};
        make_map(enc, &M.sld, p_S, 5, dims, strides, box, true);
    }
    {
        const cuuint64_t dims[5] = {64, 2, 2, 64, 172}, strides[4] = {256, 128, 512, 32768};
        const cuuint32_t box[5] = {64, 2, 2, 2, 8};
        make_map(enc, &M.hld, hptr, 5, dims, strides, box, false);
    }
    fused_kernel<<<NCTA, 512, SMEM_BYTES>>>(P, M);
}
```

```cpp
#include <cuda_runtime.h>
#include <cuda_bf16.h>
#include <cuda.h>
#include <stdint.h>

#define PROF 0

namespace {

constexpr int SEQ = 2048, DM = 512, FF = 1376;
constexpr int NCTA = 132;
#define HOLD0 4
#define HOLD1 7
#define LAG 2
#define DLY1 300
#define DLY2 300
constexpr int RUNROLL = 8;
constexpr int TOKG = 344;

constexpr uint32_t OFF_W = 0;
constexpr uint32_t XBUF = 22528;
constexpr uint32_t OFF_X = 65536;
constexpr uint32_t OFF_CONV = 155648;
constexpr uint32_t CH_STRIDE = 17536;
constexpr uint32_t CH_T = 0;
constexpr uint32_t CH_A3 = 8448;
constexpr uint32_t CH_B3 = 12544;
constexpr uint32_t CH_U = 13312;
constexpr uint32_t CH_G = CH_A3 + 2064;
constexpr uint32_t UPLANE = 2112;
constexpr uint32_t OFF_LN = OFF_X + 3 * XBUF;
constexpr uint32_t OFF_SST = 60416;
constexpr uint32_t OFF_ST = 225792;
constexpr uint32_t OFF_CSUM = 228544;
constexpr uint32_t OFF_BAR = 229056;
constexpr uint32_t SMEM_BYTES = 229568;

enum {
    B_FULLW = 0, B_EMPTYW = 4, B_FULLX = 8, B_EMPTYX = 12, B_FULLD = 16, B_EMPTYD = 24,
    B_U = 32, B_XO = 33, B_S = 34, B_STG = 35, B_HF = 37, B_STATS = 38, B_LNS = 39, B_SST = 40,
    B_LNX = 41, B_GO = 42, B_CH0 = 43, B_K = 44,
    B_CONV = 46, B_LN = 50, B_CS = 51, B_EPI = 52, B_SIG = 54,
    B_COUNT = 56
};
enum { F_A = 0, F_H = 1, F_S = 13, F_EXIT = 17, F_COUNT = 18 };

__device__ uint4 g_xnT[DM * 256];
__device__ float2 g_st[6 * TOKG];
__device__ uint4 g_H[172 * 256 * 8];
__device__ uint2 g_S[256 * 1024];
__device__ unsigned g_flags[F_COUNT * 32];
#define STAMP(i) do {} while (0)
#define GSTAMP(i) do {} while (0)
#define STAMP2(i) do {} while (0)

__device__ __forceinline__ uint32_t smem_u32(const void* p) { return (uint32_t)__cvta_generic_to_shared(p); }
__device__ __forceinline__ void mbar_expect(uint32_t bar, uint32_t bytes) { asm volatile("mbarrier.arrive.expect_tx.shared::cta.b64 _, [%0], %1;" :: "r"(bar), "r"(bytes) : "memory"); }
__device__ __forceinline__ void mbar_arrive(uint32_t bar) { asm volatile("mbarrier.arrive.shared::cta.b64 _, [%0];" :: "r"(bar) : "memory"); }
__device__ __forceinline__ void mbar_wait(uint32_t bar, uint32_t parity) {
    asm volatile("{.reg .pred p; .reg .u32 n; mov.u32 n, 0x20000;\n"
                 "LW: mbarrier.try_wait.parity.shared::cta.b64 p, [%0], %1;\n"
                 "sub.u32 n, n, 1; setp.eq.or.u32 p, n, 0, p; @!p bra LW;}" :: "r"(bar), "r"(parity) : "memory");
}
__device__ __forceinline__ bool elect_one() { uint32_t p; asm volatile("{.reg .pred P; elect.sync _|P, 0xffffffff; selp.u32 %0, 1, 0, P;}" : "=r"(p)); return p; }
__device__ __forceinline__ void tma2d(uint32_t dst, const CUtensorMap* m, int c0, int c1, uint32_t bar) {
    asm volatile("cp.async.bulk.tensor.2d.shared::cluster.global.mbarrier::complete_tx::bytes [%0], [%1, {%3, %4}], [%2];"
        :: "r"(dst), "l"(m), "r"(bar), "r"(c0), "r"(c1) : "memory");
}
__device__ __forceinline__ void bulk_load(uint32_t dst, const void* src, uint32_t bytes, uint32_t bar) {
    asm volatile("cp.async.bulk.shared::cluster.global.mbarrier::complete_tx::bytes [%0], [%1], %2, [%3];" :: "r"(dst), "l"(src), "r"(bytes), "r"(bar) : "memory");
}
__device__ __forceinline__ void bulk_store(void* dst, uint32_t src, uint32_t bytes) {
    asm volatile("cp.async.bulk.global.shared::cta.bulk_group [%0], [%1], %2;" :: "l"(dst), "r"(src), "r"(bytes) : "memory");
}
__device__ __forceinline__ void fence_async_smem() { asm volatile("fence.proxy.async.shared::cta;" ::: "memory"); }
__device__ __forceinline__ void flag_wait(unsigned* g_flags, int f, unsigned target) {
    asm volatile("{.reg .pred p; .reg .u32 n, v; mov.u32 n, 0x40000;\n"
                 "LF: ld.acquire.gpu.global.u32 v, [%0]; setp.ge.u32 p, v, %1; @p bra LD;\n"
                 "sub.u32 n, n, 1; setp.ne.u32 p, n, 0; @p bra LF; trap;\nLD: }"
                 :: "l"(g_flags + f * 32), "r"(target) : "memory");
}
__device__ __forceinline__ void flag_signal(unsigned* g_flags, int f) {
    asm volatile("cp.async.bulk.commit_group; cp.async.bulk.wait_group 0; red.relaxed.gpu.global.add.u32 [%0], 1;" :: "l"(g_flags + f * 32) : "memory");
}
__device__ __forceinline__ void exit_count(unsigned* g_flags) {
    if (atomicAdd(g_flags + F_EXIT * 32, 1u) == NCTA - 1) {
        #pragma unroll 1
        for (int i = 0; i < F_COUNT; i++) g_flags[i * 32] = 0;
    }
}
__device__ __forceinline__ void bar_sync(int id) { asm volatile("bar.sync %0, 128;" :: "r"(id) : "memory"); }
__device__ __forceinline__ uint64_t mkdesc(uint32_t addr, uint32_t lbo, uint32_t sbo, uint32_t swz) {
    return (uint64_t)((addr >> 4) | ((lbo >> 4) << 16)) | ((uint64_t)((sbo >> 4) | (swz << 30)) << 32);
}
#define WG_FENCE() asm volatile("wgmma.fence.sync.aligned;" ::: "memory")
#define WG_COMMIT() asm volatile("wgmma.commit_group.sync.aligned;" ::: "memory")
#define WG_WAIT(n) asm volatile("wgmma.wait_group.sync.aligned " #n ";" ::: "memory")
template <int N> __device__ __forceinline__ void fence_acc(float (&d)[N]) {
    #pragma unroll
    for (int i = 0; i < N; i++) asm volatile("" : "+f"(d[i]) :: "memory");
}
template <int N> __device__ __forceinline__ void define_acc(float (&d)[N]) {
    #pragma unroll
    for (int i = 0; i < N; i++) asm volatile("" : "=f"(d[i]));
}
__device__ __forceinline__ uint32_t pack2(float lo, float hi) { uint32_t r; asm("cvt.rn.bf16x2.f32 %0, %1, %2;" : "=r"(r) : "f"(hi), "f"(lo)); return r; }
__device__ __forceinline__ float bf_lo(uint32_t v) { return __uint_as_float(v << 16); }
__device__ __forceinline__ float bf_hi(uint32_t v) { return __uint_as_float(v & 0xffff0000u); }
__device__ __forceinline__ float bf_round(float v) { return bf_hi(pack2(0.f, v)); }
__device__ __forceinline__ float tanh_fast(float v) { float r; asm("tanh.approx.f32 %0, %1;" : "=f"(r) : "f"(v)); return r; }
__device__ __forceinline__ float ex2(float v) { float r; asm("ex2.approx.ftz.f32 %0, %1;" : "=f"(r) : "f"(v)); return r; }
__device__ __forceinline__ uint4 lds128(uint32_t a) { uint4 v; asm volatile("ld.shared.v4.b32 {%0,%1,%2,%3}, [%4];" : "=r"(v.x), "=r"(v.y), "=r"(v.z), "=r"(v.w) : "r"(a)); return v; }
__device__ __forceinline__ uint2 lds64(uint32_t a) { uint2 v; asm volatile("ld.shared.v2.b32 {%0,%1}, [%2];" : "=r"(v.x), "=r"(v.y) : "r"(a)); return v; }
__device__ __forceinline__ float ldsf(uint32_t a) { float v; asm volatile("ld.shared.f32 %0, [%1];" : "=f"(v) : "r"(a)); return v; }
__device__ __forceinline__ void sts128(uint32_t a, uint32_t x, uint32_t y, uint32_t z, uint32_t w) { asm volatile("st.shared.v4.b32 [%0], {%1,%2,%3,%4};" :: "r"(a), "r"(x), "r"(y), "r"(z), "r"(w) : "memory"); }
__device__ __forceinline__ void sts64(uint32_t a, uint32_t x, uint32_t y) { asm volatile("st.shared.v2.b32 [%0], {%1,%2};" :: "r"(a), "r"(x), "r"(y) : "memory"); }
__device__ __forceinline__ void stsf(uint32_t a, float x) { asm volatile("st.shared.f32 [%0], %1;" :: "r"(a), "f"(x) : "memory"); }
__device__ __forceinline__ void sts16(uint32_t a, uint32_t x) { asm volatile("st.shared.b16 [%0], %1;" :: "r"(a), "h"((unsigned short)x) : "memory"); }
__device__ __forceinline__ void stsm4(uint32_t a, uint32_t r0, uint32_t r1, uint32_t r2, uint32_t r3) {
    asm volatile("stmatrix.sync.aligned.m8n8.x4.shared.b16 [%0], {%1,%2,%3,%4};" :: "r"(a), "r"(r0), "r"(r1), "r"(r2), "r"(r3) : "memory");
}
__device__ __forceinline__ void ldsm4(uint32_t (&r)[4], uint32_t a) {
    asm volatile("ldmatrix.sync.aligned.m8n8.x4.shared.b16 {%0,%1,%2,%3}, [%4];" : "=r"(r[0]), "=r"(r[1]), "=r"(r[2]), "=r"(r[3]) : "r"(a) : "memory");
}
#define FU(x) __float_as_uint(x)
#define UF(x) __uint_as_float(x)
__device__ __forceinline__ uint32_t wd_slot(int s) { return (uint32_t)((0xbba8403056201000ull >> (8 * s)) & 0xff) << 10; }
__device__ __forceinline__ uint32_t h_slot(int s) { return (uint32_t)((0xcba0908880787068ull >> (8 * s)) & 0xff) << 10; }

template<int N> __device__ __forceinline__ void wg_rs(float (&d)[64], uint32_t a0, uint32_t a1, uint32_t a2, uint32_t a3, uint64_t db);
template<> __device__ __forceinline__ void wg_rs<128>(float (&d)[64], uint32_t a0, uint32_t a1, uint32_t a2, uint32_t a3, uint64_t db) {
  asm volatile("{.reg .pred p; setp.ne.b32 p, 1, 0; wgmma.mma_async.sync.aligned.m64n128k16.f32.bf16.bf16 {%0,%1,%2,%3,%4,%5,%6,%7,%8,%9,%10,%11,%12,%13,%14,%15,%16,%17,%18,%19,%20,%21,%22,%23,%24,%25,%26,%27,%28,%29,%30,%31,%32,%33,%34,%35,%36,%37,%38,%39,%40,%41,%42,%43,%44,%45,%46,%47,%48,%49,%50,%51,%52,%53,%54,%55,%56,%57,%58,%59,%60,%61,%62,%63}, {%64,%65,%66,%67}, %68, p, 1, 1, 0;}"
    : "+f"(d[0]),"+f"(d[1]),"+f"(d[2]),"+f"(d[3]),"+f"(d[4]),"+f"(d[5]),"+f"(d[6]),"+f"(d[7]),"+f"(d[8]),"+f"(d[9]),"+f"(d[10]),"+f"(d[11]),"+f"(d[12]),"+f"(d[13]),"+f"(d[14]),"+f"(d[15]),"+f"(d[16]),"+f"(d[17]),"+f"(d[18]),"+f"(d[19]),"+f"(d[20]),"+f"(d[21]),"+f"(d[22]),"+f"(d[23]),"+f"(d[24]),"+f"(d[25]),"+f"(d[26]),"+f"(d[27]),"+f"(d[28]),"+f"(d[29]),"+f"(d[30]),"+f"(d[31]),"+f"(d[32]),"+f"(d[33]),"+f"(d[34]),"+f"(d[35]),"+f"(d[36]),"+f"(d[37]),"+f"(d[38]),"+f"(d[39]),"+f"(d[40]),"+f"(d[41]),"+f"(d[42]),"+f"(d[43]),"+f"(d[44]),"+f"(d[45]),"+f"(d[46]),"+f"(d[47]),"+f"(d[48]),"+f"(d[49]),"+f"(d[50]),"+f"(d[51]),"+f"(d[52]),"+f"(d[53]),"+f"(d[54]),"+f"(d[55]),"+f"(d[56]),"+f"(d[57]),"+f"(d[58]),"+f"(d[59]),"+f"(d[60]),"+f"(d[61]),"+f"(d[62]),"+f"(d[63]) : "r"(a0), "r"(a1), "r"(a2), "r"(a3), "l"(db));
}
template<> __device__ __forceinline__ void wg_rs<120>(float (&d)[64], uint32_t a0, uint32_t a1, uint32_t a2, uint32_t a3, uint64_t db) {
  asm volatile("{.reg .pred p; setp.ne.b32 p, 1, 0; wgmma.mma_async.sync.aligned.m64n120k16.f32.bf16.bf16 {%0,%1,%2,%3,%4,%5,%6,%7,%8,%9,%10,%11,%12,%13,%14,%15,%16,%17,%18,%19,%20,%21,%22,%23,%24,%25,%26,%27,%28,%29,%30,%31,%32,%33,%34,%35,%36,%37,%38,%39,%40,%41,%42,%43,%44,%45,%46,%47,%48,%49,%50,%51,%52,%53,%54,%55,%56,%57,%58,%59}, {%60,%61,%62,%63}, %64, p, 1, 1, 0;}"
    : "+f"(d[0]),"+f"(d[1]),"+f"(d[2]),"+f"(d[3]),"+f"(d[4]),"+f"(d[5]),"+f"(d[6]),"+f"(d[7]),"+f"(d[8]),"+f"(d[9]),"+f"(d[10]),"+f"(d[11]),"+f"(d[12]),"+f"(d[13]),"+f"(d[14]),"+f"(d[15]),"+f"(d[16]),"+f"(d[17]),"+f"(d[18]),"+f"(d[19]),"+f"(d[20]),"+f"(d[21]),"+f"(d[22]),"+f"(d[23]),"+f"(d[24]),"+f"(d[25]),"+f"(d[26]),"+f"(d[27]),"+f"(d[28]),"+f"(d[29]),"+f"(d[30]),"+f"(d[31]),"+f"(d[32]),"+f"(d[33]),"+f"(d[34]),"+f"(d[35]),"+f"(d[36]),"+f"(d[37]),"+f"(d[38]),"+f"(d[39]),"+f"(d[40]),"+f"(d[41]),"+f"(d[42]),"+f"(d[43]),"+f"(d[44]),"+f"(d[45]),"+f"(d[46]),"+f"(d[47]),"+f"(d[48]),"+f"(d[49]),"+f"(d[50]),"+f"(d[51]),"+f"(d[52]),"+f"(d[53]),"+f"(d[54]),"+f"(d[55]),"+f"(d[56]),"+f"(d[57]),"+f"(d[58]),"+f"(d[59]) : "r"(a0), "r"(a1), "r"(a2), "r"(a3), "l"(db));
}
template<> __device__ __forceinline__ void wg_rs<112>(float (&d)[64], uint32_t a0, uint32_t a1, uint32_t a2, uint32_t a3, uint64_t db) {
  asm volatile("{.reg .pred p; setp.ne.b32 p, 1, 0; wgmma.mma_async.sync.aligned.m64n112k16.f32.bf16.bf16 {%0,%1,%2,%3,%4,%5,%6,%7,%8,%9,%10,%11,%12,%13,%14,%15,%16,%17,%18,%19,%20,%21,%22,%23,%24,%25,%26,%27,%28,%29,%30,%31,%32,%33,%34,%35,%36,%37,%38,%39,%40,%41,%42,%43,%44,%45,%46,%47,%48,%49,%50,%51,%52,%53,%54,%55}, {%56,%57,%58,%59}, %60, p, 1, 1, 0;}"
    : "+f"(d[0]),"+f"(d[1]),"+f"(d[2]),"+f"(d[3]),"+f"(d[4]),"+f"(d[5]),"+f"(d[6]),"+f"(d[7]),"+f"(d[8]),"+f"(d[9]),"+f"(d[10]),"+f"(d[11]),"+f"(d[12]),"+f"(d[13]),"+f"(d[14]),"+f"(d[15]),"+f"(d[16]),"+f"(d[17]),"+f"(d[18]),"+f"(d[19]),"+f"(d[20]),"+f"(d[21]),"+f"(d[22]),"+f"(d[23]),"+f"(d[24]),"+f"(d[25]),"+f"(d[26]),"+f"(d[27]),"+f"(d[28]),"+f"(d[29]),"+f"(d[30]),"+f"(d[31]),"+f"(d[32]),"+f"(d[33]),"+f"(d[34]),"+f"(d[35]),"+f"(d[36]),"+f"(d[37]),"+f"(d[38]),"+f"(d[39]),"+f"(d[40]),"+f"(d[41]),"+f"(d[42]),"+f"(d[43]),"+f"(d[44]),"+f"(d[45]),"+f"(d[46]),"+f"(d[47]),"+f"(d[48]),"+f"(d[49]),"+f"(d[50]),"+f"(d[51]),"+f"(d[52]),"+f"(d[53]),"+f"(d[54]),"+f"(d[55]) : "r"(a0), "r"(a1), "r"(a2), "r"(a3), "l"(db));
}
template<> __device__ __forceinline__ void wg_rs<104>(float (&d)[64], uint32_t a0, uint32_t a1, uint32_t a2, uint32_t a3, uint64_t db) {
  asm volatile("{.reg .pred p; setp.ne.b32 p, 1, 0; wgmma.mma_async.sync.aligned.m64n104k16.f32.bf16.bf16 {%0,%1,%2,%3,%4,%5,%6,%7,%8,%9,%10,%11,%12,%13,%14,%15,%16,%17,%18,%19,%20,%21,%22,%23,%24,%25,%26,%27,%28,%29,%30,%31,%32,%33,%34,%35,%36,%37,%38,%39,%40,%41,%42,%43,%44,%45,%46,%47,%48,%49,%50,%51}, {%52,%53,%54,%55}, %56, p, 1, 1, 0;}"
    : "+f"(d[0]),"+f"(d[1]),"+f"(d[2]),"+f"(d[3]),"+f"(d[4]),"+f"(d[5]),"+f"(d[6]),"+f"(d[7]),"+f"(d[8]),"+f"(d[9]),"+f"(d[10]),"+f"(d[11]),"+f"(d[12]),"+f"(d[13]),"+f"(d[14]),"+f"(d[15]),"+f"(d[16]),"+f"(d[17]),"+f"(d[18]),"+f"(d[19]),"+f"(d[20]),"+f"(d[21]),"+f"(d[22]),"+f"(d[23]),"+f"(d[24]),"+f"(d[25]),"+f"(d[26]),"+f"(d[27]),"+f"(d[28]),"+f"(d[29]),"+f"(d[30]),"+f"(d[31]),"+f"(d[32]),"+f"(d[33]),"+f"(d[34]),"+f"(d[35]),"+f"(d[36]),"+f"(d[37]),"+f"(d[38]),"+f"(d[39]),"+f"(d[40]),"+f"(d[41]),"+f"(d[42]),"+f"(d[43]),"+f"(d[44]),"+f"(d[45]),"+f"(d[46]),"+f"(d[47]),"+f"(d[48]),"+f"(d[49]),"+f"(d[50]),"+f"(d[51]) : "r"(a0), "r"(a1), "r"(a2), "r"(a3), "l"(db));
}
template<> __device__ __forceinline__ void wg_rs<96>(float (&d)[64], uint32_t a0, uint32_t a1, uint32_t a2, uint32_t a3, uint64_t db) {
  asm volatile("{.reg .pred p; setp.ne.b32 p, 1, 0; wgmma.mma_async.sync.aligned.m64n96k16.f32.bf16.bf16 {%0,%1,%2,%3,%4,%5,%6,%7,%8,%9,%10,%11,%12,%13,%14,%15,%16,%17,%18,%19,%20,%21,%22,%23,%24,%25,%26,%27,%28,%29,%30,%31,%32,%33,%34,%35,%36,%37,%38,%39,%40,%41,%42,%43,%44,%45,%46,%47}, {%48,%49,%50,%51}, %52, p, 1, 1, 0;}"
    : "+f"(d[0]),"+f"(d[1]),"+f"(d[2]),"+f"(d[3]),"+f"(d[4]),"+f"(d[5]),"+f"(d[6]),"+f"(d[7]),"+f"(d[8]),"+f"(d[9]),"+f"(d[10]),"+f"(d[11]),"+f"(d[12]),"+f"(d[13]),"+f"(d[14]),"+f"(d[15]),"+f"(d[16]),"+f"(d[17]),"+f"(d[18]),"+f"(d[19]),"+f"(d[20]),"+f"(d[21]),"+f"(d[22]),"+f"(d[23]),"+f"(d[24]),"+f"(d[25]),"+f"(d[26]),"+f"(d[27]),"+f"(d[28]),"+f"(d[29]),"+f"(d[30]),"+f"(d[31]),"+f"(d[32]),"+f"(d[33]),"+f"(d[34]),"+f"(d[35]),"+f"(d[36]),"+f"(d[37]),"+f"(d[38]),"+f"(d[39]),"+f"(d[40]),"+f"(d[41]),"+f"(d[42]),"+f"(d[43]),"+f"(d[44]),"+f"(d[45]),"+f"(d[46]),"+f"(d[47]) : "r"(a0), "r"(a1), "r"(a2), "r"(a3), "l"(db));
}
template<> __device__ __forceinline__ void wg_rs<88>(float (&d)[64], uint32_t a0, uint32_t a1, uint32_t a2, uint32_t a3, uint64_t db) {
  asm volatile("{.reg .pred p; setp.ne.b32 p, 1, 0; wgmma.mma_async.sync.aligned.m64n88k16.f32.bf16.bf16 {%0,%1,%2,%3,%4,%5,%6,%7,%8,%9,%10,%11,%12,%13,%14,%15,%16,%17,%18,%19,%20,%21,%22,%23,%24,%25,%26,%27,%28,%29,%30,%31,%32,%33,%34,%35,%36,%37,%38,%39,%40,%41,%42,%43}, {%44,%45,%46,%47}, %48, p, 1, 1, 0;}"
    : "+f"(d[0]),"+f"(d[1]),"+f"(d[2]),"+f"(d[3]),"+f"(d[4]),"+f"(d[5]),"+f"(d[6]),"+f"(d[7]),"+f"(d[8]),"+f"(d[9]),"+f"(d[10]),"+f"(d[11]),"+f"(d[12]),"+f"(d[13]),"+f"(d[14]),"+f"(d[15]),"+f"(d[16]),"+f"(d[17]),"+f"(d[18]),"+f"(d[19]),"+f"(d[20]),"+f"(d[21]),"+f"(d[22]),"+f"(d[23]),"+f"(d[24]),"+f"(d[25]),"+f"(d[26]),"+f"(d[27]),"+f"(d[28]),"+f"(d[29]),"+f"(d[30]),"+f"(d[31]),"+f"(d[32]),"+f"(d[33]),"+f"(d[34]),"+f"(d[35]),"+f"(d[36]),"+f"(d[37]),"+f"(d[38]),"+f"(d[39]),"+f"(d[40]),"+f"(d[41]),"+f"(d[42]),"+f"(d[43]) : "r"(a0), "r"(a1), "r"(a2), "r"(a3), "l"(db));
}
template<> __device__ __forceinline__ void wg_rs<80>(float (&d)[64], uint32_t a0, uint32_t a1, uint32_t a2, uint32_t a3, uint64_t db) {
  asm volatile("{.reg .pred p; setp.ne.b32 p, 1, 0; wgmma.mma_async.sync.aligned.m64n80k16.f32.bf16.bf16 {%0,%1,%2,%3,%4,%5,%6,%7,%8,%9,%10,%11,%12,%13,%14,%15,%16,%17,%18,%19,%20,%21,%22,%23,%24,%25,%26,%27,%28,%29,%30,%31,%32,%33,%34,%35,%36,%37,%38,%39}, {%40,%41,%42,%43}, %44, p, 1, 1, 0;}"
    : "+f"(d[0]),"+f"(d[1]),"+f"(d[2]),"+f"(d[3]),"+f"(d[4]),"+f"(d[5]),"+f"(d[6]),"+f"(d[7]),"+f"(d[8]),"+f"(d[9]),"+f"(d[10]),"+f"(d[11]),"+f"(d[12]),"+f"(d[13]),"+f"(d[14]),"+f"(d[15]),"+f"(d[16]),"+f"(d[17]),"+f"(d[18]),"+f"(d[19]),"+f"(d[20]),"+f"(d[21]),"+f"(d[22]),"+f"(d[23]),"+f"(d[24]),"+f"(d[25]),"+f"(d[26]),"+f"(d[27]),"+f"(d[28]),"+f"(d[29]),"+f"(d[30]),"+f"(d[31]),"+f"(d[32]),"+f"(d[33]),"+f"(d[34]),"+f"(d[35]),"+f"(d[36]),"+f"(d[37]),"+f"(d[38]),"+f"(d[39]) : "r"(a0), "r"(a1), "r"(a2), "r"(a3), "l"(db));
}
template<> __device__ __forceinline__ void wg_rs<72>(float (&d)[64], uint32_t a0, uint32_t a1, uint32_t a2, uint32_t a3, uint64_t db) {
  asm volatile("{.reg .pred p; setp.ne.b32 p, 1, 0; wgmma.mma_async.sync.aligned.m64n72k16.f32.bf16.bf16 {%0,%1,%2,%3,%4,%5,%6,%7,%8,%9,%10,%11,%12,%13,%14,%15,%16,%17,%18,%19,%20,%21,%22,%23,%24,%25,%26,%27,%28,%29,%30,%31,%32,%33,%34,%35}, {%36,%37,%38,%39}, %40, p, 1, 1, 0;}"
    : "+f"(d[0]),"+f"(d[1]),"+f"(d[2]),"+f"(d[3]),"+f"(d[4]),"+f"(d[5]),"+f"(d[6]),"+f"(d[7]),"+f"(d[8]),"+f"(d[9]),"+f"(d[10]),"+f"(d[11]),"+f"(d[12]),"+f"(d[13]),"+f"(d[14]),"+f"(d[15]),"+f"(d[16]),"+f"(d[17]),"+f"(d[18]),"+f"(d[19]),"+f"(d[20]),"+f"(d[21]),"+f"(d[22]),"+f"(d[23]),"+f"(d[24]),"+f"(d[25]),"+f"(d[26]),"+f"(d[27]),"+f"(d[28]),"+f"(d[29]),"+f"(d[30]),"+f"(d[31]),"+f"(d[32]),"+f"(d[33]),"+f"(d[34]),"+f"(d[35]) : "r"(a0), "r"(a1), "r"(a2), "r"(a3), "l"(db));
}
template<> __device__ __forceinline__ void wg_rs<64>(float (&d)[64], uint32_t a0, uint32_t a1, uint32_t a2, uint32_t a3, uint64_t db) {
  asm volatile("{.reg .pred p; setp.ne.b32 p, 1, 0; wgmma.mma_async.sync.aligned.m64n64k16.f32.bf16.bf16 {%0,%1,%2,%3,%4,%5,%6,%7,%8,%9,%10,%11,%12,%13,%14,%15,%16,%17,%18,%19,%20,%21,%22,%23,%24,%25,%26,%27,%28,%29,%30,%31}, {%32,%33,%34,%35}, %36, p, 1, 1, 0;}"
    : "+f"(d[0]),"+f"(d[1]),"+f"(d[2]),"+f"(d[3]),"+f"(d[4]),"+f"(d[5]),"+f"(d[6]),"+f"(d[7]),"+f"(d[8]),"+f"(d[9]),"+f"(d[10]),"+f"(d[11]),"+f"(d[12]),"+f"(d[13]),"+f"(d[14]),"+f"(d[15]),"+f"(d[16]),"+f"(d[17]),"+f"(d[18]),"+f"(d[19]),"+f"(d[20]),"+f"(d[21]),"+f"(d[22]),"+f"(d[23]),"+f"(d[24]),"+f"(d[25]),"+f"(d[26]),"+f"(d[27]),"+f"(d[28]),"+f"(d[29]),"+f"(d[30]),"+f"(d[31]) : "r"(a0), "r"(a1), "r"(a2), "r"(a3), "l"(db));
}
__device__ __forceinline__ void wg_rs_first(float (&d)[64], uint32_t a0, uint32_t a1, uint32_t a2, uint32_t a3, uint64_t db) {
  asm volatile("{.reg .pred p; setp.ne.b32 p, 0, 0; wgmma.mma_async.sync.aligned.m64n128k16.f32.bf16.bf16 {%0,%1,%2,%3,%4,%5,%6,%7,%8,%9,%10,%11,%12,%13,%14,%15,%16,%17,%18,%19,%20,%21,%22,%23,%24,%25,%26,%27,%28,%29,%30,%31,%32,%33,%34,%35,%36,%37,%38,%39,%40,%41,%42,%43,%44,%45,%46,%47,%48,%49,%50,%51,%52,%53,%54,%55,%56,%57,%58,%59,%60,%61,%62,%63}, {%64,%65,%66,%67}, %68, p, 1, 1, 0;}"
    : "=f"(d[0]),"=f"(d[1]),"=f"(d[2]),"=f"(d[3]),"=f"(d[4]),"=f"(d[5]),"=f"(d[6]),"=f"(d[7]),"=f"(d[8]),"=f"(d[9]),"=f"(d[10]),"=f"(d[11]),"=f"(d[12]),"=f"(d[13]),"=f"(d[14]),"=f"(d[15]),"=f"(d[16]),"=f"(d[17]),"=f"(d[18]),"=f"(d[19]),"=f"(d[20]),"=f"(d[21]),"=f"(d[22]),"=f"(d[23]),"=f"(d[24]),"=f"(d[25]),"=f"(d[26]),"=f"(d[27]),"=f"(d[28]),"=f"(d[29]),"=f"(d[30]),"=f"(d[31]),"=f"(d[32]),"=f"(d[33]),"=f"(d[34]),"=f"(d[35]),"=f"(d[36]),"=f"(d[37]),"=f"(d[38]),"=f"(d[39]),"=f"(d[40]),"=f"(d[41]),"=f"(d[42]),"=f"(d[43]),"=f"(d[44]),"=f"(d[45]),"=f"(d[46]),"=f"(d[47]),"=f"(d[48]),"=f"(d[49]),"=f"(d[50]),"=f"(d[51]),"=f"(d[52]),"=f"(d[53]),"=f"(d[54]),"=f"(d[55]),"=f"(d[56]),"=f"(d[57]),"=f"(d[58]),"=f"(d[59]),"=f"(d[60]),"=f"(d[61]),"=f"(d[62]),"=f"(d[63]) : "r"(a0), "r"(a1), "r"(a2), "r"(a3), "l"(db));
}
__device__ __forceinline__ void wg_tt128(float (&d)[64], uint64_t da, uint64_t db, int sc) {
  asm volatile("{.reg .pred p; setp.ne.b32 p, %66, 0; wgmma.mma_async.sync.aligned.m64n128k16.f32.bf16.bf16 {%0,%1,%2,%3,%4,%5,%6,%7,%8,%9,%10,%11,%12,%13,%14,%15,%16,%17,%18,%19,%20,%21,%22,%23,%24,%25,%26,%27,%28,%29,%30,%31,%32,%33,%34,%35,%36,%37,%38,%39,%40,%41,%42,%43,%44,%45,%46,%47,%48,%49,%50,%51,%52,%53,%54,%55,%56,%57,%58,%59,%60,%61,%62,%63}, %64, %65, p, 1, 1, 1, 1;}"
    : "+f"(d[0]),"+f"(d[1]),"+f"(d[2]),"+f"(d[3]),"+f"(d[4]),"+f"(d[5]),"+f"(d[6]),"+f"(d[7]),"+f"(d[8]),"+f"(d[9]),"+f"(d[10]),"+f"(d[11]),"+f"(d[12]),"+f"(d[13]),"+f"(d[14]),"+f"(d[15]),"+f"(d[16]),"+f"(d[17]),"+f"(d[18]),"+f"(d[19]),"+f"(d[20]),"+f"(d[21]),"+f"(d[22]),"+f"(d[23]),"+f"(d[24]),"+f"(d[25]),"+f"(d[26]),"+f"(d[27]),"+f"(d[28]),"+f"(d[29]),"+f"(d[30]),"+f"(d[31]),"+f"(d[32]),"+f"(d[33]),"+f"(d[34]),"+f"(d[35]),"+f"(d[36]),"+f"(d[37]),"+f"(d[38]),"+f"(d[39]),"+f"(d[40]),"+f"(d[41]),"+f"(d[42]),"+f"(d[43]),"+f"(d[44]),"+f"(d[45]),"+f"(d[46]),"+f"(d[47]),"+f"(d[48]),"+f"(d[49]),"+f"(d[50]),"+f"(d[51]),"+f"(d[52]),"+f"(d[53]),"+f"(d[54]),"+f"(d[55]),"+f"(d[56]),"+f"(d[57]),"+f"(d[58]),"+f"(d[59]),"+f"(d[60]),"+f"(d[61]),"+f"(d[62]),"+f"(d[63]) : "l"(da), "l"(db), "r"(sc));
}
__device__ __forceinline__ void wg_tt64(float (&d)[64], uint64_t da, uint64_t db, int sc) {
  asm volatile("{.reg .pred p; setp.ne.b32 p, %34, 0; wgmma.mma_async.sync.aligned.m64n64k16.f32.bf16.bf16 {%0,%1,%2,%3,%4,%5,%6,%7,%8,%9,%10,%11,%12,%13,%14,%15,%16,%17,%18,%19,%20,%21,%22,%23,%24,%25,%26,%27,%28,%29,%30,%31}, %32, %33, p, 1, 1, 1, 1;}"
    : "+f"(d[0]),"+f"(d[1]),"+f"(d[2]),"+f"(d[3]),"+f"(d[4]),"+f"(d[5]),"+f"(d[6]),"+f"(d[7]),"+f"(d[8]),"+f"(d[9]),"+f"(d[10]),"+f"(d[11]),"+f"(d[12]),"+f"(d[13]),"+f"(d[14]),"+f"(d[15]),"+f"(d[16]),"+f"(d[17]),"+f"(d[18]),"+f"(d[19]),"+f"(d[20]),"+f"(d[21]),"+f"(d[22]),"+f"(d[23]),"+f"(d[24]),"+f"(d[25]),"+f"(d[26]),"+f"(d[27]),"+f"(d[28]),"+f"(d[29]),"+f"(d[30]),"+f"(d[31]) : "l"(da), "l"(db), "r"(sc));
}
__device__ __forceinline__ void wg_tt32(float (&d)[64], uint64_t da, uint64_t db, int sc) {
  asm volatile("{.reg .pred p; setp.ne.b32 p, %18, 0; wgmma.mma_async.sync.aligned.m64n32k16.f32.bf16.bf16 {%0,%1,%2,%3,%4,%5,%6,%7,%8,%9,%10,%11,%12,%13,%14,%15}, %16, %17, p, 1, 1, 1, 1;}"
    : "+f"(d[0]),"+f"(d[1]),"+f"(d[2]),"+f"(d[3]),"+f"(d[4]),"+f"(d[5]),"+f"(d[6]),"+f"(d[7]),"+f"(d[8]),"+f"(d[9]),"+f"(d[10]),"+f"(d[11]),"+f"(d[12]),"+f"(d[13]),"+f"(d[14]),"+f"(d[15]) : "l"(da), "l"(db), "r"(sc));
}
__device__ __forceinline__ void wg_g1(float (&d)[88], uint64_t da, uint64_t db, int sc) {
  asm volatile("{.reg .pred p; setp.ne.b32 p, %90, 0; wgmma.mma_async.sync.aligned.m64n176k16.f32.bf16.bf16 {%0,%1,%2,%3,%4,%5,%6,%7,%8,%9,%10,%11,%12,%13,%14,%15,%16,%17,%18,%19,%20,%21,%22,%23,%24,%25,%26,%27,%28,%29,%30,%31,%32,%33,%34,%35,%36,%37,%38,%39,%40,%41,%42,%43,%44,%45,%46,%47,%48,%49,%50,%51,%52,%53,%54,%55,%56,%57,%58,%59,%60,%61,%62,%63,%64,%65,%66,%67,%68,%69,%70,%71,%72,%73,%74,%75,%76,%77,%78,%79,%80,%81,%82,%83,%84,%85,%86,%87}, %88, %89, p, 1, 1, 1, 0;}"
    : "+f"(d[0]),"+f"(d[1]),"+f"(d[2]),"+f"(d[3]),"+f"(d[4]),"+f"(d[5]),"+f"(d[6]),"+f"(d[7]),"+f"(d[8]),"+f"(d[9]),"+f"(d[10]),"+f"(d[11]),"+f"(d[12]),"+f"(d[13]),"+f"(d[14]),"+f"(d[15]),"+f"(d[16]),"+f"(d[17]),"+f"(d[18]),"+f"(d[19]),"+f"(d[20]),"+f"(d[21]),"+f"(d[22]),"+f"(d[23]),"+f"(d[24]),"+f"(d[25]),"+f"(d[26]),"+f"(d[27]),"+f"(d[28]),"+f"(d[29]),"+f"(d[30]),"+f"(d[31]),"+f"(d[32]),"+f"(d[33]),"+f"(d[34]),"+f"(d[35]),"+f"(d[36]),"+f"(d[37]),"+f"(d[38]),"+f"(d[39]),"+f"(d[40]),"+f"(d[41]),"+f"(d[42]),"+f"(d[43]),"+f"(d[44]),"+f"(d[45]),"+f"(d[46]),"+f"(d[47]),"+f"(d[48]),"+f"(d[49]),"+f"(d[50]),"+f"(d[51]),"+f"(d[52]),"+f"(d[53]),"+f"(d[54]),"+f"(d[55]),"+f"(d[56]),"+f"(d[57]),"+f"(d[58]),"+f"(d[59]),"+f"(d[60]),"+f"(d[61]),"+f"(d[62]),"+f"(d[63]),"+f"(d[64]),"+f"(d[65]),"+f"(d[66]),"+f"(d[67]),"+f"(d[68]),"+f"(d[69]),"+f"(d[70]),"+f"(d[71]),"+f"(d[72]),"+f"(d[73]),"+f"(d[74]),"+f"(d[75]),"+f"(d[76]),"+f"(d[77]),"+f"(d[78]),"+f"(d[79]),"+f"(d[80]),"+f"(d[81]),"+f"(d[82]),"+f"(d[83]),"+f"(d[84]),"+f"(d[85]),"+f"(d[86]),"+f"(d[87]) : "l"(da), "l"(db), "r"(sc));
}

struct Params { const __nv_bfloat16 *x, *logA, *Aim, *Cr, *Ci, *logdt, *Dskip, *Wd; uint4* xnT; float2* st; uint2* S; unsigned* flags; };
struct Maps { CUtensorMap x[2], xo, out, wg, wu, wd, hst[2], hld, xt, sld; };

__device__ __forceinline__ void conv_channel(uint32_t cb, int w, int lane, uint32_t (&res)[8], uint32_t sig, int sidx) {
    const int q = lane & 3, g = lane >> 2, gam = g >> 2;
    float acc[64];
    uint2 a[17][2];
    const uint32_t t0 = cb + CH_T + (uint32_t)(14 + 4 * w + (g & 3) - 2 * q) * 280u + gam * 8;
#define LDA(s0, s1) _Pragma("unroll") for (int s = s0; s < s1; s++) { a[s][0] = lds64(t0 + s * 16); a[s][1] = lds64(t0 - 8 * 280 + s * 16); }
#define CT(N, s) wg_rs<N>(acc, a[s][0].x, a[s][0].y, a[s][1].x, a[s][1].y, dU + 4 * (s))
    const uint64_t dU = mkdesc(cb + CH_U, UPLANE, 128, 0);
    LDA(0, 17)
    if (sig) { fence_async_smem(); mbar_arrive(sig); }
    WG_FENCE();
    if (w == 0) STAMP2(52 + 3 * sidx);
    wg_rs_first(acc, a[0][0].x, a[0][0].y, a[0][1].x, a[0][1].y, dU);
    CT(128, 1); CT(120, 2); CT(120, 3); CT(112, 4); CT(112, 5); CT(104, 6); CT(104, 7); CT(96, 8);
    CT(96, 9); CT(88, 10); CT(88, 11); CT(80, 12); CT(80, 13); CT(72, 14); CT(72, 15); CT(64, 16);
#undef CT
#undef LDA
    wg_tt64(acc, mkdesc(cb + CH_A3, 128, 512, 0), mkdesc(cb + CH_B3, 384, 32, 0), 1);
    wg_tt32(acc, mkdesc(cb + CH_A3 + 256, 128, 512, 0), mkdesc(cb + CH_B3 + 128, 384, 32, 0), 1);
    WG_COMMIT();
    if (w == 0) STAMP2(53 + 3 * sidx);
    WG_WAIT(0);
    fence_acc(acc);
    if (w == 0) STAMP2(54 + 3 * sidx);
    const int src1 = (lane & ~3) | ((q + 1) & 3);
    float E[16][2];
    #pragma unroll
    for (int j = 0; j < 16; j++) {
        const float nxt = (j < 15) ? acc[4 * (j + 1) + 2] : 0.f;
        const float sup = (q == 0) ? nxt : acc[4 * j + 2];
        const float v = __shfl_sync(0xffffffffu, sup, src1);
        E[j][0] = acc[4 * j] + acc[4 * j + 3];
        E[j][1] = acc[4 * j + 1] + v;
    }
    const int src2 = gam ? ((lane & 12) | ((q + 3) & 3)) : (16 | (lane & 12) | ((q + 1) & 3));
    const bool c1 = gam && q != 0, c2 = gam && q == 0;
    #pragma unroll
    for (int a2 = 0; a2 < 8; a2++) {
        float y[2];
        #pragma unroll
        for (int e = 0; e < 2; e++) {
            const float sup = c1 ? E[2 * a2][e] : E[2 * a2 + 1][e];
            const float nxt = (a2 < 7) ? E[2 * a2 + 2][e] : 0.f;
            const float keep = c2 ? nxt : (c1 ? E[2 * a2 + 1][e] : E[2 * a2][e]);
            y[e] = keep + __shfl_sync(0xffffffffu, sup, src2);
        }
        res[a2] = pack2(y[1], y[0]);
    }
}

__device__ __forceinline__ void layer_norm(uint32_t sb, int w, int lane, const __nv_bfloat16* x) {
    const uint32_t bars = sb + OFF_BAR;
    const int c = blockIdx.x;
    {
        if (elect_one()) {
            { const uint32_t t0 = clock(); while ((uint32_t)clock() - t0 < DLY2) ; }
            mbar_expect(bars + 8 * B_LNX, 4096);
            #pragma unroll
            for (int i = 0; i < 4; i++)
                bulk_load(sb + OFF_LN + (w + 4 * i) * 1152 + ((w & 1) + 2 * i) * 16, x + (16 * (c & ~1) + 8 * (c & 1) + 16 + w + 4 * (i & 1) - 8 * (i & 2)) * DM, 1024, bars + 8 * B_LNX);
        }
        mbar_wait(bars + 8 * B_LNX, 0);
        STAMP(34);
        {
            const int r = w + 4 * (lane >> 3);
            const uint32_t r0 = sb + OFF_LN + r * 1152 + ((w & 1) + 2 * (lane >> 3)) * 16, ra = r0 + (lane & 7) * 16;
            const float pv = bf_lo(FU(ldsf(r0)));
            float s0 = 0.f, s1 = 0.f, a0 = 0.f, a1 = 0.f;
            uint4 nx = lds128(ra), ny = lds128(ra + 128);
            #pragma unroll 2
            for (int k = 128; k <= 1024; k += 128) {
                const uint32_t v[4] = {nx.x, nx.y, nx.z, nx.w};
                nx = ny; ny = lds128(ra + ((k + 128) & 1023));
                #pragma unroll
                for (int i = 0; i < 4; i++) { const float t0 = bf_lo(v[i]) - pv, t1 = bf_hi(v[i]) - pv; s0 += t0; s1 += t1; a0 = fmaf(t0, t0, a0); a1 = fmaf(t1, t1, a1); }
            }
            s0 += s1; a0 += a1;
            #pragma unroll
            for (int o = 4; o; o >>= 1) { s0 += __shfl_xor_sync(0xffffffffu, s0, o); a0 += __shfl_xor_sync(0xffffffffu, a0, o); }
            s0 *= 1.f / DM;
            const float m = pv + s0, var = fmaxf(fmaf(-s0, s0, a0 * (1.f / DM)), 0.f);
            float sd, ri;
            asm("sqrt.approx.ftz.f32 %0, %1;" : "=f"(sd) : "f"(bf_round(bf_round(var) + 1e-5f)));
            asm("rcp.approx.ftz.f32 %0, %1;" : "=f"(ri) : "f"(bf_round(sd)));
            const uint32_t m2 = pack2(m, m);
            if ((lane & 7) == 0) {
                sts64(sb + OFF_CSUM + r * 8, m2 & 0xffff0000u, FU(0.5f * ri));
            }
            #pragma unroll 2
            for (int k = 128; k <= 1024; k += 128) {
                uint32_t v[4] = {nx.x, nx.y, nx.z, nx.w};
                nx = ny; ny = lds128(ra + ((k + 128) & 1023));
                #pragma unroll
                for (int i = 0; i < 4; i++) {
                    uint32_t dv; asm("sub.rn.bf16x2 %0, %1, %2;" : "=r"(dv) : "r"(v[i]), "r"(m2));
                    v[i] = pack2(bf_lo(dv) * ri, bf_hi(dv) * ri);
                }
                sts128(ra + k - 128, v[0], v[1], v[2], v[3]);
            }
        }
        STAMP(62);
        bar_sync(4);
        {
            const uint32_t ad = sb + OFF_LN + (4 * ((lane & 7) >> 1) + (lane & 1) + 2 * ((lane >> 3) & 1)) * 1152 + (16 * w + (lane >> 4) + (lane & 7)) * 16;
            uint32_t r[8][4];
            #pragma unroll
            for (int i = 0; i < 8; i++)
                asm volatile("ldmatrix.sync.aligned.m8n8.x4.trans.shared.b16 {%0,%1,%2,%3}, [%4];" : "=r"(r[i][0]), "=r"(r[i][1]), "=r"(r[i][2]), "=r"(r[i][3]) : "r"(ad + 32 * i) : "memory");
            bar_sync(4);
            const uint32_t od = sb + OFF_LN + w * 4096 + lane * 8;
            #pragma unroll
            for (int i = 0; i < 8; i++) { sts64(od + i * 512, r[i][0], r[i][1]); sts64(od + i * 512 + 256, r[i][2], r[i][3]); }
        }
        fence_async_smem();
        mbar_arrive(bars + 8 * B_LN);
        STAMP(16);
    }
}

__device__ __forceinline__ void consumer(uint32_t sb, int warp, const Params& P, const Maps& M) {
    const int V = warp >> 2, w = warp & 3, lane = threadIdx.x & 31, q = lane & 3, g = lane >> 2;
    const int c = blockIdx.x;
    const uint32_t bars = sb + OFF_BAR, xb = sb + OFF_X + V * 2 * XBUF;
    {
        float ag[88], au[88];
        if (V == 0) {
            sts128(xb + (w >> 1) * XBUF + 168 * 128 + (threadIdx.x & 63) * 16, 0x3f803f80u, 0x3f803f80u, 0x3f803f80u, 0x3f803f80u);
            fence_async_smem();
            bar_sync(1);
        } else {
            if (c < 128) layer_norm(sb, w, lane, P.x); else mbar_arrive(bars + 8 * B_LN);
            mbar_wait(bars + 8 * B_GO, 0);
        }
        define_acc(ag); define_acc(au);
        #pragma unroll 1
        for (int st = 0; st < 8; st++) {
            if (st + LAG * V == HOLD0 || st + LAG * V == HOLD1) mbar_wait(bars + 8 * (B_K + (st + LAG * V == HOLD1)), 0);
            mbar_wait(bars + 8 * (B_FULLW + (st & 3)), st >> 2);
            mbar_wait(bars + 8 * (B_FULLX + 2 * V + (st & 1)), (st >> 1) & 1);
            STAMP(40 + 8 * V + st);
            const uint64_t dG = mkdesc(sb + OFF_W + (st & 3) * 16384, 0, 1024, 1);
            const uint64_t dX = mkdesc(xb + (st & 1) * XBUF, 16, 1024, 1);
            WG_FENCE();
            #pragma unroll
            for (int k = 0; k < 4; k++) {
                wg_g1(ag, dG + k * 128, dX + k * 2, k ? 1 : st);
                wg_g1(au, dG + 512 + k * 128, dX + k * 2, k ? 1 : st);
            }
            WG_COMMIT();
            WG_WAIT(1);
            if (lane == 0 && st > 0) {
                mbar_arrive(bars + 8 * (B_EMPTYW + ((st - 1) & 3)));
                mbar_arrive(bars + 8 * (B_EMPTYX + 2 * V + ((st - 1) & 1)));
                if (warp < 4 && st == LAG) mbar_arrive(bars + 8 * B_GO);
            }
        }
        WG_WAIT(0);
        fence_acc(ag); fence_acc(au);
        if (lane == 0) { mbar_arrive(bars + 8 * (B_EMPTYW + 3)); mbar_arrive(bars + 8 * (B_EMPTYX + 2 * V + 1)); }
        STAMP(8 * V + 1);
        float cg0 = ag[84], cg1 = ag[86], cu0 = au[84], cu1 = au[86];
        const uint32_t ca = sb + OFF_CSUM + (8 * w + g) * 16;
        if (V == 0) { sts128(ca, FU(cg0), FU(cg1), FU(cu0), FU(cu1)); mbar_arrive(bars + 8 * B_CS); }
        else { mbar_wait(bars + 8 * B_CS, 0); const uint4 t = lds128(ca); cg0 = UF(t.x); cg1 = UF(t.y); cu0 = UF(t.z); cu1 = UF(t.w); }
        mbar_wait(bars + 8 * B_STATS, 0);
        mbar_wait(bars + 8 * (B_EMPTYX + 2 * V), 1);
        STAMP(13 + V);
        const uint32_t hs = xb + (2 * w + ((lane >> 3) & 1)) * (2688 + 128 * V) + (lane >> 4) * 128 + (lane & 7) * 16;
        const uint32_t sa = sb + OFF_ST + (168 * V + 2 * q) * 8;
        uint4 sq[22];
        #pragma unroll
        for (int j = 0; j < 3; j++) sq[j] = lds128(sa + j * 64);
        #pragma unroll
        for (int j = 0; j < 22; j += 2) {
            uint32_t o[4];
            #pragma unroll
            for (int jj = 0; jj < 2; jj++) {
                const uint4 sv = sq[j + jj];
                float hv[4];
                #pragma unroll
                for (int i = 0; i < 4; i++) {
                    const float m = UF((i & 1) ? sv.z : sv.x);
                    const float gh = fmaf(-m, (i & 2) ? cg1 : cg0, ag[4 * (j + jj) + i]) * UF((i & 1) ? sv.w : sv.y);
                    const float p = gh * fmaf(-m, (i & 2) ? cu1 : cu0, au[4 * (j + jj) + i]);
                    hv[i] = fmaf(p, tanh_fast(gh), p);
                }
                o[2 * jj] = pack2(hv[0], hv[1]); o[2 * jj + 1] = pack2(hv[2], hv[3]);
            }
            #pragma unroll
            for (int k = (j ? 3 + 3 * j / 2 : 3); k < 6 + 3 * j / 2 && k < 22; k++) sq[k] = lds128(sa + k * 64);
            uint32_t ad = hs + j * 128;
            if (j == 20 && V == 0 && lane >= 16) ad = xb + 21504 + (lane & 7) * 16;
            stsm4(ad, o[0], o[1], o[2], o[3]);
        }
        if (c >= 128) { fence_async_smem(); mbar_arrive(bars + 8 * (B_EPI + V)); }
        STAMP(8 * V + 2);
    }
    if (c >= 128) return;
    {
        uint32_t r0[8], r1[8];
        #pragma unroll
        for (int i = 0; i < 8; i++) asm volatile("" : "=r"(r1[i]));
        #pragma unroll 1
        for (int e = 0; e < 2; e++) {
            #pragma unroll
            for (int i = 0; i < 8; i++) r0[i] = r1[i];
            mbar_wait(bars + 8 * (B_CONV + 2 * V + e), 0);
            conv_channel(sb + OFF_CONV + (2 * V + e) * CH_STRIDE, w, lane, r1, e ? 0 : bars + 8 * (B_EPI + V), 2 * V + e);
            if (e == 0) STAMP(8 * V + 3);
        }
        const int gam = g >> 2, qq = gam ? ((q + 3) & 3) : q;
        const uint32_t sp = sb + OFF_CONV + V * OFF_SST + ((63 - 4 * gam - qq) * 16 + 4 * (w ^ (3 - qq)) + (g & 3)) * 8;
        bar_sync(3 + V);
        #pragma unroll
        for (int a2 = 0; a2 < 8; a2++) sts64(sp - a2 * 1024, r0[a2], r1[a2]);
        fence_async_smem();
        mbar_arrive(bars + 8 * (B_SIG + V));
        STAMP(8 * V + 4);
    }
    if (V == 1) return;
    {
        const int tau = c >> 2, dg = c & 3;
        const uint32_t row = 8 * (w & 1) + 32 * (w >> 1);
        float acc[64];
        define_acc(acc);
        const float rr0 = __ldcg(&P.st[64 * tau + row + g].y), rr1 = __ldcg(&P.st[64 * tau + row + g + 16].y);
        mbar_wait(bars + 8 * B_FULLD, 0);
        STAMP(5);
        uint64_t dB = mkdesc(sb + wd_slot(0), 8192, 1024, 1), dA = mkdesc(sb + h_slot(0), 1024, 128, 0);
        #pragma unroll 1
        for (int st = 0; st < 21; st++) {
            WG_FENCE();
            wg_tt128(acc, dA, dB, st);
            wg_tt128(acc, dA + 128, dB + 128, 1);
            wg_tt128(acc, dA + 256, dB + 256, 1);
            wg_tt128(acc, dA + 384, dB + 384, 1);
            WG_COMMIT();
            const int sd = (st + 1) & 7;
            const uint32_t nb = bars + 8 * (B_FULLD + sd), np = ((st + 1) >> 3) & 1;
            uint32_t ro = st == 15 ? 8 * B_CH0 : 8 * (B_EMPTYD + ((st - 1) & 7)), m = lane == 0 && st > 0, ok;
            dB = mkdesc(sb + wd_slot(sd), 8192, 1024, 1); dA = mkdesc(sb + h_slot(sd), 1024, 128, 0);
            asm volatile("{.reg .pred p; mbarrier.test_wait.parity.shared::cta.b64 p, [%5], %6; vote.sync.all.pred p, p, -1; selp.u32 %0, 1, 0, p;}"
                : "=r"(ok), "+l"(dA), "+l"(dB), "+r"(ro), "+r"(m) : "r"(nb), "r"(np) : "memory");
            WG_WAIT(1);
            asm volatile("{.reg .pred p; setp.ne.u32 p, %1, 0; @p mbarrier.arrive.shared::cta.b64 _, [%0];}" :: "r"(bars + ro), "r"(m) : "memory");
            if (!ok) mbar_wait(nb, np);
            if (w == 0) STAMP2(20 + st);
        }
        WG_FENCE();
        wg_tt128(acc, dA, dB, 1);
        wg_tt128(acc, dA + 128, dB + 128, 1);
        WG_COMMIT();
        mbar_wait(bars + 8 * B_XO, 0);
        const uint32_t xo = sb + OFF_CONV + (row + (lane & 7) + 16 * ((lane >> 3) & 1)) * 128;
        const uint32_t so = sb + wd_slot(6) + (w >> 1) * 8192 + q * 256 + (g & 1) * 8;
        const uint32_t sx = (4 * (w & 1) + (g >> 1)) ^ (2 * q) ^ (2 * ((2 * tau + (w >> 1)) & 3));
        uint32_t xr[8][4];
        uint2 sv[16];
        #pragma unroll
        for (int j = 0; j < 16; j += 2) {
            ldsm4(xr[j >> 1], xo + (j >> 3) * 8192 + ((((j & 7) + (lane >> 4)) ^ (lane & 7)) << 4));
            sv[j] = lds64(so + j * 512 + (sx << 4));
            sv[j + 1] = lds64(so + j * 512 + 128 + ((sx ^ 1) << 4));
        }
        WG_WAIT(0);
        fence_acc(acc);
        STAMP(6);
        #pragma unroll
        for (int j = 0; j < 16; j += 2) {
            #pragma unroll
            for (int i = 0; i < 4; i++) {
                const int jj = j + (i >> 1), hh = i & 1;
                const float f0 = acc[4 * jj + 2 * hh] * (hh ? rr1 : rr0), f1 = acc[4 * jj + 2 * hh + 1] * (hh ? rr1 : rr0);
                const uint32_t G = pack2(fmaf(f0, tanh_fast(f0), f0), fmaf(f1, tanh_fast(f1), f1));
                const uint32_t s2 = __byte_perm(sv[jj].x, sv[jj].y, hh ? 0x7632 : 0x5410);
                asm("fma.rn.bf16x2 %0, %1, %2, %0;" : "+r"(xr[j >> 1][i]) : "r"(s2), "r"(G));
            }
            stsm4(xo + (j >> 3) * 8192 + ((((j & 7) + (lane >> 4)) ^ (lane & 7)) << 4), xr[j >> 1][0], xr[j >> 1][1], xr[j >> 1][2], xr[j >> 1][3]);
        }
        fence_async_smem();
        bar_sync(1);
        if (w == 0 && elect_one()) {
            #pragma unroll
            for (int i = 0; i < 2; i++)
                asm volatile("cp.async.bulk.tensor.2d.global.shared::cta.bulk_group [%0, {%2, %3}], [%1];"
                    :: "l"(&M.out), "r"(sb + OFF_CONV + i * 8192), "r"(dg * 128 + 64 * i), "r"(tau * 64) : "memory");
            asm volatile("cp.async.bulk.commit_group; cp.async.bulk.wait_group.read 0;" ::: "memory");
        }
        STAMP(7); GSTAMP(23);
    }
}

__device__ __forceinline__ float2 cexp_p(float re2, float im, float p) {
    float sn, cs;
    const float mag = ex2(re2 * p), th = im * p;
    asm("sin.approx.ftz.f32 %0, %1;" : "=f"(sn) : "f"(th));
    asm("cos.approx.ftz.f32 %0, %1;" : "=f"(cs) : "f"(th));
    return make_float2(mag * cs, mag * sn);
}
__device__ __forceinline__ unsigned short ldu16(const void* p) { unsigned short v; asm volatile("ld.global.nc.u16 %0, [%1];" : "=h"(v) : "l"(p)); return v; }
__device__ __forceinline__ float2 cmul(float2 a, float2 b) { return make_float2(fmaf(a.x, b.x, -a.y * b.y), fmaf(a.x, b.y, a.y * b.x)); }
__device__ __forceinline__ float2 csqr(float2 a) { const float t = a.x * a.y; return make_float2(fmaf(a.x, a.x, -a.y * a.y), t + t); }
__device__ __forceinline__ void mma16816(float (&d)[4], const uint32_t (&a)[4], uint32_t b0, uint32_t b1) {
    asm volatile("mma.sync.aligned.m16n8k16.row.col.f32.bf16.bf16.f32 {%0,%1,%2,%3}, {%4,%5,%6,%7}, {%8,%9}, {%0,%1,%2,%3};"
        : "+f"(d[0]), "+f"(d[1]), "+f"(d[2]), "+f"(d[3]) : "r"(a[0]), "r"(a[1]), "r"(a[2]), "r"(a[3]), "r"(b0), "r"(b1));
}

__device__ __forceinline__ void aux_role(uint32_t sb, int w, const Params& P) {
    const int lane = threadIdx.x & 31, q = lane & 3, g = lane >> 2;
    const int c = blockIdx.x;
    const uint32_t bars = sb + OFF_BAR;
    if (c >= 128) {
        if (lane == 0) { mbar_arrive(bars + 8 * B_K); mbar_arrive(bars + 8 * (B_K + 1)); }
        return;
    }
    {
        const uint32_t cb = sb + OFF_CONV + w * CH_STRIDE;
        const uint32_t sF = cb + CH_A3;
        const int d = 4 * c + w;
        const int po = d * 128 + lane;
        unsigned short la = ldu16(P.logA + po), ai = ldu16(P.Aim + po), cr = ldu16(P.Cr + po), ci = ldu16(P.Ci + po);
        const float ldt = __bfloat162float(P.logdt[d]), dsk = __bfloat162float(P.Dskip[d]);
        float dacc[2][3][4];
        #pragma unroll
        for (int i = 0; i < 24; i++) (&dacc[0][0][0])[i] = 0.f;
        const float dt = bf_round(ex2(ldt * 1.4426950408889634f));
        #pragma unroll 1
        for (int ck = 0; ck < 4; ck++) {
            const uint32_t fa = cb + lane * 4 + (ck & 1) * 8064;
            const float re2 = bf_round(ex2(bf_lo((uint32_t)la) * 1.4426950408889634f)) * dt * -1.4426950408889634f, im = bf_lo((uint32_t)ai) * dt;
            const float2 C = make_float2(bf_lo((uint32_t)cr) * (dt + dt), bf_lo((uint32_t)ci) * -(dt + dt));
            {
                const int pn = po + 32 * min(ck + 1, 3);
                la = ldu16(P.logA + pn); ai = ldu16(P.Aim + pn); cr = ldu16(P.Cr + pn); ci = ldu16(P.Ci + pn);
            }
            const float2 z8 = cexp_p(re2, im, 8.f), y1 = cexp_p(re2, -im, 1.f);
            float2 b0 = make_float2(1.f, 0.f), b1 = cexp_p(re2, im, 64.f), b2 = csqr(b1), b3 = cmul(b2, b1), l0 = C;
            const uint32_t fm = cb + (ck & 1) * 8064 + (lane >> 3) * 144 + (lane & 7) * 16;
#define PK(v) pack2((v).x, (v).y)
            #pragma unroll RUNROLL
            for (uint32_t ro = 0; ro < 8 * 144; ro += 144) {
                stsm4(fm + (lane >> 3) * 7 * 144 + ro, PK(b0), PK(b1), PK(b2), PK(b3));
                stsf(fa + 32 * 144 + ro, UF(PK(l0)));
                b0 = cmul(b0, z8); b1 = cmul(b1, z8); b2 = cmul(b2, z8); b3 = cmul(b3, z8); l0 = cmul(l0, y1);
            }
            if (ck < 2) STAMP(56 + 3 * ck);
            const float2 y256 = cexp_p(re2, -im, 256.f), y2 = csqr(y1), y4 = csqr(y2), y8 = make_float2(z8.x, -z8.y);
            const float2 t0 = cmul(C, y256), t1 = cmul(t0, y256), t2 = cmul(t1, y256), t3_ = cmul(t2, y256);
            const float2 u1 = cmul(t0, y2), u2 = cmul(u1, y2), u3 = cmul(u2, y2);
            stsm4(fm + 40 * 144, PK(t0), PK(u1), PK(u2), PK(u3));
            stsm4(fm + 44 * 144, PK(t1), PK(cmul(t1, y4)), PK(t2), PK(cmul(t2, y4)));
            const float2 v0 = cmul(t3_, y8), v1 = cmul(v0, y256), v2 = cmul(v1, y256), v3 = cmul(v2, y256);
            stsm4(fm + 48 * 144, PK(v0), PK(v1), PK(v2), PK(v3));
            stsf(fa + 52 * 144, UF(PK(t3_)));
#undef PK
            if (ck < 2) STAMP(57 + 3 * ck);
            if (ck & 1) {
                uint32_t ln_; asm volatile("mov.u32 %0, %%laneid;" : "=r"(ln_));
                const uint32_t lda = cb + (ln_ & 15) * 144 + (ln_ & 16);
                const uint32_t ldb = cb + (32 + (ln_ & 7)) * 144 + (ln_ >> 3) * 16;
                __syncwarp();
                #pragma unroll
                for (int k2 = 0; k2 < 4; k2++) {
                    const uint32_t ko = (k2 >> 1) * 8064 + (k2 & 1) * 64;
                    uint32_t b[3][4];
                    #pragma unroll
                    for (int t3 = 0; t3 < 3; t3++) ldsm4(b[t3], ldb + t3 * 8 * 144 + ko);
                    #pragma unroll
                    for (int k = 0; k < 2; k++)
                        #pragma unroll
                        for (int mu = 0; mu < 2; mu++) {
                            uint32_t a[4];
                            ldsm4(a, lda + mu * 16 * 144 + ko + k * 32);
                            #pragma unroll
                            for (int t3 = 0; t3 < 3; t3++) mma16816(dacc[mu][t3], a, b[t3][2 * k], b[t3][2 * k + 1]);
                        }
                }
                __syncwarp();
                if (lane == 0) mbar_arrive(bars + 8 * (B_K + (ck >> 1)));
                STAMP(58 + 3 * (ck >> 1));
            }
        }
        STAMP(18);
        const uint32_t sG = cb + CH_G;
        if (lane == 0) dacc[0][0][0] += dsk;
        if (lane < 18) sts128(lane < 8 ? cb + CH_U + 2048 + (lane & 4) * (UPLANE / 4) + (lane & 3) * 16 : sG + 128 + (lane & 1) * 208 + ((lane - 8) >> 1) * 16, 0, 0, 0, 0);
        {
            const uint32_t f0 = sF + (8 * g + 2 * q) * 4, f1 = sF + ((q < 2) ? 256 + 4 * g + 2 * q : 256 + 2 * g + 64 * q) * 4, st1 = (q < 2) ? 128 : 64;
            const uint32_t ga = sG + ((g & 1) ? 0 : 208) + (63 - (g >> 1) - 32 * q) * 2;
            #pragma unroll
            for (int i = 0; i < 4; i++) {
                const int mu = i >> 1, hh = i & 1;
                sts64(f0 + i * 256, FU(dacc[mu][0][2 * hh]), FU(dacc[mu][0][2 * hh + 1]));
                sts64(f1 + i * st1, FU(dacc[mu][1][2 * hh]), FU(dacc[mu][1][2 * hh + 1]));
                const uint32_t pk = pack2(dacc[mu][2][2 * hh], dacc[mu][2][2 * hh + 1]);
                if (q < 2) { sts16(ga - 8 * i, pk & 0xffff); sts16(ga - 8 * i - 32, pk >> 16); }
            }
            if (lane == 2) stsf(sF + 2048, dacc[0][2][0]);
        }
    }
    bar_sync(2);
    STAMP(19);
    const int u = min(lane, 30) - 15, r2 = (u + ((u >> 1) & 1)) >> 1, r4 = (u + 1 + ((u >> 2) & 1)) >> 2, xt = 1024 + 16 * w + u;
    const uint32_t o0 = CH_A3 + 4 * (w == 0 ? u : w == 1 ? 256 + r2 : 256 + 64 * w + r4), ost = w == 0 ? 64 : w == 1 ? 32 : 16;
    const uint32_t oa0 = u >= 0 || w == 3 ? o0 : CH_A3 + 4 * (w == 1 ? 256 + u : w == 2 ? 384 + r2 : 0);
    const uint32_t ot = CH_A3 + 4 * min(512, 256 + ((xt + 1 + ((xt >> 2) & 1)) >> 2));
    const int kap = (lane >> 4) * 8 + ((lane >> 1) & 7), gam = lane & 1, hh = w >> 1, wp = w & 1;
    const uint32_t oa = CH_U + wp * UPLANE + (127 - 4 * kap - 2 * gam - hh) * 16;
    const uint32_t ob = CH_U + (wp ^ 1) * UPLANE + (128 - wp - 4 * kap - 2 * gam - hh) * 16;
    const uint32_t od = CH_A3 + (4 * wp + hh) * 512 + (kap >> 3) * 256 + (kap & 7) * 16 + gam * 8;
    #pragma unroll 1
    for (int k = 0; k < 4; k++) {
        const int ch = 2 * (k & 1) + (k >> 1);
        const uint32_t cb = sb + OFF_CONV + ch * CH_STRIDE;
        {
            float kv[17];
            kv[0] = ldsf(cb + oa0); kv[16] = ldsf(cb + ot);
            #pragma unroll
            for (int s = 1; s < 16; s++) kv[s] = ldsf(cb + o0 + s * ost);
            const int tid = threadIdx.x & 127;
            const uint32_t ga = cb + CH_G + (tid >= 24) * 16 + min(tid, 47) * 8;
            const uint2 x0 = lds64(ga), x1 = lds64(ga + 8);
            if (u < 0 && w == 0) kv[0] = 0.f;
            if (xt > 1028) kv[16] = 0.f;
            uint32_t o[17];
            #pragma unroll
            for (int s = 0; s < 17; s++) o[s] = pack2(kv[s], __shfl_up_sync(0xffffffffu, kv[s], 1));
            if (lane > 0 && lane < 31) {
                const uint32_t ta = cb + CH_T + (lane - 1) * 280;
                #pragma unroll
                for (int s2 = 0; s2 < 8; s2++) sts64(ta + 64 * w + s2 * 8, o[2 * s2], o[2 * s2 + 1]);
                stsf(ta + 256 + 4 * w, UF(o[16]));
            }
            if (tid < 48) sts128(cb + CH_B3 + tid * 16, x0.x, x0.y, x1.x, x1.y);
        }
        mbar_wait(bars + 8 * B_U, 0);
        float p[24];
        const uint2 r0 = lds64(cb + ob + 24), r3 = lds64(cb + oa);
        uint32_t r[8];
        *(uint4*)&r[0] = lds128(cb + oa + 16); *(uint4*)&r[4] = lds128(cb + ob);
        p[0] = 0.f;
        p[1] = bf_lo(r0.x); p[2] = p[1] + bf_hi(r0.x); p[3] = p[2] + bf_lo(r0.y); p[4] = p[3] + bf_hi(r0.y);
        #pragma unroll
        for (int i = 0; i < 8; i++) { p[5 + 2 * i] = p[4 + 2 * i] + bf_lo(r[i]); p[6 + 2 * i] = p[5 + 2 * i] + bf_hi(r[i]); }
        p[21] = p[20] + bf_lo(r3.x); p[22] = p[21] + bf_hi(r3.x); p[23] = p[22] + bf_lo(r3.y);
        bar_sync(2);
        #pragma unroll
        for (int i = 0; i < 8; i += 4) {
            sts64(cb + od + i * 256, pack2(p[i + 9] - p[i], p[i + 10] - p[i + 1]), pack2(p[i + 11] - p[i + 2], p[i + 12] - p[i + 3]));
            sts64(cb + od + i * 256 + 128, pack2(p[i + 16] - p[i + 9], p[i + 17] - p[i + 10]), pack2(p[i + 18] - p[i + 11], p[i + 19] - p[i + 12]));
        }
        fence_async_smem();
        mbar_arrive(bars + 8 * (B_CONV + ch));
        if (k == 0) STAMP(17);
    }
    STAMP(21);
}

__global__ void __launch_bounds__(512, 1)
fused_kernel(const __grid_constant__ Params P, const __grid_constant__ Maps M) {
    extern __shared__ __align__(1024) uint8_t smem_raw[];
    const uint32_t sb = smem_u32(smem_raw);
    const uint32_t bars = sb + OFF_BAR;
    const int warp = __shfl_sync(0xffffffffu, threadIdx.x >> 5, 0);
    const int c = blockIdx.x, tg = c / 22, fb = c - 22 * tg;
    if (elect_one()) {
        if (warp == 0) { STAMP(24); GSTAMP(22); }
        asm volatile("" :: "l"(((const uint64_t*)&P)[warp < 12 ? warp : 0]));
        if (warp < 12) asm volatile("prefetch.tensormap [%0];" :: "l"(&M.x[0] + warp) : "memory");
        #pragma unroll
        for (int k = 0; k < 4; k++) {
            const int i = 16 * k + ((warp + 4) & 15);
            const uint32_t cnt = i >= B_CONV ? 128 : ((0xf0ull >> i) & 1) ? 8 : ((0xff0000ull >> i) & 1) ? 2 : ((0x3e00ff00f000ull >> i) & 1) ? 4 : 1;
            asm volatile("mbarrier.init.shared::cta.b64 [%0], %1;" :: "r"(bars + 8 * i), "r"(cnt) : "memory");
        }
        asm volatile("fence.mbarrier_init.release.cluster; fence.proxy.async.shared::cta;" ::: "memory");
        if (warp == 13 || warp == 5 || warp == 6) { const uint32_t t0 = clock(); while ((uint32_t)clock() - t0 < DLY1) ; }
        if (warp == 12 || warp == 13) {
            const uint32_t s = warp - 12;
            mbar_expect(bars + 8 * (B_FULLW + s), 16384);
            tma2d(sb + OFF_W + s * 16384, &M.wg, 64 * fb, 64 * s, bars + 8 * (B_FULLW + s));
            tma2d(sb + OFF_W + s * 16384 + 8192, &M.wu, 64 * fb, 64 * s, bars + 8 * (B_FULLW + s));
            STAMP(31);
        } else if (warp >= 4 && warp < 7) {
            const uint32_t s = warp - 4, V = s >> 1;
            mbar_expect(bars + 8 * (B_FULLX + s), (168 + 8 * V) * 128);
            tma2d(sb + OFF_X + s * XBUF, &M.x[V], 64 * (s & 1), TOKG * tg + 168 * V, bars + 8 * (B_FULLX + s));
        }
        if (sb & 1023) __trap();
    }
    if (warp >= 8 && warp < 12 && c < 128 && (threadIdx.x & 31) < 8)
        asm volatile("prefetch.global.L2 [%0];" :: "l"((&P.logA)[(threadIdx.x >> 1) & 3] + (4 * c + warp - 8) * 128 + (threadIdx.x & 1) * 64));
    __syncthreads();
    if (warp < 8) {
        asm volatile("setmaxnreg.inc.sync.aligned.u32 208;");
        consumer(sb, warp, P, M);
    } else if (warp < 12) {
        asm volatile("setmaxnreg.dec.sync.aligned.u32 72;");
        STAMP(32);
        aux_role(sb, warp - 8, P);
    } else {
        asm volatile("setmaxnreg.dec.sync.aligned.u32 24;");
        const int tau = c >> 2, dg = c & 3;
        if (elect_one()) {
            if (warp < 15) {
                if (warp == 12) {
                    #pragma unroll 1
                    for (int st = 2; st < 8; st++) {
                        const uint32_t s = st & 3, fb_ = bars + 8 * (B_FULLW + s);
                        if (st == 2) mbar_wait(bars + 8 * B_FULLW, 0);
                        mbar_wait(bars + 8 * (B_EMPTYW + s), (st >> 2) ^ 1);
                        mbar_expect(fb_, 16384);
                        tma2d(sb + OFF_W + s * 16384, &M.wg, 64 * fb, 64 * st, fb_);
                        tma2d(sb + OFF_W + s * 16384 + 8192, &M.wu, 64 * fb, 64 * st, fb_);
                    }
                } else {
                    const int V = warp - 13;
                    #pragma unroll 1
                    for (int st = 2 - V; st < 8; st++) {
                        const uint32_t s = 2 * V + (st & 1);
                        if (s == 3 && st == 1) mbar_wait(bars + 8 * B_LNS, 0);
                        mbar_wait(bars + 8 * (B_EMPTYX + s), ((st >> 1) & 1) ^ 1);
                        mbar_expect(bars + 8 * (B_FULLX + s), (168 + 8 * V) * 128);
                        tma2d(sb + OFF_X + s * XBUF, &M.x[V], 64 * st, TOKG * tg + 168 * V, bars + 8 * (B_FULLX + s));
                    }
                }
                if (c < 128 && warp < 14) {
                    if (warp == 13) {
                        mbar_wait(bars + 8 * (B_STG + 1), 0);
                        #pragma unroll 1
                        for (int o = 8 * tau; o < 8 * tau + 8; o += 7) flag_wait(P.flags, F_H + 2 * (o / 43) + ((o % 43) >= 21), 22);
                        mbar_arrive(bars + 8 * B_HF);
                        STAMP(25);
                    }
                    #pragma unroll 1
                    for (int st = 0; st < 22; st += (st < 7 || (st == 7 && warp == 12)) ? 1 : 2) {
                        const int sd = st & 7;
                        const uint32_t fb_ = bars + 8 * (B_FULLD + sd);
                        if (st >= 8) mbar_wait(bars + 8 * (B_EMPTYD + sd), ((st >> 3) & 1) ^ 1);
                        else if (warp == 12 || st >= 6) mbar_wait(bars + 8 * (uint32_t)((0x373623070d060504ull >> (8 * st)) & 0xff), st < 5);
                        if (st >= 10 && st < 21) STAMP2(31 + st);
                        if (st >= 8 || warp == 13) {
                            mbar_expect(fb_, 8192);
                            asm volatile("cp.async.bulk.tensor.5d.shared::cluster.global.mbarrier::complete_tx::bytes [%0], [%1, {%3, %3, %3, %4, %5}], [%2];"
                                :: "r"(sb + h_slot(sd)), "l"(&M.hld), "r"(fb_), "r"(0), "r"(2 * tau), "r"(8 * st) : "memory");
                        }
                        if (st >= 8 || warp == 12) {
                            const uint32_t da = sb + wd_slot(sd);
                            mbar_expect(fb_, 16384);
                            tma2d(da, &M.wd, 128 * dg, 64 * st, fb_);
                            tma2d(da + 8192, &M.wd, 128 * dg + 64, 64 * st, fb_);
                        }
                    }
                } else if (c < 128) {
                    mbar_wait(bars + 8 * B_SST, 0);
                    flag_wait(P.flags, F_S + dg, 64);
                    STAMP(26);
                    mbar_wait(bars + 8 * B_CH0, 0);
                    mbar_expect(bars + 8 * B_XO, 32768);
                    tma2d(sb + OFF_CONV, &M.xo, 128 * dg, 64 * tau, bars + 8 * B_XO);
                    tma2d(sb + OFF_CONV + 8192, &M.xo, 128 * dg + 64, 64 * tau, bars + 8 * B_XO);
                    asm volatile("cp.async.bulk.tensor.5d.shared::cluster.global.mbarrier::complete_tx::bytes [%0], [%1, {%3, %3, %3, %4, %5}], [%2];"
                        :: "r"(sb + wd_slot(6)), "l"(&M.sld), "r"(bars + 8 * B_XO), "r"(0), "r"(8 * dg), "r"(2 * tau) : "memory");
                    mbar_wait(bars + 8 * B_HF, 0);
                    exit_count(P.flags);
                }
            } else {
                mbar_wait(bars + 8 * B_LN, 0);
                STAMP2(0);
                if (c < 128) {
                    #pragma unroll 1
                    for (int i = 0; i < 2; i++)
                        asm volatile("cp.async.bulk.tensor.2d.global.shared::cta.bulk_group [%0, {%2, %3}], [%1];"
                            :: "l"(&M.xt), "r"(sb + OFF_LN + i * 8192), "r"((c & 1) * 1024 + (126 - (c & ~1)) * 8), "r"(256 * i) : "memory");
                    #pragma unroll 1
                    for (int i = 0; i < 2; i++) bulk_store(P.st + 16 * (c & ~1) + 8 * (c & 1) + 16 - 16 * i, sb + OFF_CSUM + 64 * i, 64);
                    asm volatile("cp.async.bulk.prefetch.L2.global [%0], %1;" :: "l"(P.Wd + c * (FF * DM / 128)), "r"(FF * DM / 64) : "memory");
                }
                asm volatile("cp.async.bulk.commit_group; cp.async.bulk.wait_group.read 0;" ::: "memory");
                mbar_arrive(bars + 8 * B_LNS);
                STAMP2(1);
                flag_signal(P.flags, F_A);
                STAMP2(2);
                flag_wait(P.flags, F_A, NCTA);
                STAMP(20);
                mbar_expect(bars + 8 * B_STATS, TOKG * 8);
                bulk_load(sb + OFF_ST, P.st + TOKG * tg, TOKG * 8, bars + 8 * B_STATS);
                if (c < 128) {
                    mbar_wait(bars + 8 * (B_K + 1), 0);
                    fence_async_smem();
                    mbar_expect(bars + 8 * B_U, 8 * 2048);
                    #pragma unroll 1
                    for (int i = 0; i < 8; i++)
                        bulk_load(sb + OFF_CONV + (i >> 1) * CH_STRIDE + CH_U + (i & 1) * UPLANE, P.xnT + 4 * c * 256 + i * 128, 2048, bars + 8 * B_U);
                } else exit_count(P.flags);
                #pragma unroll 1
                for (int V = 0; V < 2; V++) {
                    mbar_wait(bars + 8 * (B_EPI + V), 0);
                    STAMP2(3 + 2 * V);
                    asm volatile("cp.async.bulk.tensor.3d.global.shared::cta.bulk_group [%0, {%2, %3, %4}], [%1];"
                        :: "l"(&M.hst[V]), "r"(sb + OFF_X + V * 2 * XBUF), "r"(0), "r"(43 * tg + 21 * V), "r"(8 * fb) : "memory");
                    flag_signal(P.flags, F_H + 2 * tg + V);
                    mbar_arrive(bars + 8 * (B_STG + V));
                    STAMP2(4 + 2 * V);
                }
                if (c < 128) {
                    #pragma unroll 1
                    for (int V = 0; V < 2; V++) {
                        mbar_wait(bars + 8 * (B_SIG + V), 0);
                        STAMP2(7 + 2 * V);
                        bulk_store(P.S + (2 * c + V) * 1024, sb + OFF_CONV + V * OFF_SST, 8192);
                        flag_signal(P.flags, F_S + (c >> 5));
                        STAMP2(8 + 2 * V);
                    }
                    mbar_arrive(bars + 8 * B_SST);
                }
            }
        }
    }
    asm volatile("nanosleep.u32 0;");
}

typedef CUresult (*EncodeFn)(CUtensorMap*, CUtensorMapDataType, cuuint32_t, void*, const cuuint64_t*, const cuuint64_t*, const cuuint32_t*,
                             const cuuint32_t*, CUtensorMapInterleave, CUtensorMapSwizzle, CUtensorMapL2promotion, CUtensorMapFloatOOBfill);

void make_map(EncodeFn enc, CUtensorMap* m, const void* ptr, int rank, const cuuint64_t* dims, const cuuint64_t* strides, const cuuint32_t* box, bool swz, bool wide = false) {
    const cuuint32_t es[5] = {1, 1, 1, 1, 1};
    enc(m, CU_TENSOR_MAP_DATA_TYPE_BFLOAT16, rank, (void*)ptr, dims, strides, box, es, CU_TENSOR_MAP_INTERLEAVE_NONE,
        swz ? CU_TENSOR_MAP_SWIZZLE_128B : CU_TENSOR_MAP_SWIZZLE_NONE, wide ? CU_TENSOR_MAP_L2_PROMOTION_L2_256B : CU_TENSOR_MAP_L2_PROMOTION_L2_128B, CU_TENSOR_MAP_FLOAT_OOB_FILL_NONE);
}
void make_map2(EncodeFn enc, CUtensorMap* m, const void* ptr, cuuint64_t inner, cuuint64_t outer, cuuint32_t rows) {
    const cuuint64_t dims[2] = {inner, outer}, strides[1] = {inner * 2};
    const cuuint32_t box[2] = {64, rows};
    make_map(enc, m, ptr, 2, dims, strides, box, true, rows > 64);
}

}

extern "C" void kernel_launch(void* const* d_in, const int* in_sizes, int n_in, void* d_out, int out_size) {
    (void)in_sizes; (void)n_in; (void)out_size;
    static EncodeFn enc = nullptr;
    static void *hptr, *p_xnT, *p_st, *p_S, *p_flags;
    if (!enc) {
        cudaDriverEntryPointQueryResult qr;
        cudaGetDriverEntryPoint("cuTensorMapEncodeTiled", (void**)&enc, cudaEnableDefault, &qr);
        cudaFuncSetAttribute(fused_kernel, cudaFuncAttributeMaxDynamicSharedMemorySize, SMEM_BYTES);
        cudaGetSymbolAddress(&hptr, g_H); cudaGetSymbolAddress(&p_xnT, g_xnT); cudaGetSymbolAddress(&p_st, g_st);
        cudaGetSymbolAddress(&p_S, g_S); cudaGetSymbolAddress(&p_flags, g_flags);
    }
    Params P;
    P.x = (const __nv_bfloat16*)d_in[0]; P.logA = (const __nv_bfloat16*)d_in[1]; P.Aim = (const __nv_bfloat16*)d_in[2];
    P.Cr = (const __nv_bfloat16*)d_in[3]; P.Ci = (const __nv_bfloat16*)d_in[4]; P.logdt = (const __nv_bfloat16*)d_in[5];
    P.Dskip = (const __nv_bfloat16*)d_in[6];
    P.Wd = (const __nv_bfloat16*)d_in[10]; P.xnT = (uint4*)p_xnT; P.st = (float2*)p_st; P.S = (uint2*)p_S; P.flags = (unsigned*)p_flags;
    Maps M;
    make_map2(enc, &M.x[0], d_in[0], DM, SEQ, 168); make_map2(enc, &M.x[1], d_in[0], DM, SEQ, 176);
    make_map2(enc, &M.xo, d_in[0], DM, SEQ, 64);    make_map2(enc, &M.out, d_out, DM, SEQ, 64);
    make_map2(enc, &M.wg, d_in[8], FF, DM, 64);     make_map2(enc, &M.wu, d_in[9], FF, DM, 64);
    make_map2(enc, &M.wd, d_in[10], DM, FF, 64);
    for (int v = 0; v < 2; v++) {
        const cuuint64_t dims[3] = {64, 256, 172}, strides[2] = {128, 32768};
        const cuuint32_t box[3] = {64, (cuuint32_t)(21 + v), 8};
        make_map(enc, &M.hst[v], hptr, 3, dims, strides, box, false);
    }
    {
        const cuuint64_t dims[2] = {2048, 512}, strides[1] = {4096};
        const cuuint32_t box[2] = {16, 256};
        make_map(enc, &M.xt, p_xnT, 2, dims, strides, box, false);
    }
    {
        const cuuint64_t dims[5] = {64, 2, 4, 32, 64}, strides[4] = {4 * 8192, 8192, 8 * 8192, 128};
        const cuuint32_t box[5] = {64, 2, 4, 8, 2};
        make_map(enc, &M.sld, p_S, 5, dims, strides, box, true);
    }
    {
        const cuuint64_t dims[5] = {64, 2, 2, 64, 172}, strides[4] = {256, 128, 512, 32768};
        const cuuint32_t box[5] = {64, 2, 2, 2, 8};
        make_map(enc, &M.hld, hptr, 5, dims, strides, box, false);
    }
    fused_kernel<<<NCTA, 512, SMEM_BYTES>>>(P, M);
}
```

```cpp
#include <cuda_runtime.h>
#include <cuda_bf16.h>
#include <cuda.h>
#include <stdint.h>

#define PROF 0

namespace {

constexpr int SEQ = 2048, DM = 512, FF = 1376;
constexpr int NCTA = 132;
#define HOLD0 4
#define HOLD1 7
#define LAG 2
#define DLY1 300
#define DLY2 300
constexpr int RUNROLL = 8;
constexpr int TOKG = 344;

constexpr uint32_t OFF_W = 0;
constexpr uint32_t XBUF = 22528;
constexpr uint32_t OFF_X = 65536;
constexpr uint32_t OFF_CONV = 155648;
constexpr uint32_t CH_STRIDE = 17536;
constexpr uint32_t CH_T = 0;
constexpr uint32_t CH_A3 = 8448;
constexpr uint32_t CH_B3 = 12544;
constexpr uint32_t CH_U = 13312;
constexpr uint32_t CH_G = CH_A3 + 2064;
constexpr uint32_t UPLANE = 2112;
constexpr uint32_t OFF_LN = OFF_X + 3 * XBUF;
constexpr uint32_t OFF_SST = 60416;
constexpr uint32_t OFF_ST = 225792;
constexpr uint32_t OFF_CSUM = 228544;
constexpr uint32_t OFF_BAR = 229056;
constexpr uint32_t SMEM_BYTES = 229568;

enum {
    B_FULLW = 0, B_EMPTYW = 4, B_FULLX = 8, B_EMPTYX = 12, B_FULLD = 16, B_EMPTYD = 24,
    B_U = 32, B_XO = 33, B_S = 34, B_STG = 35, B_HF = 37, B_STATS = 38, B_LNS = 39, B_SST = 40,
    B_LNX = 41, B_GO = 42, B_CH0 = 43, B_K = 44,
    B_CONV = 46, B_LN = 50, B_CS = 51, B_EPI = 52, B_SIG = 54,
    B_COUNT = 56
};
enum { F_A = 0, F_H = 1, F_S = 13, F_EXIT = 17, F_COUNT = 18 };

__device__ uint4 g_xnT[DM * 256];
__device__ float2 g_st[6 * TOKG];
__device__ uint4 g_H[172 * 256 * 8];
__device__ uint2 g_S[256 * 1024];
__device__ unsigned g_flags[F_COUNT * 32];
#define STAMP(i) do {} while (0)
#define GSTAMP(i) do {} while (0)
#define STAMP2(i) do {} while (0)

__device__ __forceinline__ uint32_t smem_u32(const void* p) { return (uint32_t)__cvta_generic_to_shared(p); }
__device__ __forceinline__ void mbar_expect(uint32_t bar, uint32_t bytes) { asm volatile("mbarrier.arrive.expect_tx.shared::cta.b64 _, [%0], %1;" :: "r"(bar), "r"(bytes) : "memory"); }
__device__ __forceinline__ void mbar_arrive(uint32_t bar) { asm volatile("mbarrier.arrive.shared::cta.b64 _, [%0];" :: "r"(bar) : "memory"); }
__device__ __forceinline__ void mbar_wait(uint32_t bar, uint32_t parity) {
    asm volatile("{.reg .pred p; .reg .u32 n; mov.u32 n, 0x20000;\n"
                 "LW: mbarrier.try_wait.parity.shared::cta.b64 p, [%0], %1;\n"
                 "sub.u32 n, n, 1; setp.eq.or.u32 p, n, 0, p; @!p bra LW;}" :: "r"(bar), "r"(parity) : "memory");
}
__device__ __forceinline__ bool elect_one() { uint32_t p; asm volatile("{.reg .pred P; elect.sync _|P, 0xffffffff; selp.u32 %0, 1, 0, P;}" : "=r"(p)); return p; }
__device__ __forceinline__ void tma2d(uint32_t dst, const CUtensorMap* m, int c0, int c1, uint32_t bar) {
    asm volatile("cp.async.bulk.tensor.2d.shared::cluster.global.mbarrier::complete_tx::bytes [%0], [%1, {%3, %4}], [%2];"
        :: "r"(dst), "l"(m), "r"(bar), "r"(c0), "r"(c1) : "memory");
}
__device__ __forceinline__ void bulk_load(uint32_t dst, const void* src, uint32_t bytes, uint32_t bar) {
    asm volatile("cp.async.bulk.shared::cluster.global.mbarrier::complete_tx::bytes [%0], [%1], %2, [%3];" :: "r"(dst), "l"(src), "r"(bytes), "r"(bar) : "memory");
}
__device__ __forceinline__ void bulk_store(void* dst, uint32_t src, uint32_t bytes) {
    asm volatile("cp.async.bulk.global.shared::cta.bulk_group [%0], [%1], %2;" :: "l"(dst), "r"(src), "r"(bytes) : "memory");
}
__device__ __forceinline__ void fence_async_smem() { asm volatile("fence.proxy.async.shared::cta;" ::: "memory"); }
__device__ __forceinline__ void flag_wait(unsigned* g_flags, int f, unsigned target) {
    asm volatile("{.reg .pred p; .reg .u32 n, v; mov.u32 n, 0x40000;\n"
                 "LF: ld.acquire.gpu.global.u32 v, [%0]; setp.ge.u32 p, v, %1; @p bra LD;\n"
                 "sub.u32 n, n, 1; setp.ne.u32 p, n, 0; @p bra LF; trap;\nLD: }"
                 :: "l"(g_flags + f * 32), "r"(target) : "memory");
}
__device__ __forceinline__ void flag_signal(unsigned* g_flags, int f) {
    asm volatile("cp.async.bulk.commit_group; cp.async.bulk.wait_group 0; red.relaxed.gpu.global.add.u32 [%0], 1;" :: "l"(g_flags + f * 32) : "memory");
}
__device__ __forceinline__ void exit_count(unsigned* g_flags) {
    if (atomicAdd(g_flags + F_EXIT * 32, 1u) == NCTA - 1) {
        #pragma unroll 1
        for (int i = 0; i < F_COUNT; i++) g_flags[i * 32] = 0;
    }
}
__device__ __forceinline__ void bar_sync(int id) { asm volatile("bar.sync %0, 128;" :: "r"(id) : "memory"); }
__device__ __forceinline__ uint64_t mkdesc(uint32_t addr, uint32_t lbo, uint32_t sbo, uint32_t swz) {
    return (uint64_t)((addr >> 4) | ((lbo >> 4) << 16)) | ((uint64_t)((sbo >> 4) | (swz << 30)) << 32);
}
#define WG_FENCE() asm volatile("wgmma.fence.sync.aligned;" ::: "memory")
#define WG_COMMIT() asm volatile("wgmma.commit_group.sync.aligned;" ::: "memory")
#define WG_WAIT(n) asm volatile("wgmma.wait_group.sync.aligned " #n ";" ::: "memory")
template <int N> __device__ __forceinline__ void fence_acc(float (&d)[N]) {
    #pragma unroll
    for (int i = 0; i < N; i++) asm volatile("" : "+f"(d[i]) :: "memory");
}
template <int N> __device__ __forceinline__ void define_acc(float (&d)[N]) {
    #pragma unroll
    for (int i = 0; i < N; i++) asm volatile("" : "=f"(d[i]));
}
__device__ __forceinline__ uint32_t pack2(float lo, float hi) { uint32_t r; asm("cvt.rn.bf16x2.f32 %0, %1, %2;" : "=r"(r) : "f"(hi), "f"(lo)); return r; }
__device__ __forceinline__ float bf_lo(uint32_t v) { return __uint_as_float(v << 16); }
__device__ __forceinline__ float bf_hi(uint32_t v) { return __uint_as_float(v & 0xffff0000u); }
__device__ __forceinline__ float bf_round(float v) { return bf_hi(pack2(0.f, v)); }
__device__ __forceinline__ float tanh_fast(float v) { float r; asm("tanh.approx.f32 %0, %1;" : "=f"(r) : "f"(v)); return r; }
__device__ __forceinline__ float ex2(float v) { float r; asm("ex2.approx.ftz.f32 %0, %1;" : "=f"(r) : "f"(v)); return r; }
__device__ __forceinline__ uint4 lds128(uint32_t a) { uint4 v; asm volatile("ld.shared.v4.b32 {%0,%1,%2,%3}, [%4];" : "=r"(v.x), "=r"(v.y), "=r"(v.z), "=r"(v.w) : "r"(a)); return v; }
__device__ __forceinline__ uint2 lds64(uint32_t a) { uint2 v; asm volatile("ld.shared.v2.b32 {%0,%1}, [%2];" : "=r"(v.x), "=r"(v.y) : "r"(a)); return v; }
__device__ __forceinline__ float ldsf(uint32_t a) { float v; asm volatile("ld.shared.f32 %0, [%1];" : "=f"(v) : "r"(a)); return v; }
__device__ __forceinline__ void sts128(uint32_t a, uint32_t x, uint32_t y, uint32_t z, uint32_t w) { asm volatile("st.shared.v4.b32 [%0], {%1,%2,%3,%4};" :: "r"(a), "r"(x), "r"(y), "r"(z), "r"(w) : "memory"); }
__device__ __forceinline__ void sts64(uint32_t a, uint32_t x, uint32_t y) { asm volatile("st.shared.v2.b32 [%0], {%1,%2};" :: "r"(a), "r"(x), "r"(y) : "memory"); }
__device__ __forceinline__ void stsf(uint32_t a, float x) { asm volatile("st.shared.f32 [%0], %1;" :: "r"(a), "f"(x) : "memory"); }
__device__ __forceinline__ void sts16(uint32_t a, uint32_t x) { asm volatile("st.shared.b16 [%0], %1;" :: "r"(a), "h"((unsigned short)x) : "memory"); }
__device__ __forceinline__ void stsm4(uint32_t a, uint32_t r0, uint32_t r1, uint32_t r2, uint32_t r3) {
    asm volatile("stmatrix.sync.aligned.m8n8.x4.shared.b16 [%0], {%1,%2,%3,%4};" :: "r"(a), "r"(r0), "r"(r1), "r"(r2), "r"(r3) : "memory");
}
__device__ __forceinline__ void ldsm4(uint32_t (&r)[4], uint32_t a) {
    asm volatile("ldmatrix.sync.aligned.m8n8.x4.shared.b16 {%0,%1,%2,%3}, [%4];" : "=r"(r[0]), "=r"(r[1]), "=r"(r[2]), "=r"(r[3]) : "r"(a) : "memory");
}
#define FU(x) __float_as_uint(x)
#define UF(x) __uint_as_float(x)
__device__ __forceinline__ uint32_t wd_slot(int s) { return (uint32_t)((0xbba8403056201000ull >> (8 * s)) & 0xff) << 10; }
__device__ __forceinline__ uint32_t h_slot(int s) { return (uint32_t)((0xcba0908880787068ull >> (8 * s)) & 0xff) << 10; }

template<int N> __device__ __forceinline__ void wg_rs(float (&d)[64], uint32_t a0, uint32_t a1, uint32_t a2, uint32_t a3, uint64_t db);
template<> __device__ __forceinline__ void wg_rs<128>(float (&d)[64], uint32_t a0, uint32_t a1, uint32_t a2, uint32_t a3, uint64_t db) {
  asm volatile("{.reg .pred p; setp.ne.b32 p, 1, 0; wgmma.mma_async.sync.aligned.m64n128k16.f32.bf16.bf16 {%0,%1,%2,%3,%4,%5,%6,%7,%8,%9,%10,%11,%12,%13,%14,%15,%16,%17,%18,%19,%20,%21,%22,%23,%24,%25,%26,%27,%28,%29,%30,%31,%32,%33,%34,%35,%36,%37,%38,%39,%40,%41,%42,%43,%44,%45,%46,%47,%48,%49,%50,%51,%52,%53,%54,%55,%56,%57,%58,%59,%60,%61,%62,%63}, {%64,%65,%66,%67}, %68, p, 1, 1, 0;}"
    : "+f"(d[0]),"+f"(d[1]),"+f"(d[2]),"+f"(d[3]),"+f"(d[4]),"+f"(d[5]),"+f"(d[6]),"+f"(d[7]),"+f"(d[8]),"+f"(d[9]),"+f"(d[10]),"+f"(d[11]),"+f"(d[12]),"+f"(d[13]),"+f"(d[14]),"+f"(d[15]),"+f"(d[16]),"+f"(d[17]),"+f"(d[18]),"+f"(d[19]),"+f"(d[20]),"+f"(d[21]),"+f"(d[22]),"+f"(d[23]),"+f"(d[24]),"+f"(d[25]),"+f"(d[26]),"+f"(d[27]),"+f"(d[28]),"+f"(d[29]),"+f"(d[30]),"+f"(d[31]),"+f"(d[32]),"+f"(d[33]),"+f"(d[34]),"+f"(d[35]),"+f"(d[36]),"+f"(d[37]),"+f"(d[38]),"+f"(d[39]),"+f"(d[40]),"+f"(d[41]),"+f"(d[42]),"+f"(d[43]),"+f"(d[44]),"+f"(d[45]),"+f"(d[46]),"+f"(d[47]),"+f"(d[48]),"+f"(d[49]),"+f"(d[50]),"+f"(d[51]),"+f"(d[52]),"+f"(d[53]),"+f"(d[54]),"+f"(d[55]),"+f"(d[56]),"+f"(d[57]),"+f"(d[58]),"+f"(d[59]),"+f"(d[60]),"+f"(d[61]),"+f"(d[62]),"+f"(d[63]) : "r"(a0), "r"(a1), "r"(a2), "r"(a3), "l"(db));
}
template<> __device__ __forceinline__ void wg_rs<120>(float (&d)[64], uint32_t a0, uint32_t a1, uint32_t a2, uint32_t a3, uint64_t db) {
  asm volatile("{.reg .pred p; setp.ne.b32 p, 1, 0; wgmma.mma_async.sync.aligned.m64n120k16.f32.bf16.bf16 {%0,%1,%2,%3,%4,%5,%6,%7,%8,%9,%10,%11,%12,%13,%14,%15,%16,%17,%18,%19,%20,%21,%22,%23,%24,%25,%26,%27,%28,%29,%30,%31,%32,%33,%34,%35,%36,%37,%38,%39,%40,%41,%42,%43,%44,%45,%46,%47,%48,%49,%50,%51,%52,%53,%54,%55,%56,%57,%58,%59}, {%60,%61,%62,%63}, %64, p, 1, 1, 0;}"
    : "+f"(d[0]),"+f"(d[1]),"+f"(d[2]),"+f"(d[3]),"+f"(d[4]),"+f"(d[5]),"+f"(d[6]),"+f"(d[7]),"+f"(d[8]),"+f"(d[9]),"+f"(d[10]),"+f"(d[11]),"+f"(d[12]),"+f"(d[13]),"+f"(d[14]),"+f"(d[15]),"+f"(d[16]),"+f"(d[17]),"+f"(d[18]),"+f"(d[19]),"+f"(d[20]),"+f"(d[21]),"+f"(d[22]),"+f"(d[23]),"+f"(d[24]),"+f"(d[25]),"+f"(d[26]),"+f"(d[27]),"+f"(d[28]),"+f"(d[29]),"+f"(d[30]),"+f"(d[31]),"+f"(d[32]),"+f"(d[33]),"+f"(d[34]),"+f"(d[35]),"+f"(d[36]),"+f"(d[37]),"+f"(d[38]),"+f"(d[39]),"+f"(d[40]),"+f"(d[41]),"+f"(d[42]),"+f"(d[43]),"+f"(d[44]),"+f"(d[45]),"+f"(d[46]),"+f"(d[47]),"+f"(d[48]),"+f"(d[49]),"+f"(d[50]),"+f"(d[51]),"+f"(d[52]),"+f"(d[53]),"+f"(d[54]),"+f"(d[55]),"+f"(d[56]),"+f"(d[57]),"+f"(d[58]),"+f"(d[59]) : "r"(a0), "r"(a1), "r"(a2), "r"(a3), "l"(db));
}
template<> __device__ __forceinline__ void wg_rs<112>(float (&d)[64], uint32_t a0, uint32_t a1, uint32_t a2, uint32_t a3, uint64_t db) {
  asm volatile("{.reg .pred p; setp.ne.b32 p, 1, 0; wgmma.mma_async.sync.aligned.m64n112k16.f32.bf16.bf16 {%0,%1,%2,%3,%4,%5,%6,%7,%8,%9,%10,%11,%12,%13,%14,%15,%16,%17,%18,%19,%20,%21,%22,%23,%24,%25,%26,%27,%28,%29,%30,%31,%32,%33,%34,%35,%36,%37,%38,%39,%40,%41,%42,%43,%44,%45,%46,%47,%48,%49,%50,%51,%52,%53,%54,%55}, {%56,%57,%58,%59}, %60, p, 1, 1, 0;}"
    : "+f"(d[0]),"+f"(d[1]),"+f"(d[2]),"+f"(d[3]),"+f"(d[4]),"+f"(d[5]),"+f"(d[6]),"+f"(d[7]),"+f"(d[8]),"+f"(d[9]),"+f"(d[10]),"+f"(d[11]),"+f"(d[12]),"+f"(d[13]),"+f"(d[14]),"+f"(d[15]),"+f"(d[16]),"+f"(d[17]),"+f"(d[18]),"+f"(d[19]),"+f"(d[20]),"+f"(d[21]),"+f"(d[22]),"+f"(d[23]),"+f"(d[24]),"+f"(d[25]),"+f"(d[26]),"+f"(d[27]),"+f"(d[28]),"+f"(d[29]),"+f"(d[30]),"+f"(d[31]),"+f"(d[32]),"+f"(d[33]),"+f"(d[34]),"+f"(d[35]),"+f"(d[36]),"+f"(d[37]),"+f"(d[38]),"+f"(d[39]),"+f"(d[40]),"+f"(d[41]),"+f"(d[42]),"+f"(d[43]),"+f"(d[44]),"+f"(d[45]),"+f"(d[46]),"+f"(d[47]),"+f"(d[48]),"+f"(d[49]),"+f"(d[50]),"+f"(d[51]),"+f"(d[52]),"+f"(d[53]),"+f"(d[54]),"+f"(d[55]) : "r"(a0), "r"(a1), "r"(a2), "r"(a3), "l"(db));
}
template<> __device__ __forceinline__ void wg_rs<104>(float (&d)[64], uint32_t a0, uint32_t a1, uint32_t a2, uint32_t a3, uint64_t db) {
  asm volatile("{.reg .pred p; setp.ne.b32 p, 1, 0; wgmma.mma_async.sync.aligned.m64n104k16.f32.bf16.bf16 {%0,%1,%2,%3,%4,%5,%6,%7,%8,%9,%10,%11,%12,%13,%14,%15,%16,%17,%18,%19,%20,%21,%22,%23,%24,%25,%26,%27,%28,%29,%30,%31,%32,%33,%34,%35,%36,%37,%38,%39,%40,%41,%42,%43,%44,%45,%46,%47,%48,%49,%50,%51}, {%52,%53,%54,%55}, %56, p, 1, 1, 0;}"
    : "+f"(d[0]),"+f"(d[1]),"+f"(d[2]),"+f"(d[3]),"+f"(d[4]),"+f"(d[5]),"+f"(d[6]),"+f"(d[7]),"+f"(d[8]),"+f"(d[9]),"+f"(d[10]),"+f"(d[11]),"+f"(d[12]),"+f"(d[13]),"+f"(d[14]),"+f"(d[15]),"+f"(d[16]),"+f"(d[17]),"+f"(d[18]),"+f"(d[19]),"+f"(d[20]),"+f"(d[21]),"+f"(d[22]),"+f"(d[23]),"+f"(d[24]),"+f"(d[25]),"+f"(d[26]),"+f"(d[27]),"+f"(d[28]),"+f"(d[29]),"+f"(d[30]),"+f"(d[31]),"+f"(d[32]),"+f"(d[33]),"+f"(d[34]),"+f"(d[35]),"+f"(d[36]),"+f"(d[37]),"+f"(d[38]),"+f"(d[39]),"+f"(d[40]),"+f"(d[41]),"+f"(d[42]),"+f"(d[43]),"+f"(d[44]),"+f"(d[45]),"+f"(d[46]),"+f"(d[47]),"+f"(d[48]),"+f"(d[49]),"+f"(d[50]),"+f"(d[51]) : "r"(a0), "r"(a1), "r"(a2), "r"(a3), "l"(db));
}
template<> __device__ __forceinline__ void wg_rs<96>(float (&d)[64], uint32_t a0, uint32_t a1, uint32_t a2, uint32_t a3, uint64_t db) {
  asm volatile("{.reg .pred p; setp.ne.b32 p, 1, 0; wgmma.mma_async.sync.aligned.m64n96k16.f32.bf16.bf16 {%0,%1,%2,%3,%4,%5,%6,%7,%8,%9,%10,%11,%12,%13,%14,%15,%16,%17,%18,%19,%20,%21,%22,%23,%24,%25,%26,%27,%28,%29,%30,%31,%32,%33,%34,%35,%36,%37,%38,%39,%40,%41,%42,%43,%44,%45,%46,%47}, {%48,%49,%50,%51}, %52, p, 1, 1, 0;}"
    : "+f"(d[0]),"+f"(d[1]),"+f"(d[2]),"+f"(d[3]),"+f"(d[4]),"+f"(d[5]),"+f"(d[6]),"+f"(d[7]),"+f"(d[8]),"+f"(d[9]),"+f"(d[10]),"+f"(d[11]),"+f"(d[12]),"+f"(d[13]),"+f"(d[14]),"+f"(d[15]),"+f"(d[16]),"+f"(d[17]),"+f"(d[18]),"+f"(d[19]),"+f"(d[20]),"+f"(d[21]),"+f"(d[22]),"+f"(d[23]),"+f"(d[24]),"+f"(d[25]),"+f"(d[26]),"+f"(d[27]),"+f"(d[28]),"+f"(d[29]),"+f"(d[30]),"+f"(d[31]),"+f"(d[32]),"+f"(d[33]),"+f"(d[34]),"+f"(d[35]),"+f"(d[36]),"+f"(d[37]),"+f"(d[38]),"+f"(d[39]),"+f"(d[40]),"+f"(d[41]),"+f"(d[42]),"+f"(d[43]),"+f"(d[44]),"+f"(d[45]),"+f"(d[46]),"+f"(d[47]) : "r"(a0), "r"(a1), "r"(a2), "r"(a3), "l"(db));
}
template<> __device__ __forceinline__ void wg_rs<88>(float (&d)[64], uint32_t a0, uint32_t a1, uint32_t a2, uint32_t a3, uint64_t db) {
  asm volatile("{.reg .pred p; setp.ne.b32 p, 1, 0; wgmma.mma_async.sync.aligned.m64n88k16.f32.bf16.bf16 {%0,%1,%2,%3,%4,%5,%6,%7,%8,%9,%10,%11,%12,%13,%14,%15,%16,%17,%18,%19,%20,%21,%22,%23,%24,%25,%26,%27,%28,%29,%30,%31,%32,%33,%34,%35,%36,%37,%38,%39,%40,%41,%42,%43}, {%44,%45,%46,%47}, %48, p, 1, 1, 0;}"
    : "+f"(d[0]),"+f"(d[1]),"+f"(d[2]),"+f"(d[3]),"+f"(d[4]),"+f"(d[5]),"+f"(d[6]),"+f"(d[7]),"+f"(d[8]),"+f"(d[9]),"+f"(d[10]),"+f"(d[11]),"+f"(d[12]),"+f"(d[13]),"+f"(d[14]),"+f"(d[15]),"+f"(d[16]),"+f"(d[17]),"+f"(d[18]),"+f"(d[19]),"+f"(d[20]),"+f"(d[21]),"+f"(d[22]),"+f"(d[23]),"+f"(d[24]),"+f"(d[25]),"+f"(d[26]),"+f"(d[27]),"+f"(d[28]),"+f"(d[29]),"+f"(d[30]),"+f"(d[31]),"+f"(d[32]),"+f"(d[33]),"+f"(d[34]),"+f"(d[35]),"+f"(d[36]),"+f"(d[37]),"+f"(d[38]),"+f"(d[39]),"+f"(d[40]),"+f"(d[41]),"+f"(d[42]),"+f"(d[43]) : "r"(a0), "r"(a1), "r"(a2), "r"(a3), "l"(db));
}
template<> __device__ __forceinline__ void wg_rs<80>(float (&d)[64], uint32_t a0, uint32_t a1, uint32_t a2, uint32_t a3, uint64_t db) {
  asm volatile("{.reg .pred p; setp.ne.b32 p, 1, 0; wgmma.mma_async.sync.aligned.m64n80k16.f32.bf16.bf16 {%0,%1,%2,%3,%4,%5,%6,%7,%8,%9,%10,%11,%12,%13,%14,%15,%16,%17,%18,%19,%20,%21,%22,%23,%24,%25,%26,%27,%28,%29,%30,%31,%32,%33,%34,%35,%36,%37,%38,%39}, {%40,%41,%42,%43}, %44, p, 1, 1, 0;}"
    : "+f"(d[0]),"+f"(d[1]),"+f"(d[2]),"+f"(d[3]),"+f"(d[4]),"+f"(d[5]),"+f"(d[6]),"+f"(d[7]),"+f"(d[8]),"+f"(d[9]),"+f"(d[10]),"+f"(d[11]),"+f"(d[12]),"+f"(d[13]),"+f"(d[14]),"+f"(d[15]),"+f"(d[16]),"+f"(d[17]),"+f"(d[18]),"+f"(d[19]),"+f"(d[20]),"+f"(d[21]),"+f"(d[22]),"+f"(d[23]),"+f"(d[24]),"+f"(d[25]),"+f"(d[26]),"+f"(d[27]),"+f"(d[28]),"+f"(d[29]),"+f"(d[30]),"+f"(d[31]),"+f"(d[32]),"+f"(d[33]),"+f"(d[34]),"+f"(d[35]),"+f"(d[36]),"+f"(d[37]),"+f"(d[38]),"+f"(d[39]) : "r"(a0), "r"(a1), "r"(a2), "r"(a3), "l"(db));
}
template<> __device__ __forceinline__ void wg_rs<72>(float (&d)[64], uint32_t a0, uint32_t a1, uint32_t a2, uint32_t a3, uint64_t db) {
  asm volatile("{.reg .pred p; setp.ne.b32 p, 1, 0; wgmma.mma_async.sync.aligned.m64n72k16.f32.bf16.bf16 {%0,%1,%2,%3,%4,%5,%6,%7,%8,%9,%10,%11,%12,%13,%14,%15,%16,%17,%18,%19,%20,%21,%22,%23,%24,%25,%26,%27,%28,%29,%30,%31,%32,%33,%34,%35}, {%36,%37,%38,%39}, %40, p, 1, 1, 0;}"
    : "+f"(d[0]),"+f"(d[1]),"+f"(d[2]),"+f"(d[3]),"+f"(d[4]),"+f"(d[5]),"+f"(d[6]),"+f"(d[7]),"+f"(d[8]),"+f"(d[9]),"+f"(d[10]),"+f"(d[11]),"+f"(d[12]),"+f"(d[13]),"+f"(d[14]),"+f"(d[15]),"+f"(d[16]),"+f"(d[17]),"+f"(d[18]),"+f"(d[19]),"+f"(d[20]),"+f"(d[21]),"+f"(d[22]),"+f"(d[23]),"+f"(d[24]),"+f"(d[25]),"+f"(d[26]),"+f"(d[27]),"+f"(d[28]),"+f"(d[29]),"+f"(d[30]),"+f"(d[31]),"+f"(d[32]),"+f"(d[33]),"+f"(d[34]),"+f"(d[35]) : "r"(a0), "r"(a1), "r"(a2), "r"(a3), "l"(db));
}
template<> __device__ __forceinline__ void wg_rs<64>(float (&d)[64], uint32_t a0, uint32_t a1, uint32_t a2, uint32_t a3, uint64_t db) {
  asm volatile("{.reg .pred p; setp.ne.b32 p, 1, 0; wgmma.mma_async.sync.aligned.m64n64k16.f32.bf16.bf16 {%0,%1,%2,%3,%4,%5,%6,%7,%8,%9,%10,%11,%12,%13,%14,%15,%16,%17,%18,%19,%20,%21,%22,%23,%24,%25,%26,%27,%28,%29,%30,%31}, {%32,%33,%34,%35}, %36, p, 1, 1, 0;}"
    : "+f"(d[0]),"+f"(d[1]),"+f"(d[2]),"+f"(d[3]),"+f"(d[4]),"+f"(d[5]),"+f"(d[6]),"+f"(d[7]),"+f"(d[8]),"+f"(d[9]),"+f"(d[10]),"+f"(d[11]),"+f"(d[12]),"+f"(d[13]),"+f"(d[14]),"+f"(d[15]),"+f"(d[16]),"+f"(d[17]),"+f"(d[18]),"+f"(d[19]),"+f"(d[20]),"+f"(d[21]),"+f"(d[22]),"+f"(d[23]),"+f"(d[24]),"+f"(d[25]),"+f"(d[26]),"+f"(d[27]),"+f"(d[28]),"+f"(d[29]),"+f"(d[30]),"+f"(d[31]) : "r"(a0), "r"(a1), "r"(a2), "r"(a3), "l"(db));
}
__device__ __forceinline__ void wg_rs_first(float (&d)[64], uint32_t a0, uint32_t a1, uint32_t a2, uint32_t a3, uint64_t db) {
  asm volatile("{.reg .pred p; setp.ne.b32 p, 0, 0; wgmma.mma_async.sync.aligned.m64n128k16.f32.bf16.bf16 {%0,%1,%2,%3,%4,%5,%6,%7,%8,%9,%10,%11,%12,%13,%14,%15,%16,%17,%18,%19,%20,%21,%22,%23,%24,%25,%26,%27,%28,%29,%30,%31,%32,%33,%34,%35,%36,%37,%38,%39,%40,%41,%42,%43,%44,%45,%46,%47,%48,%49,%50,%51,%52,%53,%54,%55,%56,%57,%58,%59,%60,%61,%62,%63}, {%64,%65,%66,%67}, %68, p, 1, 1, 0;}"
    : "=f"(d[0]),"=f"(d[1]),"=f"(d[2]),"=f"(d[3]),"=f"(d[4]),"=f"(d[5]),"=f"(d[6]),"=f"(d[7]),"=f"(d[8]),"=f"(d[9]),"=f"(d[10]),"=f"(d[11]),"=f"(d[12]),"=f"(d[13]),"=f"(d[14]),"=f"(d[15]),"=f"(d[16]),"=f"(d[17]),"=f"(d[18]),"=f"(d[19]),"=f"(d[20]),"=f"(d[21]),"=f"(d[22]),"=f"(d[23]),"=f"(d[24]),"=f"(d[25]),"=f"(d[26]),"=f"(d[27]),"=f"(d[28]),"=f"(d[29]),"=f"(d[30]),"=f"(d[31]),"=f"(d[32]),"=f"(d[33]),"=f"(d[34]),"=f"(d[35]),"=f"(d[36]),"=f"(d[37]),"=f"(d[38]),"=f"(d[39]),"=f"(d[40]),"=f"(d[41]),"=f"(d[42]),"=f"(d[43]),"=f"(d[44]),"=f"(d[45]),"=f"(d[46]),"=f"(d[47]),"=f"(d[48]),"=f"(d[49]),"=f"(d[50]),"=f"(d[51]),"=f"(d[52]),"=f"(d[53]),"=f"(d[54]),"=f"(d[55]),"=f"(d[56]),"=f"(d[57]),"=f"(d[58]),"=f"(d[59]),"=f"(d[60]),"=f"(d[61]),"=f"(d[62]),"=f"(d[63]) : "r"(a0), "r"(a1), "r"(a2), "r"(a3), "l"(db));
}
__device__ __forceinline__ void wg_tt128(float (&d)[64], uint64_t da, uint64_t db, int sc) {
  asm volatile("{.reg .pred p; setp.ne.b32 p, %66, 0; wgmma.mma_async.sync.aligned.m64n128k16.f32.bf16.bf16 {%0,%1,%2,%3,%4,%5,%6,%7,%8,%9,%10,%11,%12,%13,%14,%15,%16,%17,%18,%19,%20,%21,%22,%23,%24,%25,%26,%27,%28,%29,%30,%31,%32,%33,%34,%35,%36,%37,%38,%39,%40,%41,%42,%43,%44,%45,%46,%47,%48,%49,%50,%51,%52,%53,%54,%55,%56,%57,%58,%59,%60,%61,%62,%63}, %64, %65, p, 1, 1, 1, 1;}"
    : "+f"(d[0]),"+f"(d[1]),"+f"(d[2]),"+f"(d[3]),"+f"(d[4]),"+f"(d[5]),"+f"(d[6]),"+f"(d[7]),"+f"(d[8]),"+f"(d[9]),"+f"(d[10]),"+f"(d[11]),"+f"(d[12]),"+f"(d[13]),"+f"(d[14]),"+f"(d[15]),"+f"(d[16]),"+f"(d[17]),"+f"(d[18]),"+f"(d[19]),"+f"(d[20]),"+f"(d[21]),"+f"(d[22]),"+f"(d[23]),"+f"(d[24]),"+f"(d[25]),"+f"(d[26]),"+f"(d[27]),"+f"(d[28]),"+f"(d[29]),"+f"(d[30]),"+f"(d[31]),"+f"(d[32]),"+f"(d[33]),"+f"(d[34]),"+f"(d[35]),"+f"(d[36]),"+f"(d[37]),"+f"(d[38]),"+f"(d[39]),"+f"(d[40]),"+f"(d[41]),"+f"(d[42]),"+f"(d[43]),"+f"(d[44]),"+f"(d[45]),"+f"(d[46]),"+f"(d[47]),"+f"(d[48]),"+f"(d[49]),"+f"(d[50]),"+f"(d[51]),"+f"(d[52]),"+f"(d[53]),"+f"(d[54]),"+f"(d[55]),"+f"(d[56]),"+f"(d[57]),"+f"(d[58]),"+f"(d[59]),"+f"(d[60]),"+f"(d[61]),"+f"(d[62]),"+f"(d[63]) : "l"(da), "l"(db), "r"(sc));
}
__device__ __forceinline__ void wg_tt64(float (&d)[64], uint64_t da, uint64_t db, int sc) {
  asm volatile("{.reg .pred p; setp.ne.b32 p, %34, 0; wgmma.mma_async.sync.aligned.m64n64k16.f32.bf16.bf16 {%0,%1,%2,%3,%4,%5,%6,%7,%8,%9,%10,%11,%12,%13,%14,%15,%16,%17,%18,%19,%20,%21,%22,%23,%24,%25,%26,%27,%28,%29,%30,%31}, %32, %33, p, 1, 1, 1, 1;}"
    : "+f"(d[0]),"+f"(d[1]),"+f"(d[2]),"+f"(d[3]),"+f"(d[4]),"+f"(d[5]),"+f"(d[6]),"+f"(d[7]),"+f"(d[8]),"+f"(d[9]),"+f"(d[10]),"+f"(d[11]),"+f"(d[12]),"+f"(d[13]),"+f"(d[14]),"+f"(d[15]),"+f"(d[16]),"+f"(d[17]),"+f"(d[18]),"+f"(d[19]),"+f"(d[20]),"+f"(d[21]),"+f"(d[22]),"+f"(d[23]),"+f"(d[24]),"+f"(d[25]),"+f"(d[26]),"+f"(d[27]),"+f"(d[28]),"+f"(d[29]),"+f"(d[30]),"+f"(d[31]) : "l"(da), "l"(db), "r"(sc));
}
__device__ __forceinline__ void wg_tt32(float (&d)[64], uint64_t da, uint64_t db, int sc) {
  asm volatile("{.reg .pred p; setp.ne.b32 p, %18, 0; wgmma.mma_async.sync.aligned.m64n32k16.f32.bf16.bf16 {%0,%1,%2,%3,%4,%5,%6,%7,%8,%9,%10,%11,%12,%13,%14,%15}, %16, %17, p, 1, 1, 1, 1;}"
    : "+f"(d[0]),"+f"(d[1]),"+f"(d[2]),"+f"(d[3]),"+f"(d[4]),"+f"(d[5]),"+f"(d[6]),"+f"(d[7]),"+f"(d[8]),"+f"(d[9]),"+f"(d[10]),"+f"(d[11]),"+f"(d[12]),"+f"(d[13]),"+f"(d[14]),"+f"(d[15]) : "l"(da), "l"(db), "r"(sc));
}
__device__ __forceinline__ void wg_g1(float (&d)[88], uint64_t da, uint64_t db, int sc) {
  asm volatile("{.reg .pred p; setp.ne.b32 p, %90, 0; wgmma.mma_async.sync.aligned.m64n176k16.f32.bf16.bf16 {%0,%1,%2,%3,%4,%5,%6,%7,%8,%9,%10,%11,%12,%13,%14,%15,%16,%17,%18,%19,%20,%21,%22,%23,%24,%25,%26,%27,%28,%29,%30,%31,%32,%33,%34,%35,%36,%37,%38,%39,%40,%41,%42,%43,%44,%45,%46,%47,%48,%49,%50,%51,%52,%53,%54,%55,%56,%57,%58,%59,%60,%61,%62,%63,%64,%65,%66,%67,%68,%69,%70,%71,%72,%73,%74,%75,%76,%77,%78,%79,%80,%81,%82,%83,%84,%85,%86,%87}, %88, %89, p, 1, 1, 1, 0;}"
    : "+f"(d[0]),"+f"(d[1]),"+f"(d[2]),"+f"(d[3]),"+f"(d[4]),"+f"(d[5]),"+f"(d[6]),"+f"(d[7]),"+f"(d[8]),"+f"(d[9]),"+f"(d[10]),"+f"(d[11]),"+f"(d[12]),"+f"(d[13]),"+f"(d[14]),"+f"(d[15]),"+f"(d[16]),"+f"(d[17]),"+f"(d[18]),"+f"(d[19]),"+f"(d[20]),"+f"(d[21]),"+f"(d[22]),"+f"(d[23]),"+f"(d[24]),"+f"(d[25]),"+f"(d[26]),"+f"(d[27]),"+f"(d[28]),"+f"(d[29]),"+f"(d[30]),"+f"(d[31]),"+f"(d[32]),"+f"(d[33]),"+f"(d[34]),"+f"(d[35]),"+f"(d[36]),"+f"(d[37]),"+f"(d[38]),"+f"(d[39]),"+f"(d[40]),"+f"(d[41]),"+f"(d[42]),"+f"(d[43]),"+f"(d[44]),"+f"(d[45]),"+f"(d[46]),"+f"(d[47]),"+f"(d[48]),"+f"(d[49]),"+f"(d[50]),"+f"(d[51]),"+f"(d[52]),"+f"(d[53]),"+f"(d[54]),"+f"(d[55]),"+f"(d[56]),"+f"(d[57]),"+f"(d[58]),"+f"(d[59]),"+f"(d[60]),"+f"(d[61]),"+f"(d[62]),"+f"(d[63]),"+f"(d[64]),"+f"(d[65]),"+f"(d[66]),"+f"(d[67]),"+f"(d[68]),"+f"(d[69]),"+f"(d[70]),"+f"(d[71]),"+f"(d[72]),"+f"(d[73]),"+f"(d[74]),"+f"(d[75]),"+f"(d[76]),"+f"(d[77]),"+f"(d[78]),"+f"(d[79]),"+f"(d[80]),"+f"(d[81]),"+f"(d[82]),"+f"(d[83]),"+f"(d[84]),"+f"(d[85]),"+f"(d[86]),"+f"(d[87]) : "l"(da), "l"(db), "r"(sc));
}

struct Params { const __nv_bfloat16 *x, *logA, *Aim, *Cr, *Ci, *logdt, *Dskip, *Wd; uint4* xnT; float2* st; uint2* S; unsigned* flags; };
struct Maps { CUtensorMap x[2], xo, out, wg, wu, wd, hst[2], hld, xt, sld; };

__device__ __forceinline__ void conv_channel(uint32_t cb, int w, int lane, uint32_t (&res)[8], uint32_t sig, int sidx) {
    const int q = lane & 3, g = lane >> 2, gam = g >> 2;
    float acc[64];
    uint2 a[17][2];
    const uint32_t t0 = cb + CH_T + (uint32_t)(14 + 4 * w + (g & 3) - 2 * q) * 280u + gam * 8;
#define LDA(s0, s1) _Pragma("unroll") for (int s = s0; s < s1; s++) { a[s][0] = lds64(t0 + s * 16); a[s][1] = lds64(t0 - 8 * 280 + s * 16); }
#define CT(N, s) wg_rs<N>(acc, a[s][0].x, a[s][0].y, a[s][1].x, a[s][1].y, dU + 4 * (s))
    const uint64_t dU = mkdesc(cb + CH_U, UPLANE, 128, 0);
    LDA(0, 17)
    if (sig) { fence_async_smem(); mbar_arrive(sig); }
    WG_FENCE();
    if (w == 0) STAMP2(52 + 3 * sidx);
    wg_rs_first(acc, a[0][0].x, a[0][0].y, a[0][1].x, a[0][1].y, dU);
    CT(128, 1); CT(120, 2); CT(120, 3); CT(112, 4); CT(112, 5); CT(104, 6); CT(104, 7); CT(96, 8);
    CT(96, 9); CT(88, 10); CT(88, 11); CT(80, 12); CT(80, 13); CT(72, 14); CT(72, 15); CT(64, 16);
#undef CT
#undef LDA
    wg_tt64(acc, mkdesc(cb + CH_A3, 128, 512, 0), mkdesc(cb + CH_B3, 384, 32, 0), 1);
    wg_tt32(acc, mkdesc(cb + CH_A3 + 256, 128, 512, 0), mkdesc(cb + CH_B3 + 128, 384, 32, 0), 1);
    WG_COMMIT();
    if (w == 0) STAMP2(53 + 3 * sidx);
    WG_WAIT(0);
    fence_acc(acc);
    if (w == 0) STAMP2(54 + 3 * sidx);
    const int src1 = (lane & ~3) | ((q + 1) & 3);
    float E[16][2];
    #pragma unroll
    for (int j = 0; j < 16; j++) {
        const float nxt = (j < 15) ? acc[4 * (j + 1) + 2] : 0.f;
        const float sup = (q == 0) ? nxt : acc[4 * j + 2];
        const float v = __shfl_sync(0xffffffffu, sup, src1);
        E[j][0] = acc[4 * j] + acc[4 * j + 3];
        E[j][1] = acc[4 * j + 1] + v;
    }
    const int src2 = gam ? ((lane & 12) | ((q + 3) & 3)) : (16 | (lane & 12) | ((q + 1) & 3));
    const bool c1 = gam && q != 0, c2 = gam && q == 0;
    #pragma unroll
    for (int a2 = 0; a2 < 8; a2++) {
        float y[2];
        #pragma unroll
        for (int e = 0; e < 2; e++) {
            const float sup = c1 ? E[2 * a2][e] : E[2 * a2 + 1][e];
            const float nxt = (a2 < 7) ? E[2 * a2 + 2][e] : 0.f;
            const float keep = c2 ? nxt : (c1 ? E[2 * a2 + 1][e] : E[2 * a2][e]);
            y[e] = keep + __shfl_sync(0xffffffffu, sup, src2);
        }
        res[a2] = pack2(y[1], y[0]);
    }
}

__device__ __forceinline__ void layer_norm(uint32_t sb, int w, int lane, const __nv_bfloat16* x) {
    const uint32_t bars = sb + OFF_BAR;
    const int c = blockIdx.x;
    {
        if (elect_one()) {
            { const uint32_t t0 = clock(); while ((uint32_t)clock() - t0 < DLY2) ; }
            mbar_expect(bars + 8 * B_LNX, 4096);
            #pragma unroll
            for (int i = 0; i < 4; i++)
                bulk_load(sb + OFF_LN + (w + 4 * i) * 1152 + ((w & 1) + 2 * i) * 16, x + (16 * (c & ~1) + 8 * (c & 1) + 16 + w + 4 * (i & 1) - 8 * (i & 2)) * DM, 1024, bars + 8 * B_LNX);
        }
        mbar_wait(bars + 8 * B_LNX, 0);
        STAMP(34);
        {
            const int r = w + 4 * (lane >> 3);
            const uint32_t r0 = sb + OFF_LN + r * 1152 + ((w & 1) + 2 * (lane >> 3)) * 16, ra = r0 + (lane & 7) * 16;
            const float pv = bf_lo(FU(ldsf(r0)));
            float s0 = 0.f, s1 = 0.f, a0 = 0.f, a1 = 0.f;
            uint4 nx = lds128(ra), ny = lds128(ra + 128);
            #pragma unroll 2
            for (int k = 128; k <= 1024; k += 128) {
                const uint32_t v[4] = {nx.x, nx.y, nx.z, nx.w};
                nx = ny; ny = lds128(ra + ((k + 128) & 1023));
                #pragma unroll
                for (int i = 0; i < 4; i++) { const float t0 = bf_lo(v[i]) - pv, t1 = bf_hi(v[i]) - pv; s0 += t0; s1 += t1; a0 = fmaf(t0, t0, a0); a1 = fmaf(t1, t1, a1); }
            }
            s0 += s1; a0 += a1;
            #pragma unroll
            for (int o = 4; o; o >>= 1) { s0 += __shfl_xor_sync(0xffffffffu, s0, o); a0 += __shfl_xor_sync(0xffffffffu, a0, o); }
            s0 *= 1.f / DM;
            const float m = pv + s0, var = fmaxf(fmaf(-s0, s0, a0 * (1.f / DM)), 0.f);
            float sd, ri;
            asm("sqrt.approx.ftz.f32 %0, %1;" : "=f"(sd) : "f"(bf_round(bf_round(var) + 1e-5f)));
            asm("rcp.approx.ftz.f32 %0, %1;" : "=f"(ri) : "f"(bf_round(sd)));
            const uint32_t m2 = pack2(m, m);
            if ((lane & 7) == 0) {
                sts64(sb + OFF_CSUM + r * 8, m2 & 0xffff0000u, FU(0.5f * ri));
            }
            #pragma unroll 2
            for (int k = 128; k <= 1024; k += 128) {
                uint32_t v[4] = {nx.x, nx.y, nx.z, nx.w};
                nx = ny; ny = lds128(ra + ((k + 128) & 1023));
                #pragma unroll
                for (int i = 0; i < 4; i++) {
                    uint32_t dv; asm("sub.rn.bf16x2 %0, %1, %2;" : "=r"(dv) : "r"(v[i]), "r"(m2));
                    v[i] = pack2(bf_lo(dv) * ri, bf_hi(dv) * ri);
                }
                sts128(ra + k - 128, v[0], v[1], v[2], v[3]);
            }
        }
        STAMP(62);
        bar_sync(4);
        {
            const uint32_t ad = sb + OFF_LN + (4 * ((lane & 7) >> 1) + (lane & 1) + 2 * ((lane >> 3) & 1)) * 1152 + (16 * w + (lane >> 4) + (lane & 7)) * 16;
            uint32_t r[8][4];
            #pragma unroll
            for (int i = 0; i < 8; i++)
                asm volatile("ldmatrix.sync.aligned.m8n8.x4.trans.shared.b16 {%0,%1,%2,%3}, [%4];" : "=r"(r[i][0]), "=r"(r[i][1]), "=r"(r[i][2]), "=r"(r[i][3]) : "r"(ad + 32 * i) : "memory");
            bar_sync(4);
            const uint32_t od = sb + OFF_LN + w * 4096 + lane * 8;
            #pragma unroll
            for (int i = 0; i < 8; i++) { sts64(od + i * 512, r[i][0], r[i][1]); sts64(od + i * 512 + 256, r[i][2], r[i][3]); }
        }
        fence_async_smem();
        mbar_arrive(bars + 8 * B_LN);
        STAMP(16);
    }
}

__device__ __forceinline__ void consumer(uint32_t sb, int warp, const Params& P, const Maps& M) {
    const int V = warp >> 2, w = warp & 3, lane = threadIdx.x & 31, q = lane & 3, g = lane >> 2;
    const int c = blockIdx.x;
    const uint32_t bars = sb + OFF_BAR, xb = sb + OFF_X + V * 2 * XBUF;
    {
        float ag[88], au[88];
        if (V == 0) {
            sts128(xb + (w >> 1) * XBUF + 168 * 128 + (threadIdx.x & 63) * 16, 0x3f803f80u, 0x3f803f80u, 0x3f803f80u, 0x3f803f80u);
            fence_async_smem();
            bar_sync(1);
        } else {
            if (c < 128) layer_norm(sb, w, lane, P.x); else mbar_arrive(bars + 8 * B_LN);
            mbar_wait(bars + 8 * B_GO, 0);
        }
        define_acc(ag); define_acc(au);
        #pragma unroll 1
        for (int st = 0; st < 8; st++) {
            if (st + LAG * V == HOLD0 || st + LAG * V == HOLD1) mbar_wait(bars + 8 * (B_K + (st + LAG * V == HOLD1)), 0);
            mbar_wait(bars + 8 * (B_FULLW + (st & 3)), st >> 2);
            mbar_wait(bars + 8 * (B_FULLX + 2 * V + (st & 1)), (st >> 1) & 1);
            STAMP(40 + 8 * V + st);
            const uint64_t dG = mkdesc(sb + OFF_W + (st & 3) * 16384, 0, 1024, 1);
            const uint64_t dX = mkdesc(xb + (st & 1) * XBUF, 16, 1024, 1);
            WG_FENCE();
            #pragma unroll
            for (int k = 0; k < 4; k++) {
                wg_g1(ag, dG + k * 128, dX + k * 2, k ? 1 : st);
                wg_g1(au, dG + 512 + k * 128, dX + k * 2, k ? 1 : st);
            }
            WG_COMMIT();
            WG_WAIT(1);
            if (lane == 0 && st > 0) {
                mbar_arrive(bars + 8 * (B_EMPTYW + ((st - 1) & 3)));
                mbar_arrive(bars + 8 * (B_EMPTYX + 2 * V + ((st - 1) & 1)));
                if (warp < 4 && st == LAG) mbar_arrive(bars + 8 * B_GO);
            }
        }
        WG_WAIT(0);
        fence_acc(ag); fence_acc(au);
        if (lane == 0) { mbar_arrive(bars + 8 * (B_EMPTYW + 3)); mbar_arrive(bars + 8 * (B_EMPTYX + 2 * V + 1)); }
        STAMP(8 * V + 1);
        float cg0 = ag[84], cg1 = ag[86], cu0 = au[84], cu1 = au[86];
        const uint32_t ca = sb + OFF_CSUM + (8 * w + g) * 16;
        if (V == 0) { sts128(ca, FU(cg0), FU(cg1), FU(cu0), FU(cu1)); mbar_arrive(bars + 8 * B_CS); }
        else { mbar_wait(bars + 8 * B_CS, 0); const uint4 t = lds128(ca); cg0 = UF(t.x); cg1 = UF(t.y); cu0 = UF(t.z); cu1 = UF(t.w); }
        mbar_wait(bars + 8 * B_STATS, 0);
        mbar_wait(bars + 8 * (B_EMPTYX + 2 * V), 1);
        STAMP(13 + V);
        const uint32_t hs = xb + (2 * w + ((lane >> 3) & 1)) * (2688 + 128 * V) + (lane >> 4) * 128 + (lane & 7) * 16;
        const uint32_t sa = sb + OFF_ST + (168 * V + 2 * q) * 8;
        uint4 sq[22];
        #pragma unroll
        for (int j = 0; j < 3; j++) sq[j] = lds128(sa + j * 64);
        #pragma unroll
        for (int j = 0; j < 22; j += 2) {
            uint32_t o[4];
            #pragma unroll
            for (int jj = 0; jj < 2; jj++) {
                const uint4 sv = sq[j + jj];
                float hv[4];
                #pragma unroll
                for (int i = 0; i < 4; i++) {
                    const float m = UF((i & 1) ? sv.z : sv.x);
                    const float gh = fmaf(-m, (i & 2) ? cg1 : cg0, ag[4 * (j + jj) + i]) * UF((i & 1) ? sv.w : sv.y);
                    const float p = gh * fmaf(-m, (i & 2) ? cu1 : cu0, au[4 * (j + jj) + i]);
                    hv[i] = fmaf(p, tanh_fast(gh), p);
                }
                o[2 * jj] = pack2(hv[0], hv[1]); o[2 * jj + 1] = pack2(hv[2], hv[3]);
            }
            #pragma unroll
            for (int k = (j ? 3 + 3 * j / 2 : 3); k < 6 + 3 * j / 2 && k < 22; k++) sq[k] = lds128(sa + k * 64);
            uint32_t ad = hs + j * 128;
            if (j == 20 && V == 0 && lane >= 16) ad = xb + 21504 + (lane & 7) * 16;
            stsm4(ad, o[0], o[1], o[2], o[3]);
        }
        if (c >= 128) { fence_async_smem(); mbar_arrive(bars + 8 * (B_EPI + V)); }
        STAMP(8 * V + 2);
    }
    if (c >= 128) return;
    {
        uint32_t r0[8], r1[8];
        #pragma unroll
        for (int i = 0; i < 8; i++) asm volatile("" : "=r"(r1[i]));
        #pragma unroll 1
        for (int e = 0; e < 2; e++) {
            #pragma unroll
            for (int i = 0; i < 8; i++) r0[i] = r1[i];
            mbar_wait(bars + 8 * (B_CONV + 2 * V + e), 0);
            conv_channel(sb + OFF_CONV + (2 * V + e) * CH_STRIDE, w, lane, r1, e ? 0 : bars + 8 * (B_EPI + V), 2 * V + e);
            if (e == 0) STAMP(8 * V + 3);
        }
        const int gam = g >> 2, qq = gam ? ((q + 3) & 3) : q;
        const uint32_t sp = sb + OFF_CONV + V * OFF_SST + ((63 - 4 * gam - qq) * 16 + 4 * (w ^ (3 - qq)) + (g & 3)) * 8;
        bar_sync(3 + V);
        #pragma unroll
        for (int a2 = 0; a2 < 8; a2++) sts64(sp - a2 * 1024, r0[a2], r1[a2]);
        fence_async_smem();
        mbar_arrive(bars + 8 * (B_SIG + V));
        STAMP(8 * V + 4);
    }
    if (V == 1) return;
    {
        const int tau = c >> 2, dg = c & 3;
        const uint32_t row = 8 * (w & 1) + 32 * (w >> 1);
        float acc[64];
        define_acc(acc);
        const float rr0 = __ldcg(&P.st[64 * tau + row + g].y), rr1 = __ldcg(&P.st[64 * tau + row + g + 16].y);
        mbar_wait(bars + 8 * B_FULLD, 0);
        STAMP(5);
        uint64_t dB = mkdesc(sb + wd_slot(0), 8192, 1024, 1), dA = mkdesc(sb + h_slot(0), 1024, 128, 0);
        #pragma unroll 1
        for (int st = 0; st < 21; st++) {
            WG_FENCE();
            wg_tt128(acc, dA, dB, st);
            wg_tt128(acc, dA + 128, dB + 128, 1);
            wg_tt128(acc, dA + 256, dB + 256, 1);
            wg_tt128(acc, dA + 384, dB + 384, 1);
            WG_COMMIT();
            const int sd = (st + 1) & 7;
            const uint32_t nb = bars + 8 * (B_FULLD + sd), np = ((st + 1) >> 3) & 1;
            uint32_t ro = st == 15 ? 8 * B_CH0 : 8 * (B_EMPTYD + ((st - 1) & 7)), m = lane == 0 && st > 0, ok;
            dB = mkdesc(sb + wd_slot(sd), 8192, 1024, 1); dA = mkdesc(sb + h_slot(sd), 1024, 128, 0);
            asm volatile("{.reg .pred p; mbarrier.test_wait.parity.shared::cta.b64 p, [%5], %6; vote.sync.all.pred p, p, -1; selp.u32 %0, 1, 0, p;}"
                : "=r"(ok), "+l"(dA), "+l"(dB), "+r"(ro), "+r"(m) : "r"(nb), "r"(np) : "memory");
            WG_WAIT(1);
            asm volatile("{.reg .pred p; setp.ne.u32 p, %1, 0; @p mbarrier.arrive.shared::cta.b64 _, [%0];}" :: "r"(bars + ro), "r"(m) : "memory");
            if (!ok) mbar_wait(nb, np);
            if (w == 0) STAMP2(20 + st);
        }
        WG_FENCE();
        wg_tt128(acc, dA, dB, 1);
        wg_tt128(acc, dA + 128, dB + 128, 1);
        WG_COMMIT();
        mbar_wait(bars + 8 * B_XO, 0);
        const uint32_t xo = sb + OFF_CONV + (row + (lane & 7) + 16 * ((lane >> 3) & 1)) * 128;
        const uint32_t so = sb + wd_slot(6) + (w >> 1) * 8192 + q * 256 + (g & 1) * 8;
        const uint32_t sx = (4 * (w & 1) + (g >> 1)) ^ (2 * q) ^ (2 * ((2 * tau + (w >> 1)) & 3));
        uint32_t xr[8][4];
        uint2 sv[16];
        #pragma unroll
        for (int j = 0; j < 16; j += 2) {
            ldsm4(xr[j >> 1], xo + (j >> 3) * 8192 + ((((j & 7) + (lane >> 4)) ^ (lane & 7)) << 4));
            sv[j] = lds64(so + j * 512 + (sx << 4));
            sv[j + 1] = lds64(so + j * 512 + 128 + ((sx ^ 1) << 4));
        }
        WG_WAIT(0);
        fence_acc(acc);
        STAMP(6);
        #pragma unroll
        for (int j = 0; j < 16; j += 2) {
            #pragma unroll
            for (int i = 0; i < 4; i++) {
                const int jj = j + (i >> 1), hh = i & 1;
                const float f0 = acc[4 * jj + 2 * hh] * (hh ? rr1 : rr0), f1 = acc[4 * jj + 2 * hh + 1] * (hh ? rr1 : rr0);
                const uint32_t G = pack2(fmaf(f0, tanh_fast(f0), f0), fmaf(f1, tanh_fast(f1), f1));
                const uint32_t s2 = __byte_perm(sv[jj].x, sv[jj].y, hh ? 0x7632 : 0x5410);
                asm("fma.rn.bf16x2 %0, %1, %2, %0;" : "+r"(xr[j >> 1][i]) : "r"(s2), "r"(G));
            }
            stsm4(xo + (j >> 3) * 8192 + ((((j & 7) + (lane >> 4)) ^ (lane & 7)) << 4), xr[j >> 1][0], xr[j >> 1][1], xr[j >> 1][2], xr[j >> 1][3]);
        }
        fence_async_smem();
        bar_sync(1);
        if (w == 0 && elect_one()) {
            #pragma unroll
            for (int i = 0; i < 2; i++)
                asm volatile("cp.async.bulk.tensor.2d.global.shared::cta.bulk_group [%0, {%2, %3}], [%1];"
                    :: "l"(&M.out), "r"(sb + OFF_CONV + i * 8192), "r"(dg * 128 + 64 * i), "r"(tau * 64) : "memory");
            asm volatile("cp.async.bulk.commit_group; cp.async.bulk.wait_group.read 0;" ::: "memory");
        }
        STAMP(7); GSTAMP(23);
    }
}

__device__ __forceinline__ float2 cexp_p(float re2, float im, float p) {
    float sn, cs;
    const float mag = ex2(re2 * p), th = im * p;
    asm("sin.approx.ftz.f32 %0, %1;" : "=f"(sn) : "f"(th));
    asm("cos.approx.ftz.f32 %0, %1;" : "=f"(cs) : "f"(th));
    return make_float2(mag * cs, mag * sn);
}
struct SsmRaw { uint64_t la, ai, cr, ci; unsigned short ldt, dsk; };
__device__ __forceinline__ uint64_t ldg64(const void* p, int i) { uint64_t v; asm volatile("ld.global.nc.u64 %0, [%1];" : "=l"(v) : "l"((const uint64_t*)p + i)); return v; }
__device__ __forceinline__ unsigned short ldu16(const void* p) { unsigned short v; asm volatile("ld.global.nc.u16 %0, [%1];" : "=h"(v) : "l"(p)); return v; }
__device__ __forceinline__ float2 cmul(float2 a, float2 b) { return make_float2(fmaf(a.x, b.x, -a.y * b.y), fmaf(a.x, b.y, a.y * b.x)); }
__device__ __forceinline__ float2 csqr(float2 a) { const float t = a.x * a.y; return make_float2(fmaf(a.x, a.x, -a.y * a.y), t + t); }
__device__ __forceinline__ void mma16816(float (&d)[4], const uint32_t (&a)[4], uint32_t b0, uint32_t b1) {
    asm volatile("mma.sync.aligned.m16n8k16.row.col.f32.bf16.bf16.f32 {%0,%1,%2,%3}, {%4,%5,%6,%7}, {%8,%9}, {%0,%1,%2,%3};"
        : "+f"(d[0]), "+f"(d[1]), "+f"(d[2]), "+f"(d[3]) : "r"(a[0]), "r"(a[1]), "r"(a[2]), "r"(a[3]), "r"(b0), "r"(b1));
}

__device__ __forceinline__ void aux_role(uint32_t sb, int w, const SsmRaw& raw) {
    const int lane = threadIdx.x & 31, q = lane & 3, g = lane >> 2;
    const int c = blockIdx.x;
    const uint32_t bars = sb + OFF_BAR;
    if (c >= 128) {
        if (lane == 0) { mbar_arrive(bars + 8 * B_K); mbar_arrive(bars + 8 * (B_K + 1)); }
        return;
    }
    {
        const uint32_t cb = sb + OFF_CONV + w * CH_STRIDE;
        const uint32_t sF = cb + CH_A3;
        uint64_t la = raw.la, ai = raw.ai, cr = raw.cr, ci = raw.ci;
        const float ldt = bf_lo(raw.ldt), dsk = bf_lo(raw.dsk);
        float dacc[2][3][4];
        #pragma unroll
        for (int i = 0; i < 24; i++) (&dacc[0][0][0])[i] = 0.f;
        const float dt = bf_round(ex2(ldt * 1.4426950408889634f));
        #pragma unroll 1
        for (int ck = 0; ck < 4; ck++, la >>= 16, ai >>= 16, cr >>= 16, ci >>= 16) {
            const uint32_t fa = cb + lane * 4 + (ck & 1) * 8064;
            const float re2 = bf_round(ex2(bf_lo((uint32_t)la) * 1.4426950408889634f)) * dt * -1.4426950408889634f, im = bf_lo((uint32_t)ai) * dt;
            const float2 C = make_float2(bf_lo((uint32_t)cr) * (dt + dt), bf_lo((uint32_t)ci) * -(dt + dt));
            if (w == 0) { asm volatile("" :: "f"(re2), "f"(C.x) : "memory"); STAMP2(15 + ck); }
            const float2 z8 = cexp_p(re2, im, 8.f), y1 = cexp_p(re2, -im, 1.f);
            float2 b0 = make_float2(1.f, 0.f), b1 = cexp_p(re2, im, 64.f), b2 = csqr(b1), b3 = cmul(b2, b1), l0 = C;
            if (w == 0) { asm volatile("" :: "f"(b3.x), "f"(y1.x), "f"(z8.x) : "memory"); STAMP2(11 + ck); }
            const uint32_t fm = cb + (ck & 1) * 8064 + (lane >> 3) * 144 + (lane & 7) * 16;
#define PK(v) pack2((v).x, (v).y)
            #pragma unroll RUNROLL
            for (uint32_t ro = 0; ro < 8 * 144; ro += 144) {
                stsm4(fm + (lane >> 3) * 7 * 144 + ro, PK(b0), PK(b1), PK(b2), PK(b3));
                stsf(fa + 32 * 144 + ro, UF(PK(l0)));
                b0 = cmul(b0, z8); b1 = cmul(b1, z8); b2 = cmul(b2, z8); b3 = cmul(b3, z8); l0 = cmul(l0, y1);
            }
            if (ck < 2) STAMP(56 + 3 * ck);
            const float2 y256 = cexp_p(re2, -im, 256.f), y2 = csqr(y1), y4 = csqr(y2), y8 = make_float2(z8.x, -z8.y);
            const float2 t0 = cmul(C, y256), t1 = cmul(t0, y256), t2 = cmul(t1, y256), t3_ = cmul(t2, y256);
            const float2 u1 = cmul(t0, y2), u2 = cmul(u1, y2), u3 = cmul(u2, y2);
            stsm4(fm + 40 * 144, PK(t0), PK(u1), PK(u2), PK(u3));
            stsm4(fm + 44 * 144, PK(t1), PK(cmul(t1, y4)), PK(t2), PK(cmul(t2, y4)));
            const float2 v0 = cmul(t3_, y8), v1 = cmul(v0, y256), v2 = cmul(v1, y256), v3 = cmul(v2, y256);
            stsm4(fm + 48 * 144, PK(v0), PK(v1), PK(v2), PK(v3));
            stsf(fa + 52 * 144, UF(PK(t3_)));
#undef PK
            if (ck < 2) STAMP(57 + 3 * ck);
            if (ck & 1) {
                uint32_t ln_; asm volatile("mov.u32 %0, %%laneid;" : "=r"(ln_));
                const uint32_t lda = cb + (ln_ & 15) * 144 + (ln_ & 16);
                const uint32_t ldb = cb + (32 + (ln_ & 7)) * 144 + (ln_ >> 3) * 16;
                __syncwarp();
                #pragma unroll
                for (int k2 = 0; k2 < 4; k2++) {
                    const uint32_t ko = (k2 >> 1) * 8064 + (k2 & 1) * 64;
                    uint32_t b[3][4];
                    #pragma unroll
                    for (int t3 = 0; t3 < 3; t3++) ldsm4(b[t3], ldb + t3 * 8 * 144 + ko);
                    #pragma unroll
                    for (int k = 0; k < 2; k++)
                        #pragma unroll
                        for (int mu = 0; mu < 2; mu++) {
                            uint32_t a[4];
                            ldsm4(a, lda + mu * 16 * 144 + ko + k * 32);
                            #pragma unroll
                            for (int t3 = 0; t3 < 3; t3++) mma16816(dacc[mu][t3], a, b[t3][2 * k], b[t3][2 * k + 1]);
                        }
                }
                __syncwarp();
                if (lane == 0) mbar_arrive(bars + 8 * (B_K + (ck >> 1)));
                STAMP(58 + 3 * (ck >> 1));
            }
        }
        STAMP(18);
        const uint32_t sG = cb + CH_G;
        if (lane == 0) dacc[0][0][0] += dsk;
        if (lane < 18) sts128(lane < 8 ? cb + CH_U + 2048 + (lane & 4) * (UPLANE / 4) + (lane & 3) * 16 : sG + 128 + (lane & 1) * 208 + ((lane - 8) >> 1) * 16, 0, 0, 0, 0);
        {
            const uint32_t f0 = sF + (8 * g + 2 * q) * 4, f1 = sF + ((q < 2) ? 256 + 4 * g + 2 * q : 256 + 2 * g + 64 * q) * 4, st1 = (q < 2) ? 128 : 64;
            const uint32_t ga = sG + ((g & 1) ? 0 : 208) + (63 - (g >> 1) - 32 * q) * 2;
            #pragma unroll
            for (int i = 0; i < 4; i++) {
                const int mu = i >> 1, hh = i & 1;
                sts64(f0 + i * 256, FU(dacc[mu][0][2 * hh]), FU(dacc[mu][0][2 * hh + 1]));
                sts64(f1 + i * st1, FU(dacc[mu][1][2 * hh]), FU(dacc[mu][1][2 * hh + 1]));
                const uint32_t pk = pack2(dacc[mu][2][2 * hh], dacc[mu][2][2 * hh + 1]);
                if (q < 2) { sts16(ga - 8 * i, pk & 0xffff); sts16(ga - 8 * i - 32, pk >> 16); }
            }
            if (lane == 2) stsf(sF + 2048, dacc[0][2][0]);
        }
    }
    bar_sync(2);
    STAMP(19);
    const int u = min(lane, 30) - 15, r2 = (u + ((u >> 1) & 1)) >> 1, r4 = (u + 1 + ((u >> 2) & 1)) >> 2, xt = 1024 + 16 * w + u;
    const uint32_t o0 = CH_A3 + 4 * (w == 0 ? u : w == 1 ? 256 + r2 : 256 + 64 * w + r4), ost = w == 0 ? 64 : w == 1 ? 32 : 16;
    const uint32_t oa0 = u >= 0 || w == 3 ? o0 : CH_A3 + 4 * (w == 1 ? 256 + u : w == 2 ? 384 + r2 : 0);
    const uint32_t ot = CH_A3 + 4 * min(512, 256 + ((xt + 1 + ((xt >> 2) & 1)) >> 2));
    const int kap = (lane >> 4) * 8 + ((lane >> 1) & 7), gam = lane & 1, hh = w >> 1, wp = w & 1;
    const uint32_t oa = CH_U + wp * UPLANE + (127 - 4 * kap - 2 * gam - hh) * 16;
    const uint32_t ob = CH_U + (wp ^ 1) * UPLANE + (128 - wp - 4 * kap - 2 * gam - hh) * 16;
    const uint32_t od = CH_A3 + (4 * wp + hh) * 512 + (kap >> 3) * 256 + (kap & 7) * 16 + gam * 8;
    #pragma unroll 1
    for (int k = 0; k < 4; k++) {
        const int ch = 2 * (k & 1) + (k >> 1);
        const uint32_t cb = sb + OFF_CONV + ch * CH_STRIDE;
        {
            float kv[17];
            kv[0] = ldsf(cb + oa0); kv[16] = ldsf(cb + ot);
            #pragma unroll
            for (int s = 1; s < 16; s++) kv[s] = ldsf(cb + o0 + s * ost);
            const int tid = threadIdx.x & 127;
            const uint32_t ga = cb + CH_G + (tid >= 24) * 16 + min(tid, 47) * 8;
            const uint2 x0 = lds64(ga), x1 = lds64(ga + 8);
            if (u < 0 && w == 0) kv[0] = 0.f;
            if (xt > 1028) kv[16] = 0.f;
            uint32_t o[17];
            #pragma unroll
            for (int s = 0; s < 17; s++) o[s] = pack2(kv[s], __shfl_up_sync(0xffffffffu, kv[s], 1));
            if (lane > 0 && lane < 31) {
                const uint32_t ta = cb + CH_T + (lane - 1) * 280;
                #pragma unroll
                for (int s2 = 0; s2 < 8; s2++) sts64(ta + 64 * w + s2 * 8, o[2 * s2], o[2 * s2 + 1]);
                stsf(ta + 256 + 4 * w, UF(o[16]));
            }
            if (tid < 48) sts128(cb + CH_B3 + tid * 16, x0.x, x0.y, x1.x, x1.y);
        }
        mbar_wait(bars + 8 * B_U, 0);
        float p[24];
        const uint2 r0 = lds64(cb + ob + 24), r3 = lds64(cb + oa);
        uint32_t r[8];
        *(uint4*)&r[0] = lds128(cb + oa + 16); *(uint4*)&r[4] = lds128(cb + ob);
        p[0] = 0.f;
        p[1] = bf_lo(r0.x); p[2] = p[1] + bf_hi(r0.x); p[3] = p[2] + bf_lo(r0.y); p[4] = p[3] + bf_hi(r0.y);
        #pragma unroll
        for (int i = 0; i < 8; i++) { p[5 + 2 * i] = p[4 + 2 * i] + bf_lo(r[i]); p[6 + 2 * i] = p[5 + 2 * i] + bf_hi(r[i]); }
        p[21] = p[20] + bf_lo(r3.x); p[22] = p[21] + bf_hi(r3.x); p[23] = p[22] + bf_lo(r3.y);
        bar_sync(2);
        #pragma unroll
        for (int i = 0; i < 8; i += 4) {
            sts64(cb + od + i * 256, pack2(p[i + 9] - p[i], p[i + 10] - p[i + 1]), pack2(p[i + 11] - p[i + 2], p[i + 12] - p[i + 3]));
            sts64(cb + od + i * 256 + 128, pack2(p[i + 16] - p[i + 9], p[i + 17] - p[i + 10]), pack2(p[i + 18] - p[i + 11], p[i + 19] - p[i + 12]));
        }
        fence_async_smem();
        mbar_arrive(bars + 8 * (B_CONV + ch));
        if (k == 0) STAMP(17);
    }
    STAMP(21);
}

__global__ void __launch_bounds__(512, 1)
fused_kernel(const __grid_constant__ Params P, const __grid_constant__ Maps M) {
    extern __shared__ __align__(1024) uint8_t smem_raw[];
    const uint32_t sb = smem_u32(smem_raw);
    const uint32_t bars = sb + OFF_BAR;
    const int warp = __shfl_sync(0xffffffffu, threadIdx.x >> 5, 0);
    const int c = blockIdx.x, tg = c / 22, fb = c - 22 * tg;
    SsmRaw raw = {};
    if (warp >= 8 && warp < 12) {
        const int d = min(4 * c + warp - 8, DM - 1), o = d * 32 + (threadIdx.x & 31);
        raw.la = ldg64(P.logA, o); raw.ai = ldg64(P.Aim, o); raw.cr = ldg64(P.Cr, o); raw.ci = ldg64(P.Ci, o);
        raw.ldt = ldu16(P.logdt + d); raw.dsk = ldu16(P.Dskip + d);
    }
    if (elect_one()) {
        if (warp == 0) { STAMP(24); GSTAMP(22); }
        asm volatile("" :: "l"(((const uint64_t*)&P)[warp < 12 ? warp : 0]));
        if (warp < 12) asm volatile("prefetch.tensormap [%0];" :: "l"(&M.x[0] + warp) : "memory");
        #pragma unroll
        for (int k = 0; k < 4; k++) {
            const int i = 16 * k + ((warp + 4) & 15);
            const uint32_t cnt = i >= B_CONV ? 128 : ((0xf0ull >> i) & 1) ? 8 : ((0xff0000ull >> i) & 1) ? 2 : ((0x3e00ff00f000ull >> i) & 1) ? 4 : 1;
            asm volatile("mbarrier.init.shared::cta.b64 [%0], %1;" :: "r"(bars + 8 * i), "r"(cnt) : "memory");
        }
        asm volatile("fence.mbarrier_init.release.cluster; fence.proxy.async.shared::cta;" ::: "memory");
        if (warp == 13 || warp == 5 || warp == 6) { const uint32_t t0 = clock(); while ((uint32_t)clock() - t0 < DLY1) ; }
        if (warp == 12 || warp == 13) {
            const uint32_t s = warp - 12;
            mbar_expect(bars + 8 * (B_FULLW + s), 16384);
            tma2d(sb + OFF_W + s * 16384, &M.wg, 64 * fb, 64 * s, bars + 8 * (B_FULLW + s));
            tma2d(sb + OFF_W + s * 16384 + 8192, &M.wu, 64 * fb, 64 * s, bars + 8 * (B_FULLW + s));
            STAMP(31);
        } else if (warp >= 4 && warp < 7) {
            const uint32_t s = warp - 4, V = s >> 1;
            mbar_expect(bars + 8 * (B_FULLX + s), (168 + 8 * V) * 128);
            tma2d(sb + OFF_X + s * XBUF, &M.x[V], 64 * (s & 1), TOKG * tg + 168 * V, bars + 8 * (B_FULLX + s));
        }
        if (sb & 1023) __trap();
    }
    __syncthreads();
    if (warp < 8) {
        asm volatile("setmaxnreg.inc.sync.aligned.u32 208;");
        consumer(sb, warp, P, M);
    } else if (warp < 12) {
        asm volatile("setmaxnreg.dec.sync.aligned.u32 72;");
        STAMP(32);
        aux_role(sb, warp - 8, raw);
    } else {
        asm volatile("setmaxnreg.dec.sync.aligned.u32 24;");
        const int tau = c >> 2, dg = c & 3;
        if (elect_one()) {
            if (warp < 15) {
                if (warp == 12) {
                    #pragma unroll 1
                    for (int st = 2; st < 8; st++) {
                        const uint32_t s = st & 3, fb_ = bars + 8 * (B_FULLW + s);
                        if (st == 2) mbar_wait(bars + 8 * B_FULLW, 0);
                        mbar_wait(bars + 8 * (B_EMPTYW + s), (st >> 2) ^ 1);
                        mbar_expect(fb_, 16384);
                        tma2d(sb + OFF_W + s * 16384, &M.wg, 64 * fb, 64 * st, fb_);
                        tma2d(sb + OFF_W + s * 16384 + 8192, &M.wu, 64 * fb, 64 * st, fb_);
                    }
                } else {
                    const int V = warp - 13;
                    #pragma unroll 1
                    for (int st = 2 - V; st < 8; st++) {
                        const uint32_t s = 2 * V + (st & 1);
                        if (s == 3 && st == 1) mbar_wait(bars + 8 * B_LNS, 0);
                        mbar_wait(bars + 8 * (B_EMPTYX + s), ((st >> 1) & 1) ^ 1);
                        mbar_expect(bars + 8 * (B_FULLX + s), (168 + 8 * V) * 128);
                        tma2d(sb + OFF_X + s * XBUF, &M.x[V], 64 * st, TOKG * tg + 168 * V, bars + 8 * (B_FULLX + s));
                    }
                }
                if (c < 128 && warp < 14) {
                    if (warp == 13) {
                        mbar_wait(bars + 8 * (B_STG + 1), 0);
                        #pragma unroll 1
                        for (int o = 8 * tau; o < 8 * tau + 8; o += 7) flag_wait(P.flags, F_H + 2 * (o / 43) + ((o % 43) >= 21), 22);
                        mbar_arrive(bars + 8 * B_HF);
                        STAMP(25);
                    }
                    #pragma unroll 1
                    for (int st = 0; st < 22; st += (st < 7 || (st == 7 && warp == 12)) ? 1 : 2) {
                        const int sd = st & 7;
                        const uint32_t fb_ = bars + 8 * (B_FULLD + sd);
                        if (st >= 8) mbar_wait(bars + 8 * (B_EMPTYD + sd), ((st >> 3) & 1) ^ 1);
                        else if (warp == 12 || st >= 6) mbar_wait(bars + 8 * (uint32_t)((0x373623070d060504ull >> (8 * st)) & 0xff), st < 5);
                        if (st >= 10 && st < 21) STAMP2(31 + st);
                        if (st >= 8 || warp == 13) {
                            mbar_expect(fb_, 8192);
                            asm volatile("cp.async.bulk.tensor.5d.shared::cluster.global.mbarrier::complete_tx::bytes [%0], [%1, {%3, %3, %3, %4, %5}], [%2];"
                                :: "r"(sb + h_slot(sd)), "l"(&M.hld), "r"(fb_), "r"(0), "r"(2 * tau), "r"(8 * st) : "memory");
                        }
                        if (st >= 8 || warp == 12) {
                            const uint32_t da = sb + wd_slot(sd);
                            mbar_expect(fb_, 16384);
                            tma2d(da, &M.wd, 128 * dg, 64 * st, fb_);
                            tma2d(da + 8192, &M.wd, 128 * dg + 64, 64 * st, fb_);
                        }
                    }
                } else if (c < 128) {
                    mbar_wait(bars + 8 * B_SST, 0);
                    flag_wait(P.flags, F_S + dg, 64);
                    STAMP(26);
                    mbar_wait(bars + 8 * B_CH0, 0);
                    mbar_expect(bars + 8 * B_XO, 32768);
                    tma2d(sb + OFF_CONV, &M.xo, 128 * dg, 64 * tau, bars + 8 * B_XO);
                    tma2d(sb + OFF_CONV + 8192, &M.xo, 128 * dg + 64, 64 * tau, bars + 8 * B_XO);
                    asm volatile("cp.async.bulk.tensor.5d.shared::cluster.global.mbarrier::complete_tx::bytes [%0], [%1, {%3, %3, %3, %4, %5}], [%2];"
                        :: "r"(sb + wd_slot(6)), "l"(&M.sld), "r"(bars + 8 * B_XO), "r"(0), "r"(8 * dg), "r"(2 * tau) : "memory");
                    mbar_wait(bars + 8 * B_HF, 0);
                    exit_count(P.flags);
                }
            } else {
                mbar_wait(bars + 8 * B_LN, 0);
                STAMP2(0);
                if (c < 128) {
                    #pragma unroll 1
                    for (int i = 0; i < 2; i++)
                        asm volatile("cp.async.bulk.tensor.2d.global.shared::cta.bulk_group [%0, {%2, %3}], [%1];"
                            :: "l"(&M.xt), "r"(sb + OFF_LN + i * 8192), "r"((c & 1) * 1024 + (126 - (c & ~1)) * 8), "r"(256 * i) : "memory");
                    #pragma unroll 1
                    for (int i = 0; i < 2; i++) bulk_store(P.st + 16 * (c & ~1) + 8 * (c & 1) + 16 - 16 * i, sb + OFF_CSUM + 64 * i, 64);
                    asm volatile("cp.async.bulk.prefetch.L2.global [%0], %1;" :: "l"(P.Wd + c * (FF * DM / 128)), "r"(FF * DM / 64) : "memory");
                }
                asm volatile("cp.async.bulk.commit_group; cp.async.bulk.wait_group.read 0;" ::: "memory");
                mbar_arrive(bars + 8 * B_LNS);
                STAMP2(1);
                flag_signal(P.flags, F_A);
                STAMP2(2);
                flag_wait(P.flags, F_A, NCTA);
                STAMP(20);
                mbar_expect(bars + 8 * B_STATS, TOKG * 8);
                bulk_load(sb + OFF_ST, P.st + TOKG * tg, TOKG * 8, bars + 8 * B_STATS);
                if (c < 128) {
                    mbar_wait(bars + 8 * (B_K + 1), 0);
                    fence_async_smem();
                    mbar_expect(bars + 8 * B_U, 8 * 2048);
                    #pragma unroll 1
                    for (int i = 0; i < 8; i++)
                        bulk_load(sb + OFF_CONV + (i >> 1) * CH_STRIDE + CH_U + (i & 1) * UPLANE, P.xnT + 4 * c * 256 + i * 128, 2048, bars + 8 * B_U);
                } else exit_count(P.flags);
                #pragma unroll 1
                for (int V = 0; V < 2; V++) {
                    mbar_wait(bars + 8 * (B_EPI + V), 0);
                    STAMP2(3 + 2 * V);
                    asm volatile("cp.async.bulk.tensor.3d.global.shared::cta.bulk_group [%0, {%2, %3, %4}], [%1];"
                        :: "l"(&M.hst[V]), "r"(sb + OFF_X + V * 2 * XBUF), "r"(0), "r"(43 * tg + 21 * V), "r"(8 * fb) : "memory");
                    flag_signal(P.flags, F_H + 2 * tg + V);
                    mbar_arrive(bars + 8 * (B_STG + V));
                    STAMP2(4 + 2 * V);
                }
                if (c < 128) {
                    #pragma unroll 1
                    for (int V = 0; V < 2; V++) {
                        mbar_wait(bars + 8 * (B_SIG + V), 0);
                        STAMP2(7 + 2 * V);
                        bulk_store(P.S + (2 * c + V) * 1024, sb + OFF_CONV + V * OFF_SST, 8192);
                        flag_signal(P.flags, F_S + (c >> 5));
                        STAMP2(8 + 2 * V);
                    }
                    mbar_arrive(bars + 8 * B_SST);
                }
            }
        }
    }
    asm volatile("nanosleep.u32 0;");
}

typedef CUresult (*EncodeFn)(CUtensorMap*, CUtensorMapDataType, cuuint32_t, void*, const cuuint64_t*, const cuuint64_t*, const cuuint32_t*,
                             const cuuint32_t*, CUtensorMapInterleave, CUtensorMapSwizzle, CUtensorMapL2promotion, CUtensorMapFloatOOBfill);

void make_map(EncodeFn enc, CUtensorMap* m, const void* ptr, int rank, const cuuint64_t* dims, const cuuint64_t* strides, const cuuint32_t* box, bool swz, bool wide = false) {
    const cuuint32_t es[5] = {1, 1, 1, 1, 1};
    enc(m, CU_TENSOR_MAP_DATA_TYPE_BFLOAT16, rank, (void*)ptr, dims, strides, box, es, CU_TENSOR_MAP_INTERLEAVE_NONE,
        swz ? CU_TENSOR_MAP_SWIZZLE_128B : CU_TENSOR_MAP_SWIZZLE_NONE, wide ? CU_TENSOR_MAP_L2_PROMOTION_L2_256B : CU_TENSOR_MAP_L2_PROMOTION_L2_128B, CU_TENSOR_MAP_FLOAT_OOB_FILL_NONE);
}
void make_map2(EncodeFn enc, CUtensorMap* m, const void* ptr, cuuint64_t inner, cuuint64_t outer, cuuint32_t rows) {
    const cuuint64_t dims[2] = {inner, outer}, strides[1] = {inner * 2};
    const cuuint32_t box[2] = {64, rows};
    make_map(enc, m, ptr, 2, dims, strides, box, true, rows > 64);
}

}

extern "C" void kernel_launch(void* const* d_in, const int* in_sizes, int n_in, void* d_out, int out_size) {
    (void)in_sizes; (void)n_in; (void)out_size;
    static EncodeFn enc = nullptr;
    static void *hptr, *p_xnT, *p_st, *p_S, *p_flags;
    if (!enc) {
        cudaDriverEntryPointQueryResult qr;
        cudaGetDriverEntryPoint("cuTensorMapEncodeTiled", (void**)&enc, cudaEnableDefault, &qr);
        cudaFuncSetAttribute(fused_kernel, cudaFuncAttributeMaxDynamicSharedMemorySize, SMEM_BYTES);
        cudaGetSymbolAddress(&hptr, g_H); cudaGetSymbolAddress(&p_xnT, g_xnT); cudaGetSymbolAddress(&p_st, g_st);
        cudaGetSymbolAddress(&p_S, g_S); cudaGetSymbolAddress(&p_flags, g_flags);
    }
    Params P;
    P.x = (const __nv_bfloat16*)d_in[0]; P.logA = (const __nv_bfloat16*)d_in[1]; P.Aim = (const __nv_bfloat16*)d_in[2];
    P.Cr = (const __nv_bfloat16*)d_in[3]; P.Ci = (const __nv_bfloat16*)d_in[4]; P.logdt = (const __nv_bfloat16*)d_in[5];
    P.Dskip = (const __nv_bfloat16*)d_in[6];
    P.Wd = (const __nv_bfloat16*)d_in[10]; P.xnT = (uint4*)p_xnT; P.st = (float2*)p_st; P.S = (uint2*)p_S; P.flags = (unsigned*)p_flags;
    Maps M;
    make_map2(enc, &M.x[0], d_in[0], DM, SEQ, 168); make_map2(enc, &M.x[1], d_in[0], DM, SEQ, 176);
    make_map2(enc, &M.xo, d_in[0], DM, SEQ, 64);    make_map2(enc, &M.out, d_out, DM, SEQ, 64);
    make_map2(enc, &M.wg, d_in[8], FF, DM, 64);     make_map2(enc, &M.wu, d_in[9], FF, DM, 64);
    make_map2(enc, &M.wd, d_in[10], DM, FF, 64);
    for (int v = 0; v < 2; v++) {
        const cuuint64_t dims[3] = {64, 256, 172}, strides[2] = {128, 32768};
        const cuuint32_t box[3] = {64, (cuuint32_t)(21 + v), 8};
        make_map(enc, &M.hst[v], hptr, 3, dims, strides, box, false);
    }
    {
        const cuuint64_t dims[2] = {2048, 512}, strides[1] = {4096};
        const cuuint32_t box[2] = {16, 256};
        make_map(enc, &M.xt, p_xnT, 2, dims, strides, box, false);
    }
    {
        const cuuint64_t dims[5] = {64, 2, 4, 32, 64}, strides[4] = {4 * 8192, 8192, 8 * 8192, 128};
        const cuuint32_t box[5] = {64, 2, 4, 8, 2};
        make_map(enc, &M.sld, p_S, 5, dims, strides, box, true);
    }
    {
        const cuuint64_t dims[5] = {64, 2, 2, 64, 172}, strides[4] = {256, 128, 512, 32768};
        const cuuint32_t box[5] = {64, 2, 2, 2, 8};
        make_map(enc, &M.hld, hptr, 5, dims, strides, box, false);
    }
    fused_kernel<<<NCTA, 512, SMEM_BYTES>>>(P, M);
}
```

```cpp
#include <cuda_runtime.h>
#include <cuda_bf16.h>
#include <cuda.h>
#include <stdint.h>

#define PROF 0

namespace {

constexpr int SEQ = 2048, DM = 512, FF = 1376;
constexpr int NCTA = 132;
#define HOLD0 3
#define HOLD1 7
#define LAG 2
#define DLY1 300
#define DLY2 300
constexpr int RUNROLL = 8;
constexpr int TOKG = 344;

constexpr uint32_t OFF_W = 0;
constexpr uint32_t XBUF = 22528;
constexpr uint32_t OFF_X = 65536;
constexpr uint32_t OFF_CONV = 155648;
constexpr uint32_t CH_STRIDE = 17536;
constexpr uint32_t CH_T = 0;
constexpr uint32_t CH_A3 = 8448;
constexpr uint32_t CH_B3 = 12544;
constexpr uint32_t CH_U = 13312;
constexpr uint32_t CH_G = CH_A3 + 2064;
constexpr uint32_t UPLANE = 2112;
constexpr uint32_t CH_LN = 8064, CH_LNT = 13440;
constexpr uint32_t OFF_SST = 60416;
constexpr uint32_t OFF_ST = 225792;
constexpr uint32_t OFF_CSUM = 228544;
constexpr uint32_t OFF_BAR = 229056;
constexpr uint32_t SMEM_BYTES = 229568;

enum {
    B_FULLW = 0, B_EMPTYW = 4, B_FULLX = 8, B_EMPTYX = 12, B_FULLD = 16, B_EMPTYD = 24,
    B_U = 32, B_XO = 33, B_S = 34, B_STG = 35, B_HF = 37, B_STATS = 38, B_LNS = 39, B_SST = 40,
    B_LNX = 41, B_GO = 42, B_CH0 = 43, B_K = 44,
    B_CONV = 46, B_LN = 50, B_CS = 51, B_EPI = 52, B_SIG = 54,
    B_COUNT = 56
};
enum { F_A = 0, F_H = 1, F_S = 13, F_EXIT = 17, F_COUNT = 18 };

__device__ uint4 g_xnT[DM * 256];
__device__ float2 g_st[6 * TOKG];
__device__ uint4 g_H[172 * 256 * 8];
__device__ uint2 g_S[256 * 1024];
__device__ unsigned g_flags[F_COUNT * 32];
#define STAMP(i) do {} while (0)
#define GSTAMP(i) do {} while (0)
#define STAMP2(i) do {} while (0)

__device__ __forceinline__ uint32_t smem_u32(const void* p) { return (uint32_t)__cvta_generic_to_shared(p); }
__device__ __forceinline__ void mbar_expect(uint32_t bar, uint32_t bytes) { asm volatile("mbarrier.arrive.expect_tx.shared::cta.b64 _, [%0], %1;" :: "r"(bar), "r"(bytes) : "memory"); }
__device__ __forceinline__ void mbar_arrive(uint32_t bar) { asm volatile("mbarrier.arrive.shared::cta.b64 _, [%0];" :: "r"(bar) : "memory"); }
__device__ __forceinline__ void mbar_wait(uint32_t bar, uint32_t parity) {
    asm volatile("{.reg .pred p; .reg .u32 n; mov.u32 n, 0x20000;\n"
                 "LW: mbarrier.try_wait.parity.shared::cta.b64 p, [%0], %1;\n"
                 "sub.u32 n, n, 1; setp.eq.or.u32 p, n, 0, p; @!p bra LW;}" :: "r"(bar), "r"(parity) : "memory");
}
__device__ __forceinline__ bool elect_one() { uint32_t p; asm volatile("{.reg .pred P; elect.sync _|P, 0xffffffff; selp.u32 %0, 1, 0, P;}" : "=r"(p)); return p; }
__device__ __forceinline__ void tma2d(uint32_t dst, const CUtensorMap* m, int c0, int c1, uint32_t bar) {
    asm volatile("cp.async.bulk.tensor.2d.shared::cluster.global.mbarrier::complete_tx::bytes [%0], [%1, {%3, %4}], [%2];"
        :: "r"(dst), "l"(m), "r"(bar), "r"(c0), "r"(c1) : "memory");
}
__device__ __forceinline__ void bulk_load(uint32_t dst, const void* src, uint32_t bytes, uint32_t bar) {
    asm volatile("cp.async.bulk.shared::cluster.global.mbarrier::complete_tx::bytes [%0], [%1], %2, [%3];" :: "r"(dst), "l"(src), "r"(bytes), "r"(bar) : "memory");
}
__device__ __forceinline__ void bulk_store(void* dst, uint32_t src, uint32_t bytes) {
    asm volatile("cp.async.bulk.global.shared::cta.bulk_group [%0], [%1], %2;" :: "l"(dst), "r"(src), "r"(bytes) : "memory");
}
__device__ __forceinline__ void fence_async_smem() { asm volatile("fence.proxy.async.shared::cta;" ::: "memory"); }
__device__ __forceinline__ void flag_wait(unsigned* g_flags, int f, unsigned target) {
    asm volatile("{.reg .pred p; .reg .u32 n, v; mov.u32 n, 0x40000;\n"
                 "LF: ld.acquire.gpu.global.u32 v, [%0]; setp.ge.u32 p, v, %1; @p bra LD;\n"
                 "sub.u32 n, n, 1; setp.ne.u32 p, n, 0; @p bra LF; trap;\nLD: }"
                 :: "l"(g_flags + f * 32), "r"(target) : "memory");
}
__device__ __forceinline__ void flag_signal(unsigned* g_flags, int f) {
    asm volatile("cp.async.bulk.commit_group; cp.async.bulk.wait_group 0; red.relaxed.gpu.global.add.u32 [%0], 1;" :: "l"(g_flags + f * 32) : "memory");
}
__device__ __forceinline__ void exit_count(unsigned* g_flags) {
    if (atomicAdd(g_flags + F_EXIT * 32, 1u) == NCTA - 1) {
        #pragma unroll 1
        for (int i = 0; i < F_COUNT; i++) g_flags[i * 32] = 0;
    }
}
__device__ __forceinline__ void bar_sync(int id) { asm volatile("bar.sync %0, 128;" :: "r"(id) : "memory"); }
__device__ __forceinline__ uint64_t mkdesc(uint32_t addr, uint32_t lbo, uint32_t sbo, uint32_t swz) {
    return (uint64_t)((addr >> 4) | ((lbo >> 4) << 16)) | ((uint64_t)((sbo >> 4) | (swz << 30)) << 32);
}
#define WG_FENCE() asm volatile("wgmma.fence.sync.aligned;" ::: "memory")
#define WG_COMMIT() asm volatile("wgmma.commit_group.sync.aligned;" ::: "memory")
#define WG_WAIT(n) asm volatile("wgmma.wait_group.sync.aligned " #n ";" ::: "memory")
template <int N> __device__ __forceinline__ void fence_acc(float (&d)[N]) {
    #pragma unroll
    for (int i = 0; i < N; i++) asm volatile("" : "+f"(d[i]) :: "memory");
}
template <int N> __device__ __forceinline__ void define_acc(float (&d)[N]) {
    #pragma unroll
    for (int i = 0; i < N; i++) asm volatile("" : "=f"(d[i]));
}
__device__ __forceinline__ uint32_t pack2(float lo, float hi) { uint32_t r; asm("cvt.rn.bf16x2.f32 %0, %1, %2;" : "=r"(r) : "f"(hi), "f"(lo)); return r; }
__device__ __forceinline__ float bf_lo(uint32_t v) { return __uint_as_float(v << 16); }
__device__ __forceinline__ float bf_hi(uint32_t v) { return __uint_as_float(v & 0xffff0000u); }
__device__ __forceinline__ float bf_round(float v) { return bf_hi(pack2(0.f, v)); }
__device__ __forceinline__ float tanh_fast(float v) { float r; asm("tanh.approx.f32 %0, %1;" : "=f"(r) : "f"(v)); return r; }
__device__ __forceinline__ float ex2(float v) { float r; asm("ex2.approx.ftz.f32 %0, %1;" : "=f"(r) : "f"(v)); return r; }
__device__ __forceinline__ uint4 lds128(uint32_t a) { uint4 v; asm volatile("ld.shared.v4.b32 {%0,%1,%2,%3}, [%4];" : "=r"(v.x), "=r"(v.y), "=r"(v.z), "=r"(v.w) : "r"(a)); return v; }
__device__ __forceinline__ uint2 lds64(uint32_t a) { uint2 v; asm volatile("ld.shared.v2.b32 {%0,%1}, [%2];" : "=r"(v.x), "=r"(v.y) : "r"(a)); return v; }
__device__ __forceinline__ float ldsf(uint32_t a) { float v; asm volatile("ld.shared.f32 %0, [%1];" : "=f"(v) : "r"(a)); return v; }
__device__ __forceinline__ void sts128(uint32_t a, uint32_t x, uint32_t y, uint32_t z, uint32_t w) { asm volatile("st.shared.v4.b32 [%0], {%1,%2,%3,%4};" :: "r"(a), "r"(x), "r"(y), "r"(z), "r"(w) : "memory"); }
__device__ __forceinline__ void sts64(uint32_t a, uint32_t x, uint32_t y) { asm volatile("st.shared.v2.b32 [%0], {%1,%2};" :: "r"(a), "r"(x), "r"(y) : "memory"); }
__device__ __forceinline__ void stsf(uint32_t a, float x) { asm volatile("st.shared.f32 [%0], %1;" :: "r"(a), "f"(x) : "memory"); }
__device__ __forceinline__ void sts16(uint32_t a, uint32_t x) { asm volatile("st.shared.b16 [%0], %1;" :: "r"(a), "h"((unsigned short)x) : "memory"); }
__device__ __forceinline__ void stsm4(uint32_t a, uint32_t r0, uint32_t r1, uint32_t r2, uint32_t r3) {
    asm volatile("stmatrix.sync.aligned.m8n8.x4.shared.b16 [%0], {%1,%2,%3,%4};" :: "r"(a), "r"(r0), "r"(r1), "r"(r2), "r"(r3) : "memory");
}
__device__ __forceinline__ void ldsm4(uint32_t (&r)[4], uint32_t a) {
    asm volatile("ldmatrix.sync.aligned.m8n8.x4.shared.b16 {%0,%1,%2,%3}, [%4];" : "=r"(r[0]), "=r"(r[1]), "=r"(r[2]), "=r"(r[3]) : "r"(a) : "memory");
}
#define FU(x) __float_as_uint(x)
#define UF(x) __uint_as_float(x)
__device__ __forceinline__ uint32_t wd_slot(int s) { return (uint32_t)((0xbba8403056201000ull >> (8 * s)) & 0xff) << 10; }
__device__ __forceinline__ uint32_t h_slot(int s) { return (uint32_t)((0xcba0908880787068ull >> (8 * s)) & 0xff) << 10; }

template<int N> __device__ __forceinline__ void wg_rs(float (&d)[64], uint32_t a0, uint32_t a1, uint32_t a2, uint32_t a3, uint64_t db);
template<> __device__ __forceinline__ void wg_rs<128>(float (&d)[64], uint32_t a0, uint32_t a1, uint32_t a2, uint32_t a3, uint64_t db) {
  asm volatile("{.reg .pred p; setp.ne.b32 p, 1, 0; wgmma.mma_async.sync.aligned.m64n128k16.f32.bf16.bf16 {%0,%1,%2,%3,%4,%5,%6,%7,%8,%9,%10,%11,%12,%13,%14,%15,%16,%17,%18,%19,%20,%21,%22,%23,%24,%25,%26,%27,%28,%29,%30,%31,%32,%33,%34,%35,%36,%37,%38,%39,%40,%41,%42,%43,%44,%45,%46,%47,%48,%49,%50,%51,%52,%53,%54,%55,%56,%57,%58,%59,%60,%61,%62,%63}, {%64,%65,%66,%67}, %68, p, 1, 1, 0;}"
    : "+f"(d[0]),"+f"(d[1]),"+f"(d[2]),"+f"(d[3]),"+f"(d[4]),"+f"(d[5]),"+f"(d[6]),"+f"(d[7]),"+f"(d[8]),"+f"(d[9]),"+f"(d[10]),"+f"(d[11]),"+f"(d[12]),"+f"(d[13]),"+f"(d[14]),"+f"(d[15]),"+f"(d[16]),"+f"(d[17]),"+f"(d[18]),"+f"(d[19]),"+f"(d[20]),"+f"(d[21]),"+f"(d[22]),"+f"(d[23]),"+f"(d[24]),"+f"(d[25]),"+f"(d[26]),"+f"(d[27]),"+f"(d[28]),"+f"(d[29]),"+f"(d[30]),"+f"(d[31]),"+f"(d[32]),"+f"(d[33]),"+f"(d[34]),"+f"(d[35]),"+f"(d[36]),"+f"(d[37]),"+f"(d[38]),"+f"(d[39]),"+f"(d[40]),"+f"(d[41]),"+f"(d[42]),"+f"(d[43]),"+f"(d[44]),"+f"(d[45]),"+f"(d[46]),"+f"(d[47]),"+f"(d[48]),"+f"(d[49]),"+f"(d[50]),"+f"(d[51]),"+f"(d[52]),"+f"(d[53]),"+f"(d[54]),"+f"(d[55]),"+f"(d[56]),"+f"(d[57]),"+f"(d[58]),"+f"(d[59]),"+f"(d[60]),"+f"(d[61]),"+f"(d[62]),"+f"(d[63]) : "r"(a0), "r"(a1), "r"(a2), "r"(a3), "l"(db));
}
template<> __device__ __forceinline__ void wg_rs<120>(float (&d)[64], uint32_t a0, uint32_t a1, uint32_t a2, uint32_t a3, uint64_t db) {
  asm volatile("{.reg .pred p; setp.ne.b32 p, 1, 0; wgmma.mma_async.sync.aligned.m64n120k16.f32.bf16.bf16 {%0,%1,%2,%3,%4,%5,%6,%7,%8,%9,%10,%11,%12,%13,%14,%15,%16,%17,%18,%19,%20,%21,%22,%23,%24,%25,%26,%27,%28,%29,%30,%31,%32,%33,%34,%35,%36,%37,%38,%39,%40,%41,%42,%43,%44,%45,%46,%47,%48,%49,%50,%51,%52,%53,%54,%55,%56,%57,%58,%59}, {%60,%61,%62,%63}, %64, p, 1, 1, 0;}"
    : "+f"(d[0]),"+f"(d[1]),"+f"(d[2]),"+f"(d[3]),"+f"(d[4]),"+f"(d[5]),"+f"(d[6]),"+f"(d[7]),"+f"(d[8]),"+f"(d[9]),"+f"(d[10]),"+f"(d[11]),"+f"(d[12]),"+f"(d[13]),"+f"(d[14]),"+f"(d[15]),"+f"(d[16]),"+f"(d[17]),"+f"(d[18]),"+f"(d[19]),"+f"(d[20]),"+f"(d[21]),"+f"(d[22]),"+f"(d[23]),"+f"(d[24]),"+f"(d[25]),"+f"(d[26]),"+f"(d[27]),"+f"(d[28]),"+f"(d[29]),"+f"(d[30]),"+f"(d[31]),"+f"(d[32]),"+f"(d[33]),"+f"(d[34]),"+f"(d[35]),"+f"(d[36]),"+f"(d[37]),"+f"(d[38]),"+f"(d[39]),"+f"(d[40]),"+f"(d[41]),"+f"(d[42]),"+f"(d[43]),"+f"(d[44]),"+f"(d[45]),"+f"(d[46]),"+f"(d[47]),"+f"(d[48]),"+f"(d[49]),"+f"(d[50]),"+f"(d[51]),"+f"(d[52]),"+f"(d[53]),"+f"(d[54]),"+f"(d[55]),"+f"(d[56]),"+f"(d[57]),"+f"(d[58]),"+f"(d[59]) : "r"(a0), "r"(a1), "r"(a2), "r"(a3), "l"(db));
}
template<> __device__ __forceinline__ void wg_rs<112>(float (&d)[64], uint32_t a0, uint32_t a1, uint32_t a2, uint32_t a3, uint64_t db) {
  asm volatile("{.reg .pred p; setp.ne.b32 p, 1, 0; wgmma.mma_async.sync.aligned.m64n112k16.f32.bf16.bf16 {%0,%1,%2,%3,%4,%5,%6,%7,%8,%9,%10,%11,%12,%13,%14,%15,%16,%17,%18,%19,%20,%21,%22,%23,%24,%25,%26,%27,%28,%29,%30,%31,%32,%33,%34,%35,%36,%37,%38,%39,%40,%41,%42,%43,%44,%45,%46,%47,%48,%49,%50,%51,%52,%53,%54,%55}, {%56,%57,%58,%59}, %60, p, 1, 1, 0;}"
    : "+f"(d[0]),"+f"(d[1]),"+f"(d[2]),"+f"(d[3]),"+f"(d[4]),"+f"(d[5]),"+f"(d[6]),"+f"(d[7]),"+f"(d[8]),"+f"(d[9]),"+f"(d[10]),"+f"(d[11]),"+f"(d[12]),"+f"(d[13]),"+f"(d[14]),"+f"(d[15]),"+f"(d[16]),"+f"(d[17]),"+f"(d[18]),"+f"(d[19]),"+f"(d[20]),"+f"(d[21]),"+f"(d[22]),"+f"(d[23]),"+f"(d[24]),"+f"(d[25]),"+f"(d[26]),"+f"(d[27]),"+f"(d[28]),"+f"(d[29]),"+f"(d[30]),"+f"(d[31]),"+f"(d[32]),"+f"(d[33]),"+f"(d[34]),"+f"(d[35]),"+f"(d[36]),"+f"(d[37]),"+f"(d[38]),"+f"(d[39]),"+f"(d[40]),"+f"(d[41]),"+f"(d[42]),"+f"(d[43]),"+f"(d[44]),"+f"(d[45]),"+f"(d[46]),"+f"(d[47]),"+f"(d[48]),"+f"(d[49]),"+f"(d[50]),"+f"(d[51]),"+f"(d[52]),"+f"(d[53]),"+f"(d[54]),"+f"(d[55]) : "r"(a0), "r"(a1), "r"(a2), "r"(a3), "l"(db));
}
template<> __device__ __forceinline__ void wg_rs<104>(float (&d)[64], uint32_t a0, uint32_t a1, uint32_t a2, uint32_t a3, uint64_t db) {
  asm volatile("{.reg .pred p; setp.ne.b32 p, 1, 0; wgmma.mma_async.sync.aligned.m64n104k16.f32.bf16.bf16 {%0,%1,%2,%3,%4,%5,%6,%7,%8,%9,%10,%11,%12,%13,%14,%15,%16,%17,%18,%19,%20,%21,%22,%23,%24,%25,%26,%27,%28,%29,%30,%31,%32,%33,%34,%35,%36,%37,%38,%39,%40,%41,%42,%43,%44,%45,%46,%47,%48,%49,%50,%51}, {%52,%53,%54,%55}, %56, p, 1, 1, 0;}"
    : "+f"(d[0]),"+f"(d[1]),"+f"(d[2]),"+f"(d[3]),"+f"(d[4]),"+f"(d[5]),"+f"(d[6]),"+f"(d[7]),"+f"(d[8]),"+f"(d[9]),"+f"(d[10]),"+f"(d[11]),"+f"(d[12]),"+f"(d[13]),"+f"(d[14]),"+f"(d[15]),"+f"(d[16]),"+f"(d[17]),"+f"(d[18]),"+f"(d[19]),"+f"(d[20]),"+f"(d[21]),"+f"(d[22]),"+f"(d[23]),"+f"(d[24]),"+f"(d[25]),"+f"(d[26]),"+f"(d[27]),"+f"(d[28]),"+f"(d[29]),"+f"(d[30]),"+f"(d[31]),"+f"(d[32]),"+f"(d[33]),"+f"(d[34]),"+f"(d[35]),"+f"(d[36]),"+f"(d[37]),"+f"(d[38]),"+f"(d[39]),"+f"(d[40]),"+f"(d[41]),"+f"(d[42]),"+f"(d[43]),"+f"(d[44]),"+f"(d[45]),"+f"(d[46]),"+f"(d[47]),"+f"(d[48]),"+f"(d[49]),"+f"(d[50]),"+f"(d[51]) : "r"(a0), "r"(a1), "r"(a2), "r"(a3), "l"(db));
}
template<> __device__ __forceinline__ void wg_rs<96>(float (&d)[64], uint32_t a0, uint32_t a1, uint32_t a2, uint32_t a3, uint64_t db) {
  asm volatile("{.reg .pred p; setp.ne.b32 p, 1, 0; wgmma.mma_async.sync.aligned.m64n96k16.f32.bf16.bf16 {%0,%1,%2,%3,%4,%5,%6,%7,%8,%9,%10,%11,%12,%13,%14,%15,%16,%17,%18,%19,%20,%21,%22,%23,%24,%25,%26,%27,%28,%29,%30,%31,%32,%33,%34,%35,%36,%37,%38,%39,%40,%41,%42,%43,%44,%45,%46,%47}, {%48,%49,%50,%51}, %52, p, 1, 1, 0;}"
    : "+f"(d[0]),"+f"(d[1]),"+f"(d[2]),"+f"(d[3]),"+f"(d[4]),"+f"(d[5]),"+f"(d[6]),"+f"(d[7]),"+f"(d[8]),"+f"(d[9]),"+f"(d[10]),"+f"(d[11]),"+f"(d[12]),"+f"(d[13]),"+f"(d[14]),"+f"(d[15]),"+f"(d[16]),"+f"(d[17]),"+f"(d[18]),"+f"(d[19]),"+f"(d[20]),"+f"(d[21]),"+f"(d[22]),"+f"(d[23]),"+f"(d[24]),"+f"(d[25]),"+f"(d[26]),"+f"(d[27]),"+f"(d[28]),"+f"(d[29]),"+f"(d[30]),"+f"(d[31]),"+f"(d[32]),"+f"(d[33]),"+f"(d[34]),"+f"(d[35]),"+f"(d[36]),"+f"(d[37]),"+f"(d[38]),"+f"(d[39]),"+f"(d[40]),"+f"(d[41]),"+f"(d[42]),"+f"(d[43]),"+f"(d[44]),"+f"(d[45]),"+f"(d[46]),"+f"(d[47]) : "r"(a0), "r"(a1), "r"(a2), "r"(a3), "l"(db));
}
template<> __device__ __forceinline__ void wg_rs<88>(float (&d)[64], uint32_t a0, uint32_t a1, uint32_t a2, uint32_t a3, uint64_t db) {
  asm volatile("{.reg .pred p; setp.ne.b32 p, 1, 0; wgmma.mma_async.sync.aligned.m64n88k16.f32.bf16.bf16 {%0,%1,%2,%3,%4,%5,%6,%7,%8,%9,%10,%11,%12,%13,%14,%15,%16,%17,%18,%19,%20,%21,%22,%23,%24,%25,%26,%27,%28,%29,%30,%31,%32,%33,%34,%35,%36,%37,%38,%39,%40,%41,%42,%43}, {%44,%45,%46,%47}, %48, p, 1, 1, 0;}"
    : "+f"(d[0]),"+f"(d[1]),"+f"(d[2]),"+f"(d[3]),"+f"(d[4]),"+f"(d[5]),"+f"(d[6]),"+f"(d[7]),"+f"(d[8]),"+f"(d[9]),"+f"(d[10]),"+f"(d[11]),"+f"(d[12]),"+f"(d[13]),"+f"(d[14]),"+f"(d[15]),"+f"(d[16]),"+f"(d[17]),"+f"(d[18]),"+f"(d[19]),"+f"(d[20]),"+f"(d[21]),"+f"(d[22]),"+f"(d[23]),"+f"(d[24]),"+f"(d[25]),"+f"(d[26]),"+f"(d[27]),"+f"(d[28]),"+f"(d[29]),"+f"(d[30]),"+f"(d[31]),"+f"(d[32]),"+f"(d[33]),"+f"(d[34]),"+f"(d[35]),"+f"(d[36]),"+f"(d[37]),"+f"(d[38]),"+f"(d[39]),"+f"(d[40]),"+f"(d[41]),"+f"(d[42]),"+f"(d[43]) : "r"(a0), "r"(a1), "r"(a2), "r"(a3), "l"(db));
}
template<> __device__ __forceinline__ void wg_rs<80>(float (&d)[64], uint32_t a0, uint32_t a1, uint32_t a2, uint32_t a3, uint64_t db) {
  asm volatile("{.reg .pred p; setp.ne.b32 p, 1, 0; wgmma.mma_async.sync.aligned.m64n80k16.f32.bf16.bf16 {%0,%1,%2,%3,%4,%5,%6,%7,%8,%9,%10,%11,%12,%13,%14,%15,%16,%17,%18,%19,%20,%21,%22,%23,%24,%25,%26,%27,%28,%29,%30,%31,%32,%33,%34,%35,%36,%37,%38,%39}, {%40,%41,%42,%43}, %44, p, 1, 1, 0;}"
    : "+f"(d[0]),"+f"(d[1]),"+f"(d[2]),"+f"(d[3]),"+f"(d[4]),"+f"(d[5]),"+f"(d[6]),"+f"(d[7]),"+f"(d[8]),"+f"(d[9]),"+f"(d[10]),"+f"(d[11]),"+f"(d[12]),"+f"(d[13]),"+f"(d[14]),"+f"(d[15]),"+f"(d[16]),"+f"(d[17]),"+f"(d[18]),"+f"(d[19]),"+f"(d[20]),"+f"(d[21]),"+f"(d[22]),"+f"(d[23]),"+f"(d[24]),"+f"(d[25]),"+f"(d[26]),"+f"(d[27]),"+f"(d[28]),"+f"(d[29]),"+f"(d[30]),"+f"(d[31]),"+f"(d[32]),"+f"(d[33]),"+f"(d[34]),"+f"(d[35]),"+f"(d[36]),"+f"(d[37]),"+f"(d[38]),"+f"(d[39]) : "r"(a0), "r"(a1), "r"(a2), "r"(a3), "l"(db));
}
template<> __device__ __forceinline__ void wg_rs<72>(float (&d)[64], uint32_t a0, uint32_t a1, uint32_t a2, uint32_t a3, uint64_t db) {
  asm volatile("{.reg .pred p; setp.ne.b32 p, 1, 0; wgmma.mma_async.sync.aligned.m64n72k16.f32.bf16.bf16 {%0,%1,%2,%3,%4,%5,%6,%7,%8,%9,%10,%11,%12,%13,%14,%15,%16,%17,%18,%19,%20,%21,%22,%23,%24,%25,%26,%27,%28,%29,%30,%31,%32,%33,%34,%35}, {%36,%37,%38,%39}, %40, p, 1, 1, 0;}"
    : "+f"(d[0]),"+f"(d[1]),"+f"(d[2]),"+f"(d[3]),"+f"(d[4]),"+f"(d[5]),"+f"(d[6]),"+f"(d[7]),"+f"(d[8]),"+f"(d[9]),"+f"(d[10]),"+f"(d[11]),"+f"(d[12]),"+f"(d[13]),"+f"(d[14]),"+f"(d[15]),"+f"(d[16]),"+f"(d[17]),"+f"(d[18]),"+f"(d[19]),"+f"(d[20]),"+f"(d[21]),"+f"(d[22]),"+f"(d[23]),"+f"(d[24]),"+f"(d[25]),"+f"(d[26]),"+f"(d[27]),"+f"(d[28]),"+f"(d[29]),"+f"(d[30]),"+f"(d[31]),"+f"(d[32]),"+f"(d[33]),"+f"(d[34]),"+f"(d[35]) : "r"(a0), "r"(a1), "r"(a2), "r"(a3), "l"(db));
}
template<> __device__ __forceinline__ void wg_rs<64>(float (&d)[64], uint32_t a0, uint32_t a1, uint32_t a2, uint32_t a3, uint64_t db) {
  asm volatile("{.reg .pred p; setp.ne.b32 p, 1, 0; wgmma.mma_async.sync.aligned.m64n64k16.f32.bf16.bf16 {%0,%1,%2,%3,%4,%5,%6,%7,%8,%9,%10,%11,%12,%13,%14,%15,%16,%17,%18,%19,%20,%21,%22,%23,%24,%25,%26,%27,%28,%29,%30,%31}, {%32,%33,%34,%35}, %36, p, 1, 1, 0;}"
    : "+f"(d[0]),"+f"(d[1]),"+f"(d[2]),"+f"(d[3]),"+f"(d[4]),"+f"(d[5]),"+f"(d[6]),"+f"(d[7]),"+f"(d[8]),"+f"(d[9]),"+f"(d[10]),"+f"(d[11]),"+f"(d[12]),"+f"(d[13]),"+f"(d[14]),"+f"(d[15]),"+f"(d[16]),"+f"(d[17]),"+f"(d[18]),"+f"(d[19]),"+f"(d[20]),"+f"(d[21]),"+f"(d[22]),"+f"(d[23]),"+f"(d[24]),"+f"(d[25]),"+f"(d[26]),"+f"(d[27]),"+f"(d[28]),"+f"(d[29]),"+f"(d[30]),"+f"(d[31]) : "r"(a0), "r"(a1), "r"(a2), "r"(a3), "l"(db));
}
__device__ __forceinline__ void wg_rs_first(float (&d)[64], uint32_t a0, uint32_t a1, uint32_t a2, uint32_t a3, uint64_t db) {
  asm volatile("{.reg .pred p; setp.ne.b32 p, 0, 0; wgmma.mma_async.sync.aligned.m64n128k16.f32.bf16.bf16 {%0,%1,%2,%3,%4,%5,%6,%7,%8,%9,%10,%11,%12,%13,%14,%15,%16,%17,%18,%19,%20,%21,%22,%23,%24,%25,%26,%27,%28,%29,%30,%31,%32,%33,%34,%35,%36,%37,%38,%39,%40,%41,%42,%43,%44,%45,%46,%47,%48,%49,%50,%51,%52,%53,%54,%55,%56,%57,%58,%59,%60,%61,%62,%63}, {%64,%65,%66,%67}, %68, p, 1, 1, 0;}"
    : "=f"(d[0]),"=f"(d[1]),"=f"(d[2]),"=f"(d[3]),"=f"(d[4]),"=f"(d[5]),"=f"(d[6]),"=f"(d[7]),"=f"(d[8]),"=f"(d[9]),"=f"(d[10]),"=f"(d[11]),"=f"(d[12]),"=f"(d[13]),"=f"(d[14]),"=f"(d[15]),"=f"(d[16]),"=f"(d[17]),"=f"(d[18]),"=f"(d[19]),"=f"(d[20]),"=f"(d[21]),"=f"(d[22]),"=f"(d[23]),"=f"(d[24]),"=f"(d[25]),"=f"(d[26]),"=f"(d[27]),"=f"(d[28]),"=f"(d[29]),"=f"(d[30]),"=f"(d[31]),"=f"(d[32]),"=f"(d[33]),"=f"(d[34]),"=f"(d[35]),"=f"(d[36]),"=f"(d[37]),"=f"(d[38]),"=f"(d[39]),"=f"(d[40]),"=f"(d[41]),"=f"(d[42]),"=f"(d[43]),"=f"(d[44]),"=f"(d[45]),"=f"(d[46]),"=f"(d[47]),"=f"(d[48]),"=f"(d[49]),"=f"(d[50]),"=f"(d[51]),"=f"(d[52]),"=f"(d[53]),"=f"(d[54]),"=f"(d[55]),"=f"(d[56]),"=f"(d[57]),"=f"(d[58]),"=f"(d[59]),"=f"(d[60]),"=f"(d[61]),"=f"(d[62]),"=f"(d[63]) : "r"(a0), "r"(a1), "r"(a2), "r"(a3), "l"(db));
}
__device__ __forceinline__ void wg_tt128(float (&d)[64], uint64_t da, uint64_t db, int sc) {
  asm volatile("{.reg .pred p; setp.ne.b32 p, %66, 0; wgmma.mma_async.sync.aligned.m64n128k16.f32.bf16.bf16 {%0,%1,%2,%3,%4,%5,%6,%7,%8,%9,%10,%11,%12,%13,%14,%15,%16,%17,%18,%19,%20,%21,%22,%23,%24,%25,%26,%27,%28,%29,%30,%31,%32,%33,%34,%35,%36,%37,%38,%39,%40,%41,%42,%43,%44,%45,%46,%47,%48,%49,%50,%51,%52,%53,%54,%55,%56,%57,%58,%59,%60,%61,%62,%63}, %64, %65, p, 1, 1, 1, 1;}"
    : "+f"(d[0]),"+f"(d[1]),"+f"(d[2]),"+f"(d[3]),"+f"(d[4]),"+f"(d[5]),"+f"(d[6]),"+f"(d[7]),"+f"(d[8]),"+f"(d[9]),"+f"(d[10]),"+f"(d[11]),"+f"(d[12]),"+f"(d[13]),"+f"(d[14]),"+f"(d[15]),"+f"(d[16]),"+f"(d[17]),"+f"(d[18]),"+f"(d[19]),"+f"(d[20]),"+f"(d[21]),"+f"(d[22]),"+f"(d[23]),"+f"(d[24]),"+f"(d[25]),"+f"(d[26]),"+f"(d[27]),"+f"(d[28]),"+f"(d[29]),"+f"(d[30]),"+f"(d[31]),"+f"(d[32]),"+f"(d[33]),"+f"(d[34]),"+f"(d[35]),"+f"(d[36]),"+f"(d[37]),"+f"(d[38]),"+f"(d[39]),"+f"(d[40]),"+f"(d[41]),"+f"(d[42]),"+f"(d[43]),"+f"(d[44]),"+f"(d[45]),"+f"(d[46]),"+f"(d[47]),"+f"(d[48]),"+f"(d[49]),"+f"(d[50]),"+f"(d[51]),"+f"(d[52]),"+f"(d[53]),"+f"(d[54]),"+f"(d[55]),"+f"(d[56]),"+f"(d[57]),"+f"(d[58]),"+f"(d[59]),"+f"(d[60]),"+f"(d[61]),"+f"(d[62]),"+f"(d[63]) : "l"(da), "l"(db), "r"(sc));
}
__device__ __forceinline__ void wg_tt64(float (&d)[64], uint64_t da, uint64_t db, int sc) {
  asm volatile("{.reg .pred p; setp.ne.b32 p, %34, 0; wgmma.mma_async.sync.aligned.m64n64k16.f32.bf16.bf16 {%0,%1,%2,%3,%4,%5,%6,%7,%8,%9,%10,%11,%12,%13,%14,%15,%16,%17,%18,%19,%20,%21,%22,%23,%24,%25,%26,%27,%28,%29,%30,%31}, %32, %33, p, 1, 1, 1, 1;}"
    : "+f"(d[0]),"+f"(d[1]),"+f"(d[2]),"+f"(d[3]),"+f"(d[4]),"+f"(d[5]),"+f"(d[6]),"+f"(d[7]),"+f"(d[8]),"+f"(d[9]),"+f"(d[10]),"+f"(d[11]),"+f"(d[12]),"+f"(d[13]),"+f"(d[14]),"+f"(d[15]),"+f"(d[16]),"+f"(d[17]),"+f"(d[18]),"+f"(d[19]),"+f"(d[20]),"+f"(d[21]),"+f"(d[22]),"+f"(d[23]),"+f"(d[24]),"+f"(d[25]),"+f"(d[26]),"+f"(d[27]),"+f"(d[28]),"+f"(d[29]),"+f"(d[30]),"+f"(d[31]) : "l"(da), "l"(db), "r"(sc));
}
__device__ __forceinline__ void wg_tt32(float (&d)[64], uint64_t da, uint64_t db, int sc) {
  asm volatile("{.reg .pred p; setp.ne.b32 p, %18, 0; wgmma.mma_async.sync.aligned.m64n32k16.f32.bf16.bf16 {%0,%1,%2,%3,%4,%5,%6,%7,%8,%9,%10,%11,%12,%13,%14,%15}, %16, %17, p, 1, 1, 1, 1;}"
    : "+f"(d[0]),"+f"(d[1]),"+f"(d[2]),"+f"(d[3]),"+f"(d[4]),"+f"(d[5]),"+f"(d[6]),"+f"(d[7]),"+f"(d[8]),"+f"(d[9]),"+f"(d[10]),"+f"(d[11]),"+f"(d[12]),"+f"(d[13]),"+f"(d[14]),"+f"(d[15]) : "l"(da), "l"(db), "r"(sc));
}
__device__ __forceinline__ void wg_g1(float (&d)[88], uint64_t da, uint64_t db, int sc) {
  asm volatile("{.reg .pred p; setp.ne.b32 p, %90, 0; wgmma.mma_async.sync.aligned.m64n176k16.f32.bf16.bf16 {%0,%1,%2,%3,%4,%5,%6,%7,%8,%9,%10,%11,%12,%13,%14,%15,%16,%17,%18,%19,%20,%21,%22,%23,%24,%25,%26,%27,%28,%29,%30,%31,%32,%33,%34,%35,%36,%37,%38,%39,%40,%41,%42,%43,%44,%45,%46,%47,%48,%49,%50,%51,%52,%53,%54,%55,%56,%57,%58,%59,%60,%61,%62,%63,%64,%65,%66,%67,%68,%69,%70,%71,%72,%73,%74,%75,%76,%77,%78,%79,%80,%81,%82,%83,%84,%85,%86,%87}, %88, %89, p, 1, 1, 1, 0;}"
    : "+f"(d[0]),"+f"(d[1]),"+f"(d[2]),"+f"(d[3]),"+f"(d[4]),"+f"(d[5]),"+f"(d[6]),"+f"(d[7]),"+f"(d[8]),"+f"(d[9]),"+f"(d[10]),"+f"(d[11]),"+f"(d[12]),"+f"(d[13]),"+f"(d[14]),"+f"(d[15]),"+f"(d[16]),"+f"(d[17]),"+f"(d[18]),"+f"(d[19]),"+f"(d[20]),"+f"(d[21]),"+f"(d[22]),"+f"(d[23]),"+f"(d[24]),"+f"(d[25]),"+f"(d[26]),"+f"(d[27]),"+f"(d[28]),"+f"(d[29]),"+f"(d[30]),"+f"(d[31]),"+f"(d[32]),"+f"(d[33]),"+f"(d[34]),"+f"(d[35]),"+f"(d[36]),"+f"(d[37]),"+f"(d[38]),"+f"(d[39]),"+f"(d[40]),"+f"(d[41]),"+f"(d[42]),"+f"(d[43]),"+f"(d[44]),"+f"(d[45]),"+f"(d[46]),"+f"(d[47]),"+f"(d[48]),"+f"(d[49]),"+f"(d[50]),"+f"(d[51]),"+f"(d[52]),"+f"(d[53]),"+f"(d[54]),"+f"(d[55]),"+f"(d[56]),"+f"(d[57]),"+f"(d[58]),"+f"(d[59]),"+f"(d[60]),"+f"(d[61]),"+f"(d[62]),"+f"(d[63]),"+f"(d[64]),"+f"(d[65]),"+f"(d[66]),"+f"(d[67]),"+f"(d[68]),"+f"(d[69]),"+f"(d[70]),"+f"(d[71]),"+f"(d[72]),"+f"(d[73]),"+f"(d[74]),"+f"(d[75]),"+f"(d[76]),"+f"(d[77]),"+f"(d[78]),"+f"(d[79]),"+f"(d[80]),"+f"(d[81]),"+f"(d[82]),"+f"(d[83]),"+f"(d[84]),"+f"(d[85]),"+f"(d[86]),"+f"(d[87]) : "l"(da), "l"(db), "r"(sc));
}

struct Params { const __nv_bfloat16 *x, *logA, *Aim, *Cr, *Ci, *logdt, *Dskip, *Wd; uint4* xnT; float2* st; uint2* S; unsigned* flags; };
struct Maps { CUtensorMap x[2], xo, out, wg, wu, wd, hst[2], hld, xt, sld; };

__device__ __forceinline__ void conv_channel(uint32_t cb, int w, int lane, uint32_t (&res)[8], uint32_t sig, int sidx) {
    const int q = lane & 3, g = lane >> 2, gam = g >> 2;
    float acc[64];
    uint2 a[17][2];
    const uint32_t t0 = cb + CH_T + (uint32_t)(14 + 4 * w + (g & 3) - 2 * q) * 280u + gam * 8;
#define LDA(s0, s1) _Pragma("unroll") for (int s = s0; s < s1; s++) { a[s][0] = lds64(t0 + s * 16); a[s][1] = lds64(t0 - 8 * 280 + s * 16); }
#define CT(N, s) wg_rs<N>(acc, a[s][0].x, a[s][0].y, a[s][1].x, a[s][1].y, dU + 4 * (s))
    const uint64_t dU = mkdesc(cb + CH_U, UPLANE, 128, 0);
    LDA(0, 17)
    if (sig) { fence_async_smem(); mbar_arrive(sig); }
    WG_FENCE();
    if (w == 0) STAMP2(52 + 3 * sidx);
    wg_rs_first(acc, a[0][0].x, a[0][0].y, a[0][1].x, a[0][1].y, dU);
    CT(128, 1); CT(120, 2); CT(120, 3); CT(112, 4); CT(112, 5); CT(104, 6); CT(104, 7); CT(96, 8);
    CT(96, 9); CT(88, 10); CT(88, 11); CT(80, 12); CT(80, 13); CT(72, 14); CT(72, 15); CT(64, 16);
#undef CT
#undef LDA
    wg_tt64(acc, mkdesc(cb + CH_A3, 128, 512, 0), mkdesc(cb + CH_B3, 384, 32, 0), 1);
    wg_tt32(acc, mkdesc(cb + CH_A3 + 256, 128, 512, 0), mkdesc(cb + CH_B3 + 128, 384, 32, 0), 1);
    WG_COMMIT();
    if (w == 0) STAMP2(53 + 3 * sidx);
    WG_WAIT(0);
    fence_acc(acc);
    if (w == 0) STAMP2(54 + 3 * sidx);
    const int src1 = (lane & ~3) | ((q + 1) & 3);
    float E[16][2];
    #pragma unroll
    for (int j = 0; j < 16; j++) {
        const float nxt = (j < 15) ? acc[4 * (j + 1) + 2] : 0.f;
        const float sup = (q == 0) ? nxt : acc[4 * j + 2];
        const float v = __shfl_sync(0xffffffffu, sup, src1);
        E[j][0] = acc[4 * j] + acc[4 * j + 3];
        E[j][1] = acc[4 * j + 1] + v;
    }
    const int src2 = gam ? ((lane & 12) | ((q + 3) & 3)) : (16 | (lane & 12) | ((q + 1) & 3));
    const bool c1 = gam && q != 0, c2 = gam && q == 0;
    #pragma unroll
    for (int a2 = 0; a2 < 8; a2++) {
        float y[2];
        #pragma unroll
        for (int e = 0; e < 2; e++) {
            const float sup = c1 ? E[2 * a2][e] : E[2 * a2 + 1][e];
            const float nxt = (a2 < 7) ? E[2 * a2 + 2][e] : 0.f;
            const float keep = c2 ? nxt : (c1 ? E[2 * a2 + 1][e] : E[2 * a2][e]);
            y[e] = keep + __shfl_sync(0xffffffffu, sup, src2);
        }
        res[a2] = pack2(y[1], y[0]);
    }
}

__device__ __forceinline__ void consumer(uint32_t sb, int warp, const Params& P, const Maps& M) {
    const int V = warp >> 2, w = warp & 3, lane = threadIdx.x & 31, q = lane & 3, g = lane >> 2;
    const int c = blockIdx.x;
    const uint32_t bars = sb + OFF_BAR, xb = sb + OFF_X + V * 2 * XBUF;
    {
        float ag[88], au[88];
        if (V == 0) {
            sts128(xb + (w >> 1) * XBUF + 168 * 128 + (threadIdx.x & 63) * 16, 0x3f803f80u, 0x3f803f80u, 0x3f803f80u, 0x3f803f80u);
            fence_async_smem();
            bar_sync(1);
        } else mbar_wait(bars + 8 * B_GO, 0);
        define_acc(ag); define_acc(au);
        #pragma unroll 1
        for (int st = 0; st < 8; st++) {
            if (st + LAG * V == HOLD0 || st + LAG * V == HOLD1) mbar_wait(bars + 8 * (B_K + (st + LAG * V == HOLD1)), 0);
            mbar_wait(bars + 8 * (B_FULLW + (st & 3)), st >> 2);
            mbar_wait(bars + 8 * (B_FULLX + 2 * V + (st & 1)), (st >> 1) & 1);
            STAMP(40 + 8 * V + st);
            const uint64_t dG = mkdesc(sb + OFF_W + (st & 3) * 16384, 0, 1024, 1);
            const uint64_t dX = mkdesc(xb + (st & 1) * XBUF, 16, 1024, 1);
            WG_FENCE();
            #pragma unroll
            for (int k = 0; k < 4; k++) {
                wg_g1(ag, dG + k * 128, dX + k * 2, k ? 1 : st);
                wg_g1(au, dG + 512 + k * 128, dX + k * 2, k ? 1 : st);
            }
            WG_COMMIT();
            WG_WAIT(1);
            if (lane == 0 && st > 0) {
                mbar_arrive(bars + 8 * (B_EMPTYW + ((st - 1) & 3)));
                mbar_arrive(bars + 8 * (B_EMPTYX + 2 * V + ((st - 1) & 1)));
                if (warp < 4 && st == LAG) mbar_arrive(bars + 8 * B_GO);
            }
        }
        WG_WAIT(0);
        fence_acc(ag); fence_acc(au);
        if (lane == 0) { mbar_arrive(bars + 8 * (B_EMPTYW + 3)); mbar_arrive(bars + 8 * (B_EMPTYX + 2 * V + 1)); }
        STAMP(8 * V + 1);
        float cg0 = ag[84], cg1 = ag[86], cu0 = au[84], cu1 = au[86];
        const uint32_t ca = sb + OFF_CSUM + (8 * w + g) * 16;
        if (V == 0) { sts128(ca, FU(cg0), FU(cg1), FU(cu0), FU(cu1)); mbar_arrive(bars + 8 * B_CS); }
        else { mbar_wait(bars + 8 * B_CS, 0); const uint4 t = lds128(ca); cg0 = UF(t.x); cg1 = UF(t.y); cu0 = UF(t.z); cu1 = UF(t.w); }
        mbar_wait(bars + 8 * B_STATS, 0);
        mbar_wait(bars + 8 * (B_EMPTYX + 2 * V), 1);
        STAMP(13 + V);
        const uint32_t hs = xb + (2 * w + ((lane >> 3) & 1)) * (2688 + 128 * V) + (lane >> 4) * 128 + (lane & 7) * 16;
        const uint32_t sa = sb + OFF_ST + (168 * V + 2 * q) * 8;
        uint4 sq[22];
        #pragma unroll
        for (int j = 0; j < 3; j++) sq[j] = lds128(sa + j * 64);
        #pragma unroll
        for (int j = 0; j < 22; j += 2) {
            uint32_t o[4];
            #pragma unroll
            for (int jj = 0; jj < 2; jj++) {
                const uint4 sv = sq[j + jj];
                float hv[4];
                #pragma unroll
                for (int i = 0; i < 4; i++) {
                    const float m = UF((i & 1) ? sv.z : sv.x);
                    const float gh = fmaf(-m, (i & 2) ? cg1 : cg0, ag[4 * (j + jj) + i]) * UF((i & 1) ? sv.w : sv.y);
                    const float p = gh * fmaf(-m, (i & 2) ? cu1 : cu0, au[4 * (j + jj) + i]);
                    hv[i] = fmaf(p, tanh_fast(gh), p);
                }
                o[2 * jj] = pack2(hv[0], hv[1]); o[2 * jj + 1] = pack2(hv[2], hv[3]);
            }
            #pragma unroll
            for (int k = (j ? 3 + 3 * j / 2 : 3); k < 6 + 3 * j / 2 && k < 22; k++) sq[k] = lds128(sa + k * 64);
            uint32_t ad = hs + j * 128;
            if (j == 20 && V == 0 && lane >= 16) ad = xb + 21504 + (lane & 7) * 16;
            stsm4(ad, o[0], o[1], o[2], o[3]);
        }
        if (c >= 128) { fence_async_smem(); mbar_arrive(bars + 8 * (B_EPI + V)); }
        STAMP(8 * V + 2);
    }
    if (c >= 128) return;
    {
        uint32_t r0[8], r1[8];
        #pragma unroll
        for (int i = 0; i < 8; i++) asm volatile("" : "=r"(r1[i]));
        #pragma unroll 1
        for (int e = 0; e < 2; e++) {
            #pragma unroll
            for (int i = 0; i < 8; i++) r0[i] = r1[i];
            mbar_wait(bars + 8 * (B_CONV + 2 * V + e), 0);
            conv_channel(sb + OFF_CONV + (2 * V + e) * CH_STRIDE, w, lane, r1, e ? 0 : bars + 8 * (B_EPI + V), 2 * V + e);
            if (e == 0) STAMP(8 * V + 3);
        }
        const int gam = g >> 2, qq = gam ? ((q + 3) & 3) : q;
        const uint32_t sp = sb + OFF_CONV + V * OFF_SST + ((63 - 4 * gam - qq) * 16 + 4 * (w ^ (3 - qq)) + (g & 3)) * 8;
        bar_sync(3 + V);
        #pragma unroll
        for (int a2 = 0; a2 < 8; a2++) sts64(sp - a2 * 1024, r0[a2], r1[a2]);
        fence_async_smem();
        mbar_arrive(bars + 8 * (B_SIG + V));
        STAMP(8 * V + 4);
    }
    if (V == 1) return;
    {
        const int tau = c >> 2, dg = c & 3;
        const uint32_t row = 8 * (w & 1) + 32 * (w >> 1);
        float acc[64];
        define_acc(acc);
        const float rr0 = __ldcg(&P.st[64 * tau + row + g].y), rr1 = __ldcg(&P.st[64 * tau + row + g + 16].y);
        mbar_wait(bars + 8 * B_FULLD, 0);
        STAMP(5);
        uint64_t dB = mkdesc(sb + wd_slot(0), 8192, 1024, 1), dA = mkdesc(sb + h_slot(0), 1024, 128, 0);
        #pragma unroll 1
        for (int st = 0; st < 21; st++) {
            WG_FENCE();
            wg_tt128(acc, dA, dB, st);
            wg_tt128(acc, dA + 128, dB + 128, 1);
            wg_tt128(acc, dA + 256, dB + 256, 1);
            wg_tt128(acc, dA + 384, dB + 384, 1);
            WG_COMMIT();
            const int sd = (st + 1) & 7;
            const uint32_t nb = bars + 8 * (B_FULLD + sd), np = ((st + 1) >> 3) & 1;
            uint32_t ro = st == 15 ? 8 * B_CH0 : 8 * (B_EMPTYD + ((st - 1) & 7)), m = lane == 0 && st > 0, ok;
            dB = mkdesc(sb + wd_slot(sd), 8192, 1024, 1); dA = mkdesc(sb + h_slot(sd), 1024, 128, 0);
            asm volatile("{.reg .pred p; mbarrier.test_wait.parity.shared::cta.b64 p, [%5], %6; vote.sync.all.pred p, p, -1; selp.u32 %0, 1, 0, p;}"
                : "=r"(ok), "+l"(dA), "+l"(dB), "+r"(ro), "+r"(m) : "r"(nb), "r"(np) : "memory");
            WG_WAIT(1);
            asm volatile("{.reg .pred p; setp.ne.u32 p, %1, 0; @p mbarrier.arrive.shared::cta.b64 _, [%0];}" :: "r"(bars + ro), "r"(m) : "memory");
            if (!ok) mbar_wait(nb, np);
            if (w == 0) STAMP2(20 + st);
        }
        WG_FENCE();
        wg_tt128(acc, dA, dB, 1);
        wg_tt128(acc, dA + 128, dB + 128, 1);
        WG_COMMIT();
        mbar_wait(bars + 8 * B_XO, 0);
        const uint32_t xo = sb + OFF_CONV + (row + (lane & 7) + 16 * ((lane >> 3) & 1)) * 128;
        const uint32_t so = sb + wd_slot(6) + (w >> 1) * 8192 + q * 256 + (g & 1) * 8;
        const uint32_t sx = (4 * (w & 1) + (g >> 1)) ^ (2 * q) ^ (2 * ((2 * tau + (w >> 1)) & 3));
        uint32_t xr[8][4];
        uint2 sv[16];
        #pragma unroll
        for (int j = 0; j < 16; j += 2) {
            ldsm4(xr[j >> 1], xo + (j >> 3) * 8192 + ((((j & 7) + (lane >> 4)) ^ (lane & 7)) << 4));
            sv[j] = lds64(so + j * 512 + (sx << 4));
            sv[j + 1] = lds64(so + j * 512 + 128 + ((sx ^ 1) << 4));
        }
        WG_WAIT(0);
        fence_acc(acc);
        STAMP(6);
        #pragma unroll
        for (int j = 0; j < 16; j += 2) {
            #pragma unroll
            for (int i = 0; i < 4; i++) {
                const int jj = j + (i >> 1), hh = i & 1;
                const float f0 = acc[4 * jj + 2 * hh] * (hh ? rr1 : rr0), f1 = acc[4 * jj + 2 * hh + 1] * (hh ? rr1 : rr0);
                const uint32_t G = pack2(fmaf(f0, tanh_fast(f0), f0), fmaf(f1, tanh_fast(f1), f1));
                const uint32_t s2 = __byte_perm(sv[jj].x, sv[jj].y, hh ? 0x7632 : 0x5410);
                asm("fma.rn.bf16x2 %0, %1, %2, %0;" : "+r"(xr[j >> 1][i]) : "r"(s2), "r"(G));
            }
            stsm4(xo + (j >> 3) * 8192 + ((((j & 7) + (lane >> 4)) ^ (lane & 7)) << 4), xr[j >> 1][0], xr[j >> 1][1], xr[j >> 1][2], xr[j >> 1][3]);
        }
        fence_async_smem();
        bar_sync(1);
        if (w == 0 && elect_one()) {
            #pragma unroll
            for (int i = 0; i < 2; i++)
                asm volatile("cp.async.bulk.tensor.2d.global.shared::cta.bulk_group [%0, {%2, %3}], [%1];"
                    :: "l"(&M.out), "r"(sb + OFF_CONV + i * 8192), "r"(dg * 128 + 64 * i), "r"(tau * 64) : "memory");
            asm volatile("cp.async.bulk.commit_group; cp.async.bulk.wait_group.read 0;" ::: "memory");
        }
        STAMP(7); GSTAMP(23);
    }
}

__device__ __forceinline__ float2 cexp_p(float re2, float im, float p) {
    float sn, cs;
    const float mag = ex2(re2 * p), th = im * p;
    asm("sin.approx.ftz.f32 %0, %1;" : "=f"(sn) : "f"(th));
    asm("cos.approx.ftz.f32 %0, %1;" : "=f"(cs) : "f"(th));
    return make_float2(mag * cs, mag * sn);
}
struct SsmRaw { uint64_t la, ai, cr, ci; unsigned short ldt, dsk; };
__device__ __forceinline__ uint64_t ldg64(const void* p, int i) { uint64_t v; asm volatile("ld.global.nc.u64 %0, [%1];" : "=l"(v) : "l"((const uint64_t*)p + i)); return v; }
__device__ __forceinline__ unsigned short ldu16(const void* p) { unsigned short v; asm volatile("ld.global.nc.u16 %0, [%1];" : "=h"(v) : "l"(p)); return v; }
__device__ __forceinline__ float2 cmul(float2 a, float2 b) { return make_float2(fmaf(a.x, b.x, -a.y * b.y), fmaf(a.x, b.y, a.y * b.x)); }
__device__ __forceinline__ float2 csqr(float2 a) { const float t = a.x * a.y; return make_float2(fmaf(a.x, a.x, -a.y * a.y), t + t); }
__device__ __forceinline__ void mma16816(float (&d)[4], const uint32_t (&a)[4], uint32_t b0, uint32_t b1) {
    asm volatile("mma.sync.aligned.m16n8k16.row.col.f32.bf16.bf16.f32 {%0,%1,%2,%3}, {%4,%5,%6,%7}, {%8,%9}, {%0,%1,%2,%3};"
        : "+f"(d[0]), "+f"(d[1]), "+f"(d[2]), "+f"(d[3]) : "r"(a[0]), "r"(a[1]), "r"(a[2]), "r"(a[3]), "r"(b0), "r"(b1));
}

__device__ __forceinline__ void layer_norm(uint32_t sb, uint32_t cb, int w, int lane) {
    const uint32_t bars = sb + OFF_BAR;
    mbar_wait(bars + 8 * B_LNX, 0);
    STAMP(34);
    {
        const uint32_t r0 = cb + CH_LN + (w & 1) * 64 + (lane >> 3) * 1040, ra = r0 + (lane & 7) * 16;
        const float pv = bf_lo(FU(ldsf(r0)));
        float s0 = 0.f, s1 = 0.f, a0 = 0.f, a1 = 0.f;
        uint4 nx = lds128(ra), ny = lds128(ra + 128);
        #pragma unroll 2
        for (int k = 256; k <= 1152; k += 128) {
            const uint32_t v[4] = {nx.x, nx.y, nx.z, nx.w};
            nx = ny; ny = lds128(ra + (k & 1023));
            #pragma unroll
            for (int i = 0; i < 4; i++) { const float t0 = bf_lo(v[i]) - pv, t1 = bf_hi(v[i]) - pv; s0 += t0; s1 += t1; a0 = fmaf(t0, t0, a0); a1 = fmaf(t1, t1, a1); }
        }
        s0 += s1; a0 += a1;
        #pragma unroll
        for (int o = 4; o; o >>= 1) { s0 += __shfl_xor_sync(0xffffffffu, s0, o); a0 += __shfl_xor_sync(0xffffffffu, a0, o); }
        s0 *= 1.f / DM;
        float sd, ri;
        asm("sqrt.approx.ftz.f32 %0, %1;" : "=f"(sd) : "f"(bf_round(bf_round(fmaxf(fmaf(-s0, s0, a0 * (1.f / DM)), 0.f)) + 1e-5f)));
        asm("rcp.approx.ftz.f32 %0, %1;" : "=f"(ri) : "f"(bf_round(sd)));
        if ((lane & 7) == 0) sts64(sb + OFF_CSUM + (w + 4 * (lane >> 3)) * 8, FU(bf_round(pv + s0)), FU(0.5f * ri));
    }
    STAMP(62);
    bar_sync(2);
    const int r = 4 * ((lane & 7) >> 1) + (lane & 1) + 2 * ((lane >> 3) & 1);
    const uint32_t ad = sb + OFF_CONV + (r & 3) * CH_STRIDE + CH_LN + (r & 1) * 64 + (r >> 2) * 1040 + (16 * w + (lane >> 4)) * 16;
    const uint4 sa = lds128(sb + OFF_CSUM + (lane & 3) * 32), sc = lds128(sb + OFF_CSUM + (lane & 3) * 32 + 16);
    const uint32_t m2[2] = {__byte_perm(sa.x, sa.z, 0x7632), __byte_perm(sc.x, sc.z, 0x7632)};
    const float ri[4] = {2.f * UF(sa.y), 2.f * UF(sa.w), 2.f * UF(sc.y), 2.f * UF(sc.w)};
    #pragma unroll 2
    for (int i = 0; i < 8; i++) {
        uint32_t v[4];
        asm volatile("ldmatrix.sync.aligned.m8n8.x4.trans.shared.b16 {%0,%1,%2,%3}, [%4];" : "=r"(v[0]), "=r"(v[1]), "=r"(v[2]), "=r"(v[3]) : "r"(ad + 32 * i) : "memory");
        #pragma unroll
        for (int k = 0; k < 4; k++) {
            uint32_t dv; asm("sub.rn.bf16x2 %0, %1, %2;" : "=r"(dv) : "r"(v[k]), "r"(m2[k & 1]));
            v[k] = pack2(bf_lo(dv) * ri[2 * (k & 1)], bf_hi(dv) * ri[2 * (k & 1) + 1]);
        }
        sts64(cb + CH_LNT + lane * 8 + i * 512, v[0], v[1]); sts64(cb + CH_LNT + lane * 8 + i * 512 + 256, v[2], v[3]);
    }
    fence_async_smem();
    mbar_arrive(bars + 8 * B_LN);
    STAMP(16);
}

__device__ __forceinline__ void aux_role(uint32_t sb, int w, const SsmRaw& raw, const __nv_bfloat16* x) {
    const int lane = threadIdx.x & 31, q = lane & 3, g = lane >> 2;
    const int c = blockIdx.x;
    const uint32_t bars = sb + OFF_BAR;
    if (c >= 128) {
        mbar_arrive(bars + 8 * B_LN);
        if (lane == 0) { mbar_arrive(bars + 8 * B_K); mbar_arrive(bars + 8 * (B_K + 1)); }
        return;
    }
    {
        const uint32_t cb = sb + OFF_CONV + w * CH_STRIDE;
        const uint32_t sF = cb + CH_A3;
        uint64_t la = raw.la, ai = raw.ai, cr = raw.cr, ci = raw.ci;
        const float ldt = bf_lo(raw.ldt), dsk = bf_lo(raw.dsk);
        float dacc[2][3][4];
        #pragma unroll
        for (int i = 0; i < 24; i++) (&dacc[0][0][0])[i] = 0.f;
        const float dt = bf_round(ex2(ldt * 1.4426950408889634f));
        #pragma unroll 1
        for (int ck = 0; ck < 4; ck++, la >>= 16, ai >>= 16, cr >>= 16, ci >>= 16) {
            const uint32_t fa = cb + lane * 4 + (ck & 1) * 8064;
            if (ck == 2 && elect_one()) {
                fence_async_smem();
                mbar_expect(bars + 8 * B_LNX, 4096);
                #pragma unroll
                for (int i = 0; i < 4; i++)
                    bulk_load(cb + CH_LN + (w & 1) * 64 + i * 1040, x + (16 * (c & ~1) + 8 * (c & 1) + 16 + w + 4 * (i & 1) - 8 * (i & 2)) * DM, 1024, bars + 8 * B_LNX);
            }
            if (ck == 3) { layer_norm(sb, cb, w, lane); mbar_wait(bars + 8 * B_LN, 0); }
            const float re2 = bf_round(ex2(bf_lo((uint32_t)la) * 1.4426950408889634f)) * dt * -1.4426950408889634f, im = bf_lo((uint32_t)ai) * dt;
            const float2 C = make_float2(bf_lo((uint32_t)cr) * (dt + dt), bf_lo((uint32_t)ci) * -(dt + dt));
            if (w == 0) { asm volatile("" :: "f"(re2), "f"(C.x) : "memory"); STAMP2(15 + ck); }
            const float2 z8 = cexp_p(re2, im, 8.f), y1 = cexp_p(re2, -im, 1.f);
            float2 b0 = make_float2(1.f, 0.f), b1 = cexp_p(re2, im, 64.f), b2 = csqr(b1), b3 = cmul(b2, b1);
            if (w == 0) { asm volatile("" :: "f"(b3.x), "f"(y1.x), "f"(z8.x) : "memory"); STAMP2(11 + ck); }
            const uint32_t fm = cb + (ck & 1) * 8064 + (lane >> 3) * 144 + (lane & 7) * 16;
#define PK(v) pack2((v).x, (v).y)
            #pragma unroll RUNROLL
            for (uint32_t ro = 0; ro < 8 * 144; ro += 144) {
                stsm4(fm + (lane >> 3) * 7 * 144 + ro, PK(b0), PK(b1), PK(b2), PK(b3));
                b0 = cmul(b0, z8); b1 = cmul(b1, z8); b2 = cmul(b2, z8); b3 = cmul(b3, z8);
            }
            if (ck < 2) STAMP(56 + 3 * ck);
            const float2 y256 = cexp_p(re2, -im, 256.f), y2 = csqr(y1), y4 = csqr(y2), y8 = make_float2(z8.x, -z8.y);
            if (ck == 3) mbar_wait(bars + 8 * B_LNS, 0);
            {
                const float2 l1 = cmul(C, y1), l2 = cmul(C, y2), l3 = cmul(l1, y2);
                stsm4(fm + 32 * 144, PK(C), PK(l1), PK(l2), PK(l3));
                stsm4(fm + 36 * 144, PK(cmul(C, y4)), PK(cmul(l1, y4)), PK(cmul(l2, y4)), PK(cmul(l3, y4)));
            }
            const float2 t0 = cmul(C, y256), t1 = cmul(t0, y256), t2 = cmul(t1, y256), t3_ = cmul(t2, y256);
            const float2 u1 = cmul(t0, y2), u2 = cmul(u1, y2), u3 = cmul(u2, y2);
            stsm4(fm + 40 * 144, PK(t0), PK(u1), PK(u2), PK(u3));
            stsm4(fm + 44 * 144, PK(t1), PK(cmul(t1, y4)), PK(t2), PK(cmul(t2, y4)));
            const float2 v0 = cmul(t3_, y8), v1 = cmul(v0, y256), v2 = cmul(v1, y256), v3 = cmul(v2, y256);
            stsm4(fm + 48 * 144, PK(v0), PK(v1), PK(v2), PK(v3));
            stsf(fa + 52 * 144, UF(PK(t3_)));
#undef PK
            if (ck < 2) STAMP(57 + 3 * ck);
            if (ck & 1) {
                uint32_t ln_; asm volatile("mov.u32 %0, %%laneid;" : "=r"(ln_));
                const uint32_t lda = cb + (ln_ & 15) * 144 + (ln_ & 16);
                const uint32_t ldb = cb + (32 + (ln_ & 7)) * 144 + (ln_ >> 3) * 16;
                __syncwarp();
                #pragma unroll
                for (int k2 = 0; k2 < 4; k2++) {
                    const uint32_t ko = (k2 >> 1) * 8064 + (k2 & 1) * 64;
                    uint32_t b[3][4];
                    #pragma unroll
                    for (int t3 = 0; t3 < 3; t3++) ldsm4(b[t3], ldb + t3 * 8 * 144 + ko);
                    #pragma unroll
                    for (int k = 0; k < 2; k++)
                        #pragma unroll
                        for (int mu = 0; mu < 2; mu++) {
                            uint32_t a[4];
                            ldsm4(a, lda + mu * 16 * 144 + ko + k * 32);
                            #pragma unroll
                            for (int t3 = 0; t3 < 3; t3++) mma16816(dacc[mu][t3], a, b[t3][2 * k], b[t3][2 * k + 1]);
                        }
                }
                __syncwarp();
                if (lane == 0) mbar_arrive(bars + 8 * (B_K + (ck >> 1)));
                STAMP(58 + 3 * (ck >> 1));
            }
        }
        STAMP(18);
        const uint32_t sG = cb + CH_G;
        if (lane == 0) dacc[0][0][0] += dsk;
        if (lane < 18) sts128(lane < 8 ? cb + CH_U + 2048 + (lane & 4) * (UPLANE / 4) + (lane & 3) * 16 : sG + 128 + (lane & 1) * 208 + ((lane - 8) >> 1) * 16, 0, 0, 0, 0);
        {
            const uint32_t f0 = sF + (8 * g + 2 * q) * 4, f1 = sF + ((q < 2) ? 256 + 4 * g + 2 * q : 256 + 2 * g + 64 * q) * 4, st1 = (q < 2) ? 128 : 64;
            const uint32_t ga = sG + ((g & 1) ? 0 : 208) + (63 - (g >> 1) - 32 * q) * 2;
            #pragma unroll
            for (int i = 0; i < 4; i++) {
                const int mu = i >> 1, hh = i & 1;
                sts64(f0 + i * 256, FU(dacc[mu][0][2 * hh]), FU(dacc[mu][0][2 * hh + 1]));
                sts64(f1 + i * st1, FU(dacc[mu][1][2 * hh]), FU(dacc[mu][1][2 * hh + 1]));
                const uint32_t pk = pack2(dacc[mu][2][2 * hh], dacc[mu][2][2 * hh + 1]);
                if (q < 2) { sts16(ga - 8 * i, pk & 0xffff); sts16(ga - 8 * i - 32, pk >> 16); }
            }
            if (lane == 2) stsf(sF + 2048, dacc[0][2][0]);
        }
    }
    bar_sync(2);
    STAMP(19);
    const int u = min(lane, 30) - 15, r2 = (u + ((u >> 1) & 1)) >> 1, r4 = (u + 1 + ((u >> 2) & 1)) >> 2, xt = 1024 + 16 * w + u;
    const uint32_t o0 = CH_A3 + 4 * (w == 0 ? u : w == 1 ? 256 + r2 : 256 + 64 * w + r4), ost = w == 0 ? 64 : w == 1 ? 32 : 16;
    const uint32_t oa0 = u >= 0 || w == 3 ? o0 : CH_A3 + 4 * (w == 1 ? 256 + u : w == 2 ? 384 + r2 : 0);
    const uint32_t ot = CH_A3 + 4 * min(512, 256 + ((xt + 1 + ((xt >> 2) & 1)) >> 2));
    const int kap = (lane >> 4) * 8 + ((lane >> 1) & 7), gam = lane & 1, hh = w >> 1, wp = w & 1;
    const uint32_t oa = CH_U + wp * UPLANE + (127 - 4 * kap - 2 * gam - hh) * 16;
    const uint32_t ob = CH_U + (wp ^ 1) * UPLANE + (128 - wp - 4 * kap - 2 * gam - hh) * 16;
    const uint32_t od = CH_A3 + (4 * wp + hh) * 512 + (kap >> 3) * 256 + (kap & 7) * 16 + gam * 8;
    #pragma unroll 1
    for (int k = 0; k < 4; k++) {
        const int ch = 2 * (k & 1) + (k >> 1);
        const uint32_t cb = sb + OFF_CONV + ch * CH_STRIDE;
        {
            float kv[17];
            kv[0] = ldsf(cb + oa0); kv[16] = ldsf(cb + ot);
            #pragma unroll
            for (int s = 1; s < 16; s++) kv[s] = ldsf(cb + o0 + s * ost);
            const int tid = threadIdx.x & 127;
            const uint32_t ga = cb + CH_G + (tid >= 24) * 16 + min(tid, 47) * 8;
            const uint2 x0 = lds64(ga), x1 = lds64(ga + 8);
            if (u < 0 && w == 0) kv[0] = 0.f;
            if (xt > 1028) kv[16] = 0.f;
            uint32_t o[17];
            #pragma unroll
            for (int s = 0; s < 17; s++) o[s] = pack2(kv[s], __shfl_up_sync(0xffffffffu, kv[s], 1));
            if (lane > 0 && lane < 31) {
                const uint32_t ta = cb + CH_T + (lane - 1) * 280;
                #pragma unroll
                for (int s2 = 0; s2 < 8; s2++) sts64(ta + 64 * w + s2 * 8, o[2 * s2], o[2 * s2 + 1]);
                stsf(ta + 256 + 4 * w, UF(o[16]));
            }
            if (tid < 48) sts128(cb + CH_B3 + tid * 16, x0.x, x0.y, x1.x, x1.y);
        }
        mbar_wait(bars + 8 * B_U, 0);
        float p[24];
        const uint2 r0 = lds64(cb + ob + 24), r3 = lds64(cb + oa);
        uint32_t r[8];
        *(uint4*)&r[0] = lds128(cb + oa + 16); *(uint4*)&r[4] = lds128(cb + ob);
        p[0] = 0.f;
        p[1] = bf_lo(r0.x); p[2] = p[1] + bf_hi(r0.x); p[3] = p[2] + bf_lo(r0.y); p[4] = p[3] + bf_hi(r0.y);
        #pragma unroll
        for (int i = 0; i < 8; i++) { p[5 + 2 * i] = p[4 + 2 * i] + bf_lo(r[i]); p[6 + 2 * i] = p[5 + 2 * i] + bf_hi(r[i]); }
        p[21] = p[20] + bf_lo(r3.x); p[22] = p[21] + bf_hi(r3.x); p[23] = p[22] + bf_lo(r3.y);
        bar_sync(2);
        #pragma unroll
        for (int i = 0; i < 8; i += 4) {
            sts64(cb + od + i * 256, pack2(p[i + 9] - p[i], p[i + 10] - p[i + 1]), pack2(p[i + 11] - p[i + 2], p[i + 12] - p[i + 3]));
            sts64(cb + od + i * 256 + 128, pack2(p[i + 16] - p[i + 9], p[i + 17] - p[i + 10]), pack2(p[i + 18] - p[i + 11], p[i + 19] - p[i + 12]));
        }
        fence_async_smem();
        mbar_arrive(bars + 8 * (B_CONV + ch));
        if (k == 0) STAMP(17);
    }
    STAMP(21);
}

__global__ void __launch_bounds__(512, 1)
fused_kernel(const __grid_constant__ Params P, const __grid_constant__ Maps M) {
    extern __shared__ __align__(1024) uint8_t smem_raw[];
    const uint32_t sb = smem_u32(smem_raw);
    const uint32_t bars = sb + OFF_BAR;
    const int warp = __shfl_sync(0xffffffffu, threadIdx.x >> 5, 0);
    const int c = blockIdx.x, tg = c / 22, fb = c - 22 * tg;
    SsmRaw raw = {};
    if (warp >= 8 && warp < 12) {
        const int d = min(4 * c + warp - 8, DM - 1), o = d * 32 + (threadIdx.x & 31);
        raw.la = ldg64(P.logA, o); raw.ai = ldg64(P.Aim, o); raw.cr = ldg64(P.Cr, o); raw.ci = ldg64(P.Ci, o);
        raw.ldt = ldu16(P.logdt + d); raw.dsk = ldu16(P.Dskip + d);
    }
    if (elect_one()) {
        if (warp == 0) { STAMP(24); GSTAMP(22); }
        asm volatile("" :: "l"(((const uint64_t*)&P)[warp < 12 ? warp : 0]));
        if (warp < 12) asm volatile("prefetch.tensormap [%0];" :: "l"(&M.x[0] + warp) : "memory");
        #pragma unroll
        for (int k = 0; k < 4; k++) {
            const int i = 16 * k + ((warp + 4) & 15);
            const uint32_t cnt = i >= B_CONV ? 128 : ((0xf0ull >> i) & 1) ? 8 : ((0xff0000ull >> i) & 1) ? 2 : ((0x3e00ff00f000ull >> i) & 1) ? 4 : 1;
            asm volatile("mbarrier.init.shared::cta.b64 [%0], %1;" :: "r"(bars + 8 * i), "r"(cnt) : "memory");
        }
        asm volatile("fence.mbarrier_init.release.cluster; fence.proxy.async.shared::cta;" ::: "memory");
        if (warp == 13 || warp == 5 || warp == 6) { const uint32_t t0 = clock(); while ((uint32_t)clock() - t0 < DLY1) ; }
        if (warp == 12 || warp == 13) {
            const uint32_t s = warp - 12;
            mbar_expect(bars + 8 * (B_FULLW + s), 16384);
            tma2d(sb + OFF_W + s * 16384, &M.wg, 64 * fb, 64 * s, bars + 8 * (B_FULLW + s));
            tma2d(sb + OFF_W + s * 16384 + 8192, &M.wu, 64 * fb, 64 * s, bars + 8 * (B_FULLW + s));
            STAMP(31);
        } else if (warp >= 4 && warp < 7) {
            const uint32_t s = warp - 4, V = s >> 1;
            mbar_expect(bars + 8 * (B_FULLX + s), (168 + 8 * V) * 128);
            tma2d(sb + OFF_X + s * XBUF, &M.x[V], 64 * (s & 1), TOKG * tg + 168 * V, bars + 8 * (B_FULLX + s));
        }
        if (sb & 1023) __trap();
    }
    __syncthreads();
    if (warp < 8) {
        asm volatile("setmaxnreg.inc.sync.aligned.u32 208;");
        consumer(sb, warp, P, M);
    } else if (warp < 12) {
        asm volatile("setmaxnreg.dec.sync.aligned.u32 72;");
        STAMP(32);
        aux_role(sb, warp - 8, raw, P.x);
    } else {
        asm volatile("setmaxnreg.dec.sync.aligned.u32 24;");
        const int tau = c >> 2, dg = c & 3;
        if (elect_one()) {
            if (warp < 15) {
                if (warp == 12) {
                    #pragma unroll 1
                    for (int st = 2; st < 8; st++) {
                        const uint32_t s = st & 3, fb_ = bars + 8 * (B_FULLW + s);
                        if (st == 2) mbar_wait(bars + 8 * B_FULLW, 0);
                        mbar_wait(bars + 8 * (B_EMPTYW + s), (st >> 2) ^ 1);
                        mbar_expect(fb_, 16384);
                        tma2d(sb + OFF_W + s * 16384, &M.wg, 64 * fb, 64 * st, fb_);
                        tma2d(sb + OFF_W + s * 16384 + 8192, &M.wu, 64 * fb, 64 * st, fb_);
                    }
                } else {
                    const int V = warp - 13;
                    #pragma unroll 1
                    for (int st = 2 - V; st < 8; st++) {
                        const uint32_t s = 2 * V + (st & 1);
                        mbar_wait(bars + 8 * (B_EMPTYX + s), ((st >> 1) & 1) ^ 1);
                        mbar_expect(bars + 8 * (B_FULLX + s), (168 + 8 * V) * 128);
                        tma2d(sb + OFF_X + s * XBUF, &M.x[V], 64 * st, TOKG * tg + 168 * V, bars + 8 * (B_FULLX + s));
                    }
                }
                if (c < 128 && warp < 14) {
                    if (warp == 13) {
                        mbar_wait(bars + 8 * (B_STG + 1), 0);
                        #pragma unroll 1
                        for (int o = 8 * tau; o < 8 * tau + 8; o += 7) flag_wait(P.flags, F_H + 2 * (o / 43) + ((o % 43) >= 21), 22);
                        mbar_arrive(bars + 8 * B_HF);
                        STAMP(25);
                    }
                    #pragma unroll 1
                    for (int st = 0; st < 22; st += (st < 7 || (st == 7 && warp == 12)) ? 1 : 2) {
                        const int sd = st & 7;
                        const uint32_t fb_ = bars + 8 * (B_FULLD + sd);
                        if (st >= 8) mbar_wait(bars + 8 * (B_EMPTYD + sd), ((st >> 3) & 1) ^ 1);
                        else if (warp == 12 || st >= 6) mbar_wait(bars + 8 * (uint32_t)((0x373623070d060504ull >> (8 * st)) & 0xff), st < 5);
                        if (st >= 10 && st < 21) STAMP2(31 + st);
                        if (st >= 8 || warp == 13) {
                            mbar_expect(fb_, 8192);
                            asm volatile("cp.async.bulk.tensor.5d.shared::cluster.global.mbarrier::complete_tx::bytes [%0], [%1, {%3, %3, %3, %4, %5}], [%2];"
                                :: "r"(sb + h_slot(sd)), "l"(&M.hld), "r"(fb_), "r"(0), "r"(2 * tau), "r"(8 * st) : "memory");
                        }
                        if (st >= 8 || warp == 12) {
                            const uint32_t da = sb + wd_slot(sd);
                            mbar_expect(fb_, 16384);
                            tma2d(da, &M.wd, 128 * dg, 64 * st, fb_);
                            tma2d(da + 8192, &M.wd, 128 * dg + 64, 64 * st, fb_);
                        }
                    }
                } else if (c < 128) {
                    mbar_wait(bars + 8 * B_SST, 0);
                    flag_wait(P.flags, F_S + dg, 64);
                    STAMP(26);
                    mbar_wait(bars + 8 * B_CH0, 0);
                    mbar_expect(bars + 8 * B_XO, 32768);
                    tma2d(sb + OFF_CONV, &M.xo, 128 * dg, 64 * tau, bars + 8 * B_XO);
                    tma2d(sb + OFF_CONV + 8192, &M.xo, 128 * dg + 64, 64 * tau, bars + 8 * B_XO);
                    asm volatile("cp.async.bulk.tensor.5d.shared::cluster.global.mbarrier::complete_tx::bytes [%0], [%1, {%3, %3, %3, %4, %5}], [%2];"
                        :: "r"(sb + wd_slot(6)), "l"(&M.sld), "r"(bars + 8 * B_XO), "r"(0), "r"(8 * dg), "r"(2 * tau) : "memory");
                    mbar_wait(bars + 8 * B_HF, 0);
                    exit_count(P.flags);
                }
            } else {
                mbar_wait(bars + 8 * B_LN, 0);
                STAMP2(0);
                if (c < 128) {
                    #pragma unroll 1
                    for (int i = 0; i < 4; i++)
                        asm volatile("cp.async.bulk.tensor.2d.global.shared::cta.bulk_group [%0, {%2, %3}], [%1];"
                            :: "l"(&M.xt), "r"(sb + OFF_CONV + i * CH_STRIDE + CH_LNT), "r"((c & 1) * 1024 + (126 - (c & ~1)) * 8), "r"(128 * i) : "memory");
                    #pragma unroll 1
                    for (int i = 0; i < 2; i++) bulk_store(P.st + 16 * (c & ~1) + 8 * (c & 1) + 16 - 16 * i, sb + OFF_CSUM + 64 * i, 64);
                    asm volatile("cp.async.bulk.prefetch.L2.global [%0], %1;" :: "l"(P.Wd + c * (FF * DM / 128)), "r"(FF * DM / 64) : "memory");
                }
                asm volatile("cp.async.bulk.commit_group; cp.async.bulk.wait_group.read 0;" ::: "memory");
                mbar_arrive(bars + 8 * B_LNS);
                STAMP2(1);
                flag_signal(P.flags, F_A);
                STAMP2(2);
                flag_wait(P.flags, F_A, NCTA);
                STAMP(20);
                mbar_expect(bars + 8 * B_STATS, TOKG * 8);
                bulk_load(sb + OFF_ST, P.st + TOKG * tg, TOKG * 8, bars + 8 * B_STATS);
                if (c < 128) {
                    mbar_wait(bars + 8 * (B_K + 1), 0);
                    fence_async_smem();
                    mbar_expect(bars + 8 * B_U, 8 * 2048);
                    #pragma unroll 1
                    for (int i = 0; i < 8; i++)
                        bulk_load(sb + OFF_CONV + (i >> 1) * CH_STRIDE + CH_U + (i & 1) * UPLANE, P.xnT + 4 * c * 256 + i * 128, 2048, bars + 8 * B_U);
                } else exit_count(P.flags);
                #pragma unroll 1
                for (int V = 0; V < 2; V++) {
                    mbar_wait(bars + 8 * (B_EPI + V), 0);
                    STAMP2(3 + 2 * V);
                    asm volatile("cp.async.bulk.tensor.3d.global.shared::cta.bulk_group [%0, {%2, %3, %4}], [%1];"
                        :: "l"(&M.hst[V]), "r"(sb + OFF_X + V * 2 * XBUF), "r"(0), "r"(43 * tg + 21 * V), "r"(8 * fb) : "memory");
                    flag_signal(P.flags, F_H + 2 * tg + V);
                    mbar_arrive(bars + 8 * (B_STG + V));
                    STAMP2(4 + 2 * V);
                }
                if (c < 128) {
                    #pragma unroll 1
                    for (int V = 0; V < 2; V++) {
                        mbar_wait(bars + 8 * (B_SIG + V), 0);
                        STAMP2(7 + 2 * V);
                        bulk_store(P.S + (2 * c + V) * 1024, sb + OFF_CONV + V * OFF_SST, 8192);
                        flag_signal(P.flags, F_S + (c >> 5));
                        STAMP2(8 + 2 * V);
                    }
                    mbar_arrive(bars + 8 * B_SST);
                }
            }
        }
    }
    asm volatile("nanosleep.u32 0;");
}

typedef CUresult (*EncodeFn)(CUtensorMap*, CUtensorMapDataType, cuuint32_t, void*, const cuuint64_t*, const cuuint64_t*, const cuuint32_t*,
                             const cuuint32_t*, CUtensorMapInterleave, CUtensorMapSwizzle, CUtensorMapL2promotion, CUtensorMapFloatOOBfill);

void make_map(EncodeFn enc, CUtensorMap* m, const void* ptr, int rank, const cuuint64_t* dims, const cuuint64_t* strides, const cuuint32_t* box, bool swz, bool wide = false) {
    const cuuint32_t es[5] = {1, 1, 1, 1, 1};
    enc(m, CU_TENSOR_MAP_DATA_TYPE_BFLOAT16, rank, (void*)ptr, dims, strides, box, es, CU_TENSOR_MAP_INTERLEAVE_NONE,
        swz ? CU_TENSOR_MAP_SWIZZLE_128B : CU_TENSOR_MAP_SWIZZLE_NONE, wide ? CU_TENSOR_MAP_L2_PROMOTION_L2_256B : CU_TENSOR_MAP_L2_PROMOTION_L2_128B, CU_TENSOR_MAP_FLOAT_OOB_FILL_NONE);
}
void make_map2(EncodeFn enc, CUtensorMap* m, const void* ptr, cuuint64_t inner, cuuint64_t outer, cuuint32_t rows) {
    const cuuint64_t dims[2] = {inner, outer}, strides[1] = {inner * 2};
    const cuuint32_t box[2] = {64, rows};
    make_map(enc, m, ptr, 2, dims, strides, box, true, rows > 64);
}

}

extern "C" void kernel_launch(void* const* d_in, const int* in_sizes, int n_in, void* d_out, int out_size) {
    (void)in_sizes; (void)n_in; (void)out_size;
    static EncodeFn enc = nullptr;
    static void *hptr, *p_xnT, *p_st, *p_S, *p_flags;
    if (!enc) {
        cudaDriverEntryPointQueryResult qr;
        cudaGetDriverEntryPoint("cuTensorMapEncodeTiled", (void**)&enc, cudaEnableDefault, &qr);
        cudaFuncSetAttribute(fused_kernel, cudaFuncAttributeMaxDynamicSharedMemorySize, SMEM_BYTES);
        cudaGetSymbolAddress(&hptr, g_H); cudaGetSymbolAddress(&p_xnT, g_xnT); cudaGetSymbolAddress(&p_st, g_st);
        cudaGetSymbolAddress(&p_S, g_S); cudaGetSymbolAddress(&p_flags, g_flags);
    }
    Params P;
    P.x = (const __nv_bfloat16*)d_in[0]; P.logA = (const __nv_bfloat16*)d_in[1]; P.Aim = (const __nv_bfloat16*)d_in[2];
    P.Cr = (const __nv_bfloat16*)d_in[3]; P.Ci = (const __nv_bfloat16*)d_in[4]; P.logdt = (const __nv_bfloat16*)d_in[5];
    P.Dskip = (const __nv_bfloat16*)d_in[6];
    P.Wd = (const __nv_bfloat16*)d_in[10]; P.xnT = (uint4*)p_xnT; P.st = (float2*)p_st; P.S = (uint2*)p_S; P.flags = (unsigned*)p_flags;
    Maps M;
    make_map2(enc, &M.x[0], d_in[0], DM, SEQ, 168); make_map2(enc, &M.x[1], d_in[0], DM, SEQ, 176);
    make_map2(enc, &M.xo, d_in[0], DM, SEQ, 64);    make_map2(enc, &M.out, d_out, DM, SEQ, 64);
    make_map2(enc, &M.wg, d_in[8], FF, DM, 64);     make_map2(enc, &M.wu, d_in[9], FF, DM, 64);
    make_map2(enc, &M.wd, d_in[10], DM, FF, 64);
    for (int v = 0; v < 2; v++) {
        const cuuint64_t dims[3] = {64, 256, 172}, strides[2] = {128, 32768};
        const cuuint32_t box[3] = {64, (cuuint32_t)(21 + v), 8};
        make_map(enc, &M.hst[v], hptr, 3, dims, strides, box, false);
    }
    {
        const cuuint64_t dims[2] = {2048, 512}, strides[1] = {4096};
        const cuuint32_t box[2] = {16, 128};
        make_map(enc, &M.xt, p_xnT, 2, dims, strides, box, false);
    }
    {
        const cuuint64_t dims[5] = {64, 2, 4, 32, 64}, strides[4] = {4 * 8192, 8192, 8 * 8192, 128};
        const cuuint32_t box[5] = {64, 2, 4, 8, 2};
        make_map(enc, &M.sld, p_S, 5, dims, strides, box, true);
    }
    {
        const cuuint64_t dims[5] = {64, 2, 2, 64, 172}, strides[4] = {256, 128, 512, 32768};
        const cuuint32_t box[5] = {64, 2, 2, 2, 8};
        make_map(enc, &M.hld, hptr, 5, dims, strides, box, false);
    }
    fused_kernel<<<NCTA, 512, SMEM_BYTES>>>(P, M);
}
```

```cpp
#include <cuda_runtime.h>
#include <cuda_bf16.h>
#include <cuda.h>
#include <stdint.h>

#define PROF 0

namespace {

constexpr int SEQ = 2048, DM = 512, FF = 1376;
constexpr int NCTA = 132;
#define HOLD0 5
#define LNCK 1
#define HOLD1 7
#define LAG 2
#define DLY1 300
#define DLY2 300
constexpr int RUNROLL = 8;
constexpr int TOKG = 344;

constexpr uint32_t OFF_W = 0;
constexpr uint32_t XBUF = 22528;
constexpr uint32_t OFF_X = 65536;
constexpr uint32_t OFF_CONV = 155648;
constexpr uint32_t CH_STRIDE = 17536;
constexpr uint32_t CH_T = 0;
constexpr uint32_t CH_A3 = 8448;
constexpr uint32_t CH_B3 = 12544;
constexpr uint32_t CH_U = 13312;
constexpr uint32_t CH_G = CH_A3 + 2064;
constexpr uint32_t UPLANE = 2112;
constexpr uint32_t CH_LN = 8064, CH_LNT = 13440;
constexpr uint32_t OFF_SST = 60416;
constexpr uint32_t OFF_ST = 225792;
constexpr uint32_t OFF_CSUM = 228544;
constexpr uint32_t OFF_BAR = 229056;
constexpr uint32_t SMEM_BYTES = 229568;

enum {
    B_FULLW = 0, B_EMPTYW = 4, B_FULLX = 8, B_EMPTYX = 12, B_FULLD = 16, B_EMPTYD = 24,
    B_U = 32, B_XO = 33, B_S = 34, B_STG = 35, B_HF = 37, B_STATS = 38, B_LNS = 39, B_SST = 40,
    B_LNX = 41, B_GO = 42, B_CH0 = 43, B_K = 44,
    B_CONV = 46, B_LN = 50, B_CS = 51, B_EPI = 52, B_SIG = 54,
    B_COUNT = 56
};
enum { F_A = 0, F_H = 1, F_S = 13, F_EXIT = 17, F_COUNT = 18 };

__device__ uint4 g_xnT[DM * 256];
__device__ float2 g_st[6 * TOKG];
__device__ uint4 g_H[172 * 256 * 8];
__device__ uint2 g_S[256 * 1024];
__device__ unsigned g_flags[F_COUNT * 32];
#define STAMP(i) do {} while (0)
#define GSTAMP(i) do {} while (0)
#define STAMP2(i) do {} while (0)

__device__ __forceinline__ uint32_t smem_u32(const void* p) { return (uint32_t)__cvta_generic_to_shared(p); }
__device__ __forceinline__ void mbar_expect(uint32_t bar, uint32_t bytes) { asm volatile("mbarrier.arrive.expect_tx.shared::cta.b64 _, [%0], %1;" :: "r"(bar), "r"(bytes) : "memory"); }
__device__ __forceinline__ void mbar_arrive(uint32_t bar) { asm volatile("mbarrier.arrive.shared::cta.b64 _, [%0];" :: "r"(bar) : "memory"); }
__device__ __forceinline__ void mbar_wait(uint32_t bar, uint32_t parity) {
    asm volatile("{.reg .pred p; .reg .u32 n; mov.u32 n, 0x20000;\n"
                 "LW: mbarrier.try_wait.parity.shared::cta.b64 p, [%0], %1;\n"
                 "sub.u32 n, n, 1; setp.eq.or.u32 p, n, 0, p; @!p bra LW;}" :: "r"(bar), "r"(parity) : "memory");
}
__device__ __forceinline__ bool elect_one() { uint32_t p; asm volatile("{.reg .pred P; elect.sync _|P, 0xffffffff; selp.u32 %0, 1, 0, P;}" : "=r"(p)); return p; }
__device__ __forceinline__ void tma2d(uint32_t dst, const CUtensorMap* m, int c0, int c1, uint32_t bar) {
    asm volatile("cp.async.bulk.tensor.2d.shared::cluster.global.mbarrier::complete_tx::bytes [%0], [%1, {%3, %4}], [%2];"
        :: "r"(dst), "l"(m), "r"(bar), "r"(c0), "r"(c1) : "memory");
}
__device__ __forceinline__ void bulk_load(uint32_t dst, const void* src, uint32_t bytes, uint32_t bar) {
    asm volatile("cp.async.bulk.shared::cluster.global.mbarrier::complete_tx::bytes [%0], [%1], %2, [%3];" :: "r"(dst), "l"(src), "r"(bytes), "r"(bar) : "memory");
}
__device__ __forceinline__ void bulk_store(void* dst, uint32_t src, uint32_t bytes) {
    asm volatile("cp.async.bulk.global.shared::cta.bulk_group [%0], [%1], %2;" :: "l"(dst), "r"(src), "r"(bytes) : "memory");
}
__device__ __forceinline__ void fence_async_smem() { asm volatile("fence.proxy.async.shared::cta;" ::: "memory"); }
__device__ __forceinline__ void flag_wait(unsigned* g_flags, int f, unsigned target) {
    asm volatile("{.reg .pred p; .reg .u32 n, v; mov.u32 n, 0x40000;\n"
                 "LF: ld.acquire.gpu.global.u32 v, [%0]; setp.ge.u32 p, v, %1; @p bra LD;\n"
                 "sub.u32 n, n, 1; setp.ne.u32 p, n, 0; @p bra LF; trap;\nLD: }"
                 :: "l"(g_flags + f * 32), "r"(target) : "memory");
}
__device__ __forceinline__ void flag_signal(unsigned* g_flags, int f) {
    asm volatile("cp.async.bulk.commit_group; cp.async.bulk.wait_group 0; red.relaxed.gpu.global.add.u32 [%0], 1;" :: "l"(g_flags + f * 32) : "memory");
}
__device__ __forceinline__ void exit_count(unsigned* g_flags) {
    if (atomicAdd(g_flags + F_EXIT * 32, 1u) == NCTA - 1) {
        #pragma unroll 1
        for (int i = 0; i < F_COUNT; i++) g_flags[i * 32] = 0;
    }
}
__device__ __forceinline__ void bar_sync(int id) { asm volatile("bar.sync %0, 128;" :: "r"(id) : "memory"); }
__device__ __forceinline__ uint64_t mkdesc(uint32_t addr, uint32_t lbo, uint32_t sbo, uint32_t swz) {
    return (uint64_t)((addr >> 4) | ((lbo >> 4) << 16)) | ((uint64_t)((sbo >> 4) | (swz << 30)) << 32);
}
#define WG_FENCE() asm volatile("wgmma.fence.sync.aligned;" ::: "memory")
#define WG_COMMIT() asm volatile("wgmma.commit_group.sync.aligned;" ::: "memory")
#define WG_WAIT(n) asm volatile("wgmma.wait_group.sync.aligned " #n ";" ::: "memory")
template <int N> __device__ __forceinline__ void fence_acc(float (&d)[N]) {
    #pragma unroll
    for (int i = 0; i < N; i++) asm volatile("" : "+f"(d[i]) :: "memory");
}
template <int N> __device__ __forceinline__ void define_acc(float (&d)[N]) {
    #pragma unroll
    for (int i = 0; i < N; i++) asm volatile("" : "=f"(d[i]));
}
__device__ __forceinline__ uint32_t pack2(float lo, float hi) { uint32_t r; asm("cvt.rn.bf16x2.f32 %0, %1, %2;" : "=r"(r) : "f"(hi), "f"(lo)); return r; }
__device__ __forceinline__ float bf_lo(uint32_t v) { return __uint_as_float(v << 16); }
__device__ __forceinline__ float bf_hi(uint32_t v) { return __uint_as_float(v & 0xffff0000u); }
__device__ __forceinline__ float bf_round(float v) { return bf_hi(pack2(0.f, v)); }
__device__ __forceinline__ float tanh_fast(float v) { float r; asm("tanh.approx.f32 %0, %1;" : "=f"(r) : "f"(v)); return r; }
__device__ __forceinline__ float ex2(float v) { float r; asm("ex2.approx.ftz.f32 %0, %1;" : "=f"(r) : "f"(v)); return r; }
__device__ __forceinline__ uint4 lds128(uint32_t a) { uint4 v; asm volatile("ld.shared.v4.b32 {%0,%1,%2,%3}, [%4];" : "=r"(v.x), "=r"(v.y), "=r"(v.z), "=r"(v.w) : "r"(a)); return v; }
__device__ __forceinline__ uint2 lds64(uint32_t a) { uint2 v; asm volatile("ld.shared.v2.b32 {%0,%1}, [%2];" : "=r"(v.x), "=r"(v.y) : "r"(a)); return v; }
__device__ __forceinline__ float ldsf(uint32_t a) { float v; asm volatile("ld.shared.f32 %0, [%1];" : "=f"(v) : "r"(a)); return v; }
__device__ __forceinline__ void sts128(uint32_t a, uint32_t x, uint32_t y, uint32_t z, uint32_t w) { asm volatile("st.shared.v4.b32 [%0], {%1,%2,%3,%4};" :: "r"(a), "r"(x), "r"(y), "r"(z), "r"(w) : "memory"); }
__device__ __forceinline__ void sts64(uint32_t a, uint32_t x, uint32_t y) { asm volatile("st.shared.v2.b32 [%0], {%1,%2};" :: "r"(a), "r"(x), "r"(y) : "memory"); }
__device__ __forceinline__ void stsf(uint32_t a, float x) { asm volatile("st.shared.f32 [%0], %1;" :: "r"(a), "f"(x) : "memory"); }
__device__ __forceinline__ void sts16(uint32_t a, uint32_t x) { asm volatile("st.shared.b16 [%0], %1;" :: "r"(a), "h"((unsigned short)x) : "memory"); }
__device__ __forceinline__ void stsm4(uint32_t a, uint32_t r0, uint32_t r1, uint32_t r2, uint32_t r3) {
    asm volatile("stmatrix.sync.aligned.m8n8.x4.shared.b16 [%0], {%1,%2,%3,%4};" :: "r"(a), "r"(r0), "r"(r1), "r"(r2), "r"(r3) : "memory");
}
__device__ __forceinline__ void ldsm4(uint32_t (&r)[4], uint32_t a) {
    asm volatile("ldmatrix.sync.aligned.m8n8.x4.shared.b16 {%0,%1,%2,%3}, [%4];" : "=r"(r[0]), "=r"(r[1]), "=r"(r[2]), "=r"(r[3]) : "r"(a) : "memory");
}
#define FU(x) __float_as_uint(x)
#define UF(x) __uint_as_float(x)
__device__ __forceinline__ uint32_t wd_slot(int s) { return (uint32_t)((0xbba8403056201000ull >> (8 * s)) & 0xff) << 10; }
__device__ __forceinline__ uint32_t h_slot(int s) { return (uint32_t)((0xcba0908880787068ull >> (8 * s)) & 0xff) << 10; }

template<int N> __device__ __forceinline__ void wg_rs(float (&d)[64], uint32_t a0, uint32_t a1, uint32_t a2, uint32_t a3, uint64_t db);
template<> __device__ __forceinline__ void wg_rs<128>(float (&d)[64], uint32_t a0, uint32_t a1, uint32_t a2, uint32_t a3, uint64_t db) {
  asm volatile("{.reg .pred p; setp.ne.b32 p, 1, 0; wgmma.mma_async.sync.aligned.m64n128k16.f32.bf16.bf16 {%0,%1,%2,%3,%4,%5,%6,%7,%8,%9,%10,%11,%12,%13,%14,%15,%16,%17,%18,%19,%20,%21,%22,%23,%24,%25,%26,%27,%28,%29,%30,%31,%32,%33,%34,%35,%36,%37,%38,%39,%40,%41,%42,%43,%44,%45,%46,%47,%48,%49,%50,%51,%52,%53,%54,%55,%56,%57,%58,%59,%60,%61,%62,%63}, {%64,%65,%66,%67}, %68, p, 1, 1, 0;}"
    : "+f"(d[0]),"+f"(d[1]),"+f"(d[2]),"+f"(d[3]),"+f"(d[4]),"+f"(d[5]),"+f"(d[6]),"+f"(d[7]),"+f"(d[8]),"+f"(d[9]),"+f"(d[10]),"+f"(d[11]),"+f"(d[12]),"+f"(d[13]),"+f"(d[14]),"+f"(d[15]),"+f"(d[16]),"+f"(d[17]),"+f"(d[18]),"+f"(d[19]),"+f"(d[20]),"+f"(d[21]),"+f"(d[22]),"+f"(d[23]),"+f"(d[24]),"+f"(d[25]),"+f"(d[26]),"+f"(d[27]),"+f"(d[28]),"+f"(d[29]),"+f"(d[30]),"+f"(d[31]),"+f"(d[32]),"+f"(d[33]),"+f"(d[34]),"+f"(d[35]),"+f"(d[36]),"+f"(d[37]),"+f"(d[38]),"+f"(d[39]),"+f"(d[40]),"+f"(d[41]),"+f"(d[42]),"+f"(d[43]),"+f"(d[44]),"+f"(d[45]),"+f"(d[46]),"+f"(d[47]),"+f"(d[48]),"+f"(d[49]),"+f"(d[50]),"+f"(d[51]),"+f"(d[52]),"+f"(d[53]),"+f"(d[54]),"+f"(d[55]),"+f"(d[56]),"+f"(d[57]),"+f"(d[58]),"+f"(d[59]),"+f"(d[60]),"+f"(d[61]),"+f"(d[62]),"+f"(d[63]) : "r"(a0), "r"(a1), "r"(a2), "r"(a3), "l"(db));
}
template<> __device__ __forceinline__ void wg_rs<120>(float (&d)[64], uint32_t a0, uint32_t a1, uint32_t a2, uint32_t a3, uint64_t db) {
  asm volatile("{.reg .pred p; setp.ne.b32 p, 1, 0; wgmma.mma_async.sync.aligned.m64n120k16.f32.bf16.bf16 {%0,%1,%2,%3,%4,%5,%6,%7,%8,%9,%10,%11,%12,%13,%14,%15,%16,%17,%18,%19,%20,%21,%22,%23,%24,%25,%26,%27,%28,%29,%30,%31,%32,%33,%34,%35,%36,%37,%38,%39,%40,%41,%42,%43,%44,%45,%46,%47,%48,%49,%50,%51,%52,%53,%54,%55,%56,%57,%58,%59}, {%60,%61,%62,%63}, %64, p, 1, 1, 0;}"
    : "+f"(d[0]),"+f"(d[1]),"+f"(d[2]),"+f"(d[3]),"+f"(d[4]),"+f"(d[5]),"+f"(d[6]),"+f"(d[7]),"+f"(d[8]),"+f"(d[9]),"+f"(d[10]),"+f"(d[11]),"+f"(d[12]),"+f"(d[13]),"+f"(d[14]),"+f"(d[15]),"+f"(d[16]),"+f"(d[17]),"+f"(d[18]),"+f"(d[19]),"+f"(d[20]),"+f"(d[21]),"+f"(d[22]),"+f"(d[23]),"+f"(d[24]),"+f"(d[25]),"+f"(d[26]),"+f"(d[27]),"+f"(d[28]),"+f"(d[29]),"+f"(d[30]),"+f"(d[31]),"+f"(d[32]),"+f"(d[33]),"+f"(d[34]),"+f"(d[35]),"+f"(d[36]),"+f"(d[37]),"+f"(d[38]),"+f"(d[39]),"+f"(d[40]),"+f"(d[41]),"+f"(d[42]),"+f"(d[43]),"+f"(d[44]),"+f"(d[45]),"+f"(d[46]),"+f"(d[47]),"+f"(d[48]),"+f"(d[49]),"+f"(d[50]),"+f"(d[51]),"+f"(d[52]),"+f"(d[53]),"+f"(d[54]),"+f"(d[55]),"+f"(d[56]),"+f"(d[57]),"+f"(d[58]),"+f"(d[59]) : "r"(a0), "r"(a1), "r"(a2), "r"(a3), "l"(db));
}
template<> __device__ __forceinline__ void wg_rs<112>(float (&d)[64], uint32_t a0, uint32_t a1, uint32_t a2, uint32_t a3, uint64_t db) {
  asm volatile("{.reg .pred p; setp.ne.b32 p, 1, 0; wgmma.mma_async.sync.aligned.m64n112k16.f32.bf16.bf16 {%0,%1,%2,%3,%4,%5,%6,%7,%8,%9,%10,%11,%12,%13,%14,%15,%16,%17,%18,%19,%20,%21,%22,%23,%24,%25,%26,%27,%28,%29,%30,%31,%32,%33,%34,%35,%36,%37,%38,%39,%40,%41,%42,%43,%44,%45,%46,%47,%48,%49,%50,%51,%52,%53,%54,%55}, {%56,%57,%58,%59}, %60, p, 1, 1, 0;}"
    : "+f"(d[0]),"+f"(d[1]),"+f"(d[2]),"+f"(d[3]),"+f"(d[4]),"+f"(d[5]),"+f"(d[6]),"+f"(d[7]),"+f"(d[8]),"+f"(d[9]),"+f"(d[10]),"+f"(d[11]),"+f"(d[12]),"+f"(d[13]),"+f"(d[14]),"+f"(d[15]),"+f"(d[16]),"+f"(d[17]),"+f"(d[18]),"+f"(d[19]),"+f"(d[20]),"+f"(d[21]),"+f"(d[22]),"+f"(d[23]),"+f"(d[24]),"+f"(d[25]),"+f"(d[26]),"+f"(d[27]),"+f"(d[28]),"+f"(d[29]),"+f"(d[30]),"+f"(d[31]),"+f"(d[32]),"+f"(d[33]),"+f"(d[34]),"+f"(d[35]),"+f"(d[36]),"+f"(d[37]),"+f"(d[38]),"+f"(d[39]),"+f"(d[40]),"+f"(d[41]),"+f"(d[42]),"+f"(d[43]),"+f"(d[44]),"+f"(d[45]),"+f"(d[46]),"+f"(d[47]),"+f"(d[48]),"+f"(d[49]),"+f"(d[50]),"+f"(d[51]),"+f"(d[52]),"+f"(d[53]),"+f"(d[54]),"+f"(d[55]) : "r"(a0), "r"(a1), "r"(a2), "r"(a3), "l"(db));
}
template<> __device__ __forceinline__ void wg_rs<104>(float (&d)[64], uint32_t a0, uint32_t a1, uint32_t a2, uint32_t a3, uint64_t db) {
  asm volatile("{.reg .pred p; setp.ne.b32 p, 1, 0; wgmma.mma_async.sync.aligned.m64n104k16.f32.bf16.bf16 {%0,%1,%2,%3,%4,%5,%6,%7,%8,%9,%10,%11,%12,%13,%14,%15,%16,%17,%18,%19,%20,%21,%22,%23,%24,%25,%26,%27,%28,%29,%30,%31,%32,%33,%34,%35,%36,%37,%38,%39,%40,%41,%42,%43,%44,%45,%46,%47,%48,%49,%50,%51}, {%52,%53,%54,%55}, %56, p, 1, 1, 0;}"
    : "+f"(d[0]),"+f"(d[1]),"+f"(d[2]),"+f"(d[3]),"+f"(d[4]),"+f"(d[5]),"+f"(d[6]),"+f"(d[7]),"+f"(d[8]),"+f"(d[9]),"+f"(d[10]),"+f"(d[11]),"+f"(d[12]),"+f"(d[13]),"+f"(d[14]),"+f"(d[15]),"+f"(d[16]),"+f"(d[17]),"+f"(d[18]),"+f"(d[19]),"+f"(d[20]),"+f"(d[21]),"+f"(d[22]),"+f"(d[23]),"+f"(d[24]),"+f"(d[25]),"+f"(d[26]),"+f"(d[27]),"+f"(d[28]),"+f"(d[29]),"+f"(d[30]),"+f"(d[31]),"+f"(d[32]),"+f"(d[33]),"+f"(d[34]),"+f"(d[35]),"+f"(d[36]),"+f"(d[37]),"+f"(d[38]),"+f"(d[39]),"+f"(d[40]),"+f"(d[41]),"+f"(d[42]),"+f"(d[43]),"+f"(d[44]),"+f"(d[45]),"+f"(d[46]),"+f"(d[47]),"+f"(d[48]),"+f"(d[49]),"+f"(d[50]),"+f"(d[51]) : "r"(a0), "r"(a1), "r"(a2), "r"(a3), "l"(db));
}
template<> __device__ __forceinline__ void wg_rs<96>(float (&d)[64], uint32_t a0, uint32_t a1, uint32_t a2, uint32_t a3, uint64_t db) {
  asm volatile("{.reg .pred p; setp.ne.b32 p, 1, 0; wgmma.mma_async.sync.aligned.m64n96k16.f32.bf16.bf16 {%0,%1,%2,%3,%4,%5,%6,%7,%8,%9,%10,%11,%12,%13,%14,%15,%16,%17,%18,%19,%20,%21,%22,%23,%24,%25,%26,%27,%28,%29,%30,%31,%32,%33,%34,%35,%36,%37,%38,%39,%40,%41,%42,%43,%44,%45,%46,%47}, {%48,%49,%50,%51}, %52, p, 1, 1, 0;}"
    : "+f"(d[0]),"+f"(d[1]),"+f"(d[2]),"+f"(d[3]),"+f"(d[4]),"+f"(d[5]),"+f"(d[6]),"+f"(d[7]),"+f"(d[8]),"+f"(d[9]),"+f"(d[10]),"+f"(d[11]),"+f"(d[12]),"+f"(d[13]),"+f"(d[14]),"+f"(d[15]),"+f"(d[16]),"+f"(d[17]),"+f"(d[18]),"+f"(d[19]),"+f"(d[20]),"+f"(d[21]),"+f"(d[22]),"+f"(d[23]),"+f"(d[24]),"+f"(d[25]),"+f"(d[26]),"+f"(d[27]),"+f"(d[28]),"+f"(d[29]),"+f"(d[30]),"+f"(d[31]),"+f"(d[32]),"+f"(d[33]),"+f"(d[34]),"+f"(d[35]),"+f"(d[36]),"+f"(d[37]),"+f"(d[38]),"+f"(d[39]),"+f"(d[40]),"+f"(d[41]),"+f"(d[42]),"+f"(d[43]),"+f"(d[44]),"+f"(d[45]),"+f"(d[46]),"+f"(d[47]) : "r"(a0), "r"(a1), "r"(a2), "r"(a3), "l"(db));
}
template<> __device__ __forceinline__ void wg_rs<88>(float (&d)[64], uint32_t a0, uint32_t a1, uint32_t a2, uint32_t a3, uint64_t db) {
  asm volatile("{.reg .pred p; setp.ne.b32 p, 1, 0; wgmma.mma_async.sync.aligned.m64n88k16.f32.bf16.bf16 {%0,%1,%2,%3,%4,%5,%6,%7,%8,%9,%10,%11,%12,%13,%14,%15,%16,%17,%18,%19,%20,%21,%22,%23,%24,%25,%26,%27,%28,%29,%30,%31,%32,%33,%34,%35,%36,%37,%38,%39,%40,%41,%42,%43}, {%44,%45,%46,%47}, %48, p, 1, 1, 0;}"
    : "+f"(d[0]),"+f"(d[1]),"+f"(d[2]),"+f"(d[3]),"+f"(d[4]),"+f"(d[5]),"+f"(d[6]),"+f"(d[7]),"+f"(d[8]),"+f"(d[9]),"+f"(d[10]),"+f"(d[11]),"+f"(d[12]),"+f"(d[13]),"+f"(d[14]),"+f"(d[15]),"+f"(d[16]),"+f"(d[17]),"+f"(d[18]),"+f"(d[19]),"+f"(d[20]),"+f"(d[21]),"+f"(d[22]),"+f"(d[23]),"+f"(d[24]),"+f"(d[25]),"+f"(d[26]),"+f"(d[27]),"+f"(d[28]),"+f"(d[29]),"+f"(d[30]),"+f"(d[31]),"+f"(d[32]),"+f"(d[33]),"+f"(d[34]),"+f"(d[35]),"+f"(d[36]),"+f"(d[37]),"+f"(d[38]),"+f"(d[39]),"+f"(d[40]),"+f"(d[41]),"+f"(d[42]),"+f"(d[43]) : "r"(a0), "r"(a1), "r"(a2), "r"(a3), "l"(db));
}
template<> __device__ __forceinline__ void wg_rs<80>(float (&d)[64], uint32_t a0, uint32_t a1, uint32_t a2, uint32_t a3, uint64_t db) {
  asm volatile("{.reg .pred p; setp.ne.b32 p, 1, 0; wgmma.mma_async.sync.aligned.m64n80k16.f32.bf16.bf16 {%0,%1,%2,%3,%4,%5,%6,%7,%8,%9,%10,%11,%12,%13,%14,%15,%16,%17,%18,%19,%20,%21,%22,%23,%24,%25,%26,%27,%28,%29,%30,%31,%32,%33,%34,%35,%36,%37,%38,%39}, {%40,%41,%42,%43}, %44, p, 1, 1, 0;}"
    : "+f"(d[0]),"+f"(d[1]),"+f"(d[2]),"+f"(d[3]),"+f"(d[4]),"+f"(d[5]),"+f"(d[6]),"+f"(d[7]),"+f"(d[8]),"+f"(d[9]),"+f"(d[10]),"+f"(d[11]),"+f"(d[12]),"+f"(d[13]),"+f"(d[14]),"+f"(d[15]),"+f"(d[16]),"+f"(d[17]),"+f"(d[18]),"+f"(d[19]),"+f"(d[20]),"+f"(d[21]),"+f"(d[22]),"+f"(d[23]),"+f"(d[24]),"+f"(d[25]),"+f"(d[26]),"+f"(d[27]),"+f"(d[28]),"+f"(d[29]),"+f"(d[30]),"+f"(d[31]),"+f"(d[32]),"+f"(d[33]),"+f"(d[34]),"+f"(d[35]),"+f"(d[36]),"+f"(d[37]),"+f"(d[38]),"+f"(d[39]) : "r"(a0), "r"(a1), "r"(a2), "r"(a3), "l"(db));
}
template<> __device__ __forceinline__ void wg_rs<72>(float (&d)[64], uint32_t a0, uint32_t a1, uint32_t a2, uint32_t a3, uint64_t db) {
  asm volatile("{.reg .pred p; setp.ne.b32 p, 1, 0; wgmma.mma_async.sync.aligned.m64n72k16.f32.bf16.bf16 {%0,%1,%2,%3,%4,%5,%6,%7,%8,%9,%10,%11,%12,%13,%14,%15,%16,%17,%18,%19,%20,%21,%22,%23,%24,%25,%26,%27,%28,%29,%30,%31,%32,%33,%34,%35}, {%36,%37,%38,%39}, %40, p, 1, 1, 0;}"
    : "+f"(d[0]),"+f"(d[1]),"+f"(d[2]),"+f"(d[3]),"+f"(d[4]),"+f"(d[5]),"+f"(d[6]),"+f"(d[7]),"+f"(d[8]),"+f"(d[9]),"+f"(d[10]),"+f"(d[11]),"+f"(d[12]),"+f"(d[13]),"+f"(d[14]),"+f"(d[15]),"+f"(d[16]),"+f"(d[17]),"+f"(d[18]),"+f"(d[19]),"+f"(d[20]),"+f"(d[21]),"+f"(d[22]),"+f"(d[23]),"+f"(d[24]),"+f"(d[25]),"+f"(d[26]),"+f"(d[27]),"+f"(d[28]),"+f"(d[29]),"+f"(d[30]),"+f"(d[31]),"+f"(d[32]),"+f"(d[33]),"+f"(d[34]),"+f"(d[35]) : "r"(a0), "r"(a1), "r"(a2), "r"(a3), "l"(db));
}
template<> __device__ __forceinline__ void wg_rs<64>(float (&d)[64], uint32_t a0, uint32_t a1, uint32_t a2, uint32_t a3, uint64_t db) {
  asm volatile("{.reg .pred p; setp.ne.b32 p, 1, 0; wgmma.mma_async.sync.aligned.m64n64k16.f32.bf16.bf16 {%0,%1,%2,%3,%4,%5,%6,%7,%8,%9,%10,%11,%12,%13,%14,%15,%16,%17,%18,%19,%20,%21,%22,%23,%24,%25,%26,%27,%28,%29,%30,%31}, {%32,%33,%34,%35}, %36, p, 1, 1, 0;}"
    : "+f"(d[0]),"+f"(d[1]),"+f"(d[2]),"+f"(d[3]),"+f"(d[4]),"+f"(d[5]),"+f"(d[6]),"+f"(d[7]),"+f"(d[8]),"+f"(d[9]),"+f"(d[10]),"+f"(d[11]),"+f"(d[12]),"+f"(d[13]),"+f"(d[14]),"+f"(d[15]),"+f"(d[16]),"+f"(d[17]),"+f"(d[18]),"+f"(d[19]),"+f"(d[20]),"+f"(d[21]),"+f"(d[22]),"+f"(d[23]),"+f"(d[24]),"+f"(d[25]),"+f"(d[26]),"+f"(d[27]),"+f"(d[28]),"+f"(d[29]),"+f"(d[30]),"+f"(d[31]) : "r"(a0), "r"(a1), "r"(a2), "r"(a3), "l"(db));
}
__device__ __forceinline__ void wg_rs_first(float (&d)[64], uint32_t a0, uint32_t a1, uint32_t a2, uint32_t a3, uint64_t db) {
  asm volatile("{.reg .pred p; setp.ne.b32 p, 0, 0; wgmma.mma_async.sync.aligned.m64n128k16.f32.bf16.bf16 {%0,%1,%2,%3,%4,%5,%6,%7,%8,%9,%10,%11,%12,%13,%14,%15,%16,%17,%18,%19,%20,%21,%22,%23,%24,%25,%26,%27,%28,%29,%30,%31,%32,%33,%34,%35,%36,%37,%38,%39,%40,%41,%42,%43,%44,%45,%46,%47,%48,%49,%50,%51,%52,%53,%54,%55,%56,%57,%58,%59,%60,%61,%62,%63}, {%64,%65,%66,%67}, %68, p, 1, 1, 0;}"
    : "=f"(d[0]),"=f"(d[1]),"=f"(d[2]),"=f"(d[3]),"=f"(d[4]),"=f"(d[5]),"=f"(d[6]),"=f"(d[7]),"=f"(d[8]),"=f"(d[9]),"=f"(d[10]),"=f"(d[11]),"=f"(d[12]),"=f"(d[13]),"=f"(d[14]),"=f"(d[15]),"=f"(d[16]),"=f"(d[17]),"=f"(d[18]),"=f"(d[19]),"=f"(d[20]),"=f"(d[21]),"=f"(d[22]),"=f"(d[23]),"=f"(d[24]),"=f"(d[25]),"=f"(d[26]),"=f"(d[27]),"=f"(d[28]),"=f"(d[29]),"=f"(d[30]),"=f"(d[31]),"=f"(d[32]),"=f"(d[33]),"=f"(d[34]),"=f"(d[35]),"=f"(d[36]),"=f"(d[37]),"=f"(d[38]),"=f"(d[39]),"=f"(d[40]),"=f"(d[41]),"=f"(d[42]),"=f"(d[43]),"=f"(d[44]),"=f"(d[45]),"=f"(d[46]),"=f"(d[47]),"=f"(d[48]),"=f"(d[49]),"=f"(d[50]),"=f"(d[51]),"=f"(d[52]),"=f"(d[53]),"=f"(d[54]),"=f"(d[55]),"=f"(d[56]),"=f"(d[57]),"=f"(d[58]),"=f"(d[59]),"=f"(d[60]),"=f"(d[61]),"=f"(d[62]),"=f"(d[63]) : "r"(a0), "r"(a1), "r"(a2), "r"(a3), "l"(db));
}
__device__ __forceinline__ void wg_tt128(float (&d)[64], uint64_t da, uint64_t db, int sc) {
  asm volatile("{.reg .pred p; setp.ne.b32 p, %66, 0; wgmma.mma_async.sync.aligned.m64n128k16.f32.bf16.bf16 {%0,%1,%2,%3,%4,%5,%6,%7,%8,%9,%10,%11,%12,%13,%14,%15,%16,%17,%18,%19,%20,%21,%22,%23,%24,%25,%26,%27,%28,%29,%30,%31,%32,%33,%34,%35,%36,%37,%38,%39,%40,%41,%42,%43,%44,%45,%46,%47,%48,%49,%50,%51,%52,%53,%54,%55,%56,%57,%58,%59,%60,%61,%62,%63}, %64, %65, p, 1, 1, 1, 1;}"
    : "+f"(d[0]),"+f"(d[1]),"+f"(d[2]),"+f"(d[3]),"+f"(d[4]),"+f"(d[5]),"+f"(d[6]),"+f"(d[7]),"+f"(d[8]),"+f"(d[9]),"+f"(d[10]),"+f"(d[11]),"+f"(d[12]),"+f"(d[13]),"+f"(d[14]),"+f"(d[15]),"+f"(d[16]),"+f"(d[17]),"+f"(d[18]),"+f"(d[19]),"+f"(d[20]),"+f"(d[21]),"+f"(d[22]),"+f"(d[23]),"+f"(d[24]),"+f"(d[25]),"+f"(d[26]),"+f"(d[27]),"+f"(d[28]),"+f"(d[29]),"+f"(d[30]),"+f"(d[31]),"+f"(d[32]),"+f"(d[33]),"+f"(d[34]),"+f"(d[35]),"+f"(d[36]),"+f"(d[37]),"+f"(d[38]),"+f"(d[39]),"+f"(d[40]),"+f"(d[41]),"+f"(d[42]),"+f"(d[43]),"+f"(d[44]),"+f"(d[45]),"+f"(d[46]),"+f"(d[47]),"+f"(d[48]),"+f"(d[49]),"+f"(d[50]),"+f"(d[51]),"+f"(d[52]),"+f"(d[53]),"+f"(d[54]),"+f"(d[55]),"+f"(d[56]),"+f"(d[57]),"+f"(d[58]),"+f"(d[59]),"+f"(d[60]),"+f"(d[61]),"+f"(d[62]),"+f"(d[63]) : "l"(da), "l"(db), "r"(sc));
}
__device__ __forceinline__ void wg_tt64(float (&d)[64], uint64_t da, uint64_t db, int sc) {
  asm volatile("{.reg .pred p; setp.ne.b32 p, %34, 0; wgmma.mma_async.sync.aligned.m64n64k16.f32.bf16.bf16 {%0,%1,%2,%3,%4,%5,%6,%7,%8,%9,%10,%11,%12,%13,%14,%15,%16,%17,%18,%19,%20,%21,%22,%23,%24,%25,%26,%27,%28,%29,%30,%31}, %32, %33, p, 1, 1, 1, 1;}"
    : "+f"(d[0]),"+f"(d[1]),"+f"(d[2]),"+f"(d[3]),"+f"(d[4]),"+f"(d[5]),"+f"(d[6]),"+f"(d[7]),"+f"(d[8]),"+f"(d[9]),"+f"(d[10]),"+f"(d[11]),"+f"(d[12]),"+f"(d[13]),"+f"(d[14]),"+f"(d[15]),"+f"(d[16]),"+f"(d[17]),"+f"(d[18]),"+f"(d[19]),"+f"(d[20]),"+f"(d[21]),"+f"(d[22]),"+f"(d[23]),"+f"(d[24]),"+f"(d[25]),"+f"(d[26]),"+f"(d[27]),"+f"(d[28]),"+f"(d[29]),"+f"(d[30]),"+f"(d[31]) : "l"(da), "l"(db), "r"(sc));
}
__device__ __forceinline__ void wg_tt32(float (&d)[64], uint64_t da, uint64_t db, int sc) {
  asm volatile("{.reg .pred p; setp.ne.b32 p, %18, 0; wgmma.mma_async.sync.aligned.m64n32k16.f32.bf16.bf16 {%0,%1,%2,%3,%4,%5,%6,%7,%8,%9,%10,%11,%12,%13,%14,%15}, %16, %17, p, 1, 1, 1, 1;}"
    : "+f"(d[0]),"+f"(d[1]),"+f"(d[2]),"+f"(d[3]),"+f"(d[4]),"+f"(d[5]),"+f"(d[6]),"+f"(d[7]),"+f"(d[8]),"+f"(d[9]),"+f"(d[10]),"+f"(d[11]),"+f"(d[12]),"+f"(d[13]),"+f"(d[14]),"+f"(d[15]) : "l"(da), "l"(db), "r"(sc));
}
__device__ __forceinline__ void wg_g1(float (&d)[88], uint64_t da, uint64_t db, int sc) {
  asm volatile("{.reg .pred p; setp.ne.b32 p, %90, 0; wgmma.mma_async.sync.aligned.m64n176k16.f32.bf16.bf16 {%0,%1,%2,%3,%4,%5,%6,%7,%8,%9,%10,%11,%12,%13,%14,%15,%16,%17,%18,%19,%20,%21,%22,%23,%24,%25,%26,%27,%28,%29,%30,%31,%32,%33,%34,%35,%36,%37,%38,%39,%40,%41,%42,%43,%44,%45,%46,%47,%48,%49,%50,%51,%52,%53,%54,%55,%56,%57,%58,%59,%60,%61,%62,%63,%64,%65,%66,%67,%68,%69,%70,%71,%72,%73,%74,%75,%76,%77,%78,%79,%80,%81,%82,%83,%84,%85,%86,%87}, %88, %89, p, 1, 1, 1, 0;}"
    : "+f"(d[0]),"+f"(d[1]),"+f"(d[2]),"+f"(d[3]),"+f"(d[4]),"+f"(d[5]),"+f"(d[6]),"+f"(d[7]),"+f"(d[8]),"+f"(d[9]),"+f"(d[10]),"+f"(d[11]),"+f"(d[12]),"+f"(d[13]),"+f"(d[14]),"+f"(d[15]),"+f"(d[16]),"+f"(d[17]),"+f"(d[18]),"+f"(d[19]),"+f"(d[20]),"+f"(d[21]),"+f"(d[22]),"+f"(d[23]),"+f"(d[24]),"+f"(d[25]),"+f"(d[26]),"+f"(d[27]),"+f"(d[28]),"+f"(d[29]),"+f"(d[30]),"+f"(d[31]),"+f"(d[32]),"+f"(d[33]),"+f"(d[34]),"+f"(d[35]),"+f"(d[36]),"+f"(d[37]),"+f"(d[38]),"+f"(d[39]),"+f"(d[40]),"+f"(d[41]),"+f"(d[42]),"+f"(d[43]),"+f"(d[44]),"+f"(d[45]),"+f"(d[46]),"+f"(d[47]),"+f"(d[48]),"+f"(d[49]),"+f"(d[50]),"+f"(d[51]),"+f"(d[52]),"+f"(d[53]),"+f"(d[54]),"+f"(d[55]),"+f"(d[56]),"+f"(d[57]),"+f"(d[58]),"+f"(d[59]),"+f"(d[60]),"+f"(d[61]),"+f"(d[62]),"+f"(d[63]),"+f"(d[64]),"+f"(d[65]),"+f"(d[66]),"+f"(d[67]),"+f"(d[68]),"+f"(d[69]),"+f"(d[70]),"+f"(d[71]),"+f"(d[72]),"+f"(d[73]),"+f"(d[74]),"+f"(d[75]),"+f"(d[76]),"+f"(d[77]),"+f"(d[78]),"+f"(d[79]),"+f"(d[80]),"+f"(d[81]),"+f"(d[82]),"+f"(d[83]),"+f"(d[84]),"+f"(d[85]),"+f"(d[86]),"+f"(d[87]) : "l"(da), "l"(db), "r"(sc));
}

struct Params { const __nv_bfloat16 *x, *logA, *Aim, *Cr, *Ci, *logdt, *Dskip, *Wd; uint4* xnT; float2* st; uint2* S; unsigned* flags; };
struct Maps { CUtensorMap x[2], xo, out, wg, wu, wd, hst[2], hld, xt, sld; };

__device__ __forceinline__ void conv_channel(uint32_t cb, int w, int lane, uint32_t (&res)[8], uint32_t sig, int sidx) {
    const int q = lane & 3, g = lane >> 2, gam = g >> 2;
    float acc[64];
    uint2 a[17][2];
    const uint32_t t0 = cb + CH_T + (uint32_t)(14 + 4 * w + (g & 3) - 2 * q) * 280u + gam * 8;
#define LDA(s0, s1) _Pragma("unroll") for (int s = s0; s < s1; s++) { a[s][0] = lds64(t0 + s * 16); a[s][1] = lds64(t0 - 8 * 280 + s * 16); }
#define CT(N, s) wg_rs<N>(acc, a[s][0].x, a[s][0].y, a[s][1].x, a[s][1].y, dU + 4 * (s))
    const uint64_t dU = mkdesc(cb + CH_U, UPLANE, 128, 0);
    LDA(0, 17)
    if (sig) { fence_async_smem(); mbar_arrive(sig); }
    WG_FENCE();
    if (w == 0) STAMP2(52 + 3 * sidx);
    wg_rs_first(acc, a[0][0].x, a[0][0].y, a[0][1].x, a[0][1].y, dU);
    CT(128, 1); CT(120, 2); CT(120, 3); CT(112, 4); CT(112, 5); CT(104, 6); CT(104, 7); CT(96, 8);
    CT(96, 9); CT(88, 10); CT(88, 11); CT(80, 12); CT(80, 13); CT(72, 14); CT(72, 15); CT(64, 16);
#undef CT
#undef LDA
    wg_tt64(acc, mkdesc(cb + CH_A3, 128, 512, 0), mkdesc(cb + CH_B3, 384, 32, 0), 1);
    wg_tt32(acc, mkdesc(cb + CH_A3 + 256, 128, 512, 0), mkdesc(cb + CH_B3 + 128, 384, 32, 0), 1);
    WG_COMMIT();
    if (w == 0) STAMP2(53 + 3 * sidx);
    WG_WAIT(0);
    fence_acc(acc);
    if (w == 0) STAMP2(54 + 3 * sidx);
    const int src1 = (lane & ~3) | ((q + 1) & 3);
    float E[16][2];
    #pragma unroll
    for (int j = 0; j < 16; j++) {
        const float nxt = (j < 15) ? acc[4 * (j + 1) + 2] : 0.f;
        const float sup = (q == 0) ? nxt : acc[4 * j + 2];
        const float v = __shfl_sync(0xffffffffu, sup, src1);
        E[j][0] = acc[4 * j] + acc[4 * j + 3];
        E[j][1] = acc[4 * j + 1] + v;
    }
    const int src2 = gam ? ((lane & 12) | ((q + 3) & 3)) : (16 | (lane & 12) | ((q + 1) & 3));
    const bool c1 = gam && q != 0, c2 = gam && q == 0;
    #pragma unroll
    for (int a2 = 0; a2 < 8; a2++) {
        float y[2];
        #pragma unroll
        for (int e = 0; e < 2; e++) {
            const float sup = c1 ? E[2 * a2][e] : E[2 * a2 + 1][e];
            const float nxt = (a2 < 7) ? E[2 * a2 + 2][e] : 0.f;
            const float keep = c2 ? nxt : (c1 ? E[2 * a2 + 1][e] : E[2 * a2][e]);
            y[e] = keep + __shfl_sync(0xffffffffu, sup, src2);
        }
        res[a2] = pack2(y[1], y[0]);
    }
}

__device__ __forceinline__ void consumer(uint32_t sb, int warp, const Params& P, const Maps& M) {
    const int V = warp >> 2, w = warp & 3, lane = threadIdx.x & 31, q = lane & 3, g = lane >> 2;
    const int c = blockIdx.x;
    const uint32_t bars = sb + OFF_BAR, xb = sb + OFF_X + V * 2 * XBUF;
    {
        float ag[88], au[88];
        if (V == 0) {
            sts128(xb + (w >> 1) * XBUF + 168 * 128 + (threadIdx.x & 63) * 16, 0x3f803f80u, 0x3f803f80u, 0x3f803f80u, 0x3f803f80u);
            fence_async_smem();
            bar_sync(1);
        } else mbar_wait(bars + 8 * B_GO, 0);
        define_acc(ag); define_acc(au);
        #pragma unroll 1
        for (int st = 0; st < 8; st++) {
            if (st + LAG * V == HOLD0 || st + LAG * V == HOLD1) mbar_wait(bars + 8 * (B_K + (st + LAG * V == HOLD1)), 0);
            mbar_wait(bars + 8 * (B_FULLW + (st & 3)), st >> 2);
            mbar_wait(bars + 8 * (B_FULLX + 2 * V + (st & 1)), (st >> 1) & 1);
            STAMP(40 + 8 * V + st);
            const uint64_t dG = mkdesc(sb + OFF_W + (st & 3) * 16384, 0, 1024, 1);
            const uint64_t dX = mkdesc(xb + (st & 1) * XBUF, 16, 1024, 1);
            WG_FENCE();
            #pragma unroll
            for (int k = 0; k < 4; k++) {
                wg_g1(ag, dG + k * 128, dX + k * 2, k ? 1 : st);
                wg_g1(au, dG + 512 + k * 128, dX + k * 2, k ? 1 : st);
            }
            WG_COMMIT();
            WG_WAIT(1);
            if (lane == 0 && st > 0) {
                mbar_arrive(bars + 8 * (B_EMPTYW + ((st - 1) & 3)));
                mbar_arrive(bars + 8 * (B_EMPTYX + 2 * V + ((st - 1) & 1)));
                if (warp < 4 && st == 1) mbar_arrive(bars + 8 * B_GO);
            }
        }
        WG_WAIT(0);
        fence_acc(ag); fence_acc(au);
        if (lane == 0) { mbar_arrive(bars + 8 * (B_EMPTYW + 3)); mbar_arrive(bars + 8 * (B_EMPTYX + 2 * V + 1)); }
        STAMP(8 * V + 1);
        float cg0 = ag[84], cg1 = ag[86], cu0 = au[84], cu1 = au[86];
        const uint32_t ca = sb + OFF_CSUM + (8 * w + g) * 16;
        if (V == 0) { sts128(ca, FU(cg0), FU(cg1), FU(cu0), FU(cu1)); mbar_arrive(bars + 8 * B_CS); }
        else { mbar_wait(bars + 8 * B_CS, 0); const uint4 t = lds128(ca); cg0 = UF(t.x); cg1 = UF(t.y); cu0 = UF(t.z); cu1 = UF(t.w); }
        mbar_wait(bars + 8 * B_STATS, 0);
        mbar_wait(bars + 8 * (B_EMPTYX + 2 * V), 1);
        STAMP(13 + V);
        const uint32_t hs = xb + (2 * w + ((lane >> 3) & 1)) * (2688 + 128 * V) + (lane >> 4) * 128 + (lane & 7) * 16;
        const uint32_t sa = sb + OFF_ST + (168 * V + 2 * q) * 8;
        uint4 sq[22];
        #pragma unroll
        for (int j = 0; j < 3; j++) sq[j] = lds128(sa + j * 64);
        #pragma unroll
        for (int j = 0; j < 22; j += 2) {
            uint32_t o[4];
            #pragma unroll
            for (int jj = 0; jj < 2; jj++) {
                const uint4 sv = sq[j + jj];
                float hv[4];
                #pragma unroll
                for (int i = 0; i < 4; i++) {
                    const float m = UF((i & 1) ? sv.z : sv.x);
                    const float gh = fmaf(-m, (i & 2) ? cg1 : cg0, ag[4 * (j + jj) + i]) * UF((i & 1) ? sv.w : sv.y);
                    const float p = gh * fmaf(-m, (i & 2) ? cu1 : cu0, au[4 * (j + jj) + i]);
                    hv[i] = fmaf(p, tanh_fast(gh), p);
                }
                o[2 * jj] = pack2(hv[0], hv[1]); o[2 * jj + 1] = pack2(hv[2], hv[3]);
            }
            #pragma unroll
            for (int k = (j ? 3 + 3 * j / 2 : 3); k < 6 + 3 * j / 2 && k < 22; k++) sq[k] = lds128(sa + k * 64);
            uint32_t ad = hs + j * 128;
            if (j == 20 && V == 0 && lane >= 16) ad = xb + 21504 + (lane & 7) * 16;
            stsm4(ad, o[0], o[1], o[2], o[3]);
        }
        if (c >= 128) { fence_async_smem(); mbar_arrive(bars + 8 * (B_EPI + V)); }
        STAMP(8 * V + 2);
    }
    if (c >= 128) return;
    {
        uint32_t r0[8], r1[8];
        #pragma unroll
        for (int i = 0; i < 8; i++) asm volatile("" : "=r"(r1[i]));
        #pragma unroll 1
        for (int e = 0; e < 2; e++) {
            #pragma unroll
            for (int i = 0; i < 8; i++) r0[i] = r1[i];
            mbar_wait(bars + 8 * (B_CONV + 2 * V + e), 0);
            conv_channel(sb + OFF_CONV + (2 * V + e) * CH_STRIDE, w, lane, r1, e ? 0 : bars + 8 * (B_EPI + V), 2 * V + e);
            if (e == 0) STAMP(8 * V + 3);
        }
        const int gam = g >> 2, qq = gam ? ((q + 3) & 3) : q;
        const uint32_t sp = sb + OFF_CONV + V * OFF_SST + ((63 - 4 * gam - qq) * 16 + 4 * (w ^ (3 - qq)) + (g & 3)) * 8;
        bar_sync(3 + V);
        #pragma unroll
        for (int a2 = 0; a2 < 8; a2++) sts64(sp - a2 * 1024, r0[a2], r1[a2]);
        fence_async_smem();
        mbar_arrive(bars + 8 * (B_SIG + V));
        STAMP(8 * V + 4);
    }
    if (V == 1) return;
    {
        const int tau = c >> 2, dg = c & 3;
        const uint32_t row = 8 * (w & 1) + 32 * (w >> 1);
        float acc[64];
        define_acc(acc);
        const float rr0 = __ldcg(&P.st[64 * tau + row + g].y), rr1 = __ldcg(&P.st[64 * tau + row + g + 16].y);
        mbar_wait(bars + 8 * B_FULLD, 0);
        STAMP(5);
        uint64_t dB = mkdesc(sb + wd_slot(0), 8192, 1024, 1), dA = mkdesc(sb + h_slot(0), 1024, 128, 0);
        #pragma unroll 1
        for (int st = 0; st < 21; st++) {
            WG_FENCE();
            wg_tt128(acc, dA, dB, st);
            wg_tt128(acc, dA + 128, dB + 128, 1);
            wg_tt128(acc, dA + 256, dB + 256, 1);
            wg_tt128(acc, dA + 384, dB + 384, 1);
            WG_COMMIT();
            const int sd = (st + 1) & 7;
            const uint32_t nb = bars + 8 * (B_FULLD + sd), np = ((st + 1) >> 3) & 1;
            uint32_t ro = st == 15 ? 8 * B_CH0 : 8 * (B_EMPTYD + ((st - 1) & 7)), m = lane == 0 && st > 0, ok;
            dB = mkdesc(sb + wd_slot(sd), 8192, 1024, 1); dA = mkdesc(sb + h_slot(sd), 1024, 128, 0);
            asm volatile("{.reg .pred p; mbarrier.test_wait.parity.shared::cta.b64 p, [%5], %6; vote.sync.all.pred p, p, -1; selp.u32 %0, 1, 0, p;}"
                : "=r"(ok), "+l"(dA), "+l"(dB), "+r"(ro), "+r"(m) : "r"(nb), "r"(np) : "memory");
            WG_WAIT(1);
            asm volatile("{.reg .pred p; setp.ne.u32 p, %1, 0; @p mbarrier.arrive.shared::cta.b64 _, [%0];}" :: "r"(bars + ro), "r"(m) : "memory");
            if (!ok) mbar_wait(nb, np);
            if (w == 0) STAMP2(20 + st);
        }
        WG_FENCE();
        wg_tt128(acc, dA, dB, 1);
        wg_tt128(acc, dA + 128, dB + 128, 1);
        WG_COMMIT();
        mbar_wait(bars + 8 * B_XO, 0);
        const uint32_t xo = sb + OFF_CONV + (row + (lane & 7) + 16 * ((lane >> 3) & 1)) * 128;
        const uint32_t so = sb + wd_slot(6) + (w >> 1) * 8192 + q * 256 + (g & 1) * 8;
        const uint32_t sx = (4 * (w & 1) + (g >> 1)) ^ (2 * q) ^ (2 * ((2 * tau + (w >> 1)) & 3));
        uint32_t xr[8][4];
        uint2 sv[16];
        #pragma unroll
        for (int j = 0; j < 16; j += 2) {
            ldsm4(xr[j >> 1], xo + (j >> 3) * 8192 + ((((j & 7) + (lane >> 4)) ^ (lane & 7)) << 4));
            sv[j] = lds64(so + j * 512 + (sx << 4));
            sv[j + 1] = lds64(so + j * 512 + 128 + ((sx ^ 1) << 4));
        }
        WG_WAIT(0);
        fence_acc(acc);
        STAMP(6);
        #pragma unroll
        for (int j = 0; j < 16; j += 2) {
            #pragma unroll
            for (int i = 0; i < 4; i++) {
                const int jj = j + (i >> 1), hh = i & 1;
                const float f0 = acc[4 * jj + 2 * hh] * (hh ? rr1 : rr0), f1 = acc[4 * jj + 2 * hh + 1] * (hh ? rr1 : rr0);
                const uint32_t G = pack2(fmaf(f0, tanh_fast(f0), f0), fmaf(f1, tanh_fast(f1), f1));
                const uint32_t s2 = __byte_perm(sv[jj].x, sv[jj].y, hh ? 0x7632 : 0x5410);
                asm("fma.rn.bf16x2 %0, %1, %2, %0;" : "+r"(xr[j >> 1][i]) : "r"(s2), "r"(G));
            }
            stsm4(xo + (j >> 3) * 8192 + ((((j & 7) + (lane >> 4)) ^ (lane & 7)) << 4), xr[j >> 1][0], xr[j >> 1][1], xr[j >> 1][2], xr[j >> 1][3]);
        }
        fence_async_smem();
        bar_sync(1);
        if (w == 0 && elect_one()) {
            #pragma unroll
            for (int i = 0; i < 2; i++)
                asm volatile("cp.async.bulk.tensor.2d.global.shared::cta.bulk_group [%0, {%2, %3}], [%1];"
                    :: "l"(&M.out), "r"(sb + OFF_CONV + i * 8192), "r"(dg * 128 + 64 * i), "r"(tau * 64) : "memory");
            asm volatile("cp.async.bulk.commit_group; cp.async.bulk.wait_group.read 0;" ::: "memory");
        }
        STAMP(7); GSTAMP(23);
    }
}

__device__ __forceinline__ float2 cexp_p(float re2, float im, float p) {
    float sn, cs;
    const float mag = ex2(re2 * p), th = im * p;
    asm("sin.approx.ftz.f32 %0, %1;" : "=f"(sn) : "f"(th));
    asm("cos.approx.ftz.f32 %0, %1;" : "=f"(cs) : "f"(th));
    return make_float2(mag * cs, mag * sn);
}
struct SsmRaw { uint64_t la, ai, cr, ci; unsigned short ldt, dsk; };
__device__ __forceinline__ uint64_t ldg64(const void* p, int i) { uint64_t v; asm volatile("ld.global.nc.u64 %0, [%1];" : "=l"(v) : "l"((const uint64_t*)p + i)); return v; }
__device__ __forceinline__ unsigned short ldu16(const void* p) { unsigned short v; asm volatile("ld.global.nc.u16 %0, [%1];" : "=h"(v) : "l"(p)); return v; }
__device__ __forceinline__ float2 cmul(float2 a, float2 b) { return make_float2(fmaf(a.x, b.x, -a.y * b.y), fmaf(a.x, b.y, a.y * b.x)); }
__device__ __forceinline__ float2 csqr(float2 a) { const float t = a.x * a.y; return make_float2(fmaf(a.x, a.x, -a.y * a.y), t + t); }
__device__ __forceinline__ void mma16816(float (&d)[4], const uint32_t (&a)[4], uint32_t b0, uint32_t b1) {
    asm volatile("mma.sync.aligned.m16n8k16.row.col.f32.bf16.bf16.f32 {%0,%1,%2,%3}, {%4,%5,%6,%7}, {%8,%9}, {%0,%1,%2,%3};"
        : "+f"(d[0]), "+f"(d[1]), "+f"(d[2]), "+f"(d[3]) : "r"(a[0]), "r"(a[1]), "r"(a[2]), "r"(a[3]), "r"(b0), "r"(b1));
}

__device__ __forceinline__ void layer_norm(uint32_t sb, uint32_t cb, int w, int lane) {
    const uint32_t bars = sb + OFF_BAR;
    mbar_wait(bars + 8 * B_LNX, 0);
    STAMP(34);
    {
        const uint32_t r0 = cb + CH_LN + (w & 1) * 64 + (lane >> 3) * 1040, ra = r0 + (lane & 7) * 16;
        const float pv = bf_lo(FU(ldsf(r0)));
        float s0 = 0.f, s1 = 0.f, a0 = 0.f, a1 = 0.f;
        #pragma unroll 1
        for (int k = 0; k < 1024; k += 512) {
            uint32_t v[16];
            #pragma unroll
            for (int j = 0; j < 4; j++) *(uint4*)&v[4 * j] = lds128(ra + k + 128 * j);
            #pragma unroll
            for (int i = 0; i < 16; i++) { const float t0 = bf_lo(v[i]) - pv, t1 = bf_hi(v[i]) - pv; s0 += t0; s1 += t1; a0 = fmaf(t0, t0, a0); a1 = fmaf(t1, t1, a1); }
        }
        s0 += s1; a0 += a1;
        #pragma unroll
        for (int o = 4; o; o >>= 1) { s0 += __shfl_xor_sync(0xffffffffu, s0, o); a0 += __shfl_xor_sync(0xffffffffu, a0, o); }
        s0 *= 1.f / DM;
        float sd, ri;
        asm("sqrt.approx.ftz.f32 %0, %1;" : "=f"(sd) : "f"(bf_round(bf_round(fmaxf(fmaf(-s0, s0, a0 * (1.f / DM)), 0.f)) + 1e-5f)));
        asm("rcp.approx.ftz.f32 %0, %1;" : "=f"(ri) : "f"(bf_round(sd)));
        if ((lane & 7) == 0) sts64(sb + OFF_CSUM + (w + 4 * (lane >> 3)) * 8, FU(bf_round(pv + s0)), FU(0.5f * ri));
    }
    STAMP(62);
    bar_sync(2);
    const int r = 4 * ((lane & 7) >> 1) + (lane & 1) + 2 * ((lane >> 3) & 1);
    const uint32_t ad = sb + OFF_CONV + (r & 3) * CH_STRIDE + CH_LN + (r & 1) * 64 + (r >> 2) * 1040 + (16 * w + (lane >> 4)) * 16;
    const uint4 sa = lds128(sb + OFF_CSUM + (lane & 3) * 32), sc = lds128(sb + OFF_CSUM + (lane & 3) * 32 + 16);
    const uint32_t m2[2] = {__byte_perm(sa.x, sa.z, 0x7632), __byte_perm(sc.x, sc.z, 0x7632)};
    const float ri[4] = {2.f * UF(sa.y), 2.f * UF(sa.w), 2.f * UF(sc.y), 2.f * UF(sc.w)};
    #pragma unroll 1
    for (int i = 0; i < 8; i += 4) {
        uint32_t v[4][4];
        #pragma unroll
        for (int j = 0; j < 4; j++)
            asm volatile("ldmatrix.sync.aligned.m8n8.x4.trans.shared.b16 {%0,%1,%2,%3}, [%4];" : "=r"(v[j][0]), "=r"(v[j][1]), "=r"(v[j][2]), "=r"(v[j][3]) : "r"(ad + 32 * (i + j)) : "memory");
        #pragma unroll
        for (int j = 0; j < 4; j++) {
            #pragma unroll
            for (int k = 0; k < 4; k++) {
                uint32_t dv; asm("sub.rn.bf16x2 %0, %1, %2;" : "=r"(dv) : "r"(v[j][k]), "r"(m2[k & 1]));
                v[j][k] = pack2(bf_lo(dv) * ri[2 * (k & 1)], bf_hi(dv) * ri[2 * (k & 1) + 1]);
            }
            sts64(cb + CH_LNT + lane * 8 + (i + j) * 512, v[j][0], v[j][1]); sts64(cb + CH_LNT + lane * 8 + (i + j) * 512 + 256, v[j][2], v[j][3]);
        }
    }
    fence_async_smem();
    mbar_arrive(bars + 8 * B_LN);
    STAMP(16);
}

__device__ __forceinline__ void aux_role(uint32_t sb, int w, const SsmRaw& raw, const __nv_bfloat16* x) {
    const int lane = threadIdx.x & 31, q = lane & 3, g = lane >> 2;
    const int c = blockIdx.x;
    const uint32_t bars = sb + OFF_BAR;
    if (c >= 128) {
        mbar_arrive(bars + 8 * B_LN);
        if (lane == 0) { mbar_arrive(bars + 8 * B_K); mbar_arrive(bars + 8 * (B_K + 1)); }
        return;
    }
    {
        const uint32_t cb = sb + OFF_CONV + w * CH_STRIDE;
        const uint32_t sF = cb + CH_A3;
        uint64_t la = raw.la, ai = raw.ai, cr = raw.cr, ci = raw.ci;
        const float ldt = bf_lo(raw.ldt), dsk = bf_lo(raw.dsk);
        float dacc[2][3][4];
        #pragma unroll
        for (int i = 0; i < 24; i++) (&dacc[0][0][0])[i] = 0.f;
        const float dt = bf_round(ex2(ldt * 1.4426950408889634f));
        #pragma unroll 1
        for (int ck = 0; ck < 4; ck++, la >>= 16, ai >>= 16, cr >>= 16, ci >>= 16) {
            const uint32_t fa = cb + lane * 4 + (ck & 1) * 8064;
            if (ck == LNCK - 1 && elect_one()) {
                fence_async_smem();
                mbar_expect(bars + 8 * B_LNX, 4096);
                #pragma unroll
                for (int i = 0; i < 4; i++)
                    bulk_load(cb + CH_LN + (w & 1) * 64 + i * 1040, x + (16 * (c & ~1) + 8 * (c & 1) + 16 + w + 4 * (i & 1) - 8 * (i & 2)) * DM, 1024, bars + 8 * B_LNX);
            }
            if (ck == LNCK) { layer_norm(sb, cb, w, lane); mbar_wait(bars + 8 * B_LN, 0); }
            const float re2 = bf_round(ex2(bf_lo((uint32_t)la) * 1.4426950408889634f)) * dt * -1.4426950408889634f, im = bf_lo((uint32_t)ai) * dt;
            const float2 C = make_float2(bf_lo((uint32_t)cr) * (dt + dt), bf_lo((uint32_t)ci) * -(dt + dt));
            if (w == 0) { asm volatile("" :: "f"(re2), "f"(C.x) : "memory"); STAMP2(15 + ck); }
            const float2 z8 = cexp_p(re2, im, 8.f), y1 = cexp_p(re2, -im, 1.f);
            float2 b0 = make_float2(1.f, 0.f), b1 = cexp_p(re2, im, 64.f), b2 = csqr(b1), b3 = cmul(b2, b1);
            if (w == 0) { asm volatile("" :: "f"(b3.x), "f"(y1.x), "f"(z8.x) : "memory"); STAMP2(11 + ck); }
            const uint32_t fm = cb + (ck & 1) * 8064 + (lane >> 3) * 144 + (lane & 7) * 16;
#define PK(v) pack2((v).x, (v).y)
            #pragma unroll RUNROLL
            for (uint32_t ro = 0; ro < 8 * 144; ro += 144) {
                stsm4(fm + (lane >> 3) * 7 * 144 + ro, PK(b0), PK(b1), PK(b2), PK(b3));
                b0 = cmul(b0, z8); b1 = cmul(b1, z8); b2 = cmul(b2, z8); b3 = cmul(b3, z8);
            }
            if (ck < 2) STAMP(56 + 3 * ck);
            const float2 y256 = cexp_p(re2, -im, 256.f), y2 = csqr(y1), y4 = csqr(y2), y8 = make_float2(z8.x, -z8.y);
            if (ck == LNCK) mbar_wait(bars + 8 * B_LNS, 0);
            {
                const float2 l1 = cmul(C, y1), l2 = cmul(C, y2), l3 = cmul(l1, y2);
                stsm4(fm + 32 * 144, PK(C), PK(l1), PK(l2), PK(l3));
                stsm4(fm + 36 * 144, PK(cmul(C, y4)), PK(cmul(l1, y4)), PK(cmul(l2, y4)), PK(cmul(l3, y4)));
            }
            const float2 t0 = cmul(C, y256), t1 = cmul(t0, y256), t2 = cmul(t1, y256), t3_ = cmul(t2, y256);
            const float2 u1 = cmul(t0, y2), u2 = cmul(u1, y2), u3 = cmul(u2, y2);
            stsm4(fm + 40 * 144, PK(t0), PK(u1), PK(u2), PK(u3));
            stsm4(fm + 44 * 144, PK(t1), PK(cmul(t1, y4)), PK(t2), PK(cmul(t2, y4)));
            const float2 v0 = cmul(t3_, y8), v1 = cmul(v0, y256), v2 = cmul(v1, y256), v3 = cmul(v2, y256);
            stsm4(fm + 48 * 144, PK(v0), PK(v1), PK(v2), PK(v3));
            stsf(fa + 52 * 144, UF(PK(t3_)));
#undef PK
            if (ck < 2) STAMP(57 + 3 * ck);
            if (ck & 1) {
                uint32_t ln_; asm volatile("mov.u32 %0, %%laneid;" : "=r"(ln_));
                const uint32_t lda = cb + (ln_ & 15) * 144 + (ln_ & 16);
                const uint32_t ldb = cb + (32 + (ln_ & 7)) * 144 + (ln_ >> 3) * 16;
                __syncwarp();
                #pragma unroll
                for (int k2 = 0; k2 < 4; k2++) {
                    const uint32_t ko = (k2 >> 1) * 8064 + (k2 & 1) * 64;
                    uint32_t b[3][4];
                    #pragma unroll
                    for (int t3 = 0; t3 < 3; t3++) ldsm4(b[t3], ldb + t3 * 8 * 144 + ko);
                    #pragma unroll
                    for (int k = 0; k < 2; k++)
                        #pragma unroll
                        for (int mu = 0; mu < 2; mu++) {
                            uint32_t a[4];
                            ldsm4(a, lda + mu * 16 * 144 + ko + k * 32);
                            #pragma unroll
                            for (int t3 = 0; t3 < 3; t3++) mma16816(dacc[mu][t3], a, b[t3][2 * k], b[t3][2 * k + 1]);
                        }
                }
                __syncwarp();
                if (lane == 0) mbar_arrive(bars + 8 * (B_K + (ck >> 1)));
                STAMP(58 + 3 * (ck >> 1));
            }
        }
        STAMP(18);
        const uint32_t sG = cb + CH_G;
        if (lane == 0) dacc[0][0][0] += dsk;
        if (lane < 18) sts128(lane < 8 ? cb + CH_U + 2048 + (lane & 4) * (UPLANE / 4) + (lane & 3) * 16 : sG + 128 + (lane & 1) * 208 + ((lane - 8) >> 1) * 16, 0, 0, 0, 0);
        {
            const uint32_t f0 = sF + (8 * g + 2 * q) * 4, f1 = sF + ((q < 2) ? 256 + 4 * g + 2 * q : 256 + 2 * g + 64 * q) * 4, st1 = (q < 2) ? 128 : 64;
            const uint32_t ga = sG + ((g & 1) ? 0 : 208) + (63 - (g >> 1) - 32 * q) * 2;
            #pragma unroll
            for (int i = 0; i < 4; i++) {
                const int mu = i >> 1, hh = i & 1;
                sts64(f0 + i * 256, FU(dacc[mu][0][2 * hh]), FU(dacc[mu][0][2 * hh + 1]));
                sts64(f1 + i * st1, FU(dacc[mu][1][2 * hh]), FU(dacc[mu][1][2 * hh + 1]));
                const uint32_t pk = pack2(dacc[mu][2][2 * hh], dacc[mu][2][2 * hh + 1]);
                if (q < 2) { sts16(ga - 8 * i, pk & 0xffff); sts16(ga - 8 * i - 32, pk >> 16); }
            }
            if (lane == 2) stsf(sF + 2048, dacc[0][2][0]);
        }
    }
    bar_sync(2);
    STAMP(19);
    const int u = min(lane, 30) - 15, r2 = (u + ((u >> 1) & 1)) >> 1, r4 = (u + 1 + ((u >> 2) & 1)) >> 2, xt = 1024 + 16 * w + u;
    const uint32_t o0 = CH_A3 + 4 * (w == 0 ? u : w == 1 ? 256 + r2 : 256 + 64 * w + r4), ost = w == 0 ? 64 : w == 1 ? 32 : 16;
    const uint32_t oa0 = u >= 0 || w == 3 ? o0 : CH_A3 + 4 * (w == 1 ? 256 + u : w == 2 ? 384 + r2 : 0);
    const uint32_t ot = CH_A3 + 4 * min(512, 256 + ((xt + 1 + ((xt >> 2) & 1)) >> 2));
    const int kap = (lane >> 4) * 8 + ((lane >> 1) & 7), gam = lane & 1, hh = w >> 1, wp = w & 1;
    const uint32_t oa = CH_U + wp * UPLANE + (127 - 4 * kap - 2 * gam - hh) * 16;
    const uint32_t ob = CH_U + (wp ^ 1) * UPLANE + (128 - wp - 4 * kap - 2 * gam - hh) * 16;
    const uint32_t od = CH_A3 + (4 * wp + hh) * 512 + (kap >> 3) * 256 + (kap & 7) * 16 + gam * 8;
    #pragma unroll 1
    for (int k = 0; k < 4; k++) {
        const int ch = 2 * (k & 1) + (k >> 1);
        const uint32_t cb = sb + OFF_CONV + ch * CH_STRIDE;
        {
            float kv[17];
            kv[0] = ldsf(cb + oa0); kv[16] = ldsf(cb + ot);
            #pragma unroll
            for (int s = 1; s < 16; s++) kv[s] = ldsf(cb + o0 + s * ost);
            const int tid = threadIdx.x & 127;
            const uint32_t ga = cb + CH_G + (tid >= 24) * 16 + min(tid, 47) * 8;
            const uint2 x0 = lds64(ga), x1 = lds64(ga + 8);
            if (u < 0 && w == 0) kv[0] = 0.f;
            if (xt > 1028) kv[16] = 0.f;
            uint32_t o[17];
            #pragma unroll
            for (int s = 0; s < 17; s++) o[s] = pack2(kv[s], __shfl_up_sync(0xffffffffu, kv[s], 1));
            if (lane > 0 && lane < 31) {
                const uint32_t ta = cb + CH_T + (lane - 1) * 280;
                #pragma unroll
                for (int s2 = 0; s2 < 8; s2++) sts64(ta + 64 * w + s2 * 8, o[2 * s2], o[2 * s2 + 1]);
                stsf(ta + 256 + 4 * w, UF(o[16]));
            }
            if (tid < 48) sts128(cb + CH_B3 + tid * 16, x0.x, x0.y, x1.x, x1.y);
        }
        mbar_wait(bars + 8 * B_U, 0);
        float p[24];
        const uint2 r0 = lds64(cb + ob + 24), r3 = lds64(cb + oa);
        uint32_t r[8];
        *(uint4*)&r[0] = lds128(cb + oa + 16); *(uint4*)&r[4] = lds128(cb + ob);
        p[0] = 0.f;
        p[1] = bf_lo(r0.x); p[2] = p[1] + bf_hi(r0.x); p[3] = p[2] + bf_lo(r0.y); p[4] = p[3] + bf_hi(r0.y);
        #pragma unroll
        for (int i = 0; i < 8; i++) { p[5 + 2 * i] = p[4 + 2 * i] + bf_lo(r[i]); p[6 + 2 * i] = p[5 + 2 * i] + bf_hi(r[i]); }
        p[21] = p[20] + bf_lo(r3.x); p[22] = p[21] + bf_hi(r3.x); p[23] = p[22] + bf_lo(r3.y);
        bar_sync(2);
        #pragma unroll
        for (int i = 0; i < 8; i += 4) {
            sts64(cb + od + i * 256, pack2(p[i + 9] - p[i], p[i + 10] - p[i + 1]), pack2(p[i + 11] - p[i + 2], p[i + 12] - p[i + 3]));
            sts64(cb + od + i * 256 + 128, pack2(p[i + 16] - p[i + 9], p[i + 17] - p[i + 10]), pack2(p[i + 18] - p[i + 11], p[i + 19] - p[i + 12]));
        }
        fence_async_smem();
        mbar_arrive(bars + 8 * (B_CONV + ch));
        if (k == 0) STAMP(17);
    }
    STAMP(21);
}

__global__ void __launch_bounds__(512, 1)
fused_kernel(const __grid_constant__ Params P, const __grid_constant__ Maps M) {
    extern __shared__ __align__(1024) uint8_t smem_raw[];
    const uint32_t sb = smem_u32(smem_raw);
    const uint32_t bars = sb + OFF_BAR;
    const int warp = __shfl_sync(0xffffffffu, threadIdx.x >> 5, 0);
    const int c = blockIdx.x, tg = c / 22, fb = c - 22 * tg;
    SsmRaw raw = {};
    if (warp >= 8 && warp < 12) {
        const int d = min(4 * c + warp - 8, DM - 1), o = d * 32 + (threadIdx.x & 31);
        raw.la = ldg64(P.logA, o); raw.ai = ldg64(P.Aim, o); raw.cr = ldg64(P.Cr, o); raw.ci = ldg64(P.Ci, o);
        raw.ldt = ldu16(P.logdt + d); raw.dsk = ldu16(P.Dskip + d);
    }
    if (elect_one()) {
        if (warp == 0) { STAMP(24); GSTAMP(22); }
        asm volatile("" :: "l"(((const uint64_t*)&P)[warp < 12 ? warp : 0]));
        if (warp < 12) asm volatile("prefetch.tensormap [%0];" :: "l"(&M.x[0] + warp) : "memory");
        #pragma unroll
        for (int k = 0; k < 4; k++) {
            const int i = 16 * k + ((warp + 4) & 15);
            const uint32_t cnt = i >= B_CONV ? 128 : ((0xf0ull >> i) & 1) ? 8 : ((0xff0000ull >> i) & 1) ? 2 : ((0x3e00ff00f000ull >> i) & 1) ? 4 : 1;
            asm volatile("mbarrier.init.shared::cta.b64 [%0], %1;" :: "r"(bars + 8 * i), "r"(cnt) : "memory");
        }
        asm volatile("fence.mbarrier_init.release.cluster; fence.proxy.async.shared::cta;" ::: "memory");
        if (warp == 13 || warp == 5 || warp == 6) { const uint32_t t0 = clock(); while ((uint32_t)clock() - t0 < DLY1) ; }
        if (warp == 12 || warp == 13) {
            const uint32_t s = warp - 12;
            mbar_expect(bars + 8 * (B_FULLW + s), 16384);
            tma2d(sb + OFF_W + s * 16384, &M.wg, 64 * fb, 64 * s, bars + 8 * (B_FULLW + s));
            tma2d(sb + OFF_W + s * 16384 + 8192, &M.wu, 64 * fb, 64 * s, bars + 8 * (B_FULLW + s));
            STAMP(31);
        } else if (warp >= 4 && warp < 7) {
            const uint32_t s = warp - 4, V = s >> 1;
            mbar_expect(bars + 8 * (B_FULLX + s), (168 + 8 * V) * 128);
            tma2d(sb + OFF_X + s * XBUF, &M.x[V], 64 * (s & 1), TOKG * tg + 168 * V, bars + 8 * (B_FULLX + s));
        }
        if (sb & 1023) __trap();
    }
    __syncthreads();
    if (warp < 8) {
        asm volatile("setmaxnreg.inc.sync.aligned.u32 208;");
        consumer(sb, warp, P, M);
    } else if (warp < 12) {
        asm volatile("setmaxnreg.dec.sync.aligned.u32 72;");
        STAMP(32);
        aux_role(sb, warp - 8, raw, P.x);
    } else {
        asm volatile("setmaxnreg.dec.sync.aligned.u32 24;");
        const int tau = c >> 2, dg = c & 3;
        if (elect_one()) {
            if (warp < 15) {
                if (warp == 12) {
                    #pragma unroll 1
                    for (int st = 2; st < 8; st++) {
                        const uint32_t s = st & 3, fb_ = bars + 8 * (B_FULLW + s);
                        if (st == 2) mbar_wait(bars + 8 * B_FULLW, 0);
                        mbar_wait(bars + 8 * (B_EMPTYW + s), (st >> 2) ^ 1);
                        mbar_expect(fb_, 16384);
                        tma2d(sb + OFF_W + s * 16384, &M.wg, 64 * fb, 64 * st, fb_);
                        tma2d(sb + OFF_W + s * 16384 + 8192, &M.wu, 64 * fb, 64 * st, fb_);
                    }
                } else {
                    const int V = warp - 13;
                    #pragma unroll 1
                    for (int st = 2 - V; st < 8; st++) {
                        const uint32_t s = 2 * V + (st & 1);
                        mbar_wait(bars + 8 * (B_EMPTYX + s), ((st >> 1) & 1) ^ 1);
                        mbar_expect(bars + 8 * (B_FULLX + s), (168 + 8 * V) * 128);
                        tma2d(sb + OFF_X + s * XBUF, &M.x[V], 64 * st, TOKG * tg + 168 * V, bars + 8 * (B_FULLX + s));
                    }
                }
                if (c < 128 && warp < 14) {
                    if (warp == 13) {
                        mbar_wait(bars + 8 * (B_STG + 1), 0);
                        #pragma unroll 1
                        for (int o = 8 * tau; o < 8 * tau + 8; o += 7) flag_wait(P.flags, F_H + 2 * (o / 43) + ((o % 43) >= 21), 22);
                        mbar_arrive(bars + 8 * B_HF);
                        STAMP(25);
                    }
                    #pragma unroll 1
                    for (int st = 0; st < 22; st += (st < 7 || (st == 7 && warp == 12)) ? 1 : 2) {
                        const int sd = st & 7;
                        const uint32_t fb_ = bars + 8 * (B_FULLD + sd);
                        if (st >= 8) mbar_wait(bars + 8 * (B_EMPTYD + sd), ((st >> 3) & 1) ^ 1);
                        else if (warp == 12 || st >= 6) mbar_wait(bars + 8 * (uint32_t)((0x373623070d060504ull >> (8 * st)) & 0xff), st < 5);
                        if (st >= 10 && st < 21) STAMP2(31 + st);
                        if (st >= 8 || warp == 13) {
                            mbar_expect(fb_, 8192);
                            asm volatile("cp.async.bulk.tensor.5d.shared::cluster.global.mbarrier::complete_tx::bytes [%0], [%1, {%3, %3, %3, %4, %5}], [%2];"
                                :: "r"(sb + h_slot(sd)), "l"(&M.hld), "r"(fb_), "r"(0), "r"(2 * tau), "r"(8 * st) : "memory");
                        }
                        if (st >= 8 || warp == 12) {
                            const uint32_t da = sb + wd_slot(sd);
                            mbar_expect(fb_, 16384);
                            tma2d(da, &M.wd, 128 * dg, 64 * st, fb_);
                            tma2d(da + 8192, &M.wd, 128 * dg + 64, 64 * st, fb_);
                        }
                    }
                } else if (c < 128) {
                    mbar_wait(bars + 8 * B_SST, 0);
                    flag_wait(P.flags, F_S + dg, 64);
                    STAMP(26);
                    mbar_wait(bars + 8 * B_CH0, 0);
                    mbar_expect(bars + 8 * B_XO, 32768);
                    tma2d(sb + OFF_CONV, &M.xo, 128 * dg, 64 * tau, bars + 8 * B_XO);
                    tma2d(sb + OFF_CONV + 8192, &M.xo, 128 * dg + 64, 64 * tau, bars + 8 * B_XO);
                    asm volatile("cp.async.bulk.tensor.5d.shared::cluster.global.mbarrier::complete_tx::bytes [%0], [%1, {%3, %3, %3, %4, %5}], [%2];"
                        :: "r"(sb + wd_slot(6)), "l"(&M.sld), "r"(bars + 8 * B_XO), "r"(0), "r"(8 * dg), "r"(2 * tau) : "memory");
                    mbar_wait(bars + 8 * B_HF, 0);
                    exit_count(P.flags);
                }
            } else {
                mbar_wait(bars + 8 * B_LN, 0);
                STAMP2(0);
                if (c < 128) {
                    #pragma unroll 1
                    for (int i = 0; i < 4; i++)
                        asm volatile("cp.async.bulk.tensor.2d.global.shared::cta.bulk_group [%0, {%2, %3}], [%1];"
                            :: "l"(&M.xt), "r"(sb + OFF_CONV + i * CH_STRIDE + CH_LNT), "r"((c & 1) * 1024 + (126 - (c & ~1)) * 8), "r"(128 * i) : "memory");
                    #pragma unroll 1
                    for (int i = 0; i < 2; i++) bulk_store(P.st + 16 * (c & ~1) + 8 * (c & 1) + 16 - 16 * i, sb + OFF_CSUM + 64 * i, 64);
                    asm volatile("cp.async.bulk.prefetch.L2.global [%0], %1;" :: "l"(P.Wd + c * (FF * DM / 128)), "r"(FF * DM / 64) : "memory");
                }
                asm volatile("cp.async.bulk.commit_group; cp.async.bulk.wait_group.read 0;" ::: "memory");
                mbar_arrive(bars + 8 * B_LNS);
                STAMP2(1);
                flag_signal(P.flags, F_A);
                STAMP2(2);
                flag_wait(P.flags, F_A, NCTA);
                STAMP(20);
                mbar_expect(bars + 8 * B_STATS, TOKG * 8);
                bulk_load(sb + OFF_ST, P.st + TOKG * tg, TOKG * 8, bars + 8 * B_STATS);
                if (c < 128) {
                    mbar_wait(bars + 8 * (B_K + 1), 0);
                    fence_async_smem();
                    mbar_expect(bars + 8 * B_U, 8 * 2048);
                    #pragma unroll 1
                    for (int i = 0; i < 8; i++)
                        bulk_load(sb + OFF_CONV + (i >> 1) * CH_STRIDE + CH_U + (i & 1) * UPLANE, P.xnT + 4 * c * 256 + i * 128, 2048, bars + 8 * B_U);
                } else exit_count(P.flags);
                #pragma unroll 1
                for (int V = 0; V < 2; V++) {
                    mbar_wait(bars + 8 * (B_EPI + V), 0);
                    STAMP2(3 + 2 * V);
                    asm volatile("cp.async.bulk.tensor.3d.global.shared::cta.bulk_group [%0, {%2, %3, %4}], [%1];"
                        :: "l"(&M.hst[V]), "r"(sb + OFF_X + V * 2 * XBUF), "r"(0), "r"(43 * tg + 21 * V), "r"(8 * fb) : "memory");
                    flag_signal(P.flags, F_H + 2 * tg + V);
                    mbar_arrive(bars + 8 * (B_STG + V));
                    STAMP2(4 + 2 * V);
                }
                if (c < 128) {
                    #pragma unroll 1
                    for (int V = 0; V < 2; V++) {
                        mbar_wait(bars + 8 * (B_SIG + V), 0);
                        STAMP2(7 + 2 * V);
                        bulk_store(P.S + (2 * c + V) * 1024, sb + OFF_CONV + V * OFF_SST, 8192);
                        flag_signal(P.flags, F_S + (c >> 5));
                        STAMP2(8 + 2 * V);
                    }
                    mbar_arrive(bars + 8 * B_SST);
                }
            }
        }
    }
    asm volatile("nanosleep.u32 0;");
}

typedef CUresult (*EncodeFn)(CUtensorMap*, CUtensorMapDataType, cuuint32_t, void*, const cuuint64_t*, const cuuint64_t*, const cuuint32_t*,
                             const cuuint32_t*, CUtensorMapInterleave, CUtensorMapSwizzle, CUtensorMapL2promotion, CUtensorMapFloatOOBfill);

void make_map(EncodeFn enc, CUtensorMap* m, const void* ptr, int rank, const cuuint64_t* dims, const cuuint64_t* strides, const cuuint32_t* box, bool swz, bool wide = false) {
    const cuuint32_t es[5] = {1, 1, 1, 1, 1};
    enc(m, CU_TENSOR_MAP_DATA_TYPE_BFLOAT16, rank, (void*)ptr, dims, strides, box, es, CU_TENSOR_MAP_INTERLEAVE_NONE,
        swz ? CU_TENSOR_MAP_SWIZZLE_128B : CU_TENSOR_MAP_SWIZZLE_NONE, wide ? CU_TENSOR_MAP_L2_PROMOTION_L2_256B : CU_TENSOR_MAP_L2_PROMOTION_L2_128B, CU_TENSOR_MAP_FLOAT_OOB_FILL_NONE);
}
void make_map2(EncodeFn enc, CUtensorMap* m, const void* ptr, cuuint64_t inner, cuuint64_t outer, cuuint32_t rows) {
    const cuuint64_t dims[2] = {inner, outer}, strides[1] = {inner * 2};
    const cuuint32_t box[2] = {64, rows};
    make_map(enc, m, ptr, 2, dims, strides, box, true, rows > 64);
}

}

extern "C" void kernel_launch(void* const* d_in, const int* in_sizes, int n_in, void* d_out, int out_size) {
    (void)in_sizes; (void)n_in; (void)out_size;
    static EncodeFn enc = nullptr;
    static void *hptr, *p_xnT, *p_st, *p_S, *p_flags;
    if (!enc) {
        cudaDriverEntryPointQueryResult qr;
        cudaGetDriverEntryPoint("cuTensorMapEncodeTiled", (void**)&enc, cudaEnableDefault, &qr);
        cudaFuncSetAttribute(fused_kernel, cudaFuncAttributeMaxDynamicSharedMemorySize, SMEM_BYTES);
        cudaGetSymbolAddress(&hptr, g_H); cudaGetSymbolAddress(&p_xnT, g_xnT); cudaGetSymbolAddress(&p_st, g_st);
        cudaGetSymbolAddress(&p_S, g_S); cudaGetSymbolAddress(&p_flags, g_flags);
    }
    Params P;
    P.x = (const __nv_bfloat16*)d_in[0]; P.logA = (const __nv_bfloat16*)d_in[1]; P.Aim = (const __nv_bfloat16*)d_in[2];
    P.Cr = (const __nv_bfloat16*)d_in[3]; P.Ci = (const __nv_bfloat16*)d_in[4]; P.logdt = (const __nv_bfloat16*)d_in[5];
    P.Dskip = (const __nv_bfloat16*)d_in[6];
    P.Wd = (const __nv_bfloat16*)d_in[10]; P.xnT = (uint4*)p_xnT; P.st = (float2*)p_st; P.S = (uint2*)p_S; P.flags = (unsigned*)p_flags;
    Maps M;
    make_map2(enc, &M.x[0], d_in[0], DM, SEQ, 168); make_map2(enc, &M.x[1], d_in[0], DM, SEQ, 176);
    make_map2(enc, &M.xo, d_in[0], DM, SEQ, 64);    make_map2(enc, &M.out, d_out, DM, SEQ, 64);
    make_map2(enc, &M.wg, d_in[8], FF, DM, 64);     make_map2(enc, &M.wu, d_in[9], FF, DM, 64);
    make_map2(enc, &M.wd, d_in[10], DM, FF, 64);
    for (int v = 0; v < 2; v++) {
        const cuuint64_t dims[3] = {64, 256, 172}, strides[2] = {128, 32768};
        const cuuint32_t box[3] = {64, (cuuint32_t)(21 + v), 8};
        make_map(enc, &M.hst[v], hptr, 3, dims, strides, box, false);
    }
    {
        const cuuint64_t dims[2] = {2048, 512}, strides[1] = {4096};
        const cuuint32_t box[2] = {16, 128};
        make_map(enc, &M.xt, p_xnT, 2, dims, strides, box, false);
    }
    {
        const cuuint64_t dims[5] = {64, 2, 4, 32, 64}, strides[4] = {4 * 8192, 8192, 8 * 8192, 128};
        const cuuint32_t box[5] = {64, 2, 4, 8, 2};
        make_map(enc, &M.sld, p_S, 5, dims, strides, box, true);
    }
    {
        const cuuint64_t dims[5] = {64, 2, 2, 64, 172}, strides[4] = {256, 128, 512, 32768};
        const cuuint32_t box[5] = {64, 2, 2, 2, 8};
        make_map(enc, &M.hld, hptr, 5, dims, strides, box, false);
    }
    fused_kernel<<<NCTA, 512, SMEM_BYTES>>>(P, M);
}
```

```cpp
#include <cuda_runtime.h>
#include <cuda_bf16.h>
#include <cuda.h>
#include <stdint.h>

#define PROF 0

namespace {

constexpr int SEQ = 2048, DM = 512, FF = 1376;
constexpr int NCTA = 132;
#define GOST 1
#define DLY1 300
constexpr int RUNROLL = 2;
constexpr int TOKG = 344;

constexpr uint32_t OFF_W = 0;
constexpr uint32_t XBUF = 22528;
constexpr uint32_t OFF_X = 65536;
constexpr uint32_t OFF_CONV = 155648;
constexpr uint32_t CH_STRIDE = 17536;
constexpr uint32_t CH_T = 0;
constexpr uint32_t CH_A3 = 8448;
constexpr uint32_t CH_B3 = 12544;
constexpr uint32_t CH_U = 13312;
constexpr uint32_t CH_G = CH_A3 + 2064;
constexpr uint32_t UPLANE = 2112;
constexpr uint32_t CH_LN = 0, CH_PART = 4224, CH_LNT = 13440;
constexpr uint32_t OFF_SST = 60416;
constexpr uint32_t OFF_ST = 225792;
constexpr uint32_t OFF_CSUM = 228544;
constexpr uint32_t OFF_BAR = 229056;
constexpr uint32_t SMEM_BYTES = 229568;

enum {
    B_FULLW = 0, B_EMPTYW = 4, B_FULLX = 8, B_EMPTYX = 12, B_FULLD = 16, B_EMPTYD = 24,
    B_U = 32, B_XO = 33, B_S = 34, B_STG = 35, B_HF = 37, B_STATS = 38, B_LNS = 39, B_SST = 40,
    B_LNX = 41, B_GO = 42, B_CH0 = 43, B_K = 44,
    B_CONV = 46, B_LN = 50, B_CS = 51, B_EPI = 52, B_SIG = 54,
    B_COUNT = 56
};
enum { F_A = 0, F_H = 1, F_S = 13, F_EXIT = 17, F_COUNT = 18 };

__device__ uint4 g_xnT[DM * 256];
__device__ float2 g_st[6 * TOKG];
__device__ uint4 g_H[172 * 256 * 8];
__device__ uint2 g_S[256 * 1024];
__device__ unsigned g_flags[F_COUNT * 32];
#define STAMP(i) do {} while (0)
#define GSTAMP(i) do {} while (0)
#define STAMP2(i) do {} while (0)

__device__ __forceinline__ uint32_t smem_u32(const void* p) { return (uint32_t)__cvta_generic_to_shared(p); }
__device__ __forceinline__ void mbar_expect(uint32_t bar, uint32_t bytes) { asm volatile("mbarrier.arrive.expect_tx.shared::cta.b64 _, [%0], %1;" :: "r"(bar), "r"(bytes) : "memory"); }
__device__ __forceinline__ void mbar_arrive(uint32_t bar) { asm volatile("mbarrier.arrive.shared::cta.b64 _, [%0];" :: "r"(bar) : "memory"); }
__device__ __forceinline__ void mbar_wait(uint32_t bar, uint32_t parity) {
    asm volatile("{.reg .pred p; .reg .u32 n; mov.u32 n, 0x20000;\n"
                 "LW: mbarrier.try_wait.parity.shared::cta.b64 p, [%0], %1;\n"
                 "sub.u32 n, n, 1; setp.eq.or.u32 p, n, 0, p; @!p bra LW;}" :: "r"(bar), "r"(parity) : "memory");
}
__device__ __forceinline__ bool elect_one() { uint32_t p; asm volatile("{.reg .pred P; elect.sync _|P, 0xffffffff; selp.u32 %0, 1, 0, P;}" : "=r"(p)); return p; }
__device__ __forceinline__ void tma2d(uint32_t dst, const CUtensorMap* m, int c0, int c1, uint32_t bar) {
    asm volatile("cp.async.bulk.tensor.2d.shared::cluster.global.mbarrier::complete_tx::bytes [%0], [%1, {%3, %4}], [%2];"
        :: "r"(dst), "l"(m), "r"(bar), "r"(c0), "r"(c1) : "memory");
}
__device__ __forceinline__ void bulk_load(uint32_t dst, const void* src, uint32_t bytes, uint32_t bar) {
    asm volatile("cp.async.bulk.shared::cluster.global.mbarrier::complete_tx::bytes [%0], [%1], %2, [%3];" :: "r"(dst), "l"(src), "r"(bytes), "r"(bar) : "memory");
}
__device__ __forceinline__ void bulk_store(void* dst, uint32_t src, uint32_t bytes) {
    asm volatile("cp.async.bulk.global.shared::cta.bulk_group [%0], [%1], %2;" :: "l"(dst), "r"(src), "r"(bytes) : "memory");
}
__device__ __forceinline__ void fence_async_smem() { asm volatile("fence.proxy.async.shared::cta;" ::: "memory"); }
__device__ __forceinline__ void flag_wait(unsigned* g_flags, int f, unsigned target) {
    asm volatile("{.reg .pred p; .reg .u32 n, v; mov.u32 n, 0x40000;\n"
                 "LF: ld.acquire.gpu.global.u32 v, [%0]; setp.ge.u32 p, v, %1; @p bra LD;\n"
                 "sub.u32 n, n, 1; setp.ne.u32 p, n, 0; @p bra LF; trap;\nLD: }"
                 :: "l"(g_flags + f * 32), "r"(target) : "memory");
}
__device__ __forceinline__ void flag_signal(unsigned* g_flags, int f) {
    asm volatile("cp.async.bulk.commit_group; cp.async.bulk.wait_group 0; red.relaxed.gpu.global.add.u32 [%0], 1;" :: "l"(g_flags + f * 32) : "memory");
}
__device__ __forceinline__ void exit_count(unsigned* g_flags) {
    if (atomicAdd(g_flags + F_EXIT * 32, 1u) == NCTA - 1) {
        #pragma unroll 1
        for (int i = 0; i < F_COUNT; i++) g_flags[i * 32] = 0;
    }
}
__device__ __forceinline__ void bar_sync(int id) { asm volatile("bar.sync %0, 128;" :: "r"(id) : "memory"); }
__device__ __forceinline__ uint64_t mkdesc(uint32_t addr, uint32_t lbo, uint32_t sbo, uint32_t swz) {
    return (uint64_t)((addr >> 4) | ((lbo >> 4) << 16)) | ((uint64_t)((sbo >> 4) | (swz << 30)) << 32);
}
#define WG_FENCE() asm volatile("wgmma.fence.sync.aligned;" ::: "memory")
#define WG_COMMIT() asm volatile("wgmma.commit_group.sync.aligned;" ::: "memory")
#define WG_WAIT(n) asm volatile("wgmma.wait_group.sync.aligned " #n ";" ::: "memory")
template <int N> __device__ __forceinline__ void fence_acc(float (&d)[N]) {
    #pragma unroll
    for (int i = 0; i < N; i++) asm volatile("" : "+f"(d[i]) :: "memory");
}
template <int N> __device__ __forceinline__ void define_acc(float (&d)[N]) {
    #pragma unroll
    for (int i = 0; i < N; i++) asm volatile("" : "=f"(d[i]));
}
__device__ __forceinline__ uint32_t pack2(float lo, float hi) { uint32_t r; asm("cvt.rn.bf16x2.f32 %0, %1, %2;" : "=r"(r) : "f"(hi), "f"(lo)); return r; }
__device__ __forceinline__ float bf_lo(uint32_t v) { return __uint_as_float(v << 16); }
__device__ __forceinline__ float bf_hi(uint32_t v) { return __uint_as_float(v & 0xffff0000u); }
__device__ __forceinline__ float bf_round(float v) { return bf_hi(pack2(0.f, v)); }
__device__ __forceinline__ float tanh_fast(float v) { float r; asm("tanh.approx.f32 %0, %1;" : "=f"(r) : "f"(v)); return r; }
__device__ __forceinline__ float ex2(float v) { float r; asm("ex2.approx.ftz.f32 %0, %1;" : "=f"(r) : "f"(v)); return r; }
__device__ __forceinline__ uint4 lds128(uint32_t a) { uint4 v; asm volatile("ld.shared.v4.b32 {%0,%1,%2,%3}, [%4];" : "=r"(v.x), "=r"(v.y), "=r"(v.z), "=r"(v.w) : "r"(a)); return v; }
__device__ __forceinline__ uint2 lds64(uint32_t a) { uint2 v; asm volatile("ld.shared.v2.b32 {%0,%1}, [%2];" : "=r"(v.x), "=r"(v.y) : "r"(a)); return v; }
__device__ __forceinline__ float ldsf(uint32_t a) { float v; asm volatile("ld.shared.f32 %0, [%1];" : "=f"(v) : "r"(a)); return v; }
__device__ __forceinline__ void sts128(uint32_t a, uint32_t x, uint32_t y, uint32_t z, uint32_t w) { asm volatile("st.shared.v4.b32 [%0], {%1,%2,%3,%4};" :: "r"(a), "r"(x), "r"(y), "r"(z), "r"(w) : "memory"); }
__device__ __forceinline__ void sts64(uint32_t a, uint32_t x, uint32_t y) { asm volatile("st.shared.v2.b32 [%0], {%1,%2};" :: "r"(a), "r"(x), "r"(y) : "memory"); }
__device__ __forceinline__ void stsf(uint32_t a, float x) { asm volatile("st.shared.f32 [%0], %1;" :: "r"(a), "f"(x) : "memory"); }
__device__ __forceinline__ void sts16(uint32_t a, uint32_t x) { asm volatile("st.shared.b16 [%0], %1;" :: "r"(a), "h"((unsigned short)x) : "memory"); }
__device__ __forceinline__ void stsm4(uint32_t a, uint32_t r0, uint32_t r1, uint32_t r2, uint32_t r3) {
    asm volatile("stmatrix.sync.aligned.m8n8.x4.shared.b16 [%0], {%1,%2,%3,%4};" :: "r"(a), "r"(r0), "r"(r1), "r"(r2), "r"(r3) : "memory");
}
__device__ __forceinline__ void ldsm4(uint32_t (&r)[4], uint32_t a) {
    asm volatile("ldmatrix.sync.aligned.m8n8.x4.shared.b16 {%0,%1,%2,%3}, [%4];" : "=r"(r[0]), "=r"(r[1]), "=r"(r[2]), "=r"(r[3]) : "r"(a) : "memory");
}
#define FU(x) __float_as_uint(x)
#define UF(x) __uint_as_float(x)
__device__ __forceinline__ uint32_t wd_slot(int s) { return (uint32_t)((0xbba8403056201000ull >> (8 * s)) & 0xff) << 10; }
__device__ __forceinline__ uint32_t h_slot(int s) { return (uint32_t)((0xcba0908880787068ull >> (8 * s)) & 0xff) << 10; }

template<int N> __device__ __forceinline__ void wg_rs(float (&d)[64], uint32_t a0, uint32_t a1, uint32_t a2, uint32_t a3, uint64_t db);
template<> __device__ __forceinline__ void wg_rs<128>(float (&d)[64], uint32_t a0, uint32_t a1, uint32_t a2, uint32_t a3, uint64_t db) {
  asm volatile("{.reg .pred p; setp.ne.b32 p, 1, 0; wgmma.mma_async.sync.aligned.m64n128k16.f32.bf16.bf16 {%0,%1,%2,%3,%4,%5,%6,%7,%8,%9,%10,%11,%12,%13,%14,%15,%16,%17,%18,%19,%20,%21,%22,%23,%24,%25,%26,%27,%28,%29,%30,%31,%32,%33,%34,%35,%36,%37,%38,%39,%40,%41,%42,%43,%44,%45,%46,%47,%48,%49,%50,%51,%52,%53,%54,%55,%56,%57,%58,%59,%60,%61,%62,%63}, {%64,%65,%66,%67}, %68, p, 1, 1, 0;}"
    : "+f"(d[0]),"+f"(d[1]),"+f"(d[2]),"+f"(d[3]),"+f"(d[4]),"+f"(d[5]),"+f"(d[6]),"+f"(d[7]),"+f"(d[8]),"+f"(d[9]),"+f"(d[10]),"+f"(d[11]),"+f"(d[12]),"+f"(d[13]),"+f"(d[14]),"+f"(d[15]),"+f"(d[16]),"+f"(d[17]),"+f"(d[18]),"+f"(d[19]),"+f"(d[20]),"+f"(d[21]),"+f"(d[22]),"+f"(d[23]),"+f"(d[24]),"+f"(d[25]),"+f"(d[26]),"+f"(d[27]),"+f"(d[28]),"+f"(d[29]),"+f"(d[30]),"+f"(d[31]),"+f"(d[32]),"+f"(d[33]),"+f"(d[34]),"+f"(d[35]),"+f"(d[36]),"+f"(d[37]),"+f"(d[38]),"+f"(d[39]),"+f"(d[40]),"+f"(d[41]),"+f"(d[42]),"+f"(d[43]),"+f"(d[44]),"+f"(d[45]),"+f"(d[46]),"+f"(d[47]),"+f"(d[48]),"+f"(d[49]),"+f"(d[50]),"+f"(d[51]),"+f"(d[52]),"+f"(d[53]),"+f"(d[54]),"+f"(d[55]),"+f"(d[56]),"+f"(d[57]),"+f"(d[58]),"+f"(d[59]),"+f"(d[60]),"+f"(d[61]),"+f"(d[62]),"+f"(d[63]) : "r"(a0), "r"(a1), "r"(a2), "r"(a3), "l"(db));
}
template<> __device__ __forceinline__ void wg_rs<120>(float (&d)[64], uint32_t a0, uint32_t a1, uint32_t a2, uint32_t a3, uint64_t db) {
  asm volatile("{.reg .pred p; setp.ne.b32 p, 1, 0; wgmma.mma_async.sync.aligned.m64n120k16.f32.bf16.bf16 {%0,%1,%2,%3,%4,%5,%6,%7,%8,%9,%10,%11,%12,%13,%14,%15,%16,%17,%18,%19,%20,%21,%22,%23,%24,%25,%26,%27,%28,%29,%30,%31,%32,%33,%34,%35,%36,%37,%38,%39,%40,%41,%42,%43,%44,%45,%46,%47,%48,%49,%50,%51,%52,%53,%54,%55,%56,%57,%58,%59}, {%60,%61,%62,%63}, %64, p, 1, 1, 0;}"
    : "+f"(d[0]),"+f"(d[1]),"+f"(d[2]),"+f"(d[3]),"+f"(d[4]),"+f"(d[5]),"+f"(d[6]),"+f"(d[7]),"+f"(d[8]),"+f"(d[9]),"+f"(d[10]),"+f"(d[11]),"+f"(d[12]),"+f"(d[13]),"+f"(d[14]),"+f"(d[15]),"+f"(d[16]),"+f"(d[17]),"+f"(d[18]),"+f"(d[19]),"+f"(d[20]),"+f"(d[21]),"+f"(d[22]),"+f"(d[23]),"+f"(d[24]),"+f"(d[25]),"+f"(d[26]),"+f"(d[27]),"+f"(d[28]),"+f"(d[29]),"+f"(d[30]),"+f"(d[31]),"+f"(d[32]),"+f"(d[33]),"+f"(d[34]),"+f"(d[35]),"+f"(d[36]),"+f"(d[37]),"+f"(d[38]),"+f"(d[39]),"+f"(d[40]),"+f"(d[41]),"+f"(d[42]),"+f"(d[43]),"+f"(d[44]),"+f"(d[45]),"+f"(d[46]),"+f"(d[47]),"+f"(d[48]),"+f"(d[49]),"+f"(d[50]),"+f"(d[51]),"+f"(d[52]),"+f"(d[53]),"+f"(d[54]),"+f"(d[55]),"+f"(d[56]),"+f"(d[57]),"+f"(d[58]),"+f"(d[59]) : "r"(a0), "r"(a1), "r"(a2), "r"(a3), "l"(db));
}
template<> __device__ __forceinline__ void wg_rs<112>(float (&d)[64], uint32_t a0, uint32_t a1, uint32_t a2, uint32_t a3, uint64_t db) {
  asm volatile("{.reg .pred p; setp.ne.b32 p, 1, 0; wgmma.mma_async.sync.aligned.m64n112k16.f32.bf16.bf16 {%0,%1,%2,%3,%4,%5,%6,%7,%8,%9,%10,%11,%12,%13,%14,%15,%16,%17,%18,%19,%20,%21,%22,%23,%24,%25,%26,%27,%28,%29,%30,%31,%32,%33,%34,%35,%36,%37,%38,%39,%40,%41,%42,%43,%44,%45,%46,%47,%48,%49,%50,%51,%52,%53,%54,%55}, {%56,%57,%58,%59}, %60, p, 1, 1, 0;}"
    : "+f"(d[0]),"+f"(d[1]),"+f"(d[2]),"+f"(d[3]),"+f"(d[4]),"+f"(d[5]),"+f"(d[6]),"+f"(d[7]),"+f"(d[8]),"+f"(d[9]),"+f"(d[10]),"+f"(d[11]),"+f"(d[12]),"+f"(d[13]),"+f"(d[14]),"+f"(d[15]),"+f"(d[16]),"+f"(d[17]),"+f"(d[18]),"+f"(d[19]),"+f"(d[20]),"+f"(d[21]),"+f"(d[22]),"+f"(d[23]),"+f"(d[24]),"+f"(d[25]),"+f"(d[26]),"+f"(d[27]),"+f"(d[28]),"+f"(d[29]),"+f"(d[30]),"+f"(d[31]),"+f"(d[32]),"+f"(d[33]),"+f"(d[34]),"+f"(d[35]),"+f"(d[36]),"+f"(d[37]),"+f"(d[38]),"+f"(d[39]),"+f"(d[40]),"+f"(d[41]),"+f"(d[42]),"+f"(d[43]),"+f"(d[44]),"+f"(d[45]),"+f"(d[46]),"+f"(d[47]),"+f"(d[48]),"+f"(d[49]),"+f"(d[50]),"+f"(d[51]),"+f"(d[52]),"+f"(d[53]),"+f"(d[54]),"+f"(d[55]) : "r"(a0), "r"(a1), "r"(a2), "r"(a3), "l"(db));
}
template<> __device__ __forceinline__ void wg_rs<104>(float (&d)[64], uint32_t a0, uint32_t a1, uint32_t a2, uint32_t a3, uint64_t db) {
  asm volatile("{.reg .pred p; setp.ne.b32 p, 1, 0; wgmma.mma_async.sync.aligned.m64n104k16.f32.bf16.bf16 {%0,%1,%2,%3,%4,%5,%6,%7,%8,%9,%10,%11,%12,%13,%14,%15,%16,%17,%18,%19,%20,%21,%22,%23,%24,%25,%26,%27,%28,%29,%30,%31,%32,%33,%34,%35,%36,%37,%38,%39,%40,%41,%42,%43,%44,%45,%46,%47,%48,%49,%50,%51}, {%52,%53,%54,%55}, %56, p, 1, 1, 0;}"
    : "+f"(d[0]),"+f"(d[1]),"+f"(d[2]),"+f"(d[3]),"+f"(d[4]),"+f"(d[5]),"+f"(d[6]),"+f"(d[7]),"+f"(d[8]),"+f"(d[9]),"+f"(d[10]),"+f"(d[11]),"+f"(d[12]),"+f"(d[13]),"+f"(d[14]),"+f"(d[15]),"+f"(d[16]),"+f"(d[17]),"+f"(d[18]),"+f"(d[19]),"+f"(d[20]),"+f"(d[21]),"+f"(d[22]),"+f"(d[23]),"+f"(d[24]),"+f"(d[25]),"+f"(d[26]),"+f"(d[27]),"+f"(d[28]),"+f"(d[29]),"+f"(d[30]),"+f"(d[31]),"+f"(d[32]),"+f"(d[33]),"+f"(d[34]),"+f"(d[35]),"+f"(d[36]),"+f"(d[37]),"+f"(d[38]),"+f"(d[39]),"+f"(d[40]),"+f"(d[41]),"+f"(d[42]),"+f"(d[43]),"+f"(d[44]),"+f"(d[45]),"+f"(d[46]),"+f"(d[47]),"+f"(d[48]),"+f"(d[49]),"+f"(d[50]),"+f"(d[51]) : "r"(a0), "r"(a1), "r"(a2), "r"(a3), "l"(db));
}
template<> __device__ __forceinline__ void wg_rs<96>(float (&d)[64], uint32_t a0, uint32_t a1, uint32_t a2, uint32_t a3, uint64_t db) {
  asm volatile("{.reg .pred p; setp.ne.b32 p, 1, 0; wgmma.mma_async.sync.aligned.m64n96k16.f32.bf16.bf16 {%0,%1,%2,%3,%4,%5,%6,%7,%8,%9,%10,%11,%12,%13,%14,%15,%16,%17,%18,%19,%20,%21,%22,%23,%24,%25,%26,%27,%28,%29,%30,%31,%32,%33,%34,%35,%36,%37,%38,%39,%40,%41,%42,%43,%44,%45,%46,%47}, {%48,%49,%50,%51}, %52, p, 1, 1, 0;}"
    : "+f"(d[0]),"+f"(d[1]),"+f"(d[2]),"+f"(d[3]),"+f"(d[4]),"+f"(d[5]),"+f"(d[6]),"+f"(d[7]),"+f"(d[8]),"+f"(d[9]),"+f"(d[10]),"+f"(d[11]),"+f"(d[12]),"+f"(d[13]),"+f"(d[14]),"+f"(d[15]),"+f"(d[16]),"+f"(d[17]),"+f"(d[18]),"+f"(d[19]),"+f"(d[20]),"+f"(d[21]),"+f"(d[22]),"+f"(d[23]),"+f"(d[24]),"+f"(d[25]),"+f"(d[26]),"+f"(d[27]),"+f"(d[28]),"+f"(d[29]),"+f"(d[30]),"+f"(d[31]),"+f"(d[32]),"+f"(d[33]),"+f"(d[34]),"+f"(d[35]),"+f"(d[36]),"+f"(d[37]),"+f"(d[38]),"+f"(d[39]),"+f"(d[40]),"+f"(d[41]),"+f"(d[42]),"+f"(d[43]),"+f"(d[44]),"+f"(d[45]),"+f"(d[46]),"+f"(d[47]) : "r"(a0), "r"(a1), "r"(a2), "r"(a3), "l"(db));
}
template<> __device__ __forceinline__ void wg_rs<88>(float (&d)[64], uint32_t a0, uint32_t a1, uint32_t a2, uint32_t a3, uint64_t db) {
  asm volatile("{.reg .pred p; setp.ne.b32 p, 1, 0; wgmma.mma_async.sync.aligned.m64n88k16.f32.bf16.bf16 {%0,%1,%2,%3,%4,%5,%6,%7,%8,%9,%10,%11,%12,%13,%14,%15,%16,%17,%18,%19,%20,%21,%22,%23,%24,%25,%26,%27,%28,%29,%30,%31,%32,%33,%34,%35,%36,%37,%38,%39,%40,%41,%42,%43}, {%44,%45,%46,%47}, %48, p, 1, 1, 0;}"
    : "+f"(d[0]),"+f"(d[1]),"+f"(d[2]),"+f"(d[3]),"+f"(d[4]),"+f"(d[5]),"+f"(d[6]),"+f"(d[7]),"+f"(d[8]),"+f"(d[9]),"+f"(d[10]),"+f"(d[11]),"+f"(d[12]),"+f"(d[13]),"+f"(d[14]),"+f"(d[15]),"+f"(d[16]),"+f"(d[17]),"+f"(d[18]),"+f"(d[19]),"+f"(d[20]),"+f"(d[21]),"+f"(d[22]),"+f"(d[23]),"+f"(d[24]),"+f"(d[25]),"+f"(d[26]),"+f"(d[27]),"+f"(d[28]),"+f"(d[29]),"+f"(d[30]),"+f"(d[31]),"+f"(d[32]),"+f"(d[33]),"+f"(d[34]),"+f"(d[35]),"+f"(d[36]),"+f"(d[37]),"+f"(d[38]),"+f"(d[39]),"+f"(d[40]),"+f"(d[41]),"+f"(d[42]),"+f"(d[43]) : "r"(a0), "r"(a1), "r"(a2), "r"(a3), "l"(db));
}
template<> __device__ __forceinline__ void wg_rs<80>(float (&d)[64], uint32_t a0, uint32_t a1, uint32_t a2, uint32_t a3, uint64_t db) {
  asm volatile("{.reg .pred p; setp.ne.b32 p, 1, 0; wgmma.mma_async.sync.aligned.m64n80k16.f32.bf16.bf16 {%0,%1,%2,%3,%4,%5,%6,%7,%8,%9,%10,%11,%12,%13,%14,%15,%16,%17,%18,%19,%20,%21,%22,%23,%24,%25,%26,%27,%28,%29,%30,%31,%32,%33,%34,%35,%36,%37,%38,%39}, {%40,%41,%42,%43}, %44, p, 1, 1, 0;}"
    : "+f"(d[0]),"+f"(d[1]),"+f"(d[2]),"+f"(d[3]),"+f"(d[4]),"+f"(d[5]),"+f"(d[6]),"+f"(d[7]),"+f"(d[8]),"+f"(d[9]),"+f"(d[10]),"+f"(d[11]),"+f"(d[12]),"+f"(d[13]),"+f"(d[14]),"+f"(d[15]),"+f"(d[16]),"+f"(d[17]),"+f"(d[18]),"+f"(d[19]),"+f"(d[20]),"+f"(d[21]),"+f"(d[22]),"+f"(d[23]),"+f"(d[24]),"+f"(d[25]),"+f"(d[26]),"+f"(d[27]),"+f"(d[28]),"+f"(d[29]),"+f"(d[30]),"+f"(d[31]),"+f"(d[32]),"+f"(d[33]),"+f"(d[34]),"+f"(d[35]),"+f"(d[36]),"+f"(d[37]),"+f"(d[38]),"+f"(d[39]) : "r"(a0), "r"(a1), "r"(a2), "r"(a3), "l"(db));
}
template<> __device__ __forceinline__ void wg_rs<72>(float (&d)[64], uint32_t a0, uint32_t a1, uint32_t a2, uint32_t a3, uint64_t db) {
  asm volatile("{.reg .pred p; setp.ne.b32 p, 1, 0; wgmma.mma_async.sync.aligned.m64n72k16.f32.bf16.bf16 {%0,%1,%2,%3,%4,%5,%6,%7,%8,%9,%10,%11,%12,%13,%14,%15,%16,%17,%18,%19,%20,%21,%22,%23,%24,%25,%26,%27,%28,%29,%30,%31,%32,%33,%34,%35}, {%36,%37,%38,%39}, %40, p, 1, 1, 0;}"
    : "+f"(d[0]),"+f"(d[1]),"+f"(d[2]),"+f"(d[3]),"+f"(d[4]),"+f"(d[5]),"+f"(d[6]),"+f"(d[7]),"+f"(d[8]),"+f"(d[9]),"+f"(d[10]),"+f"(d[11]),"+f"(d[12]),"+f"(d[13]),"+f"(d[14]),"+f"(d[15]),"+f"(d[16]),"+f"(d[17]),"+f"(d[18]),"+f"(d[19]),"+f"(d[20]),"+f"(d[21]),"+f"(d[22]),"+f"(d[23]),"+f"(d[24]),"+f"(d[25]),"+f"(d[26]),"+f"(d[27]),"+f"(d[28]),"+f"(d[29]),"+f"(d[30]),"+f"(d[31]),"+f"(d[32]),"+f"(d[33]),"+f"(d[34]),"+f"(d[35]) : "r"(a0), "r"(a1), "r"(a2), "r"(a3), "l"(db));
}
template<> __device__ __forceinline__ void wg_rs<64>(float (&d)[64], uint32_t a0, uint32_t a1, uint32_t a2, uint32_t a3, uint64_t db) {
  asm volatile("{.reg .pred p; setp.ne.b32 p, 1, 0; wgmma.mma_async.sync.aligned.m64n64k16.f32.bf16.bf16 {%0,%1,%2,%3,%4,%5,%6,%7,%8,%9,%10,%11,%12,%13,%14,%15,%16,%17,%18,%19,%20,%21,%22,%23,%24,%25,%26,%27,%28,%29,%30,%31}, {%32,%33,%34,%35}, %36, p, 1, 1, 0;}"
    : "+f"(d[0]),"+f"(d[1]),"+f"(d[2]),"+f"(d[3]),"+f"(d[4]),"+f"(d[5]),"+f"(d[6]),"+f"(d[7]),"+f"(d[8]),"+f"(d[9]),"+f"(d[10]),"+f"(d[11]),"+f"(d[12]),"+f"(d[13]),"+f"(d[14]),"+f"(d[15]),"+f"(d[16]),"+f"(d[17]),"+f"(d[18]),"+f"(d[19]),"+f"(d[20]),"+f"(d[21]),"+f"(d[22]),"+f"(d[23]),"+f"(d[24]),"+f"(d[25]),"+f"(d[26]),"+f"(d[27]),"+f"(d[28]),"+f"(d[29]),"+f"(d[30]),"+f"(d[31]) : "r"(a0), "r"(a1), "r"(a2), "r"(a3), "l"(db));
}
__device__ __forceinline__ void wg_rs_first(float (&d)[64], uint32_t a0, uint32_t a1, uint32_t a2, uint32_t a3, uint64_t db) {
  asm volatile("{.reg .pred p; setp.ne.b32 p, 0, 0; wgmma.mma_async.sync.aligned.m64n128k16.f32.bf16.bf16 {%0,%1,%2,%3,%4,%5,%6,%7,%8,%9,%10,%11,%12,%13,%14,%15,%16,%17,%18,%19,%20,%21,%22,%23,%24,%25,%26,%27,%28,%29,%30,%31,%32,%33,%34,%35,%36,%37,%38,%39,%40,%41,%42,%43,%44,%45,%46,%47,%48,%49,%50,%51,%52,%53,%54,%55,%56,%57,%58,%59,%60,%61,%62,%63}, {%64,%65,%66,%67}, %68, p, 1, 1, 0;}"
    : "=f"(d[0]),"=f"(d[1]),"=f"(d[2]),"=f"(d[3]),"=f"(d[4]),"=f"(d[5]),"=f"(d[6]),"=f"(d[7]),"=f"(d[8]),"=f"(d[9]),"=f"(d[10]),"=f"(d[11]),"=f"(d[12]),"=f"(d[13]),"=f"(d[14]),"=f"(d[15]),"=f"(d[16]),"=f"(d[17]),"=f"(d[18]),"=f"(d[19]),"=f"(d[20]),"=f"(d[21]),"=f"(d[22]),"=f"(d[23]),"=f"(d[24]),"=f"(d[25]),"=f"(d[26]),"=f"(d[27]),"=f"(d[28]),"=f"(d[29]),"=f"(d[30]),"=f"(d[31]),"=f"(d[32]),"=f"(d[33]),"=f"(d[34]),"=f"(d[35]),"=f"(d[36]),"=f"(d[37]),"=f"(d[38]),"=f"(d[39]),"=f"(d[40]),"=f"(d[41]),"=f"(d[42]),"=f"(d[43]),"=f"(d[44]),"=f"(d[45]),"=f"(d[46]),"=f"(d[47]),"=f"(d[48]),"=f"(d[49]),"=f"(d[50]),"=f"(d[51]),"=f"(d[52]),"=f"(d[53]),"=f"(d[54]),"=f"(d[55]),"=f"(d[56]),"=f"(d[57]),"=f"(d[58]),"=f"(d[59]),"=f"(d[60]),"=f"(d[61]),"=f"(d[62]),"=f"(d[63]) : "r"(a0), "r"(a1), "r"(a2), "r"(a3), "l"(db));
}
__device__ __forceinline__ void wg_tt128(float (&d)[64], uint64_t da, uint64_t db, int sc) {
  asm volatile("{.reg .pred p; setp.ne.b32 p, %66, 0; wgmma.mma_async.sync.aligned.m64n128k16.f32.bf16.bf16 {%0,%1,%2,%3,%4,%5,%6,%7,%8,%9,%10,%11,%12,%13,%14,%15,%16,%17,%18,%19,%20,%21,%22,%23,%24,%25,%26,%27,%28,%29,%30,%31,%32,%33,%34,%35,%36,%37,%38,%39,%40,%41,%42,%43,%44,%45,%46,%47,%48,%49,%50,%51,%52,%53,%54,%55,%56,%57,%58,%59,%60,%61,%62,%63}, %64, %65, p, 1, 1, 1, 1;}"
    : "+f"(d[0]),"+f"(d[1]),"+f"(d[2]),"+f"(d[3]),"+f"(d[4]),"+f"(d[5]),"+f"(d[6]),"+f"(d[7]),"+f"(d[8]),"+f"(d[9]),"+f"(d[10]),"+f"(d[11]),"+f"(d[12]),"+f"(d[13]),"+f"(d[14]),"+f"(d[15]),"+f"(d[16]),"+f"(d[17]),"+f"(d[18]),"+f"(d[19]),"+f"(d[20]),"+f"(d[21]),"+f"(d[22]),"+f"(d[23]),"+f"(d[24]),"+f"(d[25]),"+f"(d[26]),"+f"(d[27]),"+f"(d[28]),"+f"(d[29]),"+f"(d[30]),"+f"(d[31]),"+f"(d[32]),"+f"(d[33]),"+f"(d[34]),"+f"(d[35]),"+f"(d[36]),"+f"(d[37]),"+f"(d[38]),"+f"(d[39]),"+f"(d[40]),"+f"(d[41]),"+f"(d[42]),"+f"(d[43]),"+f"(d[44]),"+f"(d[45]),"+f"(d[46]),"+f"(d[47]),"+f"(d[48]),"+f"(d[49]),"+f"(d[50]),"+f"(d[51]),"+f"(d[52]),"+f"(d[53]),"+f"(d[54]),"+f"(d[55]),"+f"(d[56]),"+f"(d[57]),"+f"(d[58]),"+f"(d[59]),"+f"(d[60]),"+f"(d[61]),"+f"(d[62]),"+f"(d[63]) : "l"(da), "l"(db), "r"(sc));
}
__device__ __forceinline__ void wg_tt64(float (&d)[64], uint64_t da, uint64_t db, int sc) {
  asm volatile("{.reg .pred p; setp.ne.b32 p, %34, 0; wgmma.mma_async.sync.aligned.m64n64k16.f32.bf16.bf16 {%0,%1,%2,%3,%4,%5,%6,%7,%8,%9,%10,%11,%12,%13,%14,%15,%16,%17,%18,%19,%20,%21,%22,%23,%24,%25,%26,%27,%28,%29,%30,%31}, %32, %33, p, 1, 1, 1, 1;}"
    : "+f"(d[0]),"+f"(d[1]),"+f"(d[2]),"+f"(d[3]),"+f"(d[4]),"+f"(d[5]),"+f"(d[6]),"+f"(d[7]),"+f"(d[8]),"+f"(d[9]),"+f"(d[10]),"+f"(d[11]),"+f"(d[12]),"+f"(d[13]),"+f"(d[14]),"+f"(d[15]),"+f"(d[16]),"+f"(d[17]),"+f"(d[18]),"+f"(d[19]),"+f"(d[20]),"+f"(d[21]),"+f"(d[22]),"+f"(d[23]),"+f"(d[24]),"+f"(d[25]),"+f"(d[26]),"+f"(d[27]),"+f"(d[28]),"+f"(d[29]),"+f"(d[30]),"+f"(d[31]) : "l"(da), "l"(db), "r"(sc));
}
__device__ __forceinline__ void wg_tt32(float (&d)[64], uint64_t da, uint64_t db, int sc) {
  asm volatile("{.reg .pred p; setp.ne.b32 p, %18, 0; wgmma.mma_async.sync.aligned.m64n32k16.f32.bf16.bf16 {%0,%1,%2,%3,%4,%5,%6,%7,%8,%9,%10,%11,%12,%13,%14,%15}, %16, %17, p, 1, 1, 1, 1;}"
    : "+f"(d[0]),"+f"(d[1]),"+f"(d[2]),"+f"(d[3]),"+f"(d[4]),"+f"(d[5]),"+f"(d[6]),"+f"(d[7]),"+f"(d[8]),"+f"(d[9]),"+f"(d[10]),"+f"(d[11]),"+f"(d[12]),"+f"(d[13]),"+f"(d[14]),"+f"(d[15]) : "l"(da), "l"(db), "r"(sc));
}
__device__ __forceinline__ void wg_g1(float (&d)[88], uint64_t da, uint64_t db, int sc) {
  asm volatile("{.reg .pred p; setp.ne.b32 p, %90, 0; wgmma.mma_async.sync.aligned.m64n176k16.f32.bf16.bf16 {%0,%1,%2,%3,%4,%5,%6,%7,%8,%9,%10,%11,%12,%13,%14,%15,%16,%17,%18,%19,%20,%21,%22,%23,%24,%25,%26,%27,%28,%29,%30,%31,%32,%33,%34,%35,%36,%37,%38,%39,%40,%41,%42,%43,%44,%45,%46,%47,%48,%49,%50,%51,%52,%53,%54,%55,%56,%57,%58,%59,%60,%61,%62,%63,%64,%65,%66,%67,%68,%69,%70,%71,%72,%73,%74,%75,%76,%77,%78,%79,%80,%81,%82,%83,%84,%85,%86,%87}, %88, %89, p, 1, 1, 1, 0;}"
    : "+f"(d[0]),"+f"(d[1]),"+f"(d[2]),"+f"(d[3]),"+f"(d[4]),"+f"(d[5]),"+f"(d[6]),"+f"(d[7]),"+f"(d[8]),"+f"(d[9]),"+f"(d[10]),"+f"(d[11]),"+f"(d[12]),"+f"(d[13]),"+f"(d[14]),"+f"(d[15]),"+f"(d[16]),"+f"(d[17]),"+f"(d[18]),"+f"(d[19]),"+f"(d[20]),"+f"(d[21]),"+f"(d[22]),"+f"(d[23]),"+f"(d[24]),"+f"(d[25]),"+f"(d[26]),"+f"(d[27]),"+f"(d[28]),"+f"(d[29]),"+f"(d[30]),"+f"(d[31]),"+f"(d[32]),"+f"(d[33]),"+f"(d[34]),"+f"(d[35]),"+f"(d[36]),"+f"(d[37]),"+f"(d[38]),"+f"(d[39]),"+f"(d[40]),"+f"(d[41]),"+f"(d[42]),"+f"(d[43]),"+f"(d[44]),"+f"(d[45]),"+f"(d[46]),"+f"(d[47]),"+f"(d[48]),"+f"(d[49]),"+f"(d[50]),"+f"(d[51]),"+f"(d[52]),"+f"(d[53]),"+f"(d[54]),"+f"(d[55]),"+f"(d[56]),"+f"(d[57]),"+f"(d[58]),"+f"(d[59]),"+f"(d[60]),"+f"(d[61]),"+f"(d[62]),"+f"(d[63]),"+f"(d[64]),"+f"(d[65]),"+f"(d[66]),"+f"(d[67]),"+f"(d[68]),"+f"(d[69]),"+f"(d[70]),"+f"(d[71]),"+f"(d[72]),"+f"(d[73]),"+f"(d[74]),"+f"(d[75]),"+f"(d[76]),"+f"(d[77]),"+f"(d[78]),"+f"(d[79]),"+f"(d[80]),"+f"(d[81]),"+f"(d[82]),"+f"(d[83]),"+f"(d[84]),"+f"(d[85]),"+f"(d[86]),"+f"(d[87]) : "l"(da), "l"(db), "r"(sc));
}

struct Params { const __nv_bfloat16 *x, *logA, *Aim, *Cr, *Ci, *logdt, *Dskip, *Wd; uint4* xnT; float2* st; uint2* S; unsigned* flags; };
struct Maps { CUtensorMap x[2], xo, out, wg, wu, wd, hst[2], hld, xt, sld; };

__device__ __forceinline__ void conv_channel(uint32_t cb, int w, int lane, uint32_t (&res)[8], uint32_t sig, int sidx) {
    const int q = lane & 3, g = lane >> 2, gam = g >> 2;
    float acc[64];
    uint2 a[17][2];
    const uint32_t t0 = cb + CH_T + (uint32_t)(14 + 4 * w + (g & 3) - 2 * q) * 280u + gam * 8;
#define LDA(s0, s1) _Pragma("unroll") for (int s = s0; s < s1; s++) { a[s][0] = lds64(t0 + s * 16); a[s][1] = lds64(t0 - 8 * 280 + s * 16); }
#define CT(N, s) wg_rs<N>(acc, a[s][0].x, a[s][0].y, a[s][1].x, a[s][1].y, dU + 4 * (s))
    const uint64_t dU = mkdesc(cb + CH_U, UPLANE, 128, 0);
    LDA(0, 17)
    if (sig) { fence_async_smem(); mbar_arrive(sig); }
    WG_FENCE();
    if (w == 0) STAMP2(52 + 3 * sidx);
    wg_rs_first(acc, a[0][0].x, a[0][0].y, a[0][1].x, a[0][1].y, dU);
    CT(128, 1); CT(120, 2); CT(120, 3); CT(112, 4); CT(112, 5); CT(104, 6); CT(104, 7); CT(96, 8);
    CT(96, 9); CT(88, 10); CT(88, 11); CT(80, 12); CT(80, 13); CT(72, 14); CT(72, 15); CT(64, 16);
#undef CT
#undef LDA
    wg_tt64(acc, mkdesc(cb + CH_A3, 128, 512, 0), mkdesc(cb + CH_B3, 384, 32, 0), 1);
    wg_tt32(acc, mkdesc(cb + CH_A3 + 256, 128, 512, 0), mkdesc(cb + CH_B3 + 128, 384, 32, 0), 1);
    WG_COMMIT();
    if (w == 0) STAMP2(53 + 3 * sidx);
    WG_WAIT(0);
    fence_acc(acc);
    if (w == 0) STAMP2(54 + 3 * sidx);
    const int src1 = (lane & ~3) | ((q + 1) & 3);
    float E[16][2];
    #pragma unroll
    for (int j = 0; j < 16; j++) {
        const float nxt = (j < 15) ? acc[4 * (j + 1) + 2] : 0.f;
        const float sup = (q == 0) ? nxt : acc[4 * j + 2];
        const float v = __shfl_sync(0xffffffffu, sup, src1);
        E[j][0] = acc[4 * j] + acc[4 * j + 3];
        E[j][1] = acc[4 * j + 1] + v;
    }
    const int src2 = gam ? ((lane & 12) | ((q + 3) & 3)) : (16 | (lane & 12) | ((q + 1) & 3));
    const bool c1 = gam && q != 0, c2 = gam && q == 0;
    #pragma unroll
    for (int a2 = 0; a2 < 8; a2++) {
        float y[2];
        #pragma unroll
        for (int e = 0; e < 2; e++) {
            const float sup = c1 ? E[2 * a2][e] : E[2 * a2 + 1][e];
            const float nxt = (a2 < 7) ? E[2 * a2 + 2][e] : 0.f;
            const float keep = c2 ? nxt : (c1 ? E[2 * a2 + 1][e] : E[2 * a2][e]);
            y[e] = keep + __shfl_sync(0xffffffffu, sup, src2);
        }
        res[a2] = pack2(y[1], y[0]);
    }
}

__device__ __forceinline__ void consumer(uint32_t sb, int warp, const Params& P, const Maps& M) {
    const int V = warp >> 2, w = warp & 3, lane = threadIdx.x & 31, q = lane & 3, g = lane >> 2;
    const int c = blockIdx.x;
    const uint32_t bars = sb + OFF_BAR, xb = sb + OFF_X + V * 2 * XBUF;
    {
        float ag[88], au[88];
        if (V) mbar_wait(bars + 8 * B_GO, 0);
        define_acc(ag); define_acc(au);
        #pragma unroll 1
        for (int st = 0; st < 8; st++) {
            mbar_wait(bars + 8 * (B_FULLW + (st & 3)), st >> 2);
            mbar_wait(bars + 8 * (B_FULLX + 2 * V + (st & 1)), (st >> 1) & 1);
            STAMP(40 + 8 * V + st);
            const uint64_t dG = mkdesc(sb + OFF_W + (st & 3) * 16384, 0, 1024, 1);
            const uint64_t dX = mkdesc(xb + (st & 1) * XBUF, 16, 1024, 1);
            WG_FENCE();
            #pragma unroll
            for (int k = 0; k < 4; k++) {
                wg_g1(ag, dG + k * 128, dX + k * 2, k ? 1 : st);
                wg_g1(au, dG + 512 + k * 128, dX + k * 2, k ? 1 : st);
            }
            WG_COMMIT();
            WG_WAIT(1);
            if (lane == 0 && st > 0) {
                mbar_arrive(bars + 8 * (B_EMPTYW + ((st - 1) & 3)));
                mbar_arrive(bars + 8 * (B_EMPTYX + 2 * V + ((st - 1) & 1)));
                if (warp < 4 && st == GOST) mbar_arrive(bars + 8 * B_GO);
            }
        }
        WG_WAIT(0);
        fence_acc(ag); fence_acc(au);
        if (lane == 0) { mbar_arrive(bars + 8 * (B_EMPTYW + 3)); mbar_arrive(bars + 8 * (B_EMPTYX + 2 * V + 1)); }
        STAMP(8 * V + 1);
        float cg0 = ag[84], cg1 = ag[86], cu0 = au[84], cu1 = au[86];
        const uint32_t ca = sb + OFF_CSUM + (8 * w + g) * 16;
        if (V == 0) { sts128(ca, FU(cg0), FU(cg1), FU(cu0), FU(cu1)); mbar_arrive(bars + 8 * B_CS); }
        else { mbar_wait(bars + 8 * B_CS, 0); const uint4 t = lds128(ca); cg0 = UF(t.x); cg1 = UF(t.y); cu0 = UF(t.z); cu1 = UF(t.w); }
        mbar_wait(bars + 8 * B_STATS, 0);
        mbar_wait(bars + 8 * (B_EMPTYX + 2 * V), 1);
        STAMP(13 + V);
        const uint32_t hs = xb + (2 * w + ((lane >> 3) & 1)) * (2688 + 128 * V) + (lane >> 4) * 128 + (lane & 7) * 16;
        const uint32_t sa = sb + OFF_ST + (168 * V + 2 * q) * 8;
        uint4 sq[22];
        #pragma unroll
        for (int j = 0; j < 3; j++) sq[j] = lds128(sa + j * 64);
        #pragma unroll
        for (int j = 0; j < 22; j += 2) {
            uint32_t o[4];
            #pragma unroll
            for (int jj = 0; jj < 2; jj++) {
                const uint4 sv = sq[j + jj];
                float hv[4];
                #pragma unroll
                for (int i = 0; i < 4; i++) {
                    const float m = UF((i & 1) ? sv.z : sv.x);
                    const float gh = fmaf(-m, (i & 2) ? cg1 : cg0, ag[4 * (j + jj) + i]) * UF((i & 1) ? sv.w : sv.y);
                    const float p = gh * fmaf(-m, (i & 2) ? cu1 : cu0, au[4 * (j + jj) + i]);
                    hv[i] = fmaf(p, tanh_fast(gh), p);
                }
                o[2 * jj] = pack2(hv[0], hv[1]); o[2 * jj + 1] = pack2(hv[2], hv[3]);
            }
            #pragma unroll
            for (int k = (j ? 3 + 3 * j / 2 : 3); k < 6 + 3 * j / 2 && k < 22; k++) sq[k] = lds128(sa + k * 64);
            uint32_t ad = hs + j * 128;
            if (j == 20 && V == 0 && lane >= 16) ad = xb + 21504 + (lane & 7) * 16;
            stsm4(ad, o[0], o[1], o[2], o[3]);
        }
        if (c >= 128) { fence_async_smem(); mbar_arrive(bars + 8 * (B_EPI + V)); }
        STAMP(8 * V + 2);
    }
    if (c >= 128) return;
    {
        uint32_t r0[8], r1[8];
        #pragma unroll
        for (int i = 0; i < 8; i++) asm volatile("" : "=r"(r1[i]));
        #pragma unroll 1
        for (int e = 0; e < 2; e++) {
            #pragma unroll
            for (int i = 0; i < 8; i++) r0[i] = r1[i];
            mbar_wait(bars + 8 * (B_CONV + 2 * V + e), 0);
            conv_channel(sb + OFF_CONV + (2 * V + e) * CH_STRIDE, w, lane, r1, e ? 0 : bars + 8 * (B_EPI + V), 2 * V + e);
            if (e == 0) STAMP(8 * V + 3);
        }
        const int gam = g >> 2, qq = gam ? ((q + 3) & 3) : q;
        const uint32_t sp = sb + OFF_CONV + V * OFF_SST + ((63 - 4 * gam - qq) * 16 + 4 * (w ^ (3 - qq)) + (g & 3)) * 8;
        bar_sync(3 + V);
        #pragma unroll
        for (int a2 = 0; a2 < 8; a2++) sts64(sp - a2 * 1024, r0[a2], r1[a2]);
        fence_async_smem();
        mbar_arrive(bars + 8 * (B_SIG + V));
        STAMP(8 * V + 4);
    }
    if (V == 1) return;
    {
        const int tau = c >> 2, dg = c & 3;
        const uint32_t row = 8 * (w & 1) + 32 * (w >> 1);
        float acc[64];
        define_acc(acc);
        const float rr0 = __ldcg(&P.st[64 * tau + row + g].y), rr1 = __ldcg(&P.st[64 * tau + row + g + 16].y);
        mbar_wait(bars + 8 * B_FULLD, 0);
        STAMP(5);
        uint64_t dB = mkdesc(sb + wd_slot(0), 8192, 1024, 1), dA = mkdesc(sb + h_slot(0), 1024, 128, 0);
        #pragma unroll 1
        for (int st = 0; st < 21; st++) {
            WG_FENCE();
            wg_tt128(acc, dA, dB, st);
            wg_tt128(acc, dA + 128, dB + 128, 1);
            wg_tt128(acc, dA + 256, dB + 256, 1);
            wg_tt128(acc, dA + 384, dB + 384, 1);
            WG_COMMIT();
            const int sd = (st + 1) & 7;
            const uint32_t nb = bars + 8 * (B_FULLD + sd), np = ((st + 1) >> 3) & 1;
            uint32_t ro = st == 15 ? 8 * B_CH0 : 8 * (B_EMPTYD + ((st - 1) & 7)), m = lane == 0 && st > 0, ok;
            dB = mkdesc(sb + wd_slot(sd), 8192, 1024, 1); dA = mkdesc(sb + h_slot(sd), 1024, 128, 0);
            asm volatile("{.reg .pred p; mbarrier.test_wait.parity.shared::cta.b64 p, [%5], %6; vote.sync.all.pred p, p, -1; selp.u32 %0, 1, 0, p;}"
                : "=r"(ok), "+l"(dA), "+l"(dB), "+r"(ro), "+r"(m) : "r"(nb), "r"(np) : "memory");
            WG_WAIT(1);
            asm volatile("{.reg .pred p; setp.ne.u32 p, %1, 0; @p mbarrier.arrive.shared::cta.b64 _, [%0];}" :: "r"(bars + ro), "r"(m) : "memory");
            if (!ok) mbar_wait(nb, np);
            if (w == 0) STAMP2(20 + st);
        }
        WG_FENCE();
        wg_tt128(acc, dA, dB, 1);
        wg_tt128(acc, dA + 128, dB + 128, 1);
        WG_COMMIT();
        mbar_wait(bars + 8 * B_XO, 0);
        const uint32_t xo = sb + OFF_CONV + (row + (lane & 7) + 16 * ((lane >> 3) & 1)) * 128;
        const uint32_t so = sb + wd_slot(6) + (w >> 1) * 8192 + q * 256 + (g & 1) * 8;
        const uint32_t sx = (4 * (w & 1) + (g >> 1)) ^ (2 * q) ^ (2 * ((2 * tau + (w >> 1)) & 3));
        uint32_t xr[8][4];
        uint2 sv[16];
        #pragma unroll
        for (int j = 0; j < 16; j += 2) {
            ldsm4(xr[j >> 1], xo + (j >> 3) * 8192 + ((((j & 7) + (lane >> 4)) ^ (lane & 7)) << 4));
            sv[j] = lds64(so + j * 512 + (sx << 4));
            sv[j + 1] = lds64(so + j * 512 + 128 + ((sx ^ 1) << 4));
        }
        WG_WAIT(0);
        fence_acc(acc);
        STAMP(6);
        #pragma unroll
        for (int j = 0; j < 16; j += 2) {
            #pragma unroll
            for (int i = 0; i < 4; i++) {
                const int jj = j + (i >> 1), hh = i & 1;
                const float f0 = acc[4 * jj + 2 * hh] * (hh ? rr1 : rr0), f1 = acc[4 * jj + 2 * hh + 1] * (hh ? rr1 : rr0);
                const uint32_t G = pack2(fmaf(f0, tanh_fast(f0), f0), fmaf(f1, tanh_fast(f1), f1));
                const uint32_t s2 = __byte_perm(sv[jj].x, sv[jj].y, hh ? 0x7632 : 0x5410);
                asm("fma.rn.bf16x2 %0, %1, %2, %0;" : "+r"(xr[j >> 1][i]) : "r"(s2), "r"(G));
            }
            stsm4(xo + (j >> 3) * 8192 + ((((j & 7) + (lane >> 4)) ^ (lane & 7)) << 4), xr[j >> 1][0], xr[j >> 1][1], xr[j >> 1][2], xr[j >> 1][3]);
        }
        fence_async_smem();
        bar_sync(1);
        if (w == 0 && elect_one()) {
            #pragma unroll
            for (int i = 0; i < 2; i++)
                asm volatile("cp.async.bulk.tensor.2d.global.shared::cta.bulk_group [%0, {%2, %3}], [%1];"
                    :: "l"(&M.out), "r"(sb + OFF_CONV + i * 8192), "r"(dg * 128 + 64 * i), "r"(tau * 64) : "memory");
            asm volatile("cp.async.bulk.commit_group; cp.async.bulk.wait_group.read 0;" ::: "memory");
        }
        STAMP(7); GSTAMP(23);
    }
}

__device__ __forceinline__ float2 cexp_p(float re2, float im, float p) {
    float sn, cs;
    const float mag = ex2(re2 * p), th = im * p;
    asm("sin.approx.ftz.f32 %0, %1;" : "=f"(sn) : "f"(th));
    asm("cos.approx.ftz.f32 %0, %1;" : "=f"(cs) : "f"(th));
    return make_float2(mag * cs, mag * sn);
}
struct SsmRaw { unsigned short la, ai, cr, ci, ldt, dsk; };
__device__ __forceinline__ unsigned short ldu16(const void* p) { unsigned short v; asm volatile("ld.global.nc.u16 %0, [%1];" : "=h"(v) : "l"(p)); return v; }
__device__ __forceinline__ float2 cmul(float2 a, float2 b) { return make_float2(fmaf(a.x, b.x, -a.y * b.y), fmaf(a.x, b.y, a.y * b.x)); }
__device__ __forceinline__ float2 csqr(float2 a) { const float t = a.x * a.y; return make_float2(fmaf(a.x, a.x, -a.y * a.y), t + t); }
__device__ __forceinline__ void mma16816(float (&d)[4], const uint32_t (&a)[4], uint32_t b0, uint32_t b1) {
    asm volatile("mma.sync.aligned.m16n8k16.row.col.f32.bf16.bf16.f32 {%0,%1,%2,%3}, {%4,%5,%6,%7}, {%8,%9}, {%0,%1,%2,%3};"
        : "+f"(d[0]), "+f"(d[1]), "+f"(d[2]), "+f"(d[3]) : "r"(a[0]), "r"(a[1]), "r"(a[2]), "r"(a[3]), "r"(b0), "r"(b1));
}

__device__ __forceinline__ void layer_norm(uint32_t sb, uint32_t cb, int w, int lane) {
    const uint32_t bars = sb + OFF_BAR;
    mbar_wait(bars + 8 * B_LNX, 0);
    STAMP(34);
    {
        const uint32_t r0 = cb + CH_LN + (w & 1) * 64 + (lane >> 3) * 1040, ra = r0 + (lane & 7) * 16;
        const float pv = bf_lo(FU(ldsf(r0)));
        float s0 = 0.f, s1 = 0.f, a0 = 0.f, a1 = 0.f;
        #pragma unroll 1
        for (int k = 0; k < 1024; k += 512) {
            uint32_t v[16];
            #pragma unroll
            for (int j = 0; j < 4; j++) *(uint4*)&v[4 * j] = lds128(ra + k + 128 * j);
            #pragma unroll
            for (int i = 0; i < 16; i++) { const float t0 = bf_lo(v[i]) - pv, t1 = bf_hi(v[i]) - pv; s0 += t0; s1 += t1; a0 = fmaf(t0, t0, a0); a1 = fmaf(t1, t1, a1); }
        }
        s0 += s1; a0 += a1;
        #pragma unroll
        for (int o = 4; o; o >>= 1) { s0 += __shfl_xor_sync(0xffffffffu, s0, o); a0 += __shfl_xor_sync(0xffffffffu, a0, o); }
        s0 *= 1.f / DM;
        float sd, ri;
        asm("sqrt.approx.ftz.f32 %0, %1;" : "=f"(sd) : "f"(bf_round(bf_round(fmaxf(fmaf(-s0, s0, a0 * (1.f / DM)), 0.f)) + 1e-5f)));
        asm("rcp.approx.ftz.f32 %0, %1;" : "=f"(ri) : "f"(bf_round(sd)));
        if ((lane & 7) == 0) sts64(sb + OFF_CSUM + (w + 4 * (lane >> 3)) * 8, FU(bf_round(pv + s0)), FU(0.5f * ri));
    }
    STAMP(62);
    bar_sync(2);
    const int r = 4 * ((lane & 7) >> 1) + (lane & 1) + 2 * ((lane >> 3) & 1);
    const uint32_t ad = sb + OFF_CONV + (r & 3) * CH_STRIDE + CH_LN + (r & 1) * 64 + (r >> 2) * 1040 + (16 * w + (lane >> 4)) * 16;
    const uint4 sa = lds128(sb + OFF_CSUM + (lane & 3) * 32), sc = lds128(sb + OFF_CSUM + (lane & 3) * 32 + 16);
    const uint32_t m2[2] = {__byte_perm(sa.x, sa.z, 0x7632), __byte_perm(sc.x, sc.z, 0x7632)};
    const float ri[4] = {2.f * UF(sa.y), 2.f * UF(sa.w), 2.f * UF(sc.y), 2.f * UF(sc.w)};
    #pragma unroll 1
    for (int i = 0; i < 8; i += 4) {
        uint32_t v[4][4];
        #pragma unroll
        for (int j = 0; j < 4; j++)
            asm volatile("ldmatrix.sync.aligned.m8n8.x4.trans.shared.b16 {%0,%1,%2,%3}, [%4];" : "=r"(v[j][0]), "=r"(v[j][1]), "=r"(v[j][2]), "=r"(v[j][3]) : "r"(ad + 32 * (i + j)) : "memory");
        #pragma unroll
        for (int j = 0; j < 4; j++) {
            #pragma unroll
            for (int k = 0; k < 4; k++) {
                uint32_t dv; asm("sub.rn.bf16x2 %0, %1, %2;" : "=r"(dv) : "r"(v[j][k]), "r"(m2[k & 1]));
                v[j][k] = pack2(bf_lo(dv) * ri[2 * (k & 1)], bf_hi(dv) * ri[2 * (k & 1) + 1]);
            }
            sts64(cb + CH_LNT + lane * 8 + (i + j) * 512, v[j][0], v[j][1]); sts64(cb + CH_LNT + lane * 8 + (i + j) * 512 + 256, v[j][2], v[j][3]);
        }
    }
    fence_async_smem();
    mbar_arrive(bars + 8 * B_LN);
    STAMP(16);
}

__device__ __forceinline__ void kernel_gen(uint32_t fs, int lane, const SsmRaw& raw, float (&dacc)[2][3][4]) {
    const float dt = bf_round(ex2(bf_lo(raw.ldt) * 1.4426950408889634f));
    const float re2 = bf_round(ex2(bf_lo(raw.la) * 1.4426950408889634f)) * dt * -1.4426950408889634f, im = bf_lo(raw.ai) * dt;
    const float2 C = make_float2(bf_lo(raw.cr) * (dt + dt), bf_lo(raw.ci) * -(dt + dt));
    STAMP(56);
    const float2 z8 = cexp_p(re2, im, 8.f), y1 = cexp_p(re2, -im, 1.f), y256 = cexp_p(re2, -im, 256.f);
    float2 b0 = make_float2(1.f, 0.f), b1 = cexp_p(re2, im, 64.f), b2 = csqr(b1), b3 = cmul(b2, b1);
    const uint32_t fm = fs + (lane >> 3) * 144 + (lane & 7) * 16;
#define PK(v) pack2((v).x, (v).y)
    #pragma unroll RUNROLL
    for (uint32_t ro = 0; ro < 8 * 144; ro += 144) {
        stsm4(fm + (lane >> 3) * 7 * 144 + ro, PK(b0), PK(b1), PK(b2), PK(b3));
        b0 = cmul(b0, z8); b1 = cmul(b1, z8); b2 = cmul(b2, z8); b3 = cmul(b3, z8);
    }
    const float2 y2 = csqr(y1), y4 = csqr(y2), y8 = make_float2(z8.x, -z8.y);
    const float2 l1 = cmul(C, y1), l2 = cmul(C, y2), l3 = cmul(l1, y2);
    stsm4(fm + 32 * 144, PK(C), PK(l1), PK(l2), PK(l3));
    stsm4(fm + 36 * 144, PK(cmul(C, y4)), PK(cmul(l1, y4)), PK(cmul(l2, y4)), PK(cmul(l3, y4)));
    const float2 t0 = cmul(C, y256), t1 = cmul(t0, y256), t2 = cmul(t1, y256), t3_ = cmul(t2, y256);
    const float2 u1 = cmul(t0, y2), u2 = cmul(u1, y2), u3 = cmul(u2, y2);
    stsm4(fm + 40 * 144, PK(t0), PK(u1), PK(u2), PK(u3));
    stsm4(fm + 44 * 144, PK(t1), PK(cmul(t1, y4)), PK(t2), PK(cmul(t2, y4)));
    const float2 v0 = cmul(t3_, y8), v1 = cmul(v0, y256), v2 = cmul(v1, y256), v3 = cmul(v2, y256);
    stsm4(fm + 48 * 144, PK(v0), PK(v1), PK(v2), PK(v3));
    stsf(fs + lane * 4 + 52 * 144, UF(PK(t3_)));
#undef PK
    STAMP(57);
    const uint32_t lda = fs + (lane & 15) * 144 + (lane & 16);
    const uint32_t ldb = fs + (32 + (lane & 7)) * 144 + (lane >> 3) * 16;
    __syncwarp();
    #pragma unroll 1
    for (int ko = 0; ko < 128; ko += 64) {
        uint32_t b[3][4], a[4][4];
        #pragma unroll
        for (int i = 0; i < 3; i++) ldsm4(b[i], ldb + i * 8 * 144 + ko);
        #pragma unroll
        for (int i = 0; i < 4; i++) ldsm4(a[i], lda + (i & 1) * 16 * 144 + ko + (i >> 1) * 32);
        #pragma unroll
        for (int i = 0; i < 4; i++)
            #pragma unroll
            for (int t = 0; t < 3; t++) mma16816(dacc[i & 1][t], a[i], b[t][i & 2], b[t][(i & 2) + 1]);
    }
    STAMP(58);
}

__device__ __forceinline__ void aux_role(uint32_t sb, int w, float (&dacc)[2][3][4], float dsk, const __nv_bfloat16* x) {
    const int lane = threadIdx.x & 31, q = lane & 3, g = lane >> 2;
    const int c = blockIdx.x;
    const uint32_t bars = sb + OFF_BAR;
    if (c >= 128) { mbar_arrive(bars + 8 * B_LN); return; }
    {
        const uint32_t cb = sb + OFF_CONV + w * CH_STRIDE;
        if (elect_one()) {
            mbar_expect(bars + 8 * B_LNX, 4096);
            #pragma unroll
            for (int i = 0; i < 4; i++)
                bulk_load(cb + CH_LN + (w & 1) * 64 + i * 1040, x + (16 * (c & ~1) + 8 * (c & 1) + 16 + w + 4 * (i & 1) - 8 * (i & 2)) * DM, 1024, bars + 8 * B_LNX);
        }
        mbar_wait(bars + 8 * B_K, 0);
        #pragma unroll 1
        for (uint32_t pa = cb + CH_PART + lane * 16; pa < cb + CH_PART + 9216; pa += 3072) {
            #pragma unroll
            for (int i = 0; i < 6; i++) {
                const uint4 v = lds128(pa + i * 512);
                float* d = &dacc[0][0][0] + 4 * i;
                d[0] += UF(v.x); d[1] += UF(v.y); d[2] += UF(v.z); d[3] += UF(v.w);
            }
        }
        __syncwarp();
        STAMP(18);
        const uint32_t sF = cb + CH_A3, sG = cb + CH_G;
        if (lane == 0) dacc[0][0][0] += dsk;
        if (lane < 10) sts128(sG + 128 + (lane & 1) * 208 + (lane >> 1) * 16, 0, 0, 0, 0);
        const uint32_t f0 = sF + (8 * g + 2 * q) * 4, f1 = sF + ((q < 2) ? 256 + 4 * g + 2 * q : 256 + 2 * g + 64 * q) * 4, st1 = (q < 2) ? 128 : 64;
        const uint32_t ga = sG + ((g & 1) ? 0 : 208) + (63 - (g >> 1) - 32 * q) * 2;
        #pragma unroll
        for (int i = 0; i < 4; i++) {
            const int mu = i >> 1, hh = i & 1;
            sts64(f0 + i * 256, FU(dacc[mu][0][2 * hh]), FU(dacc[mu][0][2 * hh + 1]));
            sts64(f1 + i * st1, FU(dacc[mu][1][2 * hh]), FU(dacc[mu][1][2 * hh + 1]));
            const uint32_t pk = pack2(dacc[mu][2][2 * hh], dacc[mu][2][2 * hh + 1]);
            if (q < 2) { sts16(ga - 8 * i, pk & 0xffff); sts16(ga - 8 * i - 32, pk >> 16); }
        }
        if (lane == 2) stsf(sF + 2048, dacc[0][2][0]);
        STAMP(19);
        layer_norm(sb, cb, w, lane);
        mbar_wait(bars + 8 * B_LNS, 0);
        if (lane < 8) sts128(cb + CH_U + 2048 + (lane & 4) * (UPLANE / 4) + (lane & 3) * 16, 0, 0, 0, 0);
        bar_sync(2);
    }
    const int u = min(lane, 30) - 15, r2 = (u + ((u >> 1) & 1)) >> 1, r4 = (u + 1 + ((u >> 2) & 1)) >> 2, xt = 1024 + 16 * w + u;
    const uint32_t o0 = CH_A3 + 4 * (w == 0 ? u : w == 1 ? 256 + r2 : 256 + 64 * w + r4), ost = w == 0 ? 64 : w == 1 ? 32 : 16;
    const uint32_t oa0 = u >= 0 || w == 3 ? o0 : CH_A3 + 4 * (w == 1 ? 256 + u : w == 2 ? 384 + r2 : 0);
    const uint32_t ot = CH_A3 + 4 * min(512, 256 + ((xt + 1 + ((xt >> 2) & 1)) >> 2));
    const int kap = (lane >> 4) * 8 + ((lane >> 1) & 7), gam = lane & 1, hh = w >> 1, wp = w & 1;
    const uint32_t oa = CH_U + wp * UPLANE + (127 - 4 * kap - 2 * gam - hh) * 16;
    const uint32_t ob = CH_U + (wp ^ 1) * UPLANE + (128 - wp - 4 * kap - 2 * gam - hh) * 16;
    const uint32_t od = CH_A3 + (4 * wp + hh) * 512 + (kap >> 3) * 256 + (kap & 7) * 16 + gam * 8;
    #pragma unroll 1
    for (int k = 0; k < 4; k++) {
        const int ch = 2 * (k & 1) + (k >> 1);
        const uint32_t cb = sb + OFF_CONV + ch * CH_STRIDE;
        {
            float kv[17];
            kv[0] = ldsf(cb + oa0); kv[16] = ldsf(cb + ot);
            #pragma unroll
            for (int s = 1; s < 16; s++) kv[s] = ldsf(cb + o0 + s * ost);
            const int tid = threadIdx.x & 127;
            const uint32_t ga = cb + CH_G + (tid >= 24) * 16 + min(tid, 47) * 8;
            const uint2 x0 = lds64(ga), x1 = lds64(ga + 8);
            if (u < 0 && w == 0) kv[0] = 0.f;
            if (xt > 1028) kv[16] = 0.f;
            uint32_t o[17];
            #pragma unroll
            for (int s = 0; s < 17; s++) o[s] = pack2(kv[s], __shfl_up_sync(0xffffffffu, kv[s], 1));
            if (lane > 0 && lane < 31) {
                const uint32_t ta = cb + CH_T + (lane - 1) * 280;
                #pragma unroll
                for (int s2 = 0; s2 < 8; s2++) sts64(ta + 64 * w + s2 * 8, o[2 * s2], o[2 * s2 + 1]);
                stsf(ta + 256 + 4 * w, UF(o[16]));
            }
            if (tid < 48) sts128(cb + CH_B3 + tid * 16, x0.x, x0.y, x1.x, x1.y);
        }
        mbar_wait(bars + 8 * B_U, 0);
        float p[24];
        const uint2 r0 = lds64(cb + ob + 24), r3 = lds64(cb + oa);
        uint32_t r[8];
        *(uint4*)&r[0] = lds128(cb + oa + 16); *(uint4*)&r[4] = lds128(cb + ob);
        p[0] = 0.f;
        p[1] = bf_lo(r0.x); p[2] = p[1] + bf_hi(r0.x); p[3] = p[2] + bf_lo(r0.y); p[4] = p[3] + bf_hi(r0.y);
        #pragma unroll
        for (int i = 0; i < 8; i++) { p[5 + 2 * i] = p[4 + 2 * i] + bf_lo(r[i]); p[6 + 2 * i] = p[5 + 2 * i] + bf_hi(r[i]); }
        p[21] = p[20] + bf_lo(r3.x); p[22] = p[21] + bf_hi(r3.x); p[23] = p[22] + bf_lo(r3.y);
        bar_sync(2);
        #pragma unroll
        for (int i = 0; i < 8; i += 4) {
            sts64(cb + od + i * 256, pack2(p[i + 9] - p[i], p[i + 10] - p[i + 1]), pack2(p[i + 11] - p[i + 2], p[i + 12] - p[i + 3]));
            sts64(cb + od + i * 256 + 128, pack2(p[i + 16] - p[i + 9], p[i + 17] - p[i + 10]), pack2(p[i + 18] - p[i + 11], p[i + 19] - p[i + 12]));
        }
        fence_async_smem();
        mbar_arrive(bars + 8 * (B_CONV + ch));
        if (k == 0) STAMP(17);
    }
    STAMP(21);
}

__global__ void __launch_bounds__(512, 1)
fused_kernel(const __grid_constant__ Params P, const __grid_constant__ Maps M) {
    extern __shared__ __align__(1024) uint8_t smem_raw[];
    const uint32_t sb = smem_u32(smem_raw);
    const uint32_t bars = sb + OFF_BAR;
    const int warp = __shfl_sync(0xffffffffu, threadIdx.x >> 5, 0);
    const int c = blockIdx.x, tg = c / 22, fb = c - 22 * tg;
    SsmRaw raw;
    {
        const int d = min(4 * c + (warp & 3), DM - 1), o = d * 128 + (warp >> 2) * 32 + (threadIdx.x & 31);
        raw.la = ldu16(P.logA + o); raw.ai = ldu16(P.Aim + o); raw.cr = ldu16(P.Cr + o); raw.ci = ldu16(P.Ci + o);
        raw.ldt = ldu16(P.logdt + d); raw.dsk = ldu16(P.Dskip + d);
    }
    if (elect_one()) {
        if (warp == 0) { STAMP(24); GSTAMP(22); }
        asm volatile("" :: "l"(((const uint64_t*)&P)[warp < 12 ? warp : 0]));
        if (warp < 12) asm volatile("prefetch.tensormap [%0];" :: "l"(&M.x[0] + warp) : "memory");
        #pragma unroll
        for (int k = 0; k < 4; k++) {
            const int i = 16 * k + ((warp + 4) & 15);
            const uint32_t cnt = i >= B_CONV ? 128 : i == B_K ? 12 : ((0xf0ull >> i) & 1) ? 8 : ((0xff0000ull >> i) & 1) ? 2 : ((0x3e00ff00f000ull >> i) & 1) ? 4 : 1;
            asm volatile("mbarrier.init.shared::cta.b64 [%0], %1;" :: "r"(bars + 8 * i), "r"(cnt) : "memory");
        }
        asm volatile("fence.mbarrier_init.release.cluster; fence.proxy.async.shared::cta;" ::: "memory");
        if (warp == 13 || warp == 5) { const uint32_t t0 = clock(); while ((uint32_t)clock() - t0 < DLY1) ; }
        if (warp == 12 || warp == 13) {
            const uint32_t s = warp - 12;
            mbar_expect(bars + 8 * (B_FULLW + s), 16384);
            tma2d(sb + OFF_W + s * 16384, &M.wg, 64 * fb, 64 * s, bars + 8 * (B_FULLW + s));
            tma2d(sb + OFF_W + s * 16384 + 8192, &M.wu, 64 * fb, 64 * s, bars + 8 * (B_FULLW + s));
            STAMP(31);
        } else if (warp == 4 || warp == 5) {
            const uint32_t s = warp - 4;
            mbar_expect(bars + 8 * (B_FULLX + s), 168 * 128);
            tma2d(sb + OFF_X + s * XBUF, &M.x[0], 64 * s, TOKG * tg, bars + 8 * (B_FULLX + s));
        }
        if (sb & 1023) __trap();
    }
    if (warp < 4) sts128(sb + OFF_X + (warp >> 1) * XBUF + 168 * 128 + (threadIdx.x & 63) * 16, 0x3f803f80u, 0x3f803f80u, 0x3f803f80u, 0x3f803f80u);
    float dacc[2][3][4];
    #pragma unroll
    for (int i = 0; i < 24; i++) (&dacc[0][0][0])[i] = 0.f;
    if (c < 128)
        kernel_gen(sb + (warp < 8 ? (warp < 4 ? OFF_W + 32768 : OFF_X + 2 * XBUF) + (warp & 3) * 8064 : OFF_CONV + (warp & 3) * CH_STRIDE + (warp >> 2 & 1) * 8064),
                   threadIdx.x & 31, raw, dacc);
    fence_async_smem();
    __syncthreads();
    if (c < 128 && (warp >> 2) != 2) {
        const uint32_t pa = sb + OFF_CONV + (warp & 3) * CH_STRIDE + CH_PART + min(warp >> 2, 2) * 3072 + (threadIdx.x & 31) * 16;
        #pragma unroll
        for (int i = 0; i < 6; i++) { const float* d = &dacc[0][0][0] + 4 * i; sts128(pa + i * 512, FU(d[0]), FU(d[1]), FU(d[2]), FU(d[3])); }
        __syncwarp();
        if ((threadIdx.x & 31) == 0) mbar_arrive(bars + 8 * B_K);
    }
    if (warp < 8) {
        asm volatile("setmaxnreg.inc.sync.aligned.u32 208;");
        consumer(sb, warp, P, M);
    } else if (warp < 12) {
        asm volatile("setmaxnreg.dec.sync.aligned.u32 72;");
        STAMP(32);
        aux_role(sb, warp - 8, dacc, bf_lo(raw.dsk), P.x);
    } else {
        asm volatile("setmaxnreg.dec.sync.aligned.u32 24;");
        const int tau = c >> 2, dg = c & 3;
        if (elect_one()) {
            if (warp < 15) {
                if (warp == 12) {
                    #pragma unroll 1
                    for (int st = 2; st < 8; st++) {
                        const uint32_t s = st & 3, fb_ = bars + 8 * (B_FULLW + s);
                        mbar_wait(bars + 8 * (B_EMPTYW + s), (st >> 2) ^ 1);
                        mbar_expect(fb_, 16384);
                        tma2d(sb + OFF_W + s * 16384, &M.wg, 64 * fb, 64 * st, fb_);
                        tma2d(sb + OFF_W + s * 16384 + 8192, &M.wu, 64 * fb, 64 * st, fb_);
                    }
                } else {
                    const int V = warp - 13;
                    #pragma unroll 1
                    for (int st = 2 - 2 * V; st < 8; st++) {
                        const uint32_t s = 2 * V + (st & 1);
                        mbar_wait(bars + 8 * (B_EMPTYX + s), ((st >> 1) & 1) ^ 1);
                        mbar_expect(bars + 8 * (B_FULLX + s), (168 + 8 * V) * 128);
                        tma2d(sb + OFF_X + s * XBUF, &M.x[V], 64 * st, TOKG * tg + 168 * V, bars + 8 * (B_FULLX + s));
                    }
                }
                if (c < 128 && warp < 14) {
                    if (warp == 13) {
                        mbar_wait(bars + 8 * (B_STG + 1), 0);
                        #pragma unroll 1
                        for (int o = 8 * tau; o < 8 * tau + 8; o += 7) flag_wait(P.flags, F_H + 2 * (o / 43) + ((o % 43) >= 21), 22);
                        mbar_arrive(bars + 8 * B_HF);
                        STAMP(25);
                    }
                    #pragma unroll 1
                    for (int st = 0; st < 22; st += (st < 7 || (st == 7 && warp == 12)) ? 1 : 2) {
                        const int sd = st & 7;
                        const uint32_t fb_ = bars + 8 * (B_FULLD + sd);
                        if (st >= 8) mbar_wait(bars + 8 * (B_EMPTYD + sd), ((st >> 3) & 1) ^ 1);
                        else if (warp == 12 || st >= 6) mbar_wait(bars + 8 * (uint32_t)((0x373623070d060504ull >> (8 * st)) & 0xff), st < 5);
                        if (st >= 10 && st < 21) STAMP2(31 + st);
                        if (st >= 8 || warp == 13) {
                            mbar_expect(fb_, 8192);
                            asm volatile("cp.async.bulk.tensor.5d.shared::cluster.global.mbarrier::complete_tx::bytes [%0], [%1, {%3, %3, %3, %4, %5}], [%2];"
                                :: "r"(sb + h_slot(sd)), "l"(&M.hld), "r"(fb_), "r"(0), "r"(2 * tau), "r"(8 * st) : "memory");
                        }
                        if (st >= 8 || warp == 12) {
                            const uint32_t da = sb + wd_slot(sd);
                            mbar_expect(fb_, 16384);
                            tma2d(da, &M.wd, 128 * dg, 64 * st, fb_);
                            tma2d(da + 8192, &M.wd, 128 * dg + 64, 64 * st, fb_);
                        }
                    }
                } else if (c < 128) {
                    mbar_wait(bars + 8 * B_SST, 0);
                    flag_wait(P.flags, F_S + dg, 64);
                    STAMP(26);
                    mbar_wait(bars + 8 * B_CH0, 0);
                    mbar_expect(bars + 8 * B_XO, 32768);
                    tma2d(sb + OFF_CONV, &M.xo, 128 * dg, 64 * tau, bars + 8 * B_XO);
                    tma2d(sb + OFF_CONV + 8192, &M.xo, 128 * dg + 64, 64 * tau, bars + 8 * B_XO);
                    asm volatile("cp.async.bulk.tensor.5d.shared::cluster.global.mbarrier::complete_tx::bytes [%0], [%1, {%3, %3, %3, %4, %5}], [%2];"
                        :: "r"(sb + wd_slot(6)), "l"(&M.sld), "r"(bars + 8 * B_XO), "r"(0), "r"(8 * dg), "r"(2 * tau) : "memory");
                    mbar_wait(bars + 8 * B_HF, 0);
                    exit_count(P.flags);
                }
            } else {
                mbar_wait(bars + 8 * B_LN, 0);
                STAMP2(0);
                if (c < 128) {
                    #pragma unroll 1
                    for (int i = 0; i < 4; i++)
                        asm volatile("cp.async.bulk.tensor.2d.global.shared::cta.bulk_group [%0, {%2, %3}], [%1];"
                            :: "l"(&M.xt), "r"(sb + OFF_CONV + i * CH_STRIDE + CH_LNT), "r"((c & 1) * 1024 + (126 - (c & ~1)) * 8), "r"(128 * i) : "memory");
                    #pragma unroll 1
                    for (int i = 0; i < 2; i++) bulk_store(P.st + 16 * (c & ~1) + 8 * (c & 1) + 16 - 16 * i, sb + OFF_CSUM + 64 * i, 64);
                    asm volatile("cp.async.bulk.prefetch.L2.global [%0], %1;" :: "l"(P.Wd + c * (FF * DM / 128)), "r"(FF * DM / 64) : "memory");
                }
                asm volatile("cp.async.bulk.commit_group; cp.async.bulk.wait_group.read 0;" ::: "memory");
                mbar_arrive(bars + 8 * B_LNS);
                STAMP2(1);
                flag_signal(P.flags, F_A);
                STAMP2(2);
                flag_wait(P.flags, F_A, NCTA);
                STAMP(20);
                mbar_expect(bars + 8 * B_STATS, TOKG * 8);
                bulk_load(sb + OFF_ST, P.st + TOKG * tg, TOKG * 8, bars + 8 * B_STATS);
                if (c < 128) {
                    mbar_expect(bars + 8 * B_U, 8 * 2048);
                    #pragma unroll 1
                    for (int i = 0; i < 8; i++)
                        bulk_load(sb + OFF_CONV + (i >> 1) * CH_STRIDE + CH_U + (i & 1) * UPLANE, P.xnT + 4 * c * 256 + i * 128, 2048, bars + 8 * B_U);
                } else exit_count(P.flags);
                #pragma unroll 1
                for (int V = 0; V < 2; V++) {
                    mbar_wait(bars + 8 * (B_EPI + V), 0);
                    STAMP2(3 + 2 * V);
                    asm volatile("cp.async.bulk.tensor.3d.global.shared::cta.bulk_group [%0, {%2, %3, %4}], [%1];"
                        :: "l"(&M.hst[V]), "r"(sb + OFF_X + V * 2 * XBUF), "r"(0), "r"(43 * tg + 21 * V), "r"(8 * fb) : "memory");
                    flag_signal(P.flags, F_H + 2 * tg + V);
                    mbar_arrive(bars + 8 * (B_STG + V));
                    STAMP2(4 + 2 * V);
                }
                if (c < 128) {
                    #pragma unroll 1
                    for (int V = 0; V < 2; V++) {
                        mbar_wait(bars + 8 * (B_SIG + V), 0);
                        STAMP2(7 + 2 * V);
                        bulk_store(P.S + (2 * c + V) * 1024, sb + OFF_CONV + V * OFF_SST, 8192);
                        flag_signal(P.flags, F_S + (c >> 5));
                        STAMP2(8 + 2 * V);
                    }
                    mbar_arrive(bars + 8 * B_SST);
                }
            }
        }
    }
    asm volatile("nanosleep.u32 0;");
}

typedef CUresult (*EncodeFn)(CUtensorMap*, CUtensorMapDataType, cuuint32_t, void*, const cuuint64_t*, const cuuint64_t*, const cuuint32_t*,
                             const cuuint32_t*, CUtensorMapInterleave, CUtensorMapSwizzle, CUtensorMapL2promotion, CUtensorMapFloatOOBfill);

void make_map(EncodeFn enc, CUtensorMap* m, const void* ptr, int rank, const cuuint64_t* dims, const cuuint64_t* strides, const cuuint32_t* box, bool swz, bool wide = false) {
    const cuuint32_t es[5] = {1, 1, 1, 1, 1};
    enc(m, CU_TENSOR_MAP_DATA_TYPE_BFLOAT16, rank, (void*)ptr, dims, strides, box, es, CU_TENSOR_MAP_INTERLEAVE_NONE,
        swz ? CU_TENSOR_MAP_SWIZZLE_128B : CU_TENSOR_MAP_SWIZZLE_NONE, wide ? CU_TENSOR_MAP_L2_PROMOTION_L2_256B : CU_TENSOR_MAP_L2_PROMOTION_L2_128B, CU_TENSOR_MAP_FLOAT_OOB_FILL_NONE);
}
void make_map2(EncodeFn enc, CUtensorMap* m, const void* ptr, cuuint64_t inner, cuuint64_t outer, cuuint32_t rows) {
    const cuuint64_t dims[2] = {inner, outer}, strides[1] = {inner * 2};
    const cuuint32_t box[2] = {64, rows};
    make_map(enc, m, ptr, 2, dims, strides, box, true, rows > 64);
}

}

extern "C" void kernel_launch(void* const* d_in, const int* in_sizes, int n_in, void* d_out, int out_size) {
    (void)in_sizes; (void)n_in; (void)out_size;
    static EncodeFn enc = nullptr;
    static void *hptr, *p_xnT, *p_st, *p_S, *p_flags;
    if (!enc) {
        cudaDriverEntryPointQueryResult qr;
        cudaGetDriverEntryPoint("cuTensorMapEncodeTiled", (void**)&enc, cudaEnableDefault, &qr);
        cudaFuncSetAttribute(fused_kernel, cudaFuncAttributeMaxDynamicSharedMemorySize, SMEM_BYTES);
        cudaGetSymbolAddress(&hptr, g_H); cudaGetSymbolAddress(&p_xnT, g_xnT); cudaGetSymbolAddress(&p_st, g_st);
        cudaGetSymbolAddress(&p_S, g_S); cudaGetSymbolAddress(&p_flags, g_flags);
    }
    Params P;
    P.x = (const __nv_bfloat16*)d_in[0]; P.logA = (const __nv_bfloat16*)d_in[1]; P.Aim = (const __nv_bfloat16*)d_in[2];
    P.Cr = (const __nv_bfloat16*)d_in[3]; P.Ci = (const __nv_bfloat16*)d_in[4]; P.logdt = (const __nv_bfloat16*)d_in[5];
    P.Dskip = (const __nv_bfloat16*)d_in[6];
    P.Wd = (const __nv_bfloat16*)d_in[10]; P.xnT = (uint4*)p_xnT; P.st = (float2*)p_st; P.S = (uint2*)p_S; P.flags = (unsigned*)p_flags;
    Maps M;
    make_map2(enc, &M.x[0], d_in[0], DM, SEQ, 168); make_map2(enc, &M.x[1], d_in[0], DM, SEQ, 176);
    make_map2(enc, &M.xo, d_in[0], DM, SEQ, 64);    make_map2(enc, &M.out, d_out, DM, SEQ, 64);
    make_map2(enc, &M.wg, d_in[8], FF, DM, 64);     make_map2(enc, &M.wu, d_in[9], FF, DM, 64);
    make_map2(enc, &M.wd, d_in[10], DM, FF, 64);
    for (int v = 0; v < 2; v++) {
        const cuuint64_t dims[3] = {64, 256, 172}, strides[2] = {128, 32768};
        const cuuint32_t box[3] = {64, (cuuint32_t)(21 + v), 8};
        make_map(enc, &M.hst[v], hptr, 3, dims, strides, box, false);
    }
    {
        const cuuint64_t dims[2] = {2048, 512}, strides[1] = {4096};
        const cuuint32_t box[2] = {16, 128};
        make_map(enc, &M.xt, p_xnT, 2, dims, strides, box, false);
    }
    {
        const cuuint64_t dims[5] = {64, 2, 4, 32, 64}, strides[4] = {4 * 8192, 8192, 8 * 8192, 128};
        const cuuint32_t box[5] = {64, 2, 4, 8, 2};
        make_map(enc, &M.sld, p_S, 5, dims, strides, box, true);
    }
    {
        const cuuint64_t dims[5] = {64, 2, 2, 64, 172}, strides[4] = {256, 128, 512, 32768};
        const cuuint32_t box[5] = {64, 2, 2, 2, 8};
        make_map(enc, &M.hld, hptr, 5, dims, strides, box, false);
    }
    fused_kernel<<<NCTA, 512, SMEM_BYTES>>>(P, M);
}
```

```cpp
#include <cuda_runtime.h>
#include <cuda_bf16.h>
#include <cuda.h>
#include <stdint.h>

#define PROF 0

namespace {

constexpr int SEQ = 2048, DM = 512, FF = 1376;
constexpr int NCTA = 132;
#define GOST 1
#define DLY1 300
constexpr int RUNROLL = 2;
constexpr int TOKG = 344;

constexpr uint32_t OFF_W = 0;
constexpr uint32_t XBUF = 22528;
constexpr uint32_t OFF_X = 65536;
constexpr uint32_t OFF_CONV = 155648;
constexpr uint32_t CH_STRIDE = 17536;
constexpr uint32_t CH_T = 0;
constexpr uint32_t CH_A3 = 8448;
constexpr uint32_t CH_B3 = 12544;
constexpr uint32_t CH_U = 13312;
constexpr uint32_t CH_G = CH_A3 + 2064;
constexpr uint32_t UPLANE = 2112;
constexpr uint32_t CH_LN = 0, CH_LNT = 13440;
constexpr uint32_t OFF_SST = 60416;
constexpr uint32_t OFF_ST = 225792;
constexpr uint32_t OFF_CSUM = 228544;
constexpr uint32_t OFF_BAR = 229056;
constexpr uint32_t SMEM_BYTES = 229568;

enum {
    B_FULLW = 0, B_EMPTYW = 4, B_FULLX = 8, B_EMPTYX = 12, B_FULLD = 16, B_EMPTYD = 24,
    B_U = 32, B_XO = 33, B_S = 34, B_STG = 35, B_HF = 37, B_STATS = 38, B_LNS = 39, B_SST = 40,
    B_LNX = 41, B_GO = 42, B_CH0 = 43, B_K = 44,
    B_CONV = 46, B_LN = 50, B_CS = 51, B_EPI = 52, B_SIG = 54,
    B_COUNT = 56
};
enum { F_A = 0, F_H = 1, F_S = 13, F_EXIT = 17, F_COUNT = 18 };

__device__ uint4 g_xnT[DM * 256];
__device__ float2 g_st[6 * TOKG];
__device__ uint4 g_H[172 * 256 * 8];
__device__ uint2 g_S[256 * 1024];
__device__ unsigned g_flags[F_COUNT * 32];
#define STAMP(i) do {} while (0)
#define GSTAMP(i) do {} while (0)
#define STAMP2(i) do {} while (0)

__device__ __forceinline__ uint32_t smem_u32(const void* p) { return (uint32_t)__cvta_generic_to_shared(p); }
__device__ __forceinline__ void mbar_expect(uint32_t bar, uint32_t bytes) { asm volatile("mbarrier.arrive.expect_tx.shared::cta.b64 _, [%0], %1;" :: "r"(bar), "r"(bytes) : "memory"); }
__device__ __forceinline__ void mbar_arrive(uint32_t bar) { asm volatile("mbarrier.arrive.shared::cta.b64 _, [%0];" :: "r"(bar) : "memory"); }
__device__ __forceinline__ void mbar_wait(uint32_t bar, uint32_t parity) {
    asm volatile("{.reg .pred p; .reg .u32 n; mov.u32 n, 0x20000;\n"
                 "LW: mbarrier.try_wait.parity.shared::cta.b64 p, [%0], %1;\n"
                 "sub.u32 n, n, 1; setp.eq.or.u32 p, n, 0, p; @!p bra LW;}" :: "r"(bar), "r"(parity) : "memory");
}
__device__ __forceinline__ bool elect_one() { uint32_t p; asm volatile("{.reg .pred P; elect.sync _|P, 0xffffffff; selp.u32 %0, 1, 0, P;}" : "=r"(p)); return p; }
__device__ __forceinline__ void tma2d(uint32_t dst, const CUtensorMap* m, int c0, int c1, uint32_t bar) {
    asm volatile("cp.async.bulk.tensor.2d.shared::cluster.global.mbarrier::complete_tx::bytes [%0], [%1, {%3, %4}], [%2];"
        :: "r"(dst), "l"(m), "r"(bar), "r"(c0), "r"(c1) : "memory");
}
__device__ __forceinline__ void bulk_load(uint32_t dst, const void* src, uint32_t bytes, uint32_t bar) {
    asm volatile("cp.async.bulk.shared::cluster.global.mbarrier::complete_tx::bytes [%0], [%1], %2, [%3];" :: "r"(dst), "l"(src), "r"(bytes), "r"(bar) : "memory");
}
__device__ __forceinline__ void bulk_store(void* dst, uint32_t src, uint32_t bytes) {
    asm volatile("cp.async.bulk.global.shared::cta.bulk_group [%0], [%1], %2;" :: "l"(dst), "r"(src), "r"(bytes) : "memory");
}
__device__ __forceinline__ void fence_async_smem() { asm volatile("fence.proxy.async.shared::cta;" ::: "memory"); }
__device__ __forceinline__ void flag_wait(unsigned* g_flags, int f, unsigned target) {
    asm volatile("{.reg .pred p; .reg .u32 n, v; mov.u32 n, 0x40000;\n"
                 "LF: ld.acquire.gpu.global.u32 v, [%0]; setp.ge.u32 p, v, %1; @p bra LD;\n"
                 "sub.u32 n, n, 1; setp.ne.u32 p, n, 0; @p bra LF; trap;\nLD: }"
                 :: "l"(g_flags + f * 32), "r"(target) : "memory");
}
__device__ __forceinline__ void flag_signal(unsigned* g_flags, int f) {
    asm volatile("cp.async.bulk.commit_group; cp.async.bulk.wait_group 0; red.relaxed.gpu.global.add.u32 [%0], 1;" :: "l"(g_flags + f * 32) : "memory");
}
__device__ __forceinline__ void exit_count(unsigned* g_flags) {
    if (atomicAdd(g_flags + F_EXIT * 32, 1u) == NCTA - 1) {
        #pragma unroll 1
        for (int i = 0; i < F_COUNT; i++) g_flags[i * 32] = 0;
    }
}
__device__ __forceinline__ void bar_sync(int id) { asm volatile("bar.sync %0, 128;" :: "r"(id) : "memory"); }
__device__ __forceinline__ uint64_t mkdesc(uint32_t addr, uint32_t lbo, uint32_t sbo, uint32_t swz) {
    return (uint64_t)((addr >> 4) | ((lbo >> 4) << 16)) | ((uint64_t)((sbo >> 4) | (swz << 30)) << 32);
}
#define WG_FENCE() asm volatile("wgmma.fence.sync.aligned;" ::: "memory")
#define WG_COMMIT() asm volatile("wgmma.commit_group.sync.aligned;" ::: "memory")
#define WG_WAIT(n) asm volatile("wgmma.wait_group.sync.aligned " #n ";" ::: "memory")
template <int N> __device__ __forceinline__ void fence_acc(float (&d)[N]) {
    #pragma unroll
    for (int i = 0; i < N; i++) asm volatile("" : "+f"(d[i]) :: "memory");
}
template <int N> __device__ __forceinline__ void define_acc(float (&d)[N]) {
    #pragma unroll
    for (int i = 0; i < N; i++) asm volatile("" : "=f"(d[i]));
}
__device__ __forceinline__ uint32_t pack2(float lo, float hi) { uint32_t r; asm("cvt.rn.bf16x2.f32 %0, %1, %2;" : "=r"(r) : "f"(hi), "f"(lo)); return r; }
__device__ __forceinline__ float bf_lo(uint32_t v) { return __uint_as_float(v << 16); }
__device__ __forceinline__ float bf_hi(uint32_t v) { return __uint_as_float(v & 0xffff0000u); }
__device__ __forceinline__ float bf_round(float v) { return bf_hi(pack2(0.f, v)); }
__device__ __forceinline__ float tanh_fast(float v) { float r; asm("tanh.approx.f32 %0, %1;" : "=f"(r) : "f"(v)); return r; }
__device__ __forceinline__ float ex2(float v) { float r; asm("ex2.approx.ftz.f32 %0, %1;" : "=f"(r) : "f"(v)); return r; }
__device__ __forceinline__ uint4 lds128(uint32_t a) { uint4 v; asm volatile("ld.shared.v4.b32 {%0,%1,%2,%3}, [%4];" : "=r"(v.x), "=r"(v.y), "=r"(v.z), "=r"(v.w) : "r"(a)); return v; }
__device__ __forceinline__ uint2 lds64(uint32_t a) { uint2 v; asm volatile("ld.shared.v2.b32 {%0,%1}, [%2];" : "=r"(v.x), "=r"(v.y) : "r"(a)); return v; }
__device__ __forceinline__ float ldsf(uint32_t a) { float v; asm volatile("ld.shared.f32 %0, [%1];" : "=f"(v) : "r"(a)); return v; }
__device__ __forceinline__ void sts128(uint32_t a, uint32_t x, uint32_t y, uint32_t z, uint32_t w) { asm volatile("st.shared.v4.b32 [%0], {%1,%2,%3,%4};" :: "r"(a), "r"(x), "r"(y), "r"(z), "r"(w) : "memory"); }
__device__ __forceinline__ void sts64(uint32_t a, uint32_t x, uint32_t y) { asm volatile("st.shared.v2.b32 [%0], {%1,%2};" :: "r"(a), "r"(x), "r"(y) : "memory"); }
__device__ __forceinline__ void stsf(uint32_t a, float x) { asm volatile("st.shared.f32 [%0], %1;" :: "r"(a), "f"(x) : "memory"); }
__device__ __forceinline__ void sts16(uint32_t a, uint32_t x) { asm volatile("st.shared.b16 [%0], %1;" :: "r"(a), "h"((unsigned short)x) : "memory"); }
__device__ __forceinline__ void stsm4(uint32_t a, uint32_t r0, uint32_t r1, uint32_t r2, uint32_t r3) {
    asm volatile("stmatrix.sync.aligned.m8n8.x4.shared.b16 [%0], {%1,%2,%3,%4};" :: "r"(a), "r"(r0), "r"(r1), "r"(r2), "r"(r3) : "memory");
}
__device__ __forceinline__ void ldsm4(uint32_t (&r)[4], uint32_t a) {
    asm volatile("ldmatrix.sync.aligned.m8n8.x4.shared.b16 {%0,%1,%2,%3}, [%4];" : "=r"(r[0]), "=r"(r[1]), "=r"(r[2]), "=r"(r[3]) : "r"(a) : "memory");
}
#define FU(x) __float_as_uint(x)
#define UF(x) __uint_as_float(x)
__device__ __forceinline__ uint32_t wd_slot(int s) { return (uint32_t)((0xbba8403056201000ull >> (8 * s)) & 0xff) << 10; }
__device__ __forceinline__ uint32_t h_slot(int s) { return (uint32_t)((0xcba0908880787068ull >> (8 * s)) & 0xff) << 10; }

template<int N> __device__ __forceinline__ void wg_rs(float (&d)[64], uint32_t a0, uint32_t a1, uint32_t a2, uint32_t a3, uint64_t db);
template<> __device__ __forceinline__ void wg_rs<128>(float (&d)[64], uint32_t a0, uint32_t a1, uint32_t a2, uint32_t a3, uint64_t db) {
  asm volatile("{.reg .pred p; setp.ne.b32 p, 1, 0; wgmma.mma_async.sync.aligned.m64n128k16.f32.bf16.bf16 {%0,%1,%2,%3,%4,%5,%6,%7,%8,%9,%10,%11,%12,%13,%14,%15,%16,%17,%18,%19,%20,%21,%22,%23,%24,%25,%26,%27,%28,%29,%30,%31,%32,%33,%34,%35,%36,%37,%38,%39,%40,%41,%42,%43,%44,%45,%46,%47,%48,%49,%50,%51,%52,%53,%54,%55,%56,%57,%58,%59,%60,%61,%62,%63}, {%64,%65,%66,%67}, %68, p, 1, 1, 0;}"
    : "+f"(d[0]),"+f"(d[1]),"+f"(d[2]),"+f"(d[3]),"+f"(d[4]),"+f"(d[5]),"+f"(d[6]),"+f"(d[7]),"+f"(d[8]),"+f"(d[9]),"+f"(d[10]),"+f"(d[11]),"+f"(d[12]),"+f"(d[13]),"+f"(d[14]),"+f"(d[15]),"+f"(d[16]),"+f"(d[17]),"+f"(d[18]),"+f"(d[19]),"+f"(d[20]),"+f"(d[21]),"+f"(d[22]),"+f"(d[23]),"+f"(d[24]),"+f"(d[25]),"+f"(d[26]),"+f"(d[27]),"+f"(d[28]),"+f"(d[29]),"+f"(d[30]),"+f"(d[31]),"+f"(d[32]),"+f"(d[33]),"+f"(d[34]),"+f"(d[35]),"+f"(d[36]),"+f"(d[37]),"+f"(d[38]),"+f"(d[39]),"+f"(d[40]),"+f"(d[41]),"+f"(d[42]),"+f"(d[43]),"+f"(d[44]),"+f"(d[45]),"+f"(d[46]),"+f"(d[47]),"+f"(d[48]),"+f"(d[49]),"+f"(d[50]),"+f"(d[51]),"+f"(d[52]),"+f"(d[53]),"+f"(d[54]),"+f"(d[55]),"+f"(d[56]),"+f"(d[57]),"+f"(d[58]),"+f"(d[59]),"+f"(d[60]),"+f"(d[61]),"+f"(d[62]),"+f"(d[63]) : "r"(a0), "r"(a1), "r"(a2), "r"(a3), "l"(db));
}
template<> __device__ __forceinline__ void wg_rs<120>(float (&d)[64], uint32_t a0, uint32_t a1, uint32_t a2, uint32_t a3, uint64_t db) {
  asm volatile("{.reg .pred p; setp.ne.b32 p, 1, 0; wgmma.mma_async.sync.aligned.m64n120k16.f32.bf16.bf16 {%0,%1,%2,%3,%4,%5,%6,%7,%8,%9,%10,%11,%12,%13,%14,%15,%16,%17,%18,%19,%20,%21,%22,%23,%24,%25,%26,%27,%28,%29,%30,%31,%32,%33,%34,%35,%36,%37,%38,%39,%40,%41,%42,%43,%44,%45,%46,%47,%48,%49,%50,%51,%52,%53,%54,%55,%56,%57,%58,%59}, {%60,%61,%62,%63}, %64, p, 1, 1, 0;}"
    : "+f"(d[0]),"+f"(d[1]),"+f"(d[2]),"+f"(d[3]),"+f"(d[4]),"+f"(d[5]),"+f"(d[6]),"+f"(d[7]),"+f"(d[8]),"+f"(d[9]),"+f"(d[10]),"+f"(d[11]),"+f"(d[12]),"+f"(d[13]),"+f"(d[14]),"+f"(d[15]),"+f"(d[16]),"+f"(d[17]),"+f"(d[18]),"+f"(d[19]),"+f"(d[20]),"+f"(d[21]),"+f"(d[22]),"+f"(d[23]),"+f"(d[24]),"+f"(d[25]),"+f"(d[26]),"+f"(d[27]),"+f"(d[28]),"+f"(d[29]),"+f"(d[30]),"+f"(d[31]),"+f"(d[32]),"+f"(d[33]),"+f"(d[34]),"+f"(d[35]),"+f"(d[36]),"+f"(d[37]),"+f"(d[38]),"+f"(d[39]),"+f"(d[40]),"+f"(d[41]),"+f"(d[42]),"+f"(d[43]),"+f"(d[44]),"+f"(d[45]),"+f"(d[46]),"+f"(d[47]),"+f"(d[48]),"+f"(d[49]),"+f"(d[50]),"+f"(d[51]),"+f"(d[52]),"+f"(d[53]),"+f"(d[54]),"+f"(d[55]),"+f"(d[56]),"+f"(d[57]),"+f"(d[58]),"+f"(d[59]) : "r"(a0), "r"(a1), "r"(a2), "r"(a3), "l"(db));
}
template<> __device__ __forceinline__ void wg_rs<112>(float (&d)[64], uint32_t a0, uint32_t a1, uint32_t a2, uint32_t a3, uint64_t db) {
  asm volatile("{.reg .pred p; setp.ne.b32 p, 1, 0; wgmma.mma_async.sync.aligned.m64n112k16.f32.bf16.bf16 {%0,%1,%2,%3,%4,%5,%6,%7,%8,%9,%10,%11,%12,%13,%14,%15,%16,%17,%18,%19,%20,%21,%22,%23,%24,%25,%26,%27,%28,%29,%30,%31,%32,%33,%34,%35,%36,%37,%38,%39,%40,%41,%42,%43,%44,%45,%46,%47,%48,%49,%50,%51,%52,%53,%54,%55}, {%56,%57,%58,%59}, %60, p, 1, 1, 0;}"
    : "+f"(d[0]),"+f"(d[1]),"+f"(d[2]),"+f"(d[3]),"+f"(d[4]),"+f"(d[5]),"+f"(d[6]),"+f"(d[7]),"+f"(d[8]),"+f"(d[9]),"+f"(d[10]),"+f"(d[11]),"+f"(d[12]),"+f"(d[13]),"+f"(d[14]),"+f"(d[15]),"+f"(d[16]),"+f"(d[17]),"+f"(d[18]),"+f"(d[19]),"+f"(d[20]),"+f"(d[21]),"+f"(d[22]),"+f"(d[23]),"+f"(d[24]),"+f"(d[25]),"+f"(d[26]),"+f"(d[27]),"+f"(d[28]),"+f"(d[29]),"+f"(d[30]),"+f"(d[31]),"+f"(d[32]),"+f"(d[33]),"+f"(d[34]),"+f"(d[35]),"+f"(d[36]),"+f"(d[37]),"+f"(d[38]),"+f"(d[39]),"+f"(d[40]),"+f"(d[41]),"+f"(d[42]),"+f"(d[43]),"+f"(d[44]),"+f"(d[45]),"+f"(d[46]),"+f"(d[47]),"+f"(d[48]),"+f"(d[49]),"+f"(d[50]),"+f"(d[51]),"+f"(d[52]),"+f"(d[53]),"+f"(d[54]),"+f"(d[55]) : "r"(a0), "r"(a1), "r"(a2), "r"(a3), "l"(db));
}
template<> __device__ __forceinline__ void wg_rs<104>(float (&d)[64], uint32_t a0, uint32_t a1, uint32_t a2, uint32_t a3, uint64_t db) {
  asm volatile("{.reg .pred p; setp.ne.b32 p, 1, 0; wgmma.mma_async.sync.aligned.m64n104k16.f32.bf16.bf16 {%0,%1,%2,%3,%4,%5,%6,%7,%8,%9,%10,%11,%12,%13,%14,%15,%16,%17,%18,%19,%20,%21,%22,%23,%24,%25,%26,%27,%28,%29,%30,%31,%32,%33,%34,%35,%36,%37,%38,%39,%40,%41,%42,%43,%44,%45,%46,%47,%48,%49,%50,%51}, {%52,%53,%54,%55}, %56, p, 1, 1, 0;}"
    : "+f"(d[0]),"+f"(d[1]),"+f"(d[2]),"+f"(d[3]),"+f"(d[4]),"+f"(d[5]),"+f"(d[6]),"+f"(d[7]),"+f"(d[8]),"+f"(d[9]),"+f"(d[10]),"+f"(d[11]),"+f"(d[12]),"+f"(d[13]),"+f"(d[14]),"+f"(d[15]),"+f"(d[16]),"+f"(d[17]),"+f"(d[18]),"+f"(d[19]),"+f"(d[20]),"+f"(d[21]),"+f"(d[22]),"+f"(d[23]),"+f"(d[24]),"+f"(d[25]),"+f"(d[26]),"+f"(d[27]),"+f"(d[28]),"+f"(d[29]),"+f"(d[30]),"+f"(d[31]),"+f"(d[32]),"+f"(d[33]),"+f"(d[34]),"+f"(d[35]),"+f"(d[36]),"+f"(d[37]),"+f"(d[38]),"+f"(d[39]),"+f"(d[40]),"+f"(d[41]),"+f"(d[42]),"+f"(d[43]),"+f"(d[44]),"+f"(d[45]),"+f"(d[46]),"+f"(d[47]),"+f"(d[48]),"+f"(d[49]),"+f"(d[50]),"+f"(d[51]) : "r"(a0), "r"(a1), "r"(a2), "r"(a3), "l"(db));
}
template<> __device__ __forceinline__ void wg_rs<96>(float (&d)[64], uint32_t a0, uint32_t a1, uint32_t a2, uint32_t a3, uint64_t db) {
  asm volatile("{.reg .pred p; setp.ne.b32 p, 1, 0; wgmma.mma_async.sync.aligned.m64n96k16.f32.bf16.bf16 {%0,%1,%2,%3,%4,%5,%6,%7,%8,%9,%10,%11,%12,%13,%14,%15,%16,%17,%18,%19,%20,%21,%22,%23,%24,%25,%26,%27,%28,%29,%30,%31,%32,%33,%34,%35,%36,%37,%38,%39,%40,%41,%42,%43,%44,%45,%46,%47}, {%48,%49,%50,%51}, %52, p, 1, 1, 0;}"
    : "+f"(d[0]),"+f"(d[1]),"+f"(d[2]),"+f"(d[3]),"+f"(d[4]),"+f"(d[5]),"+f"(d[6]),"+f"(d[7]),"+f"(d[8]),"+f"(d[9]),"+f"(d[10]),"+f"(d[11]),"+f"(d[12]),"+f"(d[13]),"+f"(d[14]),"+f"(d[15]),"+f"(d[16]),"+f"(d[17]),"+f"(d[18]),"+f"(d[19]),"+f"(d[20]),"+f"(d[21]),"+f"(d[22]),"+f"(d[23]),"+f"(d[24]),"+f"(d[25]),"+f"(d[26]),"+f"(d[27]),"+f"(d[28]),"+f"(d[29]),"+f"(d[30]),"+f"(d[31]),"+f"(d[32]),"+f"(d[33]),"+f"(d[34]),"+f"(d[35]),"+f"(d[36]),"+f"(d[37]),"+f"(d[38]),"+f"(d[39]),"+f"(d[40]),"+f"(d[41]),"+f"(d[42]),"+f"(d[43]),"+f"(d[44]),"+f"(d[45]),"+f"(d[46]),"+f"(d[47]) : "r"(a0), "r"(a1), "r"(a2), "r"(a3), "l"(db));
}
template<> __device__ __forceinline__ void wg_rs<88>(float (&d)[64], uint32_t a0, uint32_t a1, uint32_t a2, uint32_t a3, uint64_t db) {
  asm volatile("{.reg .pred p; setp.ne.b32 p, 1, 0; wgmma.mma_async.sync.aligned.m64n88k16.f32.bf16.bf16 {%0,%1,%2,%3,%4,%5,%6,%7,%8,%9,%10,%11,%12,%13,%14,%15,%16,%17,%18,%19,%20,%21,%22,%23,%24,%25,%26,%27,%28,%29,%30,%31,%32,%33,%34,%35,%36,%37,%38,%39,%40,%41,%42,%43}, {%44,%45,%46,%47}, %48, p, 1, 1, 0;}"
    : "+f"(d[0]),"+f"(d[1]),"+f"(d[2]),"+f"(d[3]),"+f"(d[4]),"+f"(d[5]),"+f"(d[6]),"+f"(d[7]),"+f"(d[8]),"+f"(d[9]),"+f"(d[10]),"+f"(d[11]),"+f"(d[12]),"+f"(d[13]),"+f"(d[14]),"+f"(d[15]),"+f"(d[16]),"+f"(d[17]),"+f"(d[18]),"+f"(d[19]),"+f"(d[20]),"+f"(d[21]),"+f"(d[22]),"+f"(d[23]),"+f"(d[24]),"+f"(d[25]),"+f"(d[26]),"+f"(d[27]),"+f"(d[28]),"+f"(d[29]),"+f"(d[30]),"+f"(d[31]),"+f"(d[32]),"+f"(d[33]),"+f"(d[34]),"+f"(d[35]),"+f"(d[36]),"+f"(d[37]),"+f"(d[38]),"+f"(d[39]),"+f"(d[40]),"+f"(d[41]),"+f"(d[42]),"+f"(d[43]) : "r"(a0), "r"(a1), "r"(a2), "r"(a3), "l"(db));
}
template<> __device__ __forceinline__ void wg_rs<80>(float (&d)[64], uint32_t a0, uint32_t a1, uint32_t a2, uint32_t a3, uint64_t db) {
  asm volatile("{.reg .pred p; setp.ne.b32 p, 1, 0; wgmma.mma_async.sync.aligned.m64n80k16.f32.bf16.bf16 {%0,%1,%2,%3,%4,%5,%6,%7,%8,%9,%10,%11,%12,%13,%14,%15,%16,%17,%18,%19,%20,%21,%22,%23,%24,%25,%26,%27,%28,%29,%30,%31,%32,%33,%34,%35,%36,%37,%38,%39}, {%40,%41,%42,%43}, %44, p, 1, 1, 0;}"
    : "+f"(d[0]),"+f"(d[1]),"+f"(d[2]),"+f"(d[3]),"+f"(d[4]),"+f"(d[5]),"+f"(d[6]),"+f"(d[7]),"+f"(d[8]),"+f"(d[9]),"+f"(d[10]),"+f"(d[11]),"+f"(d[12]),"+f"(d[13]),"+f"(d[14]),"+f"(d[15]),"+f"(d[16]),"+f"(d[17]),"+f"(d[18]),"+f"(d[19]),"+f"(d[20]),"+f"(d[21]),"+f"(d[22]),"+f"(d[23]),"+f"(d[24]),"+f"(d[25]),"+f"(d[26]),"+f"(d[27]),"+f"(d[28]),"+f"(d[29]),"+f"(d[30]),"+f"(d[31]),"+f"(d[32]),"+f"(d[33]),"+f"(d[34]),"+f"(d[35]),"+f"(d[36]),"+f"(d[37]),"+f"(d[38]),"+f"(d[39]) : "r"(a0), "r"(a1), "r"(a2), "r"(a3), "l"(db));
}
template<> __device__ __forceinline__ void wg_rs<72>(float (&d)[64], uint32_t a0, uint32_t a1, uint32_t a2, uint32_t a3, uint64_t db) {
  asm volatile("{.reg .pred p; setp.ne.b32 p, 1, 0; wgmma.mma_async.sync.aligned.m64n72k16.f32.bf16.bf16 {%0,%1,%2,%3,%4,%5,%6,%7,%8,%9,%10,%11,%12,%13,%14,%15,%16,%17,%18,%19,%20,%21,%22,%23,%24,%25,%26,%27,%28,%29,%30,%31,%32,%33,%34,%35}, {%36,%37,%38,%39}, %40, p, 1, 1, 0;}"
    : "+f"(d[0]),"+f"(d[1]),"+f"(d[2]),"+f"(d[3]),"+f"(d[4]),"+f"(d[5]),"+f"(d[6]),"+f"(d[7]),"+f"(d[8]),"+f"(d[9]),"+f"(d[10]),"+f"(d[11]),"+f"(d[12]),"+f"(d[13]),"+f"(d[14]),"+f"(d[15]),"+f"(d[16]),"+f"(d[17]),"+f"(d[18]),"+f"(d[19]),"+f"(d[20]),"+f"(d[21]),"+f"(d[22]),"+f"(d[23]),"+f"(d[24]),"+f"(d[25]),"+f"(d[26]),"+f"(d[27]),"+f"(d[28]),"+f"(d[29]),"+f"(d[30]),"+f"(d[31]),"+f"(d[32]),"+f"(d[33]),"+f"(d[34]),"+f"(d[35]) : "r"(a0), "r"(a1), "r"(a2), "r"(a3), "l"(db));
}
template<> __device__ __forceinline__ void wg_rs<64>(float (&d)[64], uint32_t a0, uint32_t a1, uint32_t a2, uint32_t a3, uint64_t db) {
  asm volatile("{.reg .pred p; setp.ne.b32 p, 1, 0; wgmma.mma_async.sync.aligned.m64n64k16.f32.bf16.bf16 {%0,%1,%2,%3,%4,%5,%6,%7,%8,%9,%10,%11,%12,%13,%14,%15,%16,%17,%18,%19,%20,%21,%22,%23,%24,%25,%26,%27,%28,%29,%30,%31}, {%32,%33,%34,%35}, %36, p, 1, 1, 0;}"
    : "+f"(d[0]),"+f"(d[1]),"+f"(d[2]),"+f"(d[3]),"+f"(d[4]),"+f"(d[5]),"+f"(d[6]),"+f"(d[7]),"+f"(d[8]),"+f"(d[9]),"+f"(d[10]),"+f"(d[11]),"+f"(d[12]),"+f"(d[13]),"+f"(d[14]),"+f"(d[15]),"+f"(d[16]),"+f"(d[17]),"+f"(d[18]),"+f"(d[19]),"+f"(d[20]),"+f"(d[21]),"+f"(d[22]),"+f"(d[23]),"+f"(d[24]),"+f"(d[25]),"+f"(d[26]),"+f"(d[27]),"+f"(d[28]),"+f"(d[29]),"+f"(d[30]),"+f"(d[31]) : "r"(a0), "r"(a1), "r"(a2), "r"(a3), "l"(db));
}
__device__ __forceinline__ void wg_rs_first(float (&d)[64], uint32_t a0, uint32_t a1, uint32_t a2, uint32_t a3, uint64_t db) {
  asm volatile("{.reg .pred p; setp.ne.b32 p, 0, 0; wgmma.mma_async.sync.aligned.m64n128k16.f32.bf16.bf16 {%0,%1,%2,%3,%4,%5,%6,%7,%8,%9,%10,%11,%12,%13,%14,%15,%16,%17,%18,%19,%20,%21,%22,%23,%24,%25,%26,%27,%28,%29,%30,%31,%32,%33,%34,%35,%36,%37,%38,%39,%40,%41,%42,%43,%44,%45,%46,%47,%48,%49,%50,%51,%52,%53,%54,%55,%56,%57,%58,%59,%60,%61,%62,%63}, {%64,%65,%66,%67}, %68, p, 1, 1, 0;}"
    : "=f"(d[0]),"=f"(d[1]),"=f"(d[2]),"=f"(d[3]),"=f"(d[4]),"=f"(d[5]),"=f"(d[6]),"=f"(d[7]),"=f"(d[8]),"=f"(d[9]),"=f"(d[10]),"=f"(d[11]),"=f"(d[12]),"=f"(d[13]),"=f"(d[14]),"=f"(d[15]),"=f"(d[16]),"=f"(d[17]),"=f"(d[18]),"=f"(d[19]),"=f"(d[20]),"=f"(d[21]),"=f"(d[22]),"=f"(d[23]),"=f"(d[24]),"=f"(d[25]),"=f"(d[26]),"=f"(d[27]),"=f"(d[28]),"=f"(d[29]),"=f"(d[30]),"=f"(d[31]),"=f"(d[32]),"=f"(d[33]),"=f"(d[34]),"=f"(d[35]),"=f"(d[36]),"=f"(d[37]),"=f"(d[38]),"=f"(d[39]),"=f"(d[40]),"=f"(d[41]),"=f"(d[42]),"=f"(d[43]),"=f"(d[44]),"=f"(d[45]),"=f"(d[46]),"=f"(d[47]),"=f"(d[48]),"=f"(d[49]),"=f"(d[50]),"=f"(d[51]),"=f"(d[52]),"=f"(d[53]),"=f"(d[54]),"=f"(d[55]),"=f"(d[56]),"=f"(d[57]),"=f"(d[58]),"=f"(d[59]),"=f"(d[60]),"=f"(d[61]),"=f"(d[62]),"=f"(d[63]) : "r"(a0), "r"(a1), "r"(a2), "r"(a3), "l"(db));
}
__device__ __forceinline__ void wg_tt128(float (&d)[64], uint64_t da, uint64_t db, int sc) {
  asm volatile("{.reg .pred p; setp.ne.b32 p, %66, 0; wgmma.mma_async.sync.aligned.m64n128k16.f32.bf16.bf16 {%0,%1,%2,%3,%4,%5,%6,%7,%8,%9,%10,%11,%12,%13,%14,%15,%16,%17,%18,%19,%20,%21,%22,%23,%24,%25,%26,%27,%28,%29,%30,%31,%32,%33,%34,%35,%36,%37,%38,%39,%40,%41,%42,%43,%44,%45,%46,%47,%48,%49,%50,%51,%52,%53,%54,%55,%56,%57,%58,%59,%60,%61,%62,%63}, %64, %65, p, 1, 1, 1, 1;}"
    : "+f"(d[0]),"+f"(d[1]),"+f"(d[2]),"+f"(d[3]),"+f"(d[4]),"+f"(d[5]),"+f"(d[6]),"+f"(d[7]),"+f"(d[8]),"+f"(d[9]),"+f"(d[10]),"+f"(d[11]),"+f"(d[12]),"+f"(d[13]),"+f"(d[14]),"+f"(d[15]),"+f"(d[16]),"+f"(d[17]),"+f"(d[18]),"+f"(d[19]),"+f"(d[20]),"+f"(d[21]),"+f"(d[22]),"+f"(d[23]),"+f"(d[24]),"+f"(d[25]),"+f"(d[26]),"+f"(d[27]),"+f"(d[28]),"+f"(d[29]),"+f"(d[30]),"+f"(d[31]),"+f"(d[32]),"+f"(d[33]),"+f"(d[34]),"+f"(d[35]),"+f"(d[36]),"+f"(d[37]),"+f"(d[38]),"+f"(d[39]),"+f"(d[40]),"+f"(d[41]),"+f"(d[42]),"+f"(d[43]),"+f"(d[44]),"+f"(d[45]),"+f"(d[46]),"+f"(d[47]),"+f"(d[48]),"+f"(d[49]),"+f"(d[50]),"+f"(d[51]),"+f"(d[52]),"+f"(d[53]),"+f"(d[54]),"+f"(d[55]),"+f"(d[56]),"+f"(d[57]),"+f"(d[58]),"+f"(d[59]),"+f"(d[60]),"+f"(d[61]),"+f"(d[62]),"+f"(d[63]) : "l"(da), "l"(db), "r"(sc));
}
__device__ __forceinline__ void wg_tt64(float (&d)[64], uint64_t da, uint64_t db, int sc) {
  asm volatile("{.reg .pred p; setp.ne.b32 p, %34, 0; wgmma.mma_async.sync.aligned.m64n64k16.f32.bf16.bf16 {%0,%1,%2,%3,%4,%5,%6,%7,%8,%9,%10,%11,%12,%13,%14,%15,%16,%17,%18,%19,%20,%21,%22,%23,%24,%25,%26,%27,%28,%29,%30,%31}, %32, %33, p, 1, 1, 1, 1;}"
    : "+f"(d[0]),"+f"(d[1]),"+f"(d[2]),"+f"(d[3]),"+f"(d[4]),"+f"(d[5]),"+f"(d[6]),"+f"(d[7]),"+f"(d[8]),"+f"(d[9]),"+f"(d[10]),"+f"(d[11]),"+f"(d[12]),"+f"(d[13]),"+f"(d[14]),"+f"(d[15]),"+f"(d[16]),"+f"(d[17]),"+f"(d[18]),"+f"(d[19]),"+f"(d[20]),"+f"(d[21]),"+f"(d[22]),"+f"(d[23]),"+f"(d[24]),"+f"(d[25]),"+f"(d[26]),"+f"(d[27]),"+f"(d[28]),"+f"(d[29]),"+f"(d[30]),"+f"(d[31]) : "l"(da), "l"(db), "r"(sc));
}
__device__ __forceinline__ void wg_tt32(float (&d)[64], uint64_t da, uint64_t db, int sc) {
  asm volatile("{.reg .pred p; setp.ne.b32 p, %18, 0; wgmma.mma_async.sync.aligned.m64n32k16.f32.bf16.bf16 {%0,%1,%2,%3,%4,%5,%6,%7,%8,%9,%10,%11,%12,%13,%14,%15}, %16, %17, p, 1, 1, 1, 1;}"
    : "+f"(d[0]),"+f"(d[1]),"+f"(d[2]),"+f"(d[3]),"+f"(d[4]),"+f"(d[5]),"+f"(d[6]),"+f"(d[7]),"+f"(d[8]),"+f"(d[9]),"+f"(d[10]),"+f"(d[11]),"+f"(d[12]),"+f"(d[13]),"+f"(d[14]),"+f"(d[15]) : "l"(da), "l"(db), "r"(sc));
}
__device__ __forceinline__ void wg_g1(float (&d)[88], uint64_t da, uint64_t db, int sc) {
  asm volatile("{.reg .pred p; setp.ne.b32 p, %90, 0; wgmma.mma_async.sync.aligned.m64n176k16.f32.bf16.bf16 {%0,%1,%2,%3,%4,%5,%6,%7,%8,%9,%10,%11,%12,%13,%14,%15,%16,%17,%18,%19,%20,%21,%22,%23,%24,%25,%26,%27,%28,%29,%30,%31,%32,%33,%34,%35,%36,%37,%38,%39,%40,%41,%42,%43,%44,%45,%46,%47,%48,%49,%50,%51,%52,%53,%54,%55,%56,%57,%58,%59,%60,%61,%62,%63,%64,%65,%66,%67,%68,%69,%70,%71,%72,%73,%74,%75,%76,%77,%78,%79,%80,%81,%82,%83,%84,%85,%86,%87}, %88, %89, p, 1, 1, 1, 0;}"
    : "+f"(d[0]),"+f"(d[1]),"+f"(d[2]),"+f"(d[3]),"+f"(d[4]),"+f"(d[5]),"+f"(d[6]),"+f"(d[7]),"+f"(d[8]),"+f"(d[9]),"+f"(d[10]),"+f"(d[11]),"+f"(d[12]),"+f"(d[13]),"+f"(d[14]),"+f"(d[15]),"+f"(d[16]),"+f"(d[17]),"+f"(d[18]),"+f"(d[19]),"+f"(d[20]),"+f"(d[21]),"+f"(d[22]),"+f"(d[23]),"+f"(d[24]),"+f"(d[25]),"+f"(d[26]),"+f"(d[27]),"+f"(d[28]),"+f"(d[29]),"+f"(d[30]),"+f"(d[31]),"+f"(d[32]),"+f"(d[33]),"+f"(d[34]),"+f"(d[35]),"+f"(d[36]),"+f"(d[37]),"+f"(d[38]),"+f"(d[39]),"+f"(d[40]),"+f"(d[41]),"+f"(d[42]),"+f"(d[43]),"+f"(d[44]),"+f"(d[45]),"+f"(d[46]),"+f"(d[47]),"+f"(d[48]),"+f"(d[49]),"+f"(d[50]),"+f"(d[51]),"+f"(d[52]),"+f"(d[53]),"+f"(d[54]),"+f"(d[55]),"+f"(d[56]),"+f"(d[57]),"+f"(d[58]),"+f"(d[59]),"+f"(d[60]),"+f"(d[61]),"+f"(d[62]),"+f"(d[63]),"+f"(d[64]),"+f"(d[65]),"+f"(d[66]),"+f"(d[67]),"+f"(d[68]),"+f"(d[69]),"+f"(d[70]),"+f"(d[71]),"+f"(d[72]),"+f"(d[73]),"+f"(d[74]),"+f"(d[75]),"+f"(d[76]),"+f"(d[77]),"+f"(d[78]),"+f"(d[79]),"+f"(d[80]),"+f"(d[81]),"+f"(d[82]),"+f"(d[83]),"+f"(d[84]),"+f"(d[85]),"+f"(d[86]),"+f"(d[87]) : "l"(da), "l"(db), "r"(sc));
}

struct Params { const __nv_bfloat16 *x, *logA, *Aim, *Cr, *Ci, *logdt, *Dskip, *Wg, *Wu, *Wd; uint4* xnT; float2* st; uint2* S; unsigned* flags; };
struct Maps { CUtensorMap x[2], xo, out, wg, wu, wd, hst[2], hld, xt, sld; };

__device__ __forceinline__ void conv_channel(uint32_t cb, int w, int lane, uint32_t (&res)[8], uint32_t sig, int sidx) {
    const int q = lane & 3, g = lane >> 2, gam = g >> 2;
    float acc[64];
    uint2 a[17][2];
    const uint32_t t0 = cb + CH_T + (uint32_t)(14 + 4 * w + (g & 3) - 2 * q) * 280u + gam * 8;
#define LDA(s0, s1) _Pragma("unroll") for (int s = s0; s < s1; s++) { a[s][0] = lds64(t0 + s * 16); a[s][1] = lds64(t0 - 8 * 280 + s * 16); }
#define CT(N, s) wg_rs<N>(acc, a[s][0].x, a[s][0].y, a[s][1].x, a[s][1].y, dU + 4 * (s))
    const uint64_t dU = mkdesc(cb + CH_U, UPLANE, 128, 0);
    LDA(0, 17)
    if (sig) { fence_async_smem(); mbar_arrive(sig); }
    WG_FENCE();
    if (w == 0) STAMP2(52 + 3 * sidx);
    wg_rs_first(acc, a[0][0].x, a[0][0].y, a[0][1].x, a[0][1].y, dU);
    CT(128, 1); CT(120, 2); CT(120, 3); CT(112, 4); CT(112, 5); CT(104, 6); CT(104, 7); CT(96, 8);
    CT(96, 9); CT(88, 10); CT(88, 11); CT(80, 12); CT(80, 13); CT(72, 14); CT(72, 15); CT(64, 16);
#undef CT
#undef LDA
    wg_tt64(acc, mkdesc(cb + CH_A3, 128, 512, 0), mkdesc(cb + CH_B3, 384, 32, 0), 1);
    wg_tt32(acc, mkdesc(cb + CH_A3 + 256, 128, 512, 0), mkdesc(cb + CH_B3 + 128, 384, 32, 0), 1);
    WG_COMMIT();
    if (w == 0) STAMP2(53 + 3 * sidx);
    WG_WAIT(0);
    fence_acc(acc);
    if (w == 0) STAMP2(54 + 3 * sidx);
    const int src1 = (lane & ~3) | ((q + 1) & 3);
    float E[16][2];
    #pragma unroll
    for (int j = 0; j < 16; j++) {
        const float nxt = (j < 15) ? acc[4 * (j + 1) + 2] : 0.f;
        const float sup = (q == 0) ? nxt : acc[4 * j + 2];
        const float v = __shfl_sync(0xffffffffu, sup, src1);
        E[j][0] = acc[4 * j] + acc[4 * j + 3];
        E[j][1] = acc[4 * j + 1] + v;
    }
    const int src2 = gam ? ((lane & 12) | ((q + 3) & 3)) : (16 | (lane & 12) | ((q + 1) & 3));
    const bool c1 = gam && q != 0, c2 = gam && q == 0;
    #pragma unroll
    for (int a2 = 0; a2 < 8; a2++) {
        float y[2];
        #pragma unroll
        for (int e = 0; e < 2; e++) {
            const float sup = c1 ? E[2 * a2][e] : E[2 * a2 + 1][e];
            const float nxt = (a2 < 7) ? E[2 * a2 + 2][e] : 0.f;
            const float keep = c2 ? nxt : (c1 ? E[2 * a2 + 1][e] : E[2 * a2][e]);
            y[e] = keep + __shfl_sync(0xffffffffu, sup, src2);
        }
        res[a2] = pack2(y[1], y[0]);
    }
}

__device__ __forceinline__ void consumer(uint32_t sb, int warp, const Params& P, const Maps& M) {
    const int V = warp >> 2, w = warp & 3, lane = threadIdx.x & 31, q = lane & 3, g = lane >> 2;
    const int c = blockIdx.x;
    const uint32_t bars = sb + OFF_BAR, xb = sb + OFF_X + V * 2 * XBUF;
    {
        float ag[88], au[88];
        if (V) mbar_wait(bars + 8 * B_GO, 0);
        define_acc(ag); define_acc(au);
        #pragma unroll 1
        for (int st = 0; st < 8; st++) {
            mbar_wait(bars + 8 * (B_FULLW + (st & 3)), st >> 2);
            mbar_wait(bars + 8 * (B_FULLX + 2 * V + (st & 1)), (st >> 1) & 1);
            STAMP(40 + 8 * V + st);
            const uint64_t dG = mkdesc(sb + OFF_W + (st & 3) * 16384, 0, 1024, 1);
            const uint64_t dX = mkdesc(xb + (st & 1) * XBUF, 16, 1024, 1);
            WG_FENCE();
            #pragma unroll
            for (int k = 0; k < 4; k++) {
                wg_g1(ag, dG + k * 128, dX + k * 2, k ? 1 : st);
                wg_g1(au, dG + 512 + k * 128, dX + k * 2, k ? 1 : st);
            }
            WG_COMMIT();
            WG_WAIT(1);
            if (lane == 0 && st > 0) {
                mbar_arrive(bars + 8 * (B_EMPTYW + ((st - 1) & 3)));
                mbar_arrive(bars + 8 * (B_EMPTYX + 2 * V + ((st - 1) & 1)));
                if (warp < 4 && st == GOST) mbar_arrive(bars + 8 * B_GO);
            }
        }
        WG_WAIT(0);
        fence_acc(ag); fence_acc(au);
        if (lane == 0) { mbar_arrive(bars + 8 * (B_EMPTYW + 3)); mbar_arrive(bars + 8 * (B_EMPTYX + 2 * V + 1)); }
        STAMP(8 * V + 1);
        float cg0 = ag[84], cg1 = ag[86], cu0 = au[84], cu1 = au[86];
        const uint32_t ca = sb + OFF_CSUM + (8 * w + g) * 16;
        if (V == 0) { sts128(ca, FU(cg0), FU(cg1), FU(cu0), FU(cu1)); mbar_arrive(bars + 8 * B_CS); }
        else { mbar_wait(bars + 8 * B_CS, 0); const uint4 t = lds128(ca); cg0 = UF(t.x); cg1 = UF(t.y); cu0 = UF(t.z); cu1 = UF(t.w); }
        mbar_wait(bars + 8 * B_STATS, 0);
        mbar_wait(bars + 8 * (B_EMPTYX + 2 * V), 1);
        STAMP(13 + V);
        const uint32_t hs = xb + (2 * w + ((lane >> 3) & 1)) * (2688 + 128 * V) + (lane >> 4) * 128 + (lane & 7) * 16;
        const uint32_t sa = sb + OFF_ST + (168 * V + 2 * q) * 8;
        uint4 sq[22];
        #pragma unroll
        for (int j = 0; j < 3; j++) sq[j] = lds128(sa + j * 64);
        #pragma unroll
        for (int j = 0; j < 22; j += 2) {
            uint32_t o[4];
            #pragma unroll
            for (int jj = 0; jj < 2; jj++) {
                const uint4 sv = sq[j + jj];
                float hv[4];
                #pragma unroll
                for (int i = 0; i < 4; i++) {
                    const float m = UF((i & 1) ? sv.z : sv.x);
                    const float gh = fmaf(-m, (i & 2) ? cg1 : cg0, ag[4 * (j + jj) + i]) * UF((i & 1) ? sv.w : sv.y);
                    const float p = gh * fmaf(-m, (i & 2) ? cu1 : cu0, au[4 * (j + jj) + i]);
                    hv[i] = fmaf(p, tanh_fast(gh), p);
                }
                o[2 * jj] = pack2(hv[0], hv[1]); o[2 * jj + 1] = pack2(hv[2], hv[3]);
            }
            #pragma unroll
            for (int k = (j ? 3 + 3 * j / 2 : 3); k < 6 + 3 * j / 2 && k < 22; k++) sq[k] = lds128(sa + k * 64);
            uint32_t ad = hs + j * 128;
            if (j == 20 && V == 0 && lane >= 16) ad = xb + 21504 + (lane & 7) * 16;
            stsm4(ad, o[0], o[1], o[2], o[3]);
        }
        if (c >= 128) { fence_async_smem(); mbar_arrive(bars + 8 * (B_EPI + V)); }
        STAMP(8 * V + 2);
    }
    if (c >= 128) return;
    {
        uint32_t r0[8], r1[8];
        #pragma unroll
        for (int i = 0; i < 8; i++) asm volatile("" : "=r"(r1[i]));
        #pragma unroll 1
        for (int e = 0; e < 2; e++) {
            #pragma unroll
            for (int i = 0; i < 8; i++) r0[i] = r1[i];
            mbar_wait(bars + 8 * (B_CONV + 2 * V + e), 0);
            conv_channel(sb + OFF_CONV + (2 * V + e) * CH_STRIDE, w, lane, r1, e ? 0 : bars + 8 * (B_EPI + V), 2 * V + e);
            if (e == 0) STAMP(8 * V + 3);
        }
        const int gam = g >> 2, qq = gam ? ((q + 3) & 3) : q;
        const uint32_t sp = sb + OFF_CONV + V * OFF_SST + ((63 - 4 * gam - qq) * 16 + 4 * (w ^ (3 - qq)) + (g & 3)) * 8;
        bar_sync(3 + V);
        #pragma unroll
        for (int a2 = 0; a2 < 8; a2++) sts64(sp - a2 * 1024, r0[a2], r1[a2]);
        fence_async_smem();
        mbar_arrive(bars + 8 * (B_SIG + V));
        STAMP(8 * V + 4);
    }
    if (V == 1) return;
    {
        const int tau = c >> 2, dg = c & 3;
        const uint32_t row = 8 * (w & 1) + 32 * (w >> 1);
        float acc[64];
        define_acc(acc);
        const float rr0 = __ldcg(&P.st[64 * tau + row + g].y), rr1 = __ldcg(&P.st[64 * tau + row + g + 16].y);
        mbar_wait(bars + 8 * B_FULLD, 0);
        STAMP(5);
        uint64_t dB = mkdesc(sb + wd_slot(0), 8192, 1024, 1), dA = mkdesc(sb + h_slot(0), 1024, 128, 0);
        #pragma unroll 1
        for (int st = 0; st < 21; st++) {
            WG_FENCE();
            wg_tt128(acc, dA, dB, st);
            wg_tt128(acc, dA + 128, dB + 128, 1);
            wg_tt128(acc, dA + 256, dB + 256, 1);
            wg_tt128(acc, dA + 384, dB + 384, 1);
            WG_COMMIT();
            const int sd = (st + 1) & 7;
            const uint32_t nb = bars + 8 * (B_FULLD + sd), np = ((st + 1) >> 3) & 1;
            uint32_t ro = st == 15 ? 8 * B_CH0 : 8 * (B_EMPTYD + ((st - 1) & 7)), m = lane == 0 && st > 0, ok;
            dB = mkdesc(sb + wd_slot(sd), 8192, 1024, 1); dA = mkdesc(sb + h_slot(sd), 1024, 128, 0);
            asm volatile("{.reg .pred p; mbarrier.test_wait.parity.shared::cta.b64 p, [%5], %6; vote.sync.all.pred p, p, -1; selp.u32 %0, 1, 0, p;}"
                : "=r"(ok), "+l"(dA), "+l"(dB), "+r"(ro), "+r"(m) : "r"(nb), "r"(np) : "memory");
            WG_WAIT(1);
            asm volatile("{.reg .pred p; setp.ne.u32 p, %1, 0; @p mbarrier.arrive.shared::cta.b64 _, [%0];}" :: "r"(bars + ro), "r"(m) : "memory");
            if (!ok) mbar_wait(nb, np);
            if (w == 0) STAMP2(20 + st);
        }
        WG_FENCE();
        wg_tt128(acc, dA, dB, 1);
        wg_tt128(acc, dA + 128, dB + 128, 1);
        WG_COMMIT();
        mbar_wait(bars + 8 * B_XO, 0);
        const uint32_t xo = sb + OFF_CONV + (row + (lane & 7) + 16 * ((lane >> 3) & 1)) * 128;
        const uint32_t so = sb + wd_slot(6) + (w >> 1) * 8192 + q * 256 + (g & 1) * 8;
        const uint32_t sx = (4 * (w & 1) + (g >> 1)) ^ (2 * q) ^ (2 * ((2 * tau + (w >> 1)) & 3));
        uint32_t xr[8][4];
        uint2 sv[16];
        #pragma unroll
        for (int j = 0; j < 16; j += 2) {
            ldsm4(xr[j >> 1], xo + (j >> 3) * 8192 + ((((j & 7) + (lane >> 4)) ^ (lane & 7)) << 4));
            sv[j] = lds64(so + j * 512 + (sx << 4));
            sv[j + 1] = lds64(so + j * 512 + 128 + ((sx ^ 1) << 4));
        }
        WG_WAIT(0);
        fence_acc(acc);
        STAMP(6);
        #pragma unroll
        for (int j = 0; j < 16; j += 2) {
            #pragma unroll
            for (int i = 0; i < 4; i++) {
                const int jj = j + (i >> 1), hh = i & 1;
                const float f0 = acc[4 * jj + 2 * hh] * (hh ? rr1 : rr0), f1 = acc[4 * jj + 2 * hh + 1] * (hh ? rr1 : rr0);
                const uint32_t G = pack2(fmaf(f0, tanh_fast(f0), f0), fmaf(f1, tanh_fast(f1), f1));
                const uint32_t s2 = __byte_perm(sv[jj].x, sv[jj].y, hh ? 0x7632 : 0x5410);
                asm("fma.rn.bf16x2 %0, %1, %2, %0;" : "+r"(xr[j >> 1][i]) : "r"(s2), "r"(G));
            }
            stsm4(xo + (j >> 3) * 8192 + ((((j & 7) + (lane >> 4)) ^ (lane & 7)) << 4), xr[j >> 1][0], xr[j >> 1][1], xr[j >> 1][2], xr[j >> 1][3]);
        }
        fence_async_smem();
        bar_sync(1);
        if (w == 0 && elect_one()) {
            #pragma unroll
            for (int i = 0; i < 2; i++)
                asm volatile("cp.async.bulk.tensor.2d.global.shared::cta.bulk_group [%0, {%2, %3}], [%1];"
                    :: "l"(&M.out), "r"(sb + OFF_CONV + i * 8192), "r"(dg * 128 + 64 * i), "r"(tau * 64) : "memory");
            asm volatile("cp.async.bulk.commit_group; cp.async.bulk.wait_group.read 0;" ::: "memory");
        }
        STAMP(7); GSTAMP(23);
    }
}

__device__ __forceinline__ float2 cexp_p(float re2, float im, float p) {
    float sn, cs;
    const float mag = ex2(re2 * p), th = im * p;
    asm("sin.approx.ftz.f32 %0, %1;" : "=f"(sn) : "f"(th));
    asm("cos.approx.ftz.f32 %0, %1;" : "=f"(cs) : "f"(th));
    return make_float2(mag * cs, mag * sn);
}
struct SsmRaw { unsigned short la, ai, cr, ci, ldt, dsk; };
__device__ __forceinline__ unsigned short ldu16(const void* p) { unsigned short v; asm volatile("ld.global.nc.u16 %0, [%1];" : "=h"(v) : "l"(p)); return v; }
__device__ __forceinline__ float2 cmul(float2 a, float2 b) { return make_float2(fmaf(a.x, b.x, -a.y * b.y), fmaf(a.x, b.y, a.y * b.x)); }
__device__ __forceinline__ float2 csqr(float2 a) { const float t = a.x * a.y; return make_float2(fmaf(a.x, a.x, -a.y * a.y), t + t); }
__device__ __forceinline__ void mma16816(float (&d)[4], const uint32_t (&a)[4], uint32_t b0, uint32_t b1) {
    asm volatile("mma.sync.aligned.m16n8k16.row.col.f32.bf16.bf16.f32 {%0,%1,%2,%3}, {%4,%5,%6,%7}, {%8,%9}, {%0,%1,%2,%3};"
        : "+f"(d[0]), "+f"(d[1]), "+f"(d[2]), "+f"(d[3]) : "r"(a[0]), "r"(a[1]), "r"(a[2]), "r"(a[3]), "r"(b0), "r"(b1));
}

__device__ __forceinline__ void layer_norm(uint32_t sb, uint32_t cb, int w, int lane) {
    const uint32_t bars = sb + OFF_BAR;
    mbar_wait(bars + 8 * B_LNX, 0);
    STAMP(34);
    {
        const uint32_t r0 = cb + CH_LN + (w & 1) * 64 + (lane >> 3) * 1040, ra = r0 + (lane & 7) * 16;
        const float pv = bf_lo(FU(ldsf(r0)));
        float s0 = 0.f, s1 = 0.f, a0 = 0.f, a1 = 0.f;
        #pragma unroll 1
        for (int k = 0; k < 1024; k += 512) {
            uint32_t v[16];
            #pragma unroll
            for (int j = 0; j < 4; j++) *(uint4*)&v[4 * j] = lds128(ra + k + 128 * j);
            #pragma unroll
            for (int i = 0; i < 16; i++) { const float t0 = bf_lo(v[i]) - pv, t1 = bf_hi(v[i]) - pv; s0 += t0; s1 += t1; a0 = fmaf(t0, t0, a0); a1 = fmaf(t1, t1, a1); }
        }
        s0 += s1; a0 += a1;
        #pragma unroll
        for (int o = 4; o; o >>= 1) { s0 += __shfl_xor_sync(0xffffffffu, s0, o); a0 += __shfl_xor_sync(0xffffffffu, a0, o); }
        s0 *= 1.f / DM;
        float sd, ri;
        asm("sqrt.approx.ftz.f32 %0, %1;" : "=f"(sd) : "f"(bf_round(bf_round(fmaxf(fmaf(-s0, s0, a0 * (1.f / DM)), 0.f)) + 1e-5f)));
        asm("rcp.approx.ftz.f32 %0, %1;" : "=f"(ri) : "f"(bf_round(sd)));
        if ((lane & 7) == 0) sts64(sb + OFF_CSUM + (w + 4 * (lane >> 3)) * 8, FU(bf_round(pv + s0)), FU(0.5f * ri));
    }
    STAMP(62);
    bar_sync(2);
    const int r = 4 * ((lane & 7) >> 1) + (lane & 1) + 2 * ((lane >> 3) & 1);
    const uint32_t ad = sb + OFF_CONV + (r & 3) * CH_STRIDE + CH_LN + (r & 1) * 64 + (r >> 2) * 1040 + (16 * w + (lane >> 4)) * 16;
    const uint4 sa = lds128(sb + OFF_CSUM + (lane & 3) * 32), sc = lds128(sb + OFF_CSUM + (lane & 3) * 32 + 16);
    const uint32_t m2[2] = {__byte_perm(sa.x, sa.z, 0x7632), __byte_perm(sc.x, sc.z, 0x7632)};
    const float ri[4] = {2.f * UF(sa.y), 2.f * UF(sa.w), 2.f * UF(sc.y), 2.f * UF(sc.w)};
    #pragma unroll 1
    for (int i = 0; i < 8; i += 4) {
        uint32_t v[4][4];
        #pragma unroll
        for (int j = 0; j < 4; j++)
            asm volatile("ldmatrix.sync.aligned.m8n8.x4.trans.shared.b16 {%0,%1,%2,%3}, [%4];" : "=r"(v[j][0]), "=r"(v[j][1]), "=r"(v[j][2]), "=r"(v[j][3]) : "r"(ad + 32 * (i + j)) : "memory");
        #pragma unroll
        for (int j = 0; j < 4; j++) {
            #pragma unroll
            for (int k = 0; k < 4; k++) {
                uint32_t dv; asm("sub.rn.bf16x2 %0, %1, %2;" : "=r"(dv) : "r"(v[j][k]), "r"(m2[k & 1]));
                v[j][k] = pack2(bf_lo(dv) * ri[2 * (k & 1)], bf_hi(dv) * ri[2 * (k & 1) + 1]);
            }
            sts64(cb + CH_LNT + lane * 8 + (i + j) * 512, v[j][0], v[j][1]); sts64(cb + CH_LNT + lane * 8 + (i + j) * 512 + 256, v[j][2], v[j][3]);
        }
    }
    fence_async_smem();
    mbar_arrive(bars + 8 * B_LN);
    STAMP(16);
}

__device__ __forceinline__ uint32_t kgen_scratch(int wg, int ch) {
    return wg < 2 ? (wg ? OFF_X + 2 * XBUF : OFF_W + 32768) + ch * 8064 : OFF_CONV + ch * CH_STRIDE + (wg & 1) * 8064;
}
__device__ __forceinline__ void kernel_gen(uint32_t fs, int lane, const SsmRaw& raw, float (&dacc)[2][3][4], const Params& P, int warp) {
    const float dt = bf_round(ex2(bf_lo(raw.ldt) * 1.4426950408889634f));
    const float re2 = bf_round(ex2(bf_lo(raw.la) * 1.4426950408889634f)) * dt * -1.4426950408889634f, im = bf_lo(raw.ai) * dt;
    const float2 C = make_float2(bf_lo(raw.cr) * (dt + dt), bf_lo(raw.ci) * -(dt + dt));
    STAMP(56);
    if (warp < 4 && lane == 0 && re2 != 1.f) {
        const int c = blockIdx.x;
        const char* p = warp < 2 ? (const char*)(P.x + (16 * (c & ~1) + 8 * (c & 1) + 16 * warp) * DM) : (const char*)(warp == 2 ? P.Wg : P.Wu) + 128 * FF * 2 + c * 8256;
        asm volatile("cp.async.bulk.prefetch.L2.global [%0], %1;" :: "l"(p), "r"(warp < 2 ? 8192 : 8256) : "memory");
    }
    const float2 z8 = cexp_p(re2, im, 8.f), y1 = cexp_p(re2, -im, 1.f), y256 = cexp_p(re2, -im, 256.f);
    float2 b0 = make_float2(1.f, 0.f), b1 = cexp_p(re2, im, 64.f), b2 = csqr(b1), b3 = cmul(b2, b1);
    const uint32_t fm = fs + (lane >> 3) * 144 + (lane & 7) * 16;
#define PK(v) pack2((v).x, (v).y)
    #pragma unroll RUNROLL
    for (uint32_t ro = 0; ro < 8 * 144; ro += 144) {
        stsm4(fm + (lane >> 3) * 7 * 144 + ro, PK(b0), PK(b1), PK(b2), PK(b3));
        b0 = cmul(b0, z8); b1 = cmul(b1, z8); b2 = cmul(b2, z8); b3 = cmul(b3, z8);
    }
    const float2 y2 = csqr(y1), y4 = csqr(y2), y8 = make_float2(z8.x, -z8.y);
    const float2 l1 = cmul(C, y1), l2 = cmul(C, y2), l3 = cmul(l1, y2);
    stsm4(fm + 32 * 144, PK(C), PK(l1), PK(l2), PK(l3));
    stsm4(fm + 36 * 144, PK(cmul(C, y4)), PK(cmul(l1, y4)), PK(cmul(l2, y4)), PK(cmul(l3, y4)));
    const float2 t0 = cmul(C, y256), t1 = cmul(t0, y256), t2 = cmul(t1, y256), t3_ = cmul(t2, y256);
    const float2 u1 = cmul(t0, y2), u2 = cmul(u1, y2), u3 = cmul(u2, y2);
    stsm4(fm + 40 * 144, PK(t0), PK(u1), PK(u2), PK(u3));
    stsm4(fm + 44 * 144, PK(t1), PK(cmul(t1, y4)), PK(t2), PK(cmul(t2, y4)));
    const float2 v0 = cmul(t3_, y8), v1 = cmul(v0, y256), v2 = cmul(v1, y256), v3 = cmul(v2, y256);
    stsm4(fm + 48 * 144, PK(v0), PK(v1), PK(v2), PK(v3));
    stsf(fs + lane * 4 + 52 * 144, UF(PK(t3_)));
#undef PK
    STAMP(57);
    const uint32_t lda = fs + (lane & 15) * 144 + (lane & 16);
    const uint32_t ldb = fs + (32 + (lane & 7)) * 144 + (lane >> 3) * 16;
    __syncwarp();
    #pragma unroll 1
    for (int ko = 0; ko < 128; ko += 64) {
        uint32_t b[3][4], a[4][4];
        #pragma unroll
        for (int i = 0; i < 3; i++) ldsm4(b[i], ldb + i * 8 * 144 + ko);
        #pragma unroll
        for (int i = 0; i < 4; i++) ldsm4(a[i], lda + (i & 1) * 16 * 144 + ko + (i >> 1) * 32);
        #pragma unroll
        for (int i = 0; i < 4; i++)
            #pragma unroll
            for (int t = 0; t < 3; t++) mma16816(dacc[i & 1][t], a[i], b[t][i & 2], b[t][(i & 2) + 1]);
    }
    STAMP(58);
}

__device__ __forceinline__ void aux_role(uint32_t sb, int w, float (&dacc)[2][3][4], float dsk, const __nv_bfloat16* x) {
    const int lane = threadIdx.x & 31, q = lane & 3, g = lane >> 2;
    const int c = blockIdx.x;
    const uint32_t bars = sb + OFF_BAR;
    if (c >= 128) { mbar_arrive(bars + 8 * B_LN); if (lane == 0) mbar_arrive(bars + 8 * B_K); return; }
    {
        const uint32_t cb = sb + OFF_CONV + w * CH_STRIDE;
        if (elect_one()) {
            mbar_expect(bars + 8 * B_LNX, 4096);
            #pragma unroll
            for (int i = 0; i < 4; i++)
                bulk_load(cb + CH_LN + (w & 1) * 64 + i * 1040, x + (16 * (c & ~1) + 8 * (c & 1) + 16 + w + 4 * (i & 1) - 8 * (i & 2)) * DM, 1024, bars + 8 * B_LNX);
        }
        #pragma unroll 1
        for (int k = 0; k < 3; k++) {
            const uint32_t pa = sb + kgen_scratch(k + (k >> 1), w) + lane * 16;
            #pragma unroll
            for (int i = 0; i < 6; i++) {
                const uint4 v = lds128(pa + i * 512);
                float* d = &dacc[0][0][0] + 4 * i;
                d[0] += UF(v.x); d[1] += UF(v.y); d[2] += UF(v.z); d[3] += UF(v.w);
            }
        }
        __syncwarp();
        if (lane == 0) mbar_arrive(bars + 8 * B_K);
        STAMP(18);
        const uint32_t sF = cb + CH_A3, sG = cb + CH_G;
        if (lane == 0) dacc[0][0][0] += dsk;
        if (lane < 10) sts128(sG + 128 + (lane & 1) * 208 + (lane >> 1) * 16, 0, 0, 0, 0);
        const uint32_t f0 = sF + (8 * g + 2 * q) * 4, f1 = sF + ((q < 2) ? 256 + 4 * g + 2 * q : 256 + 2 * g + 64 * q) * 4, st1 = (q < 2) ? 128 : 64;
        const uint32_t ga = sG + ((g & 1) ? 0 : 208) + (63 - (g >> 1) - 32 * q) * 2;
        #pragma unroll
        for (int i = 0; i < 4; i++) {
            const int mu = i >> 1, hh = i & 1;
            sts64(f0 + i * 256, FU(dacc[mu][0][2 * hh]), FU(dacc[mu][0][2 * hh + 1]));
            sts64(f1 + i * st1, FU(dacc[mu][1][2 * hh]), FU(dacc[mu][1][2 * hh + 1]));
            const uint32_t pk = pack2(dacc[mu][2][2 * hh], dacc[mu][2][2 * hh + 1]);
            if (q < 2) { sts16(ga - 8 * i, pk & 0xffff); sts16(ga - 8 * i - 32, pk >> 16); }
        }
        if (lane == 2) stsf(sF + 2048, dacc[0][2][0]);
        STAMP(19);
        layer_norm(sb, cb, w, lane);
        mbar_wait(bars + 8 * B_LNS, 0);
        if (lane < 8) sts128(cb + CH_U + 2048 + (lane & 4) * (UPLANE / 4) + (lane & 3) * 16, 0, 0, 0, 0);
        bar_sync(2);
    }
    const int u = min(lane, 30) - 15, r2 = (u + ((u >> 1) & 1)) >> 1, r4 = (u + 1 + ((u >> 2) & 1)) >> 2, xt = 1024 + 16 * w + u;
    const uint32_t o0 = CH_A3 + 4 * (w == 0 ? u : w == 1 ? 256 + r2 : 256 + 64 * w + r4), ost = w == 0 ? 64 : w == 1 ? 32 : 16;
    const uint32_t oa0 = u >= 0 || w == 3 ? o0 : CH_A3 + 4 * (w == 1 ? 256 + u : w == 2 ? 384 + r2 : 0);
    const uint32_t ot = CH_A3 + 4 * min(512, 256 + ((xt + 1 + ((xt >> 2) & 1)) >> 2));
    const int kap = (lane >> 4) * 8 + ((lane >> 1) & 7), gam = lane & 1, hh = w >> 1, wp = w & 1;
    const uint32_t oa = CH_U + wp * UPLANE + (127 - 4 * kap - 2 * gam - hh) * 16;
    const uint32_t ob = CH_U + (wp ^ 1) * UPLANE + (128 - wp - 4 * kap - 2 * gam - hh) * 16;
    const uint32_t od = CH_A3 + (4 * wp + hh) * 512 + (kap >> 3) * 256 + (kap & 7) * 16 + gam * 8;
    #pragma unroll 1
    for (int k = 0; k < 4; k++) {
        const int ch = 2 * (k & 1) + (k >> 1);
        const uint32_t cb = sb + OFF_CONV + ch * CH_STRIDE;
        {
            float kv[17];
            kv[0] = ldsf(cb + oa0); kv[16] = ldsf(cb + ot);
            #pragma unroll
            for (int s = 1; s < 16; s++) kv[s] = ldsf(cb + o0 + s * ost);
            const int tid = threadIdx.x & 127;
            const uint32_t ga = cb + CH_G + (tid >= 24) * 16 + min(tid, 47) * 8;
            const uint2 x0 = lds64(ga), x1 = lds64(ga + 8);
            if (u < 0 && w == 0) kv[0] = 0.f;
            if (xt > 1028) kv[16] = 0.f;
            uint32_t o[17];
            #pragma unroll
            for (int s = 0; s < 17; s++) o[s] = pack2(kv[s], __shfl_up_sync(0xffffffffu, kv[s], 1));
            if (lane > 0 && lane < 31) {
                const uint32_t ta = cb + CH_T + (lane - 1) * 280;
                #pragma unroll
                for (int s2 = 0; s2 < 8; s2++) sts64(ta + 64 * w + s2 * 8, o[2 * s2], o[2 * s2 + 1]);
                stsf(ta + 256 + 4 * w, UF(o[16]));
            }
            if (tid < 48) sts128(cb + CH_B3 + tid * 16, x0.x, x0.y, x1.x, x1.y);
        }
        mbar_wait(bars + 8 * B_U, 0);
        float p[24];
        const uint2 r0 = lds64(cb + ob + 24), r3 = lds64(cb + oa);
        uint32_t r[8];
        *(uint4*)&r[0] = lds128(cb + oa + 16); *(uint4*)&r[4] = lds128(cb + ob);
        p[0] = 0.f;
        p[1] = bf_lo(r0.x); p[2] = p[1] + bf_hi(r0.x); p[3] = p[2] + bf_lo(r0.y); p[4] = p[3] + bf_hi(r0.y);
        #pragma unroll
        for (int i = 0; i < 8; i++) { p[5 + 2 * i] = p[4 + 2 * i] + bf_lo(r[i]); p[6 + 2 * i] = p[5 + 2 * i] + bf_hi(r[i]); }
        p[21] = p[20] + bf_lo(r3.x); p[22] = p[21] + bf_hi(r3.x); p[23] = p[22] + bf_lo(r3.y);
        bar_sync(2);
        #pragma unroll
        for (int i = 0; i < 8; i += 4) {
            sts64(cb + od + i * 256, pack2(p[i + 9] - p[i], p[i + 10] - p[i + 1]), pack2(p[i + 11] - p[i + 2], p[i + 12] - p[i + 3]));
            sts64(cb + od + i * 256 + 128, pack2(p[i + 16] - p[i + 9], p[i + 17] - p[i + 10]), pack2(p[i + 18] - p[i + 11], p[i + 19] - p[i + 12]));
        }
        fence_async_smem();
        mbar_arrive(bars + 8 * (B_CONV + ch));
        if (k == 0) STAMP(17);
    }
    STAMP(21);
}

__global__ void __launch_bounds__(512, 1)
fused_kernel(const __grid_constant__ Params P, const __grid_constant__ Maps M) {
    extern __shared__ __align__(1024) uint8_t smem_raw[];
    const uint32_t sb = smem_u32(smem_raw);
    const uint32_t bars = sb + OFF_BAR;
    const int warp = __shfl_sync(0xffffffffu, threadIdx.x >> 5, 0);
    const int c = blockIdx.x, tg = c / 22, fb = c - 22 * tg;
    SsmRaw raw;
    {
        const int d = min(4 * c + (warp & 3), DM - 1), o = d * 128 + (warp >> 2) * 32 + (threadIdx.x & 31);
        raw.la = ldu16(P.logA + o); raw.ai = ldu16(P.Aim + o); raw.cr = ldu16(P.Cr + o); raw.ci = ldu16(P.Ci + o);
        raw.ldt = ldu16(P.logdt + d); raw.dsk = ldu16(P.Dskip + d);
    }
    if (elect_one()) {
        if (warp == 0) { STAMP(24); GSTAMP(22); }
        asm volatile("" :: "l"(((const uint64_t*)&P)[warp < 14 ? warp : 0]));
        if (warp < 12) asm volatile("prefetch.tensormap [%0];" :: "l"(&M.x[0] + warp) : "memory");
        #pragma unroll
        for (int k = 0; k < 4; k++) {
            const int i = 16 * k + ((warp + 4) & 15);
            const uint32_t cnt = i >= B_CONV ? 128 : ((0xf0ull >> i) & 1) ? 8 : ((0xff0000ull >> i) & 1) ? 2 : ((0x3e00ff00f000ull >> i) & 1) ? 4 : 1;
            asm volatile("mbarrier.init.shared::cta.b64 [%0], %1;" :: "r"(bars + 8 * i), "r"(cnt) : "memory");
        }
        asm volatile("fence.mbarrier_init.release.cluster; fence.proxy.async.shared::cta;" ::: "memory");
        if (warp == 13 || warp == 5) { const uint32_t t0 = clock(); while ((uint32_t)clock() - t0 < DLY1) ; }
        if (warp == 12 || warp == 13) {
            const uint32_t s = warp - 12;
            mbar_expect(bars + 8 * (B_FULLW + s), 16384);
            tma2d(sb + OFF_W + s * 16384, &M.wg, 64 * fb, 64 * s, bars + 8 * (B_FULLW + s));
            tma2d(sb + OFF_W + s * 16384 + 8192, &M.wu, 64 * fb, 64 * s, bars + 8 * (B_FULLW + s));
            STAMP(31);
        } else if (warp == 4 || warp == 5) {
            const uint32_t s = warp - 4;
            mbar_expect(bars + 8 * (B_FULLX + s), 168 * 128);
            tma2d(sb + OFF_X + s * XBUF, &M.x[0], 64 * s, TOKG * tg, bars + 8 * (B_FULLX + s));
        }
        if (sb & 1023) __trap();
    }
    if (warp < 4) sts128(sb + OFF_X + (warp >> 1) * XBUF + 168 * 128 + (threadIdx.x & 63) * 16, 0x3f803f80u, 0x3f803f80u, 0x3f803f80u, 0x3f803f80u);
    float dacc[2][3][4];
    #pragma unroll
    for (int i = 0; i < 24; i++) (&dacc[0][0][0])[i] = 0.f;
    if (c < 128) {
        const uint32_t fs = sb + kgen_scratch(warp >> 2, warp & 3);
        kernel_gen(fs, threadIdx.x & 31, raw, dacc, P, warp);
        if ((warp >> 2) != 2) {
            __syncwarp();
            #pragma unroll
            for (int i = 0; i < 6; i++) { const float* d = &dacc[0][0][0] + 4 * i; sts128(fs + (threadIdx.x & 31) * 16 + i * 512, FU(d[0]), FU(d[1]), FU(d[2]), FU(d[3])); }
        }
    }
    fence_async_smem();
    __syncthreads();
    if (warp < 8) {
        asm volatile("setmaxnreg.inc.sync.aligned.u32 208;");
        consumer(sb, warp, P, M);
    } else if (warp < 12) {
        asm volatile("setmaxnreg.dec.sync.aligned.u32 72;");
        STAMP(32);
        aux_role(sb, warp - 8, dacc, bf_lo(raw.dsk), P.x);
    } else {
        asm volatile("setmaxnreg.dec.sync.aligned.u32 24;");
        const int tau = c >> 2, dg = c & 3;
        if (elect_one()) {
            if (warp < 15) {
                mbar_wait(bars + 8 * B_K, 0);
                if (warp == 12) {
                    #pragma unroll 1
                    for (int st = 2; st < 8; st++) {
                        const uint32_t s = st & 3, fb_ = bars + 8 * (B_FULLW + s);
                        mbar_wait(bars + 8 * (B_EMPTYW + s), (st >> 2) ^ 1);
                        mbar_expect(fb_, 16384);
                        tma2d(sb + OFF_W + s * 16384, &M.wg, 64 * fb, 64 * st, fb_);
                        tma2d(sb + OFF_W + s * 16384 + 8192, &M.wu, 64 * fb, 64 * st, fb_);
                    }
                } else {
                    const int V = warp - 13;
                    #pragma unroll 1
                    for (int st = 2 - 2 * V; st < 8; st++) {
                        const uint32_t s = 2 * V + (st & 1);
                        mbar_wait(bars + 8 * (B_EMPTYX + s), ((st >> 1) & 1) ^ 1);
                        mbar_expect(bars + 8 * (B_FULLX + s), (168 + 8 * V) * 128);
                        tma2d(sb + OFF_X + s * XBUF, &M.x[V], 64 * st, TOKG * tg + 168 * V, bars + 8 * (B_FULLX + s));
                    }
                }
                if (c < 128 && warp < 14) {
                    if (warp == 13) {
                        mbar_wait(bars + 8 * (B_STG + 1), 0);
                        #pragma unroll 1
                        for (int o = 8 * tau; o < 8 * tau + 8; o += 7) flag_wait(P.flags, F_H + 2 * (o / 43) + ((o % 43) >= 21), 22);
                        mbar_arrive(bars + 8 * B_HF);
                        STAMP(25);
                    }
                    #pragma unroll 1
                    for (int st = 0; st < 22; st += (st < 7 || (st == 7 && warp == 12)) ? 1 : 2) {
                        const int sd = st & 7;
                        const uint32_t fb_ = bars + 8 * (B_FULLD + sd);
                        if (st >= 8) mbar_wait(bars + 8 * (B_EMPTYD + sd), ((st >> 3) & 1) ^ 1);
                        else if (warp == 12 || st >= 6) mbar_wait(bars + 8 * (uint32_t)((0x373623070d060504ull >> (8 * st)) & 0xff), st < 5);
                        if (st >= 10 && st < 21) STAMP2(31 + st);
                        if (st >= 8 || warp == 13) {
                            mbar_expect(fb_, 8192);
                            asm volatile("cp.async.bulk.tensor.5d.shared::cluster.global.mbarrier::complete_tx::bytes [%0], [%1, {%3, %3, %3, %4, %5}], [%2];"
                                :: "r"(sb + h_slot(sd)), "l"(&M.hld), "r"(fb_), "r"(0), "r"(2 * tau), "r"(8 * st) : "memory");
                        }
                        if (st >= 8 || warp == 12) {
                            const uint32_t da = sb + wd_slot(sd);
                            mbar_expect(fb_, 16384);
                            tma2d(da, &M.wd, 128 * dg, 64 * st, fb_);
                            tma2d(da + 8192, &M.wd, 128 * dg + 64, 64 * st, fb_);
                        }
                    }
                } else if (c < 128) {
                    mbar_wait(bars + 8 * B_SST, 0);
                    flag_wait(P.flags, F_S + dg, 64);
                    STAMP(26);
                    mbar_wait(bars + 8 * B_CH0, 0);
                    mbar_expect(bars + 8 * B_XO, 32768);
                    tma2d(sb + OFF_CONV, &M.xo, 128 * dg, 64 * tau, bars + 8 * B_XO);
                    tma2d(sb + OFF_CONV + 8192, &M.xo, 128 * dg + 64, 64 * tau, bars + 8 * B_XO);
                    asm volatile("cp.async.bulk.tensor.5d.shared::cluster.global.mbarrier::complete_tx::bytes [%0], [%1, {%3, %3, %3, %4, %5}], [%2];"
                        :: "r"(sb + wd_slot(6)), "l"(&M.sld), "r"(bars + 8 * B_XO), "r"(0), "r"(8 * dg), "r"(2 * tau) : "memory");
                    mbar_wait(bars + 8 * B_HF, 0);
                    exit_count(P.flags);
                }
            } else {
                mbar_wait(bars + 8 * B_LN, 0);
                STAMP2(0);
                if (c < 128) {
                    #pragma unroll 1
                    for (int i = 0; i < 4; i++)
                        asm volatile("cp.async.bulk.tensor.2d.global.shared::cta.bulk_group [%0, {%2, %3}], [%1];"
                            :: "l"(&M.xt), "r"(sb + OFF_CONV + i * CH_STRIDE + CH_LNT), "r"((c & 1) * 1024 + (126 - (c & ~1)) * 8), "r"(128 * i) : "memory");
                    #pragma unroll 1
                    for (int i = 0; i < 2; i++) bulk_store(P.st + 16 * (c & ~1) + 8 * (c & 1) + 16 - 16 * i, sb + OFF_CSUM + 64 * i, 64);
                    asm volatile("cp.async.bulk.prefetch.L2.global [%0], %1;" :: "l"(P.Wd + c * (FF * DM / 128)), "r"(FF * DM / 64) : "memory");
                }
                asm volatile("cp.async.bulk.commit_group; cp.async.bulk.wait_group.read 0;" ::: "memory");
                mbar_arrive(bars + 8 * B_LNS);
                STAMP2(1);
                flag_signal(P.flags, F_A);
                STAMP2(2);
                flag_wait(P.flags, F_A, NCTA);
                STAMP(20);
                mbar_expect(bars + 8 * B_STATS, TOKG * 8);
                bulk_load(sb + OFF_ST, P.st + TOKG * tg, TOKG * 8, bars + 8 * B_STATS);
                if (c < 128) {
                    mbar_expect(bars + 8 * B_U, 8 * 2048);
                    #pragma unroll 1
                    for (int i = 0; i < 8; i++)
                        bulk_load(sb + OFF_CONV + (i >> 1) * CH_STRIDE + CH_U + (i & 1) * UPLANE, P.xnT + 4 * c * 256 + i * 128, 2048, bars + 8 * B_U);
                } else exit_count(P.flags);
                #pragma unroll 1
                for (int V = 0; V < 2; V++) {
                    mbar_wait(bars + 8 * (B_EPI + V), 0);
                    STAMP2(3 + 2 * V);
                    asm volatile("cp.async.bulk.tensor.3d.global.shared::cta.bulk_group [%0, {%2, %3, %4}], [%1];"
                        :: "l"(&M.hst[V]), "r"(sb + OFF_X + V * 2 * XBUF), "r"(0), "r"(43 * tg + 21 * V), "r"(8 * fb) : "memory");
                    flag_signal(P.flags, F_H + 2 * tg + V);
                    mbar_arrive(bars + 8 * (B_STG + V));
                    STAMP2(4 + 2 * V);
                }
                if (c < 128) {
                    #pragma unroll 1
                    for (int V = 0; V < 2; V++) {
                        mbar_wait(bars + 8 * (B_SIG + V), 0);
                        STAMP2(7 + 2 * V);
                        bulk_store(P.S + (2 * c + V) * 1024, sb + OFF_CONV + V * OFF_SST, 8192);
                        flag_signal(P.flags, F_S + (c >> 5));
                        STAMP2(8 + 2 * V);
                    }
                    mbar_arrive(bars + 8 * B_SST);
                }
            }
        }
    }
    asm volatile("nanosleep.u32 0;");
}

typedef CUresult (*EncodeFn)(CUtensorMap*, CUtensorMapDataType, cuuint32_t, void*, const cuuint64_t*, const cuuint64_t*, const cuuint32_t*,
                             const cuuint32_t*, CUtensorMapInterleave, CUtensorMapSwizzle, CUtensorMapL2promotion, CUtensorMapFloatOOBfill);

void make_map(EncodeFn enc, CUtensorMap* m, const void* ptr, int rank, const cuuint64_t* dims, const cuuint64_t* strides, const cuuint32_t* box, bool swz, bool wide = false) {
    const cuuint32_t es[5] = {1, 1, 1, 1, 1};
    enc(m, CU_TENSOR_MAP_DATA_TYPE_BFLOAT16, rank, (void*)ptr, dims, strides, box, es, CU_TENSOR_MAP_INTERLEAVE_NONE,
        swz ? CU_TENSOR_MAP_SWIZZLE_128B : CU_TENSOR_MAP_SWIZZLE_NONE, wide ? CU_TENSOR_MAP_L2_PROMOTION_L2_256B : CU_TENSOR_MAP_L2_PROMOTION_L2_128B, CU_TENSOR_MAP_FLOAT_OOB_FILL_NONE);
}
void make_map2(EncodeFn enc, CUtensorMap* m, const void* ptr, cuuint64_t inner, cuuint64_t outer, cuuint32_t rows) {
    const cuuint64_t dims[2] = {inner, outer}, strides[1] = {inner * 2};
    const cuuint32_t box[2] = {64, rows};
    make_map(enc, m, ptr, 2, dims, strides, box, true, rows > 64);
}

}

extern "C" void kernel_launch(void* const* d_in, const int* in_sizes, int n_in, void* d_out, int out_size) {
    (void)in_sizes; (void)n_in; (void)out_size;
    static EncodeFn enc = nullptr;
    static void *hptr, *p_xnT, *p_st, *p_S, *p_flags;
    if (!enc) {
        cudaDriverEntryPointQueryResult qr;
        cudaGetDriverEntryPoint("cuTensorMapEncodeTiled", (void**)&enc, cudaEnableDefault, &qr);
        cudaFuncSetAttribute(fused_kernel, cudaFuncAttributeMaxDynamicSharedMemorySize, SMEM_BYTES);
        cudaGetSymbolAddress(&hptr, g_H); cudaGetSymbolAddress(&p_xnT, g_xnT); cudaGetSymbolAddress(&p_st, g_st);
        cudaGetSymbolAddress(&p_S, g_S); cudaGetSymbolAddress(&p_flags, g_flags);
    }
    Params P;
    P.x = (const __nv_bfloat16*)d_in[0]; P.logA = (const __nv_bfloat16*)d_in[1]; P.Aim = (const __nv_bfloat16*)d_in[2];
    P.Cr = (const __nv_bfloat16*)d_in[3]; P.Ci = (const __nv_bfloat16*)d_in[4]; P.logdt = (const __nv_bfloat16*)d_in[5];
    P.Dskip = (const __nv_bfloat16*)d_in[6];
    P.Wg = (const __nv_bfloat16*)d_in[8]; P.Wu = (const __nv_bfloat16*)d_in[9]; P.Wd = (const __nv_bfloat16*)d_in[10]; P.xnT = (uint4*)p_xnT; P.st = (float2*)p_st; P.S = (uint2*)p_S; P.flags = (unsigned*)p_flags;
    Maps M;
    make_map2(enc, &M.x[0], d_in[0], DM, SEQ, 168); make_map2(enc, &M.x[1], d_in[0], DM, SEQ, 176);
    make_map2(enc, &M.xo, d_in[0], DM, SEQ, 64);    make_map2(enc, &M.out, d_out, DM, SEQ, 64);
    make_map2(enc, &M.wg, d_in[8], FF, DM, 64);     make_map2(enc, &M.wu, d_in[9], FF, DM, 64);
    make_map2(enc, &M.wd, d_in[10], DM, FF, 64);
    for (int v = 0; v < 2; v++) {
        const cuuint64_t dims[3] = {64, 256, 172}, strides[2] = {128, 32768};
        const cuuint32_t box[3] = {64, (cuuint32_t)(21 + v), 8};
        make_map(enc, &M.hst[v], hptr, 3, dims, strides, box, false);
    }
    {
        const cuuint64_t dims[2] = {2048, 512}, strides[1] = {4096};
        const cuuint32_t box[2] = {16, 128};
        make_map(enc, &M.xt, p_xnT, 2, dims, strides, box, false);
    }
    {
        const cuuint64_t dims[5] = {64, 2, 4, 32, 64}, strides[4] = {4 * 8192, 8192, 8 * 8192, 128};
        const cuuint32_t box[5] = {64, 2, 4, 8, 2};
        make_map(enc, &M.sld, p_S, 5, dims, strides, box, true);
    }
    {
        const cuuint64_t dims[5] = {64, 2, 2, 64, 172}, strides[4] = {256, 128, 512, 32768};
        const cuuint32_t box[5] = {64, 2, 2, 2, 8};
        make_map(enc, &M.hld, hptr, 5, dims, strides, box, false);
    }
    fused_kernel<<<NCTA, 512, SMEM_BYTES>>>(P, M);
}
```

```cpp
#include <cuda_runtime.h>
#include <cuda_bf16.h>
#include <cuda.h>
#include <stdint.h>

#define PROF 0

namespace {

constexpr int SEQ = 2048, DM = 512, FF = 1376;
constexpr int NCTA = 132;
#define GOST 1
#define DLY1 300
constexpr int RUNROLL = 2;
constexpr int TOKG = 344;

constexpr uint32_t OFF_W = 0;
constexpr uint32_t XBUF = 22528;
constexpr uint32_t OFF_X = 65536;
constexpr uint32_t OFF_CONV = 155648;
constexpr uint32_t CH_STRIDE = 17536;
constexpr uint32_t CH_T = 0;
constexpr uint32_t CH_A3 = 8448;
constexpr uint32_t CH_B3 = 12544;
constexpr uint32_t CH_U = 13312;
constexpr uint32_t CH_G = CH_A3 + 2064;
constexpr uint32_t UPLANE = 2112;
constexpr uint32_t CH_LN = 0, CH_PART = 4224, CH_LNT = 13440;
constexpr uint32_t OFF_SST = 60416;
constexpr uint32_t OFF_ST = 225792;
constexpr uint32_t OFF_CSUM = 228544;
constexpr uint32_t OFF_BAR = 229056;
constexpr uint32_t SMEM_BYTES = 229568;

enum {
    B_FULLW = 0, B_EMPTYW = 4, B_FULLX = 8, B_EMPTYX = 12, B_FULLD = 16, B_EMPTYD = 24,
    B_U = 32, B_XO = 33, B_S = 34, B_STG = 35, B_HF = 37, B_STATS = 38, B_LNS = 39, B_SST = 40,
    B_LNX = 41, B_CH0 = 42, B_TURN = 43, B_K = 45,
    B_CONV = 46, B_LN = 50, B_CS = 51, B_EPI = 52, B_SIG = 54,
    B_COUNT = 56
};
enum { F_A = 0, F_H = 1, F_S = 13, F_EXIT = 17, F_COUNT = 18 };

__device__ uint4 g_xnT[DM * 256];
__device__ float2 g_st[6 * TOKG];
__device__ uint4 g_H[172 * 256 * 8];
__device__ uint2 g_S[256 * 1024];
__device__ unsigned g_flags[F_COUNT * 32];
#define STAMP(i) do {} while (0)
#define GSTAMP(i) do {} while (0)
#define STAMP2(i) do {} while (0)

__device__ __forceinline__ uint32_t smem_u32(const void* p) { return (uint32_t)__cvta_generic_to_shared(p); }
__device__ __forceinline__ void mbar_expect(uint32_t bar, uint32_t bytes) { asm volatile("mbarrier.arrive.expect_tx.shared::cta.b64 _, [%0], %1;" :: "r"(bar), "r"(bytes) : "memory"); }
__device__ __forceinline__ void mbar_arrive(uint32_t bar) { asm volatile("mbarrier.arrive.shared::cta.b64 _, [%0];" :: "r"(bar) : "memory"); }
__device__ __forceinline__ void mbar_wait(uint32_t bar, uint32_t parity) {
    asm volatile("{.reg .pred p; .reg .u32 n; mov.u32 n, 0x20000;\n"
                 "LW: mbarrier.try_wait.parity.shared::cta.b64 p, [%0], %1;\n"
                 "sub.u32 n, n, 1; setp.eq.or.u32 p, n, 0, p; @!p bra LW;}" :: "r"(bar), "r"(parity) : "memory");
}
__device__ __forceinline__ bool elect_one() { uint32_t p; asm volatile("{.reg .pred P; elect.sync _|P, 0xffffffff; selp.u32 %0, 1, 0, P;}" : "=r"(p)); return p; }
__device__ __forceinline__ void tma2d(uint32_t dst, const CUtensorMap* m, int c0, int c1, uint32_t bar) {
    asm volatile("cp.async.bulk.tensor.2d.shared::cluster.global.mbarrier::complete_tx::bytes [%0], [%1, {%3, %4}], [%2];"
        :: "r"(dst), "l"(m), "r"(bar), "r"(c0), "r"(c1) : "memory");
}
__device__ __forceinline__ void bulk_load(uint32_t dst, const void* src, uint32_t bytes, uint32_t bar) {
    asm volatile("cp.async.bulk.shared::cluster.global.mbarrier::complete_tx::bytes [%0], [%1], %2, [%3];" :: "r"(dst), "l"(src), "r"(bytes), "r"(bar) : "memory");
}
__device__ __forceinline__ void bulk_store(void* dst, uint32_t src, uint32_t bytes) {
    asm volatile("cp.async.bulk.global.shared::cta.bulk_group [%0], [%1], %2;" :: "l"(dst), "r"(src), "r"(bytes) : "memory");
}
__device__ __forceinline__ void fence_async_smem() { asm volatile("fence.proxy.async.shared::cta;" ::: "memory"); }
__device__ __forceinline__ void flag_wait(unsigned* g_flags, int f, unsigned target) {
    asm volatile("{.reg .pred p; .reg .u32 n, v; mov.u32 n, 0x40000;\n"
                 "LF: ld.acquire.gpu.global.u32 v, [%0]; setp.ge.u32 p, v, %1; @p bra LD;\n"
                 "sub.u32 n, n, 1; setp.ne.u32 p, n, 0; @p bra LF; trap;\nLD: }"
                 :: "l"(g_flags + f * 32), "r"(target) : "memory");
}
__device__ __forceinline__ void flag_signal(unsigned* g_flags, int f) {
    asm volatile("cp.async.bulk.commit_group; cp.async.bulk.wait_group 0; red.relaxed.gpu.global.add.u32 [%0], 1;" :: "l"(g_flags + f * 32) : "memory");
}
__device__ __forceinline__ void exit_count(unsigned* g_flags) {
    if (atomicAdd(g_flags + F_EXIT * 32, 1u) == NCTA - 1) {
        #pragma unroll 1
        for (int i = 0; i < F_COUNT; i++) g_flags[i * 32] = 0;
    }
}
__device__ __forceinline__ void bar_sync(int id) { asm volatile("bar.sync %0, 128;" :: "r"(id) : "memory"); }
__device__ __forceinline__ uint64_t mkdesc(uint32_t addr, uint32_t lbo, uint32_t sbo, uint32_t swz) {
    return (uint64_t)((addr >> 4) | ((lbo >> 4) << 16)) | ((uint64_t)((sbo >> 4) | (swz << 30)) << 32);
}
#define WG_FENCE() asm volatile("wgmma.fence.sync.aligned;" ::: "memory")
#define WG_COMMIT() asm volatile("wgmma.commit_group.sync.aligned;" ::: "memory")
#define WG_WAIT(n) asm volatile("wgmma.wait_group.sync.aligned " #n ";" ::: "memory")
template <int N> __device__ __forceinline__ void fence_acc(float (&d)[N]) {
    #pragma unroll
    for (int i = 0; i < N; i++) asm volatile("" : "+f"(d[i]) :: "memory");
}
template <int N> __device__ __forceinline__ void define_acc(float (&d)[N]) {
    #pragma unroll
    for (int i = 0; i < N; i++) asm volatile("" : "=f"(d[i]));
}
__device__ __forceinline__ uint32_t pack2(float lo, float hi) { uint32_t r; asm("cvt.rn.bf16x2.f32 %0, %1, %2;" : "=r"(r) : "f"(hi), "f"(lo)); return r; }
__device__ __forceinline__ float bf_lo(uint32_t v) { return __uint_as_float(v << 16); }
__device__ __forceinline__ float bf_hi(uint32_t v) { return __uint_as_float(v & 0xffff0000u); }
__device__ __forceinline__ float bf_round(float v) { return bf_hi(pack2(0.f, v)); }
__device__ __forceinline__ float tanh_fast(float v) { float r; asm("tanh.approx.f32 %0, %1;" : "=f"(r) : "f"(v)); return r; }
__device__ __forceinline__ float ex2(float v) { float r; asm("ex2.approx.ftz.f32 %0, %1;" : "=f"(r) : "f"(v)); return r; }
__device__ __forceinline__ uint4 lds128(uint32_t a) { uint4 v; asm volatile("ld.shared.v4.b32 {%0,%1,%2,%3}, [%4];" : "=r"(v.x), "=r"(v.y), "=r"(v.z), "=r"(v.w) : "r"(a)); return v; }
__device__ __forceinline__ uint2 lds64(uint32_t a) { uint2 v; asm volatile("ld.shared.v2.b32 {%0,%1}, [%2];" : "=r"(v.x), "=r"(v.y) : "r"(a)); return v; }
__device__ __forceinline__ float ldsf(uint32_t a) { float v; asm volatile("ld.shared.f32 %0, [%1];" : "=f"(v) : "r"(a)); return v; }
__device__ __forceinline__ void sts128(uint32_t a, uint32_t x, uint32_t y, uint32_t z, uint32_t w) { asm volatile("st.shared.v4.b32 [%0], {%1,%2,%3,%4};" :: "r"(a), "r"(x), "r"(y), "r"(z), "r"(w) : "memory"); }
__device__ __forceinline__ void sts64(uint32_t a, uint32_t x, uint32_t y) { asm volatile("st.shared.v2.b32 [%0], {%1,%2};" :: "r"(a), "r"(x), "r"(y) : "memory"); }
__device__ __forceinline__ void stsf(uint32_t a, float x) { asm volatile("st.shared.f32 [%0], %1;" :: "r"(a), "f"(x) : "memory"); }
__device__ __forceinline__ void sts16(uint32_t a, uint32_t x) { asm volatile("st.shared.b16 [%0], %1;" :: "r"(a), "h"((unsigned short)x) : "memory"); }
__device__ __forceinline__ void stsm4(uint32_t a, uint32_t r0, uint32_t r1, uint32_t r2, uint32_t r3) {
    asm volatile("stmatrix.sync.aligned.m8n8.x4.shared.b16 [%0], {%1,%2,%3,%4};" :: "r"(a), "r"(r0), "r"(r1), "r"(r2), "r"(r3) : "memory");
}
__device__ __forceinline__ void ldsm4(uint32_t (&r)[4], uint32_t a) {
    asm volatile("ldmatrix.sync.aligned.m8n8.x4.shared.b16 {%0,%1,%2,%3}, [%4];" : "=r"(r[0]), "=r"(r[1]), "=r"(r[2]), "=r"(r[3]) : "r"(a) : "memory");
}
#define FU(x) __float_as_uint(x)
#define UF(x) __uint_as_float(x)
__device__ __forceinline__ uint32_t wd_slot(int s) { return (uint32_t)((0xbba8403056201000ull >> (8 * s)) & 0xff) << 10; }
__device__ __forceinline__ uint32_t h_slot(int s) { return (uint32_t)((0xcba0908880787068ull >> (8 * s)) & 0xff) << 10; }

template<int N> __device__ __forceinline__ void wg_rs(float (&d)[64], uint32_t a0, uint32_t a1, uint32_t a2, uint32_t a3, uint64_t db);
template<> __device__ __forceinline__ void wg_rs<128>(float (&d)[64], uint32_t a0, uint32_t a1, uint32_t a2, uint32_t a3, uint64_t db) {
  asm volatile("{.reg .pred p; setp.ne.b32 p, 1, 0; wgmma.mma_async.sync.aligned.m64n128k16.f32.bf16.bf16 {%0,%1,%2,%3,%4,%5,%6,%7,%8,%9,%10,%11,%12,%13,%14,%15,%16,%17,%18,%19,%20,%21,%22,%23,%24,%25,%26,%27,%28,%29,%30,%31,%32,%33,%34,%35,%36,%37,%38,%39,%40,%41,%42,%43,%44,%45,%46,%47,%48,%49,%50,%51,%52,%53,%54,%55,%56,%57,%58,%59,%60,%61,%62,%63}, {%64,%65,%66,%67}, %68, p, 1, 1, 0;}"
    : "+f"(d[0]),"+f"(d[1]),"+f"(d[2]),"+f"(d[3]),"+f"(d[4]),"+f"(d[5]),"+f"(d[6]),"+f"(d[7]),"+f"(d[8]),"+f"(d[9]),"+f"(d[10]),"+f"(d[11]),"+f"(d[12]),"+f"(d[13]),"+f"(d[14]),"+f"(d[15]),"+f"(d[16]),"+f"(d[17]),"+f"(d[18]),"+f"(d[19]),"+f"(d[20]),"+f"(d[21]),"+f"(d[22]),"+f"(d[23]),"+f"(d[24]),"+f"(d[25]),"+f"(d[26]),"+f"(d[27]),"+f"(d[28]),"+f"(d[29]),"+f"(d[30]),"+f"(d[31]),"+f"(d[32]),"+f"(d[33]),"+f"(d[34]),"+f"(d[35]),"+f"(d[36]),"+f"(d[37]),"+f"(d[38]),"+f"(d[39]),"+f"(d[40]),"+f"(d[41]),"+f"(d[42]),"+f"(d[43]),"+f"(d[44]),"+f"(d[45]),"+f"(d[46]),"+f"(d[47]),"+f"(d[48]),"+f"(d[49]),"+f"(d[50]),"+f"(d[51]),"+f"(d[52]),"+f"(d[53]),"+f"(d[54]),"+f"(d[55]),"+f"(d[56]),"+f"(d[57]),"+f"(d[58]),"+f"(d[59]),"+f"(d[60]),"+f"(d[61]),"+f"(d[62]),"+f"(d[63]) : "r"(a0), "r"(a1), "r"(a2), "r"(a3), "l"(db));
}
template<> __device__ __forceinline__ void wg_rs<120>(float (&d)[64], uint32_t a0, uint32_t a1, uint32_t a2, uint32_t a3, uint64_t db) {
  asm volatile("{.reg .pred p; setp.ne.b32 p, 1, 0; wgmma.mma_async.sync.aligned.m64n120k16.f32.bf16.bf16 {%0,%1,%2,%3,%4,%5,%6,%7,%8,%9,%10,%11,%12,%13,%14,%15,%16,%17,%18,%19,%20,%21,%22,%23,%24,%25,%26,%27,%28,%29,%30,%31,%32,%33,%34,%35,%36,%37,%38,%39,%40,%41,%42,%43,%44,%45,%46,%47,%48,%49,%50,%51,%52,%53,%54,%55,%56,%57,%58,%59}, {%60,%61,%62,%63}, %64, p, 1, 1, 0;}"
    : "+f"(d[0]),"+f"(d[1]),"+f"(d[2]),"+f"(d[3]),"+f"(d[4]),"+f"(d[5]),"+f"(d[6]),"+f"(d[7]),"+f"(d[8]),"+f"(d[9]),"+f"(d[10]),"+f"(d[11]),"+f"(d[12]),"+f"(d[13]),"+f"(d[14]),"+f"(d[15]),"+f"(d[16]),"+f"(d[17]),"+f"(d[18]),"+f"(d[19]),"+f"(d[20]),"+f"(d[21]),"+f"(d[22]),"+f"(d[23]),"+f"(d[24]),"+f"(d[25]),"+f"(d[26]),"+f"(d[27]),"+f"(d[28]),"+f"(d[29]),"+f"(d[30]),"+f"(d[31]),"+f"(d[32]),"+f"(d[33]),"+f"(d[34]),"+f"(d[35]),"+f"(d[36]),"+f"(d[37]),"+f"(d[38]),"+f"(d[39]),"+f"(d[40]),"+f"(d[41]),"+f"(d[42]),"+f"(d[43]),"+f"(d[44]),"+f"(d[45]),"+f"(d[46]),"+f"(d[47]),"+f"(d[48]),"+f"(d[49]),"+f"(d[50]),"+f"(d[51]),"+f"(d[52]),"+f"(d[53]),"+f"(d[54]),"+f"(d[55]),"+f"(d[56]),"+f"(d[57]),"+f"(d[58]),"+f"(d[59]) : "r"(a0), "r"(a1), "r"(a2), "r"(a3), "l"(db));
}
template<> __device__ __forceinline__ void wg_rs<112>(float (&d)[64], uint32_t a0, uint32_t a1, uint32_t a2, uint32_t a3, uint64_t db) {
  asm volatile("{.reg .pred p; setp.ne.b32 p, 1, 0; wgmma.mma_async.sync.aligned.m64n112k16.f32.bf16.bf16 {%0,%1,%2,%3,%4,%5,%6,%7,%8,%9,%10,%11,%12,%13,%14,%15,%16,%17,%18,%19,%20,%21,%22,%23,%24,%25,%26,%27,%28,%29,%30,%31,%32,%33,%34,%35,%36,%37,%38,%39,%40,%41,%42,%43,%44,%45,%46,%47,%48,%49,%50,%51,%52,%53,%54,%55}, {%56,%57,%58,%59}, %60, p, 1, 1, 0;}"
    : "+f"(d[0]),"+f"(d[1]),"+f"(d[2]),"+f"(d[3]),"+f"(d[4]),"+f"(d[5]),"+f"(d[6]),"+f"(d[7]),"+f"(d[8]),"+f"(d[9]),"+f"(d[10]),"+f"(d[11]),"+f"(d[12]),"+f"(d[13]),"+f"(d[14]),"+f"(d[15]),"+f"(d[16]),"+f"(d[17]),"+f"(d[18]),"+f"(d[19]),"+f"(d[20]),"+f"(d[21]),"+f"(d[22]),"+f"(d[23]),"+f"(d[24]),"+f"(d[25]),"+f"(d[26]),"+f"(d[27]),"+f"(d[28]),"+f"(d[29]),"+f"(d[30]),"+f"(d[31]),"+f"(d[32]),"+f"(d[33]),"+f"(d[34]),"+f"(d[35]),"+f"(d[36]),"+f"(d[37]),"+f"(d[38]),"+f"(d[39]),"+f"(d[40]),"+f"(d[41]),"+f"(d[42]),"+f"(d[43]),"+f"(d[44]),"+f"(d[45]),"+f"(d[46]),"+f"(d[47]),"+f"(d[48]),"+f"(d[49]),"+f"(d[50]),"+f"(d[51]),"+f"(d[52]),"+f"(d[53]),"+f"(d[54]),"+f"(d[55]) : "r"(a0), "r"(a1), "r"(a2), "r"(a3), "l"(db));
}
template<> __device__ __forceinline__ void wg_rs<104>(float (&d)[64], uint32_t a0, uint32_t a1, uint32_t a2, uint32_t a3, uint64_t db) {
  asm volatile("{.reg .pred p; setp.ne.b32 p, 1, 0; wgmma.mma_async.sync.aligned.m64n104k16.f32.bf16.bf16 {%0,%1,%2,%3,%4,%5,%6,%7,%8,%9,%10,%11,%12,%13,%14,%15,%16,%17,%18,%19,%20,%21,%22,%23,%24,%25,%26,%27,%28,%29,%30,%31,%32,%33,%34,%35,%36,%37,%38,%39,%40,%41,%42,%43,%44,%45,%46,%47,%48,%49,%50,%51}, {%52,%53,%54,%55}, %56, p, 1, 1, 0;}"
    : "+f"(d[0]),"+f"(d[1]),"+f"(d[2]),"+f"(d[3]),"+f"(d[4]),"+f"(d[5]),"+f"(d[6]),"+f"(d[7]),"+f"(d[8]),"+f"(d[9]),"+f"(d[10]),"+f"(d[11]),"+f"(d[12]),"+f"(d[13]),"+f"(d[14]),"+f"(d[15]),"+f"(d[16]),"+f"(d[17]),"+f"(d[18]),"+f"(d[19]),"+f"(d[20]),"+f"(d[21]),"+f"(d[22]),"+f"(d[23]),"+f"(d[24]),"+f"(d[25]),"+f"(d[26]),"+f"(d[27]),"+f"(d[28]),"+f"(d[29]),"+f"(d[30]),"+f"(d[31]),"+f"(d[32]),"+f"(d[33]),"+f"(d[34]),"+f"(d[35]),"+f"(d[36]),"+f"(d[37]),"+f"(d[38]),"+f"(d[39]),"+f"(d[40]),"+f"(d[41]),"+f"(d[42]),"+f"(d[43]),"+f"(d[44]),"+f"(d[45]),"+f"(d[46]),"+f"(d[47]),"+f"(d[48]),"+f"(d[49]),"+f"(d[50]),"+f"(d[51]) : "r"(a0), "r"(a1), "r"(a2), "r"(a3), "l"(db));
}
template<> __device__ __forceinline__ void wg_rs<96>(float (&d)[64], uint32_t a0, uint32_t a1, uint32_t a2, uint32_t a3, uint64_t db) {
  asm volatile("{.reg .pred p; setp.ne.b32 p, 1, 0; wgmma.mma_async.sync.aligned.m64n96k16.f32.bf16.bf16 {%0,%1,%2,%3,%4,%5,%6,%7,%8,%9,%10,%11,%12,%13,%14,%15,%16,%17,%18,%19,%20,%21,%22,%23,%24,%25,%26,%27,%28,%29,%30,%31,%32,%33,%34,%35,%36,%37,%38,%39,%40,%41,%42,%43,%44,%45,%46,%47}, {%48,%49,%50,%51}, %52, p, 1, 1, 0;}"
    : "+f"(d[0]),"+f"(d[1]),"+f"(d[2]),"+f"(d[3]),"+f"(d[4]),"+f"(d[5]),"+f"(d[6]),"+f"(d[7]),"+f"(d[8]),"+f"(d[9]),"+f"(d[10]),"+f"(d[11]),"+f"(d[12]),"+f"(d[13]),"+f"(d[14]),"+f"(d[15]),"+f"(d[16]),"+f"(d[17]),"+f"(d[18]),"+f"(d[19]),"+f"(d[20]),"+f"(d[21]),"+f"(d[22]),"+f"(d[23]),"+f"(d[24]),"+f"(d[25]),"+f"(d[26]),"+f"(d[27]),"+f"(d[28]),"+f"(d[29]),"+f"(d[30]),"+f"(d[31]),"+f"(d[32]),"+f"(d[33]),"+f"(d[34]),"+f"(d[35]),"+f"(d[36]),"+f"(d[37]),"+f"(d[38]),"+f"(d[39]),"+f"(d[40]),"+f"(d[41]),"+f"(d[42]),"+f"(d[43]),"+f"(d[44]),"+f"(d[45]),"+f"(d[46]),"+f"(d[47]) : "r"(a0), "r"(a1), "r"(a2), "r"(a3), "l"(db));
}
template<> __device__ __forceinline__ void wg_rs<88>(float (&d)[64], uint32_t a0, uint32_t a1, uint32_t a2, uint32_t a3, uint64_t db) {
  asm volatile("{.reg .pred p; setp.ne.b32 p, 1, 0; wgmma.mma_async.sync.aligned.m64n88k16.f32.bf16.bf16 {%0,%1,%2,%3,%4,%5,%6,%7,%8,%9,%10,%11,%12,%13,%14,%15,%16,%17,%18,%19,%20,%21,%22,%23,%24,%25,%26,%27,%28,%29,%30,%31,%32,%33,%34,%35,%36,%37,%38,%39,%40,%41,%42,%43}, {%44,%45,%46,%47}, %48, p, 1, 1, 0;}"
    : "+f"(d[0]),"+f"(d[1]),"+f"(d[2]),"+f"(d[3]),"+f"(d[4]),"+f"(d[5]),"+f"(d[6]),"+f"(d[7]),"+f"(d[8]),"+f"(d[9]),"+f"(d[10]),"+f"(d[11]),"+f"(d[12]),"+f"(d[13]),"+f"(d[14]),"+f"(d[15]),"+f"(d[16]),"+f"(d[17]),"+f"(d[18]),"+f"(d[19]),"+f"(d[20]),"+f"(d[21]),"+f"(d[22]),"+f"(d[23]),"+f"(d[24]),"+f"(d[25]),"+f"(d[26]),"+f"(d[27]),"+f"(d[28]),"+f"(d[29]),"+f"(d[30]),"+f"(d[31]),"+f"(d[32]),"+f"(d[33]),"+f"(d[34]),"+f"(d[35]),"+f"(d[36]),"+f"(d[37]),"+f"(d[38]),"+f"(d[39]),"+f"(d[40]),"+f"(d[41]),"+f"(d[42]),"+f"(d[43]) : "r"(a0), "r"(a1), "r"(a2), "r"(a3), "l"(db));
}
template<> __device__ __forceinline__ void wg_rs<80>(float (&d)[64], uint32_t a0, uint32_t a1, uint32_t a2, uint32_t a3, uint64_t db) {
  asm volatile("{.reg .pred p; setp.ne.b32 p, 1, 0; wgmma.mma_async.sync.aligned.m64n80k16.f32.bf16.bf16 {%0,%1,%2,%3,%4,%5,%6,%7,%8,%9,%10,%11,%12,%13,%14,%15,%16,%17,%18,%19,%20,%21,%22,%23,%24,%25,%26,%27,%28,%29,%30,%31,%32,%33,%34,%35,%36,%37,%38,%39}, {%40,%41,%42,%43}, %44, p, 1, 1, 0;}"
    : "+f"(d[0]),"+f"(d[1]),"+f"(d[2]),"+f"(d[3]),"+f"(d[4]),"+f"(d[5]),"+f"(d[6]),"+f"(d[7]),"+f"(d[8]),"+f"(d[9]),"+f"(d[10]),"+f"(d[11]),"+f"(d[12]),"+f"(d[13]),"+f"(d[14]),"+f"(d[15]),"+f"(d[16]),"+f"(d[17]),"+f"(d[18]),"+f"(d[19]),"+f"(d[20]),"+f"(d[21]),"+f"(d[22]),"+f"(d[23]),"+f"(d[24]),"+f"(d[25]),"+f"(d[26]),"+f"(d[27]),"+f"(d[28]),"+f"(d[29]),"+f"(d[30]),"+f"(d[31]),"+f"(d[32]),"+f"(d[33]),"+f"(d[34]),"+f"(d[35]),"+f"(d[36]),"+f"(d[37]),"+f"(d[38]),"+f"(d[39]) : "r"(a0), "r"(a1), "r"(a2), "r"(a3), "l"(db));
}
template<> __device__ __forceinline__ void wg_rs<72>(float (&d)[64], uint32_t a0, uint32_t a1, uint32_t a2, uint32_t a3, uint64_t db) {
  asm volatile("{.reg .pred p; setp.ne.b32 p, 1, 0; wgmma.mma_async.sync.aligned.m64n72k16.f32.bf16.bf16 {%0,%1,%2,%3,%4,%5,%6,%7,%8,%9,%10,%11,%12,%13,%14,%15,%16,%17,%18,%19,%20,%21,%22,%23,%24,%25,%26,%27,%28,%29,%30,%31,%32,%33,%34,%35}, {%36,%37,%38,%39}, %40, p, 1, 1, 0;}"
    : "+f"(d[0]),"+f"(d[1]),"+f"(d[2]),"+f"(d[3]),"+f"(d[4]),"+f"(d[5]),"+f"(d[6]),"+f"(d[7]),"+f"(d[8]),"+f"(d[9]),"+f"(d[10]),"+f"(d[11]),"+f"(d[12]),"+f"(d[13]),"+f"(d[14]),"+f"(d[15]),"+f"(d[16]),"+f"(d[17]),"+f"(d[18]),"+f"(d[19]),"+f"(d[20]),"+f"(d[21]),"+f"(d[22]),"+f"(d[23]),"+f"(d[24]),"+f"(d[25]),"+f"(d[26]),"+f"(d[27]),"+f"(d[28]),"+f"(d[29]),"+f"(d[30]),"+f"(d[31]),"+f"(d[32]),"+f"(d[33]),"+f"(d[34]),"+f"(d[35]) : "r"(a0), "r"(a1), "r"(a2), "r"(a3), "l"(db));
}
template<> __device__ __forceinline__ void wg_rs<64>(float (&d)[64], uint32_t a0, uint32_t a1, uint32_t a2, uint32_t a3, uint64_t db) {
  asm volatile("{.reg .pred p; setp.ne.b32 p, 1, 0; wgmma.mma_async.sync.aligned.m64n64k16.f32.bf16.bf16 {%0,%1,%2,%3,%4,%5,%6,%7,%8,%9,%10,%11,%12,%13,%14,%15,%16,%17,%18,%19,%20,%21,%22,%23,%24,%25,%26,%27,%28,%29,%30,%31}, {%32,%33,%34,%35}, %36, p, 1, 1, 0;}"
    : "+f"(d[0]),"+f"(d[1]),"+f"(d[2]),"+f"(d[3]),"+f"(d[4]),"+f"(d[5]),"+f"(d[6]),"+f"(d[7]),"+f"(d[8]),"+f"(d[9]),"+f"(d[10]),"+f"(d[11]),"+f"(d[12]),"+f"(d[13]),"+f"(d[14]),"+f"(d[15]),"+f"(d[16]),"+f"(d[17]),"+f"(d[18]),"+f"(d[19]),"+f"(d[20]),"+f"(d[21]),"+f"(d[22]),"+f"(d[23]),"+f"(d[24]),"+f"(d[25]),"+f"(d[26]),"+f"(d[27]),"+f"(d[28]),"+f"(d[29]),"+f"(d[30]),"+f"(d[31]) : "r"(a0), "r"(a1), "r"(a2), "r"(a3), "l"(db));
}
__device__ __forceinline__ void wg_rs_first(float (&d)[64], uint32_t a0, uint32_t a1, uint32_t a2, uint32_t a3, uint64_t db) {
  asm volatile("{.reg .pred p; setp.ne.b32 p, 0, 0; wgmma.mma_async.sync.aligned.m64n128k16.f32.bf16.bf16 {%0,%1,%2,%3,%4,%5,%6,%7,%8,%9,%10,%11,%12,%13,%14,%15,%16,%17,%18,%19,%20,%21,%22,%23,%24,%25,%26,%27,%28,%29,%30,%31,%32,%33,%34,%35,%36,%37,%38,%39,%40,%41,%42,%43,%44,%45,%46,%47,%48,%49,%50,%51,%52,%53,%54,%55,%56,%57,%58,%59,%60,%61,%62,%63}, {%64,%65,%66,%67}, %68, p, 1, 1, 0;}"
    : "=f"(d[0]),"=f"(d[1]),"=f"(d[2]),"=f"(d[3]),"=f"(d[4]),"=f"(d[5]),"=f"(d[6]),"=f"(d[7]),"=f"(d[8]),"=f"(d[9]),"=f"(d[10]),"=f"(d[11]),"=f"(d[12]),"=f"(d[13]),"=f"(d[14]),"=f"(d[15]),"=f"(d[16]),"=f"(d[17]),"=f"(d[18]),"=f"(d[19]),"=f"(d[20]),"=f"(d[21]),"=f"(d[22]),"=f"(d[23]),"=f"(d[24]),"=f"(d[25]),"=f"(d[26]),"=f"(d[27]),"=f"(d[28]),"=f"(d[29]),"=f"(d[30]),"=f"(d[31]),"=f"(d[32]),"=f"(d[33]),"=f"(d[34]),"=f"(d[35]),"=f"(d[36]),"=f"(d[37]),"=f"(d[38]),"=f"(d[39]),"=f"(d[40]),"=f"(d[41]),"=f"(d[42]),"=f"(d[43]),"=f"(d[44]),"=f"(d[45]),"=f"(d[46]),"=f"(d[47]),"=f"(d[48]),"=f"(d[49]),"=f"(d[50]),"=f"(d[51]),"=f"(d[52]),"=f"(d[53]),"=f"(d[54]),"=f"(d[55]),"=f"(d[56]),"=f"(d[57]),"=f"(d[58]),"=f"(d[59]),"=f"(d[60]),"=f"(d[61]),"=f"(d[62]),"=f"(d[63]) : "r"(a0), "r"(a1), "r"(a2), "r"(a3), "l"(db));
}
__device__ __forceinline__ void wg_tt128(float (&d)[64], uint64_t da, uint64_t db, int sc) {
  asm volatile("{.reg .pred p; setp.ne.b32 p, %66, 0; wgmma.mma_async.sync.aligned.m64n128k16.f32.bf16.bf16 {%0,%1,%2,%3,%4,%5,%6,%7,%8,%9,%10,%11,%12,%13,%14,%15,%16,%17,%18,%19,%20,%21,%22,%23,%24,%25,%26,%27,%28,%29,%30,%31,%32,%33,%34,%35,%36,%37,%38,%39,%40,%41,%42,%43,%44,%45,%46,%47,%48,%49,%50,%51,%52,%53,%54,%55,%56,%57,%58,%59,%60,%61,%62,%63}, %64, %65, p, 1, 1, 1, 1;}"
    : "+f"(d[0]),"+f"(d[1]),"+f"(d[2]),"+f"(d[3]),"+f"(d[4]),"+f"(d[5]),"+f"(d[6]),"+f"(d[7]),"+f"(d[8]),"+f"(d[9]),"+f"(d[10]),"+f"(d[11]),"+f"(d[12]),"+f"(d[13]),"+f"(d[14]),"+f"(d[15]),"+f"(d[16]),"+f"(d[17]),"+f"(d[18]),"+f"(d[19]),"+f"(d[20]),"+f"(d[21]),"+f"(d[22]),"+f"(d[23]),"+f"(d[24]),"+f"(d[25]),"+f"(d[26]),"+f"(d[27]),"+f"(d[28]),"+f"(d[29]),"+f"(d[30]),"+f"(d[31]),"+f"(d[32]),"+f"(d[33]),"+f"(d[34]),"+f"(d[35]),"+f"(d[36]),"+f"(d[37]),"+f"(d[38]),"+f"(d[39]),"+f"(d[40]),"+f"(d[41]),"+f"(d[42]),"+f"(d[43]),"+f"(d[44]),"+f"(d[45]),"+f"(d[46]),"+f"(d[47]),"+f"(d[48]),"+f"(d[49]),"+f"(d[50]),"+f"(d[51]),"+f"(d[52]),"+f"(d[53]),"+f"(d[54]),"+f"(d[55]),"+f"(d[56]),"+f"(d[57]),"+f"(d[58]),"+f"(d[59]),"+f"(d[60]),"+f"(d[61]),"+f"(d[62]),"+f"(d[63]) : "l"(da), "l"(db), "r"(sc));
}
__device__ __forceinline__ void wg_tt64(float (&d)[64], uint64_t da, uint64_t db, int sc) {
  asm volatile("{.reg .pred p; setp.ne.b32 p, %34, 0; wgmma.mma_async.sync.aligned.m64n64k16.f32.bf16.bf16 {%0,%1,%2,%3,%4,%5,%6,%7,%8,%9,%10,%11,%12,%13,%14,%15,%16,%17,%18,%19,%20,%21,%22,%23,%24,%25,%26,%27,%28,%29,%30,%31}, %32, %33, p, 1, 1, 1, 1;}"
    : "+f"(d[0]),"+f"(d[1]),"+f"(d[2]),"+f"(d[3]),"+f"(d[4]),"+f"(d[5]),"+f"(d[6]),"+f"(d[7]),"+f"(d[8]),"+f"(d[9]),"+f"(d[10]),"+f"(d[11]),"+f"(d[12]),"+f"(d[13]),"+f"(d[14]),"+f"(d[15]),"+f"(d[16]),"+f"(d[17]),"+f"(d[18]),"+f"(d[19]),"+f"(d[20]),"+f"(d[21]),"+f"(d[22]),"+f"(d[23]),"+f"(d[24]),"+f"(d[25]),"+f"(d[26]),"+f"(d[27]),"+f"(d[28]),"+f"(d[29]),"+f"(d[30]),"+f"(d[31]) : "l"(da), "l"(db), "r"(sc));
}
__device__ __forceinline__ void wg_tt32(float (&d)[64], uint64_t da, uint64_t db, int sc) {
  asm volatile("{.reg .pred p; setp.ne.b32 p, %18, 0; wgmma.mma_async.sync.aligned.m64n32k16.f32.bf16.bf16 {%0,%1,%2,%3,%4,%5,%6,%7,%8,%9,%10,%11,%12,%13,%14,%15}, %16, %17, p, 1, 1, 1, 1;}"
    : "+f"(d[0]),"+f"(d[1]),"+f"(d[2]),"+f"(d[3]),"+f"(d[4]),"+f"(d[5]),"+f"(d[6]),"+f"(d[7]),"+f"(d[8]),"+f"(d[9]),"+f"(d[10]),"+f"(d[11]),"+f"(d[12]),"+f"(d[13]),"+f"(d[14]),"+f"(d[15]) : "l"(da), "l"(db), "r"(sc));
}
__device__ __forceinline__ void wg_g1(float (&d)[88], uint64_t da, uint64_t db, int sc) {
  asm volatile("{.reg .pred p; setp.ne.b32 p, %90, 0; wgmma.mma_async.sync.aligned.m64n176k16.f32.bf16.bf16 {%0,%1,%2,%3,%4,%5,%6,%7,%8,%9,%10,%11,%12,%13,%14,%15,%16,%17,%18,%19,%20,%21,%22,%23,%24,%25,%26,%27,%28,%29,%30,%31,%32,%33,%34,%35,%36,%37,%38,%39,%40,%41,%42,%43,%44,%45,%46,%47,%48,%49,%50,%51,%52,%53,%54,%55,%56,%57,%58,%59,%60,%61,%62,%63,%64,%65,%66,%67,%68,%69,%70,%71,%72,%73,%74,%75,%76,%77,%78,%79,%80,%81,%82,%83,%84,%85,%86,%87}, %88, %89, p, 1, 1, 1, 0;}"
    : "+f"(d[0]),"+f"(d[1]),"+f"(d[2]),"+f"(d[3]),"+f"(d[4]),"+f"(d[5]),"+f"(d[6]),"+f"(d[7]),"+f"(d[8]),"+f"(d[9]),"+f"(d[10]),"+f"(d[11]),"+f"(d[12]),"+f"(d[13]),"+f"(d[14]),"+f"(d[15]),"+f"(d[16]),"+f"(d[17]),"+f"(d[18]),"+f"(d[19]),"+f"(d[20]),"+f"(d[21]),"+f"(d[22]),"+f"(d[23]),"+f"(d[24]),"+f"(d[25]),"+f"(d[26]),"+f"(d[27]),"+f"(d[28]),"+f"(d[29]),"+f"(d[30]),"+f"(d[31]),"+f"(d[32]),"+f"(d[33]),"+f"(d[34]),"+f"(d[35]),"+f"(d[36]),"+f"(d[37]),"+f"(d[38]),"+f"(d[39]),"+f"(d[40]),"+f"(d[41]),"+f"(d[42]),"+f"(d[43]),"+f"(d[44]),"+f"(d[45]),"+f"(d[46]),"+f"(d[47]),"+f"(d[48]),"+f"(d[49]),"+f"(d[50]),"+f"(d[51]),"+f"(d[52]),"+f"(d[53]),"+f"(d[54]),"+f"(d[55]),"+f"(d[56]),"+f"(d[57]),"+f"(d[58]),"+f"(d[59]),"+f"(d[60]),"+f"(d[61]),"+f"(d[62]),"+f"(d[63]),"+f"(d[64]),"+f"(d[65]),"+f"(d[66]),"+f"(d[67]),"+f"(d[68]),"+f"(d[69]),"+f"(d[70]),"+f"(d[71]),"+f"(d[72]),"+f"(d[73]),"+f"(d[74]),"+f"(d[75]),"+f"(d[76]),"+f"(d[77]),"+f"(d[78]),"+f"(d[79]),"+f"(d[80]),"+f"(d[81]),"+f"(d[82]),"+f"(d[83]),"+f"(d[84]),"+f"(d[85]),"+f"(d[86]),"+f"(d[87]) : "l"(da), "l"(db), "r"(sc));
}

struct Params { const __nv_bfloat16 *x, *logA, *Aim, *Cr, *Ci, *logdt, *Dskip, *Wg, *Wu, *Wd; uint4* xnT; float2* st; uint2* S; unsigned* flags; };
struct Maps { CUtensorMap x[2], xo, out, wg, wu, wd, hst[2], hld, xt, sld; };

__device__ __forceinline__ void conv_channel(uint32_t cb, int w, int lane, uint32_t (&res)[8], uint32_t sig, int sidx) {
    const int q = lane & 3, g = lane >> 2, gam = g >> 2;
    float acc[64];
    uint2 a[17][2];
    const uint32_t t0 = cb + CH_T + (uint32_t)(14 + 4 * w + (g & 3) - 2 * q) * 280u + gam * 8;
#define LDA(s0, s1) _Pragma("unroll") for (int s = s0; s < s1; s++) { a[s][0] = lds64(t0 + s * 16); a[s][1] = lds64(t0 - 8 * 280 + s * 16); }
#define CT(N, s) wg_rs<N>(acc, a[s][0].x, a[s][0].y, a[s][1].x, a[s][1].y, dU + 4 * (s))
    const uint64_t dU = mkdesc(cb + CH_U, UPLANE, 128, 0);
    LDA(0, 17)
    if (sig) { fence_async_smem(); mbar_arrive(sig); }
    WG_FENCE();
    if (w == 0) STAMP2(52 + 3 * sidx);
    wg_rs_first(acc, a[0][0].x, a[0][0].y, a[0][1].x, a[0][1].y, dU);
    CT(128, 1); CT(120, 2); CT(120, 3); CT(112, 4); CT(112, 5); CT(104, 6); CT(104, 7); CT(96, 8);
    CT(96, 9); CT(88, 10); CT(88, 11); CT(80, 12); CT(80, 13); CT(72, 14); CT(72, 15); CT(64, 16);
#undef CT
#undef LDA
    wg_tt64(acc, mkdesc(cb + CH_A3, 128, 512, 0), mkdesc(cb + CH_B3, 384, 32, 0), 1);
    wg_tt32(acc, mkdesc(cb + CH_A3 + 256, 128, 512, 0), mkdesc(cb + CH_B3 + 128, 384, 32, 0), 1);
    WG_COMMIT();
    if (w == 0) STAMP2(53 + 3 * sidx);
    WG_WAIT(0);
    fence_acc(acc);
    if (w == 0) STAMP2(54 + 3 * sidx);
    const int src1 = (lane & ~3) | ((q + 1) & 3);
    float E[16][2];
    #pragma unroll
    for (int j = 0; j < 16; j++) {
        const float nxt = (j < 15) ? acc[4 * (j + 1) + 2] : 0.f;
        const float sup = (q == 0) ? nxt : acc[4 * j + 2];
        const float v = __shfl_sync(0xffffffffu, sup, src1);
        E[j][0] = acc[4 * j] + acc[4 * j + 3];
        E[j][1] = acc[4 * j + 1] + v;
    }
    const int src2 = gam ? ((lane & 12) | ((q + 3) & 3)) : (16 | (lane & 12) | ((q + 1) & 3));
    const bool c1 = gam && q != 0, c2 = gam && q == 0;
    #pragma unroll
    for (int a2 = 0; a2 < 8; a2++) {
        float y[2];
        #pragma unroll
        for (int e = 0; e < 2; e++) {
            const float sup = c1 ? E[2 * a2][e] : E[2 * a2 + 1][e];
            const float nxt = (a2 < 7) ? E[2 * a2 + 2][e] : 0.f;
            const float keep = c2 ? nxt : (c1 ? E[2 * a2 + 1][e] : E[2 * a2][e]);
            y[e] = keep + __shfl_sync(0xffffffffu, sup, src2);
        }
        res[a2] = pack2(y[1], y[0]);
    }
}

__device__ __forceinline__ void consumer(uint32_t sb, int warp, const Params& P, const Maps& M) {
    const int V = warp >> 2, w = warp & 3, lane = threadIdx.x & 31, q = lane & 3, g = lane >> 2;
    const int c = blockIdx.x;
    const uint32_t bars = sb + OFF_BAR, xb = sb + OFF_X + V * 2 * XBUF;
    {
        float ag[88], au[88];
        define_acc(ag); define_acc(au);
        #pragma unroll 1
        for (int st = 0; st < 8; st++) {
            mbar_wait(bars + 8 * (B_FULLW + (st & 3)), st >> 2);
            mbar_wait(bars + 8 * (B_FULLX + 2 * V + (st & 1)), (st >> 1) & 1);
            const uint64_t dG = mkdesc(sb + OFF_W + (st & 3) * 16384, 0, 1024, 1);
            const uint64_t dX = mkdesc(xb + (st & 1) * XBUF, 16, 1024, 1);
            if (V ? st < 7 : st > 1) mbar_wait(bars + 8 * (B_TURN + V), st & 1);
            STAMP(40 + 8 * V + st);
            WG_FENCE();
            #pragma unroll
            for (int k = 0; k < 4; k++) {
                wg_g1(ag, dG + k * 128, dX + k * 2, k ? 1 : st);
                wg_g1(au, dG + 512 + k * 128, dX + k * 2, k ? 1 : st);
            }
            WG_COMMIT();
            if (lane == 0 && (V ? st < 6 : st > 0)) mbar_arrive(bars + 8 * (B_TURN + 1 - V));
            const bool b2b = st == 6 * V;
            WG_WAIT(1);
            if (lane == 0 && st == 6 * V + 1) {
                mbar_arrive(bars + 8 * (B_EMPTYW + ((st - 1) & 3)));
                mbar_arrive(bars + 8 * (B_EMPTYX + 2 * V + ((st - 1) & 1)));
            }
            if (!b2b) {
                WG_WAIT(0);
                if (lane == 0) { mbar_arrive(bars + 8 * (B_EMPTYW + (st & 3))); mbar_arrive(bars + 8 * (B_EMPTYX + 2 * V + (st & 1))); }
            }
        }
        WG_WAIT(0);
        fence_acc(ag); fence_acc(au);
        STAMP(8 * V + 1);
        float cg0 = ag[84], cg1 = ag[86], cu0 = au[84], cu1 = au[86];
        const uint32_t ca = sb + OFF_CSUM + (8 * w + g) * 16;
        if (V == 0) { sts128(ca, FU(cg0), FU(cg1), FU(cu0), FU(cu1)); mbar_arrive(bars + 8 * B_CS); }
        else { mbar_wait(bars + 8 * B_CS, 0); const uint4 t = lds128(ca); cg0 = UF(t.x); cg1 = UF(t.y); cu0 = UF(t.z); cu1 = UF(t.w); }
        mbar_wait(bars + 8 * B_STATS, 0);
        mbar_wait(bars + 8 * (B_EMPTYX + 2 * V), 1);
        STAMP(13 + V);
        const uint32_t hs = xb + (2 * w + ((lane >> 3) & 1)) * (2688 + 128 * V) + (lane >> 4) * 128 + (lane & 7) * 16;
        const uint32_t sa = sb + OFF_ST + (168 * V + 2 * q) * 8;
        uint4 sq[22];
        #pragma unroll
        for (int j = 0; j < 3; j++) sq[j] = lds128(sa + j * 64);
        #pragma unroll
        for (int j = 0; j < 22; j += 2) {
            uint32_t o[4];
            #pragma unroll
            for (int jj = 0; jj < 2; jj++) {
                const uint4 sv = sq[j + jj];
                float hv[4];
                #pragma unroll
                for (int i = 0; i < 4; i++) {
                    const float m = UF((i & 1) ? sv.z : sv.x);
                    const float gh = fmaf(-m, (i & 2) ? cg1 : cg0, ag[4 * (j + jj) + i]) * UF((i & 1) ? sv.w : sv.y);
                    const float p = gh * fmaf(-m, (i & 2) ? cu1 : cu0, au[4 * (j + jj) + i]);
                    hv[i] = fmaf(p, tanh_fast(gh), p);
                }
                o[2 * jj] = pack2(hv[0], hv[1]); o[2 * jj + 1] = pack2(hv[2], hv[3]);
            }
            #pragma unroll
            for (int k = (j ? 3 + 3 * j / 2 : 3); k < 6 + 3 * j / 2 && k < 22; k++) sq[k] = lds128(sa + k * 64);
            uint32_t ad = hs + j * 128;
            if (j == 20 && V == 0 && lane >= 16) ad = xb + 21504 + (lane & 7) * 16;
            stsm4(ad, o[0], o[1], o[2], o[3]);
        }
        if (c >= 128) { fence_async_smem(); mbar_arrive(bars + 8 * (B_EPI + V)); }
        STAMP(8 * V + 2);
    }
    if (c >= 128) return;
    {
        uint32_t r0[8], r1[8];
        #pragma unroll
        for (int i = 0; i < 8; i++) asm volatile("" : "=r"(r1[i]));
        #pragma unroll 1
        for (int e = 0; e < 2; e++) {
            #pragma unroll
            for (int i = 0; i < 8; i++) r0[i] = r1[i];
            mbar_wait(bars + 8 * (B_CONV + 2 * V + e), 0);
            conv_channel(sb + OFF_CONV + (2 * V + e) * CH_STRIDE, w, lane, r1, e ? 0 : bars + 8 * (B_EPI + V), 2 * V + e);
            if (e == 0) STAMP(8 * V + 3);
        }
        const int gam = g >> 2, qq = gam ? ((q + 3) & 3) : q;
        const uint32_t sp = sb + OFF_CONV + V * OFF_SST + ((63 - 4 * gam - qq) * 16 + 4 * (w ^ (3 - qq)) + (g & 3)) * 8;
        bar_sync(3 + V);
        #pragma unroll
        for (int a2 = 0; a2 < 8; a2++) sts64(sp - a2 * 1024, r0[a2], r1[a2]);
        fence_async_smem();
        mbar_arrive(bars + 8 * (B_SIG + V));
        STAMP(8 * V + 4);
    }
    if (V == 1) return;
    {
        const int tau = c >> 2, dg = c & 3;
        const uint32_t row = 8 * (w & 1) + 32 * (w >> 1);
        float acc[64];
        define_acc(acc);
        const float rr0 = __ldcg(&P.st[64 * tau + row + g].y), rr1 = __ldcg(&P.st[64 * tau + row + g + 16].y);
        mbar_wait(bars + 8 * B_FULLD, 0);
        STAMP(5);
        uint64_t dB = mkdesc(sb + wd_slot(0), 8192, 1024, 1), dA = mkdesc(sb + h_slot(0), 1024, 128, 0);
        #pragma unroll 1
        for (int st = 0; st < 21; st++) {
            WG_FENCE();
            wg_tt128(acc, dA, dB, st);
            wg_tt128(acc, dA + 128, dB + 128, 1);
            wg_tt128(acc, dA + 256, dB + 256, 1);
            wg_tt128(acc, dA + 384, dB + 384, 1);
            WG_COMMIT();
            const int sd = (st + 1) & 7;
            const uint32_t nb = bars + 8 * (B_FULLD + sd), np = ((st + 1) >> 3) & 1;
            uint32_t ro = st == 15 ? 8 * B_CH0 : 8 * (B_EMPTYD + ((st - 1) & 7)), m = lane == 0 && st > 0, ok;
            dB = mkdesc(sb + wd_slot(sd), 8192, 1024, 1); dA = mkdesc(sb + h_slot(sd), 1024, 128, 0);
            asm volatile("{.reg .pred p; mbarrier.test_wait.parity.shared::cta.b64 p, [%5], %6; vote.sync.all.pred p, p, -1; selp.u32 %0, 1, 0, p;}"
                : "=r"(ok), "+l"(dA), "+l"(dB), "+r"(ro), "+r"(m) : "r"(nb), "r"(np) : "memory");
            WG_WAIT(1);
            asm volatile("{.reg .pred p; setp.ne.u32 p, %1, 0; @p mbarrier.arrive.shared::cta.b64 _, [%0];}" :: "r"(bars + ro), "r"(m) : "memory");
            if (!ok) mbar_wait(nb, np);
            if (w == 0) STAMP2(20 + st);
        }
        WG_FENCE();
        wg_tt128(acc, dA, dB, 1);
        wg_tt128(acc, dA + 128, dB + 128, 1);
        WG_COMMIT();
        mbar_wait(bars + 8 * B_XO, 0);
        const uint32_t xo = sb + OFF_CONV + (row + (lane & 7) + 16 * ((lane >> 3) & 1)) * 128;
        const uint32_t so = sb + wd_slot(6) + (w >> 1) * 8192 + q * 256 + (g & 1) * 8;
        const uint32_t sx = (4 * (w & 1) + (g >> 1)) ^ (2 * q) ^ (2 * ((2 * tau + (w >> 1)) & 3));
        uint32_t xr[8][4];
        uint2 sv[16];
        #pragma unroll
        for (int j = 0; j < 16; j += 2) {
            ldsm4(xr[j >> 1], xo + (j >> 3) * 8192 + ((((j & 7) + (lane >> 4)) ^ (lane & 7)) << 4));
            sv[j] = lds64(so + j * 512 + (sx << 4));
            sv[j + 1] = lds64(so + j * 512 + 128 + ((sx ^ 1) << 4));
        }
        WG_WAIT(0);
        fence_acc(acc);
        STAMP(6);
        #pragma unroll
        for (int j = 0; j < 16; j += 2) {
            #pragma unroll
            for (int i = 0; i < 4; i++) {
                const int jj = j + (i >> 1), hh = i & 1;
                const float f0 = acc[4 * jj + 2 * hh] * (hh ? rr1 : rr0), f1 = acc[4 * jj + 2 * hh + 1] * (hh ? rr1 : rr0);
                const uint32_t G = pack2(fmaf(f0, tanh_fast(f0), f0), fmaf(f1, tanh_fast(f1), f1));
                const uint32_t s2 = __byte_perm(sv[jj].x, sv[jj].y, hh ? 0x7632 : 0x5410);
                asm("fma.rn.bf16x2 %0, %1, %2, %0;" : "+r"(xr[j >> 1][i]) : "r"(s2), "r"(G));
            }
            stsm4(xo + (j >> 3) * 8192 + ((((j & 7) + (lane >> 4)) ^ (lane & 7)) << 4), xr[j >> 1][0], xr[j >> 1][1], xr[j >> 1][2], xr[j >> 1][3]);
        }
        fence_async_smem();
        bar_sync(1);
        if (w == 0 && elect_one()) {
            #pragma unroll
            for (int i = 0; i < 2; i++)
                asm volatile("cp.async.bulk.tensor.2d.global.shared::cta.bulk_group [%0, {%2, %3}], [%1];"
                    :: "l"(&M.out), "r"(sb + OFF_CONV + i * 8192), "r"(dg * 128 + 64 * i), "r"(tau * 64) : "memory");
            asm volatile("cp.async.bulk.commit_group; cp.async.bulk.wait_group.read 0;" ::: "memory");
        }
        STAMP(7); GSTAMP(23);
    }
}

__device__ __forceinline__ float2 cexp_p(float re2, float im, float p) {
    float sn, cs;
    const float mag = ex2(re2 * p), th = im * p;
    asm("sin.approx.ftz.f32 %0, %1;" : "=f"(sn) : "f"(th));
    asm("cos.approx.ftz.f32 %0, %1;" : "=f"(cs) : "f"(th));
    return make_float2(mag * cs, mag * sn);
}
struct SsmRaw { unsigned short la, ai, cr, ci, ldt, dsk; };
__device__ __forceinline__ unsigned short ldu16(const void* p) { unsigned short v; asm volatile("ld.global.nc.u16 %0, [%1];" : "=h"(v) : "l"(p)); return v; }
__device__ __forceinline__ float2 cmul(float2 a, float2 b) { return make_float2(fmaf(a.x, b.x, -a.y * b.y), fmaf(a.x, b.y, a.y * b.x)); }
__device__ __forceinline__ float2 csqr(float2 a) { const float t = a.x * a.y; return make_float2(fmaf(a.x, a.x, -a.y * a.y), t + t); }
__device__ __forceinline__ void mma16816(float (&d)[4], const uint32_t (&a)[4], uint32_t b0, uint32_t b1) {
    asm volatile("mma.sync.aligned.m16n8k16.row.col.f32.bf16.bf16.f32 {%0,%1,%2,%3}, {%4,%5,%6,%7}, {%8,%9}, {%0,%1,%2,%3};"
        : "+f"(d[0]), "+f"(d[1]), "+f"(d[2]), "+f"(d[3]) : "r"(a[0]), "r"(a[1]), "r"(a[2]), "r"(a[3]), "r"(b0), "r"(b1));
}

__device__ __forceinline__ void layer_norm(uint32_t sb, uint32_t cb, int w, int lane) {
    const uint32_t bars = sb + OFF_BAR;
    mbar_wait(bars + 8 * B_LNX, 0);
    STAMP(34);
    {
        const uint32_t r0 = cb + CH_LN + (w & 1) * 64 + (lane >> 3) * 1040, ra = r0 + (lane & 7) * 16;
        const float pv = bf_lo(FU(ldsf(r0)));
        float s0 = 0.f, s1 = 0.f, a0 = 0.f, a1 = 0.f;
        #pragma unroll 1
        for (int k = 0; k < 1024; k += 512) {
            uint32_t v[16];
            #pragma unroll
            for (int j = 0; j < 4; j++) *(uint4*)&v[4 * j] = lds128(ra + k + 128 * j);
            #pragma unroll
            for (int i = 0; i < 16; i++) { const float t0 = bf_lo(v[i]) - pv, t1 = bf_hi(v[i]) - pv; s0 += t0; s1 += t1; a0 = fmaf(t0, t0, a0); a1 = fmaf(t1, t1, a1); }
        }
        s0 += s1; a0 += a1;
        #pragma unroll
        for (int o = 4; o; o >>= 1) { s0 += __shfl_xor_sync(0xffffffffu, s0, o); a0 += __shfl_xor_sync(0xffffffffu, a0, o); }
        s0 *= 1.f / DM;
        float sd, ri;
        asm("sqrt.approx.ftz.f32 %0, %1;" : "=f"(sd) : "f"(bf_round(bf_round(fmaxf(fmaf(-s0, s0, a0 * (1.f / DM)), 0.f)) + 1e-5f)));
        asm("rcp.approx.ftz.f32 %0, %1;" : "=f"(ri) : "f"(bf_round(sd)));
        if ((lane & 7) == 0) sts64(sb + OFF_CSUM + (w + 4 * (lane >> 3)) * 8, FU(bf_round(pv + s0)), FU(0.5f * ri));
    }
    STAMP(62);
    bar_sync(2);
    const int r = 4 * ((lane & 7) >> 1) + (lane & 1) + 2 * ((lane >> 3) & 1);
    const uint32_t ad = sb + OFF_CONV + (r & 3) * CH_STRIDE + CH_LN + (r & 1) * 64 + (r >> 2) * 1040 + (16 * w + (lane >> 4)) * 16;
    const uint4 sa = lds128(sb + OFF_CSUM + (lane & 3) * 32), sc = lds128(sb + OFF_CSUM + (lane & 3) * 32 + 16);
    const uint32_t m2[2] = {__byte_perm(sa.x, sa.z, 0x7632), __byte_perm(sc.x, sc.z, 0x7632)};
    const float ri[4] = {2.f * UF(sa.y), 2.f * UF(sa.w), 2.f * UF(sc.y), 2.f * UF(sc.w)};
    #pragma unroll 1
    for (int i = 0; i < 8; i += 4) {
        uint32_t v[4][4];
        #pragma unroll
        for (int j = 0; j < 4; j++)
            asm volatile("ldmatrix.sync.aligned.m8n8.x4.trans.shared.b16 {%0,%1,%2,%3}, [%4];" : "=r"(v[j][0]), "=r"(v[j][1]), "=r"(v[j][2]), "=r"(v[j][3]) : "r"(ad + 32 * (i + j)) : "memory");
        #pragma unroll
        for (int j = 0; j < 4; j++) {
            #pragma unroll
            for (int k = 0; k < 4; k++) {
                uint32_t dv; asm("sub.rn.bf16x2 %0, %1, %2;" : "=r"(dv) : "r"(v[j][k]), "r"(m2[k & 1]));
                v[j][k] = pack2(bf_lo(dv) * ri[2 * (k & 1)], bf_hi(dv) * ri[2 * (k & 1) + 1]);
            }
            sts64(cb + CH_LNT + lane * 8 + (i + j) * 512, v[j][0], v[j][1]); sts64(cb + CH_LNT + lane * 8 + (i + j) * 512 + 256, v[j][2], v[j][3]);
        }
    }
    fence_async_smem();
    mbar_arrive(bars + 8 * B_LN);
    STAMP(16);
}

__device__ __forceinline__ void kernel_gen(uint32_t fs, int lane, const SsmRaw& raw, float (&dacc)[2][3][4], const Params& P, int warp) {
    const float dt = bf_round(ex2(bf_lo(raw.ldt) * 1.4426950408889634f));
    const float re2 = bf_round(ex2(bf_lo(raw.la) * 1.4426950408889634f)) * dt * -1.4426950408889634f, im = bf_lo(raw.ai) * dt;
    const float2 C = make_float2(bf_lo(raw.cr) * (dt + dt), bf_lo(raw.ci) * -(dt + dt));
    STAMP(56);
    if (warp < 4 && lane == 0 && re2 != 1.f) {
        const int c = blockIdx.x;
        const char* p = warp < 2 ? (const char*)(P.x + (16 * (c & ~1) + 8 * (c & 1) + 16 * warp) * DM) : (const char*)(warp == 2 ? P.Wg : P.Wu) + 128 * FF * 2 + c * 8256;
        asm volatile("cp.async.bulk.prefetch.L2.global [%0], %1;" :: "l"(p), "r"(warp < 2 ? 8192 : 8256) : "memory");
    }
    const float2 z8 = cexp_p(re2, im, 8.f), y1 = cexp_p(re2, -im, 1.f), y256 = cexp_p(re2, -im, 256.f);
    float2 b0 = make_float2(1.f, 0.f), b1 = cexp_p(re2, im, 64.f), b2 = csqr(b1), b3 = cmul(b2, b1);
    const uint32_t fm = fs + (lane >> 3) * 144 + (lane & 7) * 16;
#define PK(v) pack2((v).x, (v).y)
    #pragma unroll RUNROLL
    for (uint32_t ro = 0; ro < 8 * 144; ro += 144) {
        stsm4(fm + (lane >> 3) * 7 * 144 + ro, PK(b0), PK(b1), PK(b2), PK(b3));
        b0 = cmul(b0, z8); b1 = cmul(b1, z8); b2 = cmul(b2, z8); b3 = cmul(b3, z8);
    }
    const float2 y2 = csqr(y1), y4 = csqr(y2), y8 = make_float2(z8.x, -z8.y);
    const float2 l1 = cmul(C, y1), l2 = cmul(C, y2), l3 = cmul(l1, y2);
    stsm4(fm + 32 * 144, PK(C), PK(l1), PK(l2), PK(l3));
    stsm4(fm + 36 * 144, PK(cmul(C, y4)), PK(cmul(l1, y4)), PK(cmul(l2, y4)), PK(cmul(l3, y4)));
    const float2 t0 = cmul(C, y256), t1 = cmul(t0, y256), t2 = cmul(t1, y256), t3_ = cmul(t2, y256);
    const float2 u1 = cmul(t0, y2), u2 = cmul(u1, y2), u3 = cmul(u2, y2);
    stsm4(fm + 40 * 144, PK(t0), PK(u1), PK(u2), PK(u3));
    stsm4(fm + 44 * 144, PK(t1), PK(cmul(t1, y4)), PK(t2), PK(cmul(t2, y4)));
    const float2 v0 = cmul(t3_, y8), v1 = cmul(v0, y256), v2 = cmul(v1, y256), v3 = cmul(v2, y256);
    stsm4(fm + 48 * 144, PK(v0), PK(v1), PK(v2), PK(v3));
    stsf(fs + lane * 4 + 52 * 144, UF(PK(t3_)));
#undef PK
    STAMP(57);
    const uint32_t lda = fs + (lane & 15) * 144 + (lane & 16);
    const uint32_t ldb = fs + (32 + (lane & 7)) * 144 + (lane >> 3) * 16;
    __syncwarp();
    #pragma unroll 1
    for (int ko = 0; ko < 128; ko += 64) {
        uint32_t b[3][4], a[4][4];
        #pragma unroll
        for (int i = 0; i < 3; i++) ldsm4(b[i], ldb + i * 8 * 144 + ko);
        #pragma unroll
        for (int i = 0; i < 4; i++) ldsm4(a[i], lda + (i & 1) * 16 * 144 + ko + (i >> 1) * 32);
        #pragma unroll
        for (int i = 0; i < 4; i++)
            #pragma unroll
            for (int t = 0; t < 3; t++) mma16816(dacc[i & 1][t], a[i], b[t][i & 2], b[t][(i & 2) + 1]);
    }
    STAMP(58);
}

__device__ __forceinline__ void aux_role(uint32_t sb, int w, float (&dacc)[2][3][4], float dsk, const __nv_bfloat16* x) {
    const int lane = threadIdx.x & 31, q = lane & 3, g = lane >> 2;
    const int c = blockIdx.x;
    const uint32_t bars = sb + OFF_BAR;
    if (c >= 128) { mbar_arrive(bars + 8 * B_LN); return; }
    {
        const uint32_t cb = sb + OFF_CONV + w * CH_STRIDE;
        if (elect_one()) {
            mbar_expect(bars + 8 * B_LNX, 4096);
            #pragma unroll
            for (int i = 0; i < 4; i++)
                bulk_load(cb + CH_LN + (w & 1) * 64 + i * 1040, x + (16 * (c & ~1) + 8 * (c & 1) + 16 + w + 4 * (i & 1) - 8 * (i & 2)) * DM, 1024, bars + 8 * B_LNX);
        }
        mbar_wait(bars + 8 * B_K, 0);
        #pragma unroll 1
        for (uint32_t pa = cb + CH_PART + lane * 16; pa < cb + CH_PART + 9216; pa += 3072) {
            #pragma unroll
            for (int i = 0; i < 6; i++) {
                const uint4 v = lds128(pa + i * 512);
                float* d = &dacc[0][0][0] + 4 * i;
                d[0] += UF(v.x); d[1] += UF(v.y); d[2] += UF(v.z); d[3] += UF(v.w);
            }
        }
        __syncwarp();
        STAMP(18);
        const uint32_t sF = cb + CH_A3, sG = cb + CH_G;
        if (lane == 0) dacc[0][0][0] += dsk;
        if (lane < 10) sts128(sG + 128 + (lane & 1) * 208 + (lane >> 1) * 16, 0, 0, 0, 0);
        const uint32_t f0 = sF + (8 * g + 2 * q) * 4, f1 = sF + ((q < 2) ? 256 + 4 * g + 2 * q : 256 + 2 * g + 64 * q) * 4, st1 = (q < 2) ? 128 : 64;
        const uint32_t ga = sG + ((g & 1) ? 0 : 208) + (63 - (g >> 1) - 32 * q) * 2;
        #pragma unroll
        for (int i = 0; i < 4; i++) {
            const int mu = i >> 1, hh = i & 1;
            sts64(f0 + i * 256, FU(dacc[mu][0][2 * hh]), FU(dacc[mu][0][2 * hh + 1]));
            sts64(f1 + i * st1, FU(dacc[mu][1][2 * hh]), FU(dacc[mu][1][2 * hh + 1]));
            const uint32_t pk = pack2(dacc[mu][2][2 * hh], dacc[mu][2][2 * hh + 1]);
            if (q < 2) { sts16(ga - 8 * i, pk & 0xffff); sts16(ga - 8 * i - 32, pk >> 16); }
        }
        if (lane == 2) stsf(sF + 2048, dacc[0][2][0]);
        STAMP(19);
        layer_norm(sb, cb, w, lane);
        mbar_wait(bars + 8 * B_LNS, 0);
        if (lane < 8) sts128(cb + CH_U + 2048 + (lane & 4) * (UPLANE / 4) + (lane & 3) * 16, 0, 0, 0, 0);
        bar_sync(2);
    }
    const int u = min(lane, 30) - 15, r2 = (u + ((u >> 1) & 1)) >> 1, r4 = (u + 1 + ((u >> 2) & 1)) >> 2, xt = 1024 + 16 * w + u;
    const uint32_t o0 = CH_A3 + 4 * (w == 0 ? u : w == 1 ? 256 + r2 : 256 + 64 * w + r4), ost = w == 0 ? 64 : w == 1 ? 32 : 16;
    const uint32_t oa0 = u >= 0 || w == 3 ? o0 : CH_A3 + 4 * (w == 1 ? 256 + u : w == 2 ? 384 + r2 : 0);
    const uint32_t ot = CH_A3 + 4 * min(512, 256 + ((xt + 1 + ((xt >> 2) & 1)) >> 2));
    const int kap = (lane >> 4) * 8 + ((lane >> 1) & 7), gam = lane & 1, hh = w >> 1, wp = w & 1;
    const uint32_t oa = CH_U + wp * UPLANE + (127 - 4 * kap - 2 * gam - hh) * 16;
    const uint32_t ob = CH_U + (wp ^ 1) * UPLANE + (128 - wp - 4 * kap - 2 * gam - hh) * 16;
    const uint32_t od = CH_A3 + (4 * wp + hh) * 512 + (kap >> 3) * 256 + (kap & 7) * 16 + gam * 8;
    #pragma unroll 1
    for (int k = 0; k < 4; k++) {
        const int ch = 2 * (k & 1) + (k >> 1);
        const uint32_t cb = sb + OFF_CONV + ch * CH_STRIDE;
        {
            float kv[17];
            kv[0] = ldsf(cb + oa0); kv[16] = ldsf(cb + ot);
            #pragma unroll
            for (int s = 1; s < 16; s++) kv[s] = ldsf(cb + o0 + s * ost);
            const int tid = threadIdx.x & 127;
            const uint32_t ga = cb + CH_G + (tid >= 24) * 16 + min(tid, 47) * 8;
            const uint2 x0 = lds64(ga), x1 = lds64(ga + 8);
            if (u < 0 && w == 0) kv[0] = 0.f;
            if (xt > 1028) kv[16] = 0.f;
            uint32_t o[17];
            #pragma unroll
            for (int s = 0; s < 17; s++) o[s] = pack2(kv[s], __shfl_up_sync(0xffffffffu, kv[s], 1));
            if (lane > 0 && lane < 31) {
                const uint32_t ta = cb + CH_T + (lane - 1) * 280;
                #pragma unroll
                for (int s2 = 0; s2 < 8; s2++) sts64(ta + 64 * w + s2 * 8, o[2 * s2], o[2 * s2 + 1]);
                stsf(ta + 256 + 4 * w, UF(o[16]));
            }
            if (tid < 48) sts128(cb + CH_B3 + tid * 16, x0.x, x0.y, x1.x, x1.y);
        }
        mbar_wait(bars + 8 * B_U, 0);
        float p[24];
        const uint2 r0 = lds64(cb + ob + 24), r3 = lds64(cb + oa);
        uint32_t r[8];
        *(uint4*)&r[0] = lds128(cb + oa + 16); *(uint4*)&r[4] = lds128(cb + ob);
        p[0] = 0.f;
        p[1] = bf_lo(r0.x); p[2] = p[1] + bf_hi(r0.x); p[3] = p[2] + bf_lo(r0.y); p[4] = p[3] + bf_hi(r0.y);
        #pragma unroll
        for (int i = 0; i < 8; i++) { p[5 + 2 * i] = p[4 + 2 * i] + bf_lo(r[i]); p[6 + 2 * i] = p[5 + 2 * i] + bf_hi(r[i]); }
        p[21] = p[20] + bf_lo(r3.x); p[22] = p[21] + bf_hi(r3.x); p[23] = p[22] + bf_lo(r3.y);
        bar_sync(2);
        #pragma unroll
        for (int i = 0; i < 8; i += 4) {
            sts64(cb + od + i * 256, pack2(p[i + 9] - p[i], p[i + 10] - p[i + 1]), pack2(p[i + 11] - p[i + 2], p[i + 12] - p[i + 3]));
            sts64(cb + od + i * 256 + 128, pack2(p[i + 16] - p[i + 9], p[i + 17] - p[i + 10]), pack2(p[i + 18] - p[i + 11], p[i + 19] - p[i + 12]));
        }
        fence_async_smem();
        mbar_arrive(bars + 8 * (B_CONV + ch));
        if (k == 0) STAMP(17);
    }
    STAMP(21);
}

__global__ void __launch_bounds__(512, 1)
fused_kernel(const __grid_constant__ Params P, const __grid_constant__ Maps M) {
    extern __shared__ __align__(1024) uint8_t smem_raw[];
    const uint32_t sb = smem_u32(smem_raw);
    const uint32_t bars = sb + OFF_BAR;
    const int warp = __shfl_sync(0xffffffffu, threadIdx.x >> 5, 0);
    const int c = blockIdx.x, tg = c / 22, fb = c - 22 * tg;
    SsmRaw raw;
    {
        const int d = min(4 * c + (warp & 3), DM - 1), o = d * 128 + (warp >> 2) * 32 + (threadIdx.x & 31);
        raw.la = ldu16(P.logA + o); raw.ai = ldu16(P.Aim + o); raw.cr = ldu16(P.Cr + o); raw.ci = ldu16(P.Ci + o);
        raw.ldt = ldu16(P.logdt + d); raw.dsk = ldu16(P.Dskip + d);
    }
    if (elect_one()) {
        if (warp == 0) { STAMP(24); GSTAMP(22); }
        asm volatile("" :: "l"(((const uint64_t*)&P)[warp < 14 ? warp : 0]));
        if (warp < 12) asm volatile("prefetch.tensormap [%0];" :: "l"(&M.x[0] + warp) : "memory");
        #pragma unroll
        for (int k = 0; k < 4; k++) {
            const int i = 16 * k + ((warp + 4) & 15);
            const uint32_t cnt = i >= B_CONV ? 128 : i == B_K ? 12 : ((0xf0ull >> i) & 1) ? 8 : ((0xff0000ull >> i) & 1) ? 2 : ((0x3e00ff00f000ull >> i) & 1) ? 4 : 1;
            asm volatile("mbarrier.init.shared::cta.b64 [%0], %1;" :: "r"(bars + 8 * i), "r"(cnt) : "memory");
        }
        asm volatile("fence.mbarrier_init.release.cluster; fence.proxy.async.shared::cta;" ::: "memory");
        if (warp == 13 || warp == 5) { const uint32_t t0 = clock(); while ((uint32_t)clock() - t0 < DLY1) ; }
        if (warp == 12 || warp == 13) {
            const uint32_t s = warp - 12;
            mbar_expect(bars + 8 * (B_FULLW + s), 16384);
            tma2d(sb + OFF_W + s * 16384, &M.wg, 64 * fb, 64 * s, bars + 8 * (B_FULLW + s));
            tma2d(sb + OFF_W + s * 16384 + 8192, &M.wu, 64 * fb, 64 * s, bars + 8 * (B_FULLW + s));
            STAMP(31);
        } else if (warp == 4 || warp == 5) {
            const uint32_t s = warp - 4;
            mbar_expect(bars + 8 * (B_FULLX + s), 168 * 128);
            tma2d(sb + OFF_X + s * XBUF, &M.x[0], 64 * s, TOKG * tg, bars + 8 * (B_FULLX + s));
        }
        if (sb & 1023) __trap();
    }
    if (warp < 4) sts128(sb + OFF_X + (warp >> 1) * XBUF + 168 * 128 + (threadIdx.x & 63) * 16, 0x3f803f80u, 0x3f803f80u, 0x3f803f80u, 0x3f803f80u);
    float dacc[2][3][4];
    #pragma unroll
    for (int i = 0; i < 24; i++) (&dacc[0][0][0])[i] = 0.f;
    if (c < 128)
        kernel_gen(sb + (warp < 8 ? (warp < 4 ? OFF_W + 32768 : OFF_X + 2 * XBUF) + (warp & 3) * 8064 : OFF_CONV + (warp & 3) * CH_STRIDE + (warp >> 2 & 1) * 8064),
                   threadIdx.x & 31, raw, dacc, P, warp);
    fence_async_smem();
    __syncthreads();
    if (c < 128 && (warp >> 2) != 2) {
        const uint32_t pa = sb + OFF_CONV + (warp & 3) * CH_STRIDE + CH_PART + min(warp >> 2, 2) * 3072 + (threadIdx.x & 31) * 16;
        #pragma unroll
        for (int i = 0; i < 6; i++) { const float* d = &dacc[0][0][0] + 4 * i; sts128(pa + i * 512, FU(d[0]), FU(d[1]), FU(d[2]), FU(d[3])); }
        __syncwarp();
        if ((threadIdx.x & 31) == 0) mbar_arrive(bars + 8 * B_K);
    }
    if (warp < 8) {
        asm volatile("setmaxnreg.inc.sync.aligned.u32 208;");
        consumer(sb, warp, P, M);
    } else if (warp < 12) {
        asm volatile("setmaxnreg.dec.sync.aligned.u32 72;");
        STAMP(32);
        aux_role(sb, warp - 8, dacc, bf_lo(raw.dsk), P.x);
    } else {
        asm volatile("setmaxnreg.dec.sync.aligned.u32 24;");
        const int tau = c >> 2, dg = c & 3;
        if (elect_one()) {
            if (warp < 15) {
                if (warp == 12) {
                    #pragma unroll 1
                    for (int st = 2; st < 8; st++) {
                        const uint32_t s = st & 3, fb_ = bars + 8 * (B_FULLW + s);
                        mbar_wait(bars + 8 * (B_EMPTYW + s), (st >> 2) ^ 1);
                        mbar_expect(fb_, 16384);
                        tma2d(sb + OFF_W + s * 16384, &M.wg, 64 * fb, 64 * st, fb_);
                        tma2d(sb + OFF_W + s * 16384 + 8192, &M.wu, 64 * fb, 64 * st, fb_);
                    }
                } else {
                    const int V = warp - 13;
                    #pragma unroll 1
                    for (int st = 2 - 2 * V; st < 8; st++) {
                        const uint32_t s = 2 * V + (st & 1);
                        mbar_wait(bars + 8 * (B_EMPTYX + s), ((st >> 1) & 1) ^ 1);
                        mbar_expect(bars + 8 * (B_FULLX + s), (168 + 8 * V) * 128);
                        tma2d(sb + OFF_X + s * XBUF, &M.x[V], 64 * st, TOKG * tg + 168 * V, bars + 8 * (B_FULLX + s));
                    }
                }
                if (c < 128 && warp < 14) {
                    if (warp == 13) {
                        mbar_wait(bars + 8 * (B_STG + 1), 0);
                        #pragma unroll 1
                        for (int o = 8 * tau; o < 8 * tau + 8; o += 7) flag_wait(P.flags, F_H + 2 * (o / 43) + ((o % 43) >= 21), 22);
                        mbar_arrive(bars + 8 * B_HF);
                        STAMP(25);
                    }
                    #pragma unroll 1
                    for (int st = 0; st < 22; st += (st < 7 || (st == 7 && warp == 12)) ? 1 : 2) {
                        const int sd = st & 7;
                        const uint32_t fb_ = bars + 8 * (B_FULLD + sd);
                        if (st >= 8) mbar_wait(bars + 8 * (B_EMPTYD + sd), ((st >> 3) & 1) ^ 1);
                        else if (warp == 12 || st >= 6) mbar_wait(bars + 8 * (uint32_t)((0x373623070d060504ull >> (8 * st)) & 0xff), st < 5);
                        if (st >= 10 && st < 21) STAMP2(31 + st);
                        if (st >= 8 || warp == 13) {
                            mbar_expect(fb_, 8192);
                            asm volatile("cp.async.bulk.tensor.5d.shared::cluster.global.mbarrier::complete_tx::bytes [%0], [%1, {%3, %3, %3, %4, %5}], [%2];"
                                :: "r"(sb + h_slot(sd)), "l"(&M.hld), "r"(fb_), "r"(0), "r"(2 * tau), "r"(8 * st) : "memory");
                        }
                        if (st >= 8 || warp == 12) {
                            const uint32_t da = sb + wd_slot(sd);
                            mbar_expect(fb_, 16384);
                            tma2d(da, &M.wd, 128 * dg, 64 * st, fb_);
                            tma2d(da + 8192, &M.wd, 128 * dg + 64, 64 * st, fb_);
                        }
                    }
                } else if (c < 128) {
                    mbar_wait(bars + 8 * B_SST, 0);
                    flag_wait(P.flags, F_S + dg, 64);
                    STAMP(26);
                    mbar_wait(bars + 8 * B_CH0, 0);
                    mbar_expect(bars + 8 * B_XO, 32768);
                    tma2d(sb + OFF_CONV, &M.xo, 128 * dg, 64 * tau, bars + 8 * B_XO);
                    tma2d(sb + OFF_CONV + 8192, &M.xo, 128 * dg + 64, 64 * tau, bars + 8 * B_XO);
                    asm volatile("cp.async.bulk.tensor.5d.shared::cluster.global.mbarrier::complete_tx::bytes [%0], [%1, {%3, %3, %3, %4, %5}], [%2];"
                        :: "r"(sb + wd_slot(6)), "l"(&M.sld), "r"(bars + 8 * B_XO), "r"(0), "r"(8 * dg), "r"(2 * tau) : "memory");
                    mbar_wait(bars + 8 * B_HF, 0);
                    exit_count(P.flags);
                }
            } else {
                mbar_wait(bars + 8 * B_LN, 0);
                STAMP2(0);
                if (c < 128) {
                    #pragma unroll 1
                    for (int i = 0; i < 4; i++)
                        asm volatile("cp.async.bulk.tensor.2d.global.shared::cta.bulk_group [%0, {%2, %3}], [%1];"
                            :: "l"(&M.xt), "r"(sb + OFF_CONV + i * CH_STRIDE + CH_LNT), "r"((c & 1) * 1024 + (126 - (c & ~1)) * 8), "r"(128 * i) : "memory");
                    #pragma unroll 1
                    for (int i = 0; i < 2; i++) bulk_store(P.st + 16 * (c & ~1) + 8 * (c & 1) + 16 - 16 * i, sb + OFF_CSUM + 64 * i, 64);
                    asm volatile("cp.async.bulk.prefetch.L2.global [%0], %1;" :: "l"(P.Wd + c * (FF * DM / 128)), "r"(FF * DM / 64) : "memory");
                }
                asm volatile("cp.async.bulk.commit_group; cp.async.bulk.wait_group.read 0;" ::: "memory");
                mbar_arrive(bars + 8 * B_LNS);
                STAMP2(1);
                flag_signal(P.flags, F_A);
                STAMP2(2);
                flag_wait(P.flags, F_A, NCTA);
                STAMP(20);
                mbar_expect(bars + 8 * B_STATS, TOKG * 8);
                bulk_load(sb + OFF_ST, P.st + TOKG * tg, TOKG * 8, bars + 8 * B_STATS);
                if (c < 128) {
                    mbar_expect(bars + 8 * B_U, 8 * 2048);
                    #pragma unroll 1
                    for (int i = 0; i < 8; i++)
                        bulk_load(sb + OFF_CONV + (i >> 1) * CH_STRIDE + CH_U + (i & 1) * UPLANE, P.xnT + 4 * c * 256 + i * 128, 2048, bars + 8 * B_U);
                } else exit_count(P.flags);
                #pragma unroll 1
                for (int V = 0; V < 2; V++) {
                    mbar_wait(bars + 8 * (B_EPI + V), 0);
                    STAMP2(3 + 2 * V);
                    asm volatile("cp.async.bulk.tensor.3d.global.shared::cta.bulk_group [%0, {%2, %3, %4}], [%1];"
                        :: "l"(&M.hst[V]), "r"(sb + OFF_X + V * 2 * XBUF), "r"(0), "r"(43 * tg + 21 * V), "r"(8 * fb) : "memory");
                    flag_signal(P.flags, F_H + 2 * tg + V);
                    mbar_arrive(bars + 8 * (B_STG + V));
                    STAMP2(4 + 2 * V);
                }
                if (c < 128) {
                    #pragma unroll 1
                    for (int V = 0; V < 2; V++) {
                        mbar_wait(bars + 8 * (B_SIG + V), 0);
                        STAMP2(7 + 2 * V);
                        bulk_store(P.S + (2 * c + V) * 1024, sb + OFF_CONV + V * OFF_SST, 8192);
                        flag_signal(P.flags, F_S + (c >> 5));
                        STAMP2(8 + 2 * V);
                    }
                    mbar_arrive(bars + 8 * B_SST);
                }
            }
        }
    }
    asm volatile("nanosleep.u32 0;");
}

typedef CUresult (*EncodeFn)(CUtensorMap*, CUtensorMapDataType, cuuint32_t, void*, const cuuint64_t*, const cuuint64_t*, const cuuint32_t*,
                             const cuuint32_t*, CUtensorMapInterleave, CUtensorMapSwizzle, CUtensorMapL2promotion, CUtensorMapFloatOOBfill);

void make_map(EncodeFn enc, CUtensorMap* m, const void* ptr, int rank, const cuuint64_t* dims, const cuuint64_t* strides, const cuuint32_t* box, bool swz, bool wide = false) {
    const cuuint32_t es[5] = {1, 1, 1, 1, 1};
    enc(m, CU_TENSOR_MAP_DATA_TYPE_BFLOAT16, rank, (void*)ptr, dims, strides, box, es, CU_TENSOR_MAP_INTERLEAVE_NONE,
        swz ? CU_TENSOR_MAP_SWIZZLE_128B : CU_TENSOR_MAP_SWIZZLE_NONE, wide ? CU_TENSOR_MAP_L2_PROMOTION_L2_256B : CU_TENSOR_MAP_L2_PROMOTION_L2_128B, CU_TENSOR_MAP_FLOAT_OOB_FILL_NONE);
}
void make_map2(EncodeFn enc, CUtensorMap* m, const void* ptr, cuuint64_t inner, cuuint64_t outer, cuuint32_t rows) {
    const cuuint64_t dims[2] = {inner, outer}, strides[1] = {inner * 2};
    const cuuint32_t box[2] = {64, rows};
    make_map(enc, m, ptr, 2, dims, strides, box, true, rows > 64);
}

}

extern "C" void kernel_launch(void* const* d_in, const int* in_sizes, int n_in, void* d_out, int out_size) {
    (void)in_sizes; (void)n_in; (void)out_size;
    static EncodeFn enc = nullptr;
    static void *hptr, *p_xnT, *p_st, *p_S, *p_flags;
    if (!enc) {
        cudaDriverEntryPointQueryResult qr;
        cudaGetDriverEntryPoint("cuTensorMapEncodeTiled", (void**)&enc, cudaEnableDefault, &qr);
        cudaFuncSetAttribute(fused_kernel, cudaFuncAttributeMaxDynamicSharedMemorySize, SMEM_BYTES);
        cudaGetSymbolAddress(&hptr, g_H); cudaGetSymbolAddress(&p_xnT, g_xnT); cudaGetSymbolAddress(&p_st, g_st);
        cudaGetSymbolAddress(&p_S, g_S); cudaGetSymbolAddress(&p_flags, g_flags);
    }
    Params P;
    P.x = (const __nv_bfloat16*)d_in[0]; P.logA = (const __nv_bfloat16*)d_in[1]; P.Aim = (const __nv_bfloat16*)d_in[2];
    P.Cr = (const __nv_bfloat16*)d_in[3]; P.Ci = (const __nv_bfloat16*)d_in[4]; P.logdt = (const __nv_bfloat16*)d_in[5];
    P.Dskip = (const __nv_bfloat16*)d_in[6];
    P.Wg = (const __nv_bfloat16*)d_in[8]; P.Wu = (const __nv_bfloat16*)d_in[9]; P.Wd = (const __nv_bfloat16*)d_in[10]; P.xnT = (uint4*)p_xnT; P.st = (float2*)p_st; P.S = (uint2*)p_S; P.flags = (unsigned*)p_flags;
    Maps M;
    make_map2(enc, &M.x[0], d_in[0], DM, SEQ, 168); make_map2(enc, &M.x[1], d_in[0], DM, SEQ, 176);
    make_map2(enc, &M.xo, d_in[0], DM, SEQ, 64);    make_map2(enc, &M.out, d_out, DM, SEQ, 64);
    make_map2(enc, &M.wg, d_in[8], FF, DM, 64);     make_map2(enc, &M.wu, d_in[9], FF, DM, 64);
    make_map2(enc, &M.wd, d_in[10], DM, FF, 64);
    for (int v = 0; v < 2; v++) {
        const cuuint64_t dims[3] = {64, 256, 172}, strides[2] = {128, 32768};
        const cuuint32_t box[3] = {64, (cuuint32_t)(21 + v), 8};
        make_map(enc, &M.hst[v], hptr, 3, dims, strides, box, false);
    }
    {
        const cuuint64_t dims[2] = {2048, 512}, strides[1] = {4096};
        const cuuint32_t box[2] = {16, 128};
        make_map(enc, &M.xt, p_xnT, 2, dims, strides, box, false);
    }
    {
        const cuuint64_t dims[5] = {64, 2, 4, 32, 64}, strides[4] = {4 * 8192, 8192, 8 * 8192, 128};
        const cuuint32_t box[5] = {64, 2, 4, 8, 2};
        make_map(enc, &M.sld, p_S, 5, dims, strides, box, true);
    }
    {
        const cuuint64_t dims[5] = {64, 2, 2, 64, 172}, strides[4] = {256, 128, 512, 32768};
        const cuuint32_t box[5] = {64, 2, 2, 2, 8};
        make_map(enc, &M.hld, hptr, 5, dims, strides, box, false);
    }
    fused_kernel<<<NCTA, 512, SMEM_BYTES>>>(P, M);
}
```

```cpp
#include <cuda_runtime.h>
#include <cuda_bf16.h>
#include <cuda.h>
#include <stdint.h>

#define PROF 0

namespace {

constexpr int SEQ = 2048, DM = 512, FF = 1376;
constexpr int NCTA = 132;
#define GOST 1
#define SIGK 3
#define DLY1 300
constexpr int RUNROLL = 2;
constexpr int TOKG = 344;

constexpr uint32_t OFF_W = 0;
constexpr uint32_t XBUF = 22528;
constexpr uint32_t OFF_X = 65536;
constexpr uint32_t OFF_CONV = 155648;
constexpr uint32_t CH_STRIDE = 17536;
constexpr uint32_t CH_T = 0;
constexpr uint32_t CH_A3 = 8448;
constexpr uint32_t CH_B3 = 12544;
constexpr uint32_t CH_U = 13312;
constexpr uint32_t CH_G = CH_A3 + 2064;
constexpr uint32_t UPLANE = 2112;
constexpr uint32_t CH_LN = 0, CH_PART = 4224, CH_LNT = 13440;
constexpr uint32_t OFF_SST = 60416;
constexpr uint32_t OFF_ST = 225792;
constexpr uint32_t OFF_CSUM = 228544;
constexpr uint32_t OFF_BAR = 229056;
constexpr uint32_t SMEM_BYTES = 229568;

enum {
    B_FULLW = 0, B_EMPTYW = 4, B_FULLX = 8, B_EMPTYX = 12, B_FULLD = 16, B_EMPTYD = 24,
    B_U = 32, B_XO = 33, B_S = 34, B_STG = 35, B_HF = 37, B_STATS = 38, B_LNS = 39, B_SST = 40,
    B_LNX = 41, B_CH0 = 42, B_TURN = 43, B_K = 45,
    B_CONV = 46, B_LN = 50, B_CS = 51, B_EPI = 52, B_SIG = 54,
    B_COUNT = 56
};
enum { F_A = 0, F_H = 1, F_S = 13, F_EXIT = 17, F_COUNT = 18 };

__device__ uint4 g_xnT[DM * 256];
__device__ float2 g_st[6 * TOKG];
__device__ uint4 g_H[172 * 256 * 8];
__device__ uint2 g_S[256 * 1024];
__device__ unsigned g_flags[F_COUNT * 32];
#define STAMP(i) do {} while (0)
#define GSTAMP(i) do {} while (0)
#define STAMP2(i) do {} while (0)

__device__ __forceinline__ uint32_t smem_u32(const void* p) { return (uint32_t)__cvta_generic_to_shared(p); }
__device__ __forceinline__ void mbar_expect(uint32_t bar, uint32_t bytes) { asm volatile("mbarrier.arrive.expect_tx.shared::cta.b64 _, [%0], %1;" :: "r"(bar), "r"(bytes) : "memory"); }
__device__ __forceinline__ void mbar_arrive(uint32_t bar) { asm volatile("mbarrier.arrive.shared::cta.b64 _, [%0];" :: "r"(bar) : "memory"); }
__device__ __forceinline__ void mbar_wait(uint32_t bar, uint32_t parity) {
    asm volatile("{.reg .pred p; .reg .u32 n; mov.u32 n, 0x20000;\n"
                 "LW: mbarrier.try_wait.parity.shared::cta.b64 p, [%0], %1;\n"
                 "sub.u32 n, n, 1; setp.eq.or.u32 p, n, 0, p; @!p bra LW;}" :: "r"(bar), "r"(parity) : "memory");
}
__device__ __forceinline__ void mbar_arrive_if(uint32_t bar, uint32_t pred) {
    asm volatile("{.reg .pred p; setp.ne.u32 p, %1, 0; @p mbarrier.arrive.shared::cta.b64 _, [%0];}" :: "r"(bar), "r"(pred) : "memory");
}
__device__ __forceinline__ bool elect_one() { uint32_t p; asm volatile("{.reg .pred P; elect.sync _|P, 0xffffffff; selp.u32 %0, 1, 0, P;}" : "=r"(p)); return p; }
__device__ __forceinline__ void tma2d(uint32_t dst, const CUtensorMap* m, int c0, int c1, uint32_t bar) {
    asm volatile("cp.async.bulk.tensor.2d.shared::cluster.global.mbarrier::complete_tx::bytes [%0], [%1, {%3, %4}], [%2];"
        :: "r"(dst), "l"(m), "r"(bar), "r"(c0), "r"(c1) : "memory");
}
__device__ __forceinline__ void bulk_load(uint32_t dst, const void* src, uint32_t bytes, uint32_t bar) {
    asm volatile("cp.async.bulk.shared::cluster.global.mbarrier::complete_tx::bytes [%0], [%1], %2, [%3];" :: "r"(dst), "l"(src), "r"(bytes), "r"(bar) : "memory");
}
__device__ __forceinline__ void bulk_store(void* dst, uint32_t src, uint32_t bytes) {
    asm volatile("cp.async.bulk.global.shared::cta.bulk_group [%0], [%1], %2;" :: "l"(dst), "r"(src), "r"(bytes) : "memory");
}
__device__ __forceinline__ void fence_async_smem() { asm volatile("fence.proxy.async.shared::cta;" ::: "memory"); }
__device__ __forceinline__ void flag_wait(unsigned* g_flags, int f, unsigned target) {
    asm volatile("{.reg .pred p; .reg .u32 n, v; mov.u32 n, 0x40000;\n"
                 "LF: ld.acquire.gpu.global.u32 v, [%0]; setp.ge.u32 p, v, %1; @p bra LD;\n"
                 "sub.u32 n, n, 1; setp.ne.u32 p, n, 0; @p bra LF; trap;\nLD: }"
                 :: "l"(g_flags + f * 32), "r"(target) : "memory");
}
__device__ __forceinline__ void flag_signal(unsigned* g_flags, int f) {
    asm volatile("cp.async.bulk.commit_group; cp.async.bulk.wait_group 0; red.relaxed.gpu.global.add.u32 [%0], 1;" :: "l"(g_flags + f * 32) : "memory");
}
__device__ __forceinline__ void exit_count(unsigned* g_flags) {
    if (atomicAdd(g_flags + F_EXIT * 32, 1u) == NCTA - 1) {
        #pragma unroll 1
        for (int i = 0; i < F_COUNT; i++) g_flags[i * 32] = 0;
    }
}
__device__ __forceinline__ void bar_sync(int id) { asm volatile("bar.sync %0, 128;" :: "r"(id) : "memory"); }
__device__ __forceinline__ uint64_t mkdesc(uint32_t addr, uint32_t lbo, uint32_t sbo, uint32_t swz) {
    return (uint64_t)((addr >> 4) | ((lbo >> 4) << 16)) | ((uint64_t)((sbo >> 4) | (swz << 30)) << 32);
}
#define WG_FENCE() asm volatile("wgmma.fence.sync.aligned;" ::: "memory")
#define WG_COMMIT() asm volatile("wgmma.commit_group.sync.aligned;" ::: "memory")
#define WG_WAIT(n) asm volatile("wgmma.wait_group.sync.aligned " #n ";" ::: "memory")
template <int N> __device__ __forceinline__ void fence_acc(float (&d)[N]) {
    #pragma unroll
    for (int i = 0; i < N; i++) asm volatile("" : "+f"(d[i]) :: "memory");
}
template <int N> __device__ __forceinline__ void define_acc(float (&d)[N]) {
    #pragma unroll
    for (int i = 0; i < N; i++) asm volatile("" : "=f"(d[i]));
}
__device__ __forceinline__ uint32_t pack2(float lo, float hi) { uint32_t r; asm("cvt.rn.bf16x2.f32 %0, %1, %2;" : "=r"(r) : "f"(hi), "f"(lo)); return r; }
__device__ __forceinline__ float bf_lo(uint32_t v) { return __uint_as_float(v << 16); }
__device__ __forceinline__ float bf_hi(uint32_t v) { return __uint_as_float(v & 0xffff0000u); }
__device__ __forceinline__ float bf_round(float v) { return bf_hi(pack2(0.f, v)); }
__device__ __forceinline__ float tanh_fast(float v) { float r; asm("tanh.approx.f32 %0, %1;" : "=f"(r) : "f"(v)); return r; }
__device__ __forceinline__ float ex2(float v) { float r; asm("ex2.approx.ftz.f32 %0, %1;" : "=f"(r) : "f"(v)); return r; }
__device__ __forceinline__ uint4 lds128(uint32_t a) { uint4 v; asm volatile("ld.shared.v4.b32 {%0,%1,%2,%3}, [%4];" : "=r"(v.x), "=r"(v.y), "=r"(v.z), "=r"(v.w) : "r"(a)); return v; }
__device__ __forceinline__ uint2 lds64(uint32_t a) { uint2 v; asm volatile("ld.shared.v2.b32 {%0,%1}, [%2];" : "=r"(v.x), "=r"(v.y) : "r"(a)); return v; }
__device__ __forceinline__ float ldsf(uint32_t a) { float v; asm volatile("ld.shared.f32 %0, [%1];" : "=f"(v) : "r"(a)); return v; }
__device__ __forceinline__ void sts128(uint32_t a, uint32_t x, uint32_t y, uint32_t z, uint32_t w) { asm volatile("st.shared.v4.b32 [%0], {%1,%2,%3,%4};" :: "r"(a), "r"(x), "r"(y), "r"(z), "r"(w) : "memory"); }
__device__ __forceinline__ void sts64(uint32_t a, uint32_t x, uint32_t y) { asm volatile("st.shared.v2.b32 [%0], {%1,%2};" :: "r"(a), "r"(x), "r"(y) : "memory"); }
__device__ __forceinline__ void stsf(uint32_t a, float x) { asm volatile("st.shared.f32 [%0], %1;" :: "r"(a), "f"(x) : "memory"); }
__device__ __forceinline__ void sts16(uint32_t a, uint32_t x) { asm volatile("st.shared.b16 [%0], %1;" :: "r"(a), "h"((unsigned short)x) : "memory"); }
__device__ __forceinline__ void stsm4(uint32_t a, uint32_t r0, uint32_t r1, uint32_t r2, uint32_t r3) {
    asm volatile("stmatrix.sync.aligned.m8n8.x4.shared.b16 [%0], {%1,%2,%3,%4};" :: "r"(a), "r"(r0), "r"(r1), "r"(r2), "r"(r3) : "memory");
}
__device__ __forceinline__ void ldsm4(uint32_t (&r)[4], uint32_t a) {
    asm volatile("ldmatrix.sync.aligned.m8n8.x4.shared.b16 {%0,%1,%2,%3}, [%4];" : "=r"(r[0]), "=r"(r[1]), "=r"(r[2]), "=r"(r[3]) : "r"(a) : "memory");
}
#define FU(x) __float_as_uint(x)
#define UF(x) __uint_as_float(x)
__device__ __forceinline__ uint32_t wd_slot(int s) { return (uint32_t)((0xbba8403056201000ull >> (8 * s)) & 0xff) << 10; }
__device__ __forceinline__ uint32_t h_slot(int s) { return (uint32_t)((0xcba0908880787068ull >> (8 * s)) & 0xff) << 10; }

template<int N> __device__ __forceinline__ void wg_rs(float (&d)[64], uint32_t a0, uint32_t a1, uint32_t a2, uint32_t a3, uint64_t db);
template<> __device__ __forceinline__ void wg_rs<128>(float (&d)[64], uint32_t a0, uint32_t a1, uint32_t a2, uint32_t a3, uint64_t db) {
  asm volatile("{.reg .pred p; setp.ne.b32 p, 1, 0; wgmma.mma_async.sync.aligned.m64n128k16.f32.bf16.bf16 {%0,%1,%2,%3,%4,%5,%6,%7,%8,%9,%10,%11,%12,%13,%14,%15,%16,%17,%18,%19,%20,%21,%22,%23,%24,%25,%26,%27,%28,%29,%30,%31,%32,%33,%34,%35,%36,%37,%38,%39,%40,%41,%42,%43,%44,%45,%46,%47,%48,%49,%50,%51,%52,%53,%54,%55,%56,%57,%58,%59,%60,%61,%62,%63}, {%64,%65,%66,%67}, %68, p, 1, 1, 0;}"
    : "+f"(d[0]),"+f"(d[1]),"+f"(d[2]),"+f"(d[3]),"+f"(d[4]),"+f"(d[5]),"+f"(d[6]),"+f"(d[7]),"+f"(d[8]),"+f"(d[9]),"+f"(d[10]),"+f"(d[11]),"+f"(d[12]),"+f"(d[13]),"+f"(d[14]),"+f"(d[15]),"+f"(d[16]),"+f"(d[17]),"+f"(d[18]),"+f"(d[19]),"+f"(d[20]),"+f"(d[21]),"+f"(d[22]),"+f"(d[23]),"+f"(d[24]),"+f"(d[25]),"+f"(d[26]),"+f"(d[27]),"+f"(d[28]),"+f"(d[29]),"+f"(d[30]),"+f"(d[31]),"+f"(d[32]),"+f"(d[33]),"+f"(d[34]),"+f"(d[35]),"+f"(d[36]),"+f"(d[37]),"+f"(d[38]),"+f"(d[39]),"+f"(d[40]),"+f"(d[41]),"+f"(d[42]),"+f"(d[43]),"+f"(d[44]),"+f"(d[45]),"+f"(d[46]),"+f"(d[47]),"+f"(d[48]),"+f"(d[49]),"+f"(d[50]),"+f"(d[51]),"+f"(d[52]),"+f"(d[53]),"+f"(d[54]),"+f"(d[55]),"+f"(d[56]),"+f"(d[57]),"+f"(d[58]),"+f"(d[59]),"+f"(d[60]),"+f"(d[61]),"+f"(d[62]),"+f"(d[63]) : "r"(a0), "r"(a1), "r"(a2), "r"(a3), "l"(db));
}
template<> __device__ __forceinline__ void wg_rs<120>(float (&d)[64], uint32_t a0, uint32_t a1, uint32_t a2, uint32_t a3, uint64_t db) {
  asm volatile("{.reg .pred p; setp.ne.b32 p, 1, 0; wgmma.mma_async.sync.aligned.m64n120k16.f32.bf16.bf16 {%0,%1,%2,%3,%4,%5,%6,%7,%8,%9,%10,%11,%12,%13,%14,%15,%16,%17,%18,%19,%20,%21,%22,%23,%24,%25,%26,%27,%28,%29,%30,%31,%32,%33,%34,%35,%36,%37,%38,%39,%40,%41,%42,%43,%44,%45,%46,%47,%48,%49,%50,%51,%52,%53,%54,%55,%56,%57,%58,%59}, {%60,%61,%62,%63}, %64, p, 1, 1, 0;}"
    : "+f"(d[0]),"+f"(d[1]),"+f"(d[2]),"+f"(d[3]),"+f"(d[4]),"+f"(d[5]),"+f"(d[6]),"+f"(d[7]),"+f"(d[8]),"+f"(d[9]),"+f"(d[10]),"+f"(d[11]),"+f"(d[12]),"+f"(d[13]),"+f"(d[14]),"+f"(d[15]),"+f"(d[16]),"+f"(d[17]),"+f"(d[18]),"+f"(d[19]),"+f"(d[20]),"+f"(d[21]),"+f"(d[22]),"+f"(d[23]),"+f"(d[24]),"+f"(d[25]),"+f"(d[26]),"+f"(d[27]),"+f"(d[28]),"+f"(d[29]),"+f"(d[30]),"+f"(d[31]),"+f"(d[32]),"+f"(d[33]),"+f"(d[34]),"+f"(d[35]),"+f"(d[36]),"+f"(d[37]),"+f"(d[38]),"+f"(d[39]),"+f"(d[40]),"+f"(d[41]),"+f"(d[42]),"+f"(d[43]),"+f"(d[44]),"+f"(d[45]),"+f"(d[46]),"+f"(d[47]),"+f"(d[48]),"+f"(d[49]),"+f"(d[50]),"+f"(d[51]),"+f"(d[52]),"+f"(d[53]),"+f"(d[54]),"+f"(d[55]),"+f"(d[56]),"+f"(d[57]),"+f"(d[58]),"+f"(d[59]) : "r"(a0), "r"(a1), "r"(a2), "r"(a3), "l"(db));
}
template<> __device__ __forceinline__ void wg_rs<112>(float (&d)[64], uint32_t a0, uint32_t a1, uint32_t a2, uint32_t a3, uint64_t db) {
  asm volatile("{.reg .pred p; setp.ne.b32 p, 1, 0; wgmma.mma_async.sync.aligned.m64n112k16.f32.bf16.bf16 {%0,%1,%2,%3,%4,%5,%6,%7,%8,%9,%10,%11,%12,%13,%14,%15,%16,%17,%18,%19,%20,%21,%22,%23,%24,%25,%26,%27,%28,%29,%30,%31,%32,%33,%34,%35,%36,%37,%38,%39,%40,%41,%42,%43,%44,%45,%46,%47,%48,%49,%50,%51,%52,%53,%54,%55}, {%56,%57,%58,%59}, %60, p, 1, 1, 0;}"
    : "+f"(d[0]),"+f"(d[1]),"+f"(d[2]),"+f"(d[3]),"+f"(d[4]),"+f"(d[5]),"+f"(d[6]),"+f"(d[7]),"+f"(d[8]),"+f"(d[9]),"+f"(d[10]),"+f"(d[11]),"+f"(d[12]),"+f"(d[13]),"+f"(d[14]),"+f"(d[15]),"+f"(d[16]),"+f"(d[17]),"+f"(d[18]),"+f"(d[19]),"+f"(d[20]),"+f"(d[21]),"+f"(d[22]),"+f"(d[23]),"+f"(d[24]),"+f"(d[25]),"+f"(d[26]),"+f"(d[27]),"+f"(d[28]),"+f"(d[29]),"+f"(d[30]),"+f"(d[31]),"+f"(d[32]),"+f"(d[33]),"+f"(d[34]),"+f"(d[35]),"+f"(d[36]),"+f"(d[37]),"+f"(d[38]),"+f"(d[39]),"+f"(d[40]),"+f"(d[41]),"+f"(d[42]),"+f"(d[43]),"+f"(d[44]),"+f"(d[45]),"+f"(d[46]),"+f"(d[47]),"+f"(d[48]),"+f"(d[49]),"+f"(d[50]),"+f"(d[51]),"+f"(d[52]),"+f"(d[53]),"+f"(d[54]),"+f"(d[55]) : "r"(a0), "r"(a1), "r"(a2), "r"(a3), "l"(db));
}
template<> __device__ __forceinline__ void wg_rs<104>(float (&d)[64], uint32_t a0, uint32_t a1, uint32_t a2, uint32_t a3, uint64_t db) {
  asm volatile("{.reg .pred p; setp.ne.b32 p, 1, 0; wgmma.mma_async.sync.aligned.m64n104k16.f32.bf16.bf16 {%0,%1,%2,%3,%4,%5,%6,%7,%8,%9,%10,%11,%12,%13,%14,%15,%16,%17,%18,%19,%20,%21,%22,%23,%24,%25,%26,%27,%28,%29,%30,%31,%32,%33,%34,%35,%36,%37,%38,%39,%40,%41,%42,%43,%44,%45,%46,%47,%48,%49,%50,%51}, {%52,%53,%54,%55}, %56, p, 1, 1, 0;}"
    : "+f"(d[0]),"+f"(d[1]),"+f"(d[2]),"+f"(d[3]),"+f"(d[4]),"+f"(d[5]),"+f"(d[6]),"+f"(d[7]),"+f"(d[8]),"+f"(d[9]),"+f"(d[10]),"+f"(d[11]),"+f"(d[12]),"+f"(d[13]),"+f"(d[14]),"+f"(d[15]),"+f"(d[16]),"+f"(d[17]),"+f"(d[18]),"+f"(d[19]),"+f"(d[20]),"+f"(d[21]),"+f"(d[22]),"+f"(d[23]),"+f"(d[24]),"+f"(d[25]),"+f"(d[26]),"+f"(d[27]),"+f"(d[28]),"+f"(d[29]),"+f"(d[30]),"+f"(d[31]),"+f"(d[32]),"+f"(d[33]),"+f"(d[34]),"+f"(d[35]),"+f"(d[36]),"+f"(d[37]),"+f"(d[38]),"+f"(d[39]),"+f"(d[40]),"+f"(d[41]),"+f"(d[42]),"+f"(d[43]),"+f"(d[44]),"+f"(d[45]),"+f"(d[46]),"+f"(d[47]),"+f"(d[48]),"+f"(d[49]),"+f"(d[50]),"+f"(d[51]) : "r"(a0), "r"(a1), "r"(a2), "r"(a3), "l"(db));
}
template<> __device__ __forceinline__ void wg_rs<96>(float (&d)[64], uint32_t a0, uint32_t a1, uint32_t a2, uint32_t a3, uint64_t db) {
  asm volatile("{.reg .pred p; setp.ne.b32 p, 1, 0; wgmma.mma_async.sync.aligned.m64n96k16.f32.bf16.bf16 {%0,%1,%2,%3,%4,%5,%6,%7,%8,%9,%10,%11,%12,%13,%14,%15,%16,%17,%18,%19,%20,%21,%22,%23,%24,%25,%26,%27,%28,%29,%30,%31,%32,%33,%34,%35,%36,%37,%38,%39,%40,%41,%42,%43,%44,%45,%46,%47}, {%48,%49,%50,%51}, %52, p, 1, 1, 0;}"
    : "+f"(d[0]),"+f"(d[1]),"+f"(d[2]),"+f"(d[3]),"+f"(d[4]),"+f"(d[5]),"+f"(d[6]),"+f"(d[7]),"+f"(d[8]),"+f"(d[9]),"+f"(d[10]),"+f"(d[11]),"+f"(d[12]),"+f"(d[13]),"+f"(d[14]),"+f"(d[15]),"+f"(d[16]),"+f"(d[17]),"+f"(d[18]),"+f"(d[19]),"+f"(d[20]),"+f"(d[21]),"+f"(d[22]),"+f"(d[23]),"+f"(d[24]),"+f"(d[25]),"+f"(d[26]),"+f"(d[27]),"+f"(d[28]),"+f"(d[29]),"+f"(d[30]),"+f"(d[31]),"+f"(d[32]),"+f"(d[33]),"+f"(d[34]),"+f"(d[35]),"+f"(d[36]),"+f"(d[37]),"+f"(d[38]),"+f"(d[39]),"+f"(d[40]),"+f"(d[41]),"+f"(d[42]),"+f"(d[43]),"+f"(d[44]),"+f"(d[45]),"+f"(d[46]),"+f"(d[47]) : "r"(a0), "r"(a1), "r"(a2), "r"(a3), "l"(db));
}
template<> __device__ __forceinline__ void wg_rs<88>(float (&d)[64], uint32_t a0, uint32_t a1, uint32_t a2, uint32_t a3, uint64_t db) {
  asm volatile("{.reg .pred p; setp.ne.b32 p, 1, 0; wgmma.mma_async.sync.aligned.m64n88k16.f32.bf16.bf16 {%0,%1,%2,%3,%4,%5,%6,%7,%8,%9,%10,%11,%12,%13,%14,%15,%16,%17,%18,%19,%20,%21,%22,%23,%24,%25,%26,%27,%28,%29,%30,%31,%32,%33,%34,%35,%36,%37,%38,%39,%40,%41,%42,%43}, {%44,%45,%46,%47}, %48, p, 1, 1, 0;}"
    : "+f"(d[0]),"+f"(d[1]),"+f"(d[2]),"+f"(d[3]),"+f"(d[4]),"+f"(d[5]),"+f"(d[6]),"+f"(d[7]),"+f"(d[8]),"+f"(d[9]),"+f"(d[10]),"+f"(d[11]),"+f"(d[12]),"+f"(d[13]),"+f"(d[14]),"+f"(d[15]),"+f"(d[16]),"+f"(d[17]),"+f"(d[18]),"+f"(d[19]),"+f"(d[20]),"+f"(d[21]),"+f"(d[22]),"+f"(d[23]),"+f"(d[24]),"+f"(d[25]),"+f"(d[26]),"+f"(d[27]),"+f"(d[28]),"+f"(d[29]),"+f"(d[30]),"+f"(d[31]),"+f"(d[32]),"+f"(d[33]),"+f"(d[34]),"+f"(d[35]),"+f"(d[36]),"+f"(d[37]),"+f"(d[38]),"+f"(d[39]),"+f"(d[40]),"+f"(d[41]),"+f"(d[42]),"+f"(d[43]) : "r"(a0), "r"(a1), "r"(a2), "r"(a3), "l"(db));
}
template<> __device__ __forceinline__ void wg_rs<80>(float (&d)[64], uint32_t a0, uint32_t a1, uint32_t a2, uint32_t a3, uint64_t db) {
  asm volatile("{.reg .pred p; setp.ne.b32 p, 1, 0; wgmma.mma_async.sync.aligned.m64n80k16.f32.bf16.bf16 {%0,%1,%2,%3,%4,%5,%6,%7,%8,%9,%10,%11,%12,%13,%14,%15,%16,%17,%18,%19,%20,%21,%22,%23,%24,%25,%26,%27,%28,%29,%30,%31,%32,%33,%34,%35,%36,%37,%38,%39}, {%40,%41,%42,%43}, %44, p, 1, 1, 0;}"
    : "+f"(d[0]),"+f"(d[1]),"+f"(d[2]),"+f"(d[3]),"+f"(d[4]),"+f"(d[5]),"+f"(d[6]),"+f"(d[7]),"+f"(d[8]),"+f"(d[9]),"+f"(d[10]),"+f"(d[11]),"+f"(d[12]),"+f"(d[13]),"+f"(d[14]),"+f"(d[15]),"+f"(d[16]),"+f"(d[17]),"+f"(d[18]),"+f"(d[19]),"+f"(d[20]),"+f"(d[21]),"+f"(d[22]),"+f"(d[23]),"+f"(d[24]),"+f"(d[25]),"+f"(d[26]),"+f"(d[27]),"+f"(d[28]),"+f"(d[29]),"+f"(d[30]),"+f"(d[31]),"+f"(d[32]),"+f"(d[33]),"+f"(d[34]),"+f"(d[35]),"+f"(d[36]),"+f"(d[37]),"+f"(d[38]),"+f"(d[39]) : "r"(a0), "r"(a1), "r"(a2), "r"(a3), "l"(db));
}
template<> __device__ __forceinline__ void wg_rs<72>(float (&d)[64], uint32_t a0, uint32_t a1, uint32_t a2, uint32_t a3, uint64_t db) {
  asm volatile("{.reg .pred p; setp.ne.b32 p, 1, 0; wgmma.mma_async.sync.aligned.m64n72k16.f32.bf16.bf16 {%0,%1,%2,%3,%4,%5,%6,%7,%8,%9,%10,%11,%12,%13,%14,%15,%16,%17,%18,%19,%20,%21,%22,%23,%24,%25,%26,%27,%28,%29,%30,%31,%32,%33,%34,%35}, {%36,%37,%38,%39}, %40, p, 1, 1, 0;}"
    : "+f"(d[0]),"+f"(d[1]),"+f"(d[2]),"+f"(d[3]),"+f"(d[4]),"+f"(d[5]),"+f"(d[6]),"+f"(d[7]),"+f"(d[8]),"+f"(d[9]),"+f"(d[10]),"+f"(d[11]),"+f"(d[12]),"+f"(d[13]),"+f"(d[14]),"+f"(d[15]),"+f"(d[16]),"+f"(d[17]),"+f"(d[18]),"+f"(d[19]),"+f"(d[20]),"+f"(d[21]),"+f"(d[22]),"+f"(d[23]),"+f"(d[24]),"+f"(d[25]),"+f"(d[26]),"+f"(d[27]),"+f"(d[28]),"+f"(d[29]),"+f"(d[30]),"+f"(d[31]),"+f"(d[32]),"+f"(d[33]),"+f"(d[34]),"+f"(d[35]) : "r"(a0), "r"(a1), "r"(a2), "r"(a3), "l"(db));
}
template<> __device__ __forceinline__ void wg_rs<64>(float (&d)[64], uint32_t a0, uint32_t a1, uint32_t a2, uint32_t a3, uint64_t db) {
  asm volatile("{.reg .pred p; setp.ne.b32 p, 1, 0; wgmma.mma_async.sync.aligned.m64n64k16.f32.bf16.bf16 {%0,%1,%2,%3,%4,%5,%6,%7,%8,%9,%10,%11,%12,%13,%14,%15,%16,%17,%18,%19,%20,%21,%22,%23,%24,%25,%26,%27,%28,%29,%30,%31}, {%32,%33,%34,%35}, %36, p, 1, 1, 0;}"
    : "+f"(d[0]),"+f"(d[1]),"+f"(d[2]),"+f"(d[3]),"+f"(d[4]),"+f"(d[5]),"+f"(d[6]),"+f"(d[7]),"+f"(d[8]),"+f"(d[9]),"+f"(d[10]),"+f"(d[11]),"+f"(d[12]),"+f"(d[13]),"+f"(d[14]),"+f"(d[15]),"+f"(d[16]),"+f"(d[17]),"+f"(d[18]),"+f"(d[19]),"+f"(d[20]),"+f"(d[21]),"+f"(d[22]),"+f"(d[23]),"+f"(d[24]),"+f"(d[25]),"+f"(d[26]),"+f"(d[27]),"+f"(d[28]),"+f"(d[29]),"+f"(d[30]),"+f"(d[31]) : "r"(a0), "r"(a1), "r"(a2), "r"(a3), "l"(db));
}
__device__ __forceinline__ void wg_rs_first(float (&d)[64], uint32_t a0, uint32_t a1, uint32_t a2, uint32_t a3, uint64_t db) {
  asm volatile("{.reg .pred p; setp.ne.b32 p, 0, 0; wgmma.mma_async.sync.aligned.m64n128k16.f32.bf16.bf16 {%0,%1,%2,%3,%4,%5,%6,%7,%8,%9,%10,%11,%12,%13,%14,%15,%16,%17,%18,%19,%20,%21,%22,%23,%24,%25,%26,%27,%28,%29,%30,%31,%32,%33,%34,%35,%36,%37,%38,%39,%40,%41,%42,%43,%44,%45,%46,%47,%48,%49,%50,%51,%52,%53,%54,%55,%56,%57,%58,%59,%60,%61,%62,%63}, {%64,%65,%66,%67}, %68, p, 1, 1, 0;}"
    : "=f"(d[0]),"=f"(d[1]),"=f"(d[2]),"=f"(d[3]),"=f"(d[4]),"=f"(d[5]),"=f"(d[6]),"=f"(d[7]),"=f"(d[8]),"=f"(d[9]),"=f"(d[10]),"=f"(d[11]),"=f"(d[12]),"=f"(d[13]),"=f"(d[14]),"=f"(d[15]),"=f"(d[16]),"=f"(d[17]),"=f"(d[18]),"=f"(d[19]),"=f"(d[20]),"=f"(d[21]),"=f"(d[22]),"=f"(d[23]),"=f"(d[24]),"=f"(d[25]),"=f"(d[26]),"=f"(d[27]),"=f"(d[28]),"=f"(d[29]),"=f"(d[30]),"=f"(d[31]),"=f"(d[32]),"=f"(d[33]),"=f"(d[34]),"=f"(d[35]),"=f"(d[36]),"=f"(d[37]),"=f"(d[38]),"=f"(d[39]),"=f"(d[40]),"=f"(d[41]),"=f"(d[42]),"=f"(d[43]),"=f"(d[44]),"=f"(d[45]),"=f"(d[46]),"=f"(d[47]),"=f"(d[48]),"=f"(d[49]),"=f"(d[50]),"=f"(d[51]),"=f"(d[52]),"=f"(d[53]),"=f"(d[54]),"=f"(d[55]),"=f"(d[56]),"=f"(d[57]),"=f"(d[58]),"=f"(d[59]),"=f"(d[60]),"=f"(d[61]),"=f"(d[62]),"=f"(d[63]) : "r"(a0), "r"(a1), "r"(a2), "r"(a3), "l"(db));
}
__device__ __forceinline__ void wg_tt128(float (&d)[64], uint64_t da, uint64_t db, int sc) {
  asm volatile("{.reg .pred p; setp.ne.b32 p, %66, 0; wgmma.mma_async.sync.aligned.m64n128k16.f32.bf16.bf16 {%0,%1,%2,%3,%4,%5,%6,%7,%8,%9,%10,%11,%12,%13,%14,%15,%16,%17,%18,%19,%20,%21,%22,%23,%24,%25,%26,%27,%28,%29,%30,%31,%32,%33,%34,%35,%36,%37,%38,%39,%40,%41,%42,%43,%44,%45,%46,%47,%48,%49,%50,%51,%52,%53,%54,%55,%56,%57,%58,%59,%60,%61,%62,%63}, %64, %65, p, 1, 1, 1, 1;}"
    : "+f"(d[0]),"+f"(d[1]),"+f"(d[2]),"+f"(d[3]),"+f"(d[4]),"+f"(d[5]),"+f"(d[6]),"+f"(d[7]),"+f"(d[8]),"+f"(d[9]),"+f"(d[10]),"+f"(d[11]),"+f"(d[12]),"+f"(d[13]),"+f"(d[14]),"+f"(d[15]),"+f"(d[16]),"+f"(d[17]),"+f"(d[18]),"+f"(d[19]),"+f"(d[20]),"+f"(d[21]),"+f"(d[22]),"+f"(d[23]),"+f"(d[24]),"+f"(d[25]),"+f"(d[26]),"+f"(d[27]),"+f"(d[28]),"+f"(d[29]),"+f"(d[30]),"+f"(d[31]),"+f"(d[32]),"+f"(d[33]),"+f"(d[34]),"+f"(d[35]),"+f"(d[36]),"+f"(d[37]),"+f"(d[38]),"+f"(d[39]),"+f"(d[40]),"+f"(d[41]),"+f"(d[42]),"+f"(d[43]),"+f"(d[44]),"+f"(d[45]),"+f"(d[46]),"+f"(d[47]),"+f"(d[48]),"+f"(d[49]),"+f"(d[50]),"+f"(d[51]),"+f"(d[52]),"+f"(d[53]),"+f"(d[54]),"+f"(d[55]),"+f"(d[56]),"+f"(d[57]),"+f"(d[58]),"+f"(d[59]),"+f"(d[60]),"+f"(d[61]),"+f"(d[62]),"+f"(d[63]) : "l"(da), "l"(db), "r"(sc));
}
__device__ __forceinline__ void wg_tt64(float (&d)[64], uint64_t da, uint64_t db, int sc) {
  asm volatile("{.reg .pred p; setp.ne.b32 p, %34, 0; wgmma.mma_async.sync.aligned.m64n64k16.f32.bf16.bf16 {%0,%1,%2,%3,%4,%5,%6,%7,%8,%9,%10,%11,%12,%13,%14,%15,%16,%17,%18,%19,%20,%21,%22,%23,%24,%25,%26,%27,%28,%29,%30,%31}, %32, %33, p, 1, 1, 1, 1;}"
    : "+f"(d[0]),"+f"(d[1]),"+f"(d[2]),"+f"(d[3]),"+f"(d[4]),"+f"(d[5]),"+f"(d[6]),"+f"(d[7]),"+f"(d[8]),"+f"(d[9]),"+f"(d[10]),"+f"(d[11]),"+f"(d[12]),"+f"(d[13]),"+f"(d[14]),"+f"(d[15]),"+f"(d[16]),"+f"(d[17]),"+f"(d[18]),"+f"(d[19]),"+f"(d[20]),"+f"(d[21]),"+f"(d[22]),"+f"(d[23]),"+f"(d[24]),"+f"(d[25]),"+f"(d[26]),"+f"(d[27]),"+f"(d[28]),"+f"(d[29]),"+f"(d[30]),"+f"(d[31]) : "l"(da), "l"(db), "r"(sc));
}
__device__ __forceinline__ void wg_tt32(float (&d)[64], uint64_t da, uint64_t db, int sc) {
  asm volatile("{.reg .pred p; setp.ne.b32 p, %18, 0; wgmma.mma_async.sync.aligned.m64n32k16.f32.bf16.bf16 {%0,%1,%2,%3,%4,%5,%6,%7,%8,%9,%10,%11,%12,%13,%14,%15}, %16, %17, p, 1, 1, 1, 1;}"
    : "+f"(d[0]),"+f"(d[1]),"+f"(d[2]),"+f"(d[3]),"+f"(d[4]),"+f"(d[5]),"+f"(d[6]),"+f"(d[7]),"+f"(d[8]),"+f"(d[9]),"+f"(d[10]),"+f"(d[11]),"+f"(d[12]),"+f"(d[13]),"+f"(d[14]),"+f"(d[15]) : "l"(da), "l"(db), "r"(sc));
}
__device__ __forceinline__ void wg_g1(float (&d)[88], uint64_t da, uint64_t db, int sc) {
  asm volatile("{.reg .pred p; setp.ne.b32 p, %90, 0; wgmma.mma_async.sync.aligned.m64n176k16.f32.bf16.bf16 {%0,%1,%2,%3,%4,%5,%6,%7,%8,%9,%10,%11,%12,%13,%14,%15,%16,%17,%18,%19,%20,%21,%22,%23,%24,%25,%26,%27,%28,%29,%30,%31,%32,%33,%34,%35,%36,%37,%38,%39,%40,%41,%42,%43,%44,%45,%46,%47,%48,%49,%50,%51,%52,%53,%54,%55,%56,%57,%58,%59,%60,%61,%62,%63,%64,%65,%66,%67,%68,%69,%70,%71,%72,%73,%74,%75,%76,%77,%78,%79,%80,%81,%82,%83,%84,%85,%86,%87}, %88, %89, p, 1, 1, 1, 0;}"
    : "+f"(d[0]),"+f"(d[1]),"+f"(d[2]),"+f"(d[3]),"+f"(d[4]),"+f"(d[5]),"+f"(d[6]),"+f"(d[7]),"+f"(d[8]),"+f"(d[9]),"+f"(d[10]),"+f"(d[11]),"+f"(d[12]),"+f"(d[13]),"+f"(d[14]),"+f"(d[15]),"+f"(d[16]),"+f"(d[17]),"+f"(d[18]),"+f"(d[19]),"+f"(d[20]),"+f"(d[21]),"+f"(d[22]),"+f"(d[23]),"+f"(d[24]),"+f"(d[25]),"+f"(d[26]),"+f"(d[27]),"+f"(d[28]),"+f"(d[29]),"+f"(d[30]),"+f"(d[31]),"+f"(d[32]),"+f"(d[33]),"+f"(d[34]),"+f"(d[35]),"+f"(d[36]),"+f"(d[37]),"+f"(d[38]),"+f"(d[39]),"+f"(d[40]),"+f"(d[41]),"+f"(d[42]),"+f"(d[43]),"+f"(d[44]),"+f"(d[45]),"+f"(d[46]),"+f"(d[47]),"+f"(d[48]),"+f"(d[49]),"+f"(d[50]),"+f"(d[51]),"+f"(d[52]),"+f"(d[53]),"+f"(d[54]),"+f"(d[55]),"+f"(d[56]),"+f"(d[57]),"+f"(d[58]),"+f"(d[59]),"+f"(d[60]),"+f"(d[61]),"+f"(d[62]),"+f"(d[63]),"+f"(d[64]),"+f"(d[65]),"+f"(d[66]),"+f"(d[67]),"+f"(d[68]),"+f"(d[69]),"+f"(d[70]),"+f"(d[71]),"+f"(d[72]),"+f"(d[73]),"+f"(d[74]),"+f"(d[75]),"+f"(d[76]),"+f"(d[77]),"+f"(d[78]),"+f"(d[79]),"+f"(d[80]),"+f"(d[81]),"+f"(d[82]),"+f"(d[83]),"+f"(d[84]),"+f"(d[85]),"+f"(d[86]),"+f"(d[87]) : "l"(da), "l"(db), "r"(sc));
}

struct Params { const __nv_bfloat16 *x, *logA, *Aim, *Cr, *Ci, *logdt, *Dskip, *Wg, *Wu, *Wd; uint4* xnT; float2* st; uint2* S; unsigned* flags; };
struct Maps { CUtensorMap x[2], xo, out, wg, wu, wd, hst[2], hld, xt, sld; };

__device__ __forceinline__ void conv_channel(uint32_t cb, int w, int lane, uint32_t (&res)[8], uint32_t sig, int sidx) {
    const int q = lane & 3, g = lane >> 2, gam = g >> 2;
    float acc[64];
    uint2 a[17][2];
    const uint32_t t0 = cb + CH_T + (uint32_t)(14 + 4 * w + (g & 3) - 2 * q) * 280u + gam * 8;
#define LDA(s0, s1) _Pragma("unroll") for (int s = s0; s < s1; s++) { a[s][0] = lds64(t0 + s * 16); a[s][1] = lds64(t0 - 8 * 280 + s * 16); }
#define CT(N, s) wg_rs<N>(acc, a[s][0].x, a[s][0].y, a[s][1].x, a[s][1].y, dU + 4 * (s))
    const uint64_t dU = mkdesc(cb + CH_U, UPLANE, 128, 0);
    LDA(0, 17)
    if (sig) { fence_async_smem(); mbar_arrive(sig); }
    WG_FENCE();
    if (w == 0) STAMP2(52 + 3 * sidx);
    wg_rs_first(acc, a[0][0].x, a[0][0].y, a[0][1].x, a[0][1].y, dU);
    CT(128, 1); CT(120, 2); CT(120, 3); CT(112, 4); CT(112, 5); CT(104, 6); CT(104, 7); CT(96, 8);
    CT(96, 9); CT(88, 10); CT(88, 11); CT(80, 12); CT(80, 13); CT(72, 14); CT(72, 15); CT(64, 16);
#undef CT
#undef LDA
    wg_tt64(acc, mkdesc(cb + CH_A3, 128, 512, 0), mkdesc(cb + CH_B3, 384, 32, 0), 1);
    wg_tt32(acc, mkdesc(cb + CH_A3 + 256, 128, 512, 0), mkdesc(cb + CH_B3 + 128, 384, 32, 0), 1);
    WG_COMMIT();
    if (w == 0) STAMP2(53 + 3 * sidx);
    WG_WAIT(0);
    fence_acc(acc);
    if (w == 0) STAMP2(54 + 3 * sidx);
    const int src1 = (lane & ~3) | ((q + 1) & 3);
    float E[16][2];
    #pragma unroll
    for (int j = 0; j < 16; j++) {
        const float nxt = (j < 15) ? acc[4 * (j + 1) + 2] : 0.f;
        const float sup = (q == 0) ? nxt : acc[4 * j + 2];
        const float v = __shfl_sync(0xffffffffu, sup, src1);
        E[j][0] = acc[4 * j] + acc[4 * j + 3];
        E[j][1] = acc[4 * j + 1] + v;
    }
    const int src2 = gam ? ((lane & 12) | ((q + 3) & 3)) : (16 | (lane & 12) | ((q + 1) & 3));
    const bool c1 = gam && q != 0, c2 = gam && q == 0;
    #pragma unroll
    for (int a2 = 0; a2 < 8; a2++) {
        float y[2];
        #pragma unroll
        for (int e = 0; e < 2; e++) {
            const float sup = c1 ? E[2 * a2][e] : E[2 * a2 + 1][e];
            const float nxt = (a2 < 7) ? E[2 * a2 + 2][e] : 0.f;
            const float keep = c2 ? nxt : (c1 ? E[2 * a2 + 1][e] : E[2 * a2][e]);
            y[e] = keep + __shfl_sync(0xffffffffu, sup, src2);
        }
        res[a2] = pack2(y[1], y[0]);
    }
}

__device__ __forceinline__ void consumer(uint32_t sb, int warp, const Params& P, const Maps& M) {
    const int V = warp >> 2, w = warp & 3, lane = threadIdx.x & 31, q = lane & 3, g = lane >> 2;
    const int c = blockIdx.x;
    const uint32_t bars = sb + OFF_BAR, xb = sb + OFF_X + V * 2 * XBUF;
    {
        float ag[88], au[88];
        define_acc(ag); define_acc(au);
        mbar_wait(bars + 8 * B_FULLW, 0);
        mbar_wait(bars + 8 * (B_FULLX + 2 * V), 0);
        #pragma unroll 1
        for (int st = 0; st < 8; st++) {
            uint64_t dG = mkdesc(sb + OFF_W + (st & 3) * 16384, 0, 1024, 1), dX = mkdesc(xb + (st & 1) * XBUF, 16, 1024, 1);
            uint32_t sig = lane == 0 && (V ? st < 6 : st > 0);
            asm volatile("" : "+l"(dG), "+l"(dX), "+r"(sig) :: "memory");
            if (V ? st < 7 : st > 1) mbar_wait(bars + 8 * (B_TURN + V), st & 1);
            STAMP(40 + 8 * V + st);
            WG_FENCE();
            #pragma unroll
            for (int k = 0; k < 4; k++) {
                if (k == SIGK) mbar_arrive_if(bars + 8 * (B_TURN + 1 - V), sig);
                wg_g1(ag, dG + k * 128, dX + k * 2, k ? 1 : st);
                wg_g1(au, dG + 512 + k * 128, dX + k * 2, k ? 1 : st);
            }
            WG_COMMIT();
            if (st == 6 * V) {
                mbar_wait(bars + 8 * (B_FULLW + ((st + 1) & 3)), V);
                mbar_wait(bars + 8 * (B_FULLX + 2 * V + 1), V);
            } else {
                WG_WAIT(1);
                mbar_arrive_if(bars + 8 * (B_EMPTYW + 2 * V), lane == 0 && st == 6 * V + 1);
                mbar_arrive_if(bars + 8 * (B_EMPTYX + 2 * V), lane == 0 && st == 6 * V + 1);
                WG_WAIT(0);
                mbar_arrive_if(bars + 8 * (B_EMPTYW + (st & 3)), lane == 0);
                mbar_arrive_if(bars + 8 * (B_EMPTYX + 2 * V + (st & 1)), lane == 0);
                if (st < 7) {
                    mbar_wait(bars + 8 * (B_FULLW + ((st + 1) & 3)), (st + 1) >> 2);
                    mbar_wait(bars + 8 * (B_FULLX + 2 * V + ((st + 1) & 1)), ((st + 1) >> 1) & 1);
                }
            }
        }
        WG_WAIT(0);
        fence_acc(ag); fence_acc(au);
        STAMP(8 * V + 1);
        float cg0 = ag[84], cg1 = ag[86], cu0 = au[84], cu1 = au[86];
        const uint32_t ca = sb + OFF_CSUM + (8 * w + g) * 16;
        if (V == 0) { sts128(ca, FU(cg0), FU(cg1), FU(cu0), FU(cu1)); mbar_arrive(bars + 8 * B_CS); }
        else { mbar_wait(bars + 8 * B_CS, 0); const uint4 t = lds128(ca); cg0 = UF(t.x); cg1 = UF(t.y); cu0 = UF(t.z); cu1 = UF(t.w); }
        mbar_wait(bars + 8 * B_STATS, 0);
        mbar_wait(bars + 8 * (B_EMPTYX + 2 * V), 1);
        STAMP(13 + V);
        const uint32_t hs = xb + (2 * w + ((lane >> 3) & 1)) * (2688 + 128 * V) + (lane >> 4) * 128 + (lane & 7) * 16;
        const uint32_t sa = sb + OFF_ST + (168 * V + 2 * q) * 8;
        uint4 sq[22];
        #pragma unroll
        for (int j = 0; j < 3; j++) sq[j] = lds128(sa + j * 64);
        #pragma unroll
        for (int j = 0; j < 22; j += 2) {
            uint32_t o[4];
            #pragma unroll
            for (int jj = 0; jj < 2; jj++) {
                const uint4 sv = sq[j + jj];
                float hv[4];
                #pragma unroll
                for (int i = 0; i < 4; i++) {
                    const float m = UF((i & 1) ? sv.z : sv.x);
                    const float gh = fmaf(-m, (i & 2) ? cg1 : cg0, ag[4 * (j + jj) + i]) * UF((i & 1) ? sv.w : sv.y);
                    const float p = gh * fmaf(-m, (i & 2) ? cu1 : cu0, au[4 * (j + jj) + i]);
                    hv[i] = fmaf(p, tanh_fast(gh), p);
                }
                o[2 * jj] = pack2(hv[0], hv[1]); o[2 * jj + 1] = pack2(hv[2], hv[3]);
            }
            #pragma unroll
            for (int k = (j ? 3 + 3 * j / 2 : 3); k < 6 + 3 * j / 2 && k < 22; k++) sq[k] = lds128(sa + k * 64);
            uint32_t ad = hs + j * 128;
            if (j == 20 && V == 0 && lane >= 16) ad = xb + 21504 + (lane & 7) * 16;
            stsm4(ad, o[0], o[1], o[2], o[3]);
        }
        if (c >= 128) { fence_async_smem(); mbar_arrive(bars + 8 * (B_EPI + V)); }
        STAMP(8 * V + 2);
    }
    if (c >= 128) return;
    {
        uint32_t r0[8], r1[8];
        #pragma unroll
        for (int i = 0; i < 8; i++) asm volatile("" : "=r"(r1[i]));
        #pragma unroll 1
        for (int e = 0; e < 2; e++) {
            #pragma unroll
            for (int i = 0; i < 8; i++) r0[i] = r1[i];
            mbar_wait(bars + 8 * (B_CONV + 2 * V + e), 0);
            conv_channel(sb + OFF_CONV + (2 * V + e) * CH_STRIDE, w, lane, r1, e ? 0 : bars + 8 * (B_EPI + V), 2 * V + e);
            if (e == 0) STAMP(8 * V + 3);
        }
        const int gam = g >> 2, qq = gam ? ((q + 3) & 3) : q;
        const uint32_t sp = sb + OFF_CONV + V * OFF_SST + ((63 - 4 * gam - qq) * 16 + 4 * (w ^ (3 - qq)) + (g & 3)) * 8;
        bar_sync(3 + V);
        #pragma unroll
        for (int a2 = 0; a2 < 8; a2++) sts64(sp - a2 * 1024, r0[a2], r1[a2]);
        fence_async_smem();
        mbar_arrive(bars + 8 * (B_SIG + V));
        STAMP(8 * V + 4);
    }
    if (V == 1) return;
    {
        const int tau = c >> 2, dg = c & 3;
        const uint32_t row = 8 * (w & 1) + 32 * (w >> 1);
        float acc[64];
        define_acc(acc);
        const float rr0 = __ldcg(&P.st[64 * tau + row + g].y), rr1 = __ldcg(&P.st[64 * tau + row + g + 16].y);
        mbar_wait(bars + 8 * B_FULLD, 0);
        STAMP(5);
        uint64_t dB = mkdesc(sb + wd_slot(0), 8192, 1024, 1), dA = mkdesc(sb + h_slot(0), 1024, 128, 0);
        #pragma unroll 1
        for (int st = 0; st < 21; st++) {
            WG_FENCE();
            wg_tt128(acc, dA, dB, st);
            wg_tt128(acc, dA + 128, dB + 128, 1);
            wg_tt128(acc, dA + 256, dB + 256, 1);
            wg_tt128(acc, dA + 384, dB + 384, 1);
            WG_COMMIT();
            const int sd = (st + 1) & 7;
            const uint32_t nb = bars + 8 * (B_FULLD + sd), np = ((st + 1) >> 3) & 1;
            uint32_t ro = st == 15 ? 8 * B_CH0 : 8 * (B_EMPTYD + ((st - 1) & 7)), m = lane == 0 && st > 0, ok;
            dB = mkdesc(sb + wd_slot(sd), 8192, 1024, 1); dA = mkdesc(sb + h_slot(sd), 1024, 128, 0);
            asm volatile("{.reg .pred p; mbarrier.test_wait.parity.shared::cta.b64 p, [%5], %6; vote.sync.all.pred p, p, -1; selp.u32 %0, 1, 0, p;}"
                : "=r"(ok), "+l"(dA), "+l"(dB), "+r"(ro), "+r"(m) : "r"(nb), "r"(np) : "memory");
            WG_WAIT(1);
            mbar_arrive_if(bars + ro, m);
            if (!ok) mbar_wait(nb, np);
            if (w == 0) STAMP2(20 + st);
        }
        WG_FENCE();
        wg_tt128(acc, dA, dB, 1);
        wg_tt128(acc, dA + 128, dB + 128, 1);
        WG_COMMIT();
        mbar_wait(bars + 8 * B_XO, 0);
        const uint32_t xo = sb + OFF_CONV + (row + (lane & 7) + 16 * ((lane >> 3) & 1)) * 128;
        const uint32_t so = sb + wd_slot(6) + (w >> 1) * 8192 + q * 256 + (g & 1) * 8;
        const uint32_t sx = (4 * (w & 1) + (g >> 1)) ^ (2 * q) ^ (2 * ((2 * tau + (w >> 1)) & 3));
        uint32_t xr[8][4];
        uint2 sv[16];
        #pragma unroll
        for (int j = 0; j < 16; j += 2) {
            ldsm4(xr[j >> 1], xo + (j >> 3) * 8192 + ((((j & 7) + (lane >> 4)) ^ (lane & 7)) << 4));
            sv[j] = lds64(so + j * 512 + (sx << 4));
            sv[j + 1] = lds64(so + j * 512 + 128 + ((sx ^ 1) << 4));
        }
        WG_WAIT(0);
        fence_acc(acc);
        STAMP(6);
        #pragma unroll
        for (int j = 0; j < 16; j += 2) {
            #pragma unroll
            for (int i = 0; i < 4; i++) {
                const int jj = j + (i >> 1), hh = i & 1;
                const float f0 = acc[4 * jj + 2 * hh] * (hh ? rr1 : rr0), f1 = acc[4 * jj + 2 * hh + 1] * (hh ? rr1 : rr0);
                const uint32_t G = pack2(fmaf(f0, tanh_fast(f0), f0), fmaf(f1, tanh_fast(f1), f1));
                const uint32_t s2 = __byte_perm(sv[jj].x, sv[jj].y, hh ? 0x7632 : 0x5410);
                asm("fma.rn.bf16x2 %0, %1, %2, %0;" : "+r"(xr[j >> 1][i]) : "r"(s2), "r"(G));
            }
            stsm4(xo + (j >> 3) * 8192 + ((((j & 7) + (lane >> 4)) ^ (lane & 7)) << 4), xr[j >> 1][0], xr[j >> 1][1], xr[j >> 1][2], xr[j >> 1][3]);
        }
        fence_async_smem();
        bar_sync(1);
        if (w == 0 && elect_one()) {
            #pragma unroll
            for (int i = 0; i < 2; i++)
                asm volatile("cp.async.bulk.tensor.2d.global.shared::cta.bulk_group [%0, {%2, %3}], [%1];"
                    :: "l"(&M.out), "r"(sb + OFF_CONV + i * 8192), "r"(dg * 128 + 64 * i), "r"(tau * 64) : "memory");
            asm volatile("cp.async.bulk.commit_group; cp.async.bulk.wait_group.read 0;" ::: "memory");
        }
        STAMP(7); GSTAMP(23);
    }
}

__device__ __forceinline__ float2 cexp_p(float re2, float im, float p) {
    float sn, cs;
    const float mag = ex2(re2 * p), th = im * p;
    asm("sin.approx.ftz.f32 %0, %1;" : "=f"(sn) : "f"(th));
    asm("cos.approx.ftz.f32 %0, %1;" : "=f"(cs) : "f"(th));
    return make_float2(mag * cs, mag * sn);
}
struct SsmRaw { unsigned short la, ai, cr, ci, ldt, dsk; };
__device__ __forceinline__ unsigned short ldu16(const void* p) { unsigned short v; asm volatile("ld.global.nc.u16 %0, [%1];" : "=h"(v) : "l"(p)); return v; }
__device__ __forceinline__ float2 cmul(float2 a, float2 b) { return make_float2(fmaf(a.x, b.x, -a.y * b.y), fmaf(a.x, b.y, a.y * b.x)); }
__device__ __forceinline__ float2 csqr(float2 a) { const float t = a.x * a.y; return make_float2(fmaf(a.x, a.x, -a.y * a.y), t + t); }
__device__ __forceinline__ void mma16816(float (&d)[4], const uint32_t (&a)[4], uint32_t b0, uint32_t b1) {
    asm volatile("mma.sync.aligned.m16n8k16.row.col.f32.bf16.bf16.f32 {%0,%1,%2,%3}, {%4,%5,%6,%7}, {%8,%9}, {%0,%1,%2,%3};"
        : "+f"(d[0]), "+f"(d[1]), "+f"(d[2]), "+f"(d[3]) : "r"(a[0]), "r"(a[1]), "r"(a[2]), "r"(a[3]), "r"(b0), "r"(b1));
}

__device__ __forceinline__ void layer_norm(uint32_t sb, uint32_t cb, int w, int lane) {
    const uint32_t bars = sb + OFF_BAR;
    mbar_wait(bars + 8 * B_LNX, 0);
    STAMP(34);
    {
        const uint32_t r0 = cb + CH_LN + (w & 1) * 64 + (lane >> 3) * 1040, ra = r0 + (lane & 7) * 16;
        const float pv = bf_lo(FU(ldsf(r0)));
        float s0 = 0.f, s1 = 0.f, a0 = 0.f, a1 = 0.f;
        #pragma unroll 1
        for (int k = 0; k < 1024; k += 512) {
            uint32_t v[16];
            #pragma unroll
            for (int j = 0; j < 4; j++) *(uint4*)&v[4 * j] = lds128(ra + k + 128 * j);
            #pragma unroll
            for (int i = 0; i < 16; i++) { const float t0 = bf_lo(v[i]) - pv, t1 = bf_hi(v[i]) - pv; s0 += t0; s1 += t1; a0 = fmaf(t0, t0, a0); a1 = fmaf(t1, t1, a1); }
        }
        s0 += s1; a0 += a1;
        #pragma unroll
        for (int o = 4; o; o >>= 1) { s0 += __shfl_xor_sync(0xffffffffu, s0, o); a0 += __shfl_xor_sync(0xffffffffu, a0, o); }
        s0 *= 1.f / DM;
        float sd, ri;
        asm("sqrt.approx.ftz.f32 %0, %1;" : "=f"(sd) : "f"(bf_round(bf_round(fmaxf(fmaf(-s0, s0, a0 * (1.f / DM)), 0.f)) + 1e-5f)));
        asm("rcp.approx.ftz.f32 %0, %1;" : "=f"(ri) : "f"(bf_round(sd)));
        if ((lane & 7) == 0) sts64(sb + OFF_CSUM + (w + 4 * (lane >> 3)) * 8, FU(bf_round(pv + s0)), FU(0.5f * ri));
    }
    STAMP(62);
    bar_sync(2);
    const int r = 4 * ((lane & 7) >> 1) + (lane & 1) + 2 * ((lane >> 3) & 1);
    const uint32_t ad = sb + OFF_CONV + (r & 3) * CH_STRIDE + CH_LN + (r & 1) * 64 + (r >> 2) * 1040 + (16 * w + (lane >> 4)) * 16;
    const uint4 sa = lds128(sb + OFF_CSUM + (lane & 3) * 32), sc = lds128(sb + OFF_CSUM + (lane & 3) * 32 + 16);
    const uint32_t m2[2] = {__byte_perm(sa.x, sa.z, 0x7632), __byte_perm(sc.x, sc.z, 0x7632)};
    const float ri[4] = {2.f * UF(sa.y), 2.f * UF(sa.w), 2.f * UF(sc.y), 2.f * UF(sc.w)};
    #pragma unroll 1
    for (int i = 0; i < 8; i += 4) {
        uint32_t v[4][4];
        #pragma unroll
        for (int j = 0; j < 4; j++)
            asm volatile("ldmatrix.sync.aligned.m8n8.x4.trans.shared.b16 {%0,%1,%2,%3}, [%4];" : "=r"(v[j][0]), "=r"(v[j][1]), "=r"(v[j][2]), "=r"(v[j][3]) : "r"(ad + 32 * (i + j)) : "memory");
        #pragma unroll
        for (int j = 0; j < 4; j++) {
            #pragma unroll
            for (int k = 0; k < 4; k++) {
                uint32_t dv; asm("sub.rn.bf16x2 %0, %1, %2;" : "=r"(dv) : "r"(v[j][k]), "r"(m2[k & 1]));
                v[j][k] = pack2(bf_lo(dv) * ri[2 * (k & 1)], bf_hi(dv) * ri[2 * (k & 1) + 1]);
            }
            sts64(cb + CH_LNT + lane * 8 + (i + j) * 512, v[j][0], v[j][1]); sts64(cb + CH_LNT + lane * 8 + (i + j) * 512 + 256, v[j][2], v[j][3]);
        }
    }
    fence_async_smem();
    mbar_arrive(bars + 8 * B_LN);
    STAMP(16);
}

__device__ __forceinline__ void kernel_gen(uint32_t fs, int lane, const SsmRaw& raw, float (&dacc)[2][3][4], const Params& P, int warp) {
    const float dt = bf_round(ex2(bf_lo(raw.ldt) * 1.4426950408889634f));
    const float re2 = bf_round(ex2(bf_lo(raw.la) * 1.4426950408889634f)) * dt * -1.4426950408889634f, im = bf_lo(raw.ai) * dt;
    const float2 C = make_float2(bf_lo(raw.cr) * (dt + dt), bf_lo(raw.ci) * -(dt + dt));
    STAMP(56);
    if (warp < 4 && lane == 0 && re2 != 1.f) {
        const int c = blockIdx.x;
        const char* p = warp < 2 ? (const char*)(P.x + (16 * (c & ~1) + 8 * (c & 1) + 16 * warp) * DM) : (const char*)(warp == 2 ? P.Wg : P.Wu) + 128 * FF * 2 + c * 8256;
        asm volatile("cp.async.bulk.prefetch.L2.global [%0], %1;" :: "l"(p), "r"(warp < 2 ? 8192 : 8256) : "memory");
    }
    const float2 z8 = cexp_p(re2, im, 8.f), y1 = cexp_p(re2, -im, 1.f), y256 = cexp_p(re2, -im, 256.f);
    float2 b0 = make_float2(1.f, 0.f), b1 = cexp_p(re2, im, 64.f), b2 = csqr(b1), b3 = cmul(b2, b1);
    const uint32_t fm = fs + (lane >> 3) * 144 + (lane & 7) * 16;
#define PK(v) pack2((v).x, (v).y)
    #pragma unroll RUNROLL
    for (uint32_t ro = 0; ro < 8 * 144; ro += 144) {
        stsm4(fm + (lane >> 3) * 7 * 144 + ro, PK(b0), PK(b1), PK(b2), PK(b3));
        b0 = cmul(b0, z8); b1 = cmul(b1, z8); b2 = cmul(b2, z8); b3 = cmul(b3, z8);
    }
    const float2 y2 = csqr(y1), y4 = csqr(y2), y8 = make_float2(z8.x, -z8.y);
    const float2 l1 = cmul(C, y1), l2 = cmul(C, y2), l3 = cmul(l1, y2);
    stsm4(fm + 32 * 144, PK(C), PK(l1), PK(l2), PK(l3));
    stsm4(fm + 36 * 144, PK(cmul(C, y4)), PK(cmul(l1, y4)), PK(cmul(l2, y4)), PK(cmul(l3, y4)));
    const float2 t0 = cmul(C, y256), t1 = cmul(t0, y256), t2 = cmul(t1, y256), t3_ = cmul(t2, y256);
    const float2 u1 = cmul(t0, y2), u2 = cmul(u1, y2), u3 = cmul(u2, y2);
    stsm4(fm + 40 * 144, PK(t0), PK(u1), PK(u2), PK(u3));
    stsm4(fm + 44 * 144, PK(t1), PK(cmul(t1, y4)), PK(t2), PK(cmul(t2, y4)));
    const float2 v0 = cmul(t3_, y8), v1 = cmul(v0, y256), v2 = cmul(v1, y256), v3 = cmul(v2, y256);
    stsm4(fm + 48 * 144, PK(v0), PK(v1), PK(v2), PK(v3));
    stsf(fs + lane * 4 + 52 * 144, UF(PK(t3_)));
#undef PK
    STAMP(57);
    const uint32_t lda = fs + (lane & 15) * 144 + (lane & 16);
    const uint32_t ldb = fs + (32 + (lane & 7)) * 144 + (lane >> 3) * 16;
    __syncwarp();
    #pragma unroll 1
    for (int ko = 0; ko < 128; ko += 64) {
        uint32_t b[3][4], a[4][4];
        #pragma unroll
        for (int i = 0; i < 3; i++) ldsm4(b[i], ldb + i * 8 * 144 + ko);
        #pragma unroll
        for (int i = 0; i < 4; i++) ldsm4(a[i], lda + (i & 1) * 16 * 144 + ko + (i >> 1) * 32);
        #pragma unroll
        for (int i = 0; i < 4; i++)
            #pragma unroll
            for (int t = 0; t < 3; t++) mma16816(dacc[i & 1][t], a[i], b[t][i & 2], b[t][(i & 2) + 1]);
    }
    STAMP(58);
}

__device__ __forceinline__ void aux_role(uint32_t sb, int w, float (&dacc)[2][3][4], float dsk, const __nv_bfloat16* x) {
    const int lane = threadIdx.x & 31, q = lane & 3, g = lane >> 2;
    const int c = blockIdx.x;
    const uint32_t bars = sb + OFF_BAR;
    if (c >= 128) { mbar_arrive(bars + 8 * B_LN); return; }
    {
        const uint32_t cb = sb + OFF_CONV + w * CH_STRIDE;
        if (elect_one()) {
            mbar_expect(bars + 8 * B_LNX, 4096);
            #pragma unroll
            for (int i = 0; i < 4; i++)
                bulk_load(cb + CH_LN + (w & 1) * 64 + i * 1040, x + (16 * (c & ~1) + 8 * (c & 1) + 16 + w + 4 * (i & 1) - 8 * (i & 2)) * DM, 1024, bars + 8 * B_LNX);
        }
        mbar_wait(bars + 8 * B_K, 0);
        #pragma unroll 1
        for (uint32_t pa = cb + CH_PART + lane * 16; pa < cb + CH_PART + 9216; pa += 3072) {
            #pragma unroll
            for (int i = 0; i < 6; i++) {
                const uint4 v = lds128(pa + i * 512);
                float* d = &dacc[0][0][0] + 4 * i;
                d[0] += UF(v.x); d[1] += UF(v.y); d[2] += UF(v.z); d[3] += UF(v.w);
            }
        }
        __syncwarp();
        STAMP(18);
        const uint32_t sF = cb + CH_A3, sG = cb + CH_G;
        if (lane == 0) dacc[0][0][0] += dsk;
        if (lane < 10) sts128(sG + 128 + (lane & 1) * 208 + (lane >> 1) * 16, 0, 0, 0, 0);
        const uint32_t f0 = sF + (8 * g + 2 * q) * 4, f1 = sF + ((q < 2) ? 256 + 4 * g + 2 * q : 256 + 2 * g + 64 * q) * 4, st1 = (q < 2) ? 128 : 64;
        const uint32_t ga = sG + ((g & 1) ? 0 : 208) + (63 - (g >> 1) - 32 * q) * 2;
        #pragma unroll
        for (int i = 0; i < 4; i++) {
            const int mu = i >> 1, hh = i & 1;
            sts64(f0 + i * 256, FU(dacc[mu][0][2 * hh]), FU(dacc[mu][0][2 * hh + 1]));
            sts64(f1 + i * st1, FU(dacc[mu][1][2 * hh]), FU(dacc[mu][1][2 * hh + 1]));
            const uint32_t pk = pack2(dacc[mu][2][2 * hh], dacc[mu][2][2 * hh + 1]);
            if (q < 2) { sts16(ga - 8 * i, pk & 0xffff); sts16(ga - 8 * i - 32, pk >> 16); }
        }
        if (lane == 2) stsf(sF + 2048, dacc[0][2][0]);
        STAMP(19);
        layer_norm(sb, cb, w, lane);
        mbar_wait(bars + 8 * B_LNS, 0);
        if (lane < 8) sts128(cb + CH_U + 2048 + (lane & 4) * (UPLANE / 4) + (lane & 3) * 16, 0, 0, 0, 0);
        bar_sync(2);
    }
    const int u = min(lane, 30) - 15, r2 = (u + ((u >> 1) & 1)) >> 1, r4 = (u + 1 + ((u >> 2) & 1)) >> 2, xt = 1024 + 16 * w + u;
    const uint32_t o0 = CH_A3 + 4 * (w == 0 ? u : w == 1 ? 256 + r2 : 256 + 64 * w + r4), ost = w == 0 ? 64 : w == 1 ? 32 : 16;
    const uint32_t oa0 = u >= 0 || w == 3 ? o0 : CH_A3 + 4 * (w == 1 ? 256 + u : w == 2 ? 384 + r2 : 0);
    const uint32_t ot = CH_A3 + 4 * min(512, 256 + ((xt + 1 + ((xt >> 2) & 1)) >> 2));
    const int kap = (lane >> 4) * 8 + ((lane >> 1) & 7), gam = lane & 1, hh = w >> 1, wp = w & 1;
    const uint32_t oa = CH_U + wp * UPLANE + (127 - 4 * kap - 2 * gam - hh) * 16;
    const uint32_t ob = CH_U + (wp ^ 1) * UPLANE + (128 - wp - 4 * kap - 2 * gam - hh) * 16;
    const uint32_t od = CH_A3 + (4 * wp + hh) * 512 + (kap >> 3) * 256 + (kap & 7) * 16 + gam * 8;
    #pragma unroll 1
    for (int k = 0; k < 4; k++) {
        const int ch = 2 * (k & 1) + (k >> 1);
        const uint32_t cb = sb + OFF_CONV + ch * CH_STRIDE;
        {
            float kv[17];
            kv[0] = ldsf(cb + oa0); kv[16] = ldsf(cb + ot);
            #pragma unroll
            for (int s = 1; s < 16; s++) kv[s] = ldsf(cb + o0 + s * ost);
            const int tid = threadIdx.x & 127;
            const uint32_t ga = cb + CH_G + (tid >= 24) * 16 + min(tid, 47) * 8;
            const uint2 x0 = lds64(ga), x1 = lds64(ga + 8);
            if (u < 0 && w == 0) kv[0] = 0.f;
            if (xt > 1028) kv[16] = 0.f;
            uint32_t o[17];
            #pragma unroll
            for (int s = 0; s < 17; s++) o[s] = pack2(kv[s], __shfl_up_sync(0xffffffffu, kv[s], 1));
            if (lane > 0 && lane < 31) {
                const uint32_t ta = cb + CH_T + (lane - 1) * 280;
                #pragma unroll
                for (int s2 = 0; s2 < 8; s2++) sts64(ta + 64 * w + s2 * 8, o[2 * s2], o[2 * s2 + 1]);
                stsf(ta + 256 + 4 * w, UF(o[16]));
            }
            if (tid < 48) sts128(cb + CH_B3 + tid * 16, x0.x, x0.y, x1.x, x1.y);
        }
        mbar_wait(bars + 8 * B_U, 0);
        float p[24];
        const uint2 r0 = lds64(cb + ob + 24), r3 = lds64(cb + oa);
        uint32_t r[8];
        *(uint4*)&r[0] = lds128(cb + oa + 16); *(uint4*)&r[4] = lds128(cb + ob);
        p[0] = 0.f;
        p[1] = bf_lo(r0.x); p[2] = p[1] + bf_hi(r0.x); p[3] = p[2] + bf_lo(r0.y); p[4] = p[3] + bf_hi(r0.y);
        #pragma unroll
        for (int i = 0; i < 8; i++) { p[5 + 2 * i] = p[4 + 2 * i] + bf_lo(r[i]); p[6 + 2 * i] = p[5 + 2 * i] + bf_hi(r[i]); }
        p[21] = p[20] + bf_lo(r3.x); p[22] = p[21] + bf_hi(r3.x); p[23] = p[22] + bf_lo(r3.y);
        bar_sync(2);
        #pragma unroll
        for (int i = 0; i < 8; i += 4) {
            sts64(cb + od + i * 256, pack2(p[i + 9] - p[i], p[i + 10] - p[i + 1]), pack2(p[i + 11] - p[i + 2], p[i + 12] - p[i + 3]));
            sts64(cb + od + i * 256 + 128, pack2(p[i + 16] - p[i + 9], p[i + 17] - p[i + 10]), pack2(p[i + 18] - p[i + 11], p[i + 19] - p[i + 12]));
        }
        fence_async_smem();
        mbar_arrive(bars + 8 * (B_CONV + ch));
        if (k == 0) STAMP(17);
    }
    STAMP(21);
}

__global__ void __launch_bounds__(512, 1)
fused_kernel(const __grid_constant__ Params P, const __grid_constant__ Maps M) {
    extern __shared__ __align__(1024) uint8_t smem_raw[];
    const uint32_t sb = smem_u32(smem_raw);
    const uint32_t bars = sb + OFF_BAR;
    const int warp = __shfl_sync(0xffffffffu, threadIdx.x >> 5, 0);
    const int c = blockIdx.x, tg = c / 22, fb = c - 22 * tg;
    SsmRaw raw;
    {
        const int d = min(4 * c + (warp & 3), DM - 1), o = d * 128 + (warp >> 2) * 32 + (threadIdx.x & 31);
        raw.la = ldu16(P.logA + o); raw.ai = ldu16(P.Aim + o); raw.cr = ldu16(P.Cr + o); raw.ci = ldu16(P.Ci + o);
        raw.ldt = ldu16(P.logdt + d); raw.dsk = ldu16(P.Dskip + d);
    }
    if (elect_one()) {
        if (warp == 0) { STAMP(24); GSTAMP(22); }
        asm volatile("" :: "l"(((const uint64_t*)&P)[warp < 14 ? warp : 0]));
        if (warp < 12) asm volatile("prefetch.tensormap [%0];" :: "l"(&M.x[0] + warp) : "memory");
        #pragma unroll
        for (int k = 0; k < 4; k++) {
            const int i = 16 * k + ((warp + 4) & 15);
            const uint32_t cnt = i >= B_CONV ? 128 : i == B_K ? 12 : ((0xf0ull >> i) & 1) ? 8 : ((0xff0000ull >> i) & 1) ? 2 : ((0x3e00ff00f000ull >> i) & 1) ? 4 : 1;
            asm volatile("mbarrier.init.shared::cta.b64 [%0], %1;" :: "r"(bars + 8 * i), "r"(cnt) : "memory");
        }
        asm volatile("fence.mbarrier_init.release.cluster; fence.proxy.async.shared::cta;" ::: "memory");
        if (warp == 13 || warp == 5) { const uint32_t t0 = clock(); while ((uint32_t)clock() - t0 < DLY1) ; }
        if (warp == 12 || warp == 13) {
            const uint32_t s = warp - 12;
            mbar_expect(bars + 8 * (B_FULLW + s), 16384);
            tma2d(sb + OFF_W + s * 16384, &M.wg, 64 * fb, 64 * s, bars + 8 * (B_FULLW + s));
            tma2d(sb + OFF_W + s * 16384 + 8192, &M.wu, 64 * fb, 64 * s, bars + 8 * (B_FULLW + s));
            STAMP(31);
        } else if (warp == 4 || warp == 5) {
            const uint32_t s = warp - 4;
            mbar_expect(bars + 8 * (B_FULLX + s), 168 * 128);
            tma2d(sb + OFF_X + s * XBUF, &M.x[0], 64 * s, TOKG * tg, bars + 8 * (B_FULLX + s));
        }
        if (sb & 1023) __trap();
    }
    if (warp < 4) sts128(sb + OFF_X + (warp >> 1) * XBUF + 168 * 128 + (threadIdx.x & 63) * 16, 0x3f803f80u, 0x3f803f80u, 0x3f803f80u, 0x3f803f80u);
    float dacc[2][3][4];
    #pragma unroll
    for (int i = 0; i < 24; i++) (&dacc[0][0][0])[i] = 0.f;
    if (c < 128)
        kernel_gen(sb + (warp < 8 ? (warp < 4 ? OFF_W + 32768 : OFF_X + 2 * XBUF) + (warp & 3) * 8064 : OFF_CONV + (warp & 3) * CH_STRIDE + (warp >> 2 & 1) * 8064),
                   threadIdx.x & 31, raw, dacc, P, warp);
    fence_async_smem();
    __syncthreads();
    if (c < 128 && (warp >> 2) != 2) {
        const uint32_t pa = sb + OFF_CONV + (warp & 3) * CH_STRIDE + CH_PART + min(warp >> 2, 2) * 3072 + (threadIdx.x & 31) * 16;
        #pragma unroll
        for (int i = 0; i < 6; i++) { const float* d = &dacc[0][0][0] + 4 * i; sts128(pa + i * 512, FU(d[0]), FU(d[1]), FU(d[2]), FU(d[3])); }
        __syncwarp();
        if ((threadIdx.x & 31) == 0) mbar_arrive(bars + 8 * B_K);
    }
    if (warp < 8) {
        asm volatile("setmaxnreg.inc.sync.aligned.u32 208;");
        consumer(sb, warp, P, M);
    } else if (warp < 12) {
        asm volatile("setmaxnreg.dec.sync.aligned.u32 72;");
        STAMP(32);
        aux_role(sb, warp - 8, dacc, bf_lo(raw.dsk), P.x);
    } else {
        asm volatile("setmaxnreg.dec.sync.aligned.u32 24;");
        const int tau = c >> 2, dg = c & 3;
        if (elect_one()) {
            if (warp < 15) {
                if (warp == 12) {
                    #pragma unroll 1
                    for (int st = 2; st < 8; st++) {
                        const uint32_t s = st & 3, fb_ = bars + 8 * (B_FULLW + s);
                        mbar_wait(bars + 8 * (B_EMPTYW + s), (st >> 2) ^ 1);
                        mbar_expect(fb_, 16384);
                        tma2d(sb + OFF_W + s * 16384, &M.wg, 64 * fb, 64 * st, fb_);
                        tma2d(sb + OFF_W + s * 16384 + 8192, &M.wu, 64 * fb, 64 * st, fb_);
                    }
                } else {
                    const int V = warp - 13;
                    #pragma unroll 1
                    for (int st = 2 - 2 * V; st < 8; st++) {
                        const uint32_t s = 2 * V + (st & 1);
                        mbar_wait(bars + 8 * (B_EMPTYX + s), ((st >> 1) & 1) ^ 1);
                        mbar_expect(bars + 8 * (B_FULLX + s), (168 + 8 * V) * 128);
                        tma2d(sb + OFF_X + s * XBUF, &M.x[V], 64 * st, TOKG * tg + 168 * V, bars + 8 * (B_FULLX + s));
                    }
                }
                if (c < 128 && warp < 14) {
                    if (warp == 13) {
                        mbar_wait(bars + 8 * (B_STG + 1), 0);
                        #pragma unroll 1
                        for (int o = 8 * tau; o < 8 * tau + 8; o += 7) flag_wait(P.flags, F_H + 2 * (o / 43) + ((o % 43) >= 21), 22);
                        mbar_arrive(bars + 8 * B_HF);
                        STAMP(25);
                    }
                    #pragma unroll 1
                    for (int st = 0; st < 22; st += (st < 7 || (st == 7 && warp == 12)) ? 1 : 2) {
                        const int sd = st & 7;
                        const uint32_t fb_ = bars + 8 * (B_FULLD + sd);
                        if (st >= 8) mbar_wait(bars + 8 * (B_EMPTYD + sd), ((st >> 3) & 1) ^ 1);
                        else if (warp == 12 || st >= 6) mbar_wait(bars + 8 * (uint32_t)((0x373623070d060504ull >> (8 * st)) & 0xff), st < 5);
                        if (st >= 10 && st < 21) STAMP2(31 + st);
                        if (st >= 8 || warp == 13) {
                            mbar_expect(fb_, 8192);
                            asm volatile("cp.async.bulk.tensor.5d.shared::cluster.global.mbarrier::complete_tx::bytes [%0], [%1, {%3, %3, %3, %4, %5}], [%2];"
                                :: "r"(sb + h_slot(sd)), "l"(&M.hld), "r"(fb_), "r"(0), "r"(2 * tau), "r"(8 * st) : "memory");
                        }
                        if (st >= 8 || warp == 12) {
                            const uint32_t da = sb + wd_slot(sd);
                            mbar_expect(fb_, 16384);
                            tma2d(da, &M.wd, 128 * dg, 64 * st, fb_);
                            tma2d(da + 8192, &M.wd, 128 * dg + 64, 64 * st, fb_);
                        }
                    }
                } else if (c < 128) {
                    mbar_wait(bars + 8 * B_SST, 0);
                    flag_wait(P.flags, F_S + dg, 64);
                    STAMP(26);
                    mbar_wait(bars + 8 * B_CH0, 0);
                    mbar_expect(bars + 8 * B_XO, 32768);
                    tma2d(sb + OFF_CONV, &M.xo, 128 * dg, 64 * tau, bars + 8 * B_XO);
                    tma2d(sb + OFF_CONV + 8192, &M.xo, 128 * dg + 64, 64 * tau, bars + 8 * B_XO);
                    asm volatile("cp.async.bulk.tensor.5d.shared::cluster.global.mbarrier::complete_tx::bytes [%0], [%1, {%3, %3, %3, %4, %5}], [%2];"
                        :: "r"(sb + wd_slot(6)), "l"(&M.sld), "r"(bars + 8 * B_XO), "r"(0), "r"(8 * dg), "r"(2 * tau) : "memory");
                    mbar_wait(bars + 8 * B_HF, 0);
                    exit_count(P.flags);
                }
            } else {
                mbar_wait(bars + 8 * B_LN, 0);
                STAMP2(0);
                if (c < 128) {
                    #pragma unroll 1
                    for (int i = 0; i < 4; i++)
                        asm volatile("cp.async.bulk.tensor.2d.global.shared::cta.bulk_group [%0, {%2, %3}], [%1];"
                            :: "l"(&M.xt), "r"(sb + OFF_CONV + i * CH_STRIDE + CH_LNT), "r"((c & 1) * 1024 + (126 - (c & ~1)) * 8), "r"(128 * i) : "memory");
                    #pragma unroll 1
                    for (int i = 0; i < 2; i++) bulk_store(P.st + 16 * (c & ~1) + 8 * (c & 1) + 16 - 16 * i, sb + OFF_CSUM + 64 * i, 64);
                    asm volatile("cp.async.bulk.prefetch.L2.global [%0], %1;" :: "l"(P.Wd + c * (FF * DM / 128)), "r"(FF * DM / 64) : "memory");
                }
                asm volatile("cp.async.bulk.commit_group; cp.async.bulk.wait_group.read 0;" ::: "memory");
                mbar_arrive(bars + 8 * B_LNS);
                STAMP2(1);
                flag_signal(P.flags, F_A);
                STAMP2(2);
                flag_wait(P.flags, F_A, NCTA);
                STAMP(20);
                mbar_expect(bars + 8 * B_STATS, TOKG * 8);
                bulk_load(sb + OFF_ST, P.st + TOKG * tg, TOKG * 8, bars + 8 * B_STATS);
                if (c < 128) {
                    mbar_expect(bars + 8 * B_U, 8 * 2048);
                    #pragma unroll 1
                    for (int i = 0; i < 8; i++)
                        bulk_load(sb + OFF_CONV + (i >> 1) * CH_STRIDE + CH_U + (i & 1) * UPLANE, P.xnT + 4 * c * 256 + i * 128, 2048, bars + 8 * B_U);
                } else exit_count(P.flags);
                #pragma unroll 1
                for (int V = 0; V < 2; V++) {
                    mbar_wait(bars + 8 * (B_EPI + V), 0);
                    STAMP2(3 + 2 * V);
                    asm volatile("cp.async.bulk.tensor.3d.global.shared::cta.bulk_group [%0, {%2, %3, %4}], [%1];"
                        :: "l"(&M.hst[V]), "r"(sb + OFF_X + V * 2 * XBUF), "r"(0), "r"(43 * tg + 21 * V), "r"(8 * fb) : "memory");
                    flag_signal(P.flags, F_H + 2 * tg + V);
                    mbar_arrive(bars + 8 * (B_STG + V));
                    STAMP2(4 + 2 * V);
                }
                if (c < 128) {
                    #pragma unroll 1
                    for (int V = 0; V < 2; V++) {
                        mbar_wait(bars + 8 * (B_SIG + V), 0);
                        STAMP2(7 + 2 * V);
                        bulk_store(P.S + (2 * c + V) * 1024, sb + OFF_CONV + V * OFF_SST, 8192);
                        flag_signal(P.flags, F_S + (c >> 5));
                        STAMP2(8 + 2 * V);
                    }
                    mbar_arrive(bars + 8 * B_SST);
                }
            }
        }
    }
    asm volatile("nanosleep.u32 0;");
}

typedef CUresult (*EncodeFn)(CUtensorMap*, CUtensorMapDataType, cuuint32_t, void*, const cuuint64_t*, const cuuint64_t*, const cuuint32_t*,
                             const cuuint32_t*, CUtensorMapInterleave, CUtensorMapSwizzle, CUtensorMapL2promotion, CUtensorMapFloatOOBfill);

void make_map(EncodeFn enc, CUtensorMap* m, const void* ptr, int rank, const cuuint64_t* dims, const cuuint64_t* strides, const cuuint32_t* box, bool swz, bool wide = false) {
    const cuuint32_t es[5] = {1, 1, 1, 1, 1};
    enc(m, CU_TENSOR_MAP_DATA_TYPE_BFLOAT16, rank, (void*)ptr, dims, strides, box, es, CU_TENSOR_MAP_INTERLEAVE_NONE,
        swz ? CU_TENSOR_MAP_SWIZZLE_128B : CU_TENSOR_MAP_SWIZZLE_NONE, wide ? CU_TENSOR_MAP_L2_PROMOTION_L2_256B : CU_TENSOR_MAP_L2_PROMOTION_L2_128B, CU_TENSOR_MAP_FLOAT_OOB_FILL_NONE);
}
void make_map2(EncodeFn enc, CUtensorMap* m, const void* ptr, cuuint64_t inner, cuuint64_t outer, cuuint32_t rows) {
    const cuuint64_t dims[2] = {inner, outer}, strides[1] = {inner * 2};
    const cuuint32_t box[2] = {64, rows};
    make_map(enc, m, ptr, 2, dims, strides, box, true, rows > 64);
}

}

extern "C" void kernel_launch(void* const* d_in, const int* in_sizes, int n_in, void* d_out, int out_size) {
    (void)in_sizes; (void)n_in; (void)out_size;
    static EncodeFn enc = nullptr;
    static void *hptr, *p_xnT, *p_st, *p_S, *p_flags;
    if (!enc) {
        cudaDriverEntryPointQueryResult qr;
        cudaGetDriverEntryPoint("cuTensorMapEncodeTiled", (void**)&enc, cudaEnableDefault, &qr);
        cudaFuncSetAttribute(fused_kernel, cudaFuncAttributeMaxDynamicSharedMemorySize, SMEM_BYTES);
        cudaGetSymbolAddress(&hptr, g_H); cudaGetSymbolAddress(&p_xnT, g_xnT); cudaGetSymbolAddress(&p_st, g_st);
        cudaGetSymbolAddress(&p_S, g_S); cudaGetSymbolAddress(&p_flags, g_flags);
    }
    Params P;
    P.x = (const __nv_bfloat16*)d_in[0]; P.logA = (const __nv_bfloat16*)d_in[1]; P.Aim = (const __nv_bfloat16*)d_in[2];
    P.Cr = (const __nv_bfloat16*)d_in[3]; P.Ci = (const __nv_bfloat16*)d_in[4]; P.logdt = (const __nv_bfloat16*)d_in[5];
    P.Dskip = (const __nv_bfloat16*)d_in[6];
    P.Wg = (const __nv_bfloat16*)d_in[8]; P.Wu = (const __nv_bfloat16*)d_in[9]; P.Wd = (const __nv_bfloat16*)d_in[10]; P.xnT = (uint4*)p_xnT; P.st = (float2*)p_st; P.S = (uint2*)p_S; P.flags = (unsigned*)p_flags;
    Maps M;
    make_map2(enc, &M.x[0], d_in[0], DM, SEQ, 168); make_map2(enc, &M.x[1], d_in[0], DM, SEQ, 176);
    make_map2(enc, &M.xo, d_in[0], DM, SEQ, 64);    make_map2(enc, &M.out, d_out, DM, SEQ, 64);
    make_map2(enc, &M.wg, d_in[8], FF, DM, 64);     make_map2(enc, &M.wu, d_in[9], FF, DM, 64);
    make_map2(enc, &M.wd, d_in[10], DM, FF, 64);
    for (int v = 0; v < 2; v++) {
        const cuuint64_t dims[3] = {64, 256, 172}, strides[2] = {128, 32768};
        const cuuint32_t box[3] = {64, (cuuint32_t)(21 + v), 8};
        make_map(enc, &M.hst[v], hptr, 3, dims, strides, box, false);
    }
    {
        const cuuint64_t dims[2] = {2048, 512}, strides[1] = {4096};
        const cuuint32_t box[2] = {16, 128};
        make_map(enc, &M.xt, p_xnT, 2, dims, strides, box, false);
    }
    {
        const cuuint64_t dims[5] = {64, 2, 4, 32, 64}, strides[4] = {4 * 8192, 8192, 8 * 8192, 128};
        const cuuint32_t box[5] = {64, 2, 4, 8, 2};
        make_map(enc, &M.sld, p_S, 5, dims, strides, box, true);
    }
    {
        const cuuint64_t dims[5] = {64, 2, 2, 64, 172}, strides[4] = {256, 128, 512, 32768};
        const cuuint32_t box[5] = {64, 2, 2, 2, 8};
        make_map(enc, &M.hld, hptr, 5, dims, strides, box, false);
    }
    fused_kernel<<<NCTA, 512, SMEM_BYTES>>>(P, M);
}
```

```cpp
#include <cuda_runtime.h>
#include <cuda_bf16.h>
#include <cuda.h>
#include <stdint.h>

#define PROF 0

namespace {

constexpr int SEQ = 2048, DM = 512, FF = 1376;
constexpr int NCTA = 132;
#define GOST 1
#define SIGK 3
#define DLY1 300
constexpr int RUNROLL = 2;
constexpr int TOKG = 344;

constexpr uint32_t OFF_W = 0;
constexpr uint32_t XBUF = 22528;
constexpr uint32_t OFF_X = 65536;
constexpr uint32_t OFF_CONV = 155648;
constexpr uint32_t CH_STRIDE = 17536;
constexpr uint32_t CH_T = 0;
constexpr uint32_t CH_A3 = 8448;
constexpr uint32_t CH_B3 = 12544;
constexpr uint32_t CH_U = 13312;
constexpr uint32_t CH_G = CH_A3 + 2064;
constexpr uint32_t UPLANE = 2112;
constexpr uint32_t CH_LN = 0, CH_PART = 4224, CH_LNT = 13440;
constexpr uint32_t OFF_SST = 60416;
constexpr uint32_t OFF_ST = 225792;
constexpr uint32_t OFF_CSUM = 228544;
constexpr uint32_t OFF_BAR = 229056;
constexpr uint32_t SMEM_BYTES = 229568;

enum {
    B_FULLW = 0, B_EMPTYW = 4, B_FULLX = 8, B_EMPTYX = 12, B_FULLD = 16, B_EMPTYD = 24,
    B_U = 32, B_XO = 33, B_S = 34, B_STG = 35, B_HF = 37, B_STATS = 38, B_LNS = 39, B_SST = 40,
    B_LNX = 41, B_CH0 = 42, B_TURN = 43, B_K = 45,
    B_CONV = 46, B_LN = 50, B_CS = 51, B_EPI = 52, B_SIG = 54,
    B_COUNT = 56
};
enum { F_A = 0, F_H = 1, F_S = 13, F_EXIT = 17, F_COUNT = 18 };

__device__ uint4 g_xnT[DM * 256];
__device__ float2 g_st[6 * TOKG];
__device__ uint4 g_H[172 * 256 * 8];
__device__ uint2 g_S[256 * 1024];
__device__ unsigned g_flags[F_COUNT * 32];
#define STAMP(i) do {} while (0)
#define GSTAMP(i) do {} while (0)
#define STAMP2(i) do {} while (0)

__device__ __forceinline__ uint32_t smem_u32(const void* p) { return (uint32_t)__cvta_generic_to_shared(p); }
__device__ __forceinline__ void mbar_expect(uint32_t bar, uint32_t bytes) { asm volatile("mbarrier.arrive.expect_tx.shared::cta.b64 _, [%0], %1;" :: "r"(bar), "r"(bytes) : "memory"); }
__device__ __forceinline__ void mbar_arrive(uint32_t bar) { asm volatile("mbarrier.arrive.shared::cta.b64 _, [%0];" :: "r"(bar) : "memory"); }
__device__ __forceinline__ void mbar_wait(uint32_t bar, uint32_t parity) {
    asm volatile("{.reg .pred p; .reg .u32 n; mov.u32 n, 0x20000;\n"
                 "LW: mbarrier.try_wait.parity.shared::cta.b64 p, [%0], %1;\n"
                 "sub.u32 n, n, 1; setp.eq.or.u32 p, n, 0, p; @!p bra LW;}" :: "r"(bar), "r"(parity) : "memory");
}
__device__ __forceinline__ void mbar_arrive_if(uint32_t bar, uint32_t pred) {
    asm volatile("{.reg .pred p; setp.ne.u32 p, %1, 0; @p mbarrier.arrive.shared::cta.b64 _, [%0];}" :: "r"(bar), "r"(pred) : "memory");
}
__device__ __forceinline__ bool elect_one() { uint32_t p; asm volatile("{.reg .pred P; elect.sync _|P, 0xffffffff; selp.u32 %0, 1, 0, P;}" : "=r"(p)); return p; }
__device__ __forceinline__ void tma2d(uint32_t dst, const CUtensorMap* m, int c0, int c1, uint32_t bar) {
    asm volatile("cp.async.bulk.tensor.2d.shared::cluster.global.mbarrier::complete_tx::bytes [%0], [%1, {%3, %4}], [%2];"
        :: "r"(dst), "l"(m), "r"(bar), "r"(c0), "r"(c1) : "memory");
}
__device__ __forceinline__ void bulk_load(uint32_t dst, const void* src, uint32_t bytes, uint32_t bar) {
    asm volatile("cp.async.bulk.shared::cluster.global.mbarrier::complete_tx::bytes [%0], [%1], %2, [%3];" :: "r"(dst), "l"(src), "r"(bytes), "r"(bar) : "memory");
}
__device__ __forceinline__ void bulk_store(void* dst, uint32_t src, uint32_t bytes) {
    asm volatile("cp.async.bulk.global.shared::cta.bulk_group [%0], [%1], %2;" :: "l"(dst), "r"(src), "r"(bytes) : "memory");
}
__device__ __forceinline__ void fence_async_smem() { asm volatile("fence.proxy.async.shared::cta;" ::: "memory"); }
__device__ __forceinline__ void flag_wait(unsigned* g_flags, int f, unsigned target) {
    asm volatile("{.reg .pred p; .reg .u32 n, v; mov.u32 n, 0x40000;\n"
                 "LF: ld.acquire.gpu.global.u32 v, [%0]; setp.ge.u32 p, v, %1; @p bra LD;\n"
                 "sub.u32 n, n, 1; setp.ne.u32 p, n, 0; @p bra LF; trap;\nLD: }"
                 :: "l"(g_flags + f * 32), "r"(target) : "memory");
}
__device__ __forceinline__ void flag_signal(unsigned* g_flags, int f) {
    asm volatile("cp.async.bulk.commit_group; cp.async.bulk.wait_group 0; red.relaxed.gpu.global.add.u32 [%0], 1;" :: "l"(g_flags + f * 32) : "memory");
}
__device__ __forceinline__ void exit_count(unsigned* g_flags) {
    if (atomicAdd(g_flags + F_EXIT * 32, 1u) == NCTA - 1) {
        #pragma unroll 1
        for (int i = 0; i < F_COUNT; i++) g_flags[i * 32] = 0;
    }
}
__device__ __forceinline__ void bar_sync(int id) { asm volatile("bar.sync %0, 128;" :: "r"(id) : "memory"); }
__device__ __forceinline__ uint64_t mkdesc(uint32_t addr, uint32_t lbo, uint32_t sbo, uint32_t swz) {
    return (uint64_t)((addr >> 4) | ((lbo >> 4) << 16)) | ((uint64_t)((sbo >> 4) | (swz << 30)) << 32);
}
#define WG_FENCE() asm volatile("wgmma.fence.sync.aligned;" ::: "memory")
#define WG_COMMIT() asm volatile("wgmma.commit_group.sync.aligned;" ::: "memory")
#define WG_WAIT(n) asm volatile("wgmma.wait_group.sync.aligned " #n ";" ::: "memory")
template <int N> __device__ __forceinline__ void fence_acc(float (&d)[N]) {
    #pragma unroll
    for (int i = 0; i < N; i++) asm volatile("" : "+f"(d[i]) :: "memory");
}
template <int N> __device__ __forceinline__ void define_acc(float (&d)[N]) {
    #pragma unroll
    for (int i = 0; i < N; i++) asm volatile("" : "=f"(d[i]));
}
__device__ __forceinline__ uint32_t pack2(float lo, float hi) { uint32_t r; asm("cvt.rn.bf16x2.f32 %0, %1, %2;" : "=r"(r) : "f"(hi), "f"(lo)); return r; }
__device__ __forceinline__ float bf_lo(uint32_t v) { return __uint_as_float(v << 16); }
__device__ __forceinline__ float bf_hi(uint32_t v) { return __uint_as_float(v & 0xffff0000u); }
__device__ __forceinline__ float bf_round(float v) { return bf_hi(pack2(0.f, v)); }
__device__ __forceinline__ float tanh_fast(float v) { float r; asm("tanh.approx.f32 %0, %1;" : "=f"(r) : "f"(v)); return r; }
__device__ __forceinline__ float ex2(float v) { float r; asm("ex2.approx.ftz.f32 %0, %1;" : "=f"(r) : "f"(v)); return r; }
__device__ __forceinline__ uint4 lds128(uint32_t a) { uint4 v; asm volatile("ld.shared.v4.b32 {%0,%1,%2,%3}, [%4];" : "=r"(v.x), "=r"(v.y), "=r"(v.z), "=r"(v.w) : "r"(a)); return v; }
__device__ __forceinline__ uint2 lds64(uint32_t a) { uint2 v; asm volatile("ld.shared.v2.b32 {%0,%1}, [%2];" : "=r"(v.x), "=r"(v.y) : "r"(a)); return v; }
__device__ __forceinline__ float ldsf(uint32_t a) { float v; asm volatile("ld.shared.f32 %0, [%1];" : "=f"(v) : "r"(a)); return v; }
__device__ __forceinline__ void sts128(uint32_t a, uint32_t x, uint32_t y, uint32_t z, uint32_t w) { asm volatile("st.shared.v4.b32 [%0], {%1,%2,%3,%4};" :: "r"(a), "r"(x), "r"(y), "r"(z), "r"(w) : "memory"); }
__device__ __forceinline__ void sts64(uint32_t a, uint32_t x, uint32_t y) { asm volatile("st.shared.v2.b32 [%0], {%1,%2};" :: "r"(a), "r"(x), "r"(y) : "memory"); }
__device__ __forceinline__ void stsf(uint32_t a, float x) { asm volatile("st.shared.f32 [%0], %1;" :: "r"(a), "f"(x) : "memory"); }
__device__ __forceinline__ void sts16(uint32_t a, uint32_t x) { asm volatile("st.shared.b16 [%0], %1;" :: "r"(a), "h"((unsigned short)x) : "memory"); }
__device__ __forceinline__ void stsm4(uint32_t a, uint32_t r0, uint32_t r1, uint32_t r2, uint32_t r3) {
    asm volatile("stmatrix.sync.aligned.m8n8.x4.shared.b16 [%0], {%1,%2,%3,%4};" :: "r"(a), "r"(r0), "r"(r1), "r"(r2), "r"(r3) : "memory");
}
__device__ __forceinline__ void ldsm4(uint32_t (&r)[4], uint32_t a) {
    asm volatile("ldmatrix.sync.aligned.m8n8.x4.shared.b16 {%0,%1,%2,%3}, [%4];" : "=r"(r[0]), "=r"(r[1]), "=r"(r[2]), "=r"(r[3]) : "r"(a) : "memory");
}
#define FU(x) __float_as_uint(x)
#define UF(x) __uint_as_float(x)
__device__ __forceinline__ uint32_t wd_slot(int s) { return (uint32_t)((0xbba8403056201000ull >> (8 * s)) & 0xff) << 10; }
__device__ __forceinline__ uint32_t h_slot(int s) { return (uint32_t)((0xcba0908880787068ull >> (8 * s)) & 0xff) << 10; }

template<int N> __device__ __forceinline__ void wg_rs(float (&d)[64], uint32_t a0, uint32_t a1, uint32_t a2, uint32_t a3, uint64_t db);
template<> __device__ __forceinline__ void wg_rs<128>(float (&d)[64], uint32_t a0, uint32_t a1, uint32_t a2, uint32_t a3, uint64_t db) {
  asm volatile("{.reg .pred p; setp.ne.b32 p, 1, 0; wgmma.mma_async.sync.aligned.m64n128k16.f32.bf16.bf16 {%0,%1,%2,%3,%4,%5,%6,%7,%8,%9,%10,%11,%12,%13,%14,%15,%16,%17,%18,%19,%20,%21,%22,%23,%24,%25,%26,%27,%28,%29,%30,%31,%32,%33,%34,%35,%36,%37,%38,%39,%40,%41,%42,%43,%44,%45,%46,%47,%48,%49,%50,%51,%52,%53,%54,%55,%56,%57,%58,%59,%60,%61,%62,%63}, {%64,%65,%66,%67}, %68, p, 1, 1, 0;}"
    : "+f"(d[0]),"+f"(d[1]),"+f"(d[2]),"+f"(d[3]),"+f"(d[4]),"+f"(d[5]),"+f"(d[6]),"+f"(d[7]),"+f"(d[8]),"+f"(d[9]),"+f"(d[10]),"+f"(d[11]),"+f"(d[12]),"+f"(d[13]),"+f"(d[14]),"+f"(d[15]),"+f"(d[16]),"+f"(d[17]),"+f"(d[18]),"+f"(d[19]),"+f"(d[20]),"+f"(d[21]),"+f"(d[22]),"+f"(d[23]),"+f"(d[24]),"+f"(d[25]),"+f"(d[26]),"+f"(d[27]),"+f"(d[28]),"+f"(d[29]),"+f"(d[30]),"+f"(d[31]),"+f"(d[32]),"+f"(d[33]),"+f"(d[34]),"+f"(d[35]),"+f"(d[36]),"+f"(d[37]),"+f"(d[38]),"+f"(d[39]),"+f"(d[40]),"+f"(d[41]),"+f"(d[42]),"+f"(d[43]),"+f"(d[44]),"+f"(d[45]),"+f"(d[46]),"+f"(d[47]),"+f"(d[48]),"+f"(d[49]),"+f"(d[50]),"+f"(d[51]),"+f"(d[52]),"+f"(d[53]),"+f"(d[54]),"+f"(d[55]),"+f"(d[56]),"+f"(d[57]),"+f"(d[58]),"+f"(d[59]),"+f"(d[60]),"+f"(d[61]),"+f"(d[62]),"+f"(d[63]) : "r"(a0), "r"(a1), "r"(a2), "r"(a3), "l"(db));
}
template<> __device__ __forceinline__ void wg_rs<120>(float (&d)[64], uint32_t a0, uint32_t a1, uint32_t a2, uint32_t a3, uint64_t db) {
  asm volatile("{.reg .pred p; setp.ne.b32 p, 1, 0; wgmma.mma_async.sync.aligned.m64n120k16.f32.bf16.bf16 {%0,%1,%2,%3,%4,%5,%6,%7,%8,%9,%10,%11,%12,%13,%14,%15,%16,%17,%18,%19,%20,%21,%22,%23,%24,%25,%26,%27,%28,%29,%30,%31,%32,%33,%34,%35,%36,%37,%38,%39,%40,%41,%42,%43,%44,%45,%46,%47,%48,%49,%50,%51,%52,%53,%54,%55,%56,%57,%58,%59}, {%60,%61,%62,%63}, %64, p, 1, 1, 0;}"
    : "+f"(d[0]),"+f"(d[1]),"+f"(d[2]),"+f"(d[3]),"+f"(d[4]),"+f"(d[5]),"+f"(d[6]),"+f"(d[7]),"+f"(d[8]),"+f"(d[9]),"+f"(d[10]),"+f"(d[11]),"+f"(d[12]),"+f"(d[13]),"+f"(d[14]),"+f"(d[15]),"+f"(d[16]),"+f"(d[17]),"+f"(d[18]),"+f"(d[19]),"+f"(d[20]),"+f"(d[21]),"+f"(d[22]),"+f"(d[23]),"+f"(d[24]),"+f"(d[25]),"+f"(d[26]),"+f"(d[27]),"+f"(d[28]),"+f"(d[29]),"+f"(d[30]),"+f"(d[31]),"+f"(d[32]),"+f"(d[33]),"+f"(d[34]),"+f"(d[35]),"+f"(d[36]),"+f"(d[37]),"+f"(d[38]),"+f"(d[39]),"+f"(d[40]),"+f"(d[41]),"+f"(d[42]),"+f"(d[43]),"+f"(d[44]),"+f"(d[45]),"+f"(d[46]),"+f"(d[47]),"+f"(d[48]),"+f"(d[49]),"+f"(d[50]),"+f"(d[51]),"+f"(d[52]),"+f"(d[53]),"+f"(d[54]),"+f"(d[55]),"+f"(d[56]),"+f"(d[57]),"+f"(d[58]),"+f"(d[59]) : "r"(a0), "r"(a1), "r"(a2), "r"(a3), "l"(db));
}
template<> __device__ __forceinline__ void wg_rs<112>(float (&d)[64], uint32_t a0, uint32_t a1, uint32_t a2, uint32_t a3, uint64_t db) {
  asm volatile("{.reg .pred p; setp.ne.b32 p, 1, 0; wgmma.mma_async.sync.aligned.m64n112k16.f32.bf16.bf16 {%0,%1,%2,%3,%4,%5,%6,%7,%8,%9,%10,%11,%12,%13,%14,%15,%16,%17,%18,%19,%20,%21,%22,%23,%24,%25,%26,%27,%28,%29,%30,%31,%32,%33,%34,%35,%36,%37,%38,%39,%40,%41,%42,%43,%44,%45,%46,%47,%48,%49,%50,%51,%52,%53,%54,%55}, {%56,%57,%58,%59}, %60, p, 1, 1, 0;}"
    : "+f"(d[0]),"+f"(d[1]),"+f"(d[2]),"+f"(d[3]),"+f"(d[4]),"+f"(d[5]),"+f"(d[6]),"+f"(d[7]),"+f"(d[8]),"+f"(d[9]),"+f"(d[10]),"+f"(d[11]),"+f"(d[12]),"+f"(d[13]),"+f"(d[14]),"+f"(d[15]),"+f"(d[16]),"+f"(d[17]),"+f"(d[18]),"+f"(d[19]),"+f"(d[20]),"+f"(d[21]),"+f"(d[22]),"+f"(d[23]),"+f"(d[24]),"+f"(d[25]),"+f"(d[26]),"+f"(d[27]),"+f"(d[28]),"+f"(d[29]),"+f"(d[30]),"+f"(d[31]),"+f"(d[32]),"+f"(d[33]),"+f"(d[34]),"+f"(d[35]),"+f"(d[36]),"+f"(d[37]),"+f"(d[38]),"+f"(d[39]),"+f"(d[40]),"+f"(d[41]),"+f"(d[42]),"+f"(d[43]),"+f"(d[44]),"+f"(d[45]),"+f"(d[46]),"+f"(d[47]),"+f"(d[48]),"+f"(d[49]),"+f"(d[50]),"+f"(d[51]),"+f"(d[52]),"+f"(d[53]),"+f"(d[54]),"+f"(d[55]) : "r"(a0), "r"(a1), "r"(a2), "r"(a3), "l"(db));
}
template<> __device__ __forceinline__ void wg_rs<104>(float (&d)[64], uint32_t a0, uint32_t a1, uint32_t a2, uint32_t a3, uint64_t db) {
  asm volatile("{.reg .pred p; setp.ne.b32 p, 1, 0; wgmma.mma_async.sync.aligned.m64n104k16.f32.bf16.bf16 {%0,%1,%2,%3,%4,%5,%6,%7,%8,%9,%10,%11,%12,%13,%14,%15,%16,%17,%18,%19,%20,%21,%22,%23,%24,%25,%26,%27,%28,%29,%30,%31,%32,%33,%34,%35,%36,%37,%38,%39,%40,%41,%42,%43,%44,%45,%46,%47,%48,%49,%50,%51}, {%52,%53,%54,%55}, %56, p, 1, 1, 0;}"
    : "+f"(d[0]),"+f"(d[1]),"+f"(d[2]),"+f"(d[3]),"+f"(d[4]),"+f"(d[5]),"+f"(d[6]),"+f"(d[7]),"+f"(d[8]),"+f"(d[9]),"+f"(d[10]),"+f"(d[11]),"+f"(d[12]),"+f"(d[13]),"+f"(d[14]),"+f"(d[15]),"+f"(d[16]),"+f"(d[17]),"+f"(d[18]),"+f"(d[19]),"+f"(d[20]),"+f"(d[21]),"+f"(d[22]),"+f"(d[23]),"+f"(d[24]),"+f"(d[25]),"+f"(d[26]),"+f"(d[27]),"+f"(d[28]),"+f"(d[29]),"+f"(d[30]),"+f"(d[31]),"+f"(d[32]),"+f"(d[33]),"+f"(d[34]),"+f"(d[35]),"+f"(d[36]),"+f"(d[37]),"+f"(d[38]),"+f"(d[39]),"+f"(d[40]),"+f"(d[41]),"+f"(d[42]),"+f"(d[43]),"+f"(d[44]),"+f"(d[45]),"+f"(d[46]),"+f"(d[47]),"+f"(d[48]),"+f"(d[49]),"+f"(d[50]),"+f"(d[51]) : "r"(a0), "r"(a1), "r"(a2), "r"(a3), "l"(db));
}
template<> __device__ __forceinline__ void wg_rs<96>(float (&d)[64], uint32_t a0, uint32_t a1, uint32_t a2, uint32_t a3, uint64_t db) {
  asm volatile("{.reg .pred p; setp.ne.b32 p, 1, 0; wgmma.mma_async.sync.aligned.m64n96k16.f32.bf16.bf16 {%0,%1,%2,%3,%4,%5,%6,%7,%8,%9,%10,%11,%12,%13,%14,%15,%16,%17,%18,%19,%20,%21,%22,%23,%24,%25,%26,%27,%28,%29,%30,%31,%32,%33,%34,%35,%36,%37,%38,%39,%40,%41,%42,%43,%44,%45,%46,%47}, {%48,%49,%50,%51}, %52, p, 1, 1, 0;}"
    : "+f"(d[0]),"+f"(d[1]),"+f"(d[2]),"+f"(d[3]),"+f"(d[4]),"+f"(d[5]),"+f"(d[6]),"+f"(d[7]),"+f"(d[8]),"+f"(d[9]),"+f"(d[10]),"+f"(d[11]),"+f"(d[12]),"+f"(d[13]),"+f"(d[14]),"+f"(d[15]),"+f"(d[16]),"+f"(d[17]),"+f"(d[18]),"+f"(d[19]),"+f"(d[20]),"+f"(d[21]),"+f"(d[22]),"+f"(d[23]),"+f"(d[24]),"+f"(d[25]),"+f"(d[26]),"+f"(d[27]),"+f"(d[28]),"+f"(d[29]),"+f"(d[30]),"+f"(d[31]),"+f"(d[32]),"+f"(d[33]),"+f"(d[34]),"+f"(d[35]),"+f"(d[36]),"+f"(d[37]),"+f"(d[38]),"+f"(d[39]),"+f"(d[40]),"+f"(d[41]),"+f"(d[42]),"+f"(d[43]),"+f"(d[44]),"+f"(d[45]),"+f"(d[46]),"+f"(d[47]) : "r"(a0), "r"(a1), "r"(a2), "r"(a3), "l"(db));
}
template<> __device__ __forceinline__ void wg_rs<88>(float (&d)[64], uint32_t a0, uint32_t a1, uint32_t a2, uint32_t a3, uint64_t db) {
  asm volatile("{.reg .pred p; setp.ne.b32 p, 1, 0; wgmma.mma_async.sync.aligned.m64n88k16.f32.bf16.bf16 {%0,%1,%2,%3,%4,%5,%6,%7,%8,%9,%10,%11,%12,%13,%14,%15,%16,%17,%18,%19,%20,%21,%22,%23,%24,%25,%26,%27,%28,%29,%30,%31,%32,%33,%34,%35,%36,%37,%38,%39,%40,%41,%42,%43}, {%44,%45,%46,%47}, %48, p, 1, 1, 0;}"
    : "+f"(d[0]),"+f"(d[1]),"+f"(d[2]),"+f"(d[3]),"+f"(d[4]),"+f"(d[5]),"+f"(d[6]),"+f"(d[7]),"+f"(d[8]),"+f"(d[9]),"+f"(d[10]),"+f"(d[11]),"+f"(d[12]),"+f"(d[13]),"+f"(d[14]),"+f"(d[15]),"+f"(d[16]),"+f"(d[17]),"+f"(d[18]),"+f"(d[19]),"+f"(d[20]),"+f"(d[21]),"+f"(d[22]),"+f"(d[23]),"+f"(d[24]),"+f"(d[25]),"+f"(d[26]),"+f"(d[27]),"+f"(d[28]),"+f"(d[29]),"+f"(d[30]),"+f"(d[31]),"+f"(d[32]),"+f"(d[33]),"+f"(d[34]),"+f"(d[35]),"+f"(d[36]),"+f"(d[37]),"+f"(d[38]),"+f"(d[39]),"+f"(d[40]),"+f"(d[41]),"+f"(d[42]),"+f"(d[43]) : "r"(a0), "r"(a1), "r"(a2), "r"(a3), "l"(db));
}
template<> __device__ __forceinline__ void wg_rs<80>(float (&d)[64], uint32_t a0, uint32_t a1, uint32_t a2, uint32_t a3, uint64_t db) {
  asm volatile("{.reg .pred p; setp.ne.b32 p, 1, 0; wgmma.mma_async.sync.aligned.m64n80k16.f32.bf16.bf16 {%0,%1,%2,%3,%4,%5,%6,%7,%8,%9,%10,%11,%12,%13,%14,%15,%16,%17,%18,%19,%20,%21,%22,%23,%24,%25,%26,%27,%28,%29,%30,%31,%32,%33,%34,%35,%36,%37,%38,%39}, {%40,%41,%42,%43}, %44, p, 1, 1, 0;}"
    : "+f"(d[0]),"+f"(d[1]),"+f"(d[2]),"+f"(d[3]),"+f"(d[4]),"+f"(d[5]),"+f"(d[6]),"+f"(d[7]),"+f"(d[8]),"+f"(d[9]),"+f"(d[10]),"+f"(d[11]),"+f"(d[12]),"+f"(d[13]),"+f"(d[14]),"+f"(d[15]),"+f"(d[16]),"+f"(d[17]),"+f"(d[18]),"+f"(d[19]),"+f"(d[20]),"+f"(d[21]),"+f"(d[22]),"+f"(d[23]),"+f"(d[24]),"+f"(d[25]),"+f"(d[26]),"+f"(d[27]),"+f"(d[28]),"+f"(d[29]),"+f"(d[30]),"+f"(d[31]),"+f"(d[32]),"+f"(d[33]),"+f"(d[34]),"+f"(d[35]),"+f"(d[36]),"+f"(d[37]),"+f"(d[38]),"+f"(d[39]) : "r"(a0), "r"(a1), "r"(a2), "r"(a3), "l"(db));
}
template<> __device__ __forceinline__ void wg_rs<72>(float (&d)[64], uint32_t a0, uint32_t a1, uint32_t a2, uint32_t a3, uint64_t db) {
  asm volatile("{.reg .pred p; setp.ne.b32 p, 1, 0; wgmma.mma_async.sync.aligned.m64n72k16.f32.bf16.bf16 {%0,%1,%2,%3,%4,%5,%6,%7,%8,%9,%10,%11,%12,%13,%14,%15,%16,%17,%18,%19,%20,%21,%22,%23,%24,%25,%26,%27,%28,%29,%30,%31,%32,%33,%34,%35}, {%36,%37,%38,%39}, %40, p, 1, 1, 0;}"
    : "+f"(d[0]),"+f"(d[1]),"+f"(d[2]),"+f"(d[3]),"+f"(d[4]),"+f"(d[5]),"+f"(d[6]),"+f"(d[7]),"+f"(d[8]),"+f"(d[9]),"+f"(d[10]),"+f"(d[11]),"+f"(d[12]),"+f"(d[13]),"+f"(d[14]),"+f"(d[15]),"+f"(d[16]),"+f"(d[17]),"+f"(d[18]),"+f"(d[19]),"+f"(d[20]),"+f"(d[21]),"+f"(d[22]),"+f"(d[23]),"+f"(d[24]),"+f"(d[25]),"+f"(d[26]),"+f"(d[27]),"+f"(d[28]),"+f"(d[29]),"+f"(d[30]),"+f"(d[31]),"+f"(d[32]),"+f"(d[33]),"+f"(d[34]),"+f"(d[35]) : "r"(a0), "r"(a1), "r"(a2), "r"(a3), "l"(db));
}
template<> __device__ __forceinline__ void wg_rs<64>(float (&d)[64], uint32_t a0, uint32_t a1, uint32_t a2, uint32_t a3, uint64_t db) {
  asm volatile("{.reg .pred p; setp.ne.b32 p, 1, 0; wgmma.mma_async.sync.aligned.m64n64k16.f32.bf16.bf16 {%0,%1,%2,%3,%4,%5,%6,%7,%8,%9,%10,%11,%12,%13,%14,%15,%16,%17,%18,%19,%20,%21,%22,%23,%24,%25,%26,%27,%28,%29,%30,%31}, {%32,%33,%34,%35}, %36, p, 1, 1, 0;}"
    : "+f"(d[0]),"+f"(d[1]),"+f"(d[2]),"+f"(d[3]),"+f"(d[4]),"+f"(d[5]),"+f"(d[6]),"+f"(d[7]),"+f"(d[8]),"+f"(d[9]),"+f"(d[10]),"+f"(d[11]),"+f"(d[12]),"+f"(d[13]),"+f"(d[14]),"+f"(d[15]),"+f"(d[16]),"+f"(d[17]),"+f"(d[18]),"+f"(d[19]),"+f"(d[20]),"+f"(d[21]),"+f"(d[22]),"+f"(d[23]),"+f"(d[24]),"+f"(d[25]),"+f"(d[26]),"+f"(d[27]),"+f"(d[28]),"+f"(d[29]),"+f"(d[30]),"+f"(d[31]) : "r"(a0), "r"(a1), "r"(a2), "r"(a3), "l"(db));
}
__device__ __forceinline__ void wg_rs_first(float (&d)[64], uint32_t a0, uint32_t a1, uint32_t a2, uint32_t a3, uint64_t db) {
  asm volatile("{.reg .pred p; setp.ne.b32 p, 0, 0; wgmma.mma_async.sync.aligned.m64n128k16.f32.bf16.bf16 {%0,%1,%2,%3,%4,%5,%6,%7,%8,%9,%10,%11,%12,%13,%14,%15,%16,%17,%18,%19,%20,%21,%22,%23,%24,%25,%26,%27,%28,%29,%30,%31,%32,%33,%34,%35,%36,%37,%38,%39,%40,%41,%42,%43,%44,%45,%46,%47,%48,%49,%50,%51,%52,%53,%54,%55,%56,%57,%58,%59,%60,%61,%62,%63}, {%64,%65,%66,%67}, %68, p, 1, 1, 0;}"
    : "=f"(d[0]),"=f"(d[1]),"=f"(d[2]),"=f"(d[3]),"=f"(d[4]),"=f"(d[5]),"=f"(d[6]),"=f"(d[7]),"=f"(d[8]),"=f"(d[9]),"=f"(d[10]),"=f"(d[11]),"=f"(d[12]),"=f"(d[13]),"=f"(d[14]),"=f"(d[15]),"=f"(d[16]),"=f"(d[17]),"=f"(d[18]),"=f"(d[19]),"=f"(d[20]),"=f"(d[21]),"=f"(d[22]),"=f"(d[23]),"=f"(d[24]),"=f"(d[25]),"=f"(d[26]),"=f"(d[27]),"=f"(d[28]),"=f"(d[29]),"=f"(d[30]),"=f"(d[31]),"=f"(d[32]),"=f"(d[33]),"=f"(d[34]),"=f"(d[35]),"=f"(d[36]),"=f"(d[37]),"=f"(d[38]),"=f"(d[39]),"=f"(d[40]),"=f"(d[41]),"=f"(d[42]),"=f"(d[43]),"=f"(d[44]),"=f"(d[45]),"=f"(d[46]),"=f"(d[47]),"=f"(d[48]),"=f"(d[49]),"=f"(d[50]),"=f"(d[51]),"=f"(d[52]),"=f"(d[53]),"=f"(d[54]),"=f"(d[55]),"=f"(d[56]),"=f"(d[57]),"=f"(d[58]),"=f"(d[59]),"=f"(d[60]),"=f"(d[61]),"=f"(d[62]),"=f"(d[63]) : "r"(a0), "r"(a1), "r"(a2), "r"(a3), "l"(db));
}
__device__ __forceinline__ void wg_tt128(float (&d)[64], uint64_t da, uint64_t db, int sc) {
  asm volatile("{.reg .pred p; setp.ne.b32 p, %66, 0; wgmma.mma_async.sync.aligned.m64n128k16.f32.bf16.bf16 {%0,%1,%2,%3,%4,%5,%6,%7,%8,%9,%10,%11,%12,%13,%14,%15,%16,%17,%18,%19,%20,%21,%22,%23,%24,%25,%26,%27,%28,%29,%30,%31,%32,%33,%34,%35,%36,%37,%38,%39,%40,%41,%42,%43,%44,%45,%46,%47,%48,%49,%50,%51,%52,%53,%54,%55,%56,%57,%58,%59,%60,%61,%62,%63}, %64, %65, p, 1, 1, 1, 1;}"
    : "+f"(d[0]),"+f"(d[1]),"+f"(d[2]),"+f"(d[3]),"+f"(d[4]),"+f"(d[5]),"+f"(d[6]),"+f"(d[7]),"+f"(d[8]),"+f"(d[9]),"+f"(d[10]),"+f"(d[11]),"+f"(d[12]),"+f"(d[13]),"+f"(d[14]),"+f"(d[15]),"+f"(d[16]),"+f"(d[17]),"+f"(d[18]),"+f"(d[19]),"+f"(d[20]),"+f"(d[21]),"+f"(d[22]),"+f"(d[23]),"+f"(d[24]),"+f"(d[25]),"+f"(d[26]),"+f"(d[27]),"+f"(d[28]),"+f"(d[29]),"+f"(d[30]),"+f"(d[31]),"+f"(d[32]),"+f"(d[33]),"+f"(d[34]),"+f"(d[35]),"+f"(d[36]),"+f"(d[37]),"+f"(d[38]),"+f"(d[39]),"+f"(d[40]),"+f"(d[41]),"+f"(d[42]),"+f"(d[43]),"+f"(d[44]),"+f"(d[45]),"+f"(d[46]),"+f"(d[47]),"+f"(d[48]),"+f"(d[49]),"+f"(d[50]),"+f"(d[51]),"+f"(d[52]),"+f"(d[53]),"+f"(d[54]),"+f"(d[55]),"+f"(d[56]),"+f"(d[57]),"+f"(d[58]),"+f"(d[59]),"+f"(d[60]),"+f"(d[61]),"+f"(d[62]),"+f"(d[63]) : "l"(da), "l"(db), "r"(sc));
}
__device__ __forceinline__ void wg_tt64(float (&d)[64], uint64_t da, uint64_t db, int sc) {
  asm volatile("{.reg .pred p; setp.ne.b32 p, %34, 0; wgmma.mma_async.sync.aligned.m64n64k16.f32.bf16.bf16 {%0,%1,%2,%3,%4,%5,%6,%7,%8,%9,%10,%11,%12,%13,%14,%15,%16,%17,%18,%19,%20,%21,%22,%23,%24,%25,%26,%27,%28,%29,%30,%31}, %32, %33, p, 1, 1, 1, 1;}"
    : "+f"(d[0]),"+f"(d[1]),"+f"(d[2]),"+f"(d[3]),"+f"(d[4]),"+f"(d[5]),"+f"(d[6]),"+f"(d[7]),"+f"(d[8]),"+f"(d[9]),"+f"(d[10]),"+f"(d[11]),"+f"(d[12]),"+f"(d[13]),"+f"(d[14]),"+f"(d[15]),"+f"(d[16]),"+f"(d[17]),"+f"(d[18]),"+f"(d[19]),"+f"(d[20]),"+f"(d[21]),"+f"(d[22]),"+f"(d[23]),"+f"(d[24]),"+f"(d[25]),"+f"(d[26]),"+f"(d[27]),"+f"(d[28]),"+f"(d[29]),"+f"(d[30]),"+f"(d[31]) : "l"(da), "l"(db), "r"(sc));
}
__device__ __forceinline__ void wg_tt32(float (&d)[64], uint64_t da, uint64_t db, int sc) {
  asm volatile("{.reg .pred p; setp.ne.b32 p, %18, 0; wgmma.mma_async.sync.aligned.m64n32k16.f32.bf16.bf16 {%0,%1,%2,%3,%4,%5,%6,%7,%8,%9,%10,%11,%12,%13,%14,%15}, %16, %17, p, 1, 1, 1, 1;}"
    : "+f"(d[0]),"+f"(d[1]),"+f"(d[2]),"+f"(d[3]),"+f"(d[4]),"+f"(d[5]),"+f"(d[6]),"+f"(d[7]),"+f"(d[8]),"+f"(d[9]),"+f"(d[10]),"+f"(d[11]),"+f"(d[12]),"+f"(d[13]),"+f"(d[14]),"+f"(d[15]) : "l"(da), "l"(db), "r"(sc));
}
__device__ __forceinline__ void wg_g1(float (&d)[88], uint64_t da, uint64_t db, int sc) {
  asm volatile("{.reg .pred p; setp.ne.b32 p, %90, 0; wgmma.mma_async.sync.aligned.m64n176k16.f32.bf16.bf16 {%0,%1,%2,%3,%4,%5,%6,%7,%8,%9,%10,%11,%12,%13,%14,%15,%16,%17,%18,%19,%20,%21,%22,%23,%24,%25,%26,%27,%28,%29,%30,%31,%32,%33,%34,%35,%36,%37,%38,%39,%40,%41,%42,%43,%44,%45,%46,%47,%48,%49,%50,%51,%52,%53,%54,%55,%56,%57,%58,%59,%60,%61,%62,%63,%64,%65,%66,%67,%68,%69,%70,%71,%72,%73,%74,%75,%76,%77,%78,%79,%80,%81,%82,%83,%84,%85,%86,%87}, %88, %89, p, 1, 1, 1, 0;}"
    : "+f"(d[0]),"+f"(d[1]),"+f"(d[2]),"+f"(d[3]),"+f"(d[4]),"+f"(d[5]),"+f"(d[6]),"+f"(d[7]),"+f"(d[8]),"+f"(d[9]),"+f"(d[10]),"+f"(d[11]),"+f"(d[12]),"+f"(d[13]),"+f"(d[14]),"+f"(d[15]),"+f"(d[16]),"+f"(d[17]),"+f"(d[18]),"+f"(d[19]),"+f"(d[20]),"+f"(d[21]),"+f"(d[22]),"+f"(d[23]),"+f"(d[24]),"+f"(d[25]),"+f"(d[26]),"+f"(d[27]),"+f"(d[28]),"+f"(d[29]),"+f"(d[30]),"+f"(d[31]),"+f"(d[32]),"+f"(d[33]),"+f"(d[34]),"+f"(d[35]),"+f"(d[36]),"+f"(d[37]),"+f"(d[38]),"+f"(d[39]),"+f"(d[40]),"+f"(d[41]),"+f"(d[42]),"+f"(d[43]),"+f"(d[44]),"+f"(d[45]),"+f"(d[46]),"+f"(d[47]),"+f"(d[48]),"+f"(d[49]),"+f"(d[50]),"+f"(d[51]),"+f"(d[52]),"+f"(d[53]),"+f"(d[54]),"+f"(d[55]),"+f"(d[56]),"+f"(d[57]),"+f"(d[58]),"+f"(d[59]),"+f"(d[60]),"+f"(d[61]),"+f"(d[62]),"+f"(d[63]),"+f"(d[64]),"+f"(d[65]),"+f"(d[66]),"+f"(d[67]),"+f"(d[68]),"+f"(d[69]),"+f"(d[70]),"+f"(d[71]),"+f"(d[72]),"+f"(d[73]),"+f"(d[74]),"+f"(d[75]),"+f"(d[76]),"+f"(d[77]),"+f"(d[78]),"+f"(d[79]),"+f"(d[80]),"+f"(d[81]),"+f"(d[82]),"+f"(d[83]),"+f"(d[84]),"+f"(d[85]),"+f"(d[86]),"+f"(d[87]) : "l"(da), "l"(db), "r"(sc));
}

struct Params { const __nv_bfloat16 *x, *logA, *Aim, *Cr, *Ci, *logdt, *Dskip, *Wg, *Wu, *Wd; uint4* xnT; float2* st; uint2* S; unsigned* flags; };
struct Maps { CUtensorMap x[2], xo, out, wg, wu, wd, hst[2], hld, xt, sld; };

__device__ __forceinline__ void conv_channel(uint32_t cb, int w, int lane, uint32_t (&res)[8], uint32_t sig, int sidx) {
    const int q = lane & 3, g = lane >> 2, gam = g >> 2;
    float acc[64];
    uint2 a[17][2];
    const uint32_t t0 = cb + CH_T + (uint32_t)(14 + 4 * w + (g & 3) - 2 * q) * 280u + gam * 8;
#define LDA(s0, s1) _Pragma("unroll") for (int s = s0; s < s1; s++) { a[s][0] = lds64(t0 + s * 16); a[s][1] = lds64(t0 - 8 * 280 + s * 16); }
#define CT(N, s) wg_rs<N>(acc, a[s][0].x, a[s][0].y, a[s][1].x, a[s][1].y, dU + 4 * (s))
    const uint64_t dU = mkdesc(cb + CH_U, UPLANE, 128, 0);
    LDA(0, 17)
    if (sig) { fence_async_smem(); mbar_arrive(sig); }
    WG_FENCE();
    if (w == 0) STAMP2(52 + 3 * sidx);
    wg_rs_first(acc, a[0][0].x, a[0][0].y, a[0][1].x, a[0][1].y, dU);
    CT(128, 1); CT(120, 2); CT(120, 3); CT(112, 4); CT(112, 5); CT(104, 6); CT(104, 7); CT(96, 8);
    CT(96, 9); CT(88, 10); CT(88, 11); CT(80, 12); CT(80, 13); CT(72, 14); CT(72, 15); CT(64, 16);
#undef CT
#undef LDA
    wg_tt64(acc, mkdesc(cb + CH_A3, 128, 512, 0), mkdesc(cb + CH_B3, 384, 32, 0), 1);
    wg_tt32(acc, mkdesc(cb + CH_A3 + 256, 128, 512, 0), mkdesc(cb + CH_B3 + 128, 384, 32, 0), 1);
    WG_COMMIT();
    if (w == 0) STAMP2(53 + 3 * sidx);
    WG_WAIT(0);
    fence_acc(acc);
    if (w == 0) STAMP2(54 + 3 * sidx);
    const int src1 = (lane & ~3) | ((q + 1) & 3);
    float E[16][2];
    #pragma unroll
    for (int j = 0; j < 16; j++) {
        const float nxt = (j < 15) ? acc[4 * (j + 1) + 2] : 0.f;
        const float sup = (q == 0) ? nxt : acc[4 * j + 2];
        const float v = __shfl_sync(0xffffffffu, sup, src1);
        E[j][0] = acc[4 * j] + acc[4 * j + 3];
        E[j][1] = acc[4 * j + 1] + v;
    }
    const int src2 = gam ? ((lane & 12) | ((q + 3) & 3)) : (16 | (lane & 12) | ((q + 1) & 3));
    const bool c1 = gam && q != 0, c2 = gam && q == 0;
    #pragma unroll
    for (int a2 = 0; a2 < 8; a2++) {
        float y[2];
        #pragma unroll
        for (int e = 0; e < 2; e++) {
            const float sup = c1 ? E[2 * a2][e] : E[2 * a2 + 1][e];
            const float nxt = (a2 < 7) ? E[2 * a2 + 2][e] : 0.f;
            const float keep = c2 ? nxt : (c1 ? E[2 * a2 + 1][e] : E[2 * a2][e]);
            y[e] = keep + __shfl_sync(0xffffffffu, sup, src2);
        }
        res[a2] = pack2(y[1], y[0]);
    }
}

__device__ __forceinline__ void consumer(uint32_t sb, int warp, const Params& P, const Maps& M) {
    const int V = warp >> 2, w = warp & 3, lane = threadIdx.x & 31, q = lane & 3, g = lane >> 2;
    const int c = blockIdx.x;
    const uint32_t bars = sb + OFF_BAR, xb = sb + OFF_X + V * 2 * XBUF;
    {
        float ag[88], au[88];
        define_acc(ag); define_acc(au);
        mbar_wait(bars + 8 * B_FULLW, 0);
        mbar_wait(bars + 8 * (B_FULLX + 2 * V), 0);
        #pragma unroll 1
        for (int st = 0; st < 8; st++) {
            uint64_t dG = mkdesc(sb + OFF_W + (st & 3) * 16384, 0, 1024, 1), dX = mkdesc(xb + (st & 1) * XBUF, 16, 1024, 1);
            uint32_t sig = lane == 0 && (V ? st < 6 : st > 0);
            asm volatile("" : "+l"(dG), "+l"(dX), "+r"(sig) :: "memory");
            if (V ? st < 7 : st > 1) mbar_wait(bars + 8 * (B_TURN + V), st & 1);
            STAMP(40 + 8 * V + st);
            WG_FENCE();
            #pragma unroll
            for (int k = 0; k < 4; k++) {
                if (k == SIGK) mbar_arrive_if(bars + 8 * (B_TURN + 1 - V), sig);
                wg_g1(ag, dG + k * 128, dX + k * 2, k ? 1 : st);
                wg_g1(au, dG + 512 + k * 128, dX + k * 2, k ? 1 : st);
            }
            WG_COMMIT();
            if (st == 6 * V) {
                mbar_wait(bars + 8 * (B_FULLW + ((st + 1) & 3)), V);
                mbar_wait(bars + 8 * (B_FULLX + 2 * V + 1), V);
            } else {
                WG_WAIT(1);
                mbar_arrive_if(bars + 8 * (B_EMPTYW + 2 * V), lane == 0 && st == 6 * V + 1);
                mbar_arrive_if(bars + 8 * (B_EMPTYX + 2 * V), lane == 0 && st == 6 * V + 1);
                WG_WAIT(0);
                mbar_arrive_if(bars + 8 * (B_EMPTYW + (st & 3)), lane == 0);
                mbar_arrive_if(bars + 8 * (B_EMPTYX + 2 * V + (st & 1)), lane == 0);
                if (st < 7) {
                    mbar_wait(bars + 8 * (B_FULLW + ((st + 1) & 3)), (st + 1) >> 2);
                    mbar_wait(bars + 8 * (B_FULLX + 2 * V + ((st + 1) & 1)), ((st + 1) >> 1) & 1);
                }
            }
        }
        WG_WAIT(0);
        fence_acc(ag); fence_acc(au);
        STAMP(8 * V + 1);
        float cg0 = ag[84], cg1 = ag[86], cu0 = au[84], cu1 = au[86];
        const uint32_t ca = sb + OFF_CSUM + (8 * w + g) * 16;
        if (V == 0) { sts128(ca, FU(cg0), FU(cg1), FU(cu0), FU(cu1)); mbar_arrive(bars + 8 * B_CS); }
        else { mbar_wait(bars + 8 * B_CS, 0); const uint4 t = lds128(ca); cg0 = UF(t.x); cg1 = UF(t.y); cu0 = UF(t.z); cu1 = UF(t.w); }
        mbar_wait(bars + 8 * B_STATS, 0);
        mbar_wait(bars + 8 * (B_EMPTYX + 2 * V), 1);
        STAMP(13 + V);
        const uint32_t hs = xb + (2 * w + ((lane >> 3) & 1)) * (2688 + 128 * V) + (lane >> 4) * 128 + (lane & 7) * 16;
        const uint32_t sa = sb + OFF_ST + (168 * V + 2 * q) * 8;
        uint4 sq[22];
        #pragma unroll
        for (int j = 0; j < 3; j++) sq[j] = lds128(sa + j * 64);
        #pragma unroll
        for (int j = 0; j < 22; j += 2) {
            uint32_t o[4];
            #pragma unroll
            for (int jj = 0; jj < 2; jj++) {
                const uint4 sv = sq[j + jj];
                float hv[4];
                #pragma unroll
                for (int i = 0; i < 4; i++) {
                    const float m = UF((i & 1) ? sv.z : sv.x);
                    const float gh = fmaf(-m, (i & 2) ? cg1 : cg0, ag[4 * (j + jj) + i]) * UF((i & 1) ? sv.w : sv.y);
                    const float p = gh * fmaf(-m, (i & 2) ? cu1 : cu0, au[4 * (j + jj) + i]);
                    hv[i] = fmaf(p, tanh_fast(gh), p);
                }
                o[2 * jj] = pack2(hv[0], hv[1]); o[2 * jj + 1] = pack2(hv[2], hv[3]);
            }
            #pragma unroll
            for (int k = (j ? 3 + 3 * j / 2 : 3); k < 6 + 3 * j / 2 && k < 22; k++) sq[k] = lds128(sa + k * 64);
            uint32_t ad = hs + j * 128;
            if (j == 20 && V == 0 && lane >= 16) ad = xb + 21504 + (lane & 7) * 16;
            stsm4(ad, o[0], o[1], o[2], o[3]);
        }
        if (c >= 128 || V) { fence_async_smem(); mbar_arrive(bars + 8 * (B_EPI + V)); }
        STAMP(8 * V + 2);
    }
    if (c >= 128) return;
    {
        uint32_t r0[8], r1[8];
        #pragma unroll
        for (int i = 0; i < 8; i++) asm volatile("" : "=r"(r1[i]));
        #pragma unroll 1
        for (int e = 0; e < 2; e++) {
            #pragma unroll
            for (int i = 0; i < 8; i++) r0[i] = r1[i];
            mbar_wait(bars + 8 * (B_CONV + 2 * V + e), 0);
            conv_channel(sb + OFF_CONV + (2 * V + e) * CH_STRIDE, w, lane, r1, (e | V) ? 0 : bars + 8 * B_EPI, 2 * V + e);
            if (e == 0) STAMP(8 * V + 3);
        }
        const int gam = g >> 2, qq = gam ? ((q + 3) & 3) : q;
        const uint32_t sp = sb + OFF_CONV + V * OFF_SST + ((63 - 4 * gam - qq) * 16 + 4 * (w ^ (3 - qq)) + (g & 3)) * 8;
        bar_sync(3 + V);
        #pragma unroll
        for (int a2 = 0; a2 < 8; a2++) sts64(sp - a2 * 1024, r0[a2], r1[a2]);
        fence_async_smem();
        mbar_arrive(bars + 8 * (B_SIG + V));
        STAMP(8 * V + 4);
    }
    if (V == 1) return;
    {
        const int tau = c >> 2, dg = c & 3;
        const uint32_t row = 8 * (w & 1) + 32 * (w >> 1);
        float acc[64];
        define_acc(acc);
        const float rr0 = __ldcg(&P.st[64 * tau + row + g].y), rr1 = __ldcg(&P.st[64 * tau + row + g + 16].y);
        mbar_wait(bars + 8 * B_FULLD, 0);
        STAMP(5);
        uint64_t dB = mkdesc(sb + wd_slot(0), 8192, 1024, 1), dA = mkdesc(sb + h_slot(0), 1024, 128, 0);
        #pragma unroll 1
        for (int st = 0; st < 21; st++) {
            WG_FENCE();
            wg_tt128(acc, dA, dB, st);
            wg_tt128(acc, dA + 128, dB + 128, 1);
            wg_tt128(acc, dA + 256, dB + 256, 1);
            wg_tt128(acc, dA + 384, dB + 384, 1);
            WG_COMMIT();
            const int sd = (st + 1) & 7;
            const uint32_t nb = bars + 8 * (B_FULLD + sd), np = ((st + 1) >> 3) & 1;
            uint32_t ro = st == 15 ? 8 * B_CH0 : 8 * (B_EMPTYD + ((st - 1) & 7)), m = lane == 0 && st > 0, ok;
            dB = mkdesc(sb + wd_slot(sd), 8192, 1024, 1); dA = mkdesc(sb + h_slot(sd), 1024, 128, 0);
            asm volatile("{.reg .pred p; mbarrier.test_wait.parity.shared::cta.b64 p, [%5], %6; vote.sync.all.pred p, p, -1; selp.u32 %0, 1, 0, p;}"
                : "=r"(ok), "+l"(dA), "+l"(dB), "+r"(ro), "+r"(m) : "r"(nb), "r"(np) : "memory");
            WG_WAIT(1);
            mbar_arrive_if(bars + ro, m);
            if (!ok) mbar_wait(nb, np);
            if (w == 0) STAMP2(20 + st);
        }
        WG_FENCE();
        wg_tt128(acc, dA, dB, 1);
        wg_tt128(acc, dA + 128, dB + 128, 1);
        WG_COMMIT();
        mbar_wait(bars + 8 * B_XO, 0);
        const uint32_t xo = sb + OFF_CONV + (row + (lane & 7) + 16 * ((lane >> 3) & 1)) * 128;
        const uint32_t so = sb + wd_slot(6) + (w >> 1) * 8192 + q * 256 + (g & 1) * 8;
        const uint32_t sx = (4 * (w & 1) + (g >> 1)) ^ (2 * q) ^ (2 * ((2 * tau + (w >> 1)) & 3));
        uint32_t xr[8][4];
        uint2 sv[16];
        #pragma unroll
        for (int j = 0; j < 16; j += 2) {
            ldsm4(xr[j >> 1], xo + (j >> 3) * 8192 + ((((j & 7) + (lane >> 4)) ^ (lane & 7)) << 4));
            sv[j] = lds64(so + j * 512 + (sx << 4));
            sv[j + 1] = lds64(so + j * 512 + 128 + ((sx ^ 1) << 4));
        }
        WG_WAIT(0);
        fence_acc(acc);
        STAMP(6);
        #pragma unroll
        for (int j = 0; j < 16; j += 2) {
            #pragma unroll
            for (int i = 0; i < 4; i++) {
                const int jj = j + (i >> 1), hh = i & 1;
                const float f0 = acc[4 * jj + 2 * hh] * (hh ? rr1 : rr0), f1 = acc[4 * jj + 2 * hh + 1] * (hh ? rr1 : rr0);
                const uint32_t G = pack2(fmaf(f0, tanh_fast(f0), f0), fmaf(f1, tanh_fast(f1), f1));
                const uint32_t s2 = __byte_perm(sv[jj].x, sv[jj].y, hh ? 0x7632 : 0x5410);
                asm("fma.rn.bf16x2 %0, %1, %2, %0;" : "+r"(xr[j >> 1][i]) : "r"(s2), "r"(G));
            }
            stsm4(xo + (j >> 3) * 8192 + ((((j & 7) + (lane >> 4)) ^ (lane & 7)) << 4), xr[j >> 1][0], xr[j >> 1][1], xr[j >> 1][2], xr[j >> 1][3]);
        }
        fence_async_smem();
        bar_sync(1);
        if (w == 0 && elect_one()) {
            #pragma unroll
            for (int i = 0; i < 2; i++)
                asm volatile("cp.async.bulk.tensor.2d.global.shared::cta.bulk_group [%0, {%2, %3}], [%1];"
                    :: "l"(&M.out), "r"(sb + OFF_CONV + i * 8192), "r"(dg * 128 + 64 * i), "r"(tau * 64) : "memory");
            asm volatile("cp.async.bulk.commit_group; cp.async.bulk.wait_group.read 0;" ::: "memory");
        }
        STAMP(7); GSTAMP(23);
    }
}

__device__ __forceinline__ float2 cexp_p(float re2, float im, float p) {
    float sn, cs;
    const float mag = ex2(re2 * p), th = im * p;
    asm("sin.approx.ftz.f32 %0, %1;" : "=f"(sn) : "f"(th));
    asm("cos.approx.ftz.f32 %0, %1;" : "=f"(cs) : "f"(th));
    return make_float2(mag * cs, mag * sn);
}
struct SsmRaw { unsigned short la, ai, cr, ci, ldt, dsk; };
__device__ __forceinline__ unsigned short ldu16(const void* p) { unsigned short v; asm volatile("ld.global.nc.u16 %0, [%1];" : "=h"(v) : "l"(p)); return v; }
__device__ __forceinline__ float2 cmul(float2 a, float2 b) { return make_float2(fmaf(a.x, b.x, -a.y * b.y), fmaf(a.x, b.y, a.y * b.x)); }
__device__ __forceinline__ float2 csqr(float2 a) { const float t = a.x * a.y; return make_float2(fmaf(a.x, a.x, -a.y * a.y), t + t); }
__device__ __forceinline__ void mma16816(float (&d)[4], const uint32_t (&a)[4], uint32_t b0, uint32_t b1) {
    asm volatile("mma.sync.aligned.m16n8k16.row.col.f32.bf16.bf16.f32 {%0,%1,%2,%3}, {%4,%5,%6,%7}, {%8,%9}, {%0,%1,%2,%3};"
        : "+f"(d[0]), "+f"(d[1]), "+f"(d[2]), "+f"(d[3]) : "r"(a[0]), "r"(a[1]), "r"(a[2]), "r"(a[3]), "r"(b0), "r"(b1));
}

__device__ __forceinline__ void layer_norm(uint32_t sb, uint32_t cb, int w, int lane) {
    const uint32_t bars = sb + OFF_BAR;
    mbar_wait(bars + 8 * B_LNX, 0);
    STAMP(34);
    {
        const uint32_t r0 = cb + CH_LN + (w & 1) * 64 + (lane >> 3) * 1040, ra = r0 + (lane & 7) * 16;
        const float pv = bf_lo(FU(ldsf(r0)));
        float s0 = 0.f, s1 = 0.f, a0 = 0.f, a1 = 0.f;
        #pragma unroll 1
        for (int k = 0; k < 1024; k += 512) {
            uint32_t v[16];
            #pragma unroll
            for (int j = 0; j < 4; j++) *(uint4*)&v[4 * j] = lds128(ra + k + 128 * j);
            #pragma unroll
            for (int i = 0; i < 16; i++) { const float t0 = bf_lo(v[i]) - pv, t1 = bf_hi(v[i]) - pv; s0 += t0; s1 += t1; a0 = fmaf(t0, t0, a0); a1 = fmaf(t1, t1, a1); }
        }
        s0 += s1; a0 += a1;
        #pragma unroll
        for (int o = 4; o; o >>= 1) { s0 += __shfl_xor_sync(0xffffffffu, s0, o); a0 += __shfl_xor_sync(0xffffffffu, a0, o); }
        s0 *= 1.f / DM;
        float sd, ri;
        asm("sqrt.approx.ftz.f32 %0, %1;" : "=f"(sd) : "f"(bf_round(bf_round(fmaxf(fmaf(-s0, s0, a0 * (1.f / DM)), 0.f)) + 1e-5f)));
        asm("rcp.approx.ftz.f32 %0, %1;" : "=f"(ri) : "f"(bf_round(sd)));
        if ((lane & 7) == 0) sts64(sb + OFF_CSUM + (w + 4 * (lane >> 3)) * 8, FU(bf_round(pv + s0)), FU(0.5f * ri));
    }
    STAMP(62);
    bar_sync(2);
    const int r = 4 * ((lane & 7) >> 1) + (lane & 1) + 2 * ((lane >> 3) & 1);
    const uint32_t ad = sb + OFF_CONV + (r & 3) * CH_STRIDE + CH_LN + (r & 1) * 64 + (r >> 2) * 1040 + (16 * w + (lane >> 4)) * 16;
    const uint4 sa = lds128(sb + OFF_CSUM + (lane & 3) * 32), sc = lds128(sb + OFF_CSUM + (lane & 3) * 32 + 16);
    const uint32_t m2[2] = {__byte_perm(sa.x, sa.z, 0x7632), __byte_perm(sc.x, sc.z, 0x7632)};
    const float ri[4] = {2.f * UF(sa.y), 2.f * UF(sa.w), 2.f * UF(sc.y), 2.f * UF(sc.w)};
    #pragma unroll 1
    for (int i = 0; i < 8; i += 4) {
        uint32_t v[4][4];
        #pragma unroll
        for (int j = 0; j < 4; j++)
            asm volatile("ldmatrix.sync.aligned.m8n8.x4.trans.shared.b16 {%0,%1,%2,%3}, [%4];" : "=r"(v[j][0]), "=r"(v[j][1]), "=r"(v[j][2]), "=r"(v[j][3]) : "r"(ad + 32 * (i + j)) : "memory");
        #pragma unroll
        for (int j = 0; j < 4; j++) {
            #pragma unroll
            for (int k = 0; k < 4; k++) {
                uint32_t dv; asm("sub.rn.bf16x2 %0, %1, %2;" : "=r"(dv) : "r"(v[j][k]), "r"(m2[k & 1]));
                v[j][k] = pack2(bf_lo(dv) * ri[2 * (k & 1)], bf_hi(dv) * ri[2 * (k & 1) + 1]);
            }
            sts64(cb + CH_LNT + lane * 8 + (i + j) * 512, v[j][0], v[j][1]); sts64(cb + CH_LNT + lane * 8 + (i + j) * 512 + 256, v[j][2], v[j][3]);
        }
    }
    fence_async_smem();
    mbar_arrive(bars + 8 * B_LN);
    STAMP(16);
}

__device__ __forceinline__ void kernel_gen(uint32_t fs, int lane, const SsmRaw& raw, float (&dacc)[2][3][4], const Params& P, int warp) {
    const float dt = bf_round(ex2(bf_lo(raw.ldt) * 1.4426950408889634f));
    const float re2 = bf_round(ex2(bf_lo(raw.la) * 1.4426950408889634f)) * dt * -1.4426950408889634f, im = bf_lo(raw.ai) * dt;
    const float2 C = make_float2(bf_lo(raw.cr) * (dt + dt), bf_lo(raw.ci) * -(dt + dt));
    STAMP(56);
    if (warp < 4 && lane == 0 && re2 != 1.f) {
        const int c = blockIdx.x;
        const char* p = warp < 2 ? (const char*)(P.x + (16 * (c & ~1) + 8 * (c & 1) + 16 * warp) * DM) : (const char*)(warp == 2 ? P.Wg : P.Wu) + 256 * FF * 2 + c * 5504;
        asm volatile("cp.async.bulk.prefetch.L2.global [%0], %1;" :: "l"(p), "r"(warp < 2 ? 8192 : 5504) : "memory");
    }
    const float2 y1 = cexp_p(re2, -im, 1.f), y256 = cexp_p(re2, -im, 256.f), z64 = cexp_p(re2, im, 64.f);
    const uint32_t fm = fs + (lane >> 3) * 144 + (lane & 7) * 16;
#define PK(v) pack2((v).x, (v).y)
    const float2 y2 = csqr(y1), y4 = csqr(y2), y8 = csqr(y4);
    const float2 l1 = cmul(C, y1), l2 = cmul(C, y2), l3 = cmul(l1, y2);
    stsm4(fm, PK(C), PK(l1), PK(l2), PK(l3));
    stsm4(fm + 4 * 144, PK(cmul(C, y4)), PK(cmul(l1, y4)), PK(cmul(l2, y4)), PK(cmul(l3, y4)));
    const float2 t0 = cmul(C, y256), t1 = cmul(t0, y256), t2 = cmul(t1, y256), t3_ = cmul(t2, y256);
    const float2 u1 = cmul(t0, y2), u2 = cmul(u1, y2), u3 = cmul(u2, y2);
    stsm4(fm + 8 * 144, PK(t0), PK(u1), PK(u2), PK(u3));
    stsm4(fm + 12 * 144, PK(t1), PK(cmul(t1, y4)), PK(t2), PK(cmul(t2, y4)));
    const float2 v0 = cmul(t3_, y8), v1 = cmul(v0, y256), v2 = cmul(v1, y256), v3 = cmul(v2, y256);
    stsm4(fm + 16 * 144, PK(v0), PK(v1), PK(v2), PK(v3));
    stsf(fs + lane * 4 + 20 * 144, UF(PK(t3_)));
    STAMP(57);
    const uint32_t ldb = fs + (lane & 7) * 144 + ((lane >> 3) & 1) * 16 + (lane >> 4) * 8 * 144;
    const float p8 = (float)(2 * (lane & 28));
    __syncwarp();
    #pragma unroll 1
    for (int ks = 0; ks < 4; ks++) {
        uint32_t b01[4], b2[2], a0[4], a1[4];
        ldsm4(b01, ldb + ks * 32);
        asm volatile("ldmatrix.sync.aligned.m8n8.x2.shared.b16 {%0,%1}, [%2];" : "=r"(b2[0]), "=r"(b2[1]) : "r"(ldb + 16 * 144 + ks * 32) : "memory");
        #pragma unroll
        for (int mh = 0; mh < 2; mh++) {
            const int src = 8 * ks + 4 * mh + (lane & 3);
            const float2 z = make_float2(__shfl_sync(0xffffffffu, z64.x, src), __shfl_sync(0xffffffffu, z64.y, src));
            const float2 R0 = cexp_p(__shfl_sync(0xffffffffu, re2, src), __shfl_sync(0xffffffffu, im, src), p8);
            const float2 R1 = cmul(R0, z), R2 = cmul(R1, z), R3 = cmul(R2, z);
            a0[2 * mh] = PK(R0); a0[2 * mh + 1] = PK(R1); a1[2 * mh] = PK(R2); a1[2 * mh + 1] = PK(R3);
        }
        mma16816(dacc[0][0], a0, b01[0], b01[1]); mma16816(dacc[1][0], a1, b01[0], b01[1]);
        mma16816(dacc[0][1], a0, b01[2], b01[3]); mma16816(dacc[1][1], a1, b01[2], b01[3]);
        mma16816(dacc[0][2], a0, b2[0], b2[1]);   mma16816(dacc[1][2], a1, b2[0], b2[1]);
    }
#undef PK
    STAMP(58);
}

__device__ __forceinline__ void aux_role(uint32_t sb, int w, float (&dacc)[2][3][4], float dsk, const __nv_bfloat16* x) {
    const int lane = threadIdx.x & 31, q = lane & 3, g = lane >> 2;
    const int c = blockIdx.x;
    const uint32_t bars = sb + OFF_BAR;
    if (c >= 128) { mbar_arrive(bars + 8 * B_LN); return; }
    {
        const uint32_t cb = sb + OFF_CONV + w * CH_STRIDE;
        if (elect_one()) {
            fence_async_smem();
            mbar_expect(bars + 8 * B_LNX, 4096);
            #pragma unroll
            for (int i = 0; i < 4; i++)
                bulk_load(cb + CH_LN + (w & 1) * 64 + i * 1040, x + (16 * (c & ~1) + 8 * (c & 1) + 16 + w + 4 * (i & 1) - 8 * (i & 2)) * DM, 1024, bars + 8 * B_LNX);
        }
        #pragma unroll 1
        for (uint32_t pa = cb + CH_PART + lane * 16; pa < cb + CH_PART + 3 * 3456; pa += 3456) {
            #pragma unroll
            for (int i = 0; i < 6; i++) {
                const uint4 v = lds128(pa + i * 512);
                float* d = &dacc[0][0][0] + 4 * i;
                d[0] += UF(v.x); d[1] += UF(v.y); d[2] += UF(v.z); d[3] += UF(v.w);
            }
        }
        __syncwarp();
        STAMP(18);
        const uint32_t sF = cb + CH_A3, sG = cb + CH_G;
        if (lane == 0) dacc[0][0][0] += dsk;
        if (lane < 10) sts128(sG + 128 + (lane & 1) * 208 + (lane >> 1) * 16, 0, 0, 0, 0);
        const uint32_t f0 = sF + (8 * g + 2 * q) * 4, f1 = sF + ((q < 2) ? 256 + 4 * g + 2 * q : 256 + 2 * g + 64 * q) * 4, st1 = (q < 2) ? 128 : 64;
        const uint32_t ga = sG + ((g & 1) ? 0 : 208) + (63 - (g >> 1) - 32 * q) * 2;
        #pragma unroll
        for (int i = 0; i < 4; i++) {
            const int mu = i >> 1, hh = i & 1;
            sts64(f0 + i * 256, FU(dacc[mu][0][2 * hh]), FU(dacc[mu][0][2 * hh + 1]));
            sts64(f1 + i * st1, FU(dacc[mu][1][2 * hh]), FU(dacc[mu][1][2 * hh + 1]));
            const uint32_t pk = pack2(dacc[mu][2][2 * hh], dacc[mu][2][2 * hh + 1]);
            if (q < 2) { sts16(ga - 8 * i, pk & 0xffff); sts16(ga - 8 * i - 32, pk >> 16); }
        }
        if (lane == 2) stsf(sF + 2048, dacc[0][2][0]);
        STAMP(19);
        layer_norm(sb, cb, w, lane);
        mbar_wait(bars + 8 * B_LN, 0);
    }
    const int u = min(lane, 30) - 15, r2 = (u + ((u >> 1) & 1)) >> 1, r4 = (u + 1 + ((u >> 2) & 1)) >> 2, xt = 1024 + 16 * w + u;
    const uint32_t o0 = CH_A3 + 4 * (w == 0 ? u : w == 1 ? 256 + r2 : 256 + 64 * w + r4), ost = w == 0 ? 64 : w == 1 ? 32 : 16;
    const uint32_t oa0 = u >= 0 || w == 3 ? o0 : CH_A3 + 4 * (w == 1 ? 256 + u : w == 2 ? 384 + r2 : 0);
    const uint32_t ot = CH_A3 + 4 * min(512, 256 + ((xt + 1 + ((xt >> 2) & 1)) >> 2));
    const int kap = (lane >> 4) * 8 + ((lane >> 1) & 7), gam = lane & 1, hh = w >> 1, wp = w & 1;
    const uint32_t oa = CH_U + wp * UPLANE + (127 - 4 * kap - 2 * gam - hh) * 16;
    const uint32_t ob = CH_U + (wp ^ 1) * UPLANE + (128 - wp - 4 * kap - 2 * gam - hh) * 16;
    const uint32_t od = CH_A3 + (4 * wp + hh) * 512 + (kap >> 3) * 256 + (kap & 7) * 16 + gam * 8;
    #pragma unroll 1
    for (uint32_t cb = sb + OFF_CONV; cb < sb + OFF_CONV + 4 * CH_STRIDE; cb += CH_STRIDE) {
        {
            float kv[17];
            kv[0] = ldsf(cb + oa0); kv[16] = ldsf(cb + ot);
            #pragma unroll
            for (int s = 1; s < 16; s++) kv[s] = ldsf(cb + o0 + s * ost);
            const int tid = threadIdx.x & 127;
            const uint32_t ga = cb + CH_G + (tid >= 24) * 16 + min(tid, 47) * 8;
            const uint2 x0 = lds64(ga), x1 = lds64(ga + 8);
            if (u < 0 && w == 0) kv[0] = 0.f;
            if (xt > 1028) kv[16] = 0.f;
            uint32_t o[17];
            #pragma unroll
            for (int s = 0; s < 17; s++) o[s] = pack2(kv[s], __shfl_up_sync(0xffffffffu, kv[s], 1));
            if (lane > 0 && lane < 31) {
                const uint32_t ta = cb + CH_T + (lane - 1) * 280;
                #pragma unroll
                for (int s2 = 0; s2 < 8; s2++) sts64(ta + 64 * w + s2 * 8, o[2 * s2], o[2 * s2 + 1]);
                stsf(ta + 256 + 4 * w, UF(o[16]));
            }
            if (tid < 48) sts128(cb + CH_B3 + tid * 16, x0.x, x0.y, x1.x, x1.y);
        }
    }
    STAMP(61);
    mbar_wait(bars + 8 * B_U, 0);
    if (lane < 8) sts128(sb + OFF_CONV + w * CH_STRIDE + CH_U + 2048 + (lane & 4) * (UPLANE / 4) + (lane & 3) * 16, 0, 0, 0, 0);
    bar_sync(2);
    #pragma unroll 1
    for (int k = 0; k < 4; k++) {
        const int ch = 2 * (k & 1) + (k >> 1);
        const uint32_t cb = sb + OFF_CONV + ch * CH_STRIDE;
        float p[24];
        const uint2 r0 = lds64(cb + ob + 24), r3 = lds64(cb + oa);
        uint32_t r[8];
        *(uint4*)&r[0] = lds128(cb + oa + 16); *(uint4*)&r[4] = lds128(cb + ob);
        p[0] = 0.f;
        p[1] = bf_lo(r0.x); p[2] = p[1] + bf_hi(r0.x); p[3] = p[2] + bf_lo(r0.y); p[4] = p[3] + bf_hi(r0.y);
        #pragma unroll
        for (int i = 0; i < 8; i++) { p[5 + 2 * i] = p[4 + 2 * i] + bf_lo(r[i]); p[6 + 2 * i] = p[5 + 2 * i] + bf_hi(r[i]); }
        p[21] = p[20] + bf_lo(r3.x); p[22] = p[21] + bf_hi(r3.x); p[23] = p[22] + bf_lo(r3.y);
        #pragma unroll
        for (int i = 0; i < 8; i += 4) {
            sts64(cb + od + i * 256, pack2(p[i + 9] - p[i], p[i + 10] - p[i + 1]), pack2(p[i + 11] - p[i + 2], p[i + 12] - p[i + 3]));
            sts64(cb + od + i * 256 + 128, pack2(p[i + 16] - p[i + 9], p[i + 17] - p[i + 10]), pack2(p[i + 18] - p[i + 11], p[i + 19] - p[i + 12]));
        }
        fence_async_smem();
        mbar_arrive(bars + 8 * (B_CONV + ch));
        if (k == 0) STAMP(17);
    }
    STAMP(21);
}

__global__ void __launch_bounds__(512, 1)
fused_kernel(const __grid_constant__ Params P, const __grid_constant__ Maps M) {
    extern __shared__ __align__(1024) uint8_t smem_raw[];
    const uint32_t sb = smem_u32(smem_raw);
    const uint32_t bars = sb + OFF_BAR;
    const int warp = __shfl_sync(0xffffffffu, threadIdx.x >> 5, 0);
    const int c = blockIdx.x, tg = c / 22, fb = c - 22 * tg;
    SsmRaw raw;
    {
        const int d = min(4 * c + (warp & 3), DM - 1), o = d * 128 + (warp >> 2) * 32 + (threadIdx.x & 31);
        raw.la = ldu16(P.logA + o); raw.ai = ldu16(P.Aim + o); raw.cr = ldu16(P.Cr + o); raw.ci = ldu16(P.Ci + o);
        raw.ldt = ldu16(P.logdt + d); raw.dsk = ldu16(P.Dskip + d);
    }
    if (elect_one()) {
        if (warp == 0) { STAMP(24); GSTAMP(22); }
        asm volatile("" :: "l"(((const uint64_t*)&P)[warp < 14 ? warp : 0]));
        if (warp < 12) asm volatile("prefetch.tensormap [%0];" :: "l"(&M.x[0] + warp) : "memory");
        #pragma unroll
        for (int k = 0; k < 4; k++) {
            const int i = 16 * k + ((warp + 4) & 15);
            const uint32_t cnt = i >= B_CONV ? 128 : ((0xf0ull >> i) & 1) ? 8 : ((0xff0000ull >> i) & 1) ? 2 : ((0x3e00ff00f000ull >> i) & 1) ? 4 : 1;
            asm volatile("mbarrier.init.shared::cta.b64 [%0], %1;" :: "r"(bars + 8 * i), "r"(cnt) : "memory");
        }
        asm volatile("fence.mbarrier_init.release.cluster; fence.proxy.async.shared::cta;" ::: "memory");
        if (warp >= 12) {
            const uint32_t s = warp - 12;
            mbar_expect(bars + 8 * (B_FULLW + s), 16384);
            tma2d(sb + OFF_W + s * 16384, &M.wg, 64 * fb, 64 * s, bars + 8 * (B_FULLW + s));
            tma2d(sb + OFF_W + s * 16384 + 8192, &M.wu, 64 * fb, 64 * s, bars + 8 * (B_FULLW + s));
            STAMP(31);
        } else if ((warp >> 2) == 1) {
            const uint32_t s = warp - 4, V = s >> 1;
            mbar_expect(bars + 8 * (B_FULLX + s), (168 + 8 * V) * 128);
            tma2d(sb + OFF_X + s * XBUF, &M.x[V], 64 * (s & 1), TOKG * tg + 168 * V, bars + 8 * (B_FULLX + s));
        }
        if (sb & 1023) __trap();
    }
    if (warp < 4) sts128(sb + OFF_X + (warp >> 1) * XBUF + 168 * 128 + (threadIdx.x & 63) * 16, 0x3f803f80u, 0x3f803f80u, 0x3f803f80u, 0x3f803f80u);
    float dacc[2][3][4];
    #pragma unroll
    for (int i = 0; i < 24; i++) (&dacc[0][0][0])[i] = 0.f;
    if (c < 128) {
        const int wg = warp >> 2;
        const uint32_t fs = sb + OFF_CONV + (warp & 3) * CH_STRIDE + (wg == 2 ? 0 : CH_PART + min(wg, 2) * 3456);
        kernel_gen(fs, threadIdx.x & 31, raw, dacc, P, warp);
        if (wg != 2) {
            __syncwarp();
            #pragma unroll
            for (int i = 0; i < 6; i++) { const float* d = &dacc[0][0][0] + 4 * i; sts128(fs + (threadIdx.x & 31) * 16 + i * 512, FU(d[0]), FU(d[1]), FU(d[2]), FU(d[3])); }
        }
    }
    if (warp < 4) fence_async_smem();
    __syncthreads();
    if (warp < 8) {
        asm volatile("setmaxnreg.inc.sync.aligned.u32 208;");
        consumer(sb, warp, P, M);
    } else if (warp < 12) {
        asm volatile("setmaxnreg.dec.sync.aligned.u32 72;");
        STAMP(32);
        aux_role(sb, warp - 8, dacc, bf_lo(raw.dsk), P.x);
    } else {
        asm volatile("setmaxnreg.dec.sync.aligned.u32 24;");
        const int tau = c >> 2, dg = c & 3;
        if (elect_one()) {
            if (warp < 15) {
                if (warp == 12) {
                    #pragma unroll 1
                    for (int st = 4; st < 8; st++) {
                        const uint32_t s = st & 3, fb_ = bars + 8 * (B_FULLW + s);
                        mbar_wait(bars + 8 * (B_EMPTYW + s), 0);
                        mbar_expect(fb_, 16384);
                        tma2d(sb + OFF_W + s * 16384, &M.wg, 64 * fb, 64 * st, fb_);
                        tma2d(sb + OFF_W + s * 16384 + 8192, &M.wu, 64 * fb, 64 * st, fb_);
                    }
                } else {
                    const int V = warp - 13;
                    #pragma unroll 1
                    for (int st = 2; st < 8; st++) {
                        const uint32_t s = 2 * V + (st & 1);
                        mbar_wait(bars + 8 * (B_EMPTYX + s), ((st >> 1) & 1) ^ 1);
                        mbar_expect(bars + 8 * (B_FULLX + s), (168 + 8 * V) * 128);
                        tma2d(sb + OFF_X + s * XBUF, &M.x[V], 64 * st, TOKG * tg + 168 * V, bars + 8 * (B_FULLX + s));
                    }
                }
                if (c < 128 && warp < 14) {
                    if (warp == 13) {
                        mbar_wait(bars + 8 * (B_STG + 1), 0);
                        #pragma unroll 1
                        for (int o = 8 * tau; o < 8 * tau + 8; o += 7) flag_wait(P.flags, F_H + 2 * (o / 43) + ((o % 43) >= 21), 22);
                        mbar_arrive(bars + 8 * B_HF);
                        STAMP(25);
                    }
                    #pragma unroll 1
                    for (int st = 0; st < 22; st += (st < 7 || (st == 7 && warp == 12)) ? 1 : 2) {
                        const int sd = st & 7;
                        const uint32_t fb_ = bars + 8 * (B_FULLD + sd);
                        if (st >= 8) mbar_wait(bars + 8 * (B_EMPTYD + sd), ((st >> 3) & 1) ^ 1);
                        else if (warp == 12 || st >= 6) mbar_wait(bars + 8 * (uint32_t)((0x373623070d060504ull >> (8 * st)) & 0xff), st < 5);
                        if (st >= 10 && st < 21) STAMP2(31 + st);
                        if (st >= 8 || warp == 13) {
                            mbar_expect(fb_, 8192);
                            asm volatile("cp.async.bulk.tensor.5d.shared::cluster.global.mbarrier::complete_tx::bytes [%0], [%1, {%3, %3, %3, %4, %5}], [%2];"
                                :: "r"(sb + h_slot(sd)), "l"(&M.hld), "r"(fb_), "r"(0), "r"(2 * tau), "r"(8 * st) : "memory");
                        }
                        if (st >= 8 || warp == 12) {
                            const uint32_t da = sb + wd_slot(sd);
                            mbar_expect(fb_, 16384);
                            tma2d(da, &M.wd, 128 * dg, 64 * st, fb_);
                            tma2d(da + 8192, &M.wd, 128 * dg + 64, 64 * st, fb_);
                        }
                    }
                } else if (c < 128) {
                    mbar_wait(bars + 8 * B_SST, 0);
                    flag_wait(P.flags, F_S + dg, 64);
                    STAMP(26);
                    mbar_wait(bars + 8 * B_CH0, 0);
                    mbar_expect(bars + 8 * B_XO, 32768);
                    tma2d(sb + OFF_CONV, &M.xo, 128 * dg, 64 * tau, bars + 8 * B_XO);
                    tma2d(sb + OFF_CONV + 8192, &M.xo, 128 * dg + 64, 64 * tau, bars + 8 * B_XO);
                    asm volatile("cp.async.bulk.tensor.5d.shared::cluster.global.mbarrier::complete_tx::bytes [%0], [%1, {%3, %3, %3, %4, %5}], [%2];"
                        :: "r"(sb + wd_slot(6)), "l"(&M.sld), "r"(bars + 8 * B_XO), "r"(0), "r"(8 * dg), "r"(2 * tau) : "memory");
                    mbar_wait(bars + 8 * B_HF, 0);
                    exit_count(P.flags);
                }
            } else {
                mbar_wait(bars + 8 * B_LN, 0);
                STAMP2(0);
                if (c < 128) {
                    #pragma unroll 1
                    for (int i = 0; i < 4; i++)
                        asm volatile("cp.async.bulk.tensor.2d.global.shared::cta.bulk_group [%0, {%2, %3}], [%1];"
                            :: "l"(&M.xt), "r"(sb + OFF_CONV + i * CH_STRIDE + CH_LNT), "r"((c & 1) * 1024 + (126 - (c & ~1)) * 8), "r"(128 * i) : "memory");
                    #pragma unroll 1
                    for (int i = 0; i < 2; i++) bulk_store(P.st + 16 * (c & ~1) + 8 * (c & 1) + 16 - 16 * i, sb + OFF_CSUM + 64 * i, 64);
                    asm volatile("cp.async.bulk.prefetch.L2.global [%0], %1;" :: "l"(P.Wd + c * (FF * DM / 128)), "r"(FF * DM / 64) : "memory");
                }
                STAMP2(1);
                flag_signal(P.flags, F_A);
                STAMP2(2);
                flag_wait(P.flags, F_A, NCTA);
                STAMP(20);
                mbar_expect(bars + 8 * B_STATS, TOKG * 8);
                bulk_load(sb + OFF_ST, P.st + TOKG * tg, TOKG * 8, bars + 8 * B_STATS);
                if (c < 128) {
                    mbar_expect(bars + 8 * B_U, 8 * 2048);
                    #pragma unroll 1
                    for (int i = 0; i < 8; i++)
                        bulk_load(sb + OFF_CONV + (i >> 1) * CH_STRIDE + CH_U + (i & 1) * UPLANE, P.xnT + 4 * c * 256 + i * 128, 2048, bars + 8 * B_U);
                } else exit_count(P.flags);
                #pragma unroll 1
                for (int V = 0; V < 2; V++) {
                    mbar_wait(bars + 8 * (B_EPI + V), 0);
                    STAMP2(3 + 2 * V);
                    asm volatile("cp.async.bulk.tensor.3d.global.shared::cta.bulk_group [%0, {%2, %3, %4}], [%1];"
                        :: "l"(&M.hst[V]), "r"(sb + OFF_X + V * 2 * XBUF), "r"(0), "r"(43 * tg + 21 * V), "r"(8 * fb) : "memory");
                    flag_signal(P.flags, F_H + 2 * tg + V);
                    mbar_arrive(bars + 8 * (B_STG + V));
                    STAMP2(4 + 2 * V);
                }
                if (c < 128) {
                    #pragma unroll 1
                    for (int V = 0; V < 2; V++) {
                        mbar_wait(bars + 8 * (B_SIG + V), 0);
                        STAMP2(7 + 2 * V);
                        bulk_store(P.S + (2 * c + V) * 1024, sb + OFF_CONV + V * OFF_SST, 8192);
                        flag_signal(P.flags, F_S + (c >> 5));
                        STAMP2(8 + 2 * V);
                    }
                    mbar_arrive(bars + 8 * B_SST);
                }
            }
        }
    }
    asm volatile("nanosleep.u32 0;");
}

typedef CUresult (*EncodeFn)(CUtensorMap*, CUtensorMapDataType, cuuint32_t, void*, const cuuint64_t*, const cuuint64_t*, const cuuint32_t*,
                             const cuuint32_t*, CUtensorMapInterleave, CUtensorMapSwizzle, CUtensorMapL2promotion, CUtensorMapFloatOOBfill);

void make_map(EncodeFn enc, CUtensorMap* m, const void* ptr, int rank, const cuuint64_t* dims, const cuuint64_t* strides, const cuuint32_t* box, bool swz, bool wide = false) {
    const cuuint32_t es[5] = {1, 1, 1, 1, 1};
    enc(m, CU_TENSOR_MAP_DATA_TYPE_BFLOAT16, rank, (void*)ptr, dims, strides, box, es, CU_TENSOR_MAP_INTERLEAVE_NONE,
        swz ? CU_TENSOR_MAP_SWIZZLE_128B : CU_TENSOR_MAP_SWIZZLE_NONE, wide ? CU_TENSOR_MAP_L2_PROMOTION_L2_256B : CU_TENSOR_MAP_L2_PROMOTION_L2_128B, CU_TENSOR_MAP_FLOAT_OOB_FILL_NONE);
}
void make_map2(EncodeFn enc, CUtensorMap* m, const void* ptr, cuuint64_t inner, cuuint64_t outer, cuuint32_t rows) {
    const cuuint64_t dims[2] = {inner, outer}, strides[1] = {inner * 2};
    const cuuint32_t box[2] = {64, rows};
    make_map(enc, m, ptr, 2, dims, strides, box, true, rows > 64);
}

}

extern "C" void kernel_launch(void* const* d_in, const int* in_sizes, int n_in, void* d_out, int out_size) {
    (void)in_sizes; (void)n_in; (void)out_size;
    static EncodeFn enc = nullptr;
    static void *hptr, *p_xnT, *p_st, *p_S, *p_flags;
    if (!enc) {
        cudaDriverEntryPointQueryResult qr;
        cudaGetDriverEntryPoint("cuTensorMapEncodeTiled", (void**)&enc, cudaEnableDefault, &qr);
        cudaFuncSetAttribute(fused_kernel, cudaFuncAttributeMaxDynamicSharedMemorySize, SMEM_BYTES);
        cudaGetSymbolAddress(&hptr, g_H); cudaGetSymbolAddress(&p_xnT, g_xnT); cudaGetSymbolAddress(&p_st, g_st);
        cudaGetSymbolAddress(&p_S, g_S); cudaGetSymbolAddress(&p_flags, g_flags);
    }
    Params P;
    P.x = (const __nv_bfloat16*)d_in[0]; P.logA = (const __nv_bfloat16*)d_in[1]; P.Aim = (const __nv_bfloat16*)d_in[2];
    P.Cr = (const __nv_bfloat16*)d_in[3]; P.Ci = (const __nv_bfloat16*)d_in[4]; P.logdt = (const __nv_bfloat16*)d_in[5];
    P.Dskip = (const __nv_bfloat16*)d_in[6];
    P.Wg = (const __nv_bfloat16*)d_in[8]; P.Wu = (const __nv_bfloat16*)d_in[9]; P.Wd = (const __nv_bfloat16*)d_in[10]; P.xnT = (uint4*)p_xnT; P.st = (float2*)p_st; P.S = (uint2*)p_S; P.flags = (unsigned*)p_flags;
    Maps M;
    make_map2(enc, &M.x[0], d_in[0], DM, SEQ, 168); make_map2(enc, &M.x[1], d_in[0], DM, SEQ, 176);
    make_map2(enc, &M.xo, d_in[0], DM, SEQ, 64);    make_map2(enc, &M.out, d_out, DM, SEQ, 64);
    make_map2(enc, &M.wg, d_in[8], FF, DM, 64);     make_map2(enc, &M.wu, d_in[9], FF, DM, 64);
    make_map2(enc, &M.wd, d_in[10], DM, FF, 64);
    for (int v = 0; v < 2; v++) {
        const cuuint64_t dims[3] = {64, 256, 172}, strides[2] = {128, 32768};
        const cuuint32_t box[3] = {64, (cuuint32_t)(21 + v), 8};
        make_map(enc, &M.hst[v], hptr, 3, dims, strides, box, false);
    }
    {
        const cuuint64_t dims[2] = {2048, 512}, strides[1] = {4096};
        const cuuint32_t box[2] = {16, 128};
        make_map(enc, &M.xt, p_xnT, 2, dims, strides, box, false);
    }
    {
        const cuuint64_t dims[5] = {64, 2, 4, 32, 64}, strides[4] = {4 * 8192, 8192, 8 * 8192, 128};
        const cuuint32_t box[5] = {64, 2, 4, 8, 2};
        make_map(enc, &M.sld, p_S, 5, dims, strides, box, true);
    }
    {
        const cuuint64_t dims[5] = {64, 2, 2, 64, 172}, strides[4] = {256, 128, 512, 32768};
        const cuuint32_t box[5] = {64, 2, 2, 2, 8};
        make_map(enc, &M.hld, hptr, 5, dims, strides, box, false);
    }
    fused_kernel<<<NCTA, 512, SMEM_BYTES>>>(P, M);
}
```

```cpp
#include <cuda_runtime.h>
#include <cuda_bf16.h>
#include <cuda.h>
#include <stdint.h>

#define PROF 0

namespace {

constexpr int SEQ = 2048, DM = 512, FF = 1376;
constexpr int NCTA = 132;
#define GOST 1
#define SIGK 3
#define DLY1 300
constexpr int RUNROLL = 2;
constexpr int TOKG = 344;

constexpr uint32_t OFF_W = 0;
constexpr uint32_t XBUF = 22528;
constexpr uint32_t OFF_X = 65536;
constexpr uint32_t OFF_CONV = 155648;
constexpr uint32_t CH_STRIDE = 17536;
constexpr uint32_t CH_T = 0;
constexpr uint32_t CH_A3 = 8448;
constexpr uint32_t CH_B3 = 12544;
constexpr uint32_t CH_U = 13312;
constexpr uint32_t CH_G = CH_A3 + 2064;
constexpr uint32_t UPLANE = 2112;
constexpr uint32_t CH_LN = 0, CH_PART = 4224, CH_LNT = 13440;
constexpr uint32_t OFF_SST = 60416;
constexpr uint32_t OFF_ST = 225792;
constexpr uint32_t OFF_CSUM = 228544;
constexpr uint32_t OFF_BAR = 229056;
constexpr uint32_t SMEM_BYTES = 229568;

enum {
    B_FULLW = 0, B_EMPTYW = 4, B_FULLX = 8, B_EMPTYX = 12, B_FULLD = 16, B_EMPTYD = 24,
    B_U = 32, B_XO = 33, B_S = 34, B_STG = 35, B_HF = 37, B_STATS = 38, B_LNS = 39, B_SST = 40,
    B_LNX = 41, B_CH0 = 42, B_TURN = 43, B_K = 45,
    B_CONV = 46, B_LN = 50, B_CS = 51, B_EPI = 52, B_SIG = 54,
    B_COUNT = 56
};
enum { F_A = 0, F_H = 1, F_S = 13, F_EXIT = 17, F_COUNT = 18 };

__device__ uint4 g_xnT[DM * 256];
__device__ float2 g_st[6 * TOKG];
__device__ uint4 g_H[172 * 256 * 8];
__device__ uint2 g_S[256 * 1024];
__device__ unsigned g_flags[F_COUNT * 32];
#define STAMP(i) do {} while (0)
#define GSTAMP(i) do {} while (0)
#define STAMP2(i) do {} while (0)

__device__ __forceinline__ uint32_t smem_u32(const void* p) { return (uint32_t)__cvta_generic_to_shared(p); }
__device__ __forceinline__ void mbar_expect(uint32_t bar, uint32_t bytes) { asm volatile("mbarrier.arrive.expect_tx.shared::cta.b64 _, [%0], %1;" :: "r"(bar), "r"(bytes) : "memory"); }
__device__ __forceinline__ void mbar_arrive(uint32_t bar) { asm volatile("mbarrier.arrive.shared::cta.b64 _, [%0];" :: "r"(bar) : "memory"); }
__device__ __forceinline__ void mbar_wait(uint32_t bar, uint32_t parity) {
    asm volatile("{.reg .pred p; .reg .u32 n; mov.u32 n, 0x20000;\n"
                 "LW: mbarrier.try_wait.parity.shared::cta.b64 p, [%0], %1;\n"
                 "sub.u32 n, n, 1; setp.eq.or.u32 p, n, 0, p; @!p bra LW;}" :: "r"(bar), "r"(parity) : "memory");
}
__device__ __forceinline__ void mbar_arrive_if(uint32_t bar, uint32_t pred) {
    asm volatile("{.reg .pred p; setp.ne.u32 p, %1, 0; @p mbarrier.arrive.shared::cta.b64 _, [%0];}" :: "r"(bar), "r"(pred) : "memory");
}
__device__ __forceinline__ bool elect_one() { uint32_t p; asm volatile("{.reg .pred P; elect.sync _|P, 0xffffffff; selp.u32 %0, 1, 0, P;}" : "=r"(p)); return p; }
__device__ __forceinline__ void tma2d(uint32_t dst, const CUtensorMap* m, int c0, int c1, uint32_t bar) {
    asm volatile("cp.async.bulk.tensor.2d.shared::cluster.global.mbarrier::complete_tx::bytes [%0], [%1, {%3, %4}], [%2];"
        :: "r"(dst), "l"(m), "r"(bar), "r"(c0), "r"(c1) : "memory");
}
__device__ __forceinline__ void bulk_load(uint32_t dst, const void* src, uint32_t bytes, uint32_t bar) {
    asm volatile("cp.async.bulk.shared::cluster.global.mbarrier::complete_tx::bytes [%0], [%1], %2, [%3];" :: "r"(dst), "l"(src), "r"(bytes), "r"(bar) : "memory");
}
__device__ __forceinline__ void bulk_store(void* dst, uint32_t src, uint32_t bytes) {
    asm volatile("cp.async.bulk.global.shared::cta.bulk_group [%0], [%1], %2;" :: "l"(dst), "r"(src), "r"(bytes) : "memory");
}
__device__ __forceinline__ void fence_async_smem() { asm volatile("fence.proxy.async.shared::cta;" ::: "memory"); }
__device__ __forceinline__ void flag_wait(unsigned* g_flags, int f, unsigned target) {
    asm volatile("{.reg .pred p; .reg .u32 n, v; mov.u32 n, 0x40000;\n"
                 "LF: ld.acquire.gpu.global.u32 v, [%0]; setp.ge.u32 p, v, %1; @p bra LD;\n"
                 "sub.u32 n, n, 1; setp.ne.u32 p, n, 0; @p bra LF; trap;\nLD: }"
                 :: "l"(g_flags + f * 32), "r"(target) : "memory");
}
__device__ __forceinline__ void flag_signal(unsigned* g_flags, int f) {
    asm volatile("cp.async.bulk.commit_group; cp.async.bulk.wait_group 0; red.relaxed.gpu.global.add.u32 [%0], 1;" :: "l"(g_flags + f * 32) : "memory");
}
__device__ __forceinline__ void exit_count(unsigned* g_flags) {
    if (atomicAdd(g_flags + F_EXIT * 32, 1u) == NCTA - 1) {
        #pragma unroll 1
        for (int i = 0; i < F_COUNT; i++) g_flags[i * 32] = 0;
    }
}
__device__ __forceinline__ void bar_sync(int id) { asm volatile("bar.sync %0, 128;" :: "r"(id) : "memory"); }
__device__ __forceinline__ uint64_t mkdesc(uint32_t addr, uint32_t lbo, uint32_t sbo, uint32_t swz) {
    return (uint64_t)((addr >> 4) | ((lbo >> 4) << 16)) | ((uint64_t)((sbo >> 4) | (swz << 30)) << 32);
}
#define WG_FENCE() asm volatile("wgmma.fence.sync.aligned;" ::: "memory")
#define WG_COMMIT() asm volatile("wgmma.commit_group.sync.aligned;" ::: "memory")
#define WG_WAIT(n) asm volatile("wgmma.wait_group.sync.aligned " #n ";" ::: "memory")
template <int N> __device__ __forceinline__ void fence_acc(float (&d)[N]) {
    #pragma unroll
    for (int i = 0; i < N; i++) asm volatile("" : "+f"(d[i]) :: "memory");
}
template <int N> __device__ __forceinline__ void define_acc(float (&d)[N]) {
    #pragma unroll
    for (int i = 0; i < N; i++) asm volatile("" : "=f"(d[i]));
}
__device__ __forceinline__ uint32_t pack2(float lo, float hi) { uint32_t r; asm("cvt.rn.bf16x2.f32 %0, %1, %2;" : "=r"(r) : "f"(hi), "f"(lo)); return r; }
__device__ __forceinline__ float bf_lo(uint32_t v) { return __uint_as_float(v << 16); }
__device__ __forceinline__ float bf_hi(uint32_t v) { return __uint_as_float(v & 0xffff0000u); }
__device__ __forceinline__ float bf_round(float v) { return bf_hi(pack2(0.f, v)); }
__device__ __forceinline__ float tanh_fast(float v) { float r; asm("tanh.approx.f32 %0, %1;" : "=f"(r) : "f"(v)); return r; }
__device__ __forceinline__ float ex2(float v) { float r; asm("ex2.approx.ftz.f32 %0, %1;" : "=f"(r) : "f"(v)); return r; }
__device__ __forceinline__ uint4 lds128(uint32_t a) { uint4 v; asm volatile("ld.shared.v4.b32 {%0,%1,%2,%3}, [%4];" : "=r"(v.x), "=r"(v.y), "=r"(v.z), "=r"(v.w) : "r"(a)); return v; }
__device__ __forceinline__ uint2 lds64(uint32_t a) { uint2 v; asm volatile("ld.shared.v2.b32 {%0,%1}, [%2];" : "=r"(v.x), "=r"(v.y) : "r"(a)); return v; }
__device__ __forceinline__ float ldsf(uint32_t a) { float v; asm volatile("ld.shared.f32 %0, [%1];" : "=f"(v) : "r"(a)); return v; }
__device__ __forceinline__ void sts128(uint32_t a, uint32_t x, uint32_t y, uint32_t z, uint32_t w) { asm volatile("st.shared.v4.b32 [%0], {%1,%2,%3,%4};" :: "r"(a), "r"(x), "r"(y), "r"(z), "r"(w) : "memory"); }
__device__ __forceinline__ void sts64(uint32_t a, uint32_t x, uint32_t y) { asm volatile("st.shared.v2.b32 [%0], {%1,%2};" :: "r"(a), "r"(x), "r"(y) : "memory"); }
__device__ __forceinline__ void stsf(uint32_t a, float x) { asm volatile("st.shared.f32 [%0], %1;" :: "r"(a), "f"(x) : "memory"); }
__device__ __forceinline__ void sts16(uint32_t a, uint32_t x) { asm volatile("st.shared.b16 [%0], %1;" :: "r"(a), "h"((unsigned short)x) : "memory"); }
__device__ __forceinline__ void stsm4(uint32_t a, uint32_t r0, uint32_t r1, uint32_t r2, uint32_t r3) {
    asm volatile("stmatrix.sync.aligned.m8n8.x4.shared.b16 [%0], {%1,%2,%3,%4};" :: "r"(a), "r"(r0), "r"(r1), "r"(r2), "r"(r3) : "memory");
}
__device__ __forceinline__ void ldsm4(uint32_t (&r)[4], uint32_t a) {
    asm volatile("ldmatrix.sync.aligned.m8n8.x4.shared.b16 {%0,%1,%2,%3}, [%4];" : "=r"(r[0]), "=r"(r[1]), "=r"(r[2]), "=r"(r[3]) : "r"(a) : "memory");
}
#define FU(x) __float_as_uint(x)
#define UF(x) __uint_as_float(x)
__device__ __forceinline__ uint32_t wd_slot(int s) { return (uint32_t)((0xbba8403056201000ull >> (8 * s)) & 0xff) << 10; }
__device__ __forceinline__ uint32_t h_slot(int s) { return (uint32_t)((0xcba0908880787068ull >> (8 * s)) & 0xff) << 10; }

template<int N> __device__ __forceinline__ void wg_rs(float (&d)[64], uint32_t a0, uint32_t a1, uint32_t a2, uint32_t a3, uint64_t db);
template<> __device__ __forceinline__ void wg_rs<128>(float (&d)[64], uint32_t a0, uint32_t a1, uint32_t a2, uint32_t a3, uint64_t db) {
  asm volatile("{.reg .pred p; setp.ne.b32 p, 1, 0; wgmma.mma_async.sync.aligned.m64n128k16.f32.bf16.bf16 {%0,%1,%2,%3,%4,%5,%6,%7,%8,%9,%10,%11,%12,%13,%14,%15,%16,%17,%18,%19,%20,%21,%22,%23,%24,%25,%26,%27,%28,%29,%30,%31,%32,%33,%34,%35,%36,%37,%38,%39,%40,%41,%42,%43,%44,%45,%46,%47,%48,%49,%50,%51,%52,%53,%54,%55,%56,%57,%58,%59,%60,%61,%62,%63}, {%64,%65,%66,%67}, %68, p, 1, 1, 0;}"
    : "+f"(d[0]),"+f"(d[1]),"+f"(d[2]),"+f"(d[3]),"+f"(d[4]),"+f"(d[5]),"+f"(d[6]),"+f"(d[7]),"+f"(d[8]),"+f"(d[9]),"+f"(d[10]),"+f"(d[11]),"+f"(d[12]),"+f"(d[13]),"+f"(d[14]),"+f"(d[15]),"+f"(d[16]),"+f"(d[17]),"+f"(d[18]),"+f"(d[19]),"+f"(d[20]),"+f"(d[21]),"+f"(d[22]),"+f"(d[23]),"+f"(d[24]),"+f"(d[25]),"+f"(d[26]),"+f"(d[27]),"+f"(d[28]),"+f"(d[29]),"+f"(d[30]),"+f"(d[31]),"+f"(d[32]),"+f"(d[33]),"+f"(d[34]),"+f"(d[35]),"+f"(d[36]),"+f"(d[37]),"+f"(d[38]),"+f"(d[39]),"+f"(d[40]),"+f"(d[41]),"+f"(d[42]),"+f"(d[43]),"+f"(d[44]),"+f"(d[45]),"+f"(d[46]),"+f"(d[47]),"+f"(d[48]),"+f"(d[49]),"+f"(d[50]),"+f"(d[51]),"+f"(d[52]),"+f"(d[53]),"+f"(d[54]),"+f"(d[55]),"+f"(d[56]),"+f"(d[57]),"+f"(d[58]),"+f"(d[59]),"+f"(d[60]),"+f"(d[61]),"+f"(d[62]),"+f"(d[63]) : "r"(a0), "r"(a1), "r"(a2), "r"(a3), "l"(db));
}
template<> __device__ __forceinline__ void wg_rs<120>(float (&d)[64], uint32_t a0, uint32_t a1, uint32_t a2, uint32_t a3, uint64_t db) {
  asm volatile("{.reg .pred p; setp.ne.b32 p, 1, 0; wgmma.mma_async.sync.aligned.m64n120k16.f32.bf16.bf16 {%0,%1,%2,%3,%4,%5,%6,%7,%8,%9,%10,%11,%12,%13,%14,%15,%16,%17,%18,%19,%20,%21,%22,%23,%24,%25,%26,%27,%28,%29,%30,%31,%32,%33,%34,%35,%36,%37,%38,%39,%40,%41,%42,%43,%44,%45,%46,%47,%48,%49,%50,%51,%52,%53,%54,%55,%56,%57,%58,%59}, {%60,%61,%62,%63}, %64, p, 1, 1, 0;}"
    : "+f"(d[0]),"+f"(d[1]),"+f"(d[2]),"+f"(d[3]),"+f"(d[4]),"+f"(d[5]),"+f"(d[6]),"+f"(d[7]),"+f"(d[8]),"+f"(d[9]),"+f"(d[10]),"+f"(d[11]),"+f"(d[12]),"+f"(d[13]),"+f"(d[14]),"+f"(d[15]),"+f"(d[16]),"+f"(d[17]),"+f"(d[18]),"+f"(d[19]),"+f"(d[20]),"+f"(d[21]),"+f"(d[22]),"+f"(d[23]),"+f"(d[24]),"+f"(d[25]),"+f"(d[26]),"+f"(d[27]),"+f"(d[28]),"+f"(d[29]),"+f"(d[30]),"+f"(d[31]),"+f"(d[32]),"+f"(d[33]),"+f"(d[34]),"+f"(d[35]),"+f"(d[36]),"+f"(d[37]),"+f"(d[38]),"+f"(d[39]),"+f"(d[40]),"+f"(d[41]),"+f"(d[42]),"+f"(d[43]),"+f"(d[44]),"+f"(d[45]),"+f"(d[46]),"+f"(d[47]),"+f"(d[48]),"+f"(d[49]),"+f"(d[50]),"+f"(d[51]),"+f"(d[52]),"+f"(d[53]),"+f"(d[54]),"+f"(d[55]),"+f"(d[56]),"+f"(d[57]),"+f"(d[58]),"+f"(d[59]) : "r"(a0), "r"(a1), "r"(a2), "r"(a3), "l"(db));
}
template<> __device__ __forceinline__ void wg_rs<112>(float (&d)[64], uint32_t a0, uint32_t a1, uint32_t a2, uint32_t a3, uint64_t db) {
  asm volatile("{.reg .pred p; setp.ne.b32 p, 1, 0; wgmma.mma_async.sync.aligned.m64n112k16.f32.bf16.bf16 {%0,%1,%2,%3,%4,%5,%6,%7,%8,%9,%10,%11,%12,%13,%14,%15,%16,%17,%18,%19,%20,%21,%22,%23,%24,%25,%26,%27,%28,%29,%30,%31,%32,%33,%34,%35,%36,%37,%38,%39,%40,%41,%42,%43,%44,%45,%46,%47,%48,%49,%50,%51,%52,%53,%54,%55}, {%56,%57,%58,%59}, %60, p, 1, 1, 0;}"
    : "+f"(d[0]),"+f"(d[1]),"+f"(d[2]),"+f"(d[3]),"+f"(d[4]),"+f"(d[5]),"+f"(d[6]),"+f"(d[7]),"+f"(d[8]),"+f"(d[9]),"+f"(d[10]),"+f"(d[11]),"+f"(d[12]),"+f"(d[13]),"+f"(d[14]),"+f"(d[15]),"+f"(d[16]),"+f"(d[17]),"+f"(d[18]),"+f"(d[19]),"+f"(d[20]),"+f"(d[21]),"+f"(d[22]),"+f"(d[23]),"+f"(d[24]),"+f"(d[25]),"+f"(d[26]),"+f"(d[27]),"+f"(d[28]),"+f"(d[29]),"+f"(d[30]),"+f"(d[31]),"+f"(d[32]),"+f"(d[33]),"+f"(d[34]),"+f"(d[35]),"+f"(d[36]),"+f"(d[37]),"+f"(d[38]),"+f"(d[39]),"+f"(d[40]),"+f"(d[41]),"+f"(d[42]),"+f"(d[43]),"+f"(d[44]),"+f"(d[45]),"+f"(d[46]),"+f"(d[47]),"+f"(d[48]),"+f"(d[49]),"+f"(d[50]),"+f"(d[51]),"+f"(d[52]),"+f"(d[53]),"+f"(d[54]),"+f"(d[55]) : "r"(a0), "r"(a1), "r"(a2), "r"(a3), "l"(db));
}
template<> __device__ __forceinline__ void wg_rs<104>(float (&d)[64], uint32_t a0, uint32_t a1, uint32_t a2, uint32_t a3, uint64_t db) {
  asm volatile("{.reg .pred p; setp.ne.b32 p, 1, 0; wgmma.mma_async.sync.aligned.m64n104k16.f32.bf16.bf16 {%0,%1,%2,%3,%4,%5,%6,%7,%8,%9,%10,%11,%12,%13,%14,%15,%16,%17,%18,%19,%20,%21,%22,%23,%24,%25,%26,%27,%28,%29,%30,%31,%32,%33,%34,%35,%36,%37,%38,%39,%40,%41,%42,%43,%44,%45,%46,%47,%48,%49,%50,%51}, {%52,%53,%54,%55}, %56, p, 1, 1, 0;}"
    : "+f"(d[0]),"+f"(d[1]),"+f"(d[2]),"+f"(d[3]),"+f"(d[4]),"+f"(d[5]),"+f"(d[6]),"+f"(d[7]),"+f"(d[8]),"+f"(d[9]),"+f"(d[10]),"+f"(d[11]),"+f"(d[12]),"+f"(d[13]),"+f"(d[14]),"+f"(d[15]),"+f"(d[16]),"+f"(d[17]),"+f"(d[18]),"+f"(d[19]),"+f"(d[20]),"+f"(d[21]),"+f"(d[22]),"+f"(d[23]),"+f"(d[24]),"+f"(d[25]),"+f"(d[26]),"+f"(d[27]),"+f"(d[28]),"+f"(d[29]),"+f"(d[30]),"+f"(d[31]),"+f"(d[32]),"+f"(d[33]),"+f"(d[34]),"+f"(d[35]),"+f"(d[36]),"+f"(d[37]),"+f"(d[38]),"+f"(d[39]),"+f"(d[40]),"+f"(d[41]),"+f"(d[42]),"+f"(d[43]),"+f"(d[44]),"+f"(d[45]),"+f"(d[46]),"+f"(d[47]),"+f"(d[48]),"+f"(d[49]),"+f"(d[50]),"+f"(d[51]) : "r"(a0), "r"(a1), "r"(a2), "r"(a3), "l"(db));
}
template<> __device__ __forceinline__ void wg_rs<96>(float (&d)[64], uint32_t a0, uint32_t a1, uint32_t a2, uint32_t a3, uint64_t db) {
  asm volatile("{.reg .pred p; setp.ne.b32 p, 1, 0; wgmma.mma_async.sync.aligned.m64n96k16.f32.bf16.bf16 {%0,%1,%2,%3,%4,%5,%6,%7,%8,%9,%10,%11,%12,%13,%14,%15,%16,%17,%18,%19,%20,%21,%22,%23,%24,%25,%26,%27,%28,%29,%30,%31,%32,%33,%34,%35,%36,%37,%38,%39,%40,%41,%42,%43,%44,%45,%46,%47}, {%48,%49,%50,%51}, %52, p, 1, 1, 0;}"
    : "+f"(d[0]),"+f"(d[1]),"+f"(d[2]),"+f"(d[3]),"+f"(d[4]),"+f"(d[5]),"+f"(d[6]),"+f"(d[7]),"+f"(d[8]),"+f"(d[9]),"+f"(d[10]),"+f"(d[11]),"+f"(d[12]),"+f"(d[13]),"+f"(d[14]),"+f"(d[15]),"+f"(d[16]),"+f"(d[17]),"+f"(d[18]),"+f"(d[19]),"+f"(d[20]),"+f"(d[21]),"+f"(d[22]),"+f"(d[23]),"+f"(d[24]),"+f"(d[25]),"+f"(d[26]),"+f"(d[27]),"+f"(d[28]),"+f"(d[29]),"+f"(d[30]),"+f"(d[31]),"+f"(d[32]),"+f"(d[33]),"+f"(d[34]),"+f"(d[35]),"+f"(d[36]),"+f"(d[37]),"+f"(d[38]),"+f"(d[39]),"+f"(d[40]),"+f"(d[41]),"+f"(d[42]),"+f"(d[43]),"+f"(d[44]),"+f"(d[45]),"+f"(d[46]),"+f"(d[47]) : "r"(a0), "r"(a1), "r"(a2), "r"(a3), "l"(db));
}
template<> __device__ __forceinline__ void wg_rs<88>(float (&d)[64], uint32_t a0, uint32_t a1, uint32_t a2, uint32_t a3, uint64_t db) {
  asm volatile("{.reg .pred p; setp.ne.b32 p, 1, 0; wgmma.mma_async.sync.aligned.m64n88k16.f32.bf16.bf16 {%0,%1,%2,%3,%4,%5,%6,%7,%8,%9,%10,%11,%12,%13,%14,%15,%16,%17,%18,%19,%20,%21,%22,%23,%24,%25,%26,%27,%28,%29,%30,%31,%32,%33,%34,%35,%36,%37,%38,%39,%40,%41,%42,%43}, {%44,%45,%46,%47}, %48, p, 1, 1, 0;}"
    : "+f"(d[0]),"+f"(d[1]),"+f"(d[2]),"+f"(d[3]),"+f"(d[4]),"+f"(d[5]),"+f"(d[6]),"+f"(d[7]),"+f"(d[8]),"+f"(d[9]),"+f"(d[10]),"+f"(d[11]),"+f"(d[12]),"+f"(d[13]),"+f"(d[14]),"+f"(d[15]),"+f"(d[16]),"+f"(d[17]),"+f"(d[18]),"+f"(d[19]),"+f"(d[20]),"+f"(d[21]),"+f"(d[22]),"+f"(d[23]),"+f"(d[24]),"+f"(d[25]),"+f"(d[26]),"+f"(d[27]),"+f"(d[28]),"+f"(d[29]),"+f"(d[30]),"+f"(d[31]),"+f"(d[32]),"+f"(d[33]),"+f"(d[34]),"+f"(d[35]),"+f"(d[36]),"+f"(d[37]),"+f"(d[38]),"+f"(d[39]),"+f"(d[40]),"+f"(d[41]),"+f"(d[42]),"+f"(d[43]) : "r"(a0), "r"(a1), "r"(a2), "r"(a3), "l"(db));
}
template<> __device__ __forceinline__ void wg_rs<80>(float (&d)[64], uint32_t a0, uint32_t a1, uint32_t a2, uint32_t a3, uint64_t db) {
  asm volatile("{.reg .pred p; setp.ne.b32 p, 1, 0; wgmma.mma_async.sync.aligned.m64n80k16.f32.bf16.bf16 {%0,%1,%2,%3,%4,%5,%6,%7,%8,%9,%10,%11,%12,%13,%14,%15,%16,%17,%18,%19,%20,%21,%22,%23,%24,%25,%26,%27,%28,%29,%30,%31,%32,%33,%34,%35,%36,%37,%38,%39}, {%40,%41,%42,%43}, %44, p, 1, 1, 0;}"
    : "+f"(d[0]),"+f"(d[1]),"+f"(d[2]),"+f"(d[3]),"+f"(d[4]),"+f"(d[5]),"+f"(d[6]),"+f"(d[7]),"+f"(d[8]),"+f"(d[9]),"+f"(d[10]),"+f"(d[11]),"+f"(d[12]),"+f"(d[13]),"+f"(d[14]),"+f"(d[15]),"+f"(d[16]),"+f"(d[17]),"+f"(d[18]),"+f"(d[19]),"+f"(d[20]),"+f"(d[21]),"+f"(d[22]),"+f"(d[23]),"+f"(d[24]),"+f"(d[25]),"+f"(d[26]),"+f"(d[27]),"+f"(d[28]),"+f"(d[29]),"+f"(d[30]),"+f"(d[31]),"+f"(d[32]),"+f"(d[33]),"+f"(d[34]),"+f"(d[35]),"+f"(d[36]),"+f"(d[37]),"+f"(d[38]),"+f"(d[39]) : "r"(a0), "r"(a1), "r"(a2), "r"(a3), "l"(db));
}
template<> __device__ __forceinline__ void wg_rs<72>(float (&d)[64], uint32_t a0, uint32_t a1, uint32_t a2, uint32_t a3, uint64_t db) {
  asm volatile("{.reg .pred p; setp.ne.b32 p, 1, 0; wgmma.mma_async.sync.aligned.m64n72k16.f32.bf16.bf16 {%0,%1,%2,%3,%4,%5,%6,%7,%8,%9,%10,%11,%12,%13,%14,%15,%16,%17,%18,%19,%20,%21,%22,%23,%24,%25,%26,%27,%28,%29,%30,%31,%32,%33,%34,%35}, {%36,%37,%38,%39}, %40, p, 1, 1, 0;}"
    : "+f"(d[0]),"+f"(d[1]),"+f"(d[2]),"+f"(d[3]),"+f"(d[4]),"+f"(d[5]),"+f"(d[6]),"+f"(d[7]),"+f"(d[8]),"+f"(d[9]),"+f"(d[10]),"+f"(d[11]),"+f"(d[12]),"+f"(d[13]),"+f"(d[14]),"+f"(d[15]),"+f"(d[16]),"+f"(d[17]),"+f"(d[18]),"+f"(d[19]),"+f"(d[20]),"+f"(d[21]),"+f"(d[22]),"+f"(d[23]),"+f"(d[24]),"+f"(d[25]),"+f"(d[26]),"+f"(d[27]),"+f"(d[28]),"+f"(d[29]),"+f"(d[30]),"+f"(d[31]),"+f"(d[32]),"+f"(d[33]),"+f"(d[34]),"+f"(d[35]) : "r"(a0), "r"(a1), "r"(a2), "r"(a3), "l"(db));
}
template<> __device__ __forceinline__ void wg_rs<64>(float (&d)[64], uint32_t a0, uint32_t a1, uint32_t a2, uint32_t a3, uint64_t db) {
  asm volatile("{.reg .pred p; setp.ne.b32 p, 1, 0; wgmma.mma_async.sync.aligned.m64n64k16.f32.bf16.bf16 {%0,%1,%2,%3,%4,%5,%6,%7,%8,%9,%10,%11,%12,%13,%14,%15,%16,%17,%18,%19,%20,%21,%22,%23,%24,%25,%26,%27,%28,%29,%30,%31}, {%32,%33,%34,%35}, %36, p, 1, 1, 0;}"
    : "+f"(d[0]),"+f"(d[1]),"+f"(d[2]),"+f"(d[3]),"+f"(d[4]),"+f"(d[5]),"+f"(d[6]),"+f"(d[7]),"+f"(d[8]),"+f"(d[9]),"+f"(d[10]),"+f"(d[11]),"+f"(d[12]),"+f"(d[13]),"+f"(d[14]),"+f"(d[15]),"+f"(d[16]),"+f"(d[17]),"+f"(d[18]),"+f"(d[19]),"+f"(d[20]),"+f"(d[21]),"+f"(d[22]),"+f"(d[23]),"+f"(d[24]),"+f"(d[25]),"+f"(d[26]),"+f"(d[27]),"+f"(d[28]),"+f"(d[29]),"+f"(d[30]),"+f"(d[31]) : "r"(a0), "r"(a1), "r"(a2), "r"(a3), "l"(db));
}
__device__ __forceinline__ void wg_rs_first(float (&d)[64], uint32_t a0, uint32_t a1, uint32_t a2, uint32_t a3, uint64_t db) {
  asm volatile("{.reg .pred p; setp.ne.b32 p, 0, 0; wgmma.mma_async.sync.aligned.m64n128k16.f32.bf16.bf16 {%0,%1,%2,%3,%4,%5,%6,%7,%8,%9,%10,%11,%12,%13,%14,%15,%16,%17,%18,%19,%20,%21,%22,%23,%24,%25,%26,%27,%28,%29,%30,%31,%32,%33,%34,%35,%36,%37,%38,%39,%40,%41,%42,%43,%44,%45,%46,%47,%48,%49,%50,%51,%52,%53,%54,%55,%56,%57,%58,%59,%60,%61,%62,%63}, {%64,%65,%66,%67}, %68, p, 1, 1, 0;}"
    : "=f"(d[0]),"=f"(d[1]),"=f"(d[2]),"=f"(d[3]),"=f"(d[4]),"=f"(d[5]),"=f"(d[6]),"=f"(d[7]),"=f"(d[8]),"=f"(d[9]),"=f"(d[10]),"=f"(d[11]),"=f"(d[12]),"=f"(d[13]),"=f"(d[14]),"=f"(d[15]),"=f"(d[16]),"=f"(d[17]),"=f"(d[18]),"=f"(d[19]),"=f"(d[20]),"=f"(d[21]),"=f"(d[22]),"=f"(d[23]),"=f"(d[24]),"=f"(d[25]),"=f"(d[26]),"=f"(d[27]),"=f"(d[28]),"=f"(d[29]),"=f"(d[30]),"=f"(d[31]),"=f"(d[32]),"=f"(d[33]),"=f"(d[34]),"=f"(d[35]),"=f"(d[36]),"=f"(d[37]),"=f"(d[38]),"=f"(d[39]),"=f"(d[40]),"=f"(d[41]),"=f"(d[42]),"=f"(d[43]),"=f"(d[44]),"=f"(d[45]),"=f"(d[46]),"=f"(d[47]),"=f"(d[48]),"=f"(d[49]),"=f"(d[50]),"=f"(d[51]),"=f"(d[52]),"=f"(d[53]),"=f"(d[54]),"=f"(d[55]),"=f"(d[56]),"=f"(d[57]),"=f"(d[58]),"=f"(d[59]),"=f"(d[60]),"=f"(d[61]),"=f"(d[62]),"=f"(d[63]) : "r"(a0), "r"(a1), "r"(a2), "r"(a3), "l"(db));
}
__device__ __forceinline__ void wg_tt128(float (&d)[64], uint64_t da, uint64_t db, int sc) {
  asm volatile("{.reg .pred p; setp.ne.b32 p, %66, 0; wgmma.mma_async.sync.aligned.m64n128k16.f32.bf16.bf16 {%0,%1,%2,%3,%4,%5,%6,%7,%8,%9,%10,%11,%12,%13,%14,%15,%16,%17,%18,%19,%20,%21,%22,%23,%24,%25,%26,%27,%28,%29,%30,%31,%32,%33,%34,%35,%36,%37,%38,%39,%40,%41,%42,%43,%44,%45,%46,%47,%48,%49,%50,%51,%52,%53,%54,%55,%56,%57,%58,%59,%60,%61,%62,%63}, %64, %65, p, 1, 1, 1, 1;}"
    : "+f"(d[0]),"+f"(d[1]),"+f"(d[2]),"+f"(d[3]),"+f"(d[4]),"+f"(d[5]),"+f"(d[6]),"+f"(d[7]),"+f"(d[8]),"+f"(d[9]),"+f"(d[10]),"+f"(d[11]),"+f"(d[12]),"+f"(d[13]),"+f"(d[14]),"+f"(d[15]),"+f"(d[16]),"+f"(d[17]),"+f"(d[18]),"+f"(d[19]),"+f"(d[20]),"+f"(d[21]),"+f"(d[22]),"+f"(d[23]),"+f"(d[24]),"+f"(d[25]),"+f"(d[26]),"+f"(d[27]),"+f"(d[28]),"+f"(d[29]),"+f"(d[30]),"+f"(d[31]),"+f"(d[32]),"+f"(d[33]),"+f"(d[34]),"+f"(d[35]),"+f"(d[36]),"+f"(d[37]),"+f"(d[38]),"+f"(d[39]),"+f"(d[40]),"+f"(d[41]),"+f"(d[42]),"+f"(d[43]),"+f"(d[44]),"+f"(d[45]),"+f"(d[46]),"+f"(d[47]),"+f"(d[48]),"+f"(d[49]),"+f"(d[50]),"+f"(d[51]),"+f"(d[52]),"+f"(d[53]),"+f"(d[54]),"+f"(d[55]),"+f"(d[56]),"+f"(d[57]),"+f"(d[58]),"+f"(d[59]),"+f"(d[60]),"+f"(d[61]),"+f"(d[62]),"+f"(d[63]) : "l"(da), "l"(db), "r"(sc));
}
__device__ __forceinline__ void wg_tt64(float (&d)[64], uint64_t da, uint64_t db, int sc) {
  asm volatile("{.reg .pred p; setp.ne.b32 p, %34, 0; wgmma.mma_async.sync.aligned.m64n64k16.f32.bf16.bf16 {%0,%1,%2,%3,%4,%5,%6,%7,%8,%9,%10,%11,%12,%13,%14,%15,%16,%17,%18,%19,%20,%21,%22,%23,%24,%25,%26,%27,%28,%29,%30,%31}, %32, %33, p, 1, 1, 1, 1;}"
    : "+f"(d[0]),"+f"(d[1]),"+f"(d[2]),"+f"(d[3]),"+f"(d[4]),"+f"(d[5]),"+f"(d[6]),"+f"(d[7]),"+f"(d[8]),"+f"(d[9]),"+f"(d[10]),"+f"(d[11]),"+f"(d[12]),"+f"(d[13]),"+f"(d[14]),"+f"(d[15]),"+f"(d[16]),"+f"(d[17]),"+f"(d[18]),"+f"(d[19]),"+f"(d[20]),"+f"(d[21]),"+f"(d[22]),"+f"(d[23]),"+f"(d[24]),"+f"(d[25]),"+f"(d[26]),"+f"(d[27]),"+f"(d[28]),"+f"(d[29]),"+f"(d[30]),"+f"(d[31]) : "l"(da), "l"(db), "r"(sc));
}
__device__ __forceinline__ void wg_tt32(float (&d)[64], uint64_t da, uint64_t db, int sc) {
  asm volatile("{.reg .pred p; setp.ne.b32 p, %18, 0; wgmma.mma_async.sync.aligned.m64n32k16.f32.bf16.bf16 {%0,%1,%2,%3,%4,%5,%6,%7,%8,%9,%10,%11,%12,%13,%14,%15}, %16, %17, p, 1, 1, 1, 1;}"
    : "+f"(d[0]),"+f"(d[1]),"+f"(d[2]),"+f"(d[3]),"+f"(d[4]),"+f"(d[5]),"+f"(d[6]),"+f"(d[7]),"+f"(d[8]),"+f"(d[9]),"+f"(d[10]),"+f"(d[11]),"+f"(d[12]),"+f"(d[13]),"+f"(d[14]),"+f"(d[15]) : "l"(da), "l"(db), "r"(sc));
}
__device__ __forceinline__ void wg_g1(float (&d)[88], uint64_t da, uint64_t db, int sc) {
  asm volatile("{.reg .pred p; setp.ne.b32 p, %90, 0; wgmma.mma_async.sync.aligned.m64n176k16.f32.bf16.bf16 {%0,%1,%2,%3,%4,%5,%6,%7,%8,%9,%10,%11,%12,%13,%14,%15,%16,%17,%18,%19,%20,%21,%22,%23,%24,%25,%26,%27,%28,%29,%30,%31,%32,%33,%34,%35,%36,%37,%38,%39,%40,%41,%42,%43,%44,%45,%46,%47,%48,%49,%50,%51,%52,%53,%54,%55,%56,%57,%58,%59,%60,%61,%62,%63,%64,%65,%66,%67,%68,%69,%70,%71,%72,%73,%74,%75,%76,%77,%78,%79,%80,%81,%82,%83,%84,%85,%86,%87}, %88, %89, p, 1, 1, 1, 0;}"
    : "+f"(d[0]),"+f"(d[1]),"+f"(d[2]),"+f"(d[3]),"+f"(d[4]),"+f"(d[5]),"+f"(d[6]),"+f"(d[7]),"+f"(d[8]),"+f"(d[9]),"+f"(d[10]),"+f"(d[11]),"+f"(d[12]),"+f"(d[13]),"+f"(d[14]),"+f"(d[15]),"+f"(d[16]),"+f"(d[17]),"+f"(d[18]),"+f"(d[19]),"+f"(d[20]),"+f"(d[21]),"+f"(d[22]),"+f"(d[23]),"+f"(d[24]),"+f"(d[25]),"+f"(d[26]),"+f"(d[27]),"+f"(d[28]),"+f"(d[29]),"+f"(d[30]),"+f"(d[31]),"+f"(d[32]),"+f"(d[33]),"+f"(d[34]),"+f"(d[35]),"+f"(d[36]),"+f"(d[37]),"+f"(d[38]),"+f"(d[39]),"+f"(d[40]),"+f"(d[41]),"+f"(d[42]),"+f"(d[43]),"+f"(d[44]),"+f"(d[45]),"+f"(d[46]),"+f"(d[47]),"+f"(d[48]),"+f"(d[49]),"+f"(d[50]),"+f"(d[51]),"+f"(d[52]),"+f"(d[53]),"+f"(d[54]),"+f"(d[55]),"+f"(d[56]),"+f"(d[57]),"+f"(d[58]),"+f"(d[59]),"+f"(d[60]),"+f"(d[61]),"+f"(d[62]),"+f"(d[63]),"+f"(d[64]),"+f"(d[65]),"+f"(d[66]),"+f"(d[67]),"+f"(d[68]),"+f"(d[69]),"+f"(d[70]),"+f"(d[71]),"+f"(d[72]),"+f"(d[73]),"+f"(d[74]),"+f"(d[75]),"+f"(d[76]),"+f"(d[77]),"+f"(d[78]),"+f"(d[79]),"+f"(d[80]),"+f"(d[81]),"+f"(d[82]),"+f"(d[83]),"+f"(d[84]),"+f"(d[85]),"+f"(d[86]),"+f"(d[87]) : "l"(da), "l"(db), "r"(sc));
}

struct Params { const __nv_bfloat16 *x, *logA, *Aim, *Cr, *Ci, *logdt, *Dskip, *Wg, *Wu, *Wd; uint4* xnT; float2* st; uint2* S; unsigned* flags; };
struct Maps { CUtensorMap x[2], xo, out, wg, wu, wd, hst[2], hld, xt, sld; };

__device__ __forceinline__ void conv_channel(uint32_t cb, int w, int lane, uint32_t (&res)[8], uint32_t sig, int sidx) {
    const int q = lane & 3, g = lane >> 2, gam = g >> 2;
    float acc[64];
    uint2 a[17][2];
    const uint32_t t0 = cb + CH_T + (uint32_t)(14 + 4 * w + (g & 3) - 2 * q) * 280u + gam * 8;
#define LDA(s0, s1) _Pragma("unroll") for (int s = s0; s < s1; s++) { a[s][0] = lds64(t0 + s * 16); a[s][1] = lds64(t0 - 8 * 280 + s * 16); }
#define CT(N, s) wg_rs<N>(acc, a[s][0].x, a[s][0].y, a[s][1].x, a[s][1].y, dU + 4 * (s))
    const uint64_t dU = mkdesc(cb + CH_U, UPLANE, 128, 0);
    LDA(0, 17)
    if (sig) { fence_async_smem(); mbar_arrive(sig); }
    WG_FENCE();
    if (w == 0) STAMP2(52 + 3 * sidx);
    wg_rs_first(acc, a[0][0].x, a[0][0].y, a[0][1].x, a[0][1].y, dU);
    CT(128, 1); CT(120, 2); CT(120, 3); CT(112, 4); CT(112, 5); CT(104, 6); CT(104, 7); CT(96, 8);
    CT(96, 9); CT(88, 10); CT(88, 11); CT(80, 12); CT(80, 13); CT(72, 14); CT(72, 15); CT(64, 16);
#undef CT
#undef LDA
    wg_tt64(acc, mkdesc(cb + CH_A3, 128, 512, 0), mkdesc(cb + CH_B3, 384, 32, 0), 1);
    wg_tt32(acc, mkdesc(cb + CH_A3 + 256, 128, 512, 0), mkdesc(cb + CH_B3 + 128, 384, 32, 0), 1);
    WG_COMMIT();
    if (w == 0) STAMP2(53 + 3 * sidx);
    WG_WAIT(0);
    fence_acc(acc);
    if (w == 0) STAMP2(54 + 3 * sidx);
    const int src1 = (lane & ~3) | ((q + 1) & 3);
    float E[16][2];
    #pragma unroll
    for (int j = 0; j < 16; j++) {
        const float nxt = (j < 15) ? acc[4 * (j + 1) + 2] : 0.f;
        const float sup = (q == 0) ? nxt : acc[4 * j + 2];
        const float v = __shfl_sync(0xffffffffu, sup, src1);
        E[j][0] = acc[4 * j] + acc[4 * j + 3];
        E[j][1] = acc[4 * j + 1] + v;
    }
    const int src2 = gam ? ((lane & 12) | ((q + 3) & 3)) : (16 | (lane & 12) | ((q + 1) & 3));
    const bool c1 = gam && q != 0, c2 = gam && q == 0;
    #pragma unroll
    for (int a2 = 0; a2 < 8; a2++) {
        float y[2];
        #pragma unroll
        for (int e = 0; e < 2; e++) {
            const float sup = c1 ? E[2 * a2][e] : E[2 * a2 + 1][e];
            const float nxt = (a2 < 7) ? E[2 * a2 + 2][e] : 0.f;
            const float keep = c2 ? nxt : (c1 ? E[2 * a2 + 1][e] : E[2 * a2][e]);
            y[e] = keep + __shfl_sync(0xffffffffu, sup, src2);
        }
        res[a2] = pack2(y[1], y[0]);
    }
}

__device__ __forceinline__ void consumer(uint32_t sb, int warp, const Params& P, const Maps& M) {
    const int V = warp >> 2, w = warp & 3, lane = threadIdx.x & 31, q = lane & 3, g = lane >> 2;
    const int c = blockIdx.x;
    const uint32_t bars = sb + OFF_BAR, xb = sb + OFF_X + V * 2 * XBUF;
    {
        float ag[88], au[88];
        define_acc(ag); define_acc(au);
        mbar_wait(bars + 8 * B_FULLW, 0);
        mbar_wait(bars + 8 * (B_FULLX + 2 * V), 0);
        #pragma unroll 1
        for (int st = 0; st < 8; st++) {
            uint64_t dG = mkdesc(sb + OFF_W + (st & 3) * 16384, 0, 1024, 1), dX = mkdesc(xb + (st & 1) * XBUF, 16, 1024, 1);
            uint32_t sig = lane == 0 && (V ? st < 6 : st > 0);
            asm volatile("" : "+l"(dG), "+l"(dX), "+r"(sig) :: "memory");
            if (V ? st < 7 : st > 1) mbar_wait(bars + 8 * (B_TURN + V), st & 1);
            STAMP(40 + 8 * V + st);
            WG_FENCE();
            #pragma unroll
            for (int k = 0; k < 4; k++) {
                if (k == SIGK) mbar_arrive_if(bars + 8 * (B_TURN + 1 - V), sig);
                wg_g1(ag, dG + k * 128, dX + k * 2, k ? 1 : st);
                wg_g1(au, dG + 512 + k * 128, dX + k * 2, k ? 1 : st);
            }
            WG_COMMIT();
            if (st == 6 * V) {
                mbar_wait(bars + 8 * (B_FULLW + ((st + 1) & 3)), V);
                mbar_wait(bars + 8 * (B_FULLX + 2 * V + 1), V);
            } else {
                WG_WAIT(1);
                mbar_arrive_if(bars + 8 * (B_EMPTYW + 2 * V), lane == 0 && st == 6 * V + 1);
                mbar_arrive_if(bars + 8 * (B_EMPTYX + 2 * V), lane == 0 && st == 6 * V + 1);
                WG_WAIT(0);
                mbar_arrive_if(bars + 8 * (B_EMPTYW + (st & 3)), lane == 0);
                mbar_arrive_if(bars + 8 * (B_EMPTYX + 2 * V + (st & 1)), lane == 0);
                if (st < 7) {
                    mbar_wait(bars + 8 * (B_FULLW + ((st + 1) & 3)), (st + 1) >> 2);
                    mbar_wait(bars + 8 * (B_FULLX + 2 * V + ((st + 1) & 1)), ((st + 1) >> 1) & 1);
                }
            }
        }
        WG_WAIT(0);
        fence_acc(ag); fence_acc(au);
        STAMP(8 * V + 1);
        float cg0 = ag[84], cg1 = ag[86], cu0 = au[84], cu1 = au[86];
        const uint32_t ca = sb + OFF_CSUM + (8 * w + g) * 16;
        if (V == 0) { sts128(ca, FU(cg0), FU(cg1), FU(cu0), FU(cu1)); mbar_arrive(bars + 8 * B_CS); }
        else { mbar_wait(bars + 8 * B_CS, 0); const uint4 t = lds128(ca); cg0 = UF(t.x); cg1 = UF(t.y); cu0 = UF(t.z); cu1 = UF(t.w); }
        mbar_wait(bars + 8 * B_STATS, 0);
        mbar_wait(bars + 8 * (B_EMPTYX + 2 * V), 1);
        STAMP(13 + V);
        const uint32_t hs = xb + (2 * w + ((lane >> 3) & 1)) * (2688 + 128 * V) + (lane >> 4) * 128 + (lane & 7) * 16;
        const uint32_t sa = sb + OFF_ST + (168 * V + 2 * q) * 8;
        uint4 sq[22];
        #pragma unroll
        for (int j = 0; j < 3; j++) sq[j] = lds128(sa + j * 64);
        #pragma unroll
        for (int j = 0; j < 22; j += 2) {
            uint32_t o[4];
            #pragma unroll
            for (int jj = 0; jj < 2; jj++) {
                const uint4 sv = sq[j + jj];
                float hv[4];
                #pragma unroll
                for (int i = 0; i < 4; i++) {
                    const float m = UF((i & 1) ? sv.z : sv.x);
                    const float gh = fmaf(-m, (i & 2) ? cg1 : cg0, ag[4 * (j + jj) + i]) * UF((i & 1) ? sv.w : sv.y);
                    const float p = gh * fmaf(-m, (i & 2) ? cu1 : cu0, au[4 * (j + jj) + i]);
                    hv[i] = fmaf(p, tanh_fast(gh), p);
                }
                o[2 * jj] = pack2(hv[0], hv[1]); o[2 * jj + 1] = pack2(hv[2], hv[3]);
            }
            #pragma unroll
            for (int k = (j ? 3 + 3 * j / 2 : 3); k < 6 + 3 * j / 2 && k < 22; k++) sq[k] = lds128(sa + k * 64);
            uint32_t ad = hs + j * 128;
            if (j == 20 && V == 0 && lane >= 16) ad = xb + 21504 + (lane & 7) * 16;
            stsm4(ad, o[0], o[1], o[2], o[3]);
        }
        if (c >= 128 || V) { fence_async_smem(); mbar_arrive(bars + 8 * (B_EPI + V)); }
        STAMP(8 * V + 2);
    }
    if (c >= 128) return;
    {
        uint32_t r0[8], r1[8];
        #pragma unroll
        for (int i = 0; i < 8; i++) asm volatile("" : "=r"(r1[i]));
        #pragma unroll 1
        for (int e = 0; e < 2; e++) {
            #pragma unroll
            for (int i = 0; i < 8; i++) r0[i] = r1[i];
            mbar_wait(bars + 8 * (B_CONV + 2 * V + e), 0);
            conv_channel(sb + OFF_CONV + (2 * V + e) * CH_STRIDE, w, lane, r1, (e | V) ? 0 : bars + 8 * B_EPI, 2 * V + e);
            if (e == 0) STAMP(8 * V + 3);
        }
        const int gam = g >> 2, qq = gam ? ((q + 3) & 3) : q;
        const uint32_t sp = sb + OFF_CONV + V * OFF_SST + ((63 - 4 * gam - qq) * 16 + 4 * (w ^ (3 - qq)) + (g & 3)) * 8;
        bar_sync(3 + V);
        #pragma unroll
        for (int a2 = 0; a2 < 8; a2++) sts64(sp - a2 * 1024, r0[a2], r1[a2]);
        fence_async_smem();
        mbar_arrive(bars + 8 * (B_SIG + V));
        STAMP(8 * V + 4);
    }
    if (V == 1) return;
    {
        const int tau = c >> 2, dg = c & 3;
        const uint32_t row = 8 * (w & 1) + 32 * (w >> 1);
        float acc[64];
        define_acc(acc);
        const float rr0 = __ldcg(&P.st[64 * tau + row + g].y), rr1 = __ldcg(&P.st[64 * tau + row + g + 16].y);
        mbar_wait(bars + 8 * B_FULLD, 0);
        STAMP(5);
        uint64_t dB = mkdesc(sb + wd_slot(0), 8192, 1024, 1), dA = mkdesc(sb + h_slot(0), 1024, 128, 0);
        #pragma unroll 1
        for (int st = 0; st < 21; st++) {
            WG_FENCE();
            wg_tt128(acc, dA, dB, st);
            wg_tt128(acc, dA + 128, dB + 128, 1);
            wg_tt128(acc, dA + 256, dB + 256, 1);
            wg_tt128(acc, dA + 384, dB + 384, 1);
            WG_COMMIT();
            const int sd = (st + 1) & 7;
            const uint32_t nb = bars + 8 * (B_FULLD + sd), np = ((st + 1) >> 3) & 1;
            uint32_t ro = st == 15 ? 8 * B_CH0 : 8 * (B_EMPTYD + ((st - 1) & 7)), m = lane == 0 && st > 0, ok;
            dB = mkdesc(sb + wd_slot(sd), 8192, 1024, 1); dA = mkdesc(sb + h_slot(sd), 1024, 128, 0);
            asm volatile("{.reg .pred p; mbarrier.test_wait.parity.shared::cta.b64 p, [%5], %6; vote.sync.all.pred p, p, -1; selp.u32 %0, 1, 0, p;}"
                : "=r"(ok), "+l"(dA), "+l"(dB), "+r"(ro), "+r"(m) : "r"(nb), "r"(np) : "memory");
            WG_WAIT(1);
            mbar_arrive_if(bars + ro, m);
            if (!ok) mbar_wait(nb, np);
            if (w == 0) STAMP2(20 + st);
        }
        WG_FENCE();
        wg_tt128(acc, dA, dB, 1);
        wg_tt128(acc, dA + 128, dB + 128, 1);
        WG_COMMIT();
        mbar_wait(bars + 8 * B_XO, 0);
        const uint32_t xo = sb + OFF_CONV + (row + (lane & 7) + 16 * ((lane >> 3) & 1)) * 128;
        const uint32_t so = sb + wd_slot(6) + (w >> 1) * 8192 + q * 256 + (g & 1) * 8;
        const uint32_t sx = (4 * (w & 1) + (g >> 1)) ^ (2 * q) ^ (2 * ((2 * tau + (w >> 1)) & 3));
        uint32_t xr[8][4];
        uint2 sv[16];
        #pragma unroll
        for (int j = 0; j < 16; j += 2) {
            ldsm4(xr[j >> 1], xo + (j >> 3) * 8192 + ((((j & 7) + (lane >> 4)) ^ (lane & 7)) << 4));
            sv[j] = lds64(so + j * 512 + (sx << 4));
            sv[j + 1] = lds64(so + j * 512 + 128 + ((sx ^ 1) << 4));
        }
        WG_WAIT(0);
        fence_acc(acc);
        STAMP(6);
        #pragma unroll
        for (int j = 0; j < 16; j += 2) {
            #pragma unroll
            for (int i = 0; i < 4; i++) {
                const int jj = j + (i >> 1), hh = i & 1;
                const float f0 = acc[4 * jj + 2 * hh] * (hh ? rr1 : rr0), f1 = acc[4 * jj + 2 * hh + 1] * (hh ? rr1 : rr0);
                const uint32_t G = pack2(fmaf(f0, tanh_fast(f0), f0), fmaf(f1, tanh_fast(f1), f1));
                const uint32_t s2 = __byte_perm(sv[jj].x, sv[jj].y, hh ? 0x7632 : 0x5410);
                asm("fma.rn.bf16x2 %0, %1, %2, %0;" : "+r"(xr[j >> 1][i]) : "r"(s2), "r"(G));
            }
            stsm4(xo + (j >> 3) * 8192 + ((((j & 7) + (lane >> 4)) ^ (lane & 7)) << 4), xr[j >> 1][0], xr[j >> 1][1], xr[j >> 1][2], xr[j >> 1][3]);
        }
        fence_async_smem();
        bar_sync(1);
        if (w == 0 && elect_one()) {
            #pragma unroll
            for (int i = 0; i < 2; i++)
                asm volatile("cp.async.bulk.tensor.2d.global.shared::cta.bulk_group [%0, {%2, %3}], [%1];"
                    :: "l"(&M.out), "r"(sb + OFF_CONV + i * 8192), "r"(dg * 128 + 64 * i), "r"(tau * 64) : "memory");
            asm volatile("cp.async.bulk.commit_group; cp.async.bulk.wait_group.read 0;" ::: "memory");
        }
        STAMP(7); GSTAMP(23);
    }
}

__device__ __forceinline__ float2 cexp_p(float re2, float im, float p) {
    float sn, cs;
    const float mag = ex2(re2 * p), th = im * p;
    asm("sin.approx.ftz.f32 %0, %1;" : "=f"(sn) : "f"(th));
    asm("cos.approx.ftz.f32 %0, %1;" : "=f"(cs) : "f"(th));
    return make_float2(mag * cs, mag * sn);
}
struct SsmRaw { unsigned short la, ai, cr, ci, ldt, dsk; };
__device__ __forceinline__ unsigned short ldu16(const void* p) { unsigned short v; asm volatile("ld.global.nc.u16 %0, [%1];" : "=h"(v) : "l"(p)); return v; }
__device__ __forceinline__ float2 cmul(float2 a, float2 b) { return make_float2(fmaf(a.x, b.x, -a.y * b.y), fmaf(a.x, b.y, a.y * b.x)); }
__device__ __forceinline__ float2 csqr(float2 a) { const float t = a.x * a.y; return make_float2(fmaf(a.x, a.x, -a.y * a.y), t + t); }
__device__ __forceinline__ void mma16816(float (&d)[4], const uint32_t (&a)[4], uint32_t b0, uint32_t b1) {
    asm volatile("mma.sync.aligned.m16n8k16.row.col.f32.bf16.bf16.f32 {%0,%1,%2,%3}, {%4,%5,%6,%7}, {%8,%9}, {%0,%1,%2,%3};"
        : "+f"(d[0]), "+f"(d[1]), "+f"(d[2]), "+f"(d[3]) : "r"(a[0]), "r"(a[1]), "r"(a[2]), "r"(a[3]), "r"(b0), "r"(b1));
}

__device__ __forceinline__ void layer_norm(uint32_t sb, uint32_t cb, int w, int lane) {
    const uint32_t bars = sb + OFF_BAR;
    mbar_wait(bars + 8 * B_LNX, 0);
    STAMP(34);
    {
        const uint32_t r0 = cb + CH_LN + (w & 1) * 64 + (lane >> 3) * 1040, ra = r0 + (lane & 7) * 16;
        const float pv = bf_lo(FU(ldsf(r0)));
        float s0 = 0.f, s1 = 0.f, a0 = 0.f, a1 = 0.f;
        #pragma unroll 1
        for (int k = 0; k < 1024; k += 512) {
            uint32_t v[16];
            #pragma unroll
            for (int j = 0; j < 4; j++) *(uint4*)&v[4 * j] = lds128(ra + k + 128 * j);
            #pragma unroll
            for (int i = 0; i < 16; i++) { const float t0 = bf_lo(v[i]) - pv, t1 = bf_hi(v[i]) - pv; s0 += t0; s1 += t1; a0 = fmaf(t0, t0, a0); a1 = fmaf(t1, t1, a1); }
        }
        s0 += s1; a0 += a1;
        #pragma unroll
        for (int o = 4; o; o >>= 1) { s0 += __shfl_xor_sync(0xffffffffu, s0, o); a0 += __shfl_xor_sync(0xffffffffu, a0, o); }
        s0 *= 1.f / DM;
        float sd, ri;
        asm("sqrt.approx.ftz.f32 %0, %1;" : "=f"(sd) : "f"(bf_round(bf_round(fmaxf(fmaf(-s0, s0, a0 * (1.f / DM)), 0.f)) + 1e-5f)));
        asm("rcp.approx.ftz.f32 %0, %1;" : "=f"(ri) : "f"(bf_round(sd)));
        if ((lane & 7) == 0) sts64(sb + OFF_CSUM + (w + 4 * (lane >> 3)) * 8, FU(bf_round(pv + s0)), FU(0.5f * ri));
    }
    STAMP(62);
    bar_sync(2);
    const int r = 4 * ((lane & 7) >> 1) + (lane & 1) + 2 * ((lane >> 3) & 1);
    const uint32_t ad = sb + OFF_CONV + (r & 3) * CH_STRIDE + CH_LN + (r & 1) * 64 + (r >> 2) * 1040 + (16 * w + (lane >> 4)) * 16;
    const uint4 sa = lds128(sb + OFF_CSUM + (lane & 3) * 32), sc = lds128(sb + OFF_CSUM + (lane & 3) * 32 + 16);
    const uint32_t m2[2] = {__byte_perm(sa.x, sa.z, 0x7632), __byte_perm(sc.x, sc.z, 0x7632)};
    const float ri[4] = {2.f * UF(sa.y), 2.f * UF(sa.w), 2.f * UF(sc.y), 2.f * UF(sc.w)};
    #pragma unroll 1
    for (int i = 0; i < 8; i += 4) {
        uint32_t v[4][4];
        #pragma unroll
        for (int j = 0; j < 4; j++)
            asm volatile("ldmatrix.sync.aligned.m8n8.x4.trans.shared.b16 {%0,%1,%2,%3}, [%4];" : "=r"(v[j][0]), "=r"(v[j][1]), "=r"(v[j][2]), "=r"(v[j][3]) : "r"(ad + 32 * (i + j)) : "memory");
        #pragma unroll
        for (int j = 0; j < 4; j++) {
            #pragma unroll
            for (int k = 0; k < 4; k++) {
                uint32_t dv; asm("sub.rn.bf16x2 %0, %1, %2;" : "=r"(dv) : "r"(v[j][k]), "r"(m2[k & 1]));
                v[j][k] = pack2(bf_lo(dv) * ri[2 * (k & 1)], bf_hi(dv) * ri[2 * (k & 1) + 1]);
            }
            sts64(cb + CH_LNT + lane * 8 + (i + j) * 512, v[j][0], v[j][1]); sts64(cb + CH_LNT + lane * 8 + (i + j) * 512 + 256, v[j][2], v[j][3]);
        }
    }
    fence_async_smem();
    mbar_arrive(bars + 8 * B_LN);
    STAMP(16);
}

__device__ __forceinline__ void kernel_gen(uint32_t fs, int lane, const SsmRaw& raw, float (&dacc)[2][3][4], const Params& P, int warp) {
    const float dt = bf_round(ex2(bf_lo(raw.ldt) * 1.4426950408889634f));
    const float re2 = bf_round(ex2(bf_lo(raw.la) * 1.4426950408889634f)) * dt * -1.4426950408889634f, im = bf_lo(raw.ai) * dt;
    const float2 C = make_float2(bf_lo(raw.cr) * (dt + dt), bf_lo(raw.ci) * -(dt + dt));
    STAMP(56);
    if (warp < 4 && lane == 0 && re2 != 1.f) {
        const int c = blockIdx.x;
        const char* p = warp < 2 ? (const char*)(P.x + (16 * (c & ~1) + 8 * (c & 1) + 16 * warp) * DM) : (const char*)(warp == 2 ? P.Wg : P.Wu) + 256 * FF * 2 + c * 5504;
        asm volatile("cp.async.bulk.prefetch.L2.global [%0], %1;" :: "l"(p), "r"(warp < 2 ? 8192 : 5504) : "memory");
    }
    const float2 y1 = cexp_p(re2, -im, 1.f), y256 = cexp_p(re2, -im, 256.f), z64 = cexp_p(re2, im, 64.f);
    const uint32_t fm = fs + (lane >> 3) * 144 + (lane & 7) * 16;
#define PK(v) pack2((v).x, (v).y)
    const float2 y2 = csqr(y1), y4 = csqr(y2), y8 = csqr(y4);
    const float2 l1 = cmul(C, y1), l2 = cmul(C, y2), l3 = cmul(l1, y2);
    stsm4(fm, PK(C), PK(l1), PK(l2), PK(l3));
    stsm4(fm + 4 * 144, PK(cmul(C, y4)), PK(cmul(l1, y4)), PK(cmul(l2, y4)), PK(cmul(l3, y4)));
    const float2 t0 = cmul(C, y256), t1 = cmul(t0, y256), t2 = cmul(t1, y256), t3_ = cmul(t2, y256);
    const float2 u1 = cmul(t0, y2), u2 = cmul(u1, y2), u3 = cmul(u2, y2);
    stsm4(fm + 8 * 144, PK(t0), PK(u1), PK(u2), PK(u3));
    stsm4(fm + 12 * 144, PK(t1), PK(cmul(t1, y4)), PK(t2), PK(cmul(t2, y4)));
    const float2 v0 = cmul(t3_, y8), v1 = cmul(v0, y256), v2 = cmul(v1, y256), v3 = cmul(v2, y256);
    stsm4(fm + 16 * 144, PK(v0), PK(v1), PK(v2), PK(v3));
    stsf(fs + lane * 4 + 20 * 144, UF(PK(t3_)));
    STAMP(57);
    const uint32_t ldb = fs + (lane & 7) * 144 + ((lane >> 3) & 1) * 16 + (lane >> 4) * 8 * 144;
    const float p8 = (float)(2 * (lane & 28));
    __syncwarp();
    #pragma unroll 1
    for (int ks = 0; ks < 4; ks++) {
        uint32_t b01[4], b2[2], a0[4], a1[4];
        ldsm4(b01, ldb + ks * 32);
        asm volatile("ldmatrix.sync.aligned.m8n8.x2.shared.b16 {%0,%1}, [%2];" : "=r"(b2[0]), "=r"(b2[1]) : "r"(ldb + 16 * 144 + ks * 32) : "memory");
        #pragma unroll
        for (int mh = 0; mh < 2; mh++) {
            const int src = 8 * ks + 4 * mh + (lane & 3);
            const float2 z = make_float2(__shfl_sync(0xffffffffu, z64.x, src), __shfl_sync(0xffffffffu, z64.y, src));
            const float2 R0 = cexp_p(__shfl_sync(0xffffffffu, re2, src), __shfl_sync(0xffffffffu, im, src), p8);
            const float2 R1 = cmul(R0, z), R2 = cmul(R1, z), R3 = cmul(R2, z);
            a0[2 * mh] = PK(R0); a0[2 * mh + 1] = PK(R1); a1[2 * mh] = PK(R2); a1[2 * mh + 1] = PK(R3);
        }
        mma16816(dacc[0][0], a0, b01[0], b01[1]); mma16816(dacc[1][0], a1, b01[0], b01[1]);
        mma16816(dacc[0][1], a0, b01[2], b01[3]); mma16816(dacc[1][1], a1, b01[2], b01[3]);
        mma16816(dacc[0][2], a0, b2[0], b2[1]);   mma16816(dacc[1][2], a1, b2[0], b2[1]);
    }
#undef PK
    STAMP(58);
}

__device__ __forceinline__ void aux_role(uint32_t sb, int w, float (&dacc)[2][3][4], float dsk, const __nv_bfloat16* x) {
    const int lane = threadIdx.x & 31, q = lane & 3, g = lane >> 2;
    const int c = blockIdx.x;
    const uint32_t bars = sb + OFF_BAR;
    if (c >= 128) { mbar_arrive(bars + 8 * B_LN); return; }
    {
        const uint32_t cb = sb + OFF_CONV + w * CH_STRIDE;
        if (elect_one()) {
            fence_async_smem();
            mbar_expect(bars + 8 * B_LNX, 4096);
            #pragma unroll
            for (int i = 0; i < 4; i++)
                bulk_load(cb + CH_LN + (w & 1) * 64 + i * 1040, x + (16 * (c & ~1) + 8 * (c & 1) + 16 + w + 4 * (i & 1) - 8 * (i & 2)) * DM, 1024, bars + 8 * B_LNX);
        }
        #pragma unroll 1
        for (uint32_t pa = cb + CH_PART + lane * 16; pa < cb + CH_PART + 3 * 3456; pa += 3456) {
            #pragma unroll
            for (int i = 0; i < 6; i++) {
                const uint4 v = lds128(pa + i * 512);
                float* d = &dacc[0][0][0] + 4 * i;
                d[0] += UF(v.x); d[1] += UF(v.y); d[2] += UF(v.z); d[3] += UF(v.w);
            }
        }
        __syncwarp();
        STAMP(18);
        const uint32_t sF = cb + CH_A3, sG = cb + CH_G;
        if (lane == 0) dacc[0][0][0] += dsk;
        if (lane < 10) sts128(sG + 128 + (lane & 1) * 208 + (lane >> 1) * 16, 0, 0, 0, 0);
        const uint32_t f0 = sF + (8 * g + 2 * q) * 4, f1 = sF + ((q < 2) ? 256 + 4 * g + 2 * q : 256 + 2 * g + 64 * q) * 4, st1 = (q < 2) ? 128 : 64;
        const uint32_t ga = sG + ((g & 1) ? 0 : 208) + (63 - (g >> 1) - 32 * q) * 2;
        #pragma unroll
        for (int i = 0; i < 4; i++) {
            const int mu = i >> 1, hh = i & 1;
            sts64(f0 + i * 256, FU(dacc[mu][0][2 * hh]), FU(dacc[mu][0][2 * hh + 1]));
            sts64(f1 + i * st1, FU(dacc[mu][1][2 * hh]), FU(dacc[mu][1][2 * hh + 1]));
            const uint32_t pk = pack2(dacc[mu][2][2 * hh], dacc[mu][2][2 * hh + 1]);
            if (q < 2) { sts16(ga - 8 * i, pk & 0xffff); sts16(ga - 8 * i - 32, pk >> 16); }
        }
        if (lane == 2) stsf(sF + 2048, dacc[0][2][0]);
        STAMP(19);
        layer_norm(sb, cb, w, lane);
        mbar_wait(bars + 8 * B_LN, 0);
    }
    const int u = min(lane, 30) - 15, r2 = (u + ((u >> 1) & 1)) >> 1, r4 = (u + 1 + ((u >> 2) & 1)) >> 2, xt = 1024 + 16 * w + u;
    const uint32_t o0 = CH_A3 + 4 * (w == 0 ? u : w == 1 ? 256 + r2 : 256 + 64 * w + r4), ost = w == 0 ? 64 : w == 1 ? 32 : 16;
    const uint32_t oa0 = u >= 0 || w == 3 ? o0 : CH_A3 + 4 * (w == 1 ? 256 + u : w == 2 ? 384 + r2 : 0);
    const uint32_t ot = CH_A3 + 4 * min(512, 256 + ((xt + 1 + ((xt >> 2) & 1)) >> 2));
    const int kap = (lane >> 4) * 8 + ((lane >> 1) & 7), gam = lane & 1, hh = w >> 1, wp = w & 1;
    const uint32_t oa = CH_U + wp * UPLANE + (127 - 4 * kap - 2 * gam - hh) * 16;
    const uint32_t ob = CH_U + (wp ^ 1) * UPLANE + (128 - wp - 4 * kap - 2 * gam - hh) * 16;
    const uint32_t od = CH_A3 + (4 * wp + hh) * 512 + (kap >> 3) * 256 + (kap & 7) * 16 + gam * 8;
    #pragma unroll 1
    for (uint32_t cb = sb + OFF_CONV; cb < sb + OFF_CONV + 4 * CH_STRIDE; cb += CH_STRIDE) {
        {
            float kv[17];
            kv[0] = ldsf(cb + oa0); kv[16] = ldsf(cb + ot);
            #pragma unroll
            for (int s = 1; s < 16; s++) kv[s] = ldsf(cb + o0 + s * ost);
            const int tid = threadIdx.x & 127;
            const uint32_t ga = cb + CH_G + (tid >= 24) * 16 + min(tid, 47) * 8;
            const uint2 x0 = lds64(ga), x1 = lds64(ga + 8);
            if (u < 0 && w == 0) kv[0] = 0.f;
            if (xt > 1028) kv[16] = 0.f;
            uint32_t o[17];
            #pragma unroll
            for (int s = 0; s < 17; s++) o[s] = pack2(kv[s], __shfl_up_sync(0xffffffffu, kv[s], 1));
            if (lane > 0 && lane < 31) {
                const uint32_t ta = cb + CH_T + (lane - 1) * 280;
                #pragma unroll
                for (int s2 = 0; s2 < 8; s2++) sts64(ta + 64 * w + s2 * 8, o[2 * s2], o[2 * s2 + 1]);
                stsf(ta + 256 + 4 * w, UF(o[16]));
            }
            if (tid < 48) sts128(cb + CH_B3 + tid * 16, x0.x, x0.y, x1.x, x1.y);
        }
    }
    STAMP(61);
    mbar_wait(bars + 8 * B_U, 0);
    if (lane < 8) sts128(sb + OFF_CONV + w * CH_STRIDE + CH_U + 2048 + (lane & 4) * (UPLANE / 4) + (lane & 3) * 16, 0, 0, 0, 0);
    bar_sync(2);
    #pragma unroll 1
    for (int k = 0; k < 4; k++) {
        const int ch = 2 * (k & 1) + (k >> 1);
        const uint32_t cb = sb + OFF_CONV + ch * CH_STRIDE;
        float p[24];
        const uint2 r0 = lds64(cb + ob + 24), r3 = lds64(cb + oa);
        uint32_t r[8];
        *(uint4*)&r[0] = lds128(cb + oa + 16); *(uint4*)&r[4] = lds128(cb + ob);
        p[0] = 0.f;
        p[1] = bf_lo(r0.x); p[2] = p[1] + bf_hi(r0.x); p[3] = p[2] + bf_lo(r0.y); p[4] = p[3] + bf_hi(r0.y);
        #pragma unroll
        for (int i = 0; i < 8; i++) { p[5 + 2 * i] = p[4 + 2 * i] + bf_lo(r[i]); p[6 + 2 * i] = p[5 + 2 * i] + bf_hi(r[i]); }
        p[21] = p[20] + bf_lo(r3.x); p[22] = p[21] + bf_hi(r3.x); p[23] = p[22] + bf_lo(r3.y);
        #pragma unroll
        for (int i = 0; i < 8; i += 4) {
            sts64(cb + od + i * 256, pack2(p[i + 9] - p[i], p[i + 10] - p[i + 1]), pack2(p[i + 11] - p[i + 2], p[i + 12] - p[i + 3]));
            sts64(cb + od + i * 256 + 128, pack2(p[i + 16] - p[i + 9], p[i + 17] - p[i + 10]), pack2(p[i + 18] - p[i + 11], p[i + 19] - p[i + 12]));
        }
        fence_async_smem();
        mbar_arrive(bars + 8 * (B_CONV + ch));
        if (k == 0) STAMP(17);
    }
    STAMP(21);
}

__device__ __forceinline__ void store_h(uint32_t sb, const Params& P, const Maps& M, int V, int tg, int fb) {
    const uint32_t bars = sb + OFF_BAR;
    mbar_wait(bars + 8 * (B_EPI + V), 0);
    STAMP2(3 + 2 * V);
    asm volatile("cp.async.bulk.tensor.3d.global.shared::cta.bulk_group [%0, {%2, %3, %4}], [%1];"
        :: "l"(&M.hst[V]), "r"(sb + OFF_X + V * 2 * XBUF), "r"(0), "r"(43 * tg + 21 * V), "r"(8 * fb) : "memory");
    flag_signal(P.flags, F_H + 2 * tg + V);
    mbar_arrive(bars + 8 * (B_STG + V));
    STAMP2(4 + 2 * V);
}

__global__ void __launch_bounds__(512, 1)
fused_kernel(const __grid_constant__ Params P, const __grid_constant__ Maps M) {
    extern __shared__ __align__(1024) uint8_t smem_raw[];
    const uint32_t sb = smem_u32(smem_raw);
    const uint32_t bars = sb + OFF_BAR;
    const int warp = __shfl_sync(0xffffffffu, threadIdx.x >> 5, 0);
    const int c = blockIdx.x, tg = c / 22, fb = c - 22 * tg;
    SsmRaw raw;
    {
        const int d = min(4 * c + (warp & 3), DM - 1), o = d * 128 + (warp >> 2) * 32 + (threadIdx.x & 31);
        raw.la = ldu16(P.logA + o); raw.ai = ldu16(P.Aim + o); raw.cr = ldu16(P.Cr + o); raw.ci = ldu16(P.Ci + o);
        raw.ldt = ldu16(P.logdt + d); raw.dsk = ldu16(P.Dskip + d);
    }
    if (elect_one()) {
        if (warp == 0) { STAMP(24); GSTAMP(22); }
        asm volatile("" :: "l"(((const uint64_t*)&P)[warp < 14 ? warp : 0]));
        if (warp < 12) asm volatile("prefetch.tensormap [%0];" :: "l"(&M.x[0] + warp) : "memory");
        #pragma unroll
        for (int k = 0; k < 4; k++) {
            const int i = 16 * k + ((warp + 4) & 15);
            const uint32_t cnt = i >= B_CONV ? 128 : ((0xf0ull >> i) & 1) ? 8 : ((0xff0000ull >> i) & 1) ? 2 : ((0x3e00ff00f000ull >> i) & 1) ? 4 : 1;
            asm volatile("mbarrier.init.shared::cta.b64 [%0], %1;" :: "r"(bars + 8 * i), "r"(cnt) : "memory");
        }
        asm volatile("fence.mbarrier_init.release.cluster; fence.proxy.async.shared::cta;" ::: "memory");
        if (warp >= 12) {
            const uint32_t s = warp - 12;
            mbar_expect(bars + 8 * (B_FULLW + s), 16384);
            tma2d(sb + OFF_W + s * 16384, &M.wg, 64 * fb, 64 * s, bars + 8 * (B_FULLW + s));
            tma2d(sb + OFF_W + s * 16384 + 8192, &M.wu, 64 * fb, 64 * s, bars + 8 * (B_FULLW + s));
            STAMP(31);
        } else if ((warp >> 2) == 1) {
            const uint32_t s = warp - 4, V = s >> 1;
            mbar_expect(bars + 8 * (B_FULLX + s), (168 + 8 * V) * 128);
            tma2d(sb + OFF_X + s * XBUF, &M.x[V], 64 * (s & 1), TOKG * tg + 168 * V, bars + 8 * (B_FULLX + s));
        }
        if (sb & 1023) __trap();
    }
    if (warp < 4) sts128(sb + OFF_X + (warp >> 1) * XBUF + 168 * 128 + (threadIdx.x & 63) * 16, 0x3f803f80u, 0x3f803f80u, 0x3f803f80u, 0x3f803f80u);
    float dacc[2][3][4];
    #pragma unroll
    for (int i = 0; i < 24; i++) (&dacc[0][0][0])[i] = 0.f;
    if (c < 128) {
        const int wg = warp >> 2;
        const uint32_t fs = sb + OFF_CONV + (warp & 3) * CH_STRIDE + (wg == 2 ? 0 : CH_PART + min(wg, 2) * 3456);
        kernel_gen(fs, threadIdx.x & 31, raw, dacc, P, warp);
        if (wg != 2) {
            __syncwarp();
            #pragma unroll
            for (int i = 0; i < 6; i++) { const float* d = &dacc[0][0][0] + 4 * i; sts128(fs + (threadIdx.x & 31) * 16 + i * 512, FU(d[0]), FU(d[1]), FU(d[2]), FU(d[3])); }
        }
    }
    if (warp < 4) fence_async_smem();
    __syncthreads();
    if (warp < 8) {
        asm volatile("setmaxnreg.inc.sync.aligned.u32 208;");
        consumer(sb, warp, P, M);
        asm volatile("nanosleep.u32 1;");
    } else if (warp < 12) {
        asm volatile("setmaxnreg.dec.sync.aligned.u32 72;");
        STAMP(32);
        aux_role(sb, warp - 8, dacc, bf_lo(raw.dsk), P.x);
        asm volatile("nanosleep.u32 2;");
    } else {
        asm volatile("setmaxnreg.dec.sync.aligned.u32 24;");
        const int tau = c >> 2, dg = c & 3;
        if (elect_one()) {
            if (warp < 15) {
                if (warp == 12) {
                    #pragma unroll 1
                    for (int st = 4; st < 8; st++) {
                        const uint32_t s = st & 3, fb_ = bars + 8 * (B_FULLW + s);
                        mbar_wait(bars + 8 * (B_EMPTYW + s), 0);
                        mbar_expect(fb_, 16384);
                        tma2d(sb + OFF_W + s * 16384, &M.wg, 64 * fb, 64 * st, fb_);
                        tma2d(sb + OFF_W + s * 16384 + 8192, &M.wu, 64 * fb, 64 * st, fb_);
                    }
                } else {
                    const int V = warp - 13;
                    #pragma unroll 1
                    for (int st = 2; st < 8; st++) {
                        const uint32_t s = 2 * V + (st & 1);
                        mbar_wait(bars + 8 * (B_EMPTYX + s), ((st >> 1) & 1) ^ 1);
                        mbar_expect(bars + 8 * (B_FULLX + s), (168 + 8 * V) * 128);
                        tma2d(sb + OFF_X + s * XBUF, &M.x[V], 64 * st, TOKG * tg + 168 * V, bars + 8 * (B_FULLX + s));
                    }
                }
                if (warp == 14) store_h(sb, P, M, 1, tg, fb);
                if (c < 128 && warp < 14) {
                    if (warp == 13) {
                        mbar_wait(bars + 8 * (B_STG + 1), 0);
                        #pragma unroll 1
                        for (int o = 8 * tau; o < 8 * tau + 8; o += 7) flag_wait(P.flags, F_H + 2 * (o / 43) + ((o % 43) >= 21), 22);
                        mbar_arrive(bars + 8 * B_HF);
                        STAMP(25);
                    }
                    #pragma unroll 1
                    for (int st = 0; st < 22; st += (st < 7 || (st == 7 && warp == 12)) ? 1 : 2) {
                        const int sd = st & 7;
                        const uint32_t fb_ = bars + 8 * (B_FULLD + sd);
                        if (st >= 8) mbar_wait(bars + 8 * (B_EMPTYD + sd), ((st >> 3) & 1) ^ 1);
                        else if (warp == 12 || st >= 6) mbar_wait(bars + 8 * (uint32_t)((0x373623070d060504ull >> (8 * st)) & 0xff), st < 5);
                        if (st >= 10 && st < 21) STAMP2(31 + st);
                        if (st >= 8 || warp == 13) {
                            mbar_expect(fb_, 8192);
                            asm volatile("cp.async.bulk.tensor.5d.shared::cluster.global.mbarrier::complete_tx::bytes [%0], [%1, {%3, %3, %3, %4, %5}], [%2];"
                                :: "r"(sb + h_slot(sd)), "l"(&M.hld), "r"(fb_), "r"(0), "r"(2 * tau), "r"(8 * st) : "memory");
                        }
                        if (st >= 8 || warp == 12) {
                            const uint32_t da = sb + wd_slot(sd);
                            mbar_expect(fb_, 16384);
                            tma2d(da, &M.wd, 128 * dg, 64 * st, fb_);
                            tma2d(da + 8192, &M.wd, 128 * dg + 64, 64 * st, fb_);
                        }
                    }
                } else if (c < 128) {
                    mbar_wait(bars + 8 * B_SST, 0);
                    flag_wait(P.flags, F_S + dg, 64);
                    STAMP(26);
                    mbar_wait(bars + 8 * B_CH0, 0);
                    mbar_expect(bars + 8 * B_XO, 32768);
                    tma2d(sb + OFF_CONV, &M.xo, 128 * dg, 64 * tau, bars + 8 * B_XO);
                    tma2d(sb + OFF_CONV + 8192, &M.xo, 128 * dg + 64, 64 * tau, bars + 8 * B_XO);
                    asm volatile("cp.async.bulk.tensor.5d.shared::cluster.global.mbarrier::complete_tx::bytes [%0], [%1, {%3, %3, %3, %4, %5}], [%2];"
                        :: "r"(sb + wd_slot(6)), "l"(&M.sld), "r"(bars + 8 * B_XO), "r"(0), "r"(8 * dg), "r"(2 * tau) : "memory");
                    mbar_wait(bars + 8 * B_HF, 0);
                    exit_count(P.flags);
                }
            } else {
                mbar_wait(bars + 8 * B_LN, 0);
                STAMP2(0);
                if (c < 128) {
                    #pragma unroll 1
                    for (int i = 0; i < 4; i++)
                        asm volatile("cp.async.bulk.tensor.2d.global.shared::cta.bulk_group [%0, {%2, %3}], [%1];"
                            :: "l"(&M.xt), "r"(sb + OFF_CONV + i * CH_STRIDE + CH_LNT), "r"((c & 1) * 1024 + (126 - (c & ~1)) * 8), "r"(128 * i) : "memory");
                    #pragma unroll 1
                    for (int i = 0; i < 2; i++) bulk_store(P.st + 16 * (c & ~1) + 8 * (c & 1) + 16 - 16 * i, sb + OFF_CSUM + 64 * i, 64);
                    asm volatile("cp.async.bulk.prefetch.L2.global [%0], %1;" :: "l"(P.Wd + c * (FF * DM / 128)), "r"(FF * DM / 64) : "memory");
                }
                STAMP2(1);
                flag_signal(P.flags, F_A);
                STAMP2(2);
                flag_wait(P.flags, F_A, NCTA);
                STAMP(20);
                mbar_expect(bars + 8 * B_STATS, TOKG * 8);
                bulk_load(sb + OFF_ST, P.st + TOKG * tg, TOKG * 8, bars + 8 * B_STATS);
                if (c < 128) {
                    mbar_expect(bars + 8 * B_U, 8 * 2048);
                    #pragma unroll 1
                    for (int i = 0; i < 8; i++)
                        bulk_load(sb + OFF_CONV + (i >> 1) * CH_STRIDE + CH_U + (i & 1) * UPLANE, P.xnT + 4 * c * 256 + i * 128, 2048, bars + 8 * B_U);
                } else exit_count(P.flags);
                store_h(sb, P, M, 0, tg, fb);
                if (c < 128) {
                    #pragma unroll 1
                    for (int V = 0; V < 2; V++) {
                        mbar_wait(bars + 8 * (B_SIG + V), 0);
                        STAMP2(7 + 2 * V);
                        bulk_store(P.S + (2 * c + V) * 1024, sb + OFF_CONV + V * OFF_SST, 8192);
                        flag_signal(P.flags, F_S + (c >> 5));
                        STAMP2(8 + 2 * V);
                    }
                    mbar_arrive(bars + 8 * B_SST);
                }
            }
            asm volatile("nanosleep.u32 0;");
        }
    }
}

typedef CUresult (*EncodeFn)(CUtensorMap*, CUtensorMapDataType, cuuint32_t, void*, const cuuint64_t*, const cuuint64_t*, const cuuint32_t*,
                             const cuuint32_t*, CUtensorMapInterleave, CUtensorMapSwizzle, CUtensorMapL2promotion, CUtensorMapFloatOOBfill);

void make_map(EncodeFn enc, CUtensorMap* m, const void* ptr, int rank, const cuuint64_t* dims, const cuuint64_t* strides, const cuuint32_t* box, bool swz, bool wide = false) {
    const cuuint32_t es[5] = {1, 1, 1, 1, 1};
    enc(m, CU_TENSOR_MAP_DATA_TYPE_BFLOAT16, rank, (void*)ptr, dims, strides, box, es, CU_TENSOR_MAP_INTERLEAVE_NONE,
        swz ? CU_TENSOR_MAP_SWIZZLE_128B : CU_TENSOR_MAP_SWIZZLE_NONE, wide ? CU_TENSOR_MAP_L2_PROMOTION_L2_256B : CU_TENSOR_MAP_L2_PROMOTION_L2_128B, CU_TENSOR_MAP_FLOAT_OOB_FILL_NONE);
}
void make_map2(EncodeFn enc, CUtensorMap* m, const void* ptr, cuuint64_t inner, cuuint64_t outer, cuuint32_t rows) {
    const cuuint64_t dims[2] = {inner, outer}, strides[1] = {inner * 2};
    const cuuint32_t box[2] = {64, rows};
    make_map(enc, m, ptr, 2, dims, strides, box, true, rows > 64);
}

}

extern "C" void kernel_launch(void* const* d_in, const int* in_sizes, int n_in, void* d_out, int out_size) {
    (void)in_sizes; (void)n_in; (void)out_size;
    static EncodeFn enc = nullptr;
    static void *hptr, *p_xnT, *p_st, *p_S, *p_flags;
    if (!enc) {
        cudaDriverEntryPointQueryResult qr;
        cudaGetDriverEntryPoint("cuTensorMapEncodeTiled", (void**)&enc, cudaEnableDefault, &qr);
        cudaFuncSetAttribute(fused_kernel, cudaFuncAttributeMaxDynamicSharedMemorySize, SMEM_BYTES);
        cudaGetSymbolAddress(&hptr, g_H); cudaGetSymbolAddress(&p_xnT, g_xnT); cudaGetSymbolAddress(&p_st, g_st);
        cudaGetSymbolAddress(&p_S, g_S); cudaGetSymbolAddress(&p_flags, g_flags);
    }
    Params P;
    P.x = (const __nv_bfloat16*)d_in[0]; P.logA = (const __nv_bfloat16*)d_in[1]; P.Aim = (const __nv_bfloat16*)d_in[2];
    P.Cr = (const __nv_bfloat16*)d_in[3]; P.Ci = (const __nv_bfloat16*)d_in[4]; P.logdt = (const __nv_bfloat16*)d_in[5];
    P.Dskip = (const __nv_bfloat16*)d_in[6];
    P.Wg = (const __nv_bfloat16*)d_in[8]; P.Wu = (const __nv_bfloat16*)d_in[9]; P.Wd = (const __nv_bfloat16*)d_in[10]; P.xnT = (uint4*)p_xnT; P.st = (float2*)p_st; P.S = (uint2*)p_S; P.flags = (unsigned*)p_flags;
    Maps M;
    make_map2(enc, &M.x[0], d_in[0], DM, SEQ, 168); make_map2(enc, &M.x[1], d_in[0], DM, SEQ, 176);
    make_map2(enc, &M.xo, d_in[0], DM, SEQ, 64);    make_map2(enc, &M.out, d_out, DM, SEQ, 64);
    make_map2(enc, &M.wg, d_in[8], FF, DM, 64);     make_map2(enc, &M.wu, d_in[9], FF, DM, 64);
    make_map2(enc, &M.wd, d_in[10], DM, FF, 64);
    for (int v = 0; v < 2; v++) {
        const cuuint64_t dims[3] = {64, 256, 172}, strides[2] = {128, 32768};
        const cuuint32_t box[3] = {64, (cuuint32_t)(21 + v), 8};
        make_map(enc, &M.hst[v], hptr, 3, dims, strides, box, false);
    }
    {
        const cuuint64_t dims[2] = {2048, 512}, strides[1] = {4096};
        const cuuint32_t box[2] = {16, 128};
        make_map(enc, &M.xt, p_xnT, 2, dims, strides, box, false);
    }
    {
        const cuuint64_t dims[5] = {64, 2, 4, 32, 64}, strides[4] = {4 * 8192, 8192, 8 * 8192, 128};
        const cuuint32_t box[5] = {64, 2, 4, 8, 2};
        make_map(enc, &M.sld, p_S, 5, dims, strides, box, true);
    }
    {
        const cuuint64_t dims[5] = {64, 2, 2, 64, 172}, strides[4] = {256, 128, 512, 32768};
        const cuuint32_t box[5] = {64, 2, 2, 2, 8};
        make_map(enc, &M.hld, hptr, 5, dims, strides, box, false);
    }
    fused_kernel<<<NCTA, 512, SMEM_BYTES>>>(P, M);
}
```

```cpp
#include <cuda_runtime.h>
#include <cuda_bf16.h>
#include <cuda.h>
#include <stdint.h>

#define PROF 0

namespace {

constexpr int SEQ = 2048, DM = 512, FF = 1376;
constexpr int NCTA = 132;
#define GOST 1
#define SIGK 3
#define DLY1 300
constexpr int RUNROLL = 2;
constexpr int TOKG = 344;

constexpr uint32_t OFF_W = 0;
constexpr uint32_t XBUF = 22528;
constexpr uint32_t OFF_X = 65536;
constexpr uint32_t OFF_CONV = 155648;
constexpr uint32_t CH_STRIDE = 17536;
constexpr uint32_t CH_T = 0;
constexpr uint32_t CH_A3 = 8448;
constexpr uint32_t CH_B3 = 12544;
constexpr uint32_t CH_U = 13312;
constexpr uint32_t CH_G = CH_A3 + 2064;
constexpr uint32_t UPLANE = 2112;
constexpr uint32_t CH_LN = 0, CH_PART = 4224, CH_PSZ = 3072, CH_LNT = 13440;
constexpr uint32_t OFF_SST = 60416;
constexpr uint32_t OFF_XO = 191488, OFF_SI = 207872;
constexpr uint32_t OFF_ST = 225792;
constexpr uint32_t OFF_CSUM = 228544;
constexpr uint32_t OFF_BAR = 229056;
constexpr uint32_t SMEM_BYTES = 229568;

enum {
    B_FULLW = 0, B_EMPTYW = 4, B_FULLX = 8, B_EMPTYX = 12, B_FULLD = 16, B_EMPTYD = 24,
    B_U = 32, B_XO = 33, B_S = 34, B_STG = 35, B_HF = 37, B_STATS = 38, B_LNS = 39, B_SST = 40,
    B_LNX = 41, B_CH0 = 42, B_TURN = 43, B_K = 45,
    B_CONV = 46, B_LN = 50, B_CS = 51, B_EPI = 52, B_SIG = 54,
    B_COUNT = 56
};
enum { F_A = 0, F_H = 1, F_S = 13, F_EXIT = 17, F_COUNT = 18 };

__device__ uint4 g_xnT[DM * 256];
__device__ float2 g_st[6 * TOKG];
__device__ uint4 g_H[172 * 256 * 8];
__device__ uint2 g_S[256 * 1024];
__device__ unsigned g_flags[F_COUNT * 32];
#define STAMP(i) do {} while (0)
#define GSTAMP(i) do {} while (0)
#define STAMP2(i) do {} while (0)

__device__ __forceinline__ uint32_t smem_u32(const void* p) { return (uint32_t)__cvta_generic_to_shared(p); }
__device__ __forceinline__ void mbar_expect(uint32_t bar, uint32_t bytes) { asm volatile("mbarrier.arrive.expect_tx.shared::cta.b64 _, [%0], %1;" :: "r"(bar), "r"(bytes) : "memory"); }
__device__ __forceinline__ void mbar_arrive(uint32_t bar) { asm volatile("mbarrier.arrive.shared::cta.b64 _, [%0];" :: "r"(bar) : "memory"); }
__device__ __forceinline__ void mbar_wait(uint32_t bar, uint32_t parity) {
    asm volatile("{.reg .pred p; .reg .u32 n; mov.u32 n, 0x20000;\n"
                 "LW: mbarrier.try_wait.parity.shared::cta.b64 p, [%0], %1;\n"
                 "sub.u32 n, n, 1; setp.eq.or.u32 p, n, 0, p; @!p bra LW;}" :: "r"(bar), "r"(parity) : "memory");
}
__device__ __forceinline__ void mbar_arrive_if(uint32_t bar, uint32_t pred) {
    asm volatile("{.reg .pred p; setp.ne.u32 p, %1, 0; @p mbarrier.arrive.shared::cta.b64 _, [%0];}" :: "r"(bar), "r"(pred) : "memory");
}
__device__ __forceinline__ bool elect_one() { uint32_t p; asm volatile("{.reg .pred P; elect.sync _|P, 0xffffffff; selp.u32 %0, 1, 0, P;}" : "=r"(p)); return p; }
__device__ __forceinline__ void tma2d(uint32_t dst, const CUtensorMap* m, int c0, int c1, uint32_t bar) {
    asm volatile("cp.async.bulk.tensor.2d.shared::cluster.global.mbarrier::complete_tx::bytes [%0], [%1, {%3, %4}], [%2];"
        :: "r"(dst), "l"(m), "r"(bar), "r"(c0), "r"(c1) : "memory");
}
__device__ __forceinline__ void bulk_load(uint32_t dst, const void* src, uint32_t bytes, uint32_t bar) {
    asm volatile("cp.async.bulk.shared::cluster.global.mbarrier::complete_tx::bytes [%0], [%1], %2, [%3];" :: "r"(dst), "l"(src), "r"(bytes), "r"(bar) : "memory");
}
__device__ __forceinline__ void bulk_store(void* dst, uint32_t src, uint32_t bytes) {
    asm volatile("cp.async.bulk.global.shared::cta.bulk_group [%0], [%1], %2;" :: "l"(dst), "r"(src), "r"(bytes) : "memory");
}
__device__ __forceinline__ void fence_async_smem() { asm volatile("fence.proxy.async.shared::cta;" ::: "memory"); }
__device__ __forceinline__ void flag_wait(unsigned* g_flags, int f, unsigned target) {
    asm volatile("{.reg .pred p; .reg .u32 n, v; mov.u32 n, 0x40000;\n"
                 "LF: ld.acquire.gpu.global.u32 v, [%0]; setp.ge.u32 p, v, %1; @p bra LD;\n"
                 "sub.u32 n, n, 1; setp.ne.u32 p, n, 0; @p bra LF; trap;\nLD: }"
                 :: "l"(g_flags + f * 32), "r"(target) : "memory");
}
__device__ __forceinline__ void flag_signal(unsigned* g_flags, int f) {
    asm volatile("cp.async.bulk.commit_group; cp.async.bulk.wait_group 0; red.relaxed.gpu.global.add.u32 [%0], 1;" :: "l"(g_flags + f * 32) : "memory");
}
__device__ __forceinline__ void exit_count(unsigned* g_flags) {
    if (atomicAdd(g_flags + F_EXIT * 32, 1u) == NCTA - 1) {
        #pragma unroll 1
        for (int i = 0; i < F_COUNT; i++) g_flags[i * 32] = 0;
    }
}
__device__ __forceinline__ void bar_sync(int id) { asm volatile("bar.sync %0, 128;" :: "r"(id) : "memory"); }
__device__ __forceinline__ uint64_t mkdesc(uint32_t addr, uint32_t lbo, uint32_t sbo, uint32_t swz) {
    return (uint64_t)((addr >> 4) | ((lbo >> 4) << 16)) | ((uint64_t)((sbo >> 4) | (swz << 30)) << 32);
}
#define WG_FENCE() asm volatile("wgmma.fence.sync.aligned;" ::: "memory")
#define WG_COMMIT() asm volatile("wgmma.commit_group.sync.aligned;" ::: "memory")
#define WG_WAIT(n) asm volatile("wgmma.wait_group.sync.aligned " #n ";" ::: "memory")
template <int N> __device__ __forceinline__ void fence_acc(float (&d)[N]) {
    #pragma unroll
    for (int i = 0; i < N; i++) asm volatile("" : "+f"(d[i]) :: "memory");
}
template <int N> __device__ __forceinline__ void define_acc(float (&d)[N]) {
    #pragma unroll
    for (int i = 0; i < N; i++) asm volatile("" : "=f"(d[i]));
}
__device__ __forceinline__ uint32_t pack2(float lo, float hi) { uint32_t r; asm("cvt.rn.bf16x2.f32 %0, %1, %2;" : "=r"(r) : "f"(hi), "f"(lo)); return r; }
__device__ __forceinline__ float bf_lo(uint32_t v) { return __uint_as_float(v << 16); }
__device__ __forceinline__ float bf_hi(uint32_t v) { return __uint_as_float(v & 0xffff0000u); }
__device__ __forceinline__ float bf_round(float v) { return bf_hi(pack2(0.f, v)); }
__device__ __forceinline__ float tanh_fast(float v) { float r; asm("tanh.approx.f32 %0, %1;" : "=f"(r) : "f"(v)); return r; }
__device__ __forceinline__ float ex2(float v) { float r; asm("ex2.approx.ftz.f32 %0, %1;" : "=f"(r) : "f"(v)); return r; }
__device__ __forceinline__ uint4 lds128(uint32_t a) { uint4 v; asm volatile("ld.shared.v4.b32 {%0,%1,%2,%3}, [%4];" : "=r"(v.x), "=r"(v.y), "=r"(v.z), "=r"(v.w) : "r"(a)); return v; }
__device__ __forceinline__ uint2 lds64(uint32_t a) { uint2 v; asm volatile("ld.shared.v2.b32 {%0,%1}, [%2];" : "=r"(v.x), "=r"(v.y) : "r"(a)); return v; }
__device__ __forceinline__ float ldsf(uint32_t a) { float v; asm volatile("ld.shared.f32 %0, [%1];" : "=f"(v) : "r"(a)); return v; }
__device__ __forceinline__ void sts128(uint32_t a, uint32_t x, uint32_t y, uint32_t z, uint32_t w) { asm volatile("st.shared.v4.b32 [%0], {%1,%2,%3,%4};" :: "r"(a), "r"(x), "r"(y), "r"(z), "r"(w) : "memory"); }
__device__ __forceinline__ void sts64(uint32_t a, uint32_t x, uint32_t y) { asm volatile("st.shared.v2.b32 [%0], {%1,%2};" :: "r"(a), "r"(x), "r"(y) : "memory"); }
__device__ __forceinline__ void stsf(uint32_t a, float x) { asm volatile("st.shared.f32 [%0], %1;" :: "r"(a), "f"(x) : "memory"); }
__device__ __forceinline__ void sts16(uint32_t a, uint32_t x) { asm volatile("st.shared.b16 [%0], %1;" :: "r"(a), "h"((unsigned short)x) : "memory"); }
__device__ __forceinline__ void stsm4(uint32_t a, uint32_t r0, uint32_t r1, uint32_t r2, uint32_t r3) {
    asm volatile("stmatrix.sync.aligned.m8n8.x4.shared.b16 [%0], {%1,%2,%3,%4};" :: "r"(a), "r"(r0), "r"(r1), "r"(r2), "r"(r3) : "memory");
}
__device__ __forceinline__ void ldsm4(uint32_t (&r)[4], uint32_t a) {
    asm volatile("ldmatrix.sync.aligned.m8n8.x4.shared.b16 {%0,%1,%2,%3}, [%4];" : "=r"(r[0]), "=r"(r[1]), "=r"(r[2]), "=r"(r[3]) : "r"(a) : "memory");
}
#define FU(x) __float_as_uint(x)
#define UF(x) __uint_as_float(x)
__device__ __forceinline__ uint32_t wd_slot(int s) { return (uint32_t)((0xbba8403056201000ull >> (8 * s)) & 0xff) << 10; }
__device__ __forceinline__ uint32_t h_slot(int s) { return (uint32_t)((0xcba0908880787068ull >> (8 * s)) & 0xff) << 10; }

template<int N> __device__ __forceinline__ void wg_rs(float (&d)[64], uint32_t a0, uint32_t a1, uint32_t a2, uint32_t a3, uint64_t db);
template<> __device__ __forceinline__ void wg_rs<128>(float (&d)[64], uint32_t a0, uint32_t a1, uint32_t a2, uint32_t a3, uint64_t db) {
  asm volatile("{.reg .pred p; setp.ne.b32 p, 1, 0; wgmma.mma_async.sync.aligned.m64n128k16.f32.bf16.bf16 {%0,%1,%2,%3,%4,%5,%6,%7,%8,%9,%10,%11,%12,%13,%14,%15,%16,%17,%18,%19,%20,%21,%22,%23,%24,%25,%26,%27,%28,%29,%30,%31,%32,%33,%34,%35,%36,%37,%38,%39,%40,%41,%42,%43,%44,%45,%46,%47,%48,%49,%50,%51,%52,%53,%54,%55,%56,%57,%58,%59,%60,%61,%62,%63}, {%64,%65,%66,%67}, %68, p, 1, 1, 0;}"
    : "+f"(d[0]),"+f"(d[1]),"+f"(d[2]),"+f"(d[3]),"+f"(d[4]),"+f"(d[5]),"+f"(d[6]),"+f"(d[7]),"+f"(d[8]),"+f"(d[9]),"+f"(d[10]),"+f"(d[11]),"+f"(d[12]),"+f"(d[13]),"+f"(d[14]),"+f"(d[15]),"+f"(d[16]),"+f"(d[17]),"+f"(d[18]),"+f"(d[19]),"+f"(d[20]),"+f"(d[21]),"+f"(d[22]),"+f"(d[23]),"+f"(d[24]),"+f"(d[25]),"+f"(d[26]),"+f"(d[27]),"+f"(d[28]),"+f"(d[29]),"+f"(d[30]),"+f"(d[31]),"+f"(d[32]),"+f"(d[33]),"+f"(d[34]),"+f"(d[35]),"+f"(d[36]),"+f"(d[37]),"+f"(d[38]),"+f"(d[39]),"+f"(d[40]),"+f"(d[41]),"+f"(d[42]),"+f"(d[43]),"+f"(d[44]),"+f"(d[45]),"+f"(d[46]),"+f"(d[47]),"+f"(d[48]),"+f"(d[49]),"+f"(d[50]),"+f"(d[51]),"+f"(d[52]),"+f"(d[53]),"+f"(d[54]),"+f"(d[55]),"+f"(d[56]),"+f"(d[57]),"+f"(d[58]),"+f"(d[59]),"+f"(d[60]),"+f"(d[61]),"+f"(d[62]),"+f"(d[63]) : "r"(a0), "r"(a1), "r"(a2), "r"(a3), "l"(db));
}
template<> __device__ __forceinline__ void wg_rs<120>(float (&d)[64], uint32_t a0, uint32_t a1, uint32_t a2, uint32_t a3, uint64_t db) {
  asm volatile("{.reg .pred p; setp.ne.b32 p, 1, 0; wgmma.mma_async.sync.aligned.m64n120k16.f32.bf16.bf16 {%0,%1,%2,%3,%4,%5,%6,%7,%8,%9,%10,%11,%12,%13,%14,%15,%16,%17,%18,%19,%20,%21,%22,%23,%24,%25,%26,%27,%28,%29,%30,%31,%32,%33,%34,%35,%36,%37,%38,%39,%40,%41,%42,%43,%44,%45,%46,%47,%48,%49,%50,%51,%52,%53,%54,%55,%56,%57,%58,%59}, {%60,%61,%62,%63}, %64, p, 1, 1, 0;}"
    : "+f"(d[0]),"+f"(d[1]),"+f"(d[2]),"+f"(d[3]),"+f"(d[4]),"+f"(d[5]),"+f"(d[6]),"+f"(d[7]),"+f"(d[8]),"+f"(d[9]),"+f"(d[10]),"+f"(d[11]),"+f"(d[12]),"+f"(d[13]),"+f"(d[14]),"+f"(d[15]),"+f"(d[16]),"+f"(d[17]),"+f"(d[18]),"+f"(d[19]),"+f"(d[20]),"+f"(d[21]),"+f"(d[22]),"+f"(d[23]),"+f"(d[24]),"+f"(d[25]),"+f"(d[26]),"+f"(d[27]),"+f"(d[28]),"+f"(d[29]),"+f"(d[30]),"+f"(d[31]),"+f"(d[32]),"+f"(d[33]),"+f"(d[34]),"+f"(d[35]),"+f"(d[36]),"+f"(d[37]),"+f"(d[38]),"+f"(d[39]),"+f"(d[40]),"+f"(d[41]),"+f"(d[42]),"+f"(d[43]),"+f"(d[44]),"+f"(d[45]),"+f"(d[46]),"+f"(d[47]),"+f"(d[48]),"+f"(d[49]),"+f"(d[50]),"+f"(d[51]),"+f"(d[52]),"+f"(d[53]),"+f"(d[54]),"+f"(d[55]),"+f"(d[56]),"+f"(d[57]),"+f"(d[58]),"+f"(d[59]) : "r"(a0), "r"(a1), "r"(a2), "r"(a3), "l"(db));
}
template<> __device__ __forceinline__ void wg_rs<112>(float (&d)[64], uint32_t a0, uint32_t a1, uint32_t a2, uint32_t a3, uint64_t db) {
  asm volatile("{.reg .pred p; setp.ne.b32 p, 1, 0; wgmma.mma_async.sync.aligned.m64n112k16.f32.bf16.bf16 {%0,%1,%2,%3,%4,%5,%6,%7,%8,%9,%10,%11,%12,%13,%14,%15,%16,%17,%18,%19,%20,%21,%22,%23,%24,%25,%26,%27,%28,%29,%30,%31,%32,%33,%34,%35,%36,%37,%38,%39,%40,%41,%42,%43,%44,%45,%46,%47,%48,%49,%50,%51,%52,%53,%54,%55}, {%56,%57,%58,%59}, %60, p, 1, 1, 0;}"
    : "+f"(d[0]),"+f"(d[1]),"+f"(d[2]),"+f"(d[3]),"+f"(d[4]),"+f"(d[5]),"+f"(d[6]),"+f"(d[7]),"+f"(d[8]),"+f"(d[9]),"+f"(d[10]),"+f"(d[11]),"+f"(d[12]),"+f"(d[13]),"+f"(d[14]),"+f"(d[15]),"+f"(d[16]),"+f"(d[17]),"+f"(d[18]),"+f"(d[19]),"+f"(d[20]),"+f"(d[21]),"+f"(d[22]),"+f"(d[23]),"+f"(d[24]),"+f"(d[25]),"+f"(d[26]),"+f"(d[27]),"+f"(d[28]),"+f"(d[29]),"+f"(d[30]),"+f"(d[31]),"+f"(d[32]),"+f"(d[33]),"+f"(d[34]),"+f"(d[35]),"+f"(d[36]),"+f"(d[37]),"+f"(d[38]),"+f"(d[39]),"+f"(d[40]),"+f"(d[41]),"+f"(d[42]),"+f"(d[43]),"+f"(d[44]),"+f"(d[45]),"+f"(d[46]),"+f"(d[47]),"+f"(d[48]),"+f"(d[49]),"+f"(d[50]),"+f"(d[51]),"+f"(d[52]),"+f"(d[53]),"+f"(d[54]),"+f"(d[55]) : "r"(a0), "r"(a1), "r"(a2), "r"(a3), "l"(db));
}
template<> __device__ __forceinline__ void wg_rs<104>(float (&d)[64], uint32_t a0, uint32_t a1, uint32_t a2, uint32_t a3, uint64_t db) {
  asm volatile("{.reg .pred p; setp.ne.b32 p, 1, 0; wgmma.mma_async.sync.aligned.m64n104k16.f32.bf16.bf16 {%0,%1,%2,%3,%4,%5,%6,%7,%8,%9,%10,%11,%12,%13,%14,%15,%16,%17,%18,%19,%20,%21,%22,%23,%24,%25,%26,%27,%28,%29,%30,%31,%32,%33,%34,%35,%36,%37,%38,%39,%40,%41,%42,%43,%44,%45,%46,%47,%48,%49,%50,%51}, {%52,%53,%54,%55}, %56, p, 1, 1, 0;}"
    : "+f"(d[0]),"+f"(d[1]),"+f"(d[2]),"+f"(d[3]),"+f"(d[4]),"+f"(d[5]),"+f"(d[6]),"+f"(d[7]),"+f"(d[8]),"+f"(d[9]),"+f"(d[10]),"+f"(d[11]),"+f"(d[12]),"+f"(d[13]),"+f"(d[14]),"+f"(d[15]),"+f"(d[16]),"+f"(d[17]),"+f"(d[18]),"+f"(d[19]),"+f"(d[20]),"+f"(d[21]),"+f"(d[22]),"+f"(d[23]),"+f"(d[24]),"+f"(d[25]),"+f"(d[26]),"+f"(d[27]),"+f"(d[28]),"+f"(d[29]),"+f"(d[30]),"+f"(d[31]),"+f"(d[32]),"+f"(d[33]),"+f"(d[34]),"+f"(d[35]),"+f"(d[36]),"+f"(d[37]),"+f"(d[38]),"+f"(d[39]),"+f"(d[40]),"+f"(d[41]),"+f"(d[42]),"+f"(d[43]),"+f"(d[44]),"+f"(d[45]),"+f"(d[46]),"+f"(d[47]),"+f"(d[48]),"+f"(d[49]),"+f"(d[50]),"+f"(d[51]) : "r"(a0), "r"(a1), "r"(a2), "r"(a3), "l"(db));
}
template<> __device__ __forceinline__ void wg_rs<96>(float (&d)[64], uint32_t a0, uint32_t a1, uint32_t a2, uint32_t a3, uint64_t db) {
  asm volatile("{.reg .pred p; setp.ne.b32 p, 1, 0; wgmma.mma_async.sync.aligned.m64n96k16.f32.bf16.bf16 {%0,%1,%2,%3,%4,%5,%6,%7,%8,%9,%10,%11,%12,%13,%14,%15,%16,%17,%18,%19,%20,%21,%22,%23,%24,%25,%26,%27,%28,%29,%30,%31,%32,%33,%34,%35,%36,%37,%38,%39,%40,%41,%42,%43,%44,%45,%46,%47}, {%48,%49,%50,%51}, %52, p, 1, 1, 0;}"
    : "+f"(d[0]),"+f"(d[1]),"+f"(d[2]),"+f"(d[3]),"+f"(d[4]),"+f"(d[5]),"+f"(d[6]),"+f"(d[7]),"+f"(d[8]),"+f"(d[9]),"+f"(d[10]),"+f"(d[11]),"+f"(d[12]),"+f"(d[13]),"+f"(d[14]),"+f"(d[15]),"+f"(d[16]),"+f"(d[17]),"+f"(d[18]),"+f"(d[19]),"+f"(d[20]),"+f"(d[21]),"+f"(d[22]),"+f"(d[23]),"+f"(d[24]),"+f"(d[25]),"+f"(d[26]),"+f"(d[27]),"+f"(d[28]),"+f"(d[29]),"+f"(d[30]),"+f"(d[31]),"+f"(d[32]),"+f"(d[33]),"+f"(d[34]),"+f"(d[35]),"+f"(d[36]),"+f"(d[37]),"+f"(d[38]),"+f"(d[39]),"+f"(d[40]),"+f"(d[41]),"+f"(d[42]),"+f"(d[43]),"+f"(d[44]),"+f"(d[45]),"+f"(d[46]),"+f"(d[47]) : "r"(a0), "r"(a1), "r"(a2), "r"(a3), "l"(db));
}
template<> __device__ __forceinline__ void wg_rs<88>(float (&d)[64], uint32_t a0, uint32_t a1, uint32_t a2, uint32_t a3, uint64_t db) {
  asm volatile("{.reg .pred p; setp.ne.b32 p, 1, 0; wgmma.mma_async.sync.aligned.m64n88k16.f32.bf16.bf16 {%0,%1,%2,%3,%4,%5,%6,%7,%8,%9,%10,%11,%12,%13,%14,%15,%16,%17,%18,%19,%20,%21,%22,%23,%24,%25,%26,%27,%28,%29,%30,%31,%32,%33,%34,%35,%36,%37,%38,%39,%40,%41,%42,%43}, {%44,%45,%46,%47}, %48, p, 1, 1, 0;}"
    : "+f"(d[0]),"+f"(d[1]),"+f"(d[2]),"+f"(d[3]),"+f"(d[4]),"+f"(d[5]),"+f"(d[6]),"+f"(d[7]),"+f"(d[8]),"+f"(d[9]),"+f"(d[10]),"+f"(d[11]),"+f"(d[12]),"+f"(d[13]),"+f"(d[14]),"+f"(d[15]),"+f"(d[16]),"+f"(d[17]),"+f"(d[18]),"+f"(d[19]),"+f"(d[20]),"+f"(d[21]),"+f"(d[22]),"+f"(d[23]),"+f"(d[24]),"+f"(d[25]),"+f"(d[26]),"+f"(d[27]),"+f"(d[28]),"+f"(d[29]),"+f"(d[30]),"+f"(d[31]),"+f"(d[32]),"+f"(d[33]),"+f"(d[34]),"+f"(d[35]),"+f"(d[36]),"+f"(d[37]),"+f"(d[38]),"+f"(d[39]),"+f"(d[40]),"+f"(d[41]),"+f"(d[42]),"+f"(d[43]) : "r"(a0), "r"(a1), "r"(a2), "r"(a3), "l"(db));
}
template<> __device__ __forceinline__ void wg_rs<80>(float (&d)[64], uint32_t a0, uint32_t a1, uint32_t a2, uint32_t a3, uint64_t db) {
  asm volatile("{.reg .pred p; setp.ne.b32 p, 1, 0; wgmma.mma_async.sync.aligned.m64n80k16.f32.bf16.bf16 {%0,%1,%2,%3,%4,%5,%6,%7,%8,%9,%10,%11,%12,%13,%14,%15,%16,%17,%18,%19,%20,%21,%22,%23,%24,%25,%26,%27,%28,%29,%30,%31,%32,%33,%34,%35,%36,%37,%38,%39}, {%40,%41,%42,%43}, %44, p, 1, 1, 0;}"
    : "+f"(d[0]),"+f"(d[1]),"+f"(d[2]),"+f"(d[3]),"+f"(d[4]),"+f"(d[5]),"+f"(d[6]),"+f"(d[7]),"+f"(d[8]),"+f"(d[9]),"+f"(d[10]),"+f"(d[11]),"+f"(d[12]),"+f"(d[13]),"+f"(d[14]),"+f"(d[15]),"+f"(d[16]),"+f"(d[17]),"+f"(d[18]),"+f"(d[19]),"+f"(d[20]),"+f"(d[21]),"+f"(d[22]),"+f"(d[23]),"+f"(d[24]),"+f"(d[25]),"+f"(d[26]),"+f"(d[27]),"+f"(d[28]),"+f"(d[29]),"+f"(d[30]),"+f"(d[31]),"+f"(d[32]),"+f"(d[33]),"+f"(d[34]),"+f"(d[35]),"+f"(d[36]),"+f"(d[37]),"+f"(d[38]),"+f"(d[39]) : "r"(a0), "r"(a1), "r"(a2), "r"(a3), "l"(db));
}
template<> __device__ __forceinline__ void wg_rs<72>(float (&d)[64], uint32_t a0, uint32_t a1, uint32_t a2, uint32_t a3, uint64_t db) {
  asm volatile("{.reg .pred p; setp.ne.b32 p, 1, 0; wgmma.mma_async.sync.aligned.m64n72k16.f32.bf16.bf16 {%0,%1,%2,%3,%4,%5,%6,%7,%8,%9,%10,%11,%12,%13,%14,%15,%16,%17,%18,%19,%20,%21,%22,%23,%24,%25,%26,%27,%28,%29,%30,%31,%32,%33,%34,%35}, {%36,%37,%38,%39}, %40, p, 1, 1, 0;}"
    : "+f"(d[0]),"+f"(d[1]),"+f"(d[2]),"+f"(d[3]),"+f"(d[4]),"+f"(d[5]),"+f"(d[6]),"+f"(d[7]),"+f"(d[8]),"+f"(d[9]),"+f"(d[10]),"+f"(d[11]),"+f"(d[12]),"+f"(d[13]),"+f"(d[14]),"+f"(d[15]),"+f"(d[16]),"+f"(d[17]),"+f"(d[18]),"+f"(d[19]),"+f"(d[20]),"+f"(d[21]),"+f"(d[22]),"+f"(d[23]),"+f"(d[24]),"+f"(d[25]),"+f"(d[26]),"+f"(d[27]),"+f"(d[28]),"+f"(d[29]),"+f"(d[30]),"+f"(d[31]),"+f"(d[32]),"+f"(d[33]),"+f"(d[34]),"+f"(d[35]) : "r"(a0), "r"(a1), "r"(a2), "r"(a3), "l"(db));
}
template<> __device__ __forceinline__ void wg_rs<64>(float (&d)[64], uint32_t a0, uint32_t a1, uint32_t a2, uint32_t a3, uint64_t db) {
  asm volatile("{.reg .pred p; setp.ne.b32 p, 1, 0; wgmma.mma_async.sync.aligned.m64n64k16.f32.bf16.bf16 {%0,%1,%2,%3,%4,%5,%6,%7,%8,%9,%10,%11,%12,%13,%14,%15,%16,%17,%18,%19,%20,%21,%22,%23,%24,%25,%26,%27,%28,%29,%30,%31}, {%32,%33,%34,%35}, %36, p, 1, 1, 0;}"
    : "+f"(d[0]),"+f"(d[1]),"+f"(d[2]),"+f"(d[3]),"+f"(d[4]),"+f"(d[5]),"+f"(d[6]),"+f"(d[7]),"+f"(d[8]),"+f"(d[9]),"+f"(d[10]),"+f"(d[11]),"+f"(d[12]),"+f"(d[13]),"+f"(d[14]),"+f"(d[15]),"+f"(d[16]),"+f"(d[17]),"+f"(d[18]),"+f"(d[19]),"+f"(d[20]),"+f"(d[21]),"+f"(d[22]),"+f"(d[23]),"+f"(d[24]),"+f"(d[25]),"+f"(d[26]),"+f"(d[27]),"+f"(d[28]),"+f"(d[29]),"+f"(d[30]),"+f"(d[31]) : "r"(a0), "r"(a1), "r"(a2), "r"(a3), "l"(db));
}
__device__ __forceinline__ void wg_rs_first(float (&d)[64], uint32_t a0, uint32_t a1, uint32_t a2, uint32_t a3, uint64_t db) {
  asm volatile("{.reg .pred p; setp.ne.b32 p, 0, 0; wgmma.mma_async.sync.aligned.m64n128k16.f32.bf16.bf16 {%0,%1,%2,%3,%4,%5,%6,%7,%8,%9,%10,%11,%12,%13,%14,%15,%16,%17,%18,%19,%20,%21,%22,%23,%24,%25,%26,%27,%28,%29,%30,%31,%32,%33,%34,%35,%36,%37,%38,%39,%40,%41,%42,%43,%44,%45,%46,%47,%48,%49,%50,%51,%52,%53,%54,%55,%56,%57,%58,%59,%60,%61,%62,%63}, {%64,%65,%66,%67}, %68, p, 1, 1, 0;}"
    : "=f"(d[0]),"=f"(d[1]),"=f"(d[2]),"=f"(d[3]),"=f"(d[4]),"=f"(d[5]),"=f"(d[6]),"=f"(d[7]),"=f"(d[8]),"=f"(d[9]),"=f"(d[10]),"=f"(d[11]),"=f"(d[12]),"=f"(d[13]),"=f"(d[14]),"=f"(d[15]),"=f"(d[16]),"=f"(d[17]),"=f"(d[18]),"=f"(d[19]),"=f"(d[20]),"=f"(d[21]),"=f"(d[22]),"=f"(d[23]),"=f"(d[24]),"=f"(d[25]),"=f"(d[26]),"=f"(d[27]),"=f"(d[28]),"=f"(d[29]),"=f"(d[30]),"=f"(d[31]),"=f"(d[32]),"=f"(d[33]),"=f"(d[34]),"=f"(d[35]),"=f"(d[36]),"=f"(d[37]),"=f"(d[38]),"=f"(d[39]),"=f"(d[40]),"=f"(d[41]),"=f"(d[42]),"=f"(d[43]),"=f"(d[44]),"=f"(d[45]),"=f"(d[46]),"=f"(d[47]),"=f"(d[48]),"=f"(d[49]),"=f"(d[50]),"=f"(d[51]),"=f"(d[52]),"=f"(d[53]),"=f"(d[54]),"=f"(d[55]),"=f"(d[56]),"=f"(d[57]),"=f"(d[58]),"=f"(d[59]),"=f"(d[60]),"=f"(d[61]),"=f"(d[62]),"=f"(d[63]) : "r"(a0), "r"(a1), "r"(a2), "r"(a3), "l"(db));
}
__device__ __forceinline__ void wg_tt128(float (&d)[64], uint64_t da, uint64_t db, int sc) {
  asm volatile("{.reg .pred p; setp.ne.b32 p, %66, 0; wgmma.mma_async.sync.aligned.m64n128k16.f32.bf16.bf16 {%0,%1,%2,%3,%4,%5,%6,%7,%8,%9,%10,%11,%12,%13,%14,%15,%16,%17,%18,%19,%20,%21,%22,%23,%24,%25,%26,%27,%28,%29,%30,%31,%32,%33,%34,%35,%36,%37,%38,%39,%40,%41,%42,%43,%44,%45,%46,%47,%48,%49,%50,%51,%52,%53,%54,%55,%56,%57,%58,%59,%60,%61,%62,%63}, %64, %65, p, 1, 1, 1, 1;}"
    : "+f"(d[0]),"+f"(d[1]),"+f"(d[2]),"+f"(d[3]),"+f"(d[4]),"+f"(d[5]),"+f"(d[6]),"+f"(d[7]),"+f"(d[8]),"+f"(d[9]),"+f"(d[10]),"+f"(d[11]),"+f"(d[12]),"+f"(d[13]),"+f"(d[14]),"+f"(d[15]),"+f"(d[16]),"+f"(d[17]),"+f"(d[18]),"+f"(d[19]),"+f"(d[20]),"+f"(d[21]),"+f"(d[22]),"+f"(d[23]),"+f"(d[24]),"+f"(d[25]),"+f"(d[26]),"+f"(d[27]),"+f"(d[28]),"+f"(d[29]),"+f"(d[30]),"+f"(d[31]),"+f"(d[32]),"+f"(d[33]),"+f"(d[34]),"+f"(d[35]),"+f"(d[36]),"+f"(d[37]),"+f"(d[38]),"+f"(d[39]),"+f"(d[40]),"+f"(d[41]),"+f"(d[42]),"+f"(d[43]),"+f"(d[44]),"+f"(d[45]),"+f"(d[46]),"+f"(d[47]),"+f"(d[48]),"+f"(d[49]),"+f"(d[50]),"+f"(d[51]),"+f"(d[52]),"+f"(d[53]),"+f"(d[54]),"+f"(d[55]),"+f"(d[56]),"+f"(d[57]),"+f"(d[58]),"+f"(d[59]),"+f"(d[60]),"+f"(d[61]),"+f"(d[62]),"+f"(d[63]) : "l"(da), "l"(db), "r"(sc));
}
__device__ __forceinline__ void wg_tt64(float (&d)[64], uint64_t da, uint64_t db, int sc) {
  asm volatile("{.reg .pred p; setp.ne.b32 p, %34, 0; wgmma.mma_async.sync.aligned.m64n64k16.f32.bf16.bf16 {%0,%1,%2,%3,%4,%5,%6,%7,%8,%9,%10,%11,%12,%13,%14,%15,%16,%17,%18,%19,%20,%21,%22,%23,%24,%25,%26,%27,%28,%29,%30,%31}, %32, %33, p, 1, 1, 1, 1;}"
    : "+f"(d[0]),"+f"(d[1]),"+f"(d[2]),"+f"(d[3]),"+f"(d[4]),"+f"(d[5]),"+f"(d[6]),"+f"(d[7]),"+f"(d[8]),"+f"(d[9]),"+f"(d[10]),"+f"(d[11]),"+f"(d[12]),"+f"(d[13]),"+f"(d[14]),"+f"(d[15]),"+f"(d[16]),"+f"(d[17]),"+f"(d[18]),"+f"(d[19]),"+f"(d[20]),"+f"(d[21]),"+f"(d[22]),"+f"(d[23]),"+f"(d[24]),"+f"(d[25]),"+f"(d[26]),"+f"(d[27]),"+f"(d[28]),"+f"(d[29]),"+f"(d[30]),"+f"(d[31]) : "l"(da), "l"(db), "r"(sc));
}
__device__ __forceinline__ void wg_tt32(float (&d)[64], uint64_t da, uint64_t db, int sc) {
  asm volatile("{.reg .pred p; setp.ne.b32 p, %18, 0; wgmma.mma_async.sync.aligned.m64n32k16.f32.bf16.bf16 {%0,%1,%2,%3,%4,%5,%6,%7,%8,%9,%10,%11,%12,%13,%14,%15}, %16, %17, p, 1, 1, 1, 1;}"
    : "+f"(d[0]),"+f"(d[1]),"+f"(d[2]),"+f"(d[3]),"+f"(d[4]),"+f"(d[5]),"+f"(d[6]),"+f"(d[7]),"+f"(d[8]),"+f"(d[9]),"+f"(d[10]),"+f"(d[11]),"+f"(d[12]),"+f"(d[13]),"+f"(d[14]),"+f"(d[15]) : "l"(da), "l"(db), "r"(sc));
}
__device__ __forceinline__ void wg_g1(float (&d)[88], uint64_t da, uint64_t db, int sc) {
  asm volatile("{.reg .pred p; setp.ne.b32 p, %90, 0; wgmma.mma_async.sync.aligned.m64n176k16.f32.bf16.bf16 {%0,%1,%2,%3,%4,%5,%6,%7,%8,%9,%10,%11,%12,%13,%14,%15,%16,%17,%18,%19,%20,%21,%22,%23,%24,%25,%26,%27,%28,%29,%30,%31,%32,%33,%34,%35,%36,%37,%38,%39,%40,%41,%42,%43,%44,%45,%46,%47,%48,%49,%50,%51,%52,%53,%54,%55,%56,%57,%58,%59,%60,%61,%62,%63,%64,%65,%66,%67,%68,%69,%70,%71,%72,%73,%74,%75,%76,%77,%78,%79,%80,%81,%82,%83,%84,%85,%86,%87}, %88, %89, p, 1, 1, 1, 0;}"
    : "+f"(d[0]),"+f"(d[1]),"+f"(d[2]),"+f"(d[3]),"+f"(d[4]),"+f"(d[5]),"+f"(d[6]),"+f"(d[7]),"+f"(d[8]),"+f"(d[9]),"+f"(d[10]),"+f"(d[11]),"+f"(d[12]),"+f"(d[13]),"+f"(d[14]),"+f"(d[15]),"+f"(d[16]),"+f"(d[17]),"+f"(d[18]),"+f"(d[19]),"+f"(d[20]),"+f"(d[21]),"+f"(d[22]),"+f"(d[23]),"+f"(d[24]),"+f"(d[25]),"+f"(d[26]),"+f"(d[27]),"+f"(d[28]),"+f"(d[29]),"+f"(d[30]),"+f"(d[31]),"+f"(d[32]),"+f"(d[33]),"+f"(d[34]),"+f"(d[35]),"+f"(d[36]),"+f"(d[37]),"+f"(d[38]),"+f"(d[39]),"+f"(d[40]),"+f"(d[41]),"+f"(d[42]),"+f"(d[43]),"+f"(d[44]),"+f"(d[45]),"+f"(d[46]),"+f"(d[47]),"+f"(d[48]),"+f"(d[49]),"+f"(d[50]),"+f"(d[51]),"+f"(d[52]),"+f"(d[53]),"+f"(d[54]),"+f"(d[55]),"+f"(d[56]),"+f"(d[57]),"+f"(d[58]),"+f"(d[59]),"+f"(d[60]),"+f"(d[61]),"+f"(d[62]),"+f"(d[63]),"+f"(d[64]),"+f"(d[65]),"+f"(d[66]),"+f"(d[67]),"+f"(d[68]),"+f"(d[69]),"+f"(d[70]),"+f"(d[71]),"+f"(d[72]),"+f"(d[73]),"+f"(d[74]),"+f"(d[75]),"+f"(d[76]),"+f"(d[77]),"+f"(d[78]),"+f"(d[79]),"+f"(d[80]),"+f"(d[81]),"+f"(d[82]),"+f"(d[83]),"+f"(d[84]),"+f"(d[85]),"+f"(d[86]),"+f"(d[87]) : "l"(da), "l"(db), "r"(sc));
}

struct Params { const __nv_bfloat16 *x, *logA, *Aim, *Cr, *Ci, *logdt, *Dskip, *Wg, *Wu, *Wd; __nv_bfloat16* out; uint4* xnT; float2* st; uint2* S; unsigned* flags; };
struct Maps { CUtensorMap x[2], xo, wg, wu, wd, hst[2], hld, xt, sld; };

__device__ __forceinline__ void conv_channel(uint32_t cb, int w, int lane, uint32_t (&res)[8], uint32_t sig, int sidx) {
    const int q = lane & 3, g = lane >> 2, gam = g >> 2;
    float acc[64];
    uint2 a[17][2];
    const uint32_t t0 = cb + CH_T + (uint32_t)(14 + 4 * w + (g & 3) - 2 * q) * 280u + gam * 8;
#define LDA(s0, s1) _Pragma("unroll") for (int s = s0; s < s1; s++) { a[s][0] = lds64(t0 + s * 16); a[s][1] = lds64(t0 - 8 * 280 + s * 16); }
#define CT(N, s) wg_rs<N>(acc, a[s][0].x, a[s][0].y, a[s][1].x, a[s][1].y, dU + 4 * (s))
    const uint64_t dU = mkdesc(cb + CH_U, UPLANE, 128, 0);
    LDA(0, 17)
    if (sig) { fence_async_smem(); mbar_arrive(sig); }
    WG_FENCE();
    if (w == 0) STAMP2(52 + 3 * sidx);
    wg_rs_first(acc, a[0][0].x, a[0][0].y, a[0][1].x, a[0][1].y, dU);
    CT(128, 1); CT(120, 2); CT(120, 3); CT(112, 4); CT(112, 5); CT(104, 6); CT(104, 7); CT(96, 8);
    CT(96, 9); CT(88, 10); CT(88, 11); CT(80, 12); CT(80, 13); CT(72, 14); CT(72, 15); CT(64, 16);
#undef CT
#undef LDA
    wg_tt64(acc, mkdesc(cb + CH_A3, 128, 512, 0), mkdesc(cb + CH_B3, 384, 32, 0), 1);
    wg_tt32(acc, mkdesc(cb + CH_A3 + 256, 128, 512, 0), mkdesc(cb + CH_B3 + 128, 384, 32, 0), 1);
    WG_COMMIT();
    if (w == 0) STAMP2(53 + 3 * sidx);
    WG_WAIT(0);
    fence_acc(acc);
    if (w == 0) STAMP2(54 + 3 * sidx);
    const int src1 = (lane & ~3) | ((q + 1) & 3);
    float E[16][2];
    #pragma unroll
    for (int j = 0; j < 16; j++) {
        const float nxt = (j < 15) ? acc[4 * (j + 1) + 2] : 0.f;
        const float sup = (q == 0) ? nxt : acc[4 * j + 2];
        const float v = __shfl_sync(0xffffffffu, sup, src1);
        E[j][0] = acc[4 * j] + acc[4 * j + 3];
        E[j][1] = acc[4 * j + 1] + v;
    }
    const int src2 = gam ? ((lane & 12) | ((q + 3) & 3)) : (16 | (lane & 12) | ((q + 1) & 3));
    const bool c1 = gam && q != 0, c2 = gam && q == 0;
    #pragma unroll
    for (int a2 = 0; a2 < 8; a2++) {
        float y[2];
        #pragma unroll
        for (int e = 0; e < 2; e++) {
            const float sup = c1 ? E[2 * a2][e] : E[2 * a2 + 1][e];
            const float nxt = (a2 < 7) ? E[2 * a2 + 2][e] : 0.f;
            const float keep = c2 ? nxt : (c1 ? E[2 * a2 + 1][e] : E[2 * a2][e]);
            y[e] = keep + __shfl_sync(0xffffffffu, sup, src2);
        }
        res[a2] = pack2(y[1], y[0]);
    }
}

__device__ __forceinline__ void consumer(uint32_t sb, int warp, const Params& P, const Maps& M) {
    const int V = warp >> 2, w = warp & 3, lane = threadIdx.x & 31, q = lane & 3, g = lane >> 2;
    const int c = blockIdx.x;
    const uint32_t bars = sb + OFF_BAR, xb = sb + OFF_X + V * 2 * XBUF;
    {
        float ag[88], au[88];
        define_acc(ag); define_acc(au);
        mbar_wait(bars + 8 * B_FULLW, 0);
        mbar_wait(bars + 8 * (B_FULLX + 2 * V), 0);
        #pragma unroll 1
        for (int st = 0; st < 8; st++) {
            uint64_t dG = mkdesc(sb + OFF_W + (st & 3) * 16384, 0, 1024, 1), dX = mkdesc(xb + (st & 1) * XBUF, 16, 1024, 1);
            uint32_t sig = lane == 0 && (V ? st < 6 : st > 0);
            asm volatile("" : "+l"(dG), "+l"(dX), "+r"(sig) :: "memory");
            if (V ? st < 7 : st > 1) mbar_wait(bars + 8 * (B_TURN + V), st & 1);
            STAMP(40 + 8 * V + st);
            WG_FENCE();
            #pragma unroll
            for (int k = 0; k < 4; k++) {
                if (k == SIGK) mbar_arrive_if(bars + 8 * (B_TURN + 1 - V), sig);
                wg_g1(ag, dG + k * 128, dX + k * 2, k ? 1 : st);
                wg_g1(au, dG + 512 + k * 128, dX + k * 2, k ? 1 : st);
            }
            WG_COMMIT();
            if (st == 6 * V) {
                mbar_wait(bars + 8 * (B_FULLW + ((st + 1) & 3)), V);
                mbar_wait(bars + 8 * (B_FULLX + 2 * V + 1), V);
            } else {
                WG_WAIT(1);
                mbar_arrive_if(bars + 8 * (B_EMPTYW + 2 * V), lane == 0 && st == 6 * V + 1);
                mbar_arrive_if(bars + 8 * (B_EMPTYX + 2 * V), lane == 0 && st == 6 * V + 1);
                WG_WAIT(0);
                mbar_arrive_if(bars + 8 * (B_EMPTYW + (st & 3)), lane == 0);
                mbar_arrive_if(bars + 8 * (B_EMPTYX + 2 * V + (st & 1)), lane == 0);
                if (st < 7) {
                    mbar_wait(bars + 8 * (B_FULLW + ((st + 1) & 3)), (st + 1) >> 2);
                    mbar_wait(bars + 8 * (B_FULLX + 2 * V + ((st + 1) & 1)), ((st + 1) >> 1) & 1);
                }
            }
        }
        WG_WAIT(0);
        fence_acc(ag); fence_acc(au);
        STAMP(8 * V + 1);
        float cg0 = ag[84], cg1 = ag[86], cu0 = au[84], cu1 = au[86];
        const uint32_t ca = sb + OFF_CSUM + (8 * w + g) * 16;
        if (V == 0) { sts128(ca, FU(cg0), FU(cg1), FU(cu0), FU(cu1)); mbar_arrive(bars + 8 * B_CS); }
        else { mbar_wait(bars + 8 * B_CS, 0); const uint4 t = lds128(ca); cg0 = UF(t.x); cg1 = UF(t.y); cu0 = UF(t.z); cu1 = UF(t.w); }
        mbar_wait(bars + 8 * B_STATS, 0);
        mbar_wait(bars + 8 * (B_EMPTYX + 2 * V), 1);
        STAMP(13 + V);
        const uint32_t hs = xb + (2 * w + ((lane >> 3) & 1)) * (2688 + 128 * V) + (lane >> 4) * 128 + (lane & 7) * 16;
        const uint32_t sa = sb + OFF_ST + (168 * V + 2 * q) * 8;
        uint4 sq[22];
        #pragma unroll
        for (int j = 0; j < 3; j++) sq[j] = lds128(sa + j * 64);
        #pragma unroll
        for (int j = 0; j < 22; j += 2) {
            uint32_t o[4];
            #pragma unroll
            for (int jj = 0; jj < 2; jj++) {
                const uint4 sv = sq[j + jj];
                float hv[4];
                #pragma unroll
                for (int i = 0; i < 4; i++) {
                    const float m = UF((i & 1) ? sv.z : sv.x);
                    const float gh = fmaf(-m, (i & 2) ? cg1 : cg0, ag[4 * (j + jj) + i]) * UF((i & 1) ? sv.w : sv.y);
                    const float p = gh * fmaf(-m, (i & 2) ? cu1 : cu0, au[4 * (j + jj) + i]);
                    hv[i] = fmaf(p, tanh_fast(gh), p);
                }
                o[2 * jj] = pack2(hv[0], hv[1]); o[2 * jj + 1] = pack2(hv[2], hv[3]);
            }
            #pragma unroll
            for (int k = (j ? 3 + 3 * j / 2 : 3); k < 6 + 3 * j / 2 && k < 22; k++) sq[k] = lds128(sa + k * 64);
            uint32_t ad = hs + j * 128;
            if (j == 20 && V == 0 && lane >= 16) ad = xb + 21504 + (lane & 7) * 16;
            stsm4(ad, o[0], o[1], o[2], o[3]);
        }
        if (c >= 128 || V) { fence_async_smem(); mbar_arrive(bars + 8 * (B_EPI + V)); }
        STAMP(8 * V + 2);
    }
    if (c >= 128) return;
    {
        uint32_t r0[8], r1[8];
        #pragma unroll
        for (int i = 0; i < 8; i++) asm volatile("" : "=r"(r1[i]));
        #pragma unroll 1
        for (int e = 0; e < 2; e++) {
            #pragma unroll
            for (int i = 0; i < 8; i++) r0[i] = r1[i];
            mbar_wait(bars + 8 * (B_CONV + 2 * V + e), 0);
            conv_channel(sb + OFF_CONV + (2 * V + e) * CH_STRIDE, w, lane, r1, (e | V) ? 0 : bars + 8 * B_EPI, 2 * V + e);
            if (e == 0) STAMP(8 * V + 3);
        }
        const int gam = g >> 2, qq = gam ? ((q + 3) & 3) : q;
        const uint32_t sp = sb + OFF_CONV + V * OFF_SST + ((63 - 4 * gam - qq) * 16 + 4 * (w ^ (3 - qq)) + (g & 3)) * 8;
        bar_sync(3 + V);
        #pragma unroll
        for (int a2 = 0; a2 < 8; a2++) sts64(sp - a2 * 1024, r0[a2], r1[a2]);
        fence_async_smem();
        mbar_arrive(bars + 8 * (B_SIG + V));
        STAMP(8 * V + 4);
    }
    if (V == 1) return;
    {
        const int tau = c >> 2, dg = c & 3;
        const uint32_t row = 8 * (w & 1) + 32 * (w >> 1);
        float acc[64];
        define_acc(acc);
        const float rr0 = __ldcg(&P.st[64 * tau + row + g].y), rr1 = __ldcg(&P.st[64 * tau + row + g + 16].y);
        mbar_wait(bars + 8 * B_FULLD, 0);
        STAMP(5);
        uint64_t dB = mkdesc(sb + wd_slot(0), 8192, 1024, 1), dA = mkdesc(sb + h_slot(0), 1024, 128, 0);
        int sd = 0; uint32_t np = 0;
        #pragma unroll 1
        for (int st = 0; st < 21; st++) {
            WG_FENCE();
            wg_tt128(acc, dA, dB, st);
            wg_tt128(acc, dA + 128, dB + 128, 1);
            wg_tt128(acc, dA + 256, dB + 256, 1);
            wg_tt128(acc, dA + 384, dB + 384, 1);
            WG_COMMIT();
            uint32_t ro = bars + 8 * (B_EMPTYD + (sd ? sd - 1 : 6)), m = lane == 0 && st > 0, ok;
            if (++sd == 7) { sd = 0; np ^= 1; }
            const uint32_t nb = bars + 8 * (B_FULLD + sd);
            dB = mkdesc(sb + wd_slot(sd), 8192, 1024, 1); dA = mkdesc(sb + h_slot(sd), 1024, 128, 0);
            asm volatile("{.reg .pred p; mbarrier.test_wait.parity.shared::cta.b64 p, [%5], %6; vote.sync.all.pred p, p, -1; selp.u32 %0, 1, 0, p;}"
                : "=r"(ok), "+l"(dA), "+l"(dB), "+r"(ro), "+r"(m) : "r"(nb), "r"(np) : "memory");
            WG_WAIT(1);
            mbar_arrive_if(ro, m);
            if (!ok) mbar_wait(nb, np);
            if (w == 0) STAMP2(20 + st);
        }
        WG_FENCE();
        wg_tt128(acc, dA, dB, 1);
        wg_tt128(acc, dA + 128, dB + 128, 1);
        WG_COMMIT();
        mbar_wait(bars + 8 * B_XO, 0);
        const uint32_t xo = sb + OFF_XO + (row + (lane & 7) + 16 * ((lane >> 3) & 1)) * 128;
        const uint32_t so = sb + OFF_SI + (w >> 1) * 8192 + q * 256 + (g & 1) * 8;
        const uint32_t sx = (4 * (w & 1) + (g >> 1)) ^ (2 * q) ^ (2 * ((2 * tau + (w >> 1)) & 3));
        uint32_t xr[8][4];
        uint2 sv[16];
        #pragma unroll
        for (int j = 0; j < 16; j += 2) {
            ldsm4(xr[j >> 1], xo + (j >> 3) * 8192 + ((((j & 7) + (lane >> 4)) ^ (lane & 7)) << 4));
            sv[j] = lds64(so + j * 512 + (sx << 4));
            sv[j + 1] = lds64(so + j * 512 + 128 + ((sx ^ 1) << 4));
        }
        WG_WAIT(0);
        fence_acc(acc);
        STAMP(6);
        #pragma unroll
        for (int j = 0; j < 16; j += 2) {
            #pragma unroll
            for (int i = 0; i < 4; i++) {
                const int jj = j + (i >> 1), hh = i & 1;
                const float f0 = acc[4 * jj + 2 * hh] * (hh ? rr1 : rr0), f1 = acc[4 * jj + 2 * hh + 1] * (hh ? rr1 : rr0);
                const uint32_t G = pack2(fmaf(f0, tanh_fast(f0), f0), fmaf(f1, tanh_fast(f1), f1));
                const uint32_t s2 = __byte_perm(sv[jj].x, sv[jj].y, hh ? 0x7632 : 0x5410);
                asm("fma.rn.bf16x2 %0, %1, %2, %0;" : "+r"(xr[j >> 1][i]) : "r"(s2), "r"(G));
            }
            stsm4(xo + (j >> 3) * 8192 + ((((j & 7) + (lane >> 4)) ^ (lane & 7)) << 4), xr[j >> 1][0], xr[j >> 1][1], xr[j >> 1][2], xr[j >> 1][3]);
        }
        __syncwarp();
        {
            const uint32_t rr = row + ((lane >> 4) << 4), la = sb + OFF_XO + rr * 128 + ((lane >> 3) & 1) * 8192;
            uint4* dst = (uint4*)(P.out + (64 * tau + rr) * DM + 128 * dg) + (lane & 15);
            uint4 v[8];
            #pragma unroll
            for (int i = 0; i < 8; i++) v[i] = lds128(la + i * 128 + (((lane & 7) ^ i) << 4));
            #pragma unroll
            for (int i = 0; i < 8; i++) dst[i * 64] = v[i];
        }
        STAMP(7); GSTAMP(23);
    }
}

__device__ __forceinline__ float2 cexp_p(float re2, float im, float p) {
    float sn, cs;
    const float mag = ex2(re2 * p), th = im * p;
    asm("sin.approx.ftz.f32 %0, %1;" : "=f"(sn) : "f"(th));
    asm("cos.approx.ftz.f32 %0, %1;" : "=f"(cs) : "f"(th));
    return make_float2(mag * cs, mag * sn);
}
struct SsmRaw { unsigned short la, ai, cr, ci, ldt, dsk; };
__device__ __forceinline__ unsigned short ldu16(const void* p) { unsigned short v; asm volatile("ld.global.nc.u16 %0, [%1];" : "=h"(v) : "l"(p)); return v; }
__device__ __forceinline__ float2 cmul(float2 a, float2 b) { return make_float2(fmaf(a.x, b.x, -a.y * b.y), fmaf(a.x, b.y, a.y * b.x)); }
__device__ __forceinline__ float2 csqr(float2 a) { const float t = a.x * a.y; return make_float2(fmaf(a.x, a.x, -a.y * a.y), t + t); }
__device__ __forceinline__ void mma16816(float (&d)[4], const uint32_t (&a)[4], uint32_t b0, uint32_t b1) {
    asm volatile("mma.sync.aligned.m16n8k16.row.col.f32.bf16.bf16.f32 {%0,%1,%2,%3}, {%4,%5,%6,%7}, {%8,%9}, {%0,%1,%2,%3};"
        : "+f"(d[0]), "+f"(d[1]), "+f"(d[2]), "+f"(d[3]) : "r"(a[0]), "r"(a[1]), "r"(a[2]), "r"(a[3]), "r"(b0), "r"(b1));
}

__device__ __forceinline__ void layer_norm(uint32_t sb, uint32_t cb, int w, int lane) {
    const uint32_t bars = sb + OFF_BAR;
    mbar_wait(bars + 8 * B_LNX, 0);
    STAMP(34);
    {
        const uint32_t r0 = cb + CH_LN + (w & 1) * 64 + (lane >> 3) * 1040, ra = r0 + (lane & 7) * 16;
        const float pv = bf_lo(FU(ldsf(r0)));
        float s0 = 0.f, s1 = 0.f, a0 = 0.f, a1 = 0.f;
        #pragma unroll 1
        for (int k = 0; k < 1024; k += 512) {
            uint32_t v[16];
            #pragma unroll
            for (int j = 0; j < 4; j++) *(uint4*)&v[4 * j] = lds128(ra + k + 128 * j);
            #pragma unroll
            for (int i = 0; i < 16; i++) { const float t0 = bf_lo(v[i]) - pv, t1 = bf_hi(v[i]) - pv; s0 += t0; s1 += t1; a0 = fmaf(t0, t0, a0); a1 = fmaf(t1, t1, a1); }
        }
        s0 += s1; a0 += a1;
        #pragma unroll
        for (int o = 4; o; o >>= 1) { s0 += __shfl_xor_sync(0xffffffffu, s0, o); a0 += __shfl_xor_sync(0xffffffffu, a0, o); }
        s0 *= 1.f / DM;
        float sd, ri;
        asm("sqrt.approx.ftz.f32 %0, %1;" : "=f"(sd) : "f"(bf_round(bf_round(fmaxf(fmaf(-s0, s0, a0 * (1.f / DM)), 0.f)) + 1e-5f)));
        asm("rcp.approx.ftz.f32 %0, %1;" : "=f"(ri) : "f"(bf_round(sd)));
        if ((lane & 7) == 0) sts64(sb + OFF_CSUM + (w + 4 * (lane >> 3)) * 8, FU(bf_round(pv + s0)), FU(0.5f * ri));
    }
    STAMP(62);
    bar_sync(2);
    const int r = 4 * ((lane & 7) >> 1) + (lane & 1) + 2 * ((lane >> 3) & 1);
    const uint32_t ad = sb + OFF_CONV + (r & 3) * CH_STRIDE + CH_LN + (r & 1) * 64 + (r >> 2) * 1040 + (16 * w + (lane >> 4)) * 16;
    const uint4 sa = lds128(sb + OFF_CSUM + (lane & 3) * 32), sc = lds128(sb + OFF_CSUM + (lane & 3) * 32 + 16);
    const uint32_t m2[2] = {__byte_perm(sa.x, sa.z, 0x7632), __byte_perm(sc.x, sc.z, 0x7632)};
    const float ri[4] = {2.f * UF(sa.y), 2.f * UF(sa.w), 2.f * UF(sc.y), 2.f * UF(sc.w)};
    #pragma unroll 1
    for (int i = 0; i < 8; i += 4) {
        uint32_t v[4][4];
        #pragma unroll
        for (int j = 0; j < 4; j++)
            asm volatile("ldmatrix.sync.aligned.m8n8.x4.trans.shared.b16 {%0,%1,%2,%3}, [%4];" : "=r"(v[j][0]), "=r"(v[j][1]), "=r"(v[j][2]), "=r"(v[j][3]) : "r"(ad + 32 * (i + j)) : "memory");
        #pragma unroll
        for (int j = 0; j < 4; j++) {
            #pragma unroll
            for (int k = 0; k < 4; k++) {
                uint32_t dv; asm("sub.rn.bf16x2 %0, %1, %2;" : "=r"(dv) : "r"(v[j][k]), "r"(m2[k & 1]));
                v[j][k] = pack2(bf_lo(dv) * ri[2 * (k & 1)], bf_hi(dv) * ri[2 * (k & 1) + 1]);
            }
            sts64(cb + CH_LNT + lane * 8 + (i + j) * 512, v[j][0], v[j][1]); sts64(cb + CH_LNT + lane * 8 + (i + j) * 512 + 256, v[j][2], v[j][3]);
        }
    }
    fence_async_smem();
    mbar_arrive(bars + 8 * B_LN);
    STAMP(16);
}

__device__ __forceinline__ void kernel_gen(uint32_t fs, int lane, const SsmRaw& raw, float (&dacc)[2][3][4], const Params& P, int warp) {
    const float dt = bf_round(ex2(bf_lo(raw.ldt) * 1.4426950408889634f));
    const float re2 = bf_round(ex2(bf_lo(raw.la) * 1.4426950408889634f)) * dt * -1.4426950408889634f, im = bf_lo(raw.ai) * dt;
    const float2 C = make_float2(bf_lo(raw.cr) * (dt + dt), bf_lo(raw.ci) * -(dt + dt));
    STAMP(56);
    if (warp < 4 && lane == 0 && re2 != 1.f) {
        const int c = blockIdx.x;
        const char* p = warp < 2 ? (const char*)(P.x + (16 * (c & ~1) + 8 * (c & 1) + 16 * warp) * DM) : (const char*)(warp == 2 ? P.Wg : P.Wu) + 256 * FF * 2 + c * 5504;
        asm volatile("cp.async.bulk.prefetch.L2.global [%0], %1;" :: "l"(p), "r"(warp < 2 ? 8192 : 5504) : "memory");
    }
    const float2 y1 = cexp_p(re2, -im, 1.f), y256 = cexp_p(re2, -im, 256.f), z64 = cexp_p(re2, im, 64.f);
    const uint32_t fm = fs + (lane >> 3) * 144 + (lane & 7) * 16;
#define PK(v) pack2((v).x, (v).y)
    const float2 y2 = csqr(y1), y4 = csqr(y2), y8 = csqr(y4);
    const float2 l1 = cmul(C, y1), l2 = cmul(C, y2), l3 = cmul(l1, y2);
    stsm4(fm, PK(C), PK(l1), PK(l2), PK(l3));
    stsm4(fm + 4 * 144, PK(cmul(C, y4)), PK(cmul(l1, y4)), PK(cmul(l2, y4)), PK(cmul(l3, y4)));
    const float2 t0 = cmul(C, y256), t1 = cmul(t0, y256), t2 = cmul(t1, y256), t3_ = cmul(t2, y256);
    const float2 u1 = cmul(t0, y2), u2 = cmul(u1, y2), u3 = cmul(u2, y2);
    stsm4(fm + 8 * 144, PK(t0), PK(u1), PK(u2), PK(u3));
    stsm4(fm + 12 * 144, PK(t1), PK(cmul(t1, y4)), PK(t2), PK(cmul(t2, y4)));
    const float2 v0 = cmul(t3_, y8), v1 = cmul(v0, y256), v2 = cmul(v1, y256), v3 = cmul(v2, y256);
    stsm4(fm + 16 * 144, PK(v0), PK(v1), PK(v2), PK(v3));
    stsf(fs + lane * 4 + 20 * 144, UF(PK(t3_)));
    STAMP(57);
    const uint32_t ldb = fs + (lane & 7) * 144 + ((lane >> 3) & 1) * 16 + (lane >> 4) * 8 * 144;
    const float p8 = (float)(2 * (lane & 28));
    __syncwarp();
    #pragma unroll 1
    for (int ks = 0; ks < 4; ks++) {
        uint32_t b01[4], b2[2], a0[4], a1[4];
        ldsm4(b01, ldb + ks * 32);
        asm volatile("ldmatrix.sync.aligned.m8n8.x2.shared.b16 {%0,%1}, [%2];" : "=r"(b2[0]), "=r"(b2[1]) : "r"(ldb + 16 * 144 + ks * 32) : "memory");
        #pragma unroll
        for (int mh = 0; mh < 2; mh++) {
            const int src = 8 * ks + 4 * mh + (lane & 3);
            const float2 z = make_float2(__shfl_sync(0xffffffffu, z64.x, src), __shfl_sync(0xffffffffu, z64.y, src));
            const float2 R0 = cexp_p(__shfl_sync(0xffffffffu, re2, src), __shfl_sync(0xffffffffu, im, src), p8);
            const float2 R1 = cmul(R0, z), R2 = cmul(R1, z), R3 = cmul(R2, z);
            a0[2 * mh] = PK(R0); a0[2 * mh + 1] = PK(R1); a1[2 * mh] = PK(R2); a1[2 * mh + 1] = PK(R3);
        }
        mma16816(dacc[0][0], a0, b01[0], b01[1]); mma16816(dacc[1][0], a1, b01[0], b01[1]);
        mma16816(dacc[0][1], a0, b01[2], b01[3]); mma16816(dacc[1][1], a1, b01[2], b01[3]);
        mma16816(dacc[0][2], a0, b2[0], b2[1]);   mma16816(dacc[1][2], a1, b2[0], b2[1]);
    }
#undef PK
    STAMP(58);
}

__device__ __forceinline__ void aux_role(uint32_t sb, int w, float (&dacc)[2][3][4], float dsk, const __nv_bfloat16* x) {
    const int lane = threadIdx.x & 31, q = lane & 3, g = lane >> 2;
    const int c = blockIdx.x;
    const uint32_t bars = sb + OFF_BAR;
    if (c >= 128) { mbar_arrive(bars + 8 * B_LN); return; }
    {
        const uint32_t cb = sb + OFF_CONV + w * CH_STRIDE;
        if (elect_one()) {
            fence_async_smem();
            mbar_expect(bars + 8 * B_LNX, 4096);
            #pragma unroll
            for (int i = 0; i < 4; i++)
                bulk_load(cb + CH_LN + (w & 1) * 64 + i * 1040, x + (16 * (c & ~1) + 8 * (c & 1) + 16 + w + 4 * (i & 1) - 8 * (i & 2)) * DM, 1024, bars + 8 * B_LNX);
        }
        layer_norm(sb, cb, w, lane);
        #pragma unroll 1
        for (uint32_t pa = cb + CH_PART + lane * 16; pa < cb + CH_PART + 3 * CH_PSZ; pa += CH_PSZ) {
            #pragma unroll
            for (int i = 0; i < 6; i++) {
                const uint4 v = lds128(pa + i * 512);
                float* d = &dacc[0][0][0] + 4 * i;
                d[0] += UF(v.x); d[1] += UF(v.y); d[2] += UF(v.z); d[3] += UF(v.w);
            }
        }
        __syncwarp();
        STAMP(18);
        const uint32_t sF = cb + CH_A3, sG = cb + CH_G;
        if (lane == 0) dacc[0][0][0] += dsk;
        if (lane < 10) sts128(sG + 128 + (lane & 1) * 208 + (lane >> 1) * 16, 0, 0, 0, 0);
        const uint32_t f0 = sF + (8 * g + 2 * q) * 4, f1 = sF + ((q < 2) ? 256 + 4 * g + 2 * q : 256 + 2 * g + 64 * q) * 4, st1 = (q < 2) ? 128 : 64;
        const uint32_t ga = sG + ((g & 1) ? 0 : 208) + (63 - (g >> 1) - 32 * q) * 2;
        #pragma unroll
        for (int i = 0; i < 4; i++) {
            const int mu = i >> 1, hh = i & 1;
            sts64(f0 + i * 256, FU(dacc[mu][0][2 * hh]), FU(dacc[mu][0][2 * hh + 1]));
            sts64(f1 + i * st1, FU(dacc[mu][1][2 * hh]), FU(dacc[mu][1][2 * hh + 1]));
            const uint32_t pk = pack2(dacc[mu][2][2 * hh], dacc[mu][2][2 * hh + 1]);
            if (q < 2) { sts16(ga - 8 * i, pk & 0xffff); sts16(ga - 8 * i - 32, pk >> 16); }
        }
        if (lane == 2) stsf(sF + 2048, dacc[0][2][0]);
        STAMP(19);
        bar_sync(2);
    }
    const int u = min(lane, 30) - 15, r2 = (u + ((u >> 1) & 1)) >> 1, r4 = (u + 1 + ((u >> 2) & 1)) >> 2, xt = 1024 + 16 * w + u;
    const uint32_t o0 = CH_A3 + 4 * (w == 0 ? u : w == 1 ? 256 + r2 : 256 + 64 * w + r4), ost = w == 0 ? 64 : w == 1 ? 32 : 16;
    const uint32_t oa0 = u >= 0 || w == 3 ? o0 : CH_A3 + 4 * (w == 1 ? 256 + u : w == 2 ? 384 + r2 : 0);
    const uint32_t ot = CH_A3 + 4 * min(512, 256 + ((xt + 1 + ((xt >> 2) & 1)) >> 2));
    const int kap = (lane >> 4) * 8 + ((lane >> 1) & 7), gam = lane & 1, hh = w >> 1, wp = w & 1;
    const uint32_t oa = CH_U + wp * UPLANE + (127 - 4 * kap - 2 * gam - hh) * 16;
    const uint32_t ob = CH_U + (wp ^ 1) * UPLANE + (128 - wp - 4 * kap - 2 * gam - hh) * 16;
    const uint32_t od = CH_A3 + (4 * wp + hh) * 512 + (kap >> 3) * 256 + (kap & 7) * 16 + gam * 8;
    #pragma unroll 1
    for (uint32_t cb = sb + OFF_CONV; cb < sb + OFF_CONV + 4 * CH_STRIDE; cb += CH_STRIDE) {
        {
            float kv[17];
            kv[0] = ldsf(cb + oa0); kv[16] = ldsf(cb + ot);
            #pragma unroll
            for (int s = 1; s < 16; s++) kv[s] = ldsf(cb + o0 + s * ost);
            const int tid = threadIdx.x & 127;
            const uint32_t ga = cb + CH_G + (tid >= 24) * 16 + min(tid, 47) * 8;
            const uint2 x0 = lds64(ga), x1 = lds64(ga + 8);
            if (u < 0 && w == 0) kv[0] = 0.f;
            if (xt > 1028) kv[16] = 0.f;
            uint32_t o[17];
            #pragma unroll
            for (int s = 0; s < 17; s++) o[s] = pack2(kv[s], __shfl_up_sync(0xffffffffu, kv[s], 1));
            if (lane > 0 && lane < 31) {
                const uint32_t ta = cb + CH_T + (lane - 1) * 280;
                #pragma unroll
                for (int s2 = 0; s2 < 8; s2++) sts64(ta + 64 * w + s2 * 8, o[2 * s2], o[2 * s2 + 1]);
                stsf(ta + 256 + 4 * w, UF(o[16]));
            }
            if (tid < 48) sts128(cb + CH_B3 + tid * 16, x0.x, x0.y, x1.x, x1.y);
        }
    }
    STAMP(61);
    mbar_wait(bars + 8 * B_U, 0);
    if (lane < 8) sts128(sb + OFF_CONV + w * CH_STRIDE + CH_U + 2048 + (lane & 4) * (UPLANE / 4) + (lane & 3) * 16, 0, 0, 0, 0);
    bar_sync(2);
    #pragma unroll 1
    for (int k = 0; k < 4; k++) {
        const int ch = 2 * (k & 1) + (k >> 1);
        const uint32_t cb = sb + OFF_CONV + ch * CH_STRIDE;
        float p[24];
        const uint2 r0 = lds64(cb + ob + 24), r3 = lds64(cb + oa);
        uint32_t r[8];
        *(uint4*)&r[0] = lds128(cb + oa + 16); *(uint4*)&r[4] = lds128(cb + ob);
        p[0] = 0.f;
        p[1] = bf_lo(r0.x); p[2] = p[1] + bf_hi(r0.x); p[3] = p[2] + bf_lo(r0.y); p[4] = p[3] + bf_hi(r0.y);
        #pragma unroll
        for (int i = 0; i < 8; i++) { p[5 + 2 * i] = p[4 + 2 * i] + bf_lo(r[i]); p[6 + 2 * i] = p[5 + 2 * i] + bf_hi(r[i]); }
        p[21] = p[20] + bf_lo(r3.x); p[22] = p[21] + bf_hi(r3.x); p[23] = p[22] + bf_lo(r3.y);
        #pragma unroll
        for (int i = 0; i < 8; i += 4) {
            sts64(cb + od + i * 256, pack2(p[i + 9] - p[i], p[i + 10] - p[i + 1]), pack2(p[i + 11] - p[i + 2], p[i + 12] - p[i + 3]));
            sts64(cb + od + i * 256 + 128, pack2(p[i + 16] - p[i + 9], p[i + 17] - p[i + 10]), pack2(p[i + 18] - p[i + 11], p[i + 19] - p[i + 12]));
        }
        fence_async_smem();
        mbar_arrive(bars + 8 * (B_CONV + ch));
        if (k == 0) STAMP(17);
    }
    STAMP(21);
}

__device__ __forceinline__ void store_h(uint32_t sb, const Params& P, const Maps& M, int V, int tg, int fb) {
    const uint32_t bars = sb + OFF_BAR;
    mbar_wait(bars + 8 * (B_EPI + V), 0);
    STAMP2(3 + 2 * V);
    asm volatile("cp.async.bulk.tensor.3d.global.shared::cta.bulk_group [%0, {%2, %3, %4}], [%1];"
        :: "l"(&M.hst[V]), "r"(sb + OFF_X + V * 2 * XBUF), "r"(0), "r"(43 * tg + 21 * V), "r"(8 * fb) : "memory");
    flag_signal(P.flags, F_H + 2 * tg + V);
    mbar_arrive(bars + 8 * (B_STG + V));
    STAMP2(4 + 2 * V);
}

__global__ void __launch_bounds__(512, 1)
fused_kernel(const __grid_constant__ Params P, const __grid_constant__ Maps M) {
    extern __shared__ __align__(1024) uint8_t smem_raw[];
    const uint32_t sb = smem_u32(smem_raw);
    const uint32_t bars = sb + OFF_BAR;
    const int warp = __shfl_sync(0xffffffffu, threadIdx.x >> 5, 0);
    const int c = blockIdx.x, tg = c / 22, fb = c - 22 * tg;
    SsmRaw raw;
    {
        const int d = min(4 * c + (warp & 3), DM - 1), o = d * 128 + (warp >> 2) * 32 + (threadIdx.x & 31);
        raw.la = ldu16(P.logA + o); raw.ai = ldu16(P.Aim + o); raw.cr = ldu16(P.Cr + o); raw.ci = ldu16(P.Ci + o);
        raw.ldt = ldu16(P.logdt + d); raw.dsk = ldu16(P.Dskip + d);
    }
    if (elect_one()) {
        if (warp == 0) { STAMP(24); GSTAMP(22); }
        asm volatile("" :: "l"(((const uint64_t*)&P)[warp < 15 ? warp : 0]));
        if (warp < 11) asm volatile("prefetch.tensormap [%0];" :: "l"(&M.x[0] + warp) : "memory");
        #pragma unroll
        for (int k = 0; k < 4; k++) {
            const int i = 16 * k + ((warp + 4) & 15);
            const uint32_t cnt = i >= B_CONV ? 128 : ((0xf0ull >> i) & 1) ? 8 : ((0xff0000ull >> i) & 1) ? 2 : ((0x3e00ff00f000ull >> i) & 1) ? 4 : 1;
            asm volatile("mbarrier.init.shared::cta.b64 [%0], %1;" :: "r"(bars + 8 * i), "r"(cnt) : "memory");
        }
        asm volatile("fence.mbarrier_init.release.cluster; fence.proxy.async.shared::cta;" ::: "memory");
        if (warp >= 12) {
            const uint32_t s = warp - 12;
            mbar_expect(bars + 8 * (B_FULLW + s), 16384);
            tma2d(sb + OFF_W + s * 16384, &M.wg, 64 * fb, 64 * s, bars + 8 * (B_FULLW + s));
            tma2d(sb + OFF_W + s * 16384 + 8192, &M.wu, 64 * fb, 64 * s, bars + 8 * (B_FULLW + s));
            STAMP(31);
        } else if ((warp >> 2) == 1) {
            const uint32_t s = warp - 4, V = s >> 1;
            mbar_expect(bars + 8 * (B_FULLX + s), (168 + 8 * V) * 128);
            tma2d(sb + OFF_X + s * XBUF, &M.x[V], 64 * (s & 1), TOKG * tg + 168 * V, bars + 8 * (B_FULLX + s));
        }
        if (sb & 1023) __trap();
    }
    if (warp < 4) sts128(sb + OFF_X + (warp >> 1) * XBUF + 168 * 128 + (threadIdx.x & 63) * 16, 0x3f803f80u, 0x3f803f80u, 0x3f803f80u, 0x3f803f80u);
    float dacc[2][3][4];
    #pragma unroll
    for (int i = 0; i < 24; i++) (&dacc[0][0][0])[i] = 0.f;
    if (c < 128) {
        const int wg = warp >> 2;
        const uint32_t fs = sb + OFF_CONV + (warp & 3) * CH_STRIDE + (wg == 2 ? 0 : CH_PART + min(wg, 2) * CH_PSZ);
        kernel_gen(fs, threadIdx.x & 31, raw, dacc, P, warp);
        if (wg != 2) {
            __syncwarp();
            #pragma unroll
            for (int i = 0; i < 6; i++) { const float* d = &dacc[0][0][0] + 4 * i; sts128(fs + (threadIdx.x & 31) * 16 + i * 512, FU(d[0]), FU(d[1]), FU(d[2]), FU(d[3])); }
        }
    }
    if (warp < 4) fence_async_smem();
    __syncthreads();
    if (warp < 8) {
        asm volatile("setmaxnreg.inc.sync.aligned.u32 208;");
        consumer(sb, warp, P, M);
        asm volatile("nanosleep.u32 1;");
    } else if (warp < 12) {
        asm volatile("setmaxnreg.dec.sync.aligned.u32 72;");
        STAMP(32);
        aux_role(sb, warp - 8, dacc, bf_lo(raw.dsk), P.x);
        asm volatile("nanosleep.u32 2;");
    } else {
        asm volatile("setmaxnreg.dec.sync.aligned.u32 24;");
        const int tau = c >> 2, dg = c & 3;
        if (elect_one()) {
            if (warp < 15) {
                if (warp == 12) {
                    #pragma unroll 1
                    for (int st = 4; st < 8; st++) {
                        const uint32_t s = st & 3, fb_ = bars + 8 * (B_FULLW + s);
                        mbar_wait(bars + 8 * (B_EMPTYW + s), 0);
                        mbar_expect(fb_, 16384);
                        tma2d(sb + OFF_W + s * 16384, &M.wg, 64 * fb, 64 * st, fb_);
                        tma2d(sb + OFF_W + s * 16384 + 8192, &M.wu, 64 * fb, 64 * st, fb_);
                    }
                } else {
                    const int V = warp - 13;
                    #pragma unroll 1
                    for (int st = 2; st < 8; st++) {
                        const uint32_t s = 2 * V + (st & 1);
                        mbar_wait(bars + 8 * (B_EMPTYX + s), ((st >> 1) & 1) ^ 1);
                        mbar_expect(bars + 8 * (B_FULLX + s), (168 + 8 * V) * 128);
                        tma2d(sb + OFF_X + s * XBUF, &M.x[V], 64 * st, TOKG * tg + 168 * V, bars + 8 * (B_FULLX + s));
                    }
                }
                if (warp == 14) store_h(sb, P, M, 1, tg, fb);
                if (c < 128 && warp < 14) {
                    if (warp == 13) {
                        mbar_wait(bars + 8 * (B_STG + 1), 0);
                        #pragma unroll 1
                        for (int o = 8 * tau; o < 8 * tau + 8; o += 7) flag_wait(P.flags, F_H + 2 * (o / 43) + ((o % 43) >= 21), 22);
                        mbar_arrive(bars + 8 * B_HF);
                        STAMP(25);
                    }
                    #pragma unroll 1
                    for (int st = 0; st < 22; st += (st < 6 || (st == 6 && warp == 13)) ? 1 : 2) {
                        const int rd = (st >= 7) + (st >= 14) + (st >= 21), sd = st - 7 * rd;
                        const uint32_t fb_ = bars + 8 * (B_FULLD + sd);
                        if (rd) mbar_wait(bars + 8 * (B_EMPTYD + sd), (rd & 1) ^ 1);
                        else if (warp == 12 || st == 6) mbar_wait(bars + 8 * (uint32_t)((0x3623070d060504ull >> (8 * st)) & 0xff), st < 5);
                        if (st >= 10 && st < 21) STAMP2(31 + st);
                        if (rd || warp == 13) {
                            mbar_expect(fb_, 8192);
                            asm volatile("cp.async.bulk.tensor.5d.shared::cluster.global.mbarrier::complete_tx::bytes [%0], [%1, {%3, %3, %3, %4, %5}], [%2];"
                                :: "r"(sb + h_slot(sd)), "l"(&M.hld), "r"(fb_), "r"(0), "r"(2 * tau), "r"(8 * st) : "memory");
                        }
                        if (rd || warp == 12) {
                            const uint32_t da = sb + wd_slot(sd);
                            mbar_expect(fb_, 16384);
                            tma2d(da, &M.wd, 128 * dg, 64 * st, fb_);
                            tma2d(da + 8192, &M.wd, 128 * dg + 64, 64 * st, fb_);
                        }
                    }
                } else if (c < 128) {
                    mbar_wait(bars + 8 * (B_SIG + 1), 0);
                    mbar_expect(bars + 8 * B_XO, 32768);
                    tma2d(sb + OFF_XO, &M.xo, 128 * dg, 64 * tau, bars + 8 * B_XO);
                    tma2d(sb + OFF_XO + 8192, &M.xo, 128 * dg + 64, 64 * tau, bars + 8 * B_XO);
                    mbar_wait(bars + 8 * B_SST, 0);
                    flag_wait(P.flags, F_S + dg, 64);
                    STAMP(26);
                    asm volatile("cp.async.bulk.tensor.5d.shared::cluster.global.mbarrier::complete_tx::bytes [%0], [%1, {%3, %3, %3, %4, %5}], [%2];"
                        :: "r"(sb + OFF_SI), "l"(&M.sld), "r"(bars + 8 * B_XO), "r"(0), "r"(8 * dg), "r"(2 * tau) : "memory");
                    mbar_wait(bars + 8 * B_HF, 0);
                    exit_count(P.flags);
                }
            } else {
                mbar_wait(bars + 8 * B_LN, 0);
                STAMP2(0);
                if (c < 128) {
                    #pragma unroll 1
                    for (int i = 0; i < 4; i++)
                        asm volatile("cp.async.bulk.tensor.2d.global.shared::cta.bulk_group [%0, {%2, %3}], [%1];"
                            :: "l"(&M.xt), "r"(sb + OFF_CONV + i * CH_STRIDE + CH_LNT), "r"((c & 1) * 1024 + (126 - (c & ~1)) * 8), "r"(128 * i) : "memory");
                    #pragma unroll 1
                    for (int i = 0; i < 2; i++) bulk_store(P.st + 16 * (c & ~1) + 8 * (c & 1) + 16 - 16 * i, sb + OFF_CSUM + 64 * i, 64);
                    asm volatile("cp.async.bulk.prefetch.L2.global [%0], %1;" :: "l"(P.Wd + c * (FF * DM / 128)), "r"(FF * DM / 64) : "memory");
                }
                STAMP2(1);
                flag_signal(P.flags, F_A);
                STAMP2(2);
                flag_wait(P.flags, F_A, NCTA);
                STAMP(20);
                mbar_expect(bars + 8 * B_STATS, TOKG * 8);
                bulk_load(sb + OFF_ST, P.st + TOKG * tg, TOKG * 8, bars + 8 * B_STATS);
                if (c < 128) {
                    mbar_expect(bars + 8 * B_U, 8 * 2048);
                    #pragma unroll 1
                    for (int i = 0; i < 8; i++)
                        bulk_load(sb + OFF_CONV + (i >> 1) * CH_STRIDE + CH_U + (i & 1) * UPLANE, P.xnT + 4 * c * 256 + i * 128, 2048, bars + 8 * B_U);
                } else exit_count(P.flags);
                store_h(sb, P, M, 0, tg, fb);
                if (c < 128) {
                    #pragma unroll 1
                    for (int V = 0; V < 2; V++) {
                        mbar_wait(bars + 8 * (B_SIG + V), 0);
                        STAMP2(7 + 2 * V);
                        bulk_store(P.S + (2 * c + V) * 1024, sb + OFF_CONV + V * OFF_SST, 8192);
                        flag_signal(P.flags, F_S + (c >> 5));
                        STAMP2(8 + 2 * V);
                    }
                    mbar_arrive(bars + 8 * B_SST);
                }
            }
            asm volatile("nanosleep.u32 0;");
        }
    }
}

typedef CUresult (*EncodeFn)(CUtensorMap*, CUtensorMapDataType, cuuint32_t, void*, const cuuint64_t*, const cuuint64_t*, const cuuint32_t*,
                             const cuuint32_t*, CUtensorMapInterleave, CUtensorMapSwizzle, CUtensorMapL2promotion, CUtensorMapFloatOOBfill);

void make_map(EncodeFn enc, CUtensorMap* m, const void* ptr, int rank, const cuuint64_t* dims, const cuuint64_t* strides, const cuuint32_t* box, bool swz, bool wide = false) {
    const cuuint32_t es[5] = {1, 1, 1, 1, 1};
    enc(m, CU_TENSOR_MAP_DATA_TYPE_BFLOAT16, rank, (void*)ptr, dims, strides, box, es, CU_TENSOR_MAP_INTERLEAVE_NONE,
        swz ? CU_TENSOR_MAP_SWIZZLE_128B : CU_TENSOR_MAP_SWIZZLE_NONE, wide ? CU_TENSOR_MAP_L2_PROMOTION_L2_256B : CU_TENSOR_MAP_L2_PROMOTION_L2_128B, CU_TENSOR_MAP_FLOAT_OOB_FILL_NONE);
}
void make_map2(EncodeFn enc, CUtensorMap* m, const void* ptr, cuuint64_t inner, cuuint64_t outer, cuuint32_t rows) {
    const cuuint64_t dims[2] = {inner, outer}, strides[1] = {inner * 2};
    const cuuint32_t box[2] = {64, rows};
    make_map(enc, m, ptr, 2, dims, strides, box, true, rows > 64);
}

}

extern "C" void kernel_launch(void* const* d_in, const int* in_sizes, int n_in, void* d_out, int out_size) {
    (void)in_sizes; (void)n_in; (void)out_size;
    static EncodeFn enc = nullptr;
    static void *hptr, *p_xnT, *p_st, *p_S, *p_flags;
    if (!enc) {
        cudaDriverEntryPointQueryResult qr;
        cudaGetDriverEntryPoint("cuTensorMapEncodeTiled", (void**)&enc, cudaEnableDefault, &qr);
        cudaFuncSetAttribute(fused_kernel, cudaFuncAttributeMaxDynamicSharedMemorySize, SMEM_BYTES);
        cudaGetSymbolAddress(&hptr, g_H); cudaGetSymbolAddress(&p_xnT, g_xnT); cudaGetSymbolAddress(&p_st, g_st);
        cudaGetSymbolAddress(&p_S, g_S); cudaGetSymbolAddress(&p_flags, g_flags);
    }
    Params P;
    P.x = (const __nv_bfloat16*)d_in[0]; P.logA = (const __nv_bfloat16*)d_in[1]; P.Aim = (const __nv_bfloat16*)d_in[2];
    P.Cr = (const __nv_bfloat16*)d_in[3]; P.Ci = (const __nv_bfloat16*)d_in[4]; P.logdt = (const __nv_bfloat16*)d_in[5];
    P.Dskip = (const __nv_bfloat16*)d_in[6];
    P.Wg = (const __nv_bfloat16*)d_in[8]; P.Wu = (const __nv_bfloat16*)d_in[9]; P.Wd = (const __nv_bfloat16*)d_in[10]; P.out = (__nv_bfloat16*)d_out; P.xnT = (uint4*)p_xnT; P.st = (float2*)p_st; P.S = (uint2*)p_S; P.flags = (unsigned*)p_flags;
    Maps M;
    make_map2(enc, &M.x[0], d_in[0], DM, SEQ, 168); make_map2(enc, &M.x[1], d_in[0], DM, SEQ, 176);
    make_map2(enc, &M.xo, d_in[0], DM, SEQ, 64);
    make_map2(enc, &M.wg, d_in[8], FF, DM, 64);     make_map2(enc, &M.wu, d_in[9], FF, DM, 64);
    make_map2(enc, &M.wd, d_in[10], DM, FF, 64);
    for (int v = 0; v < 2; v++) {
        const cuuint64_t dims[3] = {64, 256, 172}, strides[2] = {128, 32768};
        const cuuint32_t box[3] = {64, (cuuint32_t)(21 + v), 8};
        make_map(enc, &M.hst[v], hptr, 3, dims, strides, box, false);
    }
    {
        const cuuint64_t dims[2] = {2048, 512}, strides[1] = {4096};
        const cuuint32_t box[2] = {16, 128};
        make_map(enc, &M.xt, p_xnT, 2, dims, strides, box, false);
    }
    {
        const cuuint64_t dims[5] = {64, 2, 4, 32, 64}, strides[4] = {4 * 8192, 8192, 8 * 8192, 128};
        const cuuint32_t box[5] = {64, 2, 4, 8, 2};
        make_map(enc, &M.sld, p_S, 5, dims, strides, box, true);
    }
    {
        const cuuint64_t dims[5] = {64, 2, 2, 64, 172}, strides[4] = {256, 128, 512, 32768};
        const cuuint32_t box[5] = {64, 2, 2, 2, 8};
        make_map(enc, &M.hld, hptr, 5, dims, strides, box, false);
    }
    fused_kernel<<<NCTA, 512, SMEM_BYTES>>>(P, M);
}
```

```cpp
#include <cuda_runtime.h>
#include <cuda_bf16.h>
#include <cuda.h>
#include <stdint.h>

#define PROF 0

namespace {

constexpr int SEQ = 2048, DM = 512, FF = 1376;
constexpr int NCTA = 132;
#define GOST 1
#define SIGK 3
#define DLY1 300
constexpr int RUNROLL = 2;
constexpr int TOKG = 344;

constexpr uint32_t OFF_W = 0;
constexpr uint32_t XBUF = 22528;
constexpr uint32_t OFF_X = 65536;
constexpr uint32_t OFF_CONV = 155648;
constexpr uint32_t CH_STRIDE = 17536;
constexpr uint32_t CH_T = 0;
constexpr uint32_t CH_A3 = 8448;
constexpr uint32_t CH_B3 = 12544;
constexpr uint32_t CH_U = 13312;
constexpr uint32_t CH_G = CH_A3 + 2064;
constexpr uint32_t UPLANE = 2112;
constexpr uint32_t CH_LN = 0, CH_PART = 4224, CH_PSZ = 3072, CH_LNT = 13440;
constexpr uint32_t OFF_SST = 60416;
constexpr uint32_t OFF_XO = 191488, OFF_SI = 207872;
constexpr uint32_t OFF_ST = 225792;
constexpr uint32_t OFF_CSUM = 228544;
constexpr uint32_t OFF_BAR = 229056;
constexpr uint32_t SMEM_BYTES = 229568;

enum {
    B_FULLW = 0, B_EMPTYW = 4, B_FULLX = 8, B_EMPTYX = 12, B_FULLD = 16, B_EMPTYD = 24,
    B_U = 32, B_XO = 33, B_S = 34, B_STG = 35, B_HF = 37, B_STATS = 38, B_LNS = 39, B_SST = 40,
    B_LNX = 41, B_CH0 = 42, B_TURN = 43, B_K = 45,
    B_CONV = 46, B_LN = 50, B_CS = 51, B_EPI = 52, B_SIG = 54,
    B_COUNT = 56
};
enum { F_A = 0, F_H = 1, F_S = 13, F_EXIT = 17, F_COUNT = 18 };

__device__ uint4 g_xnT[DM * 256];
__device__ float2 g_st[6 * TOKG];
__device__ uint4 g_H[172 * 256 * 8];
__device__ uint2 g_S[256 * 1024];
__device__ unsigned g_flags[F_COUNT * 32];
#define STAMP(i) do {} while (0)
#define GSTAMP(i) do {} while (0)
#define STAMP2(i) do {} while (0)

__device__ __forceinline__ uint32_t smem_u32(const void* p) { return (uint32_t)__cvta_generic_to_shared(p); }
__device__ __forceinline__ void mbar_expect(uint32_t bar, uint32_t bytes) { asm volatile("mbarrier.arrive.expect_tx.shared::cta.b64 _, [%0], %1;" :: "r"(bar), "r"(bytes) : "memory"); }
__device__ __forceinline__ void mbar_arrive(uint32_t bar) { asm volatile("mbarrier.arrive.shared::cta.b64 _, [%0];" :: "r"(bar) : "memory"); }
__device__ __forceinline__ void mbar_wait(uint32_t bar, uint32_t parity) {
    asm volatile("{.reg .pred p; .reg .u32 n; mov.u32 n, 0x20000;\n"
                 "LW: mbarrier.try_wait.parity.shared::cta.b64 p, [%0], %1;\n"
                 "sub.u32 n, n, 1; setp.eq.or.u32 p, n, 0, p; @!p bra LW;}" :: "r"(bar), "r"(parity) : "memory");
}
__device__ __forceinline__ void mbar_arrive_if(uint32_t bar, uint32_t pred) {
    asm volatile("{.reg .pred p; setp.ne.u32 p, %1, 0; @p mbarrier.arrive.shared::cta.b64 _, [%0];}" :: "r"(bar), "r"(pred) : "memory");
}
__device__ __forceinline__ bool elect_one() { uint32_t p; asm volatile("{.reg .pred P; elect.sync _|P, 0xffffffff; selp.u32 %0, 1, 0, P;}" : "=r"(p)); return p; }
__device__ __forceinline__ void tma2d(uint32_t dst, const CUtensorMap* m, int c0, int c1, uint32_t bar) {
    asm volatile("cp.async.bulk.tensor.2d.shared::cluster.global.mbarrier::complete_tx::bytes [%0], [%1, {%3, %4}], [%2];"
        :: "r"(dst), "l"(m), "r"(bar), "r"(c0), "r"(c1) : "memory");
}
__device__ __forceinline__ void bulk_load(uint32_t dst, const void* src, uint32_t bytes, uint32_t bar) {
    asm volatile("cp.async.bulk.shared::cluster.global.mbarrier::complete_tx::bytes [%0], [%1], %2, [%3];" :: "r"(dst), "l"(src), "r"(bytes), "r"(bar) : "memory");
}
__device__ __forceinline__ void bulk_store(void* dst, uint32_t src, uint32_t bytes) {
    asm volatile("cp.async.bulk.global.shared::cta.bulk_group [%0], [%1], %2;" :: "l"(dst), "r"(src), "r"(bytes) : "memory");
}
__device__ __forceinline__ void fence_async_smem() { asm volatile("fence.proxy.async.shared::cta;" ::: "memory"); }
__device__ __forceinline__ void flag_wait(unsigned* g_flags, int f, unsigned target) {
    asm volatile("{.reg .pred p; .reg .u32 n, v; mov.u32 n, 0x40000;\n"
                 "LF: ld.acquire.gpu.global.u32 v, [%0]; setp.ge.u32 p, v, %1; @p bra LD;\n"
                 "sub.u32 n, n, 1; setp.ne.u32 p, n, 0; @p bra LF; trap;\nLD: }"
                 :: "l"(g_flags + f * 32), "r"(target) : "memory");
}
__device__ __forceinline__ void flag_signal(unsigned* g_flags, int f) {
    asm volatile("cp.async.bulk.commit_group; cp.async.bulk.wait_group 0; red.relaxed.gpu.global.add.u32 [%0], 1;" :: "l"(g_flags + f * 32) : "memory");
}
__device__ __forceinline__ void exit_count(unsigned* g_flags) {
    if (atomicAdd(g_flags + F_EXIT * 32, 1u) == NCTA - 1) {
        #pragma unroll 1
        for (int i = 0; i < F_COUNT; i++) g_flags[i * 32] = 0;
    }
}
__device__ __forceinline__ void bar_sync(int id) { asm volatile("bar.sync %0, 128;" :: "r"(id) : "memory"); }
__device__ __forceinline__ uint64_t mkdesc(uint32_t addr, uint32_t lbo, uint32_t sbo, uint32_t swz) {
    return (uint64_t)((addr >> 4) | ((lbo >> 4) << 16)) | ((uint64_t)((sbo >> 4) | (swz << 30)) << 32);
}
#define WG_FENCE() asm volatile("wgmma.fence.sync.aligned;" ::: "memory")
#define WG_COMMIT() asm volatile("wgmma.commit_group.sync.aligned;" ::: "memory")
#define WG_WAIT(n) asm volatile("wgmma.wait_group.sync.aligned " #n ";" ::: "memory")
template <int N> __device__ __forceinline__ void fence_acc(float (&d)[N]) {
    #pragma unroll
    for (int i = 0; i < N; i++) asm volatile("" : "+f"(d[i]) :: "memory");
}
template <int N> __device__ __forceinline__ void define_acc(float (&d)[N]) {
    #pragma unroll
    for (int i = 0; i < N; i++) asm volatile("" : "=f"(d[i]));
}
__device__ __forceinline__ uint32_t pack2(float lo, float hi) { uint32_t r; asm("cvt.rn.bf16x2.f32 %0, %1, %2;" : "=r"(r) : "f"(hi), "f"(lo)); return r; }
__device__ __forceinline__ float bf_lo(uint32_t v) { return __uint_as_float(v << 16); }
__device__ __forceinline__ float bf_hi(uint32_t v) { return __uint_as_float(v & 0xffff0000u); }
__device__ __forceinline__ float bf_round(float v) { return bf_hi(pack2(0.f, v)); }
__device__ __forceinline__ float tanh_fast(float v) { float r; asm("tanh.approx.f32 %0, %1;" : "=f"(r) : "f"(v)); return r; }
__device__ __forceinline__ float ex2(float v) { float r; asm("ex2.approx.ftz.f32 %0, %1;" : "=f"(r) : "f"(v)); return r; }
__device__ __forceinline__ uint4 lds128(uint32_t a) { uint4 v; asm volatile("ld.shared.v4.b32 {%0,%1,%2,%3}, [%4];" : "=r"(v.x), "=r"(v.y), "=r"(v.z), "=r"(v.w) : "r"(a)); return v; }
__device__ __forceinline__ uint2 lds64(uint32_t a) { uint2 v; asm volatile("ld.shared.v2.b32 {%0,%1}, [%2];" : "=r"(v.x), "=r"(v.y) : "r"(a)); return v; }
__device__ __forceinline__ float ldsf(uint32_t a) { float v; asm volatile("ld.shared.f32 %0, [%1];" : "=f"(v) : "r"(a)); return v; }
__device__ __forceinline__ void sts128(uint32_t a, uint32_t x, uint32_t y, uint32_t z, uint32_t w) { asm volatile("st.shared.v4.b32 [%0], {%1,%2,%3,%4};" :: "r"(a), "r"(x), "r"(y), "r"(z), "r"(w) : "memory"); }
__device__ __forceinline__ void sts64(uint32_t a, uint32_t x, uint32_t y) { asm volatile("st.shared.v2.b32 [%0], {%1,%2};" :: "r"(a), "r"(x), "r"(y) : "memory"); }
__device__ __forceinline__ void stsf(uint32_t a, float x) { asm volatile("st.shared.f32 [%0], %1;" :: "r"(a), "f"(x) : "memory"); }
__device__ __forceinline__ void sts16(uint32_t a, uint32_t x) { asm volatile("st.shared.b16 [%0], %1;" :: "r"(a), "h"((unsigned short)x) : "memory"); }
__device__ __forceinline__ void stsm4(uint32_t a, uint32_t r0, uint32_t r1, uint32_t r2, uint32_t r3) {
    asm volatile("stmatrix.sync.aligned.m8n8.x4.shared.b16 [%0], {%1,%2,%3,%4};" :: "r"(a), "r"(r0), "r"(r1), "r"(r2), "r"(r3) : "memory");
}
__device__ __forceinline__ void ldsm4(uint32_t (&r)[4], uint32_t a) {
    asm volatile("ldmatrix.sync.aligned.m8n8.x4.shared.b16 {%0,%1,%2,%3}, [%4];" : "=r"(r[0]), "=r"(r[1]), "=r"(r[2]), "=r"(r[3]) : "r"(a) : "memory");
}
#define FU(x) __float_as_uint(x)
#define UF(x) __uint_as_float(x)
__device__ __forceinline__ uint32_t wd_slot(int s) { return (uint32_t)((0xbba8403056201000ull >> (8 * s)) & 0xff) << 10; }
__device__ __forceinline__ uint32_t h_slot(int s) { return (uint32_t)((0xcba0908880787068ull >> (8 * s)) & 0xff) << 10; }

template<int N> __device__ __forceinline__ void wg_rs(float (&d)[64], uint32_t a0, uint32_t a1, uint32_t a2, uint32_t a3, uint64_t db);
template<> __device__ __forceinline__ void wg_rs<128>(float (&d)[64], uint32_t a0, uint32_t a1, uint32_t a2, uint32_t a3, uint64_t db) {
  asm volatile("{.reg .pred p; setp.ne.b32 p, 1, 0; wgmma.mma_async.sync.aligned.m64n128k16.f32.bf16.bf16 {%0,%1,%2,%3,%4,%5,%6,%7,%8,%9,%10,%11,%12,%13,%14,%15,%16,%17,%18,%19,%20,%21,%22,%23,%24,%25,%26,%27,%28,%29,%30,%31,%32,%33,%34,%35,%36,%37,%38,%39,%40,%41,%42,%43,%44,%45,%46,%47,%48,%49,%50,%51,%52,%53,%54,%55,%56,%57,%58,%59,%60,%61,%62,%63}, {%64,%65,%66,%67}, %68, p, 1, 1, 0;}"
    : "+f"(d[0]),"+f"(d[1]),"+f"(d[2]),"+f"(d[3]),"+f"(d[4]),"+f"(d[5]),"+f"(d[6]),"+f"(d[7]),"+f"(d[8]),"+f"(d[9]),"+f"(d[10]),"+f"(d[11]),"+f"(d[12]),"+f"(d[13]),"+f"(d[14]),"+f"(d[15]),"+f"(d[16]),"+f"(d[17]),"+f"(d[18]),"+f"(d[19]),"+f"(d[20]),"+f"(d[21]),"+f"(d[22]),"+f"(d[23]),"+f"(d[24]),"+f"(d[25]),"+f"(d[26]),"+f"(d[27]),"+f"(d[28]),"+f"(d[29]),"+f"(d[30]),"+f"(d[31]),"+f"(d[32]),"+f"(d[33]),"+f"(d[34]),"+f"(d[35]),"+f"(d[36]),"+f"(d[37]),"+f"(d[38]),"+f"(d[39]),"+f"(d[40]),"+f"(d[41]),"+f"(d[42]),"+f"(d[43]),"+f"(d[44]),"+f"(d[45]),"+f"(d[46]),"+f"(d[47]),"+f"(d[48]),"+f"(d[49]),"+f"(d[50]),"+f"(d[51]),"+f"(d[52]),"+f"(d[53]),"+f"(d[54]),"+f"(d[55]),"+f"(d[56]),"+f"(d[57]),"+f"(d[58]),"+f"(d[59]),"+f"(d[60]),"+f"(d[61]),"+f"(d[62]),"+f"(d[63]) : "r"(a0), "r"(a1), "r"(a2), "r"(a3), "l"(db));
}
template<> __device__ __forceinline__ void wg_rs<120>(float (&d)[64], uint32_t a0, uint32_t a1, uint32_t a2, uint32_t a3, uint64_t db) {
  asm volatile("{.reg .pred p; setp.ne.b32 p, 1, 0; wgmma.mma_async.sync.aligned.m64n120k16.f32.bf16.bf16 {%0,%1,%2,%3,%4,%5,%6,%7,%8,%9,%10,%11,%12,%13,%14,%15,%16,%17,%18,%19,%20,%21,%22,%23,%24,%25,%26,%27,%28,%29,%30,%31,%32,%33,%34,%35,%36,%37,%38,%39,%40,%41,%42,%43,%44,%45,%46,%47,%48,%49,%50,%51,%52,%53,%54,%55,%56,%57,%58,%59}, {%60,%61,%62,%63}, %64, p, 1, 1, 0;}"
    : "+f"(d[0]),"+f"(d[1]),"+f"(d[2]),"+f"(d[3]),"+f"(d[4]),"+f"(d[5]),"+f"(d[6]),"+f"(d[7]),"+f"(d[8]),"+f"(d[9]),"+f"(d[10]),"+f"(d[11]),"+f"(d[12]),"+f"(d[13]),"+f"(d[14]),"+f"(d[15]),"+f"(d[16]),"+f"(d[17]),"+f"(d[18]),"+f"(d[19]),"+f"(d[20]),"+f"(d[21]),"+f"(d[22]),"+f"(d[23]),"+f"(d[24]),"+f"(d[25]),"+f"(d[26]),"+f"(d[27]),"+f"(d[28]),"+f"(d[29]),"+f"(d[30]),"+f"(d[31]),"+f"(d[32]),"+f"(d[33]),"+f"(d[34]),"+f"(d[35]),"+f"(d[36]),"+f"(d[37]),"+f"(d[38]),"+f"(d[39]),"+f"(d[40]),"+f"(d[41]),"+f"(d[42]),"+f"(d[43]),"+f"(d[44]),"+f"(d[45]),"+f"(d[46]),"+f"(d[47]),"+f"(d[48]),"+f"(d[49]),"+f"(d[50]),"+f"(d[51]),"+f"(d[52]),"+f"(d[53]),"+f"(d[54]),"+f"(d[55]),"+f"(d[56]),"+f"(d[57]),"+f"(d[58]),"+f"(d[59]) : "r"(a0), "r"(a1), "r"(a2), "r"(a3), "l"(db));
}
template<> __device__ __forceinline__ void wg_rs<112>(float (&d)[64], uint32_t a0, uint32_t a1, uint32_t a2, uint32_t a3, uint64_t db) {
  asm volatile("{.reg .pred p; setp.ne.b32 p, 1, 0; wgmma.mma_async.sync.aligned.m64n112k16.f32.bf16.bf16 {%0,%1,%2,%3,%4,%5,%6,%7,%8,%9,%10,%11,%12,%13,%14,%15,%16,%17,%18,%19,%20,%21,%22,%23,%24,%25,%26,%27,%28,%29,%30,%31,%32,%33,%34,%35,%36,%37,%38,%39,%40,%41,%42,%43,%44,%45,%46,%47,%48,%49,%50,%51,%52,%53,%54,%55}, {%56,%57,%58,%59}, %60, p, 1, 1, 0;}"
    : "+f"(d[0]),"+f"(d[1]),"+f"(d[2]),"+f"(d[3]),"+f"(d[4]),"+f"(d[5]),"+f"(d[6]),"+f"(d[7]),"+f"(d[8]),"+f"(d[9]),"+f"(d[10]),"+f"(d[11]),"+f"(d[12]),"+f"(d[13]),"+f"(d[14]),"+f"(d[15]),"+f"(d[16]),"+f"(d[17]),"+f"(d[18]),"+f"(d[19]),"+f"(d[20]),"+f"(d[21]),"+f"(d[22]),"+f"(d[23]),"+f"(d[24]),"+f"(d[25]),"+f"(d[26]),"+f"(d[27]),"+f"(d[28]),"+f"(d[29]),"+f"(d[30]),"+f"(d[31]),"+f"(d[32]),"+f"(d[33]),"+f"(d[34]),"+f"(d[35]),"+f"(d[36]),"+f"(d[37]),"+f"(d[38]),"+f"(d[39]),"+f"(d[40]),"+f"(d[41]),"+f"(d[42]),"+f"(d[43]),"+f"(d[44]),"+f"(d[45]),"+f"(d[46]),"+f"(d[47]),"+f"(d[48]),"+f"(d[49]),"+f"(d[50]),"+f"(d[51]),"+f"(d[52]),"+f"(d[53]),"+f"(d[54]),"+f"(d[55]) : "r"(a0), "r"(a1), "r"(a2), "r"(a3), "l"(db));
}
template<> __device__ __forceinline__ void wg_rs<104>(float (&d)[64], uint32_t a0, uint32_t a1, uint32_t a2, uint32_t a3, uint64_t db) {
  asm volatile("{.reg .pred p; setp.ne.b32 p, 1, 0; wgmma.mma_async.sync.aligned.m64n104k16.f32.bf16.bf16 {%0,%1,%2,%3,%4,%5,%6,%7,%8,%9,%10,%11,%12,%13,%14,%15,%16,%17,%18,%19,%20,%21,%22,%23,%24,%25,%26,%27,%28,%29,%30,%31,%32,%33,%34,%35,%36,%37,%38,%39,%40,%41,%42,%43,%44,%45,%46,%47,%48,%49,%50,%51}, {%52,%53,%54,%55}, %56, p, 1, 1, 0;}"
    : "+f"(d[0]),"+f"(d[1]),"+f"(d[2]),"+f"(d[3]),"+f"(d[4]),"+f"(d[5]),"+f"(d[6]),"+f"(d[7]),"+f"(d[8]),"+f"(d[9]),"+f"(d[10]),"+f"(d[11]),"+f"(d[12]),"+f"(d[13]),"+f"(d[14]),"+f"(d[15]),"+f"(d[16]),"+f"(d[17]),"+f"(d[18]),"+f"(d[19]),"+f"(d[20]),"+f"(d[21]),"+f"(d[22]),"+f"(d[23]),"+f"(d[24]),"+f"(d[25]),"+f"(d[26]),"+f"(d[27]),"+f"(d[28]),"+f"(d[29]),"+f"(d[30]),"+f"(d[31]),"+f"(d[32]),"+f"(d[33]),"+f"(d[34]),"+f"(d[35]),"+f"(d[36]),"+f"(d[37]),"+f"(d[38]),"+f"(d[39]),"+f"(d[40]),"+f"(d[41]),"+f"(d[42]),"+f"(d[43]),"+f"(d[44]),"+f"(d[45]),"+f"(d[46]),"+f"(d[47]),"+f"(d[48]),"+f"(d[49]),"+f"(d[50]),"+f"(d[51]) : "r"(a0), "r"(a1), "r"(a2), "r"(a3), "l"(db));
}
template<> __device__ __forceinline__ void wg_rs<96>(float (&d)[64], uint32_t a0, uint32_t a1, uint32_t a2, uint32_t a3, uint64_t db) {
  asm volatile("{.reg .pred p; setp.ne.b32 p, 1, 0; wgmma.mma_async.sync.aligned.m64n96k16.f32.bf16.bf16 {%0,%1,%2,%3,%4,%5,%6,%7,%8,%9,%10,%11,%12,%13,%14,%15,%16,%17,%18,%19,%20,%21,%22,%23,%24,%25,%26,%27,%28,%29,%30,%31,%32,%33,%34,%35,%36,%37,%38,%39,%40,%41,%42,%43,%44,%45,%46,%47}, {%48,%49,%50,%51}, %52, p, 1, 1, 0;}"
    : "+f"(d[0]),"+f"(d[1]),"+f"(d[2]),"+f"(d[3]),"+f"(d[4]),"+f"(d[5]),"+f"(d[6]),"+f"(d[7]),"+f"(d[8]),"+f"(d[9]),"+f"(d[10]),"+f"(d[11]),"+f"(d[12]),"+f"(d[13]),"+f"(d[14]),"+f"(d[15]),"+f"(d[16]),"+f"(d[17]),"+f"(d[18]),"+f"(d[19]),"+f"(d[20]),"+f"(d[21]),"+f"(d[22]),"+f"(d[23]),"+f"(d[24]),"+f"(d[25]),"+f"(d[26]),"+f"(d[27]),"+f"(d[28]),"+f"(d[29]),"+f"(d[30]),"+f"(d[31]),"+f"(d[32]),"+f"(d[33]),"+f"(d[34]),"+f"(d[35]),"+f"(d[36]),"+f"(d[37]),"+f"(d[38]),"+f"(d[39]),"+f"(d[40]),"+f"(d[41]),"+f"(d[42]),"+f"(d[43]),"+f"(d[44]),"+f"(d[45]),"+f"(d[46]),"+f"(d[47]) : "r"(a0), "r"(a1), "r"(a2), "r"(a3), "l"(db));
}
template<> __device__ __forceinline__ void wg_rs<88>(float (&d)[64], uint32_t a0, uint32_t a1, uint32_t a2, uint32_t a3, uint64_t db) {
  asm volatile("{.reg .pred p; setp.ne.b32 p, 1, 0; wgmma.mma_async.sync.aligned.m64n88k16.f32.bf16.bf16 {%0,%1,%2,%3,%4,%5,%6,%7,%8,%9,%10,%11,%12,%13,%14,%15,%16,%17,%18,%19,%20,%21,%22,%23,%24,%25,%26,%27,%28,%29,%30,%31,%32,%33,%34,%35,%36,%37,%38,%39,%40,%41,%42,%43}, {%44,%45,%46,%47}, %48, p, 1, 1, 0;}"
    : "+f"(d[0]),"+f"(d[1]),"+f"(d[2]),"+f"(d[3]),"+f"(d[4]),"+f"(d[5]),"+f"(d[6]),"+f"(d[7]),"+f"(d[8]),"+f"(d[9]),"+f"(d[10]),"+f"(d[11]),"+f"(d[12]),"+f"(d[13]),"+f"(d[14]),"+f"(d[15]),"+f"(d[16]),"+f"(d[17]),"+f"(d[18]),"+f"(d[19]),"+f"(d[20]),"+f"(d[21]),"+f"(d[22]),"+f"(d[23]),"+f"(d[24]),"+f"(d[25]),"+f"(d[26]),"+f"(d[27]),"+f"(d[28]),"+f"(d[29]),"+f"(d[30]),"+f"(d[31]),"+f"(d[32]),"+f"(d[33]),"+f"(d[34]),"+f"(d[35]),"+f"(d[36]),"+f"(d[37]),"+f"(d[38]),"+f"(d[39]),"+f"(d[40]),"+f"(d[41]),"+f"(d[42]),"+f"(d[43]) : "r"(a0), "r"(a1), "r"(a2), "r"(a3), "l"(db));
}
template<> __device__ __forceinline__ void wg_rs<80>(float (&d)[64], uint32_t a0, uint32_t a1, uint32_t a2, uint32_t a3, uint64_t db) {
  asm volatile("{.reg .pred p; setp.ne.b32 p, 1, 0; wgmma.mma_async.sync.aligned.m64n80k16.f32.bf16.bf16 {%0,%1,%2,%3,%4,%5,%6,%7,%8,%9,%10,%11,%12,%13,%14,%15,%16,%17,%18,%19,%20,%21,%22,%23,%24,%25,%26,%27,%28,%29,%30,%31,%32,%33,%34,%35,%36,%37,%38,%39}, {%40,%41,%42,%43}, %44, p, 1, 1, 0;}"
    : "+f"(d[0]),"+f"(d[1]),"+f"(d[2]),"+f"(d[3]),"+f"(d[4]),"+f"(d[5]),"+f"(d[6]),"+f"(d[7]),"+f"(d[8]),"+f"(d[9]),"+f"(d[10]),"+f"(d[11]),"+f"(d[12]),"+f"(d[13]),"+f"(d[14]),"+f"(d[15]),"+f"(d[16]),"+f"(d[17]),"+f"(d[18]),"+f"(d[19]),"+f"(d[20]),"+f"(d[21]),"+f"(d[22]),"+f"(d[23]),"+f"(d[24]),"+f"(d[25]),"+f"(d[26]),"+f"(d[27]),"+f"(d[28]),"+f"(d[29]),"+f"(d[30]),"+f"(d[31]),"+f"(d[32]),"+f"(d[33]),"+f"(d[34]),"+f"(d[35]),"+f"(d[36]),"+f"(d[37]),"+f"(d[38]),"+f"(d[39]) : "r"(a0), "r"(a1), "r"(a2), "r"(a3), "l"(db));
}
template<> __device__ __forceinline__ void wg_rs<72>(float (&d)[64], uint32_t a0, uint32_t a1, uint32_t a2, uint32_t a3, uint64_t db) {
  asm volatile("{.reg .pred p; setp.ne.b32 p, 1, 0; wgmma.mma_async.sync.aligned.m64n72k16.f32.bf16.bf16 {%0,%1,%2,%3,%4,%5,%6,%7,%8,%9,%10,%11,%12,%13,%14,%15,%16,%17,%18,%19,%20,%21,%22,%23,%24,%25,%26,%27,%28,%29,%30,%31,%32,%33,%34,%35}, {%36,%37,%38,%39}, %40, p, 1, 1, 0;}"
    : "+f"(d[0]),"+f"(d[1]),"+f"(d[2]),"+f"(d[3]),"+f"(d[4]),"+f"(d[5]),"+f"(d[6]),"+f"(d[7]),"+f"(d[8]),"+f"(d[9]),"+f"(d[10]),"+f"(d[11]),"+f"(d[12]),"+f"(d[13]),"+f"(d[14]),"+f"(d[15]),"+f"(d[16]),"+f"(d[17]),"+f"(d[18]),"+f"(d[19]),"+f"(d[20]),"+f"(d[21]),"+f"(d[22]),"+f"(d[23]),"+f"(d[24]),"+f"(d[25]),"+f"(d[26]),"+f"(d[27]),"+f"(d[28]),"+f"(d[29]),"+f"(d[30]),"+f"(d[31]),"+f"(d[32]),"+f"(d[33]),"+f"(d[34]),"+f"(d[35]) : "r"(a0), "r"(a1), "r"(a2), "r"(a3), "l"(db));
}
template<> __device__ __forceinline__ void wg_rs<64>(float (&d)[64], uint32_t a0, uint32_t a1, uint32_t a2, uint32_t a3, uint64_t db) {
  asm volatile("{.reg .pred p; setp.ne.b32 p, 1, 0; wgmma.mma_async.sync.aligned.m64n64k16.f32.bf16.bf16 {%0,%1,%2,%3,%4,%5,%6,%7,%8,%9,%10,%11,%12,%13,%14,%15,%16,%17,%18,%19,%20,%21,%22,%23,%24,%25,%26,%27,%28,%29,%30,%31}, {%32,%33,%34,%35}, %36, p, 1, 1, 0;}"
    : "+f"(d[0]),"+f"(d[1]),"+f"(d[2]),"+f"(d[3]),"+f"(d[4]),"+f"(d[5]),"+f"(d[6]),"+f"(d[7]),"+f"(d[8]),"+f"(d[9]),"+f"(d[10]),"+f"(d[11]),"+f"(d[12]),"+f"(d[13]),"+f"(d[14]),"+f"(d[15]),"+f"(d[16]),"+f"(d[17]),"+f"(d[18]),"+f"(d[19]),"+f"(d[20]),"+f"(d[21]),"+f"(d[22]),"+f"(d[23]),"+f"(d[24]),"+f"(d[25]),"+f"(d[26]),"+f"(d[27]),"+f"(d[28]),"+f"(d[29]),"+f"(d[30]),"+f"(d[31]) : "r"(a0), "r"(a1), "r"(a2), "r"(a3), "l"(db));
}
__device__ __forceinline__ void wg_rs_first(float (&d)[64], uint32_t a0, uint32_t a1, uint32_t a2, uint32_t a3, uint64_t db) {
  asm volatile("{.reg .pred p; setp.ne.b32 p, 0, 0; wgmma.mma_async.sync.aligned.m64n128k16.f32.bf16.bf16 {%0,%1,%2,%3,%4,%5,%6,%7,%8,%9,%10,%11,%12,%13,%14,%15,%16,%17,%18,%19,%20,%21,%22,%23,%24,%25,%26,%27,%28,%29,%30,%31,%32,%33,%34,%35,%36,%37,%38,%39,%40,%41,%42,%43,%44,%45,%46,%47,%48,%49,%50,%51,%52,%53,%54,%55,%56,%57,%58,%59,%60,%61,%62,%63}, {%64,%65,%66,%67}, %68, p, 1, 1, 0;}"
    : "=f"(d[0]),"=f"(d[1]),"=f"(d[2]),"=f"(d[3]),"=f"(d[4]),"=f"(d[5]),"=f"(d[6]),"=f"(d[7]),"=f"(d[8]),"=f"(d[9]),"=f"(d[10]),"=f"(d[11]),"=f"(d[12]),"=f"(d[13]),"=f"(d[14]),"=f"(d[15]),"=f"(d[16]),"=f"(d[17]),"=f"(d[18]),"=f"(d[19]),"=f"(d[20]),"=f"(d[21]),"=f"(d[22]),"=f"(d[23]),"=f"(d[24]),"=f"(d[25]),"=f"(d[26]),"=f"(d[27]),"=f"(d[28]),"=f"(d[29]),"=f"(d[30]),"=f"(d[31]),"=f"(d[32]),"=f"(d[33]),"=f"(d[34]),"=f"(d[35]),"=f"(d[36]),"=f"(d[37]),"=f"(d[38]),"=f"(d[39]),"=f"(d[40]),"=f"(d[41]),"=f"(d[42]),"=f"(d[43]),"=f"(d[44]),"=f"(d[45]),"=f"(d[46]),"=f"(d[47]),"=f"(d[48]),"=f"(d[49]),"=f"(d[50]),"=f"(d[51]),"=f"(d[52]),"=f"(d[53]),"=f"(d[54]),"=f"(d[55]),"=f"(d[56]),"=f"(d[57]),"=f"(d[58]),"=f"(d[59]),"=f"(d[60]),"=f"(d[61]),"=f"(d[62]),"=f"(d[63]) : "r"(a0), "r"(a1), "r"(a2), "r"(a3), "l"(db));
}
__device__ __forceinline__ void wg_tt128(float (&d)[64], uint64_t da, uint64_t db, int sc) {
  asm volatile("{.reg .pred p; setp.ne.b32 p, %66, 0; wgmma.mma_async.sync.aligned.m64n128k16.f32.bf16.bf16 {%0,%1,%2,%3,%4,%5,%6,%7,%8,%9,%10,%11,%12,%13,%14,%15,%16,%17,%18,%19,%20,%21,%22,%23,%24,%25,%26,%27,%28,%29,%30,%31,%32,%33,%34,%35,%36,%37,%38,%39,%40,%41,%42,%43,%44,%45,%46,%47,%48,%49,%50,%51,%52,%53,%54,%55,%56,%57,%58,%59,%60,%61,%62,%63}, %64, %65, p, 1, 1, 1, 1;}"
    : "+f"(d[0]),"+f"(d[1]),"+f"(d[2]),"+f"(d[3]),"+f"(d[4]),"+f"(d[5]),"+f"(d[6]),"+f"(d[7]),"+f"(d[8]),"+f"(d[9]),"+f"(d[10]),"+f"(d[11]),"+f"(d[12]),"+f"(d[13]),"+f"(d[14]),"+f"(d[15]),"+f"(d[16]),"+f"(d[17]),"+f"(d[18]),"+f"(d[19]),"+f"(d[20]),"+f"(d[21]),"+f"(d[22]),"+f"(d[23]),"+f"(d[24]),"+f"(d[25]),"+f"(d[26]),"+f"(d[27]),"+f"(d[28]),"+f"(d[29]),"+f"(d[30]),"+f"(d[31]),"+f"(d[32]),"+f"(d[33]),"+f"(d[34]),"+f"(d[35]),"+f"(d[36]),"+f"(d[37]),"+f"(d[38]),"+f"(d[39]),"+f"(d[40]),"+f"(d[41]),"+f"(d[42]),"+f"(d[43]),"+f"(d[44]),"+f"(d[45]),"+f"(d[46]),"+f"(d[47]),"+f"(d[48]),"+f"(d[49]),"+f"(d[50]),"+f"(d[51]),"+f"(d[52]),"+f"(d[53]),"+f"(d[54]),"+f"(d[55]),"+f"(d[56]),"+f"(d[57]),"+f"(d[58]),"+f"(d[59]),"+f"(d[60]),"+f"(d[61]),"+f"(d[62]),"+f"(d[63]) : "l"(da), "l"(db), "r"(sc));
}
__device__ __forceinline__ void wg_tt64(float (&d)[64], uint64_t da, uint64_t db, int sc) {
  asm volatile("{.reg .pred p; setp.ne.b32 p, %34, 0; wgmma.mma_async.sync.aligned.m64n64k16.f32.bf16.bf16 {%0,%1,%2,%3,%4,%5,%6,%7,%8,%9,%10,%11,%12,%13,%14,%15,%16,%17,%18,%19,%20,%21,%22,%23,%24,%25,%26,%27,%28,%29,%30,%31}, %32, %33, p, 1, 1, 1, 1;}"
    : "+f"(d[0]),"+f"(d[1]),"+f"(d[2]),"+f"(d[3]),"+f"(d[4]),"+f"(d[5]),"+f"(d[6]),"+f"(d[7]),"+f"(d[8]),"+f"(d[9]),"+f"(d[10]),"+f"(d[11]),"+f"(d[12]),"+f"(d[13]),"+f"(d[14]),"+f"(d[15]),"+f"(d[16]),"+f"(d[17]),"+f"(d[18]),"+f"(d[19]),"+f"(d[20]),"+f"(d[21]),"+f"(d[22]),"+f"(d[23]),"+f"(d[24]),"+f"(d[25]),"+f"(d[26]),"+f"(d[27]),"+f"(d[28]),"+f"(d[29]),"+f"(d[30]),"+f"(d[31]) : "l"(da), "l"(db), "r"(sc));
}
__device__ __forceinline__ void wg_tt32(float (&d)[64], uint64_t da, uint64_t db, int sc) {
  asm volatile("{.reg .pred p; setp.ne.b32 p, %18, 0; wgmma.mma_async.sync.aligned.m64n32k16.f32.bf16.bf16 {%0,%1,%2,%3,%4,%5,%6,%7,%8,%9,%10,%11,%12,%13,%14,%15}, %16, %17, p, 1, 1, 1, 1;}"
    : "+f"(d[0]),"+f"(d[1]),"+f"(d[2]),"+f"(d[3]),"+f"(d[4]),"+f"(d[5]),"+f"(d[6]),"+f"(d[7]),"+f"(d[8]),"+f"(d[9]),"+f"(d[10]),"+f"(d[11]),"+f"(d[12]),"+f"(d[13]),"+f"(d[14]),"+f"(d[15]) : "l"(da), "l"(db), "r"(sc));
}
__device__ __forceinline__ void wg_g1(float (&d)[88], uint64_t da, uint64_t db, int sc) {
  asm volatile("{.reg .pred p; setp.ne.b32 p, %90, 0; wgmma.mma_async.sync.aligned.m64n176k16.f32.bf16.bf16 {%0,%1,%2,%3,%4,%5,%6,%7,%8,%9,%10,%11,%12,%13,%14,%15,%16,%17,%18,%19,%20,%21,%22,%23,%24,%25,%26,%27,%28,%29,%30,%31,%32,%33,%34,%35,%36,%37,%38,%39,%40,%41,%42,%43,%44,%45,%46,%47,%48,%49,%50,%51,%52,%53,%54,%55,%56,%57,%58,%59,%60,%61,%62,%63,%64,%65,%66,%67,%68,%69,%70,%71,%72,%73,%74,%75,%76,%77,%78,%79,%80,%81,%82,%83,%84,%85,%86,%87}, %88, %89, p, 1, 1, 1, 0;}"
    : "+f"(d[0]),"+f"(d[1]),"+f"(d[2]),"+f"(d[3]),"+f"(d[4]),"+f"(d[5]),"+f"(d[6]),"+f"(d[7]),"+f"(d[8]),"+f"(d[9]),"+f"(d[10]),"+f"(d[11]),"+f"(d[12]),"+f"(d[13]),"+f"(d[14]),"+f"(d[15]),"+f"(d[16]),"+f"(d[17]),"+f"(d[18]),"+f"(d[19]),"+f"(d[20]),"+f"(d[21]),"+f"(d[22]),"+f"(d[23]),"+f"(d[24]),"+f"(d[25]),"+f"(d[26]),"+f"(d[27]),"+f"(d[28]),"+f"(d[29]),"+f"(d[30]),"+f"(d[31]),"+f"(d[32]),"+f"(d[33]),"+f"(d[34]),"+f"(d[35]),"+f"(d[36]),"+f"(d[37]),"+f"(d[38]),"+f"(d[39]),"+f"(d[40]),"+f"(d[41]),"+f"(d[42]),"+f"(d[43]),"+f"(d[44]),"+f"(d[45]),"+f"(d[46]),"+f"(d[47]),"+f"(d[48]),"+f"(d[49]),"+f"(d[50]),"+f"(d[51]),"+f"(d[52]),"+f"(d[53]),"+f"(d[54]),"+f"(d[55]),"+f"(d[56]),"+f"(d[57]),"+f"(d[58]),"+f"(d[59]),"+f"(d[60]),"+f"(d[61]),"+f"(d[62]),"+f"(d[63]),"+f"(d[64]),"+f"(d[65]),"+f"(d[66]),"+f"(d[67]),"+f"(d[68]),"+f"(d[69]),"+f"(d[70]),"+f"(d[71]),"+f"(d[72]),"+f"(d[73]),"+f"(d[74]),"+f"(d[75]),"+f"(d[76]),"+f"(d[77]),"+f"(d[78]),"+f"(d[79]),"+f"(d[80]),"+f"(d[81]),"+f"(d[82]),"+f"(d[83]),"+f"(d[84]),"+f"(d[85]),"+f"(d[86]),"+f"(d[87]) : "l"(da), "l"(db), "r"(sc));
}

struct Params { const __nv_bfloat16 *x, *logA, *Aim, *Cr, *Ci, *logdt, *Dskip, *Wg, *Wu, *Wd; __nv_bfloat16* out; uint4* xnT; float2* st; uint2* S; unsigned* flags; };
struct Maps { CUtensorMap x[2], xo, wg, wu, wd, hst[2], hld, xt, sld; };

__device__ __forceinline__ void conv_channel(uint32_t cb, int w, int lane, uint32_t (&res)[8], uint32_t sig, int sidx) {
    const int q = lane & 3, g = lane >> 2, gam = g >> 2;
    float acc[64];
    uint2 a[17][2];
    const uint32_t t0 = cb + CH_T + (uint32_t)(14 + 4 * w + (g & 3) - 2 * q) * 280u + gam * 8;
#define LDA(s0, s1) _Pragma("unroll") for (int s = s0; s < s1; s++) { a[s][0] = lds64(t0 + s * 16); a[s][1] = lds64(t0 - 8 * 280 + s * 16); }
#define CT(N, s) wg_rs<N>(acc, a[s][0].x, a[s][0].y, a[s][1].x, a[s][1].y, dU + 4 * (s))
    const uint64_t dU = mkdesc(cb + CH_U, UPLANE, 128, 0);
    LDA(0, 17)
    if (sig) { fence_async_smem(); mbar_arrive(sig); }
    WG_FENCE();
    if (w == 0) STAMP2(52 + 3 * sidx);
    wg_rs_first(acc, a[0][0].x, a[0][0].y, a[0][1].x, a[0][1].y, dU);
    CT(128, 1); CT(120, 2); CT(120, 3); CT(112, 4); CT(112, 5); CT(104, 6); CT(104, 7); CT(96, 8);
    CT(96, 9); CT(88, 10); CT(88, 11); CT(80, 12); CT(80, 13); CT(72, 14); CT(72, 15); CT(64, 16);
#undef CT
#undef LDA
    wg_tt64(acc, mkdesc(cb + CH_A3, 128, 512, 0), mkdesc(cb + CH_B3, 384, 32, 0), 1);
    wg_tt32(acc, mkdesc(cb + CH_A3 + 256, 128, 512, 0), mkdesc(cb + CH_B3 + 128, 384, 32, 0), 1);
    WG_COMMIT();
    if (w == 0) STAMP2(53 + 3 * sidx);
    WG_WAIT(0);
    fence_acc(acc);
    if (w == 0) STAMP2(54 + 3 * sidx);
    const int src1 = (lane & ~3) | ((q + 1) & 3);
    float E[16][2];
    #pragma unroll
    for (int j = 0; j < 16; j++) {
        const float nxt = (j < 15) ? acc[4 * (j + 1) + 2] : 0.f;
        const float sup = (q == 0) ? nxt : acc[4 * j + 2];
        const float v = __shfl_sync(0xffffffffu, sup, src1);
        E[j][0] = acc[4 * j] + acc[4 * j + 3];
        E[j][1] = acc[4 * j + 1] + v;
    }
    const int src2 = gam ? ((lane & 12) | ((q + 3) & 3)) : (16 | (lane & 12) | ((q + 1) & 3));
    const bool c1 = gam && q != 0, c2 = gam && q == 0;
    #pragma unroll
    for (int a2 = 0; a2 < 8; a2++) {
        float y[2];
        #pragma unroll
        for (int e = 0; e < 2; e++) {
            const float sup = c1 ? E[2 * a2][e] : E[2 * a2 + 1][e];
            const float nxt = (a2 < 7) ? E[2 * a2 + 2][e] : 0.f;
            const float keep = c2 ? nxt : (c1 ? E[2 * a2 + 1][e] : E[2 * a2][e]);
            y[e] = keep + __shfl_sync(0xffffffffu, sup, src2);
        }
        res[a2] = pack2(y[1], y[0]);
    }
}

__device__ __forceinline__ void consumer(uint32_t sb, int warp, const Params& P, const Maps& M) {
    const int V = warp >> 2, w = warp & 3, lane = threadIdx.x & 31, q = lane & 3, g = lane >> 2;
    const int c = blockIdx.x;
    const uint32_t bars = sb + OFF_BAR, xb = sb + OFF_X + V * 2 * XBUF;
    {
        float ag[88], au[88];
        define_acc(ag); define_acc(au);
        mbar_wait(bars + 8 * B_FULLW, 0);
        mbar_wait(bars + 8 * (B_FULLX + 2 * V), 0);
        #pragma unroll 1
        for (int st = 0; st < 8; st++) {
            uint64_t dG = mkdesc(sb + OFF_W + (st & 3) * 16384, 0, 1024, 1), dX = mkdesc(xb + (st & 1) * XBUF, 16, 1024, 1);
            uint32_t sig = lane == 0 && (V ? st < 6 : st > 0);
            asm volatile("" : "+l"(dG), "+l"(dX), "+r"(sig) :: "memory");
            if (V ? st < 7 : st > 1) mbar_wait(bars + 8 * (B_TURN + V), st & 1);
            STAMP(40 + 8 * V + st);
            WG_FENCE();
            #pragma unroll
            for (int k = 0; k < 4; k++) {
                if (k == SIGK) mbar_arrive_if(bars + 8 * (B_TURN + 1 - V), sig);
                wg_g1(ag, dG + k * 128, dX + k * 2, k ? 1 : st);
                wg_g1(au, dG + 512 + k * 128, dX + k * 2, k ? 1 : st);
            }
            WG_COMMIT();
            if (st == 6 * V) {
                mbar_wait(bars + 8 * (B_FULLW + ((st + 1) & 3)), V);
                mbar_wait(bars + 8 * (B_FULLX + 2 * V + 1), V);
            } else {
                WG_WAIT(1);
                mbar_arrive_if(bars + 8 * (B_EMPTYW + 2 * V), lane == 0 && st == 6 * V + 1);
                mbar_arrive_if(bars + 8 * (B_EMPTYX + 2 * V), lane == 0 && st == 6 * V + 1);
                WG_WAIT(0);
                mbar_arrive_if(bars + 8 * (B_EMPTYW + (st & 3)), lane == 0);
                mbar_arrive_if(bars + 8 * (B_EMPTYX + 2 * V + (st & 1)), lane == 0);
                if (st < 7) {
                    mbar_wait(bars + 8 * (B_FULLW + ((st + 1) & 3)), (st + 1) >> 2);
                    mbar_wait(bars + 8 * (B_FULLX + 2 * V + ((st + 1) & 1)), ((st + 1) >> 1) & 1);
                }
            }
        }
        WG_WAIT(0);
        fence_acc(ag); fence_acc(au);
        STAMP(8 * V + 1);
        float cg0 = ag[84], cg1 = ag[86], cu0 = au[84], cu1 = au[86];
        const uint32_t ca = sb + OFF_CSUM + (8 * w + g) * 16;
        if (V == 0) { sts128(ca, FU(cg0), FU(cg1), FU(cu0), FU(cu1)); mbar_arrive(bars + 8 * B_CS); }
        else { mbar_wait(bars + 8 * B_CS, 0); const uint4 t = lds128(ca); cg0 = UF(t.x); cg1 = UF(t.y); cu0 = UF(t.z); cu1 = UF(t.w); }
        mbar_wait(bars + 8 * B_STATS, 0);
        mbar_wait(bars + 8 * (B_EMPTYX + 2 * V), 1);
        STAMP(13 + V);
        const uint32_t hs = xb + (2 * w + ((lane >> 3) & 1)) * (2688 + 128 * V) + (lane >> 4) * 128 + (lane & 7) * 16;
        const uint32_t sa = sb + OFF_ST + (168 * V + 2 * q) * 8;
        uint4 sq[22];
        #pragma unroll
        for (int j = 0; j < 3; j++) sq[j] = lds128(sa + j * 64);
        #pragma unroll
        for (int j = 0; j < 22; j += 2) {
            uint32_t o[4];
            #pragma unroll
            for (int jj = 0; jj < 2; jj++) {
                const uint4 sv = sq[j + jj];
                float hv[4];
                #pragma unroll
                for (int i = 0; i < 4; i++) {
                    const float m = UF((i & 1) ? sv.z : sv.x);
                    const float gh = fmaf(-m, (i & 2) ? cg1 : cg0, ag[4 * (j + jj) + i]) * UF((i & 1) ? sv.w : sv.y);
                    const float p = gh * fmaf(-m, (i & 2) ? cu1 : cu0, au[4 * (j + jj) + i]);
                    hv[i] = fmaf(p, tanh_fast(gh), p);
                }
                o[2 * jj] = pack2(hv[0], hv[1]); o[2 * jj + 1] = pack2(hv[2], hv[3]);
            }
            #pragma unroll
            for (int k = (j ? 3 + 3 * j / 2 : 3); k < 6 + 3 * j / 2 && k < 22; k++) sq[k] = lds128(sa + k * 64);
            uint32_t ad = hs + j * 128;
            if (j == 20 && V == 0 && lane >= 16) ad = xb + 21504 + (lane & 7) * 16;
            stsm4(ad, o[0], o[1], o[2], o[3]);
        }
        if (c >= 128 || V) { fence_async_smem(); mbar_arrive(bars + 8 * (B_EPI + V)); }
        STAMP(8 * V + 2);
    }
    if (c >= 128) return;
    {
        mbar_wait(bars + 8 * B_CONV, 0);
        uint32_t r0[8], r1[8];
        #pragma unroll
        for (int i = 0; i < 8; i++) asm volatile("" : "=r"(r1[i]));
        #pragma unroll 1
        for (int e = 0; e < 2; e++) {
            #pragma unroll
            for (int i = 0; i < 8; i++) r0[i] = r1[i];
            conv_channel(sb + OFF_CONV + (2 * V + e) * CH_STRIDE, w, lane, r1, (e | V) ? 0 : bars + 8 * B_EPI, 2 * V + e);
            if (e == 0) STAMP(8 * V + 3);
        }
        const int gam = g >> 2, qq = gam ? ((q + 3) & 3) : q;
        const uint32_t sp = sb + OFF_CONV + V * OFF_SST + ((63 - 4 * gam - qq) * 16 + 4 * (w ^ (3 - qq)) + (g & 3)) * 8;
        bar_sync(3 + V);
        #pragma unroll
        for (int a2 = 0; a2 < 8; a2++) sts64(sp - a2 * 1024, r0[a2], r1[a2]);
        fence_async_smem();
        mbar_arrive(bars + 8 * (B_SIG + V));
        STAMP(8 * V + 4);
    }
    if (V == 1) return;
    {
        const int tau = c >> 2, dg = c & 3;
        const uint32_t row = 8 * (w & 1) + 32 * (w >> 1);
        float acc[64];
        define_acc(acc);
        const float rr0 = __ldcg(&P.st[64 * tau + row + g].y), rr1 = __ldcg(&P.st[64 * tau + row + g + 16].y);
        mbar_wait(bars + 8 * B_FULLD, 0);
        STAMP(5);
        uint64_t dB = mkdesc(sb + wd_slot(0), 8192, 1024, 1), dA = mkdesc(sb + h_slot(0), 1024, 128, 0);
        int sd = 0; uint32_t np = 0;
        #pragma unroll 1
        for (int st = 0; st < 21; st++) {
            WG_FENCE();
            wg_tt128(acc, dA, dB, st);
            wg_tt128(acc, dA + 128, dB + 128, 1);
            wg_tt128(acc, dA + 256, dB + 256, 1);
            wg_tt128(acc, dA + 384, dB + 384, 1);
            WG_COMMIT();
            uint32_t ro = bars + 8 * (B_EMPTYD + (sd ? sd - 1 : 6)), m = lane == 0 && st > 0, ok;
            if (++sd == 7) { sd = 0; np ^= 1; }
            const uint32_t nb = bars + 8 * (B_FULLD + sd);
            dB = mkdesc(sb + wd_slot(sd), 8192, 1024, 1); dA = mkdesc(sb + h_slot(sd), 1024, 128, 0);
            asm volatile("{.reg .pred p; mbarrier.test_wait.parity.shared::cta.b64 p, [%5], %6; vote.sync.all.pred p, p, -1; selp.u32 %0, 1, 0, p;}"
                : "=r"(ok), "+l"(dA), "+l"(dB), "+r"(ro), "+r"(m) : "r"(nb), "r"(np) : "memory");
            WG_WAIT(1);
            mbar_arrive_if(ro, m);
            if (!ok) mbar_wait(nb, np);
            if (w == 0) STAMP2(20 + st);
        }
        WG_FENCE();
        wg_tt128(acc, dA, dB, 1);
        wg_tt128(acc, dA + 128, dB + 128, 1);
        WG_COMMIT();
        mbar_wait(bars + 8 * B_XO, 0);
        const uint32_t xo = sb + OFF_XO + (row + (lane & 7) + 16 * ((lane >> 3) & 1)) * 128;
        const uint32_t so = sb + OFF_SI + (w >> 1) * 8192 + q * 256 + (g & 1) * 8;
        const uint32_t sx = (4 * (w & 1) + (g >> 1)) ^ (2 * q) ^ (2 * ((2 * tau + (w >> 1)) & 3));
        uint32_t xr[8][4];
        uint2 sv[16];
        #pragma unroll
        for (int j = 0; j < 16; j += 2) {
            ldsm4(xr[j >> 1], xo + (j >> 3) * 8192 + ((((j & 7) + (lane >> 4)) ^ (lane & 7)) << 4));
            sv[j] = lds64(so + j * 512 + (sx << 4));
            sv[j + 1] = lds64(so + j * 512 + 128 + ((sx ^ 1) << 4));
        }
        WG_WAIT(0);
        fence_acc(acc);
        STAMP(6);
        #pragma unroll
        for (int j = 0; j < 16; j += 2) {
            #pragma unroll
            for (int i = 0; i < 4; i++) {
                const int jj = j + (i >> 1), hh = i & 1;
                const float f0 = acc[4 * jj + 2 * hh] * (hh ? rr1 : rr0), f1 = acc[4 * jj + 2 * hh + 1] * (hh ? rr1 : rr0);
                const uint32_t G = pack2(fmaf(f0, tanh_fast(f0), f0), fmaf(f1, tanh_fast(f1), f1));
                const uint32_t s2 = __byte_perm(sv[jj].x, sv[jj].y, hh ? 0x7632 : 0x5410);
                asm("fma.rn.bf16x2 %0, %1, %2, %0;" : "+r"(xr[j >> 1][i]) : "r"(s2), "r"(G));
            }
            stsm4(xo + (j >> 3) * 8192 + ((((j & 7) + (lane >> 4)) ^ (lane & 7)) << 4), xr[j >> 1][0], xr[j >> 1][1], xr[j >> 1][2], xr[j >> 1][3]);
        }
        __syncwarp();
        {
            const uint32_t rr = row + ((lane >> 4) << 4), la = sb + OFF_XO + rr * 128 + ((lane >> 3) & 1) * 8192;
            uint4* dst = (uint4*)(P.out + (64 * tau + rr) * DM + 128 * dg) + (lane & 15);
            uint4 v[8];
            #pragma unroll
            for (int i = 0; i < 8; i++) v[i] = lds128(la + i * 128 + (((lane & 7) ^ i) << 4));
            #pragma unroll
            for (int i = 0; i < 8; i++) dst[i * 64] = v[i];
        }
        STAMP(7); GSTAMP(23);
    }
}

__device__ __forceinline__ float2 cexp_p(float re2, float im, float p) {
    float sn, cs;
    const float mag = ex2(re2 * p), th = im * p;
    asm("sin.approx.ftz.f32 %0, %1;" : "=f"(sn) : "f"(th));
    asm("cos.approx.ftz.f32 %0, %1;" : "=f"(cs) : "f"(th));
    return make_float2(mag * cs, mag * sn);
}
struct SsmRaw { unsigned short la, ai, cr, ci, ldt, dsk; };
__device__ __forceinline__ unsigned short ldu16(const void* p) { unsigned short v; asm volatile("ld.global.nc.u16 %0, [%1];" : "=h"(v) : "l"(p)); return v; }
__device__ __forceinline__ float2 cmul(float2 a, float2 b) { return make_float2(fmaf(a.x, b.x, -a.y * b.y), fmaf(a.x, b.y, a.y * b.x)); }
__device__ __forceinline__ float2 csqr(float2 a) { const float t = a.x * a.y; return make_float2(fmaf(a.x, a.x, -a.y * a.y), t + t); }
__device__ __forceinline__ void mma16816(float (&d)[4], const uint32_t (&a)[4], uint32_t b0, uint32_t b1) {
    asm volatile("mma.sync.aligned.m16n8k16.row.col.f32.bf16.bf16.f32 {%0,%1,%2,%3}, {%4,%5,%6,%7}, {%8,%9}, {%0,%1,%2,%3};"
        : "+f"(d[0]), "+f"(d[1]), "+f"(d[2]), "+f"(d[3]) : "r"(a[0]), "r"(a[1]), "r"(a[2]), "r"(a[3]), "r"(b0), "r"(b1));
}

__device__ __forceinline__ void layer_norm(uint32_t sb, uint32_t cb, int w, int lane) {
    const uint32_t bars = sb + OFF_BAR;
    mbar_wait(bars + 8 * B_LNX, 0);
    STAMP(34);
    {
        const uint32_t r0 = cb + CH_LN + (w & 1) * 64 + (lane >> 3) * 1040, ra = r0 + (lane & 7) * 16;
        const float pv = bf_lo(FU(ldsf(r0)));
        float s0 = 0.f, s1 = 0.f, a0 = 0.f, a1 = 0.f;
        #pragma unroll 1
        for (int k = 0; k < 1024; k += 512) {
            uint32_t v[16];
            #pragma unroll
            for (int j = 0; j < 4; j++) *(uint4*)&v[4 * j] = lds128(ra + k + 128 * j);
            #pragma unroll
            for (int i = 0; i < 16; i++) { const float t0 = bf_lo(v[i]) - pv, t1 = bf_hi(v[i]) - pv; s0 += t0; s1 += t1; a0 = fmaf(t0, t0, a0); a1 = fmaf(t1, t1, a1); }
        }
        s0 += s1; a0 += a1;
        #pragma unroll
        for (int o = 4; o; o >>= 1) { s0 += __shfl_xor_sync(0xffffffffu, s0, o); a0 += __shfl_xor_sync(0xffffffffu, a0, o); }
        s0 *= 1.f / DM;
        float sd, ri;
        asm("sqrt.approx.ftz.f32 %0, %1;" : "=f"(sd) : "f"(bf_round(bf_round(fmaxf(fmaf(-s0, s0, a0 * (1.f / DM)), 0.f)) + 1e-5f)));
        asm("rcp.approx.ftz.f32 %0, %1;" : "=f"(ri) : "f"(bf_round(sd)));
        if ((lane & 7) == 0) sts64(sb + OFF_CSUM + (w + 4 * (lane >> 3)) * 8, FU(bf_round(pv + s0)), FU(0.5f * ri));
    }
    STAMP(62);
    bar_sync(2);
    const int r = 4 * ((lane & 7) >> 1) + (lane & 1) + 2 * ((lane >> 3) & 1);
    const uint32_t ad = sb + OFF_CONV + (r & 3) * CH_STRIDE + CH_LN + (r & 1) * 64 + (r >> 2) * 1040 + (16 * w + (lane >> 4)) * 16;
    const uint4 sa = lds128(sb + OFF_CSUM + (lane & 3) * 32), sc = lds128(sb + OFF_CSUM + (lane & 3) * 32 + 16);
    const uint32_t m2[2] = {__byte_perm(sa.x, sa.z, 0x7632), __byte_perm(sc.x, sc.z, 0x7632)};
    const float ri[4] = {2.f * UF(sa.y), 2.f * UF(sa.w), 2.f * UF(sc.y), 2.f * UF(sc.w)};
    #pragma unroll 1
    for (int i = 0; i < 8; i += 4) {
        uint32_t v[4][4];
        #pragma unroll
        for (int j = 0; j < 4; j++)
            asm volatile("ldmatrix.sync.aligned.m8n8.x4.trans.shared.b16 {%0,%1,%2,%3}, [%4];" : "=r"(v[j][0]), "=r"(v[j][1]), "=r"(v[j][2]), "=r"(v[j][3]) : "r"(ad + 32 * (i + j)) : "memory");
        #pragma unroll
        for (int j = 0; j < 4; j++) {
            #pragma unroll
            for (int k = 0; k < 4; k++) {
                uint32_t dv; asm("sub.rn.bf16x2 %0, %1, %2;" : "=r"(dv) : "r"(v[j][k]), "r"(m2[k & 1]));
                v[j][k] = pack2(bf_lo(dv) * ri[2 * (k & 1)], bf_hi(dv) * ri[2 * (k & 1) + 1]);
            }
            sts64(cb + CH_LNT + lane * 8 + (i + j) * 512, v[j][0], v[j][1]); sts64(cb + CH_LNT + lane * 8 + (i + j) * 512 + 256, v[j][2], v[j][3]);
        }
    }
    fence_async_smem();
    mbar_arrive(bars + 8 * B_LN);
    STAMP(16);
}

__device__ __forceinline__ void kernel_gen(uint32_t fs, int lane, const SsmRaw& raw, float (&dacc)[2][3][4], const Params& P, int warp) {
    const float dt = bf_round(ex2(bf_lo(raw.ldt) * 1.4426950408889634f));
    const float re2 = bf_round(ex2(bf_lo(raw.la) * 1.4426950408889634f)) * dt * -1.4426950408889634f, im = bf_lo(raw.ai) * dt;
    const float2 C = make_float2(bf_lo(raw.cr) * (dt + dt), bf_lo(raw.ci) * -(dt + dt));
    STAMP(56);
    if (warp < 4 && lane == 0 && re2 != 1.f) {
        const int c = blockIdx.x;
        const char* p = warp < 2 ? (const char*)(P.x + (16 * (c & ~1) + 8 * (c & 1) + 16 * warp) * DM) : (const char*)(warp == 2 ? P.Wg : P.Wu) + 256 * FF * 2 + c * 5504;
        asm volatile("cp.async.bulk.prefetch.L2.global [%0], %1;" :: "l"(p), "r"(warp < 2 ? 8192 : 5504) : "memory");
    }
    const float2 y1 = cexp_p(re2, -im, 1.f), y256 = cexp_p(re2, -im, 256.f), z64 = cexp_p(re2, im, 64.f);
    const uint32_t fm = fs + (lane >> 3) * 144 + (lane & 7) * 16;
#define PK(v) pack2((v).x, (v).y)
    const float2 y2 = csqr(y1), y4 = csqr(y2), y8 = csqr(y4);
    const float2 l1 = cmul(C, y1), l2 = cmul(C, y2), l3 = cmul(l1, y2);
    stsm4(fm, PK(C), PK(l1), PK(l2), PK(l3));
    stsm4(fm + 4 * 144, PK(cmul(C, y4)), PK(cmul(l1, y4)), PK(cmul(l2, y4)), PK(cmul(l3, y4)));
    const float2 t0 = cmul(C, y256), t1 = cmul(t0, y256), t2 = cmul(t1, y256), t3_ = cmul(t2, y256);
    const float2 u1 = cmul(t0, y2), u2 = cmul(u1, y2), u3 = cmul(u2, y2);
    stsm4(fm + 8 * 144, PK(t0), PK(u1), PK(u2), PK(u3));
    stsm4(fm + 12 * 144, PK(t1), PK(cmul(t1, y4)), PK(t2), PK(cmul(t2, y4)));
    const float2 v0 = cmul(t3_, y8), v1 = cmul(v0, y256), v2 = cmul(v1, y256), v3 = cmul(v2, y256);
    stsm4(fm + 16 * 144, PK(v0), PK(v1), PK(v2), PK(v3));
    stsf(fs + lane * 4 + 20 * 144, UF(PK(t3_)));
    STAMP(57);
    const uint32_t ldb = fs + (lane & 7) * 144 + ((lane >> 3) & 1) * 16 + (lane >> 4) * 8 * 144;
    const float p8 = (float)(2 * (lane & 28));
    __syncwarp();
    #pragma unroll 1
    for (int ks = 0; ks < 4; ks++) {
        uint32_t b01[4], b2[2], a0[4], a1[4];
        ldsm4(b01, ldb + ks * 32);
        asm volatile("ldmatrix.sync.aligned.m8n8.x2.shared.b16 {%0,%1}, [%2];" : "=r"(b2[0]), "=r"(b2[1]) : "r"(ldb + 16 * 144 + ks * 32) : "memory");
        #pragma unroll
        for (int mh = 0; mh < 2; mh++) {
            const int src = 8 * ks + 4 * mh + (lane & 3);
            const float2 z = make_float2(__shfl_sync(0xffffffffu, z64.x, src), __shfl_sync(0xffffffffu, z64.y, src));
            const float2 R0 = cexp_p(__shfl_sync(0xffffffffu, re2, src), __shfl_sync(0xffffffffu, im, src), p8);
            const float2 R1 = cmul(R0, z), R2 = cmul(R1, z), R3 = cmul(R2, z);
            a0[2 * mh] = PK(R0); a0[2 * mh + 1] = PK(R1); a1[2 * mh] = PK(R2); a1[2 * mh + 1] = PK(R3);
        }
        mma16816(dacc[0][0], a0, b01[0], b01[1]); mma16816(dacc[1][0], a1, b01[0], b01[1]);
        mma16816(dacc[0][1], a0, b01[2], b01[3]); mma16816(dacc[1][1], a1, b01[2], b01[3]);
        mma16816(dacc[0][2], a0, b2[0], b2[1]);   mma16816(dacc[1][2], a1, b2[0], b2[1]);
    }
#undef PK
    STAMP(58);
}

__device__ __forceinline__ void aux_role(uint32_t sb, int w, float (&dacc)[2][3][4], float dsk, const __nv_bfloat16* x) {
    const int lane = threadIdx.x & 31, q = lane & 3, g = lane >> 2;
    const int c = blockIdx.x;
    const uint32_t bars = sb + OFF_BAR;
    if (c >= 128) { mbar_arrive(bars + 8 * B_LN); return; }
    {
        const uint32_t cb = sb + OFF_CONV + w * CH_STRIDE;
        if (elect_one()) {
            fence_async_smem();
            mbar_expect(bars + 8 * B_LNX, 4096);
            #pragma unroll
            for (int i = 0; i < 4; i++)
                bulk_load(cb + CH_LN + (w & 1) * 64 + i * 1040, x + (16 * (c & ~1) + 8 * (c & 1) + 16 + w + 4 * (i & 1) - 8 * (i & 2)) * DM, 1024, bars + 8 * B_LNX);
        }
        layer_norm(sb, cb, w, lane);
        {
            uint4 v[2][3];
            #pragma unroll
            for (int i = 0; i < 3; i++) v[0][i] = lds128(cb + CH_PART + lane * 16 + i * 512);
            #pragma unroll
            for (int k = 0; k < 6; k++) {
                #pragma unroll
                for (int i = 0; i < 3; i++) if (k < 5) v[(k + 1) & 1][i] = lds128(cb + CH_PART + lane * 16 + (k + 1) * 1536 + i * 512);
                #pragma unroll
                for (int i = 0; i < 3; i++) {
                    float* d = &dacc[0][0][0] + 12 * (k & 1) + 4 * i;
                    d[0] += UF(v[k & 1][i].x); d[1] += UF(v[k & 1][i].y); d[2] += UF(v[k & 1][i].z); d[3] += UF(v[k & 1][i].w);
                }
            }
        }
        __syncwarp();
        STAMP(18);
        const uint32_t sF = cb + CH_A3, sG = cb + CH_G;
        if (lane == 0) dacc[0][0][0] += dsk;
        if (lane < 10) sts128(sG + 128 + (lane & 1) * 208 + (lane >> 1) * 16, 0, 0, 0, 0);
        const uint32_t f0 = sF + (8 * g + 2 * q) * 4, f1 = sF + ((q < 2) ? 256 + 4 * g + 2 * q : 256 + 2 * g + 64 * q) * 4, st1 = (q < 2) ? 128 : 64;
        const uint32_t ga = sG + ((g & 1) ? 0 : 208) + (63 - (g >> 1) - 32 * q) * 2;
        #pragma unroll
        for (int i = 0; i < 4; i++) {
            const int mu = i >> 1, hh = i & 1;
            sts64(f0 + i * 256, FU(dacc[mu][0][2 * hh]), FU(dacc[mu][0][2 * hh + 1]));
            sts64(f1 + i * st1, FU(dacc[mu][1][2 * hh]), FU(dacc[mu][1][2 * hh + 1]));
            const uint32_t pk = pack2(dacc[mu][2][2 * hh], dacc[mu][2][2 * hh + 1]);
            if (q < 2) { sts16(ga - 8 * i, pk & 0xffff); sts16(ga - 8 * i - 32, pk >> 16); }
        }
        if (lane == 2) stsf(sF + 2048, dacc[0][2][0]);
        STAMP(19);
        bar_sync(2);
    }
    const int u = min(lane, 30) - 15, r2 = (u + ((u >> 1) & 1)) >> 1, r4 = (u + 1 + ((u >> 2) & 1)) >> 2, xt = 1024 + 16 * w + u;
    const uint32_t o0 = CH_A3 + 4 * (w == 0 ? u : w == 1 ? 256 + r2 : 256 + 64 * w + r4), ost = w == 0 ? 64 : w == 1 ? 32 : 16;
    const uint32_t oa0 = u >= 0 || w == 3 ? o0 : CH_A3 + 4 * (w == 1 ? 256 + u : w == 2 ? 384 + r2 : 0);
    const uint32_t ot = CH_A3 + 4 * min(512, 256 + ((xt + 1 + ((xt >> 2) & 1)) >> 2));
    const int kap = (lane >> 4) * 8 + ((lane >> 1) & 7), gam = lane & 1, hh = w >> 1, wp = w & 1;
    const uint32_t oa = CH_U + wp * UPLANE + (127 - 4 * kap - 2 * gam - hh) * 16;
    const uint32_t ob = CH_U + (wp ^ 1) * UPLANE + (128 - wp - 4 * kap - 2 * gam - hh) * 16;
    const uint32_t od = CH_A3 + (4 * wp + hh) * 512 + (kap >> 3) * 256 + (kap & 7) * 16 + gam * 8;
    const int tid = threadIdx.x & 127;
    const uint32_t og = CH_G + (tid >= 24) * 16 + min(tid, 47) * 8, cend = sb + OFF_CONV + 3 * CH_STRIDE;
    {
        float nx[17]; uint2 n0, n1;
#define LDT(b) nx[0] = ldsf((b) + oa0); nx[16] = ldsf((b) + ot); _Pragma("unroll") for (int s = 1; s < 16; s++) nx[s] = ldsf((b) + o0 + s * ost); n0 = lds64((b) + og); n1 = lds64((b) + og + 8)
        LDT(sb + OFF_CONV);
        #pragma unroll 1
        for (uint32_t cb = sb + OFF_CONV; cb <= cend; cb += CH_STRIDE) {
            float kv[17];
            #pragma unroll
            for (int s = 0; s < 17; s++) kv[s] = nx[s];
            if (tid < 48) sts128(cb + CH_B3 + tid * 16, n0.x, n0.y, n1.x, n1.y);
            LDT(min(cb + CH_STRIDE, cend));
            if (u < 0 && w == 0) kv[0] = 0.f;
            if (xt > 1028) kv[16] = 0.f;
            uint32_t o[17];
            #pragma unroll
            for (int s = 0; s < 17; s++) o[s] = pack2(kv[s], __shfl_up_sync(0xffffffffu, kv[s], 1));
            if (lane > 0 && lane < 31) {
                const uint32_t ta = cb + CH_T + (lane - 1) * 280;
                #pragma unroll
                for (int s2 = 0; s2 < 8; s2++) sts64(ta + 64 * w + s2 * 8, o[2 * s2], o[2 * s2 + 1]);
                stsf(ta + 256 + 4 * w, UF(o[16]));
            }
        }
#undef LDT
    }
    STAMP(61);
    mbar_wait(bars + 8 * B_U, 0);
    if (lane < 8) sts128(sb + OFF_CONV + w * CH_STRIDE + CH_U + 2048 + (lane & 4) * (UPLANE / 4) + (lane & 3) * 16, 0, 0, 0, 0);
    bar_sync(2);
    STAMP(17);
    uint2 n0 = lds64(sb + OFF_CONV + ob + 24), n3 = lds64(sb + OFF_CONV + oa);
    uint4 n1 = lds128(sb + OFF_CONV + oa + 16), n2 = lds128(sb + OFF_CONV + ob);
    #pragma unroll 1
    for (uint32_t cb = sb + OFF_CONV; cb <= cend; cb += CH_STRIDE) {
        const uint32_t r[12] = {n0.x, n0.y, n1.x, n1.y, n1.z, n1.w, n2.x, n2.y, n2.z, n2.w, n3.x, n3.y}, nb = min(cb + CH_STRIDE, cend);
        n0 = lds64(nb + ob + 24); n3 = lds64(nb + oa); n1 = lds128(nb + oa + 16); n2 = lds128(nb + ob);
        float p[24];
        p[0] = 0.f; p[1] = bf_lo(r[0]);
        #pragma unroll
        for (int i = 2; i < 24; i++) p[i] = p[i - 1] + ((i & 1) ? bf_lo(r[i >> 1]) : bf_hi(r[(i - 1) >> 1]));
        #pragma unroll
        for (int i = 0; i < 8; i += 4) {
            sts64(cb + od + i * 256, pack2(p[i + 9] - p[i], p[i + 10] - p[i + 1]), pack2(p[i + 11] - p[i + 2], p[i + 12] - p[i + 3]));
            sts64(cb + od + i * 256 + 128, pack2(p[i + 16] - p[i + 9], p[i + 17] - p[i + 10]), pack2(p[i + 18] - p[i + 11], p[i + 19] - p[i + 12]));
        }
    }
    fence_async_smem();
    mbar_arrive(bars + 8 * B_CONV);
    STAMP(21);
}

__device__ __forceinline__ void store_h(uint32_t sb, const Params& P, const Maps& M, int V, int tg, int fb) {
    const uint32_t bars = sb + OFF_BAR;
    mbar_wait(bars + 8 * (B_EPI + V), 0);
    STAMP2(3 + 2 * V);
    asm volatile("cp.async.bulk.tensor.3d.global.shared::cta.bulk_group [%0, {%2, %3, %4}], [%1];"
        :: "l"(&M.hst[V]), "r"(sb + OFF_X + V * 2 * XBUF), "r"(0), "r"(43 * tg + 21 * V), "r"(8 * fb) : "memory");
    flag_signal(P.flags, F_H + 2 * tg + V);
    mbar_arrive(bars + 8 * (B_STG + V));
    STAMP2(4 + 2 * V);
}

__global__ void __launch_bounds__(512, 1)
fused_kernel(const __grid_constant__ Params P, const __grid_constant__ Maps M) {
    extern __shared__ __align__(1024) uint8_t smem_raw[];
    const uint32_t sb = smem_u32(smem_raw);
    const uint32_t bars = sb + OFF_BAR;
    const int warp = __shfl_sync(0xffffffffu, threadIdx.x >> 5, 0);
    const int c = blockIdx.x, tg = c / 22, fb = c - 22 * tg;
    SsmRaw raw;
    {
        const int d = min(4 * c + (warp & 3), DM - 1), o = d * 128 + (warp >> 2) * 32 + (threadIdx.x & 31);
        raw.la = ldu16(P.logA + o); raw.ai = ldu16(P.Aim + o); raw.cr = ldu16(P.Cr + o); raw.ci = ldu16(P.Ci + o);
        raw.ldt = ldu16(P.logdt + d); raw.dsk = ldu16(P.Dskip + d);
    }
    if (elect_one()) {
        if (warp == 0) { STAMP(24); GSTAMP(22); }
        asm volatile("" :: "l"(((const uint64_t*)&P)[warp < 15 ? warp : 0]));
        if (warp < 11) asm volatile("prefetch.tensormap [%0];" :: "l"(&M.x[0] + warp) : "memory");
        #pragma unroll
        for (int k = 0; k < 4; k++) {
            const int i = 16 * k + ((warp + 4) & 15);
            const uint32_t cnt = i >= B_CONV ? 128 : ((0xf0ull >> i) & 1) ? 8 : ((0xff0000ull >> i) & 1) ? 2 : ((0x3e00ff00f000ull >> i) & 1) ? 4 : 1;
            asm volatile("mbarrier.init.shared::cta.b64 [%0], %1;" :: "r"(bars + 8 * i), "r"(cnt) : "memory");
        }
        asm volatile("fence.mbarrier_init.release.cluster; fence.proxy.async.shared::cta;" ::: "memory");
        if (warp >= 12) {
            const uint32_t s = warp - 12;
            mbar_expect(bars + 8 * (B_FULLW + s), 16384);
            tma2d(sb + OFF_W + s * 16384, &M.wg, 64 * fb, 64 * s, bars + 8 * (B_FULLW + s));
            tma2d(sb + OFF_W + s * 16384 + 8192, &M.wu, 64 * fb, 64 * s, bars + 8 * (B_FULLW + s));
            STAMP(31);
        } else if ((warp >> 2) == 1) {
            const uint32_t s = warp - 4, V = s >> 1;
            mbar_expect(bars + 8 * (B_FULLX + s), (168 + 8 * V) * 128);
            tma2d(sb + OFF_X + s * XBUF, &M.x[V], 64 * (s & 1), TOKG * tg + 168 * V, bars + 8 * (B_FULLX + s));
        }
        if (sb & 1023) __trap();
    }
    if (warp < 4) sts128(sb + OFF_X + (warp >> 1) * XBUF + 168 * 128 + (threadIdx.x & 63) * 16, 0x3f803f80u, 0x3f803f80u, 0x3f803f80u, 0x3f803f80u);
    float dacc[2][3][4];
    #pragma unroll
    for (int i = 0; i < 24; i++) (&dacc[0][0][0])[i] = 0.f;
    if (c < 128) {
        const int wg = warp >> 2;
        const uint32_t fs = sb + OFF_CONV + (warp & 3) * CH_STRIDE + (wg == 2 ? 0 : CH_PART + min(wg, 2) * CH_PSZ);
        kernel_gen(fs, threadIdx.x & 31, raw, dacc, P, warp);
        if (wg != 2) {
            __syncwarp();
            #pragma unroll
            for (int i = 0; i < 6; i++) { const float* d = &dacc[0][0][0] + 4 * i; sts128(fs + (threadIdx.x & 31) * 16 + i * 512, FU(d[0]), FU(d[1]), FU(d[2]), FU(d[3])); }
        }
    }
    if (warp < 4) fence_async_smem();
    __syncthreads();
    if (warp < 8) {
        asm volatile("setmaxnreg.inc.sync.aligned.u32 208;");
        consumer(sb, warp, P, M);
        asm volatile("nanosleep.u32 1;");
    } else if (warp < 12) {
        asm volatile("setmaxnreg.dec.sync.aligned.u32 72;");
        STAMP(32);
        aux_role(sb, warp - 8, dacc, bf_lo(raw.dsk), P.x);
        asm volatile("nanosleep.u32 2;");
    } else {
        asm volatile("setmaxnreg.dec.sync.aligned.u32 24;");
        const int tau = c >> 2, dg = c & 3;
        if (elect_one()) {
            if (warp < 15) {
                if (warp == 12) {
                    #pragma unroll 1
                    for (int st = 4; st < 8; st++) {
                        const uint32_t s = st & 3, fb_ = bars + 8 * (B_FULLW + s);
                        mbar_wait(bars + 8 * (B_EMPTYW + s), 0);
                        mbar_expect(fb_, 16384);
                        tma2d(sb + OFF_W + s * 16384, &M.wg, 64 * fb, 64 * st, fb_);
                        tma2d(sb + OFF_W + s * 16384 + 8192, &M.wu, 64 * fb, 64 * st, fb_);
                    }
                } else {
                    const int V = warp - 13;
                    #pragma unroll 1
                    for (int st = 2; st < 8; st++) {
                        const uint32_t s = 2 * V + (st & 1);
                        mbar_wait(bars + 8 * (B_EMPTYX + s), ((st >> 1) & 1) ^ 1);
                        mbar_expect(bars + 8 * (B_FULLX + s), (168 + 8 * V) * 128);
                        tma2d(sb + OFF_X + s * XBUF, &M.x[V], 64 * st, TOKG * tg + 168 * V, bars + 8 * (B_FULLX + s));
                    }
                }
                if (warp == 14) store_h(sb, P, M, 1, tg, fb);
                if (c < 128 && warp < 14) {
                    if (warp == 13) {
                        mbar_wait(bars + 8 * (B_STG + 1), 0);
                        #pragma unroll 1
                        for (int o = 8 * tau; o < 8 * tau + 8; o += 7) flag_wait(P.flags, F_H + 2 * (o / 43) + ((o % 43) >= 21), 22);
                        mbar_arrive(bars + 8 * B_HF);
                        STAMP(25);
                    }
                    #pragma unroll 1
                    for (int st = 0; st < 22; st += (st < 6 || (st == 6 && warp == 13)) ? 1 : 2) {
                        const int rd = (st >= 7) + (st >= 14) + (st >= 21), sd = st - 7 * rd;
                        const uint32_t fb_ = bars + 8 * (B_FULLD + sd);
                        if (rd) mbar_wait(bars + 8 * (B_EMPTYD + sd), (rd & 1) ^ 1);
                        else if (warp == 12 || st == 6) mbar_wait(bars + 8 * (uint32_t)((0x3623070d060504ull >> (8 * st)) & 0xff), st < 5);
                        if (st >= 10 && st < 21) STAMP2(31 + st);
                        if (rd || warp == 13) {
                            mbar_expect(fb_, 8192);
                            asm volatile("cp.async.bulk.tensor.5d.shared::cluster.global.mbarrier::complete_tx::bytes [%0], [%1, {%3, %3, %3, %4, %5}], [%2];"
                                :: "r"(sb + h_slot(sd)), "l"(&M.hld), "r"(fb_), "r"(0), "r"(2 * tau), "r"(8 * st) : "memory");
                        }
                        if (rd || warp == 12) {
                            const uint32_t da = sb + wd_slot(sd);
                            mbar_expect(fb_, 16384);
                            tma2d(da, &M.wd, 128 * dg, 64 * st, fb_);
                            tma2d(da + 8192, &M.wd, 128 * dg + 64, 64 * st, fb_);
                        }
                    }
                } else if (c < 128) {
                    mbar_wait(bars + 8 * (B_SIG + 1), 0);
                    mbar_expect(bars + 8 * B_XO, 32768);
                    tma2d(sb + OFF_XO, &M.xo, 128 * dg, 64 * tau, bars + 8 * B_XO);
                    tma2d(sb + OFF_XO + 8192, &M.xo, 128 * dg + 64, 64 * tau, bars + 8 * B_XO);
                    mbar_wait(bars + 8 * B_SST, 0);
                    flag_wait(P.flags, F_S + dg, 64);
                    STAMP(26);
                    asm volatile("cp.async.bulk.tensor.5d.shared::cluster.global.mbarrier::complete_tx::bytes [%0], [%1, {%3, %3, %3, %4, %5}], [%2];"
                        :: "r"(sb + OFF_SI), "l"(&M.sld), "r"(bars + 8 * B_XO), "r"(0), "r"(8 * dg), "r"(2 * tau) : "memory");
                    mbar_wait(bars + 8 * B_HF, 0);
                    exit_count(P.flags);
                }
            } else {
                mbar_wait(bars + 8 * B_LN, 0);
                STAMP2(0);
                if (c < 128) {
                    #pragma unroll 1
                    for (int i = 0; i < 4; i++)
                        asm volatile("cp.async.bulk.tensor.2d.global.shared::cta.bulk_group [%0, {%2, %3}], [%1];"
                            :: "l"(&M.xt), "r"(sb + OFF_CONV + i * CH_STRIDE + CH_LNT), "r"((c & 1) * 1024 + (126 - (c & ~1)) * 8), "r"(128 * i) : "memory");
                    #pragma unroll 1
                    for (int i = 0; i < 2; i++) bulk_store(P.st + 16 * (c & ~1) + 8 * (c & 1) + 16 - 16 * i, sb + OFF_CSUM + 64 * i, 64);
                    asm volatile("cp.async.bulk.prefetch.L2.global [%0], %1;" :: "l"(P.Wd + c * (FF * DM / 128)), "r"(FF * DM / 64) : "memory");
                }
                STAMP2(1);
                flag_signal(P.flags, F_A);
                STAMP2(2);
                flag_wait(P.flags, F_A, NCTA);
                STAMP(20);
                mbar_expect(bars + 8 * B_STATS, TOKG * 8);
                bulk_load(sb + OFF_ST, P.st + TOKG * tg, TOKG * 8, bars + 8 * B_STATS);
                if (c < 128) {
                    mbar_expect(bars + 8 * B_U, 8 * 2048);
                    #pragma unroll 1
                    for (int i = 0; i < 8; i++)
                        bulk_load(sb + OFF_CONV + (i >> 1) * CH_STRIDE + CH_U + (i & 1) * UPLANE, P.xnT + 4 * c * 256 + i * 128, 2048, bars + 8 * B_U);
                } else exit_count(P.flags);
                store_h(sb, P, M, 0, tg, fb);
                if (c < 128) {
                    #pragma unroll 1
                    for (int V = 0; V < 2; V++) {
                        mbar_wait(bars + 8 * (B_SIG + V), 0);
                        STAMP2(7 + 2 * V);
                        bulk_store(P.S + (2 * c + V) * 1024, sb + OFF_CONV + V * OFF_SST, 8192);
                        flag_signal(P.flags, F_S + (c >> 5));
                        STAMP2(8 + 2 * V);
                    }
                    mbar_arrive(bars + 8 * B_SST);
                }
            }
            asm volatile("nanosleep.u32 0;");
        }
    }
}

typedef CUresult (*EncodeFn)(CUtensorMap*, CUtensorMapDataType, cuuint32_t, void*, const cuuint64_t*, const cuuint64_t*, const cuuint32_t*,
                             const cuuint32_t*, CUtensorMapInterleave, CUtensorMapSwizzle, CUtensorMapL2promotion, CUtensorMapFloatOOBfill);

void make_map(EncodeFn enc, CUtensorMap* m, const void* ptr, int rank, const cuuint64_t* dims, const cuuint64_t* strides, const cuuint32_t* box, bool swz, bool wide = false) {
    const cuuint32_t es[5] = {1, 1, 1, 1, 1};
    enc(m, CU_TENSOR_MAP_DATA_TYPE_BFLOAT16, rank, (void*)ptr, dims, strides, box, es, CU_TENSOR_MAP_INTERLEAVE_NONE,
        swz ? CU_TENSOR_MAP_SWIZZLE_128B : CU_TENSOR_MAP_SWIZZLE_NONE, wide ? CU_TENSOR_MAP_L2_PROMOTION_L2_256B : CU_TENSOR_MAP_L2_PROMOTION_L2_128B, CU_TENSOR_MAP_FLOAT_OOB_FILL_NONE);
}
void make_map2(EncodeFn enc, CUtensorMap* m, const void* ptr, cuuint64_t inner, cuuint64_t outer, cuuint32_t rows) {
    const cuuint64_t dims[2] = {inner, outer}, strides[1] = {inner * 2};
    const cuuint32_t box[2] = {64, rows};
    make_map(enc, m, ptr, 2, dims, strides, box, true, rows > 64);
}

}

extern "C" void kernel_launch(void* const* d_in, const int* in_sizes, int n_in, void* d_out, int out_size) {
    (void)in_sizes; (void)n_in; (void)out_size;
    static EncodeFn enc = nullptr;
    static void *hptr, *p_xnT, *p_st, *p_S, *p_flags;
    if (!enc) {
        cudaDriverEntryPointQueryResult qr;
        cudaGetDriverEntryPoint("cuTensorMapEncodeTiled", (void**)&enc, cudaEnableDefault, &qr);
        cudaFuncSetAttribute(fused_kernel, cudaFuncAttributeMaxDynamicSharedMemorySize, SMEM_BYTES);
        cudaGetSymbolAddress(&hptr, g_H); cudaGetSymbolAddress(&p_xnT, g_xnT); cudaGetSymbolAddress(&p_st, g_st);
        cudaGetSymbolAddress(&p_S, g_S); cudaGetSymbolAddress(&p_flags, g_flags);
    }
    Params P;
    P.x = (const __nv_bfloat16*)d_in[0]; P.logA = (const __nv_bfloat16*)d_in[1]; P.Aim = (const __nv_bfloat16*)d_in[2];
    P.Cr = (const __nv_bfloat16*)d_in[3]; P.Ci = (const __nv_bfloat16*)d_in[4]; P.logdt = (const __nv_bfloat16*)d_in[5];
    P.Dskip = (const __nv_bfloat16*)d_in[6];
    P.Wg = (const __nv_bfloat16*)d_in[8]; P.Wu = (const __nv_bfloat16*)d_in[9]; P.Wd = (const __nv_bfloat16*)d_in[10]; P.out = (__nv_bfloat16*)d_out; P.xnT = (uint4*)p_xnT; P.st = (float2*)p_st; P.S = (uint2*)p_S; P.flags = (unsigned*)p_flags;
    Maps M;
    make_map2(enc, &M.x[0], d_in[0], DM, SEQ, 168); make_map2(enc, &M.x[1], d_in[0], DM, SEQ, 176);
    make_map2(enc, &M.xo, d_in[0], DM, SEQ, 64);
    make_map2(enc, &M.wg, d_in[8], FF, DM, 64);     make_map2(enc, &M.wu, d_in[9], FF, DM, 64);
    make_map2(enc, &M.wd, d_in[10], DM, FF, 64);
    for (int v = 0; v < 2; v++) {
        const cuuint64_t dims[3] = {64, 256, 172}, strides[2] = {128, 32768};
        const cuuint32_t box[3] = {64, (cuuint32_t)(21 + v), 8};
        make_map(enc, &M.hst[v], hptr, 3, dims, strides, box, false);
    }
    {
        const cuuint64_t dims[2] = {2048, 512}, strides[1] = {4096};
        const cuuint32_t box[2] = {16, 128};
        make_map(enc, &M.xt, p_xnT, 2, dims, strides, box, false);
    }
    {
        const cuuint64_t dims[5] = {64, 2, 4, 32, 64}, strides[4] = {4 * 8192, 8192, 8 * 8192, 128};
        const cuuint32_t box[5] = {64, 2, 4, 8, 2};
        make_map(enc, &M.sld, p_S, 5, dims, strides, box, true);
    }
    {
        const cuuint64_t dims[5] = {64, 2, 2, 64, 172}, strides[4] = {256, 128, 512, 32768};
        const cuuint32_t box[5] = {64, 2, 2, 2, 8};
        make_map(enc, &M.hld, hptr, 5, dims, strides, box, false);
    }
    fused_kernel<<<NCTA, 512, SMEM_BYTES>>>(P, M);
}
```

```cpp
#include <cuda_runtime.h>
#include <cuda_bf16.h>
#include <cuda.h>
#include <stdint.h>

#define PROF 0

namespace {

constexpr int SEQ = 2048, DM = 512, FF = 1376;
constexpr int NCTA = 132;
#define GOST 1
#define SIGK 3
#define DLY1 300
constexpr int RUNROLL = 2;
constexpr int TOKG = 344;

constexpr uint32_t OFF_W = 0;
constexpr uint32_t XBUF = 22528;
constexpr uint32_t OFF_X = 65536;
constexpr uint32_t OFF_CONV = 155648;
constexpr uint32_t CH_STRIDE = 17536;
constexpr uint32_t CH_T = 0;
constexpr uint32_t CH_A3 = 8448;
constexpr uint32_t CH_B3 = 12544;
constexpr uint32_t CH_U = 13312;
constexpr uint32_t CH_G = CH_A3 + 2064;
constexpr uint32_t UPLANE = 2112;
constexpr uint32_t CH_LN = 0, CH_PART = 4224, CH_PSZ = 3072, CH_LNT = 13440;
constexpr uint32_t OFF_SST = 60416;
constexpr uint32_t OFF_XO = 191488, OFF_SI = 207872;
constexpr uint32_t OFF_ST = 225792;
constexpr uint32_t OFF_CSUM = 228544;
constexpr uint32_t OFF_BAR = 229056;
constexpr uint32_t SMEM_BYTES = 229568;

enum {
    B_FULLW = 0, B_EMPTYW = 4, B_FULLX = 8, B_EMPTYX = 12, B_FULLD = 16, B_EMPTYD = 24,
    B_U = 32, B_XO = 33, B_S = 34, B_STG = 35, B_HF = 37, B_STATS = 38, B_LNS = 39, B_SST = 40,
    B_TURN = 43,
    B_CONV = 46, B_LN = 50, B_CS = 51, B_EPI = 52, B_SIG = 54,
    B_LNX = 60
};
enum { F_A = 0, F_H = 1, F_S = 13, F_EXIT = 17, F_COUNT = 18 };

__device__ uint4 g_xnT[DM * 256];
__device__ float2 g_st[6 * TOKG];
__device__ uint4 g_H[172 * 256 * 8];
__device__ uint2 g_S[256 * 1024];
__device__ unsigned g_flags[F_COUNT * 32];
#define STAMP(i) do {} while (0)
#define GSTAMP(i) do {} while (0)
#define STAMP2(i) do {} while (0)

__device__ __forceinline__ uint32_t smem_u32(const void* p) { return (uint32_t)__cvta_generic_to_shared(p); }
__device__ __forceinline__ void mbar_expect(uint32_t bar, uint32_t bytes) { asm volatile("mbarrier.arrive.expect_tx.shared::cta.b64 _, [%0], %1;" :: "r"(bar), "r"(bytes) : "memory"); }
__device__ __forceinline__ void mbar_arrive(uint32_t bar) { asm volatile("mbarrier.arrive.shared::cta.b64 _, [%0];" :: "r"(bar) : "memory"); }
__device__ __forceinline__ void mbar_wait(uint32_t bar, uint32_t parity) {
    asm volatile("{.reg .pred p; .reg .u32 n; mov.u32 n, 0x20000;\n"
                 "LW: mbarrier.try_wait.parity.shared::cta.b64 p, [%0], %1;\n"
                 "sub.u32 n, n, 1; setp.eq.or.u32 p, n, 0, p; @!p bra LW;}" :: "r"(bar), "r"(parity) : "memory");
}
__device__ __forceinline__ void mbar_arrive_if(uint32_t bar, uint32_t pred) {
    asm volatile("{.reg .pred p; setp.ne.u32 p, %1, 0; @p mbarrier.arrive.shared::cta.b64 _, [%0];}" :: "r"(bar), "r"(pred) : "memory");
}
__device__ __forceinline__ bool elect_one() { uint32_t p; asm volatile("{.reg .pred P; elect.sync _|P, 0xffffffff; selp.u32 %0, 1, 0, P;}" : "=r"(p)); return p; }
__device__ __forceinline__ void tma2d(uint32_t dst, const CUtensorMap* m, int c0, int c1, uint32_t bar) {
    asm volatile("cp.async.bulk.tensor.2d.shared::cluster.global.mbarrier::complete_tx::bytes [%0], [%1, {%3, %4}], [%2];"
        :: "r"(dst), "l"(m), "r"(bar), "r"(c0), "r"(c1) : "memory");
}
__device__ __forceinline__ void bulk_load(uint32_t dst, const void* src, uint32_t bytes, uint32_t bar) {
    asm volatile("cp.async.bulk.shared::cluster.global.mbarrier::complete_tx::bytes [%0], [%1], %2, [%3];" :: "r"(dst), "l"(src), "r"(bytes), "r"(bar) : "memory");
}
__device__ __forceinline__ void bulk_store(void* dst, uint32_t src, uint32_t bytes) {
    asm volatile("cp.async.bulk.global.shared::cta.bulk_group [%0], [%1], %2;" :: "l"(dst), "r"(src), "r"(bytes) : "memory");
}
__device__ __forceinline__ void fence_async_smem() { asm volatile("fence.proxy.async.shared::cta;" ::: "memory"); }
__device__ __forceinline__ void flag_wait(unsigned* g_flags, int f, unsigned target) {
    asm volatile("{.reg .pred p; .reg .u32 n, v; mov.u32 n, 0x40000;\n"
                 "LF: ld.acquire.gpu.global.u32 v, [%0]; setp.ge.u32 p, v, %1; @p bra LD;\n"
                 "sub.u32 n, n, 1; setp.ne.u32 p, n, 0; @p bra LF; trap;\nLD: }"
                 :: "l"(g_flags + f * 32), "r"(target) : "memory");
}
__device__ __forceinline__ void flag_signal(unsigned* g_flags, int f) {
    asm volatile("cp.async.bulk.commit_group; cp.async.bulk.wait_group 0; red.relaxed.gpu.global.add.u32 [%0], 1;" :: "l"(g_flags + f * 32) : "memory");
}
__device__ __forceinline__ void exit_count(unsigned* g_flags) {
    if (atomicAdd(g_flags + F_EXIT * 32, 1u) == NCTA - 1) {
        #pragma unroll 1
        for (int i = 0; i < F_COUNT; i++) g_flags[i * 32] = 0;
    }
}
__device__ __forceinline__ void bar_sync(int id) { asm volatile("bar.sync %0, 128;" :: "r"(id) : "memory"); }
__device__ __forceinline__ uint64_t mkdesc(uint32_t addr, uint32_t lbo, uint32_t sbo, uint32_t swz) {
    return (uint64_t)((addr >> 4) | ((lbo >> 4) << 16)) | ((uint64_t)((sbo >> 4) | (swz << 30)) << 32);
}
#define WG_FENCE() asm volatile("wgmma.fence.sync.aligned;" ::: "memory")
#define WG_COMMIT() asm volatile("wgmma.commit_group.sync.aligned;" ::: "memory")
#define WG_WAIT(n) asm volatile("wgmma.wait_group.sync.aligned " #n ";" ::: "memory")
template <int N> __device__ __forceinline__ void fence_acc(float (&d)[N]) {
    #pragma unroll
    for (int i = 0; i < N; i++) asm volatile("" : "+f"(d[i]) :: "memory");
}
template <int N> __device__ __forceinline__ void define_acc(float (&d)[N]) {
    #pragma unroll
    for (int i = 0; i < N; i++) asm volatile("" : "=f"(d[i]));
}
__device__ __forceinline__ uint32_t pack2(float lo, float hi) { uint32_t r; asm("cvt.rn.bf16x2.f32 %0, %1, %2;" : "=r"(r) : "f"(hi), "f"(lo)); return r; }
__device__ __forceinline__ float bf_lo(uint32_t v) { return __uint_as_float(v << 16); }
__device__ __forceinline__ float bf_hi(uint32_t v) { return __uint_as_float(v & 0xffff0000u); }
__device__ __forceinline__ float bf_round(float v) { return bf_hi(pack2(0.f, v)); }
__device__ __forceinline__ float tanh_fast(float v) { float r; asm("tanh.approx.f32 %0, %1;" : "=f"(r) : "f"(v)); return r; }
__device__ __forceinline__ float ex2(float v) { float r; asm("ex2.approx.ftz.f32 %0, %1;" : "=f"(r) : "f"(v)); return r; }
__device__ __forceinline__ uint4 lds128(uint32_t a) { uint4 v; asm volatile("ld.shared.v4.b32 {%0,%1,%2,%3}, [%4];" : "=r"(v.x), "=r"(v.y), "=r"(v.z), "=r"(v.w) : "r"(a)); return v; }
__device__ __forceinline__ uint2 lds64(uint32_t a) { uint2 v; asm volatile("ld.shared.v2.b32 {%0,%1}, [%2];" : "=r"(v.x), "=r"(v.y) : "r"(a)); return v; }
__device__ __forceinline__ float ldsf(uint32_t a) { float v; asm volatile("ld.shared.f32 %0, [%1];" : "=f"(v) : "r"(a)); return v; }
__device__ __forceinline__ void sts128(uint32_t a, uint32_t x, uint32_t y, uint32_t z, uint32_t w) { asm volatile("st.shared.v4.b32 [%0], {%1,%2,%3,%4};" :: "r"(a), "r"(x), "r"(y), "r"(z), "r"(w) : "memory"); }
__device__ __forceinline__ void sts64(uint32_t a, uint32_t x, uint32_t y) { asm volatile("st.shared.v2.b32 [%0], {%1,%2};" :: "r"(a), "r"(x), "r"(y) : "memory"); }
__device__ __forceinline__ void stsf(uint32_t a, float x) { asm volatile("st.shared.f32 [%0], %1;" :: "r"(a), "f"(x) : "memory"); }
__device__ __forceinline__ void sts16(uint32_t a, uint32_t x) { asm volatile("st.shared.b16 [%0], %1;" :: "r"(a), "h"((unsigned short)x) : "memory"); }
__device__ __forceinline__ void stsm4(uint32_t a, uint32_t r0, uint32_t r1, uint32_t r2, uint32_t r3) {
    asm volatile("stmatrix.sync.aligned.m8n8.x4.shared.b16 [%0], {%1,%2,%3,%4};" :: "r"(a), "r"(r0), "r"(r1), "r"(r2), "r"(r3) : "memory");
}
__device__ __forceinline__ void ldsm4(uint32_t (&r)[4], uint32_t a) {
    asm volatile("ldmatrix.sync.aligned.m8n8.x4.shared.b16 {%0,%1,%2,%3}, [%4];" : "=r"(r[0]), "=r"(r[1]), "=r"(r[2]), "=r"(r[3]) : "r"(a) : "memory");
}
#define FU(x) __float_as_uint(x)
#define UF(x) __uint_as_float(x)
__device__ __forceinline__ uint32_t wd_slot(int s) { return (uint32_t)((0xbba8403056201000ull >> (8 * s)) & 0xff) << 10; }
__device__ __forceinline__ uint32_t h_slot(int s) { return (uint32_t)((0xcba0908880787068ull >> (8 * s)) & 0xff) << 10; }

template<int N> __device__ __forceinline__ void wg_rs(float (&d)[64], uint32_t a0, uint32_t a1, uint32_t a2, uint32_t a3, uint64_t db);
template<> __device__ __forceinline__ void wg_rs<128>(float (&d)[64], uint32_t a0, uint32_t a1, uint32_t a2, uint32_t a3, uint64_t db) {
  asm volatile("{.reg .pred p; setp.ne.b32 p, 1, 0; wgmma.mma_async.sync.aligned.m64n128k16.f32.bf16.bf16 {%0,%1,%2,%3,%4,%5,%6,%7,%8,%9,%10,%11,%12,%13,%14,%15,%16,%17,%18,%19,%20,%21,%22,%23,%24,%25,%26,%27,%28,%29,%30,%31,%32,%33,%34,%35,%36,%37,%38,%39,%40,%41,%42,%43,%44,%45,%46,%47,%48,%49,%50,%51,%52,%53,%54,%55,%56,%57,%58,%59,%60,%61,%62,%63}, {%64,%65,%66,%67}, %68, p, 1, 1, 0;}"
    : "+f"(d[0]),"+f"(d[1]),"+f"(d[2]),"+f"(d[3]),"+f"(d[4]),"+f"(d[5]),"+f"(d[6]),"+f"(d[7]),"+f"(d[8]),"+f"(d[9]),"+f"(d[10]),"+f"(d[11]),"+f"(d[12]),"+f"(d[13]),"+f"(d[14]),"+f"(d[15]),"+f"(d[16]),"+f"(d[17]),"+f"(d[18]),"+f"(d[19]),"+f"(d[20]),"+f"(d[21]),"+f"(d[22]),"+f"(d[23]),"+f"(d[24]),"+f"(d[25]),"+f"(d[26]),"+f"(d[27]),"+f"(d[28]),"+f"(d[29]),"+f"(d[30]),"+f"(d[31]),"+f"(d[32]),"+f"(d[33]),"+f"(d[34]),"+f"(d[35]),"+f"(d[36]),"+f"(d[37]),"+f"(d[38]),"+f"(d[39]),"+f"(d[40]),"+f"(d[41]),"+f"(d[42]),"+f"(d[43]),"+f"(d[44]),"+f"(d[45]),"+f"(d[46]),"+f"(d[47]),"+f"(d[48]),"+f"(d[49]),"+f"(d[50]),"+f"(d[51]),"+f"(d[52]),"+f"(d[53]),"+f"(d[54]),"+f"(d[55]),"+f"(d[56]),"+f"(d[57]),"+f"(d[58]),"+f"(d[59]),"+f"(d[60]),"+f"(d[61]),"+f"(d[62]),"+f"(d[63]) : "r"(a0), "r"(a1), "r"(a2), "r"(a3), "l"(db));
}
template<> __device__ __forceinline__ void wg_rs<120>(float (&d)[64], uint32_t a0, uint32_t a1, uint32_t a2, uint32_t a3, uint64_t db) {
  asm volatile("{.reg .pred p; setp.ne.b32 p, 1, 0; wgmma.mma_async.sync.aligned.m64n120k16.f32.bf16.bf16 {%0,%1,%2,%3,%4,%5,%6,%7,%8,%9,%10,%11,%12,%13,%14,%15,%16,%17,%18,%19,%20,%21,%22,%23,%24,%25,%26,%27,%28,%29,%30,%31,%32,%33,%34,%35,%36,%37,%38,%39,%40,%41,%42,%43,%44,%45,%46,%47,%48,%49,%50,%51,%52,%53,%54,%55,%56,%57,%58,%59}, {%60,%61,%62,%63}, %64, p, 1, 1, 0;}"
    : "+f"(d[0]),"+f"(d[1]),"+f"(d[2]),"+f"(d[3]),"+f"(d[4]),"+f"(d[5]),"+f"(d[6]),"+f"(d[7]),"+f"(d[8]),"+f"(d[9]),"+f"(d[10]),"+f"(d[11]),"+f"(d[12]),"+f"(d[13]),"+f"(d[14]),"+f"(d[15]),"+f"(d[16]),"+f"(d[17]),"+f"(d[18]),"+f"(d[19]),"+f"(d[20]),"+f"(d[21]),"+f"(d[22]),"+f"(d[23]),"+f"(d[24]),"+f"(d[25]),"+f"(d[26]),"+f"(d[27]),"+f"(d[28]),"+f"(d[29]),"+f"(d[30]),"+f"(d[31]),"+f"(d[32]),"+f"(d[33]),"+f"(d[34]),"+f"(d[35]),"+f"(d[36]),"+f"(d[37]),"+f"(d[38]),"+f"(d[39]),"+f"(d[40]),"+f"(d[41]),"+f"(d[42]),"+f"(d[43]),"+f"(d[44]),"+f"(d[45]),"+f"(d[46]),"+f"(d[47]),"+f"(d[48]),"+f"(d[49]),"+f"(d[50]),"+f"(d[51]),"+f"(d[52]),"+f"(d[53]),"+f"(d[54]),"+f"(d[55]),"+f"(d[56]),"+f"(d[57]),"+f"(d[58]),"+f"(d[59]) : "r"(a0), "r"(a1), "r"(a2), "r"(a3), "l"(db));
}
template<> __device__ __forceinline__ void wg_rs<112>(float (&d)[64], uint32_t a0, uint32_t a1, uint32_t a2, uint32_t a3, uint64_t db) {
  asm volatile("{.reg .pred p; setp.ne.b32 p, 1, 0; wgmma.mma_async.sync.aligned.m64n112k16.f32.bf16.bf16 {%0,%1,%2,%3,%4,%5,%6,%7,%8,%9,%10,%11,%12,%13,%14,%15,%16,%17,%18,%19,%20,%21,%22,%23,%24,%25,%26,%27,%28,%29,%30,%31,%32,%33,%34,%35,%36,%37,%38,%39,%40,%41,%42,%43,%44,%45,%46,%47,%48,%49,%50,%51,%52,%53,%54,%55}, {%56,%57,%58,%59}, %60, p, 1, 1, 0;}"
    : "+f"(d[0]),"+f"(d[1]),"+f"(d[2]),"+f"(d[3]),"+f"(d[4]),"+f"(d[5]),"+f"(d[6]),"+f"(d[7]),"+f"(d[8]),"+f"(d[9]),"+f"(d[10]),"+f"(d[11]),"+f"(d[12]),"+f"(d[13]),"+f"(d[14]),"+f"(d[15]),"+f"(d[16]),"+f"(d[17]),"+f"(d[18]),"+f"(d[19]),"+f"(d[20]),"+f"(d[21]),"+f"(d[22]),"+f"(d[23]),"+f"(d[24]),"+f"(d[25]),"+f"(d[26]),"+f"(d[27]),"+f"(d[28]),"+f"(d[29]),"+f"(d[30]),"+f"(d[31]),"+f"(d[32]),"+f"(d[33]),"+f"(d[34]),"+f"(d[35]),"+f"(d[36]),"+f"(d[37]),"+f"(d[38]),"+f"(d[39]),"+f"(d[40]),"+f"(d[41]),"+f"(d[42]),"+f"(d[43]),"+f"(d[44]),"+f"(d[45]),"+f"(d[46]),"+f"(d[47]),"+f"(d[48]),"+f"(d[49]),"+f"(d[50]),"+f"(d[51]),"+f"(d[52]),"+f"(d[53]),"+f"(d[54]),"+f"(d[55]) : "r"(a0), "r"(a1), "r"(a2), "r"(a3), "l"(db));
}
template<> __device__ __forceinline__ void wg_rs<104>(float (&d)[64], uint32_t a0, uint32_t a1, uint32_t a2, uint32_t a3, uint64_t db) {
  asm volatile("{.reg .pred p; setp.ne.b32 p, 1, 0; wgmma.mma_async.sync.aligned.m64n104k16.f32.bf16.bf16 {%0,%1,%2,%3,%4,%5,%6,%7,%8,%9,%10,%11,%12,%13,%14,%15,%16,%17,%18,%19,%20,%21,%22,%23,%24,%25,%26,%27,%28,%29,%30,%31,%32,%33,%34,%35,%36,%37,%38,%39,%40,%41,%42,%43,%44,%45,%46,%47,%48,%49,%50,%51}, {%52,%53,%54,%55}, %56, p, 1, 1, 0;}"
    : "+f"(d[0]),"+f"(d[1]),"+f"(d[2]),"+f"(d[3]),"+f"(d[4]),"+f"(d[5]),"+f"(d[6]),"+f"(d[7]),"+f"(d[8]),"+f"(d[9]),"+f"(d[10]),"+f"(d[11]),"+f"(d[12]),"+f"(d[13]),"+f"(d[14]),"+f"(d[15]),"+f"(d[16]),"+f"(d[17]),"+f"(d[18]),"+f"(d[19]),"+f"(d[20]),"+f"(d[21]),"+f"(d[22]),"+f"(d[23]),"+f"(d[24]),"+f"(d[25]),"+f"(d[26]),"+f"(d[27]),"+f"(d[28]),"+f"(d[29]),"+f"(d[30]),"+f"(d[31]),"+f"(d[32]),"+f"(d[33]),"+f"(d[34]),"+f"(d[35]),"+f"(d[36]),"+f"(d[37]),"+f"(d[38]),"+f"(d[39]),"+f"(d[40]),"+f"(d[41]),"+f"(d[42]),"+f"(d[43]),"+f"(d[44]),"+f"(d[45]),"+f"(d[46]),"+f"(d[47]),"+f"(d[48]),"+f"(d[49]),"+f"(d[50]),"+f"(d[51]) : "r"(a0), "r"(a1), "r"(a2), "r"(a3), "l"(db));
}
template<> __device__ __forceinline__ void wg_rs<96>(float (&d)[64], uint32_t a0, uint32_t a1, uint32_t a2, uint32_t a3, uint64_t db) {
  asm volatile("{.reg .pred p; setp.ne.b32 p, 1, 0; wgmma.mma_async.sync.aligned.m64n96k16.f32.bf16.bf16 {%0,%1,%2,%3,%4,%5,%6,%7,%8,%9,%10,%11,%12,%13,%14,%15,%16,%17,%18,%19,%20,%21,%22,%23,%24,%25,%26,%27,%28,%29,%30,%31,%32,%33,%34,%35,%36,%37,%38,%39,%40,%41,%42,%43,%44,%45,%46,%47}, {%48,%49,%50,%51}, %52, p, 1, 1, 0;}"
    : "+f"(d[0]),"+f"(d[1]),"+f"(d[2]),"+f"(d[3]),"+f"(d[4]),"+f"(d[5]),"+f"(d[6]),"+f"(d[7]),"+f"(d[8]),"+f"(d[9]),"+f"(d[10]),"+f"(d[11]),"+f"(d[12]),"+f"(d[13]),"+f"(d[14]),"+f"(d[15]),"+f"(d[16]),"+f"(d[17]),"+f"(d[18]),"+f"(d[19]),"+f"(d[20]),"+f"(d[21]),"+f"(d[22]),"+f"(d[23]),"+f"(d[24]),"+f"(d[25]),"+f"(d[26]),"+f"(d[27]),"+f"(d[28]),"+f"(d[29]),"+f"(d[30]),"+f"(d[31]),"+f"(d[32]),"+f"(d[33]),"+f"(d[34]),"+f"(d[35]),"+f"(d[36]),"+f"(d[37]),"+f"(d[38]),"+f"(d[39]),"+f"(d[40]),"+f"(d[41]),"+f"(d[42]),"+f"(d[43]),"+f"(d[44]),"+f"(d[45]),"+f"(d[46]),"+f"(d[47]) : "r"(a0), "r"(a1), "r"(a2), "r"(a3), "l"(db));
}
template<> __device__ __forceinline__ void wg_rs<88>(float (&d)[64], uint32_t a0, uint32_t a1, uint32_t a2, uint32_t a3, uint64_t db) {
  asm volatile("{.reg .pred p; setp.ne.b32 p, 1, 0; wgmma.mma_async.sync.aligned.m64n88k16.f32.bf16.bf16 {%0,%1,%2,%3,%4,%5,%6,%7,%8,%9,%10,%11,%12,%13,%14,%15,%16,%17,%18,%19,%20,%21,%22,%23,%24,%25,%26,%27,%28,%29,%30,%31,%32,%33,%34,%35,%36,%37,%38,%39,%40,%41,%42,%43}, {%44,%45,%46,%47}, %48, p, 1, 1, 0;}"
    : "+f"(d[0]),"+f"(d[1]),"+f"(d[2]),"+f"(d[3]),"+f"(d[4]),"+f"(d[5]),"+f"(d[6]),"+f"(d[7]),"+f"(d[8]),"+f"(d[9]),"+f"(d[10]),"+f"(d[11]),"+f"(d[12]),"+f"(d[13]),"+f"(d[14]),"+f"(d[15]),"+f"(d[16]),"+f"(d[17]),"+f"(d[18]),"+f"(d[19]),"+f"(d[20]),"+f"(d[21]),"+f"(d[22]),"+f"(d[23]),"+f"(d[24]),"+f"(d[25]),"+f"(d[26]),"+f"(d[27]),"+f"(d[28]),"+f"(d[29]),"+f"(d[30]),"+f"(d[31]),"+f"(d[32]),"+f"(d[33]),"+f"(d[34]),"+f"(d[35]),"+f"(d[36]),"+f"(d[37]),"+f"(d[38]),"+f"(d[39]),"+f"(d[40]),"+f"(d[41]),"+f"(d[42]),"+f"(d[43]) : "r"(a0), "r"(a1), "r"(a2), "r"(a3), "l"(db));
}
template<> __device__ __forceinline__ void wg_rs<80>(float (&d)[64], uint32_t a0, uint32_t a1, uint32_t a2, uint32_t a3, uint64_t db) {
  asm volatile("{.reg .pred p; setp.ne.b32 p, 1, 0; wgmma.mma_async.sync.aligned.m64n80k16.f32.bf16.bf16 {%0,%1,%2,%3,%4,%5,%6,%7,%8,%9,%10,%11,%12,%13,%14,%15,%16,%17,%18,%19,%20,%21,%22,%23,%24,%25,%26,%27,%28,%29,%30,%31,%32,%33,%34,%35,%36,%37,%38,%39}, {%40,%41,%42,%43}, %44, p, 1, 1, 0;}"
    : "+f"(d[0]),"+f"(d[1]),"+f"(d[2]),"+f"(d[3]),"+f"(d[4]),"+f"(d[5]),"+f"(d[6]),"+f"(d[7]),"+f"(d[8]),"+f"(d[9]),"+f"(d[10]),"+f"(d[11]),"+f"(d[12]),"+f"(d[13]),"+f"(d[14]),"+f"(d[15]),"+f"(d[16]),"+f"(d[17]),"+f"(d[18]),"+f"(d[19]),"+f"(d[20]),"+f"(d[21]),"+f"(d[22]),"+f"(d[23]),"+f"(d[24]),"+f"(d[25]),"+f"(d[26]),"+f"(d[27]),"+f"(d[28]),"+f"(d[29]),"+f"(d[30]),"+f"(d[31]),"+f"(d[32]),"+f"(d[33]),"+f"(d[34]),"+f"(d[35]),"+f"(d[36]),"+f"(d[37]),"+f"(d[38]),"+f"(d[39]) : "r"(a0), "r"(a1), "r"(a2), "r"(a3), "l"(db));
}
template<> __device__ __forceinline__ void wg_rs<72>(float (&d)[64], uint32_t a0, uint32_t a1, uint32_t a2, uint32_t a3, uint64_t db) {
  asm volatile("{.reg .pred p; setp.ne.b32 p, 1, 0; wgmma.mma_async.sync.aligned.m64n72k16.f32.bf16.bf16 {%0,%1,%2,%3,%4,%5,%6,%7,%8,%9,%10,%11,%12,%13,%14,%15,%16,%17,%18,%19,%20,%21,%22,%23,%24,%25,%26,%27,%28,%29,%30,%31,%32,%33,%34,%35}, {%36,%37,%38,%39}, %40, p, 1, 1, 0;}"
    : "+f"(d[0]),"+f"(d[1]),"+f"(d[2]),"+f"(d[3]),"+f"(d[4]),"+f"(d[5]),"+f"(d[6]),"+f"(d[7]),"+f"(d[8]),"+f"(d[9]),"+f"(d[10]),"+f"(d[11]),"+f"(d[12]),"+f"(d[13]),"+f"(d[14]),"+f"(d[15]),"+f"(d[16]),"+f"(d[17]),"+f"(d[18]),"+f"(d[19]),"+f"(d[20]),"+f"(d[21]),"+f"(d[22]),"+f"(d[23]),"+f"(d[24]),"+f"(d[25]),"+f"(d[26]),"+f"(d[27]),"+f"(d[28]),"+f"(d[29]),"+f"(d[30]),"+f"(d[31]),"+f"(d[32]),"+f"(d[33]),"+f"(d[34]),"+f"(d[35]) : "r"(a0), "r"(a1), "r"(a2), "r"(a3), "l"(db));
}
template<> __device__ __forceinline__ void wg_rs<64>(float (&d)[64], uint32_t a0, uint32_t a1, uint32_t a2, uint32_t a3, uint64_t db) {
  asm volatile("{.reg .pred p; setp.ne.b32 p, 1, 0; wgmma.mma_async.sync.aligned.m64n64k16.f32.bf16.bf16 {%0,%1,%2,%3,%4,%5,%6,%7,%8,%9,%10,%11,%12,%13,%14,%15,%16,%17,%18,%19,%20,%21,%22,%23,%24,%25,%26,%27,%28,%29,%30,%31}, {%32,%33,%34,%35}, %36, p, 1, 1, 0;}"
    : "+f"(d[0]),"+f"(d[1]),"+f"(d[2]),"+f"(d[3]),"+f"(d[4]),"+f"(d[5]),"+f"(d[6]),"+f"(d[7]),"+f"(d[8]),"+f"(d[9]),"+f"(d[10]),"+f"(d[11]),"+f"(d[12]),"+f"(d[13]),"+f"(d[14]),"+f"(d[15]),"+f"(d[16]),"+f"(d[17]),"+f"(d[18]),"+f"(d[19]),"+f"(d[20]),"+f"(d[21]),"+f"(d[22]),"+f"(d[23]),"+f"(d[24]),"+f"(d[25]),"+f"(d[26]),"+f"(d[27]),"+f"(d[28]),"+f"(d[29]),"+f"(d[30]),"+f"(d[31]) : "r"(a0), "r"(a1), "r"(a2), "r"(a3), "l"(db));
}
__device__ __forceinline__ void wg_rs_first(float (&d)[64], uint32_t a0, uint32_t a1, uint32_t a2, uint32_t a3, uint64_t db) {
  asm volatile("{.reg .pred p; setp.ne.b32 p, 0, 0; wgmma.mma_async.sync.aligned.m64n128k16.f32.bf16.bf16 {%0,%1,%2,%3,%4,%5,%6,%7,%8,%9,%10,%11,%12,%13,%14,%15,%16,%17,%18,%19,%20,%21,%22,%23,%24,%25,%26,%27,%28,%29,%30,%31,%32,%33,%34,%35,%36,%37,%38,%39,%40,%41,%42,%43,%44,%45,%46,%47,%48,%49,%50,%51,%52,%53,%54,%55,%56,%57,%58,%59,%60,%61,%62,%63}, {%64,%65,%66,%67}, %68, p, 1, 1, 0;}"
    : "=f"(d[0]),"=f"(d[1]),"=f"(d[2]),"=f"(d[3]),"=f"(d[4]),"=f"(d[5]),"=f"(d[6]),"=f"(d[7]),"=f"(d[8]),"=f"(d[9]),"=f"(d[10]),"=f"(d[11]),"=f"(d[12]),"=f"(d[13]),"=f"(d[14]),"=f"(d[15]),"=f"(d[16]),"=f"(d[17]),"=f"(d[18]),"=f"(d[19]),"=f"(d[20]),"=f"(d[21]),"=f"(d[22]),"=f"(d[23]),"=f"(d[24]),"=f"(d[25]),"=f"(d[26]),"=f"(d[27]),"=f"(d[28]),"=f"(d[29]),"=f"(d[30]),"=f"(d[31]),"=f"(d[32]),"=f"(d[33]),"=f"(d[34]),"=f"(d[35]),"=f"(d[36]),"=f"(d[37]),"=f"(d[38]),"=f"(d[39]),"=f"(d[40]),"=f"(d[41]),"=f"(d[42]),"=f"(d[43]),"=f"(d[44]),"=f"(d[45]),"=f"(d[46]),"=f"(d[47]),"=f"(d[48]),"=f"(d[49]),"=f"(d[50]),"=f"(d[51]),"=f"(d[52]),"=f"(d[53]),"=f"(d[54]),"=f"(d[55]),"=f"(d[56]),"=f"(d[57]),"=f"(d[58]),"=f"(d[59]),"=f"(d[60]),"=f"(d[61]),"=f"(d[62]),"=f"(d[63]) : "r"(a0), "r"(a1), "r"(a2), "r"(a3), "l"(db));
}
__device__ __forceinline__ void wg_tt128(float (&d)[64], uint64_t da, uint64_t db, int sc) {
  asm volatile("{.reg .pred p; setp.ne.b32 p, %66, 0; wgmma.mma_async.sync.aligned.m64n128k16.f32.bf16.bf16 {%0,%1,%2,%3,%4,%5,%6,%7,%8,%9,%10,%11,%12,%13,%14,%15,%16,%17,%18,%19,%20,%21,%22,%23,%24,%25,%26,%27,%28,%29,%30,%31,%32,%33,%34,%35,%36,%37,%38,%39,%40,%41,%42,%43,%44,%45,%46,%47,%48,%49,%50,%51,%52,%53,%54,%55,%56,%57,%58,%59,%60,%61,%62,%63}, %64, %65, p, 1, 1, 1, 1;}"
    : "+f"(d[0]),"+f"(d[1]),"+f"(d[2]),"+f"(d[3]),"+f"(d[4]),"+f"(d[5]),"+f"(d[6]),"+f"(d[7]),"+f"(d[8]),"+f"(d[9]),"+f"(d[10]),"+f"(d[11]),"+f"(d[12]),"+f"(d[13]),"+f"(d[14]),"+f"(d[15]),"+f"(d[16]),"+f"(d[17]),"+f"(d[18]),"+f"(d[19]),"+f"(d[20]),"+f"(d[21]),"+f"(d[22]),"+f"(d[23]),"+f"(d[24]),"+f"(d[25]),"+f"(d[26]),"+f"(d[27]),"+f"(d[28]),"+f"(d[29]),"+f"(d[30]),"+f"(d[31]),"+f"(d[32]),"+f"(d[33]),"+f"(d[34]),"+f"(d[35]),"+f"(d[36]),"+f"(d[37]),"+f"(d[38]),"+f"(d[39]),"+f"(d[40]),"+f"(d[41]),"+f"(d[42]),"+f"(d[43]),"+f"(d[44]),"+f"(d[45]),"+f"(d[46]),"+f"(d[47]),"+f"(d[48]),"+f"(d[49]),"+f"(d[50]),"+f"(d[51]),"+f"(d[52]),"+f"(d[53]),"+f"(d[54]),"+f"(d[55]),"+f"(d[56]),"+f"(d[57]),"+f"(d[58]),"+f"(d[59]),"+f"(d[60]),"+f"(d[61]),"+f"(d[62]),"+f"(d[63]) : "l"(da), "l"(db), "r"(sc));
}
__device__ __forceinline__ void wg_tt64(float (&d)[64], uint64_t da, uint64_t db, int sc) {
  asm volatile("{.reg .pred p; setp.ne.b32 p, %34, 0; wgmma.mma_async.sync.aligned.m64n64k16.f32.bf16.bf16 {%0,%1,%2,%3,%4,%5,%6,%7,%8,%9,%10,%11,%12,%13,%14,%15,%16,%17,%18,%19,%20,%21,%22,%23,%24,%25,%26,%27,%28,%29,%30,%31}, %32, %33, p, 1, 1, 1, 1;}"
    : "+f"(d[0]),"+f"(d[1]),"+f"(d[2]),"+f"(d[3]),"+f"(d[4]),"+f"(d[5]),"+f"(d[6]),"+f"(d[7]),"+f"(d[8]),"+f"(d[9]),"+f"(d[10]),"+f"(d[11]),"+f"(d[12]),"+f"(d[13]),"+f"(d[14]),"+f"(d[15]),"+f"(d[16]),"+f"(d[17]),"+f"(d[18]),"+f"(d[19]),"+f"(d[20]),"+f"(d[21]),"+f"(d[22]),"+f"(d[23]),"+f"(d[24]),"+f"(d[25]),"+f"(d[26]),"+f"(d[27]),"+f"(d[28]),"+f"(d[29]),"+f"(d[30]),"+f"(d[31]) : "l"(da), "l"(db), "r"(sc));
}
__device__ __forceinline__ void wg_tt32(float (&d)[64], uint64_t da, uint64_t db, int sc) {
  asm volatile("{.reg .pred p; setp.ne.b32 p, %18, 0; wgmma.mma_async.sync.aligned.m64n32k16.f32.bf16.bf16 {%0,%1,%2,%3,%4,%5,%6,%7,%8,%9,%10,%11,%12,%13,%14,%15}, %16, %17, p, 1, 1, 1, 1;}"
    : "+f"(d[0]),"+f"(d[1]),"+f"(d[2]),"+f"(d[3]),"+f"(d[4]),"+f"(d[5]),"+f"(d[6]),"+f"(d[7]),"+f"(d[8]),"+f"(d[9]),"+f"(d[10]),"+f"(d[11]),"+f"(d[12]),"+f"(d[13]),"+f"(d[14]),"+f"(d[15]) : "l"(da), "l"(db), "r"(sc));
}
__device__ __forceinline__ void wg_g1(float (&d)[88], uint64_t da, uint64_t db, int sc) {
  asm volatile("{.reg .pred p; setp.ne.b32 p, %90, 0; wgmma.mma_async.sync.aligned.m64n176k16.f32.bf16.bf16 {%0,%1,%2,%3,%4,%5,%6,%7,%8,%9,%10,%11,%12,%13,%14,%15,%16,%17,%18,%19,%20,%21,%22,%23,%24,%25,%26,%27,%28,%29,%30,%31,%32,%33,%34,%35,%36,%37,%38,%39,%40,%41,%42,%43,%44,%45,%46,%47,%48,%49,%50,%51,%52,%53,%54,%55,%56,%57,%58,%59,%60,%61,%62,%63,%64,%65,%66,%67,%68,%69,%70,%71,%72,%73,%74,%75,%76,%77,%78,%79,%80,%81,%82,%83,%84,%85,%86,%87}, %88, %89, p, 1, 1, 1, 0;}"
    : "+f"(d[0]),"+f"(d[1]),"+f"(d[2]),"+f"(d[3]),"+f"(d[4]),"+f"(d[5]),"+f"(d[6]),"+f"(d[7]),"+f"(d[8]),"+f"(d[9]),"+f"(d[10]),"+f"(d[11]),"+f"(d[12]),"+f"(d[13]),"+f"(d[14]),"+f"(d[15]),"+f"(d[16]),"+f"(d[17]),"+f"(d[18]),"+f"(d[19]),"+f"(d[20]),"+f"(d[21]),"+f"(d[22]),"+f"(d[23]),"+f"(d[24]),"+f"(d[25]),"+f"(d[26]),"+f"(d[27]),"+f"(d[28]),"+f"(d[29]),"+f"(d[30]),"+f"(d[31]),"+f"(d[32]),"+f"(d[33]),"+f"(d[34]),"+f"(d[35]),"+f"(d[36]),"+f"(d[37]),"+f"(d[38]),"+f"(d[39]),"+f"(d[40]),"+f"(d[41]),"+f"(d[42]),"+f"(d[43]),"+f"(d[44]),"+f"(d[45]),"+f"(d[46]),"+f"(d[47]),"+f"(d[48]),"+f"(d[49]),"+f"(d[50]),"+f"(d[51]),"+f"(d[52]),"+f"(d[53]),"+f"(d[54]),"+f"(d[55]),"+f"(d[56]),"+f"(d[57]),"+f"(d[58]),"+f"(d[59]),"+f"(d[60]),"+f"(d[61]),"+f"(d[62]),"+f"(d[63]),"+f"(d[64]),"+f"(d[65]),"+f"(d[66]),"+f"(d[67]),"+f"(d[68]),"+f"(d[69]),"+f"(d[70]),"+f"(d[71]),"+f"(d[72]),"+f"(d[73]),"+f"(d[74]),"+f"(d[75]),"+f"(d[76]),"+f"(d[77]),"+f"(d[78]),"+f"(d[79]),"+f"(d[80]),"+f"(d[81]),"+f"(d[82]),"+f"(d[83]),"+f"(d[84]),"+f"(d[85]),"+f"(d[86]),"+f"(d[87]) : "l"(da), "l"(db), "r"(sc));
}

struct Params { const __nv_bfloat16 *x, *logA, *Aim, *Cr, *Ci, *logdt, *Dskip, *Wg, *Wu, *Wd; __nv_bfloat16* out; uint4* xnT; float2* st; uint2* S; unsigned* flags; };
struct Maps { CUtensorMap x[2], xo, wg, wu, wd, hst[2], hld, xt, sld; };

__device__ __forceinline__ void conv_channel(uint32_t cb, int w, int lane, uint32_t (&res)[8], uint32_t sig, int sidx) {
    const int q = lane & 3, g = lane >> 2, gam = g >> 2;
    float acc[64];
    uint2 a[17][2];
    const uint32_t t0 = cb + CH_T + (uint32_t)(14 + 4 * w + (g & 3) - 2 * q) * 280u + gam * 8;
#define LDA(s0, s1) _Pragma("unroll") for (int s = s0; s < s1; s++) { a[s][0] = lds64(t0 + s * 16); a[s][1] = lds64(t0 - 8 * 280 + s * 16); }
#define CT(N, s) wg_rs<N>(acc, a[s][0].x, a[s][0].y, a[s][1].x, a[s][1].y, dU + 4 * (s))
    const uint64_t dU = mkdesc(cb + CH_U, UPLANE, 128, 0);
    LDA(0, 17)
    if (sig) { fence_async_smem(); mbar_arrive(sig); }
    WG_FENCE();
    if (w == 0) STAMP2(52 + 3 * sidx);
    wg_rs_first(acc, a[0][0].x, a[0][0].y, a[0][1].x, a[0][1].y, dU);
    CT(128, 1); CT(120, 2); CT(120, 3); CT(112, 4); CT(112, 5); CT(104, 6); CT(104, 7); CT(96, 8);
    CT(96, 9); CT(88, 10); CT(88, 11); CT(80, 12); CT(80, 13); CT(72, 14); CT(72, 15); CT(64, 16);
#undef CT
#undef LDA
    wg_tt64(acc, mkdesc(cb + CH_A3, 128, 512, 0), mkdesc(cb + CH_B3, 384, 32, 0), 1);
    wg_tt32(acc, mkdesc(cb + CH_A3 + 256, 128, 512, 0), mkdesc(cb + CH_B3 + 128, 384, 32, 0), 1);
    WG_COMMIT();
    if (w == 0) STAMP2(53 + 3 * sidx);
    WG_WAIT(0);
    fence_acc(acc);
    if (w == 0) STAMP2(54 + 3 * sidx);
    const int src1 = (lane & ~3) | ((q + 1) & 3);
    float E[16][2];
    #pragma unroll
    for (int j = 0; j < 16; j++) {
        const float nxt = (j < 15) ? acc[4 * (j + 1) + 2] : 0.f;
        const float sup = (q == 0) ? nxt : acc[4 * j + 2];
        const float v = __shfl_sync(0xffffffffu, sup, src1);
        E[j][0] = acc[4 * j] + acc[4 * j + 3];
        E[j][1] = acc[4 * j + 1] + v;
    }
    const int src2 = gam ? ((lane & 12) | ((q + 3) & 3)) : (16 | (lane & 12) | ((q + 1) & 3));
    const bool c1 = gam && q != 0, c2 = gam && q == 0;
    #pragma unroll
    for (int a2 = 0; a2 < 8; a2++) {
        float y[2];
        #pragma unroll
        for (int e = 0; e < 2; e++) {
            const float sup = c1 ? E[2 * a2][e] : E[2 * a2 + 1][e];
            const float nxt = (a2 < 7) ? E[2 * a2 + 2][e] : 0.f;
            const float keep = c2 ? nxt : (c1 ? E[2 * a2 + 1][e] : E[2 * a2][e]);
            y[e] = keep + __shfl_sync(0xffffffffu, sup, src2);
        }
        res[a2] = pack2(y[1], y[0]);
    }
}

__device__ __forceinline__ void consumer(uint32_t sb, int warp, const Params& P, const Maps& M) {
    const int V = warp >> 2, w = warp & 3, lane = threadIdx.x & 31, q = lane & 3, g = lane >> 2;
    const int c = blockIdx.x;
    const uint32_t bars = sb + OFF_BAR, xb = sb + OFF_X + V * 2 * XBUF;
    {
        float ag[88], au[88];
        define_acc(ag); define_acc(au);
        mbar_wait(bars + 8 * B_FULLW, 0);
        mbar_wait(bars + 8 * (B_FULLX + 2 * V), 0);
        #pragma unroll 1
        for (int st = 0; st < 8; st++) {
            uint64_t dG = mkdesc(sb + OFF_W + (st & 3) * 16384, 0, 1024, 1), dX = mkdesc(xb + (st & 1) * XBUF, 16, 1024, 1);
            uint32_t sig = lane == 0 && (V ? st < 6 : st > 0);
            asm volatile("" : "+l"(dG), "+l"(dX), "+r"(sig) :: "memory");
            if (V ? st < 7 : st > 1) mbar_wait(bars + 8 * (B_TURN + V), st & 1);
            STAMP(40 + 8 * V + st);
            WG_FENCE();
            #pragma unroll
            for (int k = 0; k < 4; k++) {
                if (k == SIGK) mbar_arrive_if(bars + 8 * (B_TURN + 1 - V), sig);
                wg_g1(ag, dG + k * 128, dX + k * 2, k ? 1 : st);
                wg_g1(au, dG + 512 + k * 128, dX + k * 2, k ? 1 : st);
            }
            WG_COMMIT();
            if (st == 6 * V) {
                mbar_wait(bars + 8 * (B_FULLW + ((st + 1) & 3)), V);
                mbar_wait(bars + 8 * (B_FULLX + 2 * V + 1), V);
            } else {
                WG_WAIT(1);
                mbar_arrive_if(bars + 8 * (B_EMPTYW + 2 * V), lane == 0 && st == 6 * V + 1);
                mbar_arrive_if(bars + 8 * (B_EMPTYX + 2 * V), lane == 0 && st == 6 * V + 1);
                WG_WAIT(0);
                mbar_arrive_if(bars + 8 * (B_EMPTYW + (st & 3)), lane == 0);
                mbar_arrive_if(bars + 8 * (B_EMPTYX + 2 * V + (st & 1)), lane == 0);
                if (st < 7) {
                    mbar_wait(bars + 8 * (B_FULLW + ((st + 1) & 3)), (st + 1) >> 2);
                    mbar_wait(bars + 8 * (B_FULLX + 2 * V + ((st + 1) & 1)), ((st + 1) >> 1) & 1);
                }
            }
        }
        WG_WAIT(0);
        fence_acc(ag); fence_acc(au);
        STAMP(8 * V + 1);
        float cg0 = ag[84], cg1 = ag[86], cu0 = au[84], cu1 = au[86];
        const uint32_t ca = sb + OFF_CSUM + (8 * w + g) * 16;
        if (V == 0) { sts128(ca, FU(cg0), FU(cg1), FU(cu0), FU(cu1)); mbar_arrive(bars + 8 * B_CS); }
        else { mbar_wait(bars + 8 * B_CS, 0); const uint4 t = lds128(ca); cg0 = UF(t.x); cg1 = UF(t.y); cu0 = UF(t.z); cu1 = UF(t.w); }
        mbar_wait(bars + 8 * B_STATS, 0);
        mbar_wait(bars + 8 * (B_EMPTYX + 2 * V), 1);
        STAMP(13 + V);
        const uint32_t hs = xb + (2 * w + ((lane >> 3) & 1)) * (2688 + 128 * V) + (lane >> 4) * 128 + (lane & 7) * 16;
        const uint32_t sa = sb + OFF_ST + (168 * V + 2 * q) * 8;
        uint4 sq[22];
        #pragma unroll
        for (int j = 0; j < 3; j++) sq[j] = lds128(sa + j * 64);
        #pragma unroll
        for (int j = 0; j < 22; j += 2) {
            uint32_t o[4];
            #pragma unroll
            for (int jj = 0; jj < 2; jj++) {
                const uint4 sv = sq[j + jj];
                float hv[4];
                #pragma unroll
                for (int i = 0; i < 4; i++) {
                    const float m = UF((i & 1) ? sv.z : sv.x);
                    const float gh = fmaf(-m, (i & 2) ? cg1 : cg0, ag[4 * (j + jj) + i]) * UF((i & 1) ? sv.w : sv.y);
                    const float p = gh * fmaf(-m, (i & 2) ? cu1 : cu0, au[4 * (j + jj) + i]);
                    hv[i] = fmaf(p, tanh_fast(gh), p);
                }
                o[2 * jj] = pack2(hv[0], hv[1]); o[2 * jj + 1] = pack2(hv[2], hv[3]);
            }
            #pragma unroll
            for (int k = (j ? 3 + 3 * j / 2 : 3); k < 6 + 3 * j / 2 && k < 22; k++) sq[k] = lds128(sa + k * 64);
            uint32_t ad = hs + j * 128;
            if (j == 20 && V == 0 && lane >= 16) ad = xb + 21504 + (lane & 7) * 16;
            stsm4(ad, o[0], o[1], o[2], o[3]);
        }
        if (c >= 128 || V) { fence_async_smem(); mbar_arrive(bars + 8 * (B_EPI + V)); }
        STAMP(8 * V + 2);
    }
    if (c >= 128) return;
    {
        mbar_wait(bars + 8 * B_CONV, 0);
        uint32_t r0[8], r1[8];
        #pragma unroll
        for (int i = 0; i < 8; i++) asm volatile("" : "=r"(r1[i]));
        #pragma unroll 1
        for (int e = 0; e < 2; e++) {
            #pragma unroll
            for (int i = 0; i < 8; i++) r0[i] = r1[i];
            conv_channel(sb + OFF_CONV + (2 * V + e) * CH_STRIDE, w, lane, r1, (e | V) ? 0 : bars + 8 * B_EPI, 2 * V + e);
            if (e == 0) STAMP(8 * V + 3);
        }
        const int gam = g >> 2, qq = gam ? ((q + 3) & 3) : q;
        const uint32_t sp = sb + OFF_CONV + V * OFF_SST + ((63 - 4 * gam - qq) * 16 + 4 * (w ^ (3 - qq)) + (g & 3)) * 8;
        bar_sync(3 + V);
        #pragma unroll
        for (int a2 = 0; a2 < 8; a2++) sts64(sp - a2 * 1024, r0[a2], r1[a2]);
        fence_async_smem();
        mbar_arrive(bars + 8 * (B_SIG + V));
        STAMP(8 * V + 4);
    }
    if (V == 1) return;
    {
        const int tau = c >> 2, dg = c & 3;
        const uint32_t row = 8 * (w & 1) + 32 * (w >> 1);
        float acc[64];
        define_acc(acc);
        const float rr0 = __ldcg(&P.st[64 * tau + row + g].y), rr1 = __ldcg(&P.st[64 * tau + row + g + 16].y);
        mbar_wait(bars + 8 * B_FULLD, 0);
        STAMP(5);
        uint64_t dB = mkdesc(sb + wd_slot(0), 8192, 1024, 1), dA = mkdesc(sb + h_slot(0), 1024, 128, 0);
        int sd = 0; uint32_t np = 0;
        #pragma unroll 1
        for (int st = 0; st < 21; st++) {
            WG_FENCE();
            wg_tt128(acc, dA, dB, st);
            wg_tt128(acc, dA + 128, dB + 128, 1);
            wg_tt128(acc, dA + 256, dB + 256, 1);
            wg_tt128(acc, dA + 384, dB + 384, 1);
            WG_COMMIT();
            uint32_t ro = bars + 8 * (B_EMPTYD + (sd ? sd - 1 : 6)), m = lane == 0 && st > 0, ok;
            if (++sd == 7) { sd = 0; np ^= 1; }
            const uint32_t nb = bars + 8 * (B_FULLD + sd);
            dB = mkdesc(sb + wd_slot(sd), 8192, 1024, 1); dA = mkdesc(sb + h_slot(sd), 1024, 128, 0);
            asm volatile("{.reg .pred p; mbarrier.test_wait.parity.shared::cta.b64 p, [%5], %6; vote.sync.all.pred p, p, -1; selp.u32 %0, 1, 0, p;}"
                : "=r"(ok), "+l"(dA), "+l"(dB), "+r"(ro), "+r"(m) : "r"(nb), "r"(np) : "memory");
            WG_WAIT(1);
            mbar_arrive_if(ro, m);
            if (!ok) mbar_wait(nb, np);
            if (w == 0) STAMP2(20 + st);
        }
        WG_FENCE();
        wg_tt128(acc, dA, dB, 1);
        wg_tt128(acc, dA + 128, dB + 128, 1);
        WG_COMMIT();
        mbar_wait(bars + 8 * B_XO, 0);
        const uint32_t xo = sb + OFF_XO + (row + (lane & 7) + 16 * ((lane >> 3) & 1)) * 128;
        const uint32_t so = sb + OFF_SI + (w >> 1) * 8192 + q * 256 + (g & 1) * 8;
        const uint32_t sx = (4 * (w & 1) + (g >> 1)) ^ (2 * q) ^ (2 * ((2 * tau + (w >> 1)) & 3));
        uint32_t xr[8][4];
        uint2 sv[16];
        #pragma unroll
        for (int j = 0; j < 16; j += 2) {
            ldsm4(xr[j >> 1], xo + (j >> 3) * 8192 + ((((j & 7) + (lane >> 4)) ^ (lane & 7)) << 4));
            sv[j] = lds64(so + j * 512 + (sx << 4));
            sv[j + 1] = lds64(so + j * 512 + 128 + ((sx ^ 1) << 4));
        }
        WG_WAIT(0);
        fence_acc(acc);
        STAMP(6);
        #pragma unroll
        for (int j = 0; j < 16; j += 2) {
            #pragma unroll
            for (int i = 0; i < 4; i++) {
                const int jj = j + (i >> 1), hh = i & 1;
                const float f0 = acc[4 * jj + 2 * hh] * (hh ? rr1 : rr0), f1 = acc[4 * jj + 2 * hh + 1] * (hh ? rr1 : rr0);
                const uint32_t G = pack2(fmaf(f0, tanh_fast(f0), f0), fmaf(f1, tanh_fast(f1), f1));
                const uint32_t s2 = __byte_perm(sv[jj].x, sv[jj].y, hh ? 0x7632 : 0x5410);
                asm("fma.rn.bf16x2 %0, %1, %2, %0;" : "+r"(xr[j >> 1][i]) : "r"(s2), "r"(G));
            }
            stsm4(xo + (j >> 3) * 8192 + ((((j & 7) + (lane >> 4)) ^ (lane & 7)) << 4), xr[j >> 1][0], xr[j >> 1][1], xr[j >> 1][2], xr[j >> 1][3]);
        }
        __syncwarp();
        {
            const uint32_t rr = row + ((lane >> 4) << 4), la = sb + OFF_XO + rr * 128 + ((lane >> 3) & 1) * 8192;
            uint4* dst = (uint4*)(P.out + (64 * tau + rr) * DM + 128 * dg) + (lane & 15);
            uint4 v[8];
            #pragma unroll
            for (int i = 0; i < 8; i++) v[i] = lds128(la + i * 128 + (((lane & 7) ^ i) << 4));
            #pragma unroll
            for (int i = 0; i < 8; i++) dst[i * 64] = v[i];
        }
        STAMP(7); GSTAMP(23);
    }
}

__device__ __forceinline__ float2 cexp_p(float re2, float im, float p) {
    float sn, cs;
    const float mag = ex2(re2 * p), th = im * p;
    asm("sin.approx.ftz.f32 %0, %1;" : "=f"(sn) : "f"(th));
    asm("cos.approx.ftz.f32 %0, %1;" : "=f"(cs) : "f"(th));
    return make_float2(mag * cs, mag * sn);
}
struct SsmRaw { unsigned short la, ai, cr, ci, ldt, dsk; };
__device__ __forceinline__ unsigned short ldu16(const void* p) { unsigned short v; asm volatile("ld.global.nc.u16 %0, [%1];" : "=h"(v) : "l"(p)); return v; }
__device__ __forceinline__ float2 cmul(float2 a, float2 b) { return make_float2(fmaf(a.x, b.x, -a.y * b.y), fmaf(a.x, b.y, a.y * b.x)); }
__device__ __forceinline__ float2 csqr(float2 a) { const float t = a.x * a.y; return make_float2(fmaf(a.x, a.x, -a.y * a.y), t + t); }
__device__ __forceinline__ void mma16816(float (&d)[4], const uint32_t (&a)[4], uint32_t b0, uint32_t b1) {
    asm volatile("mma.sync.aligned.m16n8k16.row.col.f32.bf16.bf16.f32 {%0,%1,%2,%3}, {%4,%5,%6,%7}, {%8,%9}, {%0,%1,%2,%3};"
        : "+f"(d[0]), "+f"(d[1]), "+f"(d[2]), "+f"(d[3]) : "r"(a[0]), "r"(a[1]), "r"(a[2]), "r"(a[3]), "r"(b0), "r"(b1));
}

__device__ __forceinline__ void layer_norm(uint32_t sb, uint32_t cb, int w, int lane) {
    const uint32_t bars = sb + OFF_BAR;
    mbar_wait(bars + 8 * (B_LNX + w), 0);
    STAMP(34);
    {
        const uint32_t r0 = cb + CH_LN + (w & 1) * 64 + (lane >> 3) * 1040, ra = r0 + (lane & 7) * 16;
        const float pv = bf_lo(FU(ldsf(r0)));
        float s0 = 0.f, s1 = 0.f, a0 = 0.f, a1 = 0.f;
        #pragma unroll 1
        for (int k = 0; k < 1024; k += 512) {
            uint32_t v[16];
            #pragma unroll
            for (int j = 0; j < 4; j++) *(uint4*)&v[4 * j] = lds128(ra + k + 128 * j);
            #pragma unroll
            for (int i = 0; i < 16; i++) { const float t0 = bf_lo(v[i]) - pv, t1 = bf_hi(v[i]) - pv; s0 += t0; s1 += t1; a0 = fmaf(t0, t0, a0); a1 = fmaf(t1, t1, a1); }
        }
        s0 += s1; a0 += a1;
        #pragma unroll
        for (int o = 4; o; o >>= 1) { s0 += __shfl_xor_sync(0xffffffffu, s0, o); a0 += __shfl_xor_sync(0xffffffffu, a0, o); }
        s0 *= 1.f / DM;
        float sd, ri;
        asm("sqrt.approx.ftz.f32 %0, %1;" : "=f"(sd) : "f"(bf_round(bf_round(fmaxf(fmaf(-s0, s0, a0 * (1.f / DM)), 0.f)) + 1e-5f)));
        asm("rcp.approx.ftz.f32 %0, %1;" : "=f"(ri) : "f"(bf_round(sd)));
        if ((lane & 7) == 0) sts64(sb + OFF_CSUM + (w + 4 * (lane >> 3)) * 8, FU(bf_round(pv + s0)), FU(0.5f * ri));
    }
    STAMP(62);
    bar_sync(2);
    const int r = 4 * ((lane & 7) >> 1) + (lane & 1) + 2 * ((lane >> 3) & 1);
    const uint32_t ad = sb + OFF_CONV + (r & 3) * CH_STRIDE + CH_LN + (r & 1) * 64 + (r >> 2) * 1040 + (16 * w + (lane >> 4)) * 16;
    const uint4 sa = lds128(sb + OFF_CSUM + (lane & 3) * 32), sc = lds128(sb + OFF_CSUM + (lane & 3) * 32 + 16);
    const uint32_t m2[2] = {__byte_perm(sa.x, sa.z, 0x7632), __byte_perm(sc.x, sc.z, 0x7632)};
    const float ri[4] = {2.f * UF(sa.y), 2.f * UF(sa.w), 2.f * UF(sc.y), 2.f * UF(sc.w)};
    #pragma unroll 1
    for (int i = 0; i < 8; i += 4) {
        uint32_t v[4][4];
        #pragma unroll
        for (int j = 0; j < 4; j++)
            asm volatile("ldmatrix.sync.aligned.m8n8.x4.trans.shared.b16 {%0,%1,%2,%3}, [%4];" : "=r"(v[j][0]), "=r"(v[j][1]), "=r"(v[j][2]), "=r"(v[j][3]) : "r"(ad + 32 * (i + j)) : "memory");
        #pragma unroll
        for (int j = 0; j < 4; j++) {
            #pragma unroll
            for (int k = 0; k < 4; k++) {
                uint32_t dv; asm("sub.rn.bf16x2 %0, %1, %2;" : "=r"(dv) : "r"(v[j][k]), "r"(m2[k & 1]));
                v[j][k] = pack2(bf_lo(dv) * ri[2 * (k & 1)], bf_hi(dv) * ri[2 * (k & 1) + 1]);
            }
            sts64(cb + CH_LNT + lane * 8 + (i + j) * 512, v[j][0], v[j][1]); sts64(cb + CH_LNT + lane * 8 + (i + j) * 512 + 256, v[j][2], v[j][3]);
        }
    }
    fence_async_smem();
    mbar_arrive(bars + 8 * B_LN);
    STAMP(16);
}

__device__ __forceinline__ void kernel_gen(uint32_t sb, uint32_t fs, int lane, const SsmRaw& raw, float (&dacc)[2][3][4], const Params& P, int warp) {
    const float dt = bf_round(ex2(bf_lo(raw.ldt) * 1.4426950408889634f));
    const float re2 = bf_round(ex2(bf_lo(raw.la) * 1.4426950408889634f)) * dt * -1.4426950408889634f, im = bf_lo(raw.ai) * dt;
    const float2 C = make_float2(bf_lo(raw.cr) * (dt + dt), bf_lo(raw.ci) * -(dt + dt));
    STAMP(56);
    if (__any_sync(0xffffffffu, re2 != 1.f) && elect_one()) {
        const int c = blockIdx.x, w = warp & 3;
        if ((warp >> 2) == 2) {
            const uint32_t bar = sb + OFF_BAR + 8 * (B_LNX + w);
            mbar_expect(bar, 4096);
            #pragma unroll
            for (int i = 0; i < 4; i++)
                bulk_load(sb + OFF_CONV + w * CH_STRIDE + CH_LN + (w & 1) * 64 + i * 1040,
                          P.x + (16 * (c & ~1) + 8 * (c & 1) + 16 + w + 4 * (i & 1) - 8 * (i & 2)) * DM, 1024, bar);
        } else if (warp < 2)
            asm volatile("cp.async.bulk.prefetch.L2.global [%0], %1;" :: "l"((const char*)(warp ? P.Wu : P.Wg) + 256 * FF * 2 + c * 5504), "r"(5504) : "memory");
    }
    const float2 y1 = cexp_p(re2, -im, 1.f), y256 = cexp_p(re2, -im, 256.f), z64 = cexp_p(re2, im, 64.f);
    const uint32_t fm = fs + (lane >> 3) * 144 + (lane & 7) * 16;
#define PK(v) pack2((v).x, (v).y)
    const float2 y2 = csqr(y1), y4 = csqr(y2), y8 = csqr(y4);
    const float2 l1 = cmul(C, y1), l2 = cmul(C, y2), l3 = cmul(l1, y2);
    stsm4(fm, PK(C), PK(l1), PK(l2), PK(l3));
    stsm4(fm + 4 * 144, PK(cmul(C, y4)), PK(cmul(l1, y4)), PK(cmul(l2, y4)), PK(cmul(l3, y4)));
    const float2 t0 = cmul(C, y256), t1 = cmul(t0, y256), t2 = cmul(t1, y256), t3_ = cmul(t2, y256);
    const float2 u1 = cmul(t0, y2), u2 = cmul(u1, y2), u3 = cmul(u2, y2);
    stsm4(fm + 8 * 144, PK(t0), PK(u1), PK(u2), PK(u3));
    stsm4(fm + 12 * 144, PK(t1), PK(cmul(t1, y4)), PK(t2), PK(cmul(t2, y4)));
    const float2 v0 = cmul(t3_, y8), v1 = cmul(v0, y256), v2 = cmul(v1, y256), v3 = cmul(v2, y256);
    stsm4(fm + 16 * 144, PK(v0), PK(v1), PK(v2), PK(v3));
    stsf(fs + lane * 4 + 20 * 144, UF(PK(t3_)));
    STAMP(57);
    const uint32_t ldb = fs + (lane & 7) * 144 + ((lane >> 3) & 1) * 16 + (lane >> 4) * 8 * 144;
    const float p8 = (float)(2 * (lane & 28));
    __syncwarp();
    #pragma unroll 1
    for (int ks = 0; ks < 4; ks++) {
        uint32_t b01[4], b2[2], a0[4], a1[4];
        ldsm4(b01, ldb + ks * 32);
        asm volatile("ldmatrix.sync.aligned.m8n8.x2.shared.b16 {%0,%1}, [%2];" : "=r"(b2[0]), "=r"(b2[1]) : "r"(ldb + 16 * 144 + ks * 32) : "memory");
        #pragma unroll
        for (int mh = 0; mh < 2; mh++) {
            const int src = 8 * ks + 4 * mh + (lane & 3);
            const float2 z = make_float2(__shfl_sync(0xffffffffu, z64.x, src), __shfl_sync(0xffffffffu, z64.y, src));
            const float2 R0 = cexp_p(__shfl_sync(0xffffffffu, re2, src), __shfl_sync(0xffffffffu, im, src), p8);
            const float2 R1 = cmul(R0, z), R2 = cmul(R1, z), R3 = cmul(R2, z);
            a0[2 * mh] = PK(R0); a0[2 * mh + 1] = PK(R1); a1[2 * mh] = PK(R2); a1[2 * mh + 1] = PK(R3);
        }
        mma16816(dacc[0][0], a0, b01[0], b01[1]); mma16816(dacc[1][0], a1, b01[0], b01[1]);
        mma16816(dacc[0][1], a0, b01[2], b01[3]); mma16816(dacc[1][1], a1, b01[2], b01[3]);
        mma16816(dacc[0][2], a0, b2[0], b2[1]);   mma16816(dacc[1][2], a1, b2[0], b2[1]);
    }
#undef PK
    STAMP(58);
}

__device__ __forceinline__ void aux_role(uint32_t sb, int w, float (&dacc)[2][3][4], float dsk) {
    const int lane = threadIdx.x & 31, q = lane & 3, g = lane >> 2;
    const int c = blockIdx.x;
    const uint32_t bars = sb + OFF_BAR;
    if (c >= 128) { mbar_arrive(bars + 8 * B_LN); return; }
    {
        const uint32_t cb = sb + OFF_CONV + w * CH_STRIDE;
        layer_norm(sb, cb, w, lane);
        {
            uint4 v[2][3];
            #pragma unroll
            for (int i = 0; i < 3; i++) v[0][i] = lds128(cb + CH_PART + lane * 16 + i * 512);
            #pragma unroll
            for (int k = 0; k < 6; k++) {
                #pragma unroll
                for (int i = 0; i < 3; i++) if (k < 5) v[(k + 1) & 1][i] = lds128(cb + CH_PART + lane * 16 + (k + 1) * 1536 + i * 512);
                #pragma unroll
                for (int i = 0; i < 3; i++) {
                    float* d = &dacc[0][0][0] + 12 * (k & 1) + 4 * i;
                    d[0] += UF(v[k & 1][i].x); d[1] += UF(v[k & 1][i].y); d[2] += UF(v[k & 1][i].z); d[3] += UF(v[k & 1][i].w);
                }
            }
        }
        __syncwarp();
        STAMP(18);
        const uint32_t sF = cb + CH_A3, sG = cb + CH_G;
        if (lane == 0) dacc[0][0][0] += dsk;
        if (lane < 10) sts128(sG + 128 + (lane & 1) * 208 + (lane >> 1) * 16, 0, 0, 0, 0);
        const uint32_t f0 = sF + (8 * g + 2 * q) * 4, f1 = sF + ((q < 2) ? 256 + 4 * g + 2 * q : 256 + 2 * g + 64 * q) * 4, st1 = (q < 2) ? 128 : 64;
        const uint32_t ga = sG + ((g & 1) ? 0 : 208) + (63 - (g >> 1) - 32 * q) * 2;
        #pragma unroll
        for (int i = 0; i < 4; i++) {
            const int mu = i >> 1, hh = i & 1;
            sts64(f0 + i * 256, FU(dacc[mu][0][2 * hh]), FU(dacc[mu][0][2 * hh + 1]));
            sts64(f1 + i * st1, FU(dacc[mu][1][2 * hh]), FU(dacc[mu][1][2 * hh + 1]));
            const uint32_t pk = pack2(dacc[mu][2][2 * hh], dacc[mu][2][2 * hh + 1]);
            if (q < 2) { sts16(ga - 8 * i, pk & 0xffff); sts16(ga - 8 * i - 32, pk >> 16); }
        }
        if (lane == 2) stsf(sF + 2048, dacc[0][2][0]);
        STAMP(19);
        bar_sync(2);
    }
    const int u = min(lane, 30) - 15, r2 = (u + ((u >> 1) & 1)) >> 1, r4 = (u + 1 + ((u >> 2) & 1)) >> 2, xt = 1024 + 16 * w + u;
    const uint32_t o0 = CH_A3 + 4 * (w == 0 ? u : w == 1 ? 256 + r2 : 256 + 64 * w + r4), ost = w == 0 ? 64 : w == 1 ? 32 : 16;
    const uint32_t oa0 = u >= 0 || w == 3 ? o0 : CH_A3 + 4 * (w == 1 ? 256 + u : w == 2 ? 384 + r2 : 0);
    const uint32_t ot = CH_A3 + 4 * min(512, 256 + ((xt + 1 + ((xt >> 2) & 1)) >> 2));
    const int kap = (lane >> 4) * 8 + ((lane >> 1) & 7), gam = lane & 1, hh = w >> 1, wp = w & 1;
    const uint32_t oa = CH_U + wp * UPLANE + (127 - 4 * kap - 2 * gam - hh) * 16;
    const uint32_t ob = CH_U + (wp ^ 1) * UPLANE + (128 - wp - 4 * kap - 2 * gam - hh) * 16;
    const uint32_t od = CH_A3 + (4 * wp + hh) * 512 + (kap >> 3) * 256 + (kap & 7) * 16 + gam * 8;
    const int tid = threadIdx.x & 127;
    const uint32_t og = CH_G + (tid >= 24) * 16 + min(tid, 47) * 8, cend = sb + OFF_CONV + 3 * CH_STRIDE;
    {
        float nx[17]; uint2 n0, n1;
#define LDT(b) nx[0] = ldsf((b) + oa0); nx[16] = ldsf((b) + ot); _Pragma("unroll") for (int s = 1; s < 16; s++) nx[s] = ldsf((b) + o0 + s * ost); n0 = lds64((b) + og); n1 = lds64((b) + og + 8)
        LDT(sb + OFF_CONV);
        #pragma unroll 1
        for (uint32_t cb = sb + OFF_CONV; cb <= cend; cb += CH_STRIDE) {
            float kv[17];
            #pragma unroll
            for (int s = 0; s < 17; s++) kv[s] = nx[s];
            if (tid < 48) sts128(cb + CH_B3 + tid * 16, n0.x, n0.y, n1.x, n1.y);
            LDT(min(cb + CH_STRIDE, cend));
            if (u < 0 && w == 0) kv[0] = 0.f;
            if (xt > 1028) kv[16] = 0.f;
            uint32_t o[17];
            #pragma unroll
            for (int s = 0; s < 17; s++) o[s] = pack2(kv[s], __shfl_up_sync(0xffffffffu, kv[s], 1));
            if (lane > 0 && lane < 31) {
                const uint32_t ta = cb + CH_T + (lane - 1) * 280;
                #pragma unroll
                for (int s2 = 0; s2 < 8; s2++) sts64(ta + 64 * w + s2 * 8, o[2 * s2], o[2 * s2 + 1]);
                stsf(ta + 256 + 4 * w, UF(o[16]));
            }
        }
#undef LDT
    }
    STAMP(61);
    mbar_wait(bars + 8 * B_U, 0);
    if (lane < 8) sts128(sb + OFF_CONV + w * CH_STRIDE + CH_U + 2048 + (lane & 4) * (UPLANE / 4) + (lane & 3) * 16, 0, 0, 0, 0);
    bar_sync(2);
    STAMP(17);
    uint2 n0 = lds64(sb + OFF_CONV + ob + 24), n3 = lds64(sb + OFF_CONV + oa);
    uint4 n1 = lds128(sb + OFF_CONV + oa + 16), n2 = lds128(sb + OFF_CONV + ob);
    #pragma unroll 1
    for (uint32_t cb = sb + OFF_CONV; cb <= cend; cb += CH_STRIDE) {
        const uint32_t r[12] = {n0.x, n0.y, n1.x, n1.y, n1.z, n1.w, n2.x, n2.y, n2.z, n2.w, n3.x, n3.y}, nb = min(cb + CH_STRIDE, cend);
        n0 = lds64(nb + ob + 24); n3 = lds64(nb + oa); n1 = lds128(nb + oa + 16); n2 = lds128(nb + ob);
        float p[24];
        p[0] = 0.f; p[1] = bf_lo(r[0]);
        #pragma unroll
        for (int i = 2; i < 24; i++) p[i] = p[i - 1] + ((i & 1) ? bf_lo(r[i >> 1]) : bf_hi(r[(i - 1) >> 1]));
        #pragma unroll
        for (int i = 0; i < 8; i += 4) {
            sts64(cb + od + i * 256, pack2(p[i + 9] - p[i], p[i + 10] - p[i + 1]), pack2(p[i + 11] - p[i + 2], p[i + 12] - p[i + 3]));
            sts64(cb + od + i * 256 + 128, pack2(p[i + 16] - p[i + 9], p[i + 17] - p[i + 10]), pack2(p[i + 18] - p[i + 11], p[i + 19] - p[i + 12]));
        }
    }
    fence_async_smem();
    mbar_arrive(bars + 8 * B_CONV);
    STAMP(21);
}

__device__ __forceinline__ void store_h(uint32_t sb, const Params& P, const Maps& M, int V, int tg, int fb) {
    const uint32_t bars = sb + OFF_BAR;
    mbar_wait(bars + 8 * (B_EPI + V), 0);
    STAMP2(3 + 2 * V);
    asm volatile("cp.async.bulk.tensor.3d.global.shared::cta.bulk_group [%0, {%2, %3, %4}], [%1];"
        :: "l"(&M.hst[V]), "r"(sb + OFF_X + V * 2 * XBUF), "r"(0), "r"(43 * tg + 21 * V), "r"(8 * fb) : "memory");
    flag_signal(P.flags, F_H + 2 * tg + V);
    mbar_arrive(bars + 8 * (B_STG + V));
    STAMP2(4 + 2 * V);
}

__global__ void __launch_bounds__(512, 1)
fused_kernel(const __grid_constant__ Params P, const __grid_constant__ Maps M) {
    extern __shared__ __align__(1024) uint8_t smem_raw[];
    const uint32_t sb = smem_u32(smem_raw);
    const uint32_t bars = sb + OFF_BAR;
    const int warp = __shfl_sync(0xffffffffu, threadIdx.x >> 5, 0);
    const int c = blockIdx.x, tg = c / 22, fb = c - 22 * tg;
    SsmRaw raw;
    {
        const int d = min(4 * c + (warp & 3), DM - 1), o = d * 128 + (warp >> 2) * 32 + (threadIdx.x & 31);
        raw.la = ldu16(P.logA + o); raw.ai = ldu16(P.Aim + o); raw.cr = ldu16(P.Cr + o); raw.ci = ldu16(P.Ci + o);
        raw.ldt = ldu16(P.logdt + d); raw.dsk = ldu16(P.Dskip + d);
    }
    if (elect_one()) {
        if (warp == 0) { STAMP(24); GSTAMP(22); }
        asm volatile("" :: "l"(((const uint64_t*)&P)[warp < 15 ? warp : 0]));
        if (warp < 11) asm volatile("prefetch.tensormap [%0];" :: "l"(&M.x[0] + warp) : "memory");
        #pragma unroll
        for (int k = 0; k < 4; k++) {
            const int i = 16 * k + ((warp + 4) & 15);
            const uint32_t cnt = i >= B_LNX ? 1 : i >= B_CONV ? 128 : ((0xf0ull >> i) & 1) ? 8 : ((0xff0000ull >> i) & 1) ? 2 : ((0x3e00ff00f000ull >> i) & 1) ? 4 : 1;
            asm volatile("mbarrier.init.shared::cta.b64 [%0], %1;" :: "r"(bars + 8 * i), "r"(cnt) : "memory");
        }
        asm volatile("fence.mbarrier_init.release.cluster; fence.proxy.async.shared::cta;" ::: "memory");
        if (warp >= 12) {
            const uint32_t s = warp - 12;
            mbar_expect(bars + 8 * (B_FULLW + s), 16384);
            tma2d(sb + OFF_W + s * 16384, &M.wg, 64 * fb, 64 * s, bars + 8 * (B_FULLW + s));
            tma2d(sb + OFF_W + s * 16384 + 8192, &M.wu, 64 * fb, 64 * s, bars + 8 * (B_FULLW + s));
            STAMP(31);
        } else if ((warp >> 2) == 1) {
            const uint32_t s = warp - 4, V = s >> 1;
            mbar_expect(bars + 8 * (B_FULLX + s), (168 + 8 * V) * 128);
            tma2d(sb + OFF_X + s * XBUF, &M.x[V], 64 * (s & 1), TOKG * tg + 168 * V, bars + 8 * (B_FULLX + s));
        }
        if (sb & 1023) __trap();
    }
    if (warp < 4) sts128(sb + OFF_X + (warp >> 1) * XBUF + 168 * 128 + (threadIdx.x & 63) * 16, 0x3f803f80u, 0x3f803f80u, 0x3f803f80u, 0x3f803f80u);
    float dacc[2][3][4];
    #pragma unroll
    for (int i = 0; i < 24; i++) (&dacc[0][0][0])[i] = 0.f;
    if (c < 128) {
        const int wg = warp >> 2;
        const uint32_t fs = sb + OFF_CONV + (warp & 3) * CH_STRIDE + (wg == 2 ? CH_LNT : CH_PART + min(wg, 2) * CH_PSZ);
        kernel_gen(sb, fs, threadIdx.x & 31, raw, dacc, P, warp);
        if (wg != 2) {
            __syncwarp();
            #pragma unroll
            for (int i = 0; i < 6; i++) { const float* d = &dacc[0][0][0] + 4 * i; sts128(fs + (threadIdx.x & 31) * 16 + i * 512, FU(d[0]), FU(d[1]), FU(d[2]), FU(d[3])); }
        }
    }
    if (warp < 4) fence_async_smem();
    __syncthreads();
    if (warp < 8) {
        asm volatile("setmaxnreg.inc.sync.aligned.u32 208;");
        consumer(sb, warp, P, M);
        asm volatile("nanosleep.u32 1;");
    } else if (warp < 12) {
        asm volatile("setmaxnreg.dec.sync.aligned.u32 72;");
        STAMP(32);
        aux_role(sb, warp - 8, dacc, bf_lo(raw.dsk));
        asm volatile("nanosleep.u32 2;");
    } else {
        asm volatile("setmaxnreg.dec.sync.aligned.u32 24;");
        const int tau = c >> 2, dg = c & 3;
        if (elect_one()) {
            if (warp < 15) {
                if (warp == 12) {
                    #pragma unroll 1
                    for (int st = 4; st < 8; st++) {
                        const uint32_t s = st & 3, fb_ = bars + 8 * (B_FULLW + s);
                        mbar_wait(bars + 8 * (B_EMPTYW + s), 0);
                        mbar_expect(fb_, 16384);
                        tma2d(sb + OFF_W + s * 16384, &M.wg, 64 * fb, 64 * st, fb_);
                        tma2d(sb + OFF_W + s * 16384 + 8192, &M.wu, 64 * fb, 64 * st, fb_);
                    }
                } else {
                    const int V = warp - 13;
                    #pragma unroll 1
                    for (int st = 2; st < 8; st++) {
                        const uint32_t s = 2 * V + (st & 1);
                        mbar_wait(bars + 8 * (B_EMPTYX + s), ((st >> 1) & 1) ^ 1);
                        mbar_expect(bars + 8 * (B_FULLX + s), (168 + 8 * V) * 128);
                        tma2d(sb + OFF_X + s * XBUF, &M.x[V], 64 * st, TOKG * tg + 168 * V, bars + 8 * (B_FULLX + s));
                    }
                }
                if (warp == 14) store_h(sb, P, M, 1, tg, fb);
                if (c < 128 && warp < 14) {
                    if (warp == 13) {
                        mbar_wait(bars + 8 * (B_STG + 1), 0);
                        #pragma unroll 1
                        for (int o = 8 * tau; o < 8 * tau + 8; o += 7) flag_wait(P.flags, F_H + 2 * (o / 43) + ((o % 43) >= 21), 22);
                        mbar_arrive(bars + 8 * B_HF);
                        STAMP(25);
                    }
                    #pragma unroll 1
                    for (int st = 0; st < 22; st += (st < 6 || (st == 6 && warp == 13)) ? 1 : 2) {
                        const int rd = (st >= 7) + (st >= 14) + (st >= 21), sd = st - 7 * rd;
                        const uint32_t fb_ = bars + 8 * (B_FULLD + sd);
                        if (rd) mbar_wait(bars + 8 * (B_EMPTYD + sd), (rd & 1) ^ 1);
                        else if (warp == 12 || st == 6) mbar_wait(bars + 8 * (uint32_t)((0x3623070d060504ull >> (8 * st)) & 0xff), st < 5);
                        if (st >= 10 && st < 21) STAMP2(31 + st);
                        if (rd || warp == 13) {
                            mbar_expect(fb_, 8192);
                            asm volatile("cp.async.bulk.tensor.5d.shared::cluster.global.mbarrier::complete_tx::bytes [%0], [%1, {%3, %3, %3, %4, %5}], [%2];"
                                :: "r"(sb + h_slot(sd)), "l"(&M.hld), "r"(fb_), "r"(0), "r"(2 * tau), "r"(8 * st) : "memory");
                        }
                        if (rd || warp == 12) {
                            const uint32_t da = sb + wd_slot(sd);
                            mbar_expect(fb_, 16384);
                            tma2d(da, &M.wd, 128 * dg, 64 * st, fb_);
                            tma2d(da + 8192, &M.wd, 128 * dg + 64, 64 * st, fb_);
                        }
                    }
                } else if (c < 128) {
                    mbar_wait(bars + 8 * (B_SIG + 1), 0);
                    mbar_expect(bars + 8 * B_XO, 32768);
                    tma2d(sb + OFF_XO, &M.xo, 128 * dg, 64 * tau, bars + 8 * B_XO);
                    tma2d(sb + OFF_XO + 8192, &M.xo, 128 * dg + 64, 64 * tau, bars + 8 * B_XO);
                    mbar_wait(bars + 8 * B_SST, 0);
                    flag_wait(P.flags, F_S + dg, 64);
                    STAMP(26);
                    asm volatile("cp.async.bulk.tensor.5d.shared::cluster.global.mbarrier::complete_tx::bytes [%0], [%1, {%3, %3, %3, %4, %5}], [%2];"
                        :: "r"(sb + OFF_SI), "l"(&M.sld), "r"(bars + 8 * B_XO), "r"(0), "r"(8 * dg), "r"(2 * tau) : "memory");
                    mbar_wait(bars + 8 * B_HF, 0);
                    exit_count(P.flags);
                }
            } else {
                mbar_wait(bars + 8 * B_LN, 0);
                STAMP2(0);
                if (c < 128) {
                    #pragma unroll 1
                    for (int i = 0; i < 4; i++)
                        asm volatile("cp.async.bulk.tensor.2d.global.shared::cta.bulk_group [%0, {%2, %3}], [%1];"
                            :: "l"(&M.xt), "r"(sb + OFF_CONV + i * CH_STRIDE + CH_LNT), "r"((c & 1) * 1024 + (126 - (c & ~1)) * 8), "r"(128 * i) : "memory");
                    #pragma unroll 1
                    for (int i = 0; i < 2; i++) bulk_store(P.st + 16 * (c & ~1) + 8 * (c & 1) + 16 - 16 * i, sb + OFF_CSUM + 64 * i, 64);
                    asm volatile("cp.async.bulk.prefetch.L2.global [%0], %1;" :: "l"(P.Wd + c * (FF * DM / 128)), "r"(FF * DM / 64) : "memory");
                }
                STAMP2(1);
                flag_signal(P.flags, F_A);
                STAMP2(2);
                flag_wait(P.flags, F_A, NCTA);
                STAMP(20);
                mbar_expect(bars + 8 * B_STATS, TOKG * 8);
                bulk_load(sb + OFF_ST, P.st + TOKG * tg, TOKG * 8, bars + 8 * B_STATS);
                if (c < 128) {
                    mbar_expect(bars + 8 * B_U, 8 * 2048);
                    #pragma unroll 1
                    for (int i = 0; i < 8; i++)
                        bulk_load(sb + OFF_CONV + (i >> 1) * CH_STRIDE + CH_U + (i & 1) * UPLANE, P.xnT + 4 * c * 256 + i * 128, 2048, bars + 8 * B_U);
                } else exit_count(P.flags);
                store_h(sb, P, M, 0, tg, fb);
                if (c < 128) {
                    #pragma unroll 1
                    for (int V = 0; V < 2; V++) {
                        mbar_wait(bars + 8 * (B_SIG + V), 0);
                        STAMP2(7 + 2 * V);
                        bulk_store(P.S + (2 * c + V) * 1024, sb + OFF_CONV + V * OFF_SST, 8192);
                        flag_signal(P.flags, F_S + (c >> 5));
                        STAMP2(8 + 2 * V);
                    }
                    mbar_arrive(bars + 8 * B_SST);
                }
            }
            asm volatile("nanosleep.u32 0;");
        }
    }
}

typedef CUresult (*EncodeFn)(CUtensorMap*, CUtensorMapDataType, cuuint32_t, void*, const cuuint64_t*, const cuuint64_t*, const cuuint32_t*,
                             const cuuint32_t*, CUtensorMapInterleave, CUtensorMapSwizzle, CUtensorMapL2promotion, CUtensorMapFloatOOBfill);

void make_map(EncodeFn enc, CUtensorMap* m, const void* ptr, int rank, const cuuint64_t* dims, const cuuint64_t* strides, const cuuint32_t* box, bool swz, bool wide = false) {
    const cuuint32_t es[5] = {1, 1, 1, 1, 1};
    enc(m, CU_TENSOR_MAP_DATA_TYPE_BFLOAT16, rank, (void*)ptr, dims, strides, box, es, CU_TENSOR_MAP_INTERLEAVE_NONE,
        swz ? CU_TENSOR_MAP_SWIZZLE_128B : CU_TENSOR_MAP_SWIZZLE_NONE, wide ? CU_TENSOR_MAP_L2_PROMOTION_L2_256B : CU_TENSOR_MAP_L2_PROMOTION_L2_128B, CU_TENSOR_MAP_FLOAT_OOB_FILL_NONE);
}
void make_map2(EncodeFn enc, CUtensorMap* m, const void* ptr, cuuint64_t inner, cuuint64_t outer, cuuint32_t rows) {
    const cuuint64_t dims[2] = {inner, outer}, strides[1] = {inner * 2};
    const cuuint32_t box[2] = {64, rows};
    make_map(enc, m, ptr, 2, dims, strides, box, true, rows > 64);
}

}

extern "C" void kernel_launch(void* const* d_in, const int* in_sizes, int n_in, void* d_out, int out_size) {
    (void)in_sizes; (void)n_in; (void)out_size;
    static EncodeFn enc = nullptr;
    static void *hptr, *p_xnT, *p_st, *p_S, *p_flags;
    if (!enc) {
        cudaDriverEntryPointQueryResult qr;
        cudaGetDriverEntryPoint("cuTensorMapEncodeTiled", (void**)&enc, cudaEnableDefault, &qr);
        cudaFuncSetAttribute(fused_kernel, cudaFuncAttributeMaxDynamicSharedMemorySize, SMEM_BYTES);
        cudaGetSymbolAddress(&hptr, g_H); cudaGetSymbolAddress(&p_xnT, g_xnT); cudaGetSymbolAddress(&p_st, g_st);
        cudaGetSymbolAddress(&p_S, g_S); cudaGetSymbolAddress(&p_flags, g_flags);
    }
    Params P;
    P.x = (const __nv_bfloat16*)d_in[0]; P.logA = (const __nv_bfloat16*)d_in[1]; P.Aim = (const __nv_bfloat16*)d_in[2];
    P.Cr = (const __nv_bfloat16*)d_in[3]; P.Ci = (const __nv_bfloat16*)d_in[4]; P.logdt = (const __nv_bfloat16*)d_in[5];
    P.Dskip = (const __nv_bfloat16*)d_in[6];
    P.Wg = (const __nv_bfloat16*)d_in[8]; P.Wu = (const __nv_bfloat16*)d_in[9]; P.Wd = (const __nv_bfloat16*)d_in[10]; P.out = (__nv_bfloat16*)d_out; P.xnT = (uint4*)p_xnT; P.st = (float2*)p_st; P.S = (uint2*)p_S; P.flags = (unsigned*)p_flags;
    Maps M;
    make_map2(enc, &M.x[0], d_in[0], DM, SEQ, 168); make_map2(enc, &M.x[1], d_in[0], DM, SEQ, 176);
    make_map2(enc, &M.xo, d_in[0], DM, SEQ, 64);
    make_map2(enc, &M.wg, d_in[8], FF, DM, 64);     make_map2(enc, &M.wu, d_in[9], FF, DM, 64);
    make_map2(enc, &M.wd, d_in[10], DM, FF, 64);
    for (int v = 0; v < 2; v++) {
        const cuuint64_t dims[3] = {64, 256, 172}, strides[2] = {128, 32768};
        const cuuint32_t box[3] = {64, (cuuint32_t)(21 + v), 8};
        make_map(enc, &M.hst[v], hptr, 3, dims, strides, box, false);
    }
    {
        const cuuint64_t dims[2] = {2048, 512}, strides[1] = {4096};
        const cuuint32_t box[2] = {16, 128};
        make_map(enc, &M.xt, p_xnT, 2, dims, strides, box, false);
    }
    {
        const cuuint64_t dims[5] = {64, 2, 4, 32, 64}, strides[4] = {4 * 8192, 8192, 8 * 8192, 128};
        const cuuint32_t box[5] = {64, 2, 4, 8, 2};
        make_map(enc, &M.sld, p_S, 5, dims, strides, box, true);
    }
    {
        const cuuint64_t dims[5] = {64, 2, 2, 64, 172}, strides[4] = {256, 128, 512, 32768};
        const cuuint32_t box[5] = {64, 2, 2, 2, 8};
        make_map(enc, &M.hld, hptr, 5, dims, strides, box, false);
    }
    fused_kernel<<<NCTA, 512, SMEM_BYTES>>>(P, M);
}
```

```cpp
#include <cuda_runtime.h>
#include <cuda_bf16.h>
#include <cuda.h>
#include <stdint.h>

#define PROF 0

namespace {

constexpr int SEQ = 2048, DM = 512, FF = 1376;
constexpr int NCTA = 132;
#define GOST 1
#define SIGK 3
#define DLY1 300
constexpr int RUNROLL = 2;
constexpr int TOKG = 344;

constexpr uint32_t OFF_W = 0;
constexpr uint32_t XBUF = 22528;
constexpr uint32_t OFF_X = 65536;
constexpr uint32_t OFF_CONV = 155648;
constexpr uint32_t CH_STRIDE = 17536;
constexpr uint32_t CH_T = 0;
constexpr uint32_t CH_A3 = 8448;
constexpr uint32_t CH_B3 = 12544;
constexpr uint32_t CH_U = 13312;
constexpr uint32_t CH_G = CH_A3 + 2064;
constexpr uint32_t UPLANE = 2112;
constexpr uint32_t CH_LN = 0, CH_PART = 4224, CH_PSZ = 3072, CH_LNT = 13440;
constexpr uint32_t OFF_SST = 60416;
constexpr uint32_t OFF_XO = 191488, OFF_SI = 207872;
constexpr uint32_t OFF_ST = 225792;
constexpr uint32_t OFF_CSUM = 228544;
constexpr uint32_t OFF_BAR = 229056;
constexpr uint32_t SMEM_BYTES = 229568;

enum {
    B_FULLW = 0, B_EMPTYW = 4, B_FULLX = 8, B_EMPTYX = 12, B_FULLD = 16, B_EMPTYD = 24,
    B_U = 32, B_XO = 33, B_S = 34, B_STG = 35, B_HF = 37, B_STATS = 38, B_LNS = 39, B_SST = 40,
    B_TURN = 43,
    B_CONV = 46, B_LN = 50, B_CS = 51, B_EPI = 52, B_SIG = 54,
    B_LNX = 60
};
enum { F_A = 0, F_H = 1, F_S = 13, F_EXIT = 17, F_COUNT = 18 };

__device__ uint4 g_xnT[DM * 256];
__device__ float2 g_st[6 * TOKG];
__device__ uint4 g_H[172 * 256 * 8];
__device__ uint2 g_S[256 * 1024];
__device__ unsigned g_flags[F_COUNT * 32];
#define STAMP(i) do {} while (0)
#define GSTAMP(i) do {} while (0)
#define STAMP2(i) do {} while (0)

__device__ __forceinline__ uint32_t smem_u32(const void* p) { return (uint32_t)__cvta_generic_to_shared(p); }
__device__ __forceinline__ void mbar_expect(uint32_t bar, uint32_t bytes) { asm volatile("mbarrier.arrive.expect_tx.shared::cta.b64 _, [%0], %1;" :: "r"(bar), "r"(bytes) : "memory"); }
__device__ __forceinline__ void mbar_arrive(uint32_t bar) { asm volatile("mbarrier.arrive.shared::cta.b64 _, [%0];" :: "r"(bar) : "memory"); }
__device__ __forceinline__ void mbar_wait(uint32_t bar, uint32_t parity) {
    asm volatile("{.reg .pred p; .reg .u32 n; mov.u32 n, 0x20000;\n"
                 "LW: mbarrier.try_wait.parity.shared::cta.b64 p, [%0], %1;\n"
                 "sub.u32 n, n, 1; setp.eq.or.u32 p, n, 0, p; @!p bra LW;}" :: "r"(bar), "r"(parity) : "memory");
}
__device__ __forceinline__ void mbar_arrive_if(uint32_t bar, uint32_t pred) {
    asm volatile("{.reg .pred p; setp.ne.u32 p, %1, 0; @p mbarrier.arrive.shared::cta.b64 _, [%0];}" :: "r"(bar), "r"(pred) : "memory");
}
__device__ __forceinline__ bool elect_one() { uint32_t p; asm volatile("{.reg .pred P; elect.sync _|P, 0xffffffff; selp.u32 %0, 1, 0, P;}" : "=r"(p)); return p; }
__device__ __forceinline__ void tma2d(uint32_t dst, const CUtensorMap* m, int c0, int c1, uint32_t bar) {
    asm volatile("cp.async.bulk.tensor.2d.shared::cluster.global.mbarrier::complete_tx::bytes [%0], [%1, {%3, %4}], [%2];"
        :: "r"(dst), "l"(m), "r"(bar), "r"(c0), "r"(c1) : "memory");
}
__device__ __forceinline__ void bulk_load(uint32_t dst, const void* src, uint32_t bytes, uint32_t bar) {
    asm volatile("cp.async.bulk.shared::cluster.global.mbarrier::complete_tx::bytes [%0], [%1], %2, [%3];" :: "r"(dst), "l"(src), "r"(bytes), "r"(bar) : "memory");
}
__device__ __forceinline__ void bulk_store(void* dst, uint32_t src, uint32_t bytes) {
    asm volatile("cp.async.bulk.global.shared::cta.bulk_group [%0], [%1], %2;" :: "l"(dst), "r"(src), "r"(bytes) : "memory");
}
__device__ __forceinline__ void fence_async_smem() { asm volatile("fence.proxy.async.shared::cta;" ::: "memory"); }
__device__ __forceinline__ void flag_wait(unsigned* g_flags, int f, unsigned target) {
    asm volatile("{.reg .pred p; .reg .u32 n, v; mov.u32 n, 0x40000;\n"
                 "LF: ld.acquire.gpu.global.u32 v, [%0]; setp.ge.u32 p, v, %1; @p bra LD;\n"
                 "sub.u32 n, n, 1; setp.ne.u32 p, n, 0; @p bra LF; trap;\nLD: }"
                 :: "l"(g_flags + f * 32), "r"(target) : "memory");
}
__device__ __forceinline__ void flag_signal(unsigned* g_flags, int f) {
    asm volatile("cp.async.bulk.commit_group; cp.async.bulk.wait_group 0; red.relaxed.gpu.global.add.u32 [%0], 1;" :: "l"(g_flags + f * 32) : "memory");
}
__device__ __forceinline__ void exit_count(unsigned* g_flags) {
    if (atomicAdd(g_flags + F_EXIT * 32, 1u) == NCTA - 1) {
        #pragma unroll 1
        for (int i = 0; i < F_COUNT; i++) g_flags[i * 32] = 0;
    }
}
__device__ __forceinline__ void bar_sync(int id) { asm volatile("bar.sync %0, 128;" :: "r"(id) : "memory"); }
__device__ __forceinline__ uint64_t mkdesc(uint32_t addr, uint32_t lbo, uint32_t sbo, uint32_t swz) {
    return (uint64_t)((addr >> 4) | ((lbo >> 4) << 16)) | ((uint64_t)((sbo >> 4) | (swz << 30)) << 32);
}
#define WG_FENCE() asm volatile("wgmma.fence.sync.aligned;" ::: "memory")
#define WG_COMMIT() asm volatile("wgmma.commit_group.sync.aligned;" ::: "memory")
#define WG_WAIT(n) asm volatile("wgmma.wait_group.sync.aligned " #n ";" ::: "memory")
template <int N> __device__ __forceinline__ void fence_acc(float (&d)[N]) {
    #pragma unroll
    for (int i = 0; i < N; i++) asm volatile("" : "+f"(d[i]) :: "memory");
}
template <int N> __device__ __forceinline__ void define_acc(float (&d)[N]) {
    #pragma unroll
    for (int i = 0; i < N; i++) asm volatile("" : "=f"(d[i]));
}
__device__ __forceinline__ uint32_t pack2(float lo, float hi) { uint32_t r; asm("cvt.rn.bf16x2.f32 %0, %1, %2;" : "=r"(r) : "f"(hi), "f"(lo)); return r; }
__device__ __forceinline__ float bf_lo(uint32_t v) { return __uint_as_float(v << 16); }
__device__ __forceinline__ float bf_hi(uint32_t v) { return __uint_as_float(v & 0xffff0000u); }
__device__ __forceinline__ float bf_round(float v) { return bf_hi(pack2(0.f, v)); }
__device__ __forceinline__ float tanh_fast(float v) { float r; asm("tanh.approx.f32 %0, %1;" : "=f"(r) : "f"(v)); return r; }
__device__ __forceinline__ float ex2(float v) { float r; asm("ex2.approx.ftz.f32 %0, %1;" : "=f"(r) : "f"(v)); return r; }
__device__ __forceinline__ uint4 lds128(uint32_t a) { uint4 v; asm volatile("ld.shared.v4.b32 {%0,%1,%2,%3}, [%4];" : "=r"(v.x), "=r"(v.y), "=r"(v.z), "=r"(v.w) : "r"(a)); return v; }
__device__ __forceinline__ uint2 lds64(uint32_t a) { uint2 v; asm volatile("ld.shared.v2.b32 {%0,%1}, [%2];" : "=r"(v.x), "=r"(v.y) : "r"(a)); return v; }
__device__ __forceinline__ float ldsf(uint32_t a) { float v; asm volatile("ld.shared.f32 %0, [%1];" : "=f"(v) : "r"(a)); return v; }
__device__ __forceinline__ void sts128(uint32_t a, uint32_t x, uint32_t y, uint32_t z, uint32_t w) { asm volatile("st.shared.v4.b32 [%0], {%1,%2,%3,%4};" :: "r"(a), "r"(x), "r"(y), "r"(z), "r"(w) : "memory"); }
__device__ __forceinline__ void sts64(uint32_t a, uint32_t x, uint32_t y) { asm volatile("st.shared.v2.b32 [%0], {%1,%2};" :: "r"(a), "r"(x), "r"(y) : "memory"); }
__device__ __forceinline__ void stsf(uint32_t a, float x) { asm volatile("st.shared.f32 [%0], %1;" :: "r"(a), "f"(x) : "memory"); }
__device__ __forceinline__ void sts16(uint32_t a, uint32_t x) { asm volatile("st.shared.b16 [%0], %1;" :: "r"(a), "h"((unsigned short)x) : "memory"); }
__device__ __forceinline__ void stsm4(uint32_t a, uint32_t r0, uint32_t r1, uint32_t r2, uint32_t r3) {
    asm volatile("stmatrix.sync.aligned.m8n8.x4.shared.b16 [%0], {%1,%2,%3,%4};" :: "r"(a), "r"(r0), "r"(r1), "r"(r2), "r"(r3) : "memory");
}
__device__ __forceinline__ void ldsm4(uint32_t (&r)[4], uint32_t a) {
    asm volatile("ldmatrix.sync.aligned.m8n8.x4.shared.b16 {%0,%1,%2,%3}, [%4];" : "=r"(r[0]), "=r"(r[1]), "=r"(r[2]), "=r"(r[3]) : "r"(a) : "memory");
}
#define FU(x) __float_as_uint(x)
#define UF(x) __uint_as_float(x)
__device__ __forceinline__ uint32_t wd_slot(int s) { return (uint32_t)((0xbba8403056201000ull >> (8 * s)) & 0xff) << 10; }
__device__ __forceinline__ uint32_t h_slot(int s) { return (uint32_t)((0xcba0908880787068ull >> (8 * s)) & 0xff) << 10; }

template<int N> __device__ __forceinline__ void wg_rs(float (&d)[64], uint32_t a0, uint32_t a1, uint32_t a2, uint32_t a3, uint64_t db);
template<> __device__ __forceinline__ void wg_rs<128>(float (&d)[64], uint32_t a0, uint32_t a1, uint32_t a2, uint32_t a3, uint64_t db) {
  asm volatile("{.reg .pred p; setp.ne.b32 p, 1, 0; wgmma.mma_async.sync.aligned.m64n128k16.f32.bf16.bf16 {%0,%1,%2,%3,%4,%5,%6,%7,%8,%9,%10,%11,%12,%13,%14,%15,%16,%17,%18,%19,%20,%21,%22,%23,%24,%25,%26,%27,%28,%29,%30,%31,%32,%33,%34,%35,%36,%37,%38,%39,%40,%41,%42,%43,%44,%45,%46,%47,%48,%49,%50,%51,%52,%53,%54,%55,%56,%57,%58,%59,%60,%61,%62,%63}, {%64,%65,%66,%67}, %68, p, 1, 1, 0;}"
    : "+f"(d[0]),"+f"(d[1]),"+f"(d[2]),"+f"(d[3]),"+f"(d[4]),"+f"(d[5]),"+f"(d[6]),"+f"(d[7]),"+f"(d[8]),"+f"(d[9]),"+f"(d[10]),"+f"(d[11]),"+f"(d[12]),"+f"(d[13]),"+f"(d[14]),"+f"(d[15]),"+f"(d[16]),"+f"(d[17]),"+f"(d[18]),"+f"(d[19]),"+f"(d[20]),"+f"(d[21]),"+f"(d[22]),"+f"(d[23]),"+f"(d[24]),"+f"(d[25]),"+f"(d[26]),"+f"(d[27]),"+f"(d[28]),"+f"(d[29]),"+f"(d[30]),"+f"(d[31]),"+f"(d[32]),"+f"(d[33]),"+f"(d[34]),"+f"(d[35]),"+f"(d[36]),"+f"(d[37]),"+f"(d[38]),"+f"(d[39]),"+f"(d[40]),"+f"(d[41]),"+f"(d[42]),"+f"(d[43]),"+f"(d[44]),"+f"(d[45]),"+f"(d[46]),"+f"(d[47]),"+f"(d[48]),"+f"(d[49]),"+f"(d[50]),"+f"(d[51]),"+f"(d[52]),"+f"(d[53]),"+f"(d[54]),"+f"(d[55]),"+f"(d[56]),"+f"(d[57]),"+f"(d[58]),"+f"(d[59]),"+f"(d[60]),"+f"(d[61]),"+f"(d[62]),"+f"(d[63]) : "r"(a0), "r"(a1), "r"(a2), "r"(a3), "l"(db));
}
template<> __device__ __forceinline__ void wg_rs<120>(float (&d)[64], uint32_t a0, uint32_t a1, uint32_t a2, uint32_t a3, uint64_t db) {
  asm volatile("{.reg .pred p; setp.ne.b32 p, 1, 0; wgmma.mma_async.sync.aligned.m64n120k16.f32.bf16.bf16 {%0,%1,%2,%3,%4,%5,%6,%7,%8,%9,%10,%11,%12,%13,%14,%15,%16,%17,%18,%19,%20,%21,%22,%23,%24,%25,%26,%27,%28,%29,%30,%31,%32,%33,%34,%35,%36,%37,%38,%39,%40,%41,%42,%43,%44,%45,%46,%47,%48,%49,%50,%51,%52,%53,%54,%55,%56,%57,%58,%59}, {%60,%61,%62,%63}, %64, p, 1, 1, 0;}"
    : "+f"(d[0]),"+f"(d[1]),"+f"(d[2]),"+f"(d[3]),"+f"(d[4]),"+f"(d[5]),"+f"(d[6]),"+f"(d[7]),"+f"(d[8]),"+f"(d[9]),"+f"(d[10]),"+f"(d[11]),"+f"(d[12]),"+f"(d[13]),"+f"(d[14]),"+f"(d[15]),"+f"(d[16]),"+f"(d[17]),"+f"(d[18]),"+f"(d[19]),"+f"(d[20]),"+f"(d[21]),"+f"(d[22]),"+f"(d[23]),"+f"(d[24]),"+f"(d[25]),"+f"(d[26]),"+f"(d[27]),"+f"(d[28]),"+f"(d[29]),"+f"(d[30]),"+f"(d[31]),"+f"(d[32]),"+f"(d[33]),"+f"(d[34]),"+f"(d[35]),"+f"(d[36]),"+f"(d[37]),"+f"(d[38]),"+f"(d[39]),"+f"(d[40]),"+f"(d[41]),"+f"(d[42]),"+f"(d[43]),"+f"(d[44]),"+f"(d[45]),"+f"(d[46]),"+f"(d[47]),"+f"(d[48]),"+f"(d[49]),"+f"(d[50]),"+f"(d[51]),"+f"(d[52]),"+f"(d[53]),"+f"(d[54]),"+f"(d[55]),"+f"(d[56]),"+f"(d[57]),"+f"(d[58]),"+f"(d[59]) : "r"(a0), "r"(a1), "r"(a2), "r"(a3), "l"(db));
}
template<> __device__ __forceinline__ void wg_rs<112>(float (&d)[64], uint32_t a0, uint32_t a1, uint32_t a2, uint32_t a3, uint64_t db) {
  asm volatile("{.reg .pred p; setp.ne.b32 p, 1, 0; wgmma.mma_async.sync.aligned.m64n112k16.f32.bf16.bf16 {%0,%1,%2,%3,%4,%5,%6,%7,%8,%9,%10,%11,%12,%13,%14,%15,%16,%17,%18,%19,%20,%21,%22,%23,%24,%25,%26,%27,%28,%29,%30,%31,%32,%33,%34,%35,%36,%37,%38,%39,%40,%41,%42,%43,%44,%45,%46,%47,%48,%49,%50,%51,%52,%53,%54,%55}, {%56,%57,%58,%59}, %60, p, 1, 1, 0;}"
    : "+f"(d[0]),"+f"(d[1]),"+f"(d[2]),"+f"(d[3]),"+f"(d[4]),"+f"(d[5]),"+f"(d[6]),"+f"(d[7]),"+f"(d[8]),"+f"(d[9]),"+f"(d[10]),"+f"(d[11]),"+f"(d[12]),"+f"(d[13]),"+f"(d[14]),"+f"(d[15]),"+f"(d[16]),"+f"(d[17]),"+f"(d[18]),"+f"(d[19]),"+f"(d[20]),"+f"(d[21]),"+f"(d[22]),"+f"(d[23]),"+f"(d[24]),"+f"(d[25]),"+f"(d[26]),"+f"(d[27]),"+f"(d[28]),"+f"(d[29]),"+f"(d[30]),"+f"(d[31]),"+f"(d[32]),"+f"(d[33]),"+f"(d[34]),"+f"(d[35]),"+f"(d[36]),"+f"(d[37]),"+f"(d[38]),"+f"(d[39]),"+f"(d[40]),"+f"(d[41]),"+f"(d[42]),"+f"(d[43]),"+f"(d[44]),"+f"(d[45]),"+f"(d[46]),"+f"(d[47]),"+f"(d[48]),"+f"(d[49]),"+f"(d[50]),"+f"(d[51]),"+f"(d[52]),"+f"(d[53]),"+f"(d[54]),"+f"(d[55]) : "r"(a0), "r"(a1), "r"(a2), "r"(a3), "l"(db));
}
template<> __device__ __forceinline__ void wg_rs<104>(float (&d)[64], uint32_t a0, uint32_t a1, uint32_t a2, uint32_t a3, uint64_t db) {
  asm volatile("{.reg .pred p; setp.ne.b32 p, 1, 0; wgmma.mma_async.sync.aligned.m64n104k16.f32.bf16.bf16 {%0,%1,%2,%3,%4,%5,%6,%7,%8,%9,%10,%11,%12,%13,%14,%15,%16,%17,%18,%19,%20,%21,%22,%23,%24,%25,%26,%27,%28,%29,%30,%31,%32,%33,%34,%35,%36,%37,%38,%39,%40,%41,%42,%43,%44,%45,%46,%47,%48,%49,%50,%51}, {%52,%53,%54,%55}, %56, p, 1, 1, 0;}"
    : "+f"(d[0]),"+f"(d[1]),"+f"(d[2]),"+f"(d[3]),"+f"(d[4]),"+f"(d[5]),"+f"(d[6]),"+f"(d[7]),"+f"(d[8]),"+f"(d[9]),"+f"(d[10]),"+f"(d[11]),"+f"(d[12]),"+f"(d[13]),"+f"(d[14]),"+f"(d[15]),"+f"(d[16]),"+f"(d[17]),"+f"(d[18]),"+f"(d[19]),"+f"(d[20]),"+f"(d[21]),"+f"(d[22]),"+f"(d[23]),"+f"(d[24]),"+f"(d[25]),"+f"(d[26]),"+f"(d[27]),"+f"(d[28]),"+f"(d[29]),"+f"(d[30]),"+f"(d[31]),"+f"(d[32]),"+f"(d[33]),"+f"(d[34]),"+f"(d[35]),"+f"(d[36]),"+f"(d[37]),"+f"(d[38]),"+f"(d[39]),"+f"(d[40]),"+f"(d[41]),"+f"(d[42]),"+f"(d[43]),"+f"(d[44]),"+f"(d[45]),"+f"(d[46]),"+f"(d[47]),"+f"(d[48]),"+f"(d[49]),"+f"(d[50]),"+f"(d[51]) : "r"(a0), "r"(a1), "r"(a2), "r"(a3), "l"(db));
}
template<> __device__ __forceinline__ void wg_rs<96>(float (&d)[64], uint32_t a0, uint32_t a1, uint32_t a2, uint32_t a3, uint64_t db) {
  asm volatile("{.reg .pred p; setp.ne.b32 p, 1, 0; wgmma.mma_async.sync.aligned.m64n96k16.f32.bf16.bf16 {%0,%1,%2,%3,%4,%5,%6,%7,%8,%9,%10,%11,%12,%13,%14,%15,%16,%17,%18,%19,%20,%21,%22,%23,%24,%25,%26,%27,%28,%29,%30,%31,%32,%33,%34,%35,%36,%37,%38,%39,%40,%41,%42,%43,%44,%45,%46,%47}, {%48,%49,%50,%51}, %52, p, 1, 1, 0;}"
    : "+f"(d[0]),"+f"(d[1]),"+f"(d[2]),"+f"(d[3]),"+f"(d[4]),"+f"(d[5]),"+f"(d[6]),"+f"(d[7]),"+f"(d[8]),"+f"(d[9]),"+f"(d[10]),"+f"(d[11]),"+f"(d[12]),"+f"(d[13]),"+f"(d[14]),"+f"(d[15]),"+f"(d[16]),"+f"(d[17]),"+f"(d[18]),"+f"(d[19]),"+f"(d[20]),"+f"(d[21]),"+f"(d[22]),"+f"(d[23]),"+f"(d[24]),"+f"(d[25]),"+f"(d[26]),"+f"(d[27]),"+f"(d[28]),"+f"(d[29]),"+f"(d[30]),"+f"(d[31]),"+f"(d[32]),"+f"(d[33]),"+f"(d[34]),"+f"(d[35]),"+f"(d[36]),"+f"(d[37]),"+f"(d[38]),"+f"(d[39]),"+f"(d[40]),"+f"(d[41]),"+f"(d[42]),"+f"(d[43]),"+f"(d[44]),"+f"(d[45]),"+f"(d[46]),"+f"(d[47]) : "r"(a0), "r"(a1), "r"(a2), "r"(a3), "l"(db));
}
template<> __device__ __forceinline__ void wg_rs<88>(float (&d)[64], uint32_t a0, uint32_t a1, uint32_t a2, uint32_t a3, uint64_t db) {
  asm volatile("{.reg .pred p; setp.ne.b32 p, 1, 0; wgmma.mma_async.sync.aligned.m64n88k16.f32.bf16.bf16 {%0,%1,%2,%3,%4,%5,%6,%7,%8,%9,%10,%11,%12,%13,%14,%15,%16,%17,%18,%19,%20,%21,%22,%23,%24,%25,%26,%27,%28,%29,%30,%31,%32,%33,%34,%35,%36,%37,%38,%39,%40,%41,%42,%43}, {%44,%45,%46,%47}, %48, p, 1, 1, 0;}"
    : "+f"(d[0]),"+f"(d[1]),"+f"(d[2]),"+f"(d[3]),"+f"(d[4]),"+f"(d[5]),"+f"(d[6]),"+f"(d[7]),"+f"(d[8]),"+f"(d[9]),"+f"(d[10]),"+f"(d[11]),"+f"(d[12]),"+f"(d[13]),"+f"(d[14]),"+f"(d[15]),"+f"(d[16]),"+f"(d[17]),"+f"(d[18]),"+f"(d[19]),"+f"(d[20]),"+f"(d[21]),"+f"(d[22]),"+f"(d[23]),"+f"(d[24]),"+f"(d[25]),"+f"(d[26]),"+f"(d[27]),"+f"(d[28]),"+f"(d[29]),"+f"(d[30]),"+f"(d[31]),"+f"(d[32]),"+f"(d[33]),"+f"(d[34]),"+f"(d[35]),"+f"(d[36]),"+f"(d[37]),"+f"(d[38]),"+f"(d[39]),"+f"(d[40]),"+f"(d[41]),"+f"(d[42]),"+f"(d[43]) : "r"(a0), "r"(a1), "r"(a2), "r"(a3), "l"(db));
}
template<> __device__ __forceinline__ void wg_rs<80>(float (&d)[64], uint32_t a0, uint32_t a1, uint32_t a2, uint32_t a3, uint64_t db) {
  asm volatile("{.reg .pred p; setp.ne.b32 p, 1, 0; wgmma.mma_async.sync.aligned.m64n80k16.f32.bf16.bf16 {%0,%1,%2,%3,%4,%5,%6,%7,%8,%9,%10,%11,%12,%13,%14,%15,%16,%17,%18,%19,%20,%21,%22,%23,%24,%25,%26,%27,%28,%29,%30,%31,%32,%33,%34,%35,%36,%37,%38,%39}, {%40,%41,%42,%43}, %44, p, 1, 1, 0;}"
    : "+f"(d[0]),"+f"(d[1]),"+f"(d[2]),"+f"(d[3]),"+f"(d[4]),"+f"(d[5]),"+f"(d[6]),"+f"(d[7]),"+f"(d[8]),"+f"(d[9]),"+f"(d[10]),"+f"(d[11]),"+f"(d[12]),"+f"(d[13]),"+f"(d[14]),"+f"(d[15]),"+f"(d[16]),"+f"(d[17]),"+f"(d[18]),"+f"(d[19]),"+f"(d[20]),"+f"(d[21]),"+f"(d[22]),"+f"(d[23]),"+f"(d[24]),"+f"(d[25]),"+f"(d[26]),"+f"(d[27]),"+f"(d[28]),"+f"(d[29]),"+f"(d[30]),"+f"(d[31]),"+f"(d[32]),"+f"(d[33]),"+f"(d[34]),"+f"(d[35]),"+f"(d[36]),"+f"(d[37]),"+f"(d[38]),"+f"(d[39]) : "r"(a0), "r"(a1), "r"(a2), "r"(a3), "l"(db));
}
template<> __device__ __forceinline__ void wg_rs<72>(float (&d)[64], uint32_t a0, uint32_t a1, uint32_t a2, uint32_t a3, uint64_t db) {
  asm volatile("{.reg .pred p; setp.ne.b32 p, 1, 0; wgmma.mma_async.sync.aligned.m64n72k16.f32.bf16.bf16 {%0,%1,%2,%3,%4,%5,%6,%7,%8,%9,%10,%11,%12,%13,%14,%15,%16,%17,%18,%19,%20,%21,%22,%23,%24,%25,%26,%27,%28,%29,%30,%31,%32,%33,%34,%35}, {%36,%37,%38,%39}, %40, p, 1, 1, 0;}"
    : "+f"(d[0]),"+f"(d[1]),"+f"(d[2]),"+f"(d[3]),"+f"(d[4]),"+f"(d[5]),"+f"(d[6]),"+f"(d[7]),"+f"(d[8]),"+f"(d[9]),"+f"(d[10]),"+f"(d[11]),"+f"(d[12]),"+f"(d[13]),"+f"(d[14]),"+f"(d[15]),"+f"(d[16]),"+f"(d[17]),"+f"(d[18]),"+f"(d[19]),"+f"(d[20]),"+f"(d[21]),"+f"(d[22]),"+f"(d[23]),"+f"(d[24]),"+f"(d[25]),"+f"(d[26]),"+f"(d[27]),"+f"(d[28]),"+f"(d[29]),"+f"(d[30]),"+f"(d[31]),"+f"(d[32]),"+f"(d[33]),"+f"(d[34]),"+f"(d[35]) : "r"(a0), "r"(a1), "r"(a2), "r"(a3), "l"(db));
}
template<> __device__ __forceinline__ void wg_rs<64>(float (&d)[64], uint32_t a0, uint32_t a1, uint32_t a2, uint32_t a3, uint64_t db) {
  asm volatile("{.reg .pred p; setp.ne.b32 p, 1, 0; wgmma.mma_async.sync.aligned.m64n64k16.f32.bf16.bf16 {%0,%1,%2,%3,%4,%5,%6,%7,%8,%9,%10,%11,%12,%13,%14,%15,%16,%17,%18,%19,%20,%21,%22,%23,%24,%25,%26,%27,%28,%29,%30,%31}, {%32,%33,%34,%35}, %36, p, 1, 1, 0;}"
    : "+f"(d[0]),"+f"(d[1]),"+f"(d[2]),"+f"(d[3]),"+f"(d[4]),"+f"(d[5]),"+f"(d[6]),"+f"(d[7]),"+f"(d[8]),"+f"(d[9]),"+f"(d[10]),"+f"(d[11]),"+f"(d[12]),"+f"(d[13]),"+f"(d[14]),"+f"(d[15]),"+f"(d[16]),"+f"(d[17]),"+f"(d[18]),"+f"(d[19]),"+f"(d[20]),"+f"(d[21]),"+f"(d[22]),"+f"(d[23]),"+f"(d[24]),"+f"(d[25]),"+f"(d[26]),"+f"(d[27]),"+f"(d[28]),"+f"(d[29]),"+f"(d[30]),"+f"(d[31]) : "r"(a0), "r"(a1), "r"(a2), "r"(a3), "l"(db));
}
__device__ __forceinline__ void wg_rs_first(float (&d)[64], uint32_t a0, uint32_t a1, uint32_t a2, uint32_t a3, uint64_t db) {
  asm volatile("{.reg .pred p; setp.ne.b32 p, 0, 0; wgmma.mma_async.sync.aligned.m64n128k16.f32.bf16.bf16 {%0,%1,%2,%3,%4,%5,%6,%7,%8,%9,%10,%11,%12,%13,%14,%15,%16,%17,%18,%19,%20,%21,%22,%23,%24,%25,%26,%27,%28,%29,%30,%31,%32,%33,%34,%35,%36,%37,%38,%39,%40,%41,%42,%43,%44,%45,%46,%47,%48,%49,%50,%51,%52,%53,%54,%55,%56,%57,%58,%59,%60,%61,%62,%63}, {%64,%65,%66,%67}, %68, p, 1, 1, 0;}"
    : "=f"(d[0]),"=f"(d[1]),"=f"(d[2]),"=f"(d[3]),"=f"(d[4]),"=f"(d[5]),"=f"(d[6]),"=f"(d[7]),"=f"(d[8]),"=f"(d[9]),"=f"(d[10]),"=f"(d[11]),"=f"(d[12]),"=f"(d[13]),"=f"(d[14]),"=f"(d[15]),"=f"(d[16]),"=f"(d[17]),"=f"(d[18]),"=f"(d[19]),"=f"(d[20]),"=f"(d[21]),"=f"(d[22]),"=f"(d[23]),"=f"(d[24]),"=f"(d[25]),"=f"(d[26]),"=f"(d[27]),"=f"(d[28]),"=f"(d[29]),"=f"(d[30]),"=f"(d[31]),"=f"(d[32]),"=f"(d[33]),"=f"(d[34]),"=f"(d[35]),"=f"(d[36]),"=f"(d[37]),"=f"(d[38]),"=f"(d[39]),"=f"(d[40]),"=f"(d[41]),"=f"(d[42]),"=f"(d[43]),"=f"(d[44]),"=f"(d[45]),"=f"(d[46]),"=f"(d[47]),"=f"(d[48]),"=f"(d[49]),"=f"(d[50]),"=f"(d[51]),"=f"(d[52]),"=f"(d[53]),"=f"(d[54]),"=f"(d[55]),"=f"(d[56]),"=f"(d[57]),"=f"(d[58]),"=f"(d[59]),"=f"(d[60]),"=f"(d[61]),"=f"(d[62]),"=f"(d[63]) : "r"(a0), "r"(a1), "r"(a2), "r"(a3), "l"(db));
}
__device__ __forceinline__ void wg_tt128(float (&d)[64], uint64_t da, uint64_t db, int sc) {
  asm volatile("{.reg .pred p; setp.ne.b32 p, %66, 0; wgmma.mma_async.sync.aligned.m64n128k16.f32.bf16.bf16 {%0,%1,%2,%3,%4,%5,%6,%7,%8,%9,%10,%11,%12,%13,%14,%15,%16,%17,%18,%19,%20,%21,%22,%23,%24,%25,%26,%27,%28,%29,%30,%31,%32,%33,%34,%35,%36,%37,%38,%39,%40,%41,%42,%43,%44,%45,%46,%47,%48,%49,%50,%51,%52,%53,%54,%55,%56,%57,%58,%59,%60,%61,%62,%63}, %64, %65, p, 1, 1, 1, 1;}"
    : "+f"(d[0]),"+f"(d[1]),"+f"(d[2]),"+f"(d[3]),"+f"(d[4]),"+f"(d[5]),"+f"(d[6]),"+f"(d[7]),"+f"(d[8]),"+f"(d[9]),"+f"(d[10]),"+f"(d[11]),"+f"(d[12]),"+f"(d[13]),"+f"(d[14]),"+f"(d[15]),"+f"(d[16]),"+f"(d[17]),"+f"(d[18]),"+f"(d[19]),"+f"(d[20]),"+f"(d[21]),"+f"(d[22]),"+f"(d[23]),"+f"(d[24]),"+f"(d[25]),"+f"(d[26]),"+f"(d[27]),"+f"(d[28]),"+f"(d[29]),"+f"(d[30]),"+f"(d[31]),"+f"(d[32]),"+f"(d[33]),"+f"(d[34]),"+f"(d[35]),"+f"(d[36]),"+f"(d[37]),"+f"(d[38]),"+f"(d[39]),"+f"(d[40]),"+f"(d[41]),"+f"(d[42]),"+f"(d[43]),"+f"(d[44]),"+f"(d[45]),"+f"(d[46]),"+f"(d[47]),"+f"(d[48]),"+f"(d[49]),"+f"(d[50]),"+f"(d[51]),"+f"(d[52]),"+f"(d[53]),"+f"(d[54]),"+f"(d[55]),"+f"(d[56]),"+f"(d[57]),"+f"(d[58]),"+f"(d[59]),"+f"(d[60]),"+f"(d[61]),"+f"(d[62]),"+f"(d[63]) : "l"(da), "l"(db), "r"(sc));
}
__device__ __forceinline__ void wg_tt64(float (&d)[64], uint64_t da, uint64_t db, int sc) {
  asm volatile("{.reg .pred p; setp.ne.b32 p, %34, 0; wgmma.mma_async.sync.aligned.m64n64k16.f32.bf16.bf16 {%0,%1,%2,%3,%4,%5,%6,%7,%8,%9,%10,%11,%12,%13,%14,%15,%16,%17,%18,%19,%20,%21,%22,%23,%24,%25,%26,%27,%28,%29,%30,%31}, %32, %33, p, 1, 1, 1, 1;}"
    : "+f"(d[0]),"+f"(d[1]),"+f"(d[2]),"+f"(d[3]),"+f"(d[4]),"+f"(d[5]),"+f"(d[6]),"+f"(d[7]),"+f"(d[8]),"+f"(d[9]),"+f"(d[10]),"+f"(d[11]),"+f"(d[12]),"+f"(d[13]),"+f"(d[14]),"+f"(d[15]),"+f"(d[16]),"+f"(d[17]),"+f"(d[18]),"+f"(d[19]),"+f"(d[20]),"+f"(d[21]),"+f"(d[22]),"+f"(d[23]),"+f"(d[24]),"+f"(d[25]),"+f"(d[26]),"+f"(d[27]),"+f"(d[28]),"+f"(d[29]),"+f"(d[30]),"+f"(d[31]) : "l"(da), "l"(db), "r"(sc));
}
__device__ __forceinline__ void wg_tt32(float (&d)[64], uint64_t da, uint64_t db, int sc) {
  asm volatile("{.reg .pred p; setp.ne.b32 p, %18, 0; wgmma.mma_async.sync.aligned.m64n32k16.f32.bf16.bf16 {%0,%1,%2,%3,%4,%5,%6,%7,%8,%9,%10,%11,%12,%13,%14,%15}, %16, %17, p, 1, 1, 1, 1;}"
    : "+f"(d[0]),"+f"(d[1]),"+f"(d[2]),"+f"(d[3]),"+f"(d[4]),"+f"(d[5]),"+f"(d[6]),"+f"(d[7]),"+f"(d[8]),"+f"(d[9]),"+f"(d[10]),"+f"(d[11]),"+f"(d[12]),"+f"(d[13]),"+f"(d[14]),"+f"(d[15]) : "l"(da), "l"(db), "r"(sc));
}
__device__ __forceinline__ void wg_g1(float (&d)[88], uint64_t da, uint64_t db, int sc) {
  asm volatile("{.reg .pred p; setp.ne.b32 p, %90, 0; wgmma.mma_async.sync.aligned.m64n176k16.f32.bf16.bf16 {%0,%1,%2,%3,%4,%5,%6,%7,%8,%9,%10,%11,%12,%13,%14,%15,%16,%17,%18,%19,%20,%21,%22,%23,%24,%25,%26,%27,%28,%29,%30,%31,%32,%33,%34,%35,%36,%37,%38,%39,%40,%41,%42,%43,%44,%45,%46,%47,%48,%49,%50,%51,%52,%53,%54,%55,%56,%57,%58,%59,%60,%61,%62,%63,%64,%65,%66,%67,%68,%69,%70,%71,%72,%73,%74,%75,%76,%77,%78,%79,%80,%81,%82,%83,%84,%85,%86,%87}, %88, %89, p, 1, 1, 1, 0;}"
    : "+f"(d[0]),"+f"(d[1]),"+f"(d[2]),"+f"(d[3]),"+f"(d[4]),"+f"(d[5]),"+f"(d[6]),"+f"(d[7]),"+f"(d[8]),"+f"(d[9]),"+f"(d[10]),"+f"(d[11]),"+f"(d[12]),"+f"(d[13]),"+f"(d[14]),"+f"(d[15]),"+f"(d[16]),"+f"(d[17]),"+f"(d[18]),"+f"(d[19]),"+f"(d[20]),"+f"(d[21]),"+f"(d[22]),"+f"(d[23]),"+f"(d[24]),"+f"(d[25]),"+f"(d[26]),"+f"(d[27]),"+f"(d[28]),"+f"(d[29]),"+f"(d[30]),"+f"(d[31]),"+f"(d[32]),"+f"(d[33]),"+f"(d[34]),"+f"(d[35]),"+f"(d[36]),"+f"(d[37]),"+f"(d[38]),"+f"(d[39]),"+f"(d[40]),"+f"(d[41]),"+f"(d[42]),"+f"(d[43]),"+f"(d[44]),"+f"(d[45]),"+f"(d[46]),"+f"(d[47]),"+f"(d[48]),"+f"(d[49]),"+f"(d[50]),"+f"(d[51]),"+f"(d[52]),"+f"(d[53]),"+f"(d[54]),"+f"(d[55]),"+f"(d[56]),"+f"(d[57]),"+f"(d[58]),"+f"(d[59]),"+f"(d[60]),"+f"(d[61]),"+f"(d[62]),"+f"(d[63]),"+f"(d[64]),"+f"(d[65]),"+f"(d[66]),"+f"(d[67]),"+f"(d[68]),"+f"(d[69]),"+f"(d[70]),"+f"(d[71]),"+f"(d[72]),"+f"(d[73]),"+f"(d[74]),"+f"(d[75]),"+f"(d[76]),"+f"(d[77]),"+f"(d[78]),"+f"(d[79]),"+f"(d[80]),"+f"(d[81]),"+f"(d[82]),"+f"(d[83]),"+f"(d[84]),"+f"(d[85]),"+f"(d[86]),"+f"(d[87]) : "l"(da), "l"(db), "r"(sc));
}

struct Params { const __nv_bfloat16 *x, *logA, *Aim, *Cr, *Ci, *logdt, *Dskip, *Wg, *Wu, *Wd; __nv_bfloat16* out; uint4* xnT; float2* st; uint2* S; unsigned* flags; };
struct Maps { CUtensorMap x[2], xo, wg, wu, wd, hst[2], hld, xt, sld; };

__device__ __forceinline__ void conv_channel(uint32_t cb, int w, int lane, uint32_t (&res)[8], uint32_t sig, int sidx) {
    const int q = lane & 3, g = lane >> 2, gam = g >> 2;
    float acc[64];
    uint2 a[17][2];
    const uint32_t t0 = cb + CH_T + (uint32_t)(14 + 4 * w + (g & 3) - 2 * q) * 280u + gam * 8;
#define LDA(s0, s1) _Pragma("unroll") for (int s = s0; s < s1; s++) { a[s][0] = lds64(t0 + s * 16); a[s][1] = lds64(t0 - 8 * 280 + s * 16); }
#define CT(N, s) wg_rs<N>(acc, a[s][0].x, a[s][0].y, a[s][1].x, a[s][1].y, dU + 4 * (s))
    const uint64_t dU = mkdesc(cb + CH_U, UPLANE, 128, 0);
    LDA(0, 17)
    if (sig) { fence_async_smem(); mbar_arrive(sig); }
    WG_FENCE();
    if (w == 0) STAMP2(52 + 3 * sidx);
    wg_rs_first(acc, a[0][0].x, a[0][0].y, a[0][1].x, a[0][1].y, dU);
    CT(128, 1); CT(120, 2); CT(120, 3); CT(112, 4); CT(112, 5); CT(104, 6); CT(104, 7); CT(96, 8);
    CT(96, 9); CT(88, 10); CT(88, 11); CT(80, 12); CT(80, 13); CT(72, 14); CT(72, 15); CT(64, 16);
#undef CT
#undef LDA
    wg_tt64(acc, mkdesc(cb + CH_A3, 128, 512, 0), mkdesc(cb + CH_B3, 384, 32, 0), 1);
    wg_tt32(acc, mkdesc(cb + CH_A3 + 256, 128, 512, 0), mkdesc(cb + CH_B3 + 128, 384, 32, 0), 1);
    WG_COMMIT();
    if (w == 0) STAMP2(53 + 3 * sidx);
    WG_WAIT(0);
    fence_acc(acc);
    if (w == 0) STAMP2(54 + 3 * sidx);
    const int src1 = (lane & ~3) | ((q + 1) & 3);
    float E[16][2];
    #pragma unroll
    for (int j = 0; j < 16; j++) {
        const float nxt = (j < 15) ? acc[4 * (j + 1) + 2] : 0.f;
        const float sup = (q == 0) ? nxt : acc[4 * j + 2];
        const float v = __shfl_sync(0xffffffffu, sup, src1);
        E[j][0] = acc[4 * j] + acc[4 * j + 3];
        E[j][1] = acc[4 * j + 1] + v;
    }
    const int src2 = gam ? ((lane & 12) | ((q + 3) & 3)) : (16 | (lane & 12) | ((q + 1) & 3));
    const bool c1 = gam && q != 0, c2 = gam && q == 0;
    #pragma unroll
    for (int a2 = 0; a2 < 8; a2++) {
        float y[2];
        #pragma unroll
        for (int e = 0; e < 2; e++) {
            const float sup = c1 ? E[2 * a2][e] : E[2 * a2 + 1][e];
            const float nxt = (a2 < 7) ? E[2 * a2 + 2][e] : 0.f;
            const float keep = c2 ? nxt : (c1 ? E[2 * a2 + 1][e] : E[2 * a2][e]);
            y[e] = keep + __shfl_sync(0xffffffffu, sup, src2);
        }
        res[a2] = pack2(y[1], y[0]);
    }
}

__device__ __forceinline__ void consumer(uint32_t sb, int warp, const Params& P, const Maps& M) {
    const int V = warp >> 2, w = warp & 3, lane = threadIdx.x & 31, q = lane & 3, g = lane >> 2;
    const int c = blockIdx.x;
    const uint32_t bars = sb + OFF_BAR, xb = sb + OFF_X + V * 2 * XBUF;
    {
        float ag[88], au[88];
        define_acc(ag); define_acc(au);
        mbar_wait(bars + 8 * B_FULLW, 0);
        mbar_wait(bars + 8 * (B_FULLX + 2 * V), 0);
        #pragma unroll 1
        for (int st = 0; st < 8; st++) {
            uint64_t dG = mkdesc(sb + OFF_W + (st & 3) * 16384, 0, 1024, 1), dX = mkdesc(xb + (st & 1) * XBUF, 16, 1024, 1);
            uint32_t sig = lane == 0 && (V ? st < 6 : st > 0);
            asm volatile("" : "+l"(dG), "+l"(dX), "+r"(sig) :: "memory");
            if (V ? st < 7 : st > 1) mbar_wait(bars + 8 * (B_TURN + V), st & 1);
            STAMP(40 + 8 * V + st);
            WG_FENCE();
            #pragma unroll
            for (int k = 0; k < 4; k++) {
                if (k == SIGK) mbar_arrive_if(bars + 8 * (B_TURN + 1 - V), sig);
                wg_g1(ag, dG + k * 128, dX + k * 2, k ? 1 : st);
                wg_g1(au, dG + 512 + k * 128, dX + k * 2, k ? 1 : st);
            }
            WG_COMMIT();
            if (st == 6 * V) {
                mbar_wait(bars + 8 * (B_FULLW + ((st + 1) & 3)), V);
                mbar_wait(bars + 8 * (B_FULLX + 2 * V + 1), V);
            } else {
                WG_WAIT(1);
                mbar_arrive_if(bars + 8 * (B_EMPTYW + 2 * V), lane == 0 && st == 6 * V + 1);
                mbar_arrive_if(bars + 8 * (B_EMPTYX + 2 * V), lane == 0 && st == 6 * V + 1);
                WG_WAIT(0);
                mbar_arrive_if(bars + 8 * (B_EMPTYW + (st & 3)), lane == 0);
                mbar_arrive_if(bars + 8 * (B_EMPTYX + 2 * V + (st & 1)), lane == 0);
                if (st < 7) {
                    mbar_wait(bars + 8 * (B_FULLW + ((st + 1) & 3)), (st + 1) >> 2);
                    mbar_wait(bars + 8 * (B_FULLX + 2 * V + ((st + 1) & 1)), ((st + 1) >> 1) & 1);
                }
            }
        }
        WG_WAIT(0);
        fence_acc(ag); fence_acc(au);
        STAMP(8 * V + 1);
        float cg0 = ag[84], cg1 = ag[86], cu0 = au[84], cu1 = au[86];
        const uint32_t ca = sb + OFF_CSUM + (8 * w + g) * 16;
        if (V == 0) { sts128(ca, FU(cg0), FU(cg1), FU(cu0), FU(cu1)); mbar_arrive(bars + 8 * B_CS); }
        else { mbar_wait(bars + 8 * B_CS, 0); const uint4 t = lds128(ca); cg0 = UF(t.x); cg1 = UF(t.y); cu0 = UF(t.z); cu1 = UF(t.w); }
        mbar_wait(bars + 8 * B_STATS, 0);
        mbar_wait(bars + 8 * (B_EMPTYX + 2 * V), 1);
        STAMP(13 + V);
        const uint32_t hs = xb + (2 * w + ((lane >> 3) & 1)) * (2688 + 128 * V) + (lane >> 4) * 128 + (lane & 7) * 16;
        const uint32_t sa = sb + OFF_ST + (168 * V + 2 * q) * 8;
        uint4 sq[22];
        #pragma unroll
        for (int j = 0; j < 3; j++) sq[j] = lds128(sa + j * 64);
        #pragma unroll
        for (int j = 0; j < 22; j += 2) {
            uint32_t o[4];
            #pragma unroll
            for (int jj = 0; jj < 2; jj++) {
                const uint4 sv = sq[j + jj];
                float hv[4];
                #pragma unroll
                for (int i = 0; i < 4; i++) {
                    const float m = UF((i & 1) ? sv.z : sv.x);
                    const float gh = fmaf(-m, (i & 2) ? cg1 : cg0, ag[4 * (j + jj) + i]) * UF((i & 1) ? sv.w : sv.y);
                    const float p = gh * fmaf(-m, (i & 2) ? cu1 : cu0, au[4 * (j + jj) + i]);
                    hv[i] = fmaf(p, tanh_fast(gh), p);
                }
                o[2 * jj] = pack2(hv[0], hv[1]); o[2 * jj + 1] = pack2(hv[2], hv[3]);
            }
            #pragma unroll
            for (int k = (j ? 3 + 3 * j / 2 : 3); k < 6 + 3 * j / 2 && k < 22; k++) sq[k] = lds128(sa + k * 64);
            uint32_t ad = hs + j * 128;
            if (j == 20 && V == 0 && lane >= 16) ad = xb + 21504 + (lane & 7) * 16;
            stsm4(ad, o[0], o[1], o[2], o[3]);
        }
        if (c >= 128 || V) { fence_async_smem(); mbar_arrive(bars + 8 * (B_EPI + V)); }
        STAMP(8 * V + 2);
    }
    if (c >= 128) return;
    {
        mbar_wait(bars + 8 * B_CONV, 0);
        uint32_t r0[8], r1[8];
        #pragma unroll
        for (int i = 0; i < 8; i++) asm volatile("" : "=r"(r1[i]));
        #pragma unroll 1
        for (int e = 0; e < 2; e++) {
            #pragma unroll
            for (int i = 0; i < 8; i++) r0[i] = r1[i];
            conv_channel(sb + OFF_CONV + (2 * V + e) * CH_STRIDE, w, lane, r1, (e | V) ? 0 : bars + 8 * B_EPI, 2 * V + e);
            if (e == 0) STAMP(8 * V + 3);
        }
        const int gam = g >> 2, qq = gam ? ((q + 3) & 3) : q;
        const uint32_t sp = sb + OFF_CONV + V * OFF_SST + ((63 - 4 * gam - qq) * 16 + 4 * (w ^ (3 - qq)) + (g & 3)) * 8;
        bar_sync(3 + V);
        #pragma unroll
        for (int a2 = 0; a2 < 8; a2++) sts64(sp - a2 * 1024, r0[a2], r1[a2]);
        fence_async_smem();
        mbar_arrive(bars + 8 * (B_SIG + V));
        STAMP(8 * V + 4);
    }
    if (V == 1) return;
    {
        const int tau = c >> 2, dg = c & 3;
        const uint32_t row = 8 * (w & 1) + 32 * (w >> 1);
        float acc[64];
        define_acc(acc);
        const float rr0 = __ldcg(&P.st[64 * tau + row + g].y), rr1 = __ldcg(&P.st[64 * tau + row + g + 16].y);
        mbar_wait(bars + 8 * B_FULLD, 0);
        STAMP(5);
        uint64_t dB = mkdesc(sb + wd_slot(0), 8192, 1024, 1), dA = mkdesc(sb + h_slot(0), 1024, 128, 0);
        int sd = 0; uint32_t np = 0;
        #pragma unroll 1
        for (int st = 0; st < 21; st++) {
            WG_FENCE();
            wg_tt128(acc, dA, dB, st);
            wg_tt128(acc, dA + 128, dB + 128, 1);
            wg_tt128(acc, dA + 256, dB + 256, 1);
            wg_tt128(acc, dA + 384, dB + 384, 1);
            WG_COMMIT();
            uint32_t ro = bars + 8 * (B_EMPTYD + (sd ? sd - 1 : 6)), m = lane == 0 && st > 0, ok;
            if (++sd == 7) { sd = 0; np ^= 1; }
            const uint32_t nb = bars + 8 * (B_FULLD + sd);
            dB = mkdesc(sb + wd_slot(sd), 8192, 1024, 1); dA = mkdesc(sb + h_slot(sd), 1024, 128, 0);
            asm volatile("{.reg .pred p; mbarrier.test_wait.parity.shared::cta.b64 p, [%5], %6; vote.sync.all.pred p, p, -1; selp.u32 %0, 1, 0, p;}"
                : "=r"(ok), "+l"(dA), "+l"(dB), "+r"(ro), "+r"(m) : "r"(nb), "r"(np) : "memory");
            WG_WAIT(1);
            mbar_arrive_if(ro, m);
            if (!ok) mbar_wait(nb, np);
            if (w == 0) STAMP2(20 + st);
        }
        WG_FENCE();
        wg_tt128(acc, dA, dB, 1);
        wg_tt128(acc, dA + 128, dB + 128, 1);
        WG_COMMIT();
        mbar_wait(bars + 8 * B_XO, 0);
        const uint32_t xo = sb + OFF_XO + (row + (lane & 7) + 16 * ((lane >> 3) & 1)) * 128;
        const uint32_t so = sb + OFF_SI + (w >> 1) * 8192 + q * 256 + (g & 1) * 8;
        const uint32_t sx = (4 * (w & 1) + (g >> 1)) ^ (2 * q) ^ (2 * ((2 * tau + (w >> 1)) & 3));
        uint32_t xr[8][4];
        uint2 sv[16];
        #pragma unroll
        for (int j = 0; j < 16; j += 2) {
            ldsm4(xr[j >> 1], xo + (j >> 3) * 8192 + ((((j & 7) + (lane >> 4)) ^ (lane & 7)) << 4));
            sv[j] = lds64(so + j * 512 + (sx << 4));
            sv[j + 1] = lds64(so + j * 512 + 128 + ((sx ^ 1) << 4));
        }
        WG_WAIT(0);
        fence_acc(acc);
        STAMP(6);
        #pragma unroll
        for (int j = 0; j < 16; j += 2) {
            #pragma unroll
            for (int i = 0; i < 4; i++) {
                const int jj = j + (i >> 1), hh = i & 1;
                const float f0 = acc[4 * jj + 2 * hh] * (hh ? rr1 : rr0), f1 = acc[4 * jj + 2 * hh + 1] * (hh ? rr1 : rr0);
                const uint32_t G = pack2(fmaf(f0, tanh_fast(f0), f0), fmaf(f1, tanh_fast(f1), f1));
                const uint32_t s2 = __byte_perm(sv[jj].x, sv[jj].y, hh ? 0x7632 : 0x5410);
                asm("fma.rn.bf16x2 %0, %1, %2, %0;" : "+r"(xr[j >> 1][i]) : "r"(s2), "r"(G));
            }
            stsm4(xo + (j >> 3) * 8192 + ((((j & 7) + (lane >> 4)) ^ (lane & 7)) << 4), xr[j >> 1][0], xr[j >> 1][1], xr[j >> 1][2], xr[j >> 1][3]);
        }
        __syncwarp();
        {
            const uint32_t rr = row + ((lane >> 4) << 4), la = sb + OFF_XO + rr * 128 + ((lane >> 3) & 1) * 8192;
            uint4* dst = (uint4*)(P.out + (64 * tau + rr) * DM + 128 * dg) + (lane & 15);
            uint4 v[8];
            #pragma unroll
            for (int i = 0; i < 8; i++) v[i] = lds128(la + i * 128 + (((lane & 7) ^ i) << 4));
            #pragma unroll
            for (int i = 0; i < 8; i++) dst[i * 64] = v[i];
        }
        STAMP(7); GSTAMP(23);
    }
}

__device__ __forceinline__ float2 cexp_p(float re2, float im, float p) {
    float sn, cs;
    const float mag = ex2(re2 * p), th = im * p;
    asm("sin.approx.ftz.f32 %0, %1;" : "=f"(sn) : "f"(th));
    asm("cos.approx.ftz.f32 %0, %1;" : "=f"(cs) : "f"(th));
    return make_float2(mag * cs, mag * sn);
}
struct SsmRaw { unsigned short la, ai, cr, ci, ldt, dsk; };
__device__ __forceinline__ unsigned short ldu16(const void* p) { unsigned short v; asm volatile("ld.global.nc.u16 %0, [%1];" : "=h"(v) : "l"(p)); return v; }
__device__ __forceinline__ float2 cmul(float2 a, float2 b) { return make_float2(fmaf(a.x, b.x, -a.y * b.y), fmaf(a.x, b.y, a.y * b.x)); }
__device__ __forceinline__ float2 csqr(float2 a) { const float t = a.x * a.y; return make_float2(fmaf(a.x, a.x, -a.y * a.y), t + t); }
__device__ __forceinline__ void mma16816(float (&d)[4], const uint32_t (&a)[4], uint32_t b0, uint32_t b1) {
    asm volatile("mma.sync.aligned.m16n8k16.row.col.f32.bf16.bf16.f32 {%0,%1,%2,%3}, {%4,%5,%6,%7}, {%8,%9}, {%0,%1,%2,%3};"
        : "+f"(d[0]), "+f"(d[1]), "+f"(d[2]), "+f"(d[3]) : "r"(a[0]), "r"(a[1]), "r"(a[2]), "r"(a[3]), "r"(b0), "r"(b1));
}

__device__ __forceinline__ void layer_norm(uint32_t sb, uint32_t cb, int w, int lane) {
    const uint32_t bars = sb + OFF_BAR;
    mbar_wait(bars + 8 * (B_LNX + w), 0);
    STAMP(34);
    {
        const uint32_t r0 = cb + CH_LN + (w & 1) * 64 + (lane >> 3) * 1040, ra = r0 + (lane & 7) * 16;
        const float pv = bf_lo(FU(ldsf(r0)));
        float s0 = 0.f, s1 = 0.f, a0 = 0.f, a1 = 0.f;
        #pragma unroll 1
        for (int k = 0; k < 1024; k += 512) {
            uint32_t v[16];
            #pragma unroll
            for (int j = 0; j < 4; j++) *(uint4*)&v[4 * j] = lds128(ra + k + 128 * j);
            #pragma unroll
            for (int i = 0; i < 16; i++) { const float t0 = bf_lo(v[i]) - pv, t1 = bf_hi(v[i]) - pv; s0 += t0; s1 += t1; a0 = fmaf(t0, t0, a0); a1 = fmaf(t1, t1, a1); }
        }
        s0 += s1; a0 += a1;
        #pragma unroll
        for (int o = 4; o; o >>= 1) { s0 += __shfl_xor_sync(0xffffffffu, s0, o); a0 += __shfl_xor_sync(0xffffffffu, a0, o); }
        s0 *= 1.f / DM;
        float sd, ri;
        asm("sqrt.approx.ftz.f32 %0, %1;" : "=f"(sd) : "f"(bf_round(bf_round(fmaxf(fmaf(-s0, s0, a0 * (1.f / DM)), 0.f)) + 1e-5f)));
        asm("rcp.approx.ftz.f32 %0, %1;" : "=f"(ri) : "f"(bf_round(sd)));
        if ((lane & 7) == 0) sts64(sb + OFF_CSUM + (w + 4 * (lane >> 3)) * 8, FU(bf_round(pv + s0)), FU(0.5f * ri));
    }
    STAMP(62);
    bar_sync(2);
    const int r = 4 * ((lane & 7) >> 1) + (lane & 1) + 2 * ((lane >> 3) & 1);
    const uint32_t ad = sb + OFF_CONV + (r & 3) * CH_STRIDE + CH_LN + (r & 1) * 64 + (r >> 2) * 1040 + (16 * w + (lane >> 4)) * 16;
    const uint4 sa = lds128(sb + OFF_CSUM + (lane & 3) * 32), sc = lds128(sb + OFF_CSUM + (lane & 3) * 32 + 16);
    const uint32_t m2[2] = {__byte_perm(sa.x, sa.z, 0x7632), __byte_perm(sc.x, sc.z, 0x7632)};
    const float ri[4] = {2.f * UF(sa.y), 2.f * UF(sa.w), 2.f * UF(sc.y), 2.f * UF(sc.w)};
    #pragma unroll 1
    for (int i = 0; i < 8; i += 4) {
        uint32_t v[4][4];
        #pragma unroll
        for (int j = 0; j < 4; j++)
            asm volatile("ldmatrix.sync.aligned.m8n8.x4.trans.shared.b16 {%0,%1,%2,%3}, [%4];" : "=r"(v[j][0]), "=r"(v[j][1]), "=r"(v[j][2]), "=r"(v[j][3]) : "r"(ad + 32 * (i + j)) : "memory");
        #pragma unroll
        for (int j = 0; j < 4; j++) {
            #pragma unroll
            for (int k = 0; k < 4; k++) {
                uint32_t dv; asm("sub.rn.bf16x2 %0, %1, %2;" : "=r"(dv) : "r"(v[j][k]), "r"(m2[k & 1]));
                v[j][k] = pack2(bf_lo(dv) * ri[2 * (k & 1)], bf_hi(dv) * ri[2 * (k & 1) + 1]);
            }
            sts64(cb + CH_LNT + lane * 8 + (i + j) * 512, v[j][0], v[j][1]); sts64(cb + CH_LNT + lane * 8 + (i + j) * 512 + 256, v[j][2], v[j][3]);
        }
    }
    fence_async_smem();
    mbar_arrive(bars + 8 * B_LN);
    STAMP(16);
}

__device__ __forceinline__ void kernel_gen(uint32_t fs, int lane, const SsmRaw& raw, float (&dacc)[2][3][4]) {
    const float dt = bf_round(ex2(bf_lo(raw.ldt) * 1.4426950408889634f));
    const float re2 = bf_round(ex2(bf_lo(raw.la) * 1.4426950408889634f)) * dt * -1.4426950408889634f, im = bf_lo(raw.ai) * dt;
    const float2 C = make_float2(bf_lo(raw.cr) * (dt + dt), bf_lo(raw.ci) * -(dt + dt));
    STAMP(56);
    const float2 y1 = cexp_p(re2, -im, 1.f), y256 = cexp_p(re2, -im, 256.f), z64 = cexp_p(re2, im, 64.f);
    const uint32_t fm = fs + (lane >> 3) * 144 + (lane & 7) * 16;
#define PK(v) pack2((v).x, (v).y)
    const float2 y2 = csqr(y1), y4 = csqr(y2), y8 = csqr(y4);
    const float2 l1 = cmul(C, y1), l2 = cmul(C, y2), l3 = cmul(l1, y2);
    stsm4(fm, PK(C), PK(l1), PK(l2), PK(l3));
    stsm4(fm + 4 * 144, PK(cmul(C, y4)), PK(cmul(l1, y4)), PK(cmul(l2, y4)), PK(cmul(l3, y4)));
    const float2 t0 = cmul(C, y256), t1 = cmul(t0, y256), t2 = cmul(t1, y256), t3_ = cmul(t2, y256);
    const float2 u1 = cmul(t0, y2), u2 = cmul(u1, y2), u3 = cmul(u2, y2);
    stsm4(fm + 8 * 144, PK(t0), PK(u1), PK(u2), PK(u3));
    stsm4(fm + 12 * 144, PK(t1), PK(cmul(t1, y4)), PK(t2), PK(cmul(t2, y4)));
    const float2 v0 = cmul(t3_, y8), v1 = cmul(v0, y256), v2 = cmul(v1, y256), v3 = cmul(v2, y256);
    stsm4(fm + 16 * 144, PK(v0), PK(v1), PK(v2), PK(v3));
    stsf(fs + lane * 4 + 20 * 144, UF(PK(t3_)));
    STAMP(57);
    const uint32_t ldb = fs + (lane & 7) * 144 + ((lane >> 3) & 1) * 16 + (lane >> 4) * 8 * 144;
    const float p8 = (float)(2 * (lane & 28));
    __syncwarp();
    #pragma unroll 1
    for (int ks = 0; ks < 4; ks++) {
        uint32_t b01[4], b2[2], a0[4], a1[4];
        ldsm4(b01, ldb + ks * 32);
        asm volatile("ldmatrix.sync.aligned.m8n8.x2.shared.b16 {%0,%1}, [%2];" : "=r"(b2[0]), "=r"(b2[1]) : "r"(ldb + 16 * 144 + ks * 32) : "memory");
        #pragma unroll
        for (int mh = 0; mh < 2; mh++) {
            const int src = 8 * ks + 4 * mh + (lane & 3);
            const float2 z = make_float2(__shfl_sync(0xffffffffu, z64.x, src), __shfl_sync(0xffffffffu, z64.y, src));
            const float2 R0 = cexp_p(__shfl_sync(0xffffffffu, re2, src), __shfl_sync(0xffffffffu, im, src), p8);
            const float2 R1 = cmul(R0, z), R2 = cmul(R1, z), R3 = cmul(R2, z);
            a0[2 * mh] = PK(R0); a0[2 * mh + 1] = PK(R1); a1[2 * mh] = PK(R2); a1[2 * mh + 1] = PK(R3);
        }
        mma16816(dacc[0][0], a0, b01[0], b01[1]); mma16816(dacc[1][0], a1, b01[0], b01[1]);
        mma16816(dacc[0][1], a0, b01[2], b01[3]); mma16816(dacc[1][1], a1, b01[2], b01[3]);
        mma16816(dacc[0][2], a0, b2[0], b2[1]);   mma16816(dacc[1][2], a1, b2[0], b2[1]);
    }
#undef PK
    STAMP(58);
}

__device__ __forceinline__ void aux_role(uint32_t sb, int w, float (&dacc)[2][3][4], float dsk) {
    const int lane = threadIdx.x & 31, q = lane & 3, g = lane >> 2;
    const int c = blockIdx.x;
    const uint32_t bars = sb + OFF_BAR;
    if (c >= 128) { mbar_arrive(bars + 8 * B_LN); return; }
    {
        const uint32_t cb = sb + OFF_CONV + w * CH_STRIDE;
        layer_norm(sb, cb, w, lane);
        {
            uint4 v[2][3];
            #pragma unroll
            for (int i = 0; i < 3; i++) v[0][i] = lds128(cb + CH_PART + lane * 16 + i * 512);
            #pragma unroll
            for (int k = 0; k < 6; k++) {
                #pragma unroll
                for (int i = 0; i < 3; i++) if (k < 5) v[(k + 1) & 1][i] = lds128(cb + CH_PART + lane * 16 + (k + 1) * 1536 + i * 512);
                #pragma unroll
                for (int i = 0; i < 3; i++) {
                    float* d = &dacc[0][0][0] + 12 * (k & 1) + 4 * i;
                    d[0] += UF(v[k & 1][i].x); d[1] += UF(v[k & 1][i].y); d[2] += UF(v[k & 1][i].z); d[3] += UF(v[k & 1][i].w);
                }
            }
        }
        __syncwarp();
        STAMP(18);
        const uint32_t sF = cb + CH_A3, sG = cb + CH_G;
        if (lane == 0) dacc[0][0][0] += dsk;
        if (lane < 10) sts128(sG + 128 + (lane & 1) * 208 + (lane >> 1) * 16, 0, 0, 0, 0);
        const uint32_t f0 = sF + (8 * g + 2 * q) * 4, f1 = sF + ((q < 2) ? 256 + 4 * g + 2 * q : 256 + 2 * g + 64 * q) * 4, st1 = (q < 2) ? 128 : 64;
        const uint32_t ga = sG + ((g & 1) ? 0 : 208) + (63 - (g >> 1) - 32 * q) * 2;
        #pragma unroll
        for (int i = 0; i < 4; i++) {
            const int mu = i >> 1, hh = i & 1;
            sts64(f0 + i * 256, FU(dacc[mu][0][2 * hh]), FU(dacc[mu][0][2 * hh + 1]));
            sts64(f1 + i * st1, FU(dacc[mu][1][2 * hh]), FU(dacc[mu][1][2 * hh + 1]));
            const uint32_t pk = pack2(dacc[mu][2][2 * hh], dacc[mu][2][2 * hh + 1]);
            if (q < 2) { sts16(ga - 8 * i, pk & 0xffff); sts16(ga - 8 * i - 32, pk >> 16); }
        }
        if (lane == 2) stsf(sF + 2048, dacc[0][2][0]);
        STAMP(19);
        bar_sync(2);
    }
    const int u = min(lane, 30) - 15, r2 = (u + ((u >> 1) & 1)) >> 1, r4 = (u + 1 + ((u >> 2) & 1)) >> 2, xt = 1024 + 16 * w + u;
    const uint32_t o0 = CH_A3 + 4 * (w == 0 ? u : w == 1 ? 256 + r2 : 256 + 64 * w + r4), ost = w == 0 ? 64 : w == 1 ? 32 : 16;
    const uint32_t oa0 = u >= 0 || w == 3 ? o0 : CH_A3 + 4 * (w == 1 ? 256 + u : w == 2 ? 384 + r2 : 0);
    const uint32_t ot = CH_A3 + 4 * min(512, 256 + ((xt + 1 + ((xt >> 2) & 1)) >> 2));
    const int kap = (lane >> 4) * 8 + ((lane >> 1) & 7), gam = lane & 1, hh = w >> 1, wp = w & 1;
    const uint32_t oa = CH_U + wp * UPLANE + (127 - 4 * kap - 2 * gam - hh) * 16;
    const uint32_t ob = CH_U + (wp ^ 1) * UPLANE + (128 - wp - 4 * kap - 2 * gam - hh) * 16;
    const uint32_t od = CH_A3 + (4 * wp + hh) * 512 + (kap >> 3) * 256 + (kap & 7) * 16 + gam * 8;
    const int tid = threadIdx.x & 127;
    const uint32_t og = CH_G + (tid >= 24) * 16 + min(tid, 47) * 8, cend = sb + OFF_CONV + 3 * CH_STRIDE;
    {
        float nx[17]; uint2 n0, n1;
#define LDT(b) nx[0] = ldsf((b) + oa0); nx[16] = ldsf((b) + ot); _Pragma("unroll") for (int s = 1; s < 16; s++) nx[s] = ldsf((b) + o0 + s * ost); n0 = lds64((b) + og); n1 = lds64((b) + og + 8)
        LDT(sb + OFF_CONV);
        #pragma unroll 1
        for (uint32_t cb = sb + OFF_CONV; cb <= cend; cb += CH_STRIDE) {
            float kv[17];
            #pragma unroll
            for (int s = 0; s < 17; s++) kv[s] = nx[s];
            if (tid < 48) sts128(cb + CH_B3 + tid * 16, n0.x, n0.y, n1.x, n1.y);
            LDT(min(cb + CH_STRIDE, cend));
            if (u < 0 && w == 0) kv[0] = 0.f;
            if (xt > 1028) kv[16] = 0.f;
            uint32_t o[17];
            #pragma unroll
            for (int s = 0; s < 17; s++) o[s] = pack2(kv[s], __shfl_up_sync(0xffffffffu, kv[s], 1));
            if (lane > 0 && lane < 31) {
                const uint32_t ta = cb + CH_T + (lane - 1) * 280;
                #pragma unroll
                for (int s2 = 0; s2 < 8; s2++) sts64(ta + 64 * w + s2 * 8, o[2 * s2], o[2 * s2 + 1]);
                stsf(ta + 256 + 4 * w, UF(o[16]));
            }
        }
#undef LDT
    }
    STAMP(61);
    mbar_wait(bars + 8 * B_U, 0);
    if (lane < 8) sts128(sb + OFF_CONV + w * CH_STRIDE + CH_U + 2048 + (lane & 4) * (UPLANE / 4) + (lane & 3) * 16, 0, 0, 0, 0);
    bar_sync(2);
    STAMP(17);
    uint2 n0 = lds64(sb + OFF_CONV + ob + 24), n3 = lds64(sb + OFF_CONV + oa);
    uint4 n1 = lds128(sb + OFF_CONV + oa + 16), n2 = lds128(sb + OFF_CONV + ob);
    #pragma unroll 1
    for (uint32_t cb = sb + OFF_CONV; cb <= cend; cb += CH_STRIDE) {
        const uint32_t r[12] = {n0.x, n0.y, n1.x, n1.y, n1.z, n1.w, n2.x, n2.y, n2.z, n2.w, n3.x, n3.y}, nb = min(cb + CH_STRIDE, cend);
        n0 = lds64(nb + ob + 24); n3 = lds64(nb + oa); n1 = lds128(nb + oa + 16); n2 = lds128(nb + ob);
        float p[24];
        p[0] = 0.f; p[1] = bf_lo(r[0]);
        #pragma unroll
        for (int i = 2; i < 24; i++) p[i] = p[i - 1] + ((i & 1) ? bf_lo(r[i >> 1]) : bf_hi(r[(i - 1) >> 1]));
        #pragma unroll
        for (int i = 0; i < 8; i += 4) {
            sts64(cb + od + i * 256, pack2(p[i + 9] - p[i], p[i + 10] - p[i + 1]), pack2(p[i + 11] - p[i + 2], p[i + 12] - p[i + 3]));
            sts64(cb + od + i * 256 + 128, pack2(p[i + 16] - p[i + 9], p[i + 17] - p[i + 10]), pack2(p[i + 18] - p[i + 11], p[i + 19] - p[i + 12]));
        }
    }
    fence_async_smem();
    mbar_arrive(bars + 8 * B_CONV);
    STAMP(21);
}

__device__ __forceinline__ void store_h(uint32_t sb, const Params& P, const Maps& M, int V, int tg, int fb) {
    const uint32_t bars = sb + OFF_BAR;
    mbar_wait(bars + 8 * (B_EPI + V), 0);
    STAMP2(3 + 2 * V);
    asm volatile("cp.async.bulk.tensor.3d.global.shared::cta.bulk_group [%0, {%2, %3, %4}], [%1];"
        :: "l"(&M.hst[V]), "r"(sb + OFF_X + V * 2 * XBUF), "r"(0), "r"(43 * tg + 21 * V), "r"(8 * fb) : "memory");
    flag_signal(P.flags, F_H + 2 * tg + V);
    mbar_arrive(bars + 8 * (B_STG + V));
    STAMP2(4 + 2 * V);
}

__global__ void __launch_bounds__(512, 1)
fused_kernel(const __grid_constant__ Params P, const __grid_constant__ Maps M) {
    extern __shared__ __align__(1024) uint8_t smem_raw[];
    const uint32_t sb = smem_u32(smem_raw);
    const uint32_t bars = sb + OFF_BAR;
    const int warp = __shfl_sync(0xffffffffu, threadIdx.x >> 5, 0);
    const int c = blockIdx.x, tg = c / 22, fb = c - 22 * tg;
    SsmRaw raw;
    {
        const int d = min(4 * c + (warp & 3), DM - 1), o = d * 128 + (warp >> 2) * 32 + (threadIdx.x & 31);
        raw.la = ldu16(P.logA + o); raw.ai = ldu16(P.Aim + o); raw.cr = ldu16(P.Cr + o); raw.ci = ldu16(P.Ci + o);
        raw.ldt = ldu16(P.logdt + d); raw.dsk = ldu16(P.Dskip + d);
    }
    if (elect_one()) {
        if (warp == 0) { STAMP(24); GSTAMP(22); }
        asm volatile("" :: "l"(((const uint64_t*)&P)[warp < 15 ? warp : 0]));
        if (warp < 11) asm volatile("prefetch.tensormap [%0];" :: "l"(&M.x[0] + warp) : "memory");
        #pragma unroll
        for (int k = 0; k < 4; k++) {
            const int i = 16 * k + ((warp + 4) & 15);
            const uint32_t cnt = i >= B_LNX ? 1 : i >= B_CONV ? 128 : ((0xf0ull >> i) & 1) ? 8 : ((0xff0000ull >> i) & 1) ? 2 : ((0x3e00ff00f000ull >> i) & 1) ? 4 : 1;
            asm volatile("mbarrier.init.shared::cta.b64 [%0], %1;" :: "r"(bars + 8 * i), "r"(cnt) : "memory");
        }
        asm volatile("fence.mbarrier_init.release.cluster; fence.proxy.async.shared::cta;" ::: "memory");
        if (warp == 12 || warp == 13) {
            const uint32_t s = warp - 12;
            mbar_expect(bars + 8 * (B_FULLW + s), 16384);
            tma2d(sb + OFF_W + s * 16384, &M.wg, 64 * fb, 64 * s, bars + 8 * (B_FULLW + s));
            tma2d(sb + OFF_W + s * 16384 + 8192, &M.wu, 64 * fb, 64 * s, bars + 8 * (B_FULLW + s));
            STAMP(31);
        } else if (warp >= 4 && warp < 7) {
            const uint32_t s = warp - 4, V = s >> 1;
            mbar_expect(bars + 8 * (B_FULLX + s), (168 + 8 * V) * 128);
            tma2d(sb + OFF_X + s * XBUF, &M.x[V], 64 * (s & 1), TOKG * tg + 168 * V, bars + 8 * (B_FULLX + s));
        } else if ((warp >> 2) == 2 && c < 128) {
            const int w = warp & 3;
            mbar_expect(bars + 8 * (B_LNX + w), 4096);
            #pragma unroll
            for (int i = 0; i < 4; i++)
                bulk_load(sb + OFF_CONV + w * CH_STRIDE + CH_LN + (w & 1) * 64 + i * 1040,
                          P.x + (16 * (c & ~1) + 8 * (c & 1) + 16 + w + 4 * (i & 1) - 8 * (i & 2)) * DM, 1024, bars + 8 * (B_LNX + w));
        }
        if (sb & 1023) __trap();
    }
    if (warp < 4) sts128(sb + OFF_X + (warp >> 1) * XBUF + 168 * 128 + (threadIdx.x & 63) * 16, 0x3f803f80u, 0x3f803f80u, 0x3f803f80u, 0x3f803f80u);
    float dacc[2][3][4];
    #pragma unroll
    for (int i = 0; i < 24; i++) (&dacc[0][0][0])[i] = 0.f;
    if (c < 128) {
        const int wg = warp >> 2;
        const uint32_t fs = sb + OFF_CONV + (warp & 3) * CH_STRIDE + (wg == 2 ? CH_LNT : CH_PART + min(wg, 2) * CH_PSZ);
        kernel_gen(fs, threadIdx.x & 31, raw, dacc);
        if (wg != 2) {
            __syncwarp();
            #pragma unroll
            for (int i = 0; i < 6; i++) { const float* d = &dacc[0][0][0] + 4 * i; sts128(fs + (threadIdx.x & 31) * 16 + i * 512, FU(d[0]), FU(d[1]), FU(d[2]), FU(d[3])); }
        }
    }
    if (warp < 4) fence_async_smem();
    __syncthreads();
    if (warp < 8) {
        asm volatile("setmaxnreg.inc.sync.aligned.u32 208;");
        consumer(sb, warp, P, M);
        asm volatile("nanosleep.u32 1;");
    } else if (warp < 12) {
        asm volatile("setmaxnreg.dec.sync.aligned.u32 72;");
        STAMP(32);
        aux_role(sb, warp - 8, dacc, bf_lo(raw.dsk));
        asm volatile("nanosleep.u32 2;");
    } else {
        asm volatile("setmaxnreg.dec.sync.aligned.u32 24;");
        const int tau = c >> 2, dg = c & 3;
        if (elect_one()) {
            if (warp < 15) {
                if (warp == 12) {
                    #pragma unroll 1
                    for (int st = 2; st < 8; st++) {
                        const uint32_t s = st & 3, fb_ = bars + 8 * (B_FULLW + s);
                        mbar_wait(bars + 8 * (B_EMPTYW + s), (st >> 2) ^ 1);
                        mbar_expect(fb_, 16384);
                        tma2d(sb + OFF_W + s * 16384, &M.wg, 64 * fb, 64 * st, fb_);
                        tma2d(sb + OFF_W + s * 16384 + 8192, &M.wu, 64 * fb, 64 * st, fb_);
                    }
                } else {
                    const int V = warp - 13;
                    #pragma unroll 1
                    for (int st = 2 - V; st < 8; st++) {
                        const uint32_t s = 2 * V + (st & 1);
                        mbar_wait(bars + 8 * (B_EMPTYX + s), ((st >> 1) & 1) ^ 1);
                        mbar_expect(bars + 8 * (B_FULLX + s), (168 + 8 * V) * 128);
                        tma2d(sb + OFF_X + s * XBUF, &M.x[V], 64 * st, TOKG * tg + 168 * V, bars + 8 * (B_FULLX + s));
                    }
                }
                if (warp == 14) store_h(sb, P, M, 1, tg, fb);
                if (c < 128 && warp < 14) {
                    if (warp == 13) {
                        mbar_wait(bars + 8 * (B_STG + 1), 0);
                        #pragma unroll 1
                        for (int o = 8 * tau; o < 8 * tau + 8; o += 7) flag_wait(P.flags, F_H + 2 * (o / 43) + ((o % 43) >= 21), 22);
                        mbar_arrive(bars + 8 * B_HF);
                        STAMP(25);
                    }
                    #pragma unroll 1
                    for (int st = 0; st < 22; st += (st < 6 || (st == 6 && warp == 13)) ? 1 : 2) {
                        const int rd = (st >= 7) + (st >= 14) + (st >= 21), sd = st - 7 * rd;
                        const uint32_t fb_ = bars + 8 * (B_FULLD + sd);
                        if (rd) mbar_wait(bars + 8 * (B_EMPTYD + sd), (rd & 1) ^ 1);
                        else if (warp == 12 || st == 6) mbar_wait(bars + 8 * (uint32_t)((0x3623070d060504ull >> (8 * st)) & 0xff), st < 5);
                        if (st >= 10 && st < 21) STAMP2(31 + st);
                        if (rd || warp == 13) {
                            mbar_expect(fb_, 8192);
                            asm volatile("cp.async.bulk.tensor.5d.shared::cluster.global.mbarrier::complete_tx::bytes [%0], [%1, {%3, %3, %3, %4, %5}], [%2];"
                                :: "r"(sb + h_slot(sd)), "l"(&M.hld), "r"(fb_), "r"(0), "r"(2 * tau), "r"(8 * st) : "memory");
                        }
                        if (rd || warp == 12) {
                            const uint32_t da = sb + wd_slot(sd);
                            mbar_expect(fb_, 16384);
                            tma2d(da, &M.wd, 128 * dg, 64 * st, fb_);
                            tma2d(da + 8192, &M.wd, 128 * dg + 64, 64 * st, fb_);
                        }
                    }
                } else if (c < 128) {
                    mbar_wait(bars + 8 * (B_SIG + 1), 0);
                    mbar_expect(bars + 8 * B_XO, 32768);
                    tma2d(sb + OFF_XO, &M.xo, 128 * dg, 64 * tau, bars + 8 * B_XO);
                    tma2d(sb + OFF_XO + 8192, &M.xo, 128 * dg + 64, 64 * tau, bars + 8 * B_XO);
                    mbar_wait(bars + 8 * B_SST, 0);
                    flag_wait(P.flags, F_S + dg, 64);
                    STAMP(26);
                    asm volatile("cp.async.bulk.tensor.5d.shared::cluster.global.mbarrier::complete_tx::bytes [%0], [%1, {%3, %3, %3, %4, %5}], [%2];"
                        :: "r"(sb + OFF_SI), "l"(&M.sld), "r"(bars + 8 * B_XO), "r"(0), "r"(8 * dg), "r"(2 * tau) : "memory");
                    mbar_wait(bars + 8 * B_HF, 0);
                    exit_count(P.flags);
                }
            } else {
                if (c < 128) {
                    asm volatile("cp.async.bulk.prefetch.L2.global [%0], %1;" :: "l"((const char*)P.Wg + 256 * FF * 2 + c * 5504), "r"(5504) : "memory");
                    asm volatile("cp.async.bulk.prefetch.L2.global [%0], %1;" :: "l"((const char*)P.Wu + 256 * FF * 2 + c * 5504), "r"(5504) : "memory");
                }
                mbar_wait(bars + 8 * B_LN, 0);
                STAMP2(0);
                if (c < 128) {
                    #pragma unroll 1
                    for (int i = 0; i < 4; i++)
                        asm volatile("cp.async.bulk.tensor.2d.global.shared::cta.bulk_group [%0, {%2, %3}], [%1];"
                            :: "l"(&M.xt), "r"(sb + OFF_CONV + i * CH_STRIDE + CH_LNT), "r"((c & 1) * 1024 + (126 - (c & ~1)) * 8), "r"(128 * i) : "memory");
                    #pragma unroll 1
                    for (int i = 0; i < 2; i++) bulk_store(P.st + 16 * (c & ~1) + 8 * (c & 1) + 16 - 16 * i, sb + OFF_CSUM + 64 * i, 64);
                    asm volatile("cp.async.bulk.prefetch.L2.global [%0], %1;" :: "l"(P.Wd + c * (FF * DM / 128)), "r"(FF * DM / 64) : "memory");
                }
                STAMP2(1);
                flag_signal(P.flags, F_A);
                STAMP2(2);
                flag_wait(P.flags, F_A, NCTA);
                STAMP(20);
                mbar_expect(bars + 8 * B_STATS, TOKG * 8);
                bulk_load(sb + OFF_ST, P.st + TOKG * tg, TOKG * 8, bars + 8 * B_STATS);
                if (c < 128) {
                    mbar_expect(bars + 8 * B_U, 8 * 2048);
                    #pragma unroll 1
                    for (int i = 0; i < 8; i++)
                        bulk_load(sb + OFF_CONV + (i >> 1) * CH_STRIDE + CH_U + (i & 1) * UPLANE, P.xnT + 4 * c * 256 + i * 128, 2048, bars + 8 * B_U);
                } else exit_count(P.flags);
                store_h(sb, P, M, 0, tg, fb);
                if (c < 128) {
                    #pragma unroll 1
                    for (int V = 0; V < 2; V++) {
                        mbar_wait(bars + 8 * (B_SIG + V), 0);
                        STAMP2(7 + 2 * V);
                        bulk_store(P.S + (2 * c + V) * 1024, sb + OFF_CONV + V * OFF_SST, 8192);
                        flag_signal(P.flags, F_S + (c >> 5));
                        STAMP2(8 + 2 * V);
                    }
                    mbar_arrive(bars + 8 * B_SST);
                }
            }
            asm volatile("nanosleep.u32 0;");
        }
    }
}

typedef CUresult (*EncodeFn)(CUtensorMap*, CUtensorMapDataType, cuuint32_t, void*, const cuuint64_t*, const cuuint64_t*, const cuuint32_t*,
                             const cuuint32_t*, CUtensorMapInterleave, CUtensorMapSwizzle, CUtensorMapL2promotion, CUtensorMapFloatOOBfill);

void make_map(EncodeFn enc, CUtensorMap* m, const void* ptr, int rank, const cuuint64_t* dims, const cuuint64_t* strides, const cuuint32_t* box, bool swz, bool wide = false) {
    const cuuint32_t es[5] = {1, 1, 1, 1, 1};
    enc(m, CU_TENSOR_MAP_DATA_TYPE_BFLOAT16, rank, (void*)ptr, dims, strides, box, es, CU_TENSOR_MAP_INTERLEAVE_NONE,
        swz ? CU_TENSOR_MAP_SWIZZLE_128B : CU_TENSOR_MAP_SWIZZLE_NONE, wide ? CU_TENSOR_MAP_L2_PROMOTION_L2_256B : CU_TENSOR_MAP_L2_PROMOTION_L2_128B, CU_TENSOR_MAP_FLOAT_OOB_FILL_NONE);
}
void make_map2(EncodeFn enc, CUtensorMap* m, const void* ptr, cuuint64_t inner, cuuint64_t outer, cuuint32_t rows) {
    const cuuint64_t dims[2] = {inner, outer}, strides[1] = {inner * 2};
    const cuuint32_t box[2] = {64, rows};
    make_map(enc, m, ptr, 2, dims, strides, box, true, rows > 64);
}

}

extern "C" void kernel_launch(void* const* d_in, const int* in_sizes, int n_in, void* d_out, int out_size) {
    (void)in_sizes; (void)n_in; (void)out_size;
    static EncodeFn enc = nullptr;
    static void *hptr, *p_xnT, *p_st, *p_S, *p_flags;
    if (!enc) {
        cudaDriverEntryPointQueryResult qr;
        cudaGetDriverEntryPoint("cuTensorMapEncodeTiled", (void**)&enc, cudaEnableDefault, &qr);
        cudaFuncSetAttribute(fused_kernel, cudaFuncAttributeMaxDynamicSharedMemorySize, SMEM_BYTES);
        cudaGetSymbolAddress(&hptr, g_H); cudaGetSymbolAddress(&p_xnT, g_xnT); cudaGetSymbolAddress(&p_st, g_st);
        cudaGetSymbolAddress(&p_S, g_S); cudaGetSymbolAddress(&p_flags, g_flags);
    }
    Params P;
    P.x = (const __nv_bfloat16*)d_in[0]; P.logA = (const __nv_bfloat16*)d_in[1]; P.Aim = (const __nv_bfloat16*)d_in[2];
    P.Cr = (const __nv_bfloat16*)d_in[3]; P.Ci = (const __nv_bfloat16*)d_in[4]; P.logdt = (const __nv_bfloat16*)d_in[5];
    P.Dskip = (const __nv_bfloat16*)d_in[6];
    P.Wg = (const __nv_bfloat16*)d_in[8]; P.Wu = (const __nv_bfloat16*)d_in[9]; P.Wd = (const __nv_bfloat16*)d_in[10]; P.out = (__nv_bfloat16*)d_out; P.xnT = (uint4*)p_xnT; P.st = (float2*)p_st; P.S = (uint2*)p_S; P.flags = (unsigned*)p_flags;
    Maps M;
    make_map2(enc, &M.x[0], d_in[0], DM, SEQ, 168); make_map2(enc, &M.x[1], d_in[0], DM, SEQ, 176);
    make_map2(enc, &M.xo, d_in[0], DM, SEQ, 64);
    make_map2(enc, &M.wg, d_in[8], FF, DM, 64);     make_map2(enc, &M.wu, d_in[9], FF, DM, 64);
    make_map2(enc, &M.wd, d_in[10], DM, FF, 64);
    for (int v = 0; v < 2; v++) {
        const cuuint64_t dims[3] = {64, 256, 172}, strides[2] = {128, 32768};
        const cuuint32_t box[3] = {64, (cuuint32_t)(21 + v), 8};
        make_map(enc, &M.hst[v], hptr, 3, dims, strides, box, false);
    }
    {
        const cuuint64_t dims[2] = {2048, 512}, strides[1] = {4096};
        const cuuint32_t box[2] = {16, 128};
        make_map(enc, &M.xt, p_xnT, 2, dims, strides, box, false);
    }
    {
        const cuuint64_t dims[5] = {64, 2, 4, 32, 64}, strides[4] = {4 * 8192, 8192, 8 * 8192, 128};
        const cuuint32_t box[5] = {64, 2, 4, 8, 2};
        make_map(enc, &M.sld, p_S, 5, dims, strides, box, true);
    }
    {
        const cuuint64_t dims[5] = {64, 2, 2, 64, 172}, strides[4] = {256, 128, 512, 32768};
        const cuuint32_t box[5] = {64, 2, 2, 2, 8};
        make_map(enc, &M.hld, hptr, 5, dims, strides, box, false);
    }
    fused_kernel<<<NCTA, 512, SMEM_BYTES>>>(P, M);
}
```

```cpp
#include <cuda_runtime.h>
#include <cuda_bf16.h>
#include <cuda.h>
#include <stdint.h>

#define PROF 0

namespace {

constexpr int SEQ = 2048, DM = 512, FF = 1376;
constexpr int NCTA = 132;
#define GMARGIN 550
#define SIGK 3
#define ALIGN2 1
constexpr int TOKG = 344;

constexpr uint32_t OFF_W = 0;
constexpr uint32_t XBUF = 22528;
constexpr uint32_t OFF_X = 65536;
constexpr uint32_t OFF_CONV = 155648;
constexpr uint32_t CH_STRIDE = 17536;
constexpr uint32_t CH_T = 0;
constexpr uint32_t CH_A3 = 8448;
constexpr uint32_t CH_B3 = 12544;
constexpr uint32_t CH_U = 13312;
constexpr uint32_t CH_G = CH_A3 + 2064;
constexpr uint32_t UPLANE = 2112;
constexpr uint32_t CH_LN = 0, CH_PART = 4224, CH_PSZ = 3072, CH_LNT = 13440;
constexpr uint32_t OFF_SST = 60416;
constexpr uint32_t OFF_XO = 191488, OFF_SI = 207872;
constexpr uint32_t OFF_ST = 225792;
constexpr uint32_t OFF_CSUM = 228544;
constexpr uint32_t OFF_BAR = 229056;
constexpr uint32_t SMEM_BYTES = 229568;

enum {
    B_FULLW = 0, B_EMPTYW = 4, B_FULLX = 8, B_EMPTYX = 12, B_FULLD = 16, B_EMPTYD = 24,
    B_U = 32, B_XO = 33, B_S = 34, B_STG = 35, B_HF = 37, B_STATS = 38, B_LNS = 39, B_SST = 40,
    B_TURN = 43,
    B_CONV = 46, B_LN = 50, B_CS = 51, B_EPI = 52, B_SIG = 54,
    B_LNX = 60
};
enum { F_A = 0, F_H = 1, F_S = 13, F_EXIT = 17, F_G = 18, F_COUNT = 19 };

__device__ uint4 g_xnT[DM * 256];
__device__ float2 g_st[6 * TOKG];
__device__ uint4 g_H[172 * 256 * 8];
__device__ uint2 g_S[256 * 1024];
__device__ __align__(128) unsigned g_flags[F_COUNT * 32];
#define STAMP(i) do {} while (0)
#define GSTAMP(i) do {} while (0)
#define STAMP2(i) do {} while (0)

__device__ __forceinline__ uint32_t smem_u32(const void* p) { return (uint32_t)__cvta_generic_to_shared(p); }
__device__ __forceinline__ void mbar_expect(uint32_t bar, uint32_t bytes) { asm volatile("mbarrier.arrive.expect_tx.shared::cta.b64 _, [%0], %1;" :: "r"(bar), "r"(bytes) : "memory"); }
__device__ __forceinline__ void mbar_arrive(uint32_t bar) { asm volatile("mbarrier.arrive.shared::cta.b64 _, [%0];" :: "r"(bar) : "memory"); }
__device__ __forceinline__ void mbar_wait(uint32_t bar, uint32_t parity) {
    asm volatile("{.reg .pred p; .reg .u32 n; mov.u32 n, 0x20000;\n"
                 "LW: mbarrier.try_wait.parity.shared::cta.b64 p, [%0], %1;\n"
                 "sub.u32 n, n, 1; setp.eq.or.u32 p, n, 0, p; @!p bra LW;}" :: "r"(bar), "r"(parity) : "memory");
}
__device__ __forceinline__ void mbar_arrive_if(uint32_t bar, uint32_t pred) {
    asm volatile("{.reg .pred p; setp.ne.u32 p, %1, 0; @p mbarrier.arrive.shared::cta.b64 _, [%0];}" :: "r"(bar), "r"(pred) : "memory");
}
__device__ __forceinline__ bool elect_one() { uint32_t p; asm volatile("{.reg .pred P; elect.sync _|P, 0xffffffff; selp.u32 %0, 1, 0, P;}" : "=r"(p)); return p; }
__device__ __forceinline__ void tma2d(uint32_t dst, const CUtensorMap* m, int c0, int c1, uint32_t bar) {
    asm volatile("cp.async.bulk.tensor.2d.shared::cluster.global.mbarrier::complete_tx::bytes [%0], [%1, {%3, %4}], [%2];"
        :: "r"(dst), "l"(m), "r"(bar), "r"(c0), "r"(c1) : "memory");
}
__device__ __forceinline__ void bulk_load(uint32_t dst, const void* src, uint32_t bytes, uint32_t bar) {
    asm volatile("cp.async.bulk.shared::cluster.global.mbarrier::complete_tx::bytes [%0], [%1], %2, [%3];" :: "r"(dst), "l"(src), "r"(bytes), "r"(bar) : "memory");
}
__device__ __forceinline__ void bulk_store(void* dst, uint32_t src, uint32_t bytes) {
    asm volatile("cp.async.bulk.global.shared::cta.bulk_group [%0], [%1], %2;" :: "l"(dst), "r"(src), "r"(bytes) : "memory");
}
__device__ __forceinline__ void fence_async_smem() { asm volatile("fence.proxy.async.shared::cta;" ::: "memory"); }
__device__ __forceinline__ void flag_wait(unsigned* g_flags, int f, unsigned target) {
    asm volatile("{.reg .pred p; .reg .u32 n, v; mov.u32 n, 0x40000;\n"
                 "LF: ld.acquire.gpu.global.u32 v, [%0]; setp.ge.u32 p, v, %1; @p bra LD;\n"
                 "sub.u32 n, n, 1; setp.ne.u32 p, n, 0; @p bra LF; trap;\nLD: }"
                 :: "l"(g_flags + f * 32), "r"(target) : "memory");
}
__device__ __forceinline__ void flag_signal(unsigned* g_flags, int f) {
    asm volatile("cp.async.bulk.commit_group; cp.async.bulk.wait_group 0; red.relaxed.gpu.global.add.u32 [%0], 1;" :: "l"(g_flags + f * 32) : "memory");
}
__device__ __forceinline__ void start_vote(unsigned* g_flags) {
    asm volatile("{.reg .u64 t; mov.u64 t, %%globaltimer; add.u64 t, t, %1; red.relaxed.gpu.global.max.u64 [%0 + 8], t; red.relaxed.gpu.global.add.u32 [%0], 1;}"
        :: "l"(g_flags + F_G * 32), "n"(GMARGIN) : "memory");
}
__device__ __forceinline__ void start_wait(unsigned* g_flags) {
    asm volatile("{.reg .pred p; .reg .u32 n, v; .reg .u64 a, t, u; mov.u32 n, 0x40000;\n"
                 "LF: ld.relaxed.gpu.global.v2.u64 {a, t}, [%0]; cvt.u32.u64 v, a; setp.ge.u32 p, v, 256; @p bra LT;\n"
                 "sub.u32 n, n, 1; setp.ne.u32 p, n, 0; @p bra LF; trap;\n"
                 "LT: mov.u64 u, %%globaltimer; sub.u32 n, n, 1; setp.lt.u64 p, u, t; setp.ne.and.u32 p, n, 0, p; @p bra LT;}"
                 :: "l"(g_flags + F_G * 32) : "memory");
}
__device__ __forceinline__ void exit_count(unsigned* g_flags) {
    if (atomicAdd(g_flags + F_EXIT * 32, 1u) == NCTA - 1) {
        #pragma unroll 1
        for (int i = 0; i < F_COUNT; i++) *(uint4*)(g_flags + i * 32) = make_uint4(0, 0, 0, 0);
    }
}
__device__ __forceinline__ void bar_sync(int id) { asm volatile("bar.sync %0, 128;" :: "r"(id) : "memory"); }
__device__ __forceinline__ uint64_t mkdesc(uint32_t addr, uint32_t lbo, uint32_t sbo, uint32_t swz) {
    return (uint64_t)((addr >> 4) | ((lbo >> 4) << 16)) | ((uint64_t)((sbo >> 4) | (swz << 30)) << 32);
}
#define WG_FENCE() asm volatile("wgmma.fence.sync.aligned;" ::: "memory")
#define WG_COMMIT() asm volatile("wgmma.commit_group.sync.aligned;" ::: "memory")
#define WG_WAIT(n) asm volatile("wgmma.wait_group.sync.aligned " #n ";" ::: "memory")
template <int N> __device__ __forceinline__ void fence_acc(float (&d)[N]) {
    #pragma unroll
    for (int i = 0; i < N; i++) asm volatile("" : "+f"(d[i]) :: "memory");
}
template <int N> __device__ __forceinline__ void define_acc(float (&d)[N]) {
    #pragma unroll
    for (int i = 0; i < N; i++) asm volatile("" : "=f"(d[i]));
}
__device__ __forceinline__ uint32_t pack2(float lo, float hi) { uint32_t r; asm("cvt.rn.bf16x2.f32 %0, %1, %2;" : "=r"(r) : "f"(hi), "f"(lo)); return r; }
__device__ __forceinline__ float bf_lo(uint32_t v) { return __uint_as_float(v << 16); }
__device__ __forceinline__ float bf_hi(uint32_t v) { return __uint_as_float(v & 0xffff0000u); }
__device__ __forceinline__ float bf_round(float v) { return bf_hi(pack2(0.f, v)); }
__device__ __forceinline__ float tanh_fast(float v) { float r; asm("tanh.approx.f32 %0, %1;" : "=f"(r) : "f"(v)); return r; }
__device__ __forceinline__ float ex2(float v) { float r; asm("ex2.approx.ftz.f32 %0, %1;" : "=f"(r) : "f"(v)); return r; }
__device__ __forceinline__ uint4 lds128(uint32_t a) { uint4 v; asm volatile("ld.shared.v4.b32 {%0,%1,%2,%3}, [%4];" : "=r"(v.x), "=r"(v.y), "=r"(v.z), "=r"(v.w) : "r"(a)); return v; }
__device__ __forceinline__ uint2 lds64(uint32_t a) { uint2 v; asm volatile("ld.shared.v2.b32 {%0,%1}, [%2];" : "=r"(v.x), "=r"(v.y) : "r"(a)); return v; }
__device__ __forceinline__ float ldsf(uint32_t a) { float v; asm volatile("ld.shared.f32 %0, [%1];" : "=f"(v) : "r"(a)); return v; }
__device__ __forceinline__ void sts128(uint32_t a, uint32_t x, uint32_t y, uint32_t z, uint32_t w) { asm volatile("st.shared.v4.b32 [%0], {%1,%2,%3,%4};" :: "r"(a), "r"(x), "r"(y), "r"(z), "r"(w) : "memory"); }
__device__ __forceinline__ void sts64(uint32_t a, uint32_t x, uint32_t y) { asm volatile("st.shared.v2.b32 [%0], {%1,%2};" :: "r"(a), "r"(x), "r"(y) : "memory"); }
__device__ __forceinline__ void stsf(uint32_t a, float x) { asm volatile("st.shared.f32 [%0], %1;" :: "r"(a), "f"(x) : "memory"); }
__device__ __forceinline__ void sts16(uint32_t a, uint32_t x) { asm volatile("st.shared.b16 [%0], %1;" :: "r"(a), "h"((unsigned short)x) : "memory"); }
__device__ __forceinline__ void stsm4(uint32_t a, uint32_t r0, uint32_t r1, uint32_t r2, uint32_t r3) {
    asm volatile("stmatrix.sync.aligned.m8n8.x4.shared.b16 [%0], {%1,%2,%3,%4};" :: "r"(a), "r"(r0), "r"(r1), "r"(r2), "r"(r3) : "memory");
}
__device__ __forceinline__ void ldsm4(uint32_t (&r)[4], uint32_t a) {
    asm volatile("ldmatrix.sync.aligned.m8n8.x4.shared.b16 {%0,%1,%2,%3}, [%4];" : "=r"(r[0]), "=r"(r[1]), "=r"(r[2]), "=r"(r[3]) : "r"(a) : "memory");
}
#define FU(x) __float_as_uint(x)
#define UF(x) __uint_as_float(x)
__device__ __forceinline__ uint32_t wd_slot(int s) { return (uint32_t)((0xbba8403056201000ull >> (8 * s)) & 0xff) << 10; }
__device__ __forceinline__ uint32_t h_slot(int s) { return (uint32_t)((0xcba0908880787068ull >> (8 * s)) & 0xff) << 10; }

template<int N> __device__ __forceinline__ void wg_rs(float (&d)[64], uint32_t a0, uint32_t a1, uint32_t a2, uint32_t a3, uint64_t db);
template<> __device__ __forceinline__ void wg_rs<128>(float (&d)[64], uint32_t a0, uint32_t a1, uint32_t a2, uint32_t a3, uint64_t db) {
  asm volatile("{.reg .pred p; setp.ne.b32 p, 1, 0; wgmma.mma_async.sync.aligned.m64n128k16.f32.bf16.bf16 {%0,%1,%2,%3,%4,%5,%6,%7,%8,%9,%10,%11,%12,%13,%14,%15,%16,%17,%18,%19,%20,%21,%22,%23,%24,%25,%26,%27,%28,%29,%30,%31,%32,%33,%34,%35,%36,%37,%38,%39,%40,%41,%42,%43,%44,%45,%46,%47,%48,%49,%50,%51,%52,%53,%54,%55,%56,%57,%58,%59,%60,%61,%62,%63}, {%64,%65,%66,%67}, %68, p, 1, 1, 0;}"
    : "+f"(d[0]),"+f"(d[1]),"+f"(d[2]),"+f"(d[3]),"+f"(d[4]),"+f"(d[5]),"+f"(d[6]),"+f"(d[7]),"+f"(d[8]),"+f"(d[9]),"+f"(d[10]),"+f"(d[11]),"+f"(d[12]),"+f"(d[13]),"+f"(d[14]),"+f"(d[15]),"+f"(d[16]),"+f"(d[17]),"+f"(d[18]),"+f"(d[19]),"+f"(d[20]),"+f"(d[21]),"+f"(d[22]),"+f"(d[23]),"+f"(d[24]),"+f"(d[25]),"+f"(d[26]),"+f"(d[27]),"+f"(d[28]),"+f"(d[29]),"+f"(d[30]),"+f"(d[31]),"+f"(d[32]),"+f"(d[33]),"+f"(d[34]),"+f"(d[35]),"+f"(d[36]),"+f"(d[37]),"+f"(d[38]),"+f"(d[39]),"+f"(d[40]),"+f"(d[41]),"+f"(d[42]),"+f"(d[43]),"+f"(d[44]),"+f"(d[45]),"+f"(d[46]),"+f"(d[47]),"+f"(d[48]),"+f"(d[49]),"+f"(d[50]),"+f"(d[51]),"+f"(d[52]),"+f"(d[53]),"+f"(d[54]),"+f"(d[55]),"+f"(d[56]),"+f"(d[57]),"+f"(d[58]),"+f"(d[59]),"+f"(d[60]),"+f"(d[61]),"+f"(d[62]),"+f"(d[63]) : "r"(a0), "r"(a1), "r"(a2), "r"(a3), "l"(db));
}
template<> __device__ __forceinline__ void wg_rs<120>(float (&d)[64], uint32_t a0, uint32_t a1, uint32_t a2, uint32_t a3, uint64_t db) {
  asm volatile("{.reg .pred p; setp.ne.b32 p, 1, 0; wgmma.mma_async.sync.aligned.m64n120k16.f32.bf16.bf16 {%0,%1,%2,%3,%4,%5,%6,%7,%8,%9,%10,%11,%12,%13,%14,%15,%16,%17,%18,%19,%20,%21,%22,%23,%24,%25,%26,%27,%28,%29,%30,%31,%32,%33,%34,%35,%36,%37,%38,%39,%40,%41,%42,%43,%44,%45,%46,%47,%48,%49,%50,%51,%52,%53,%54,%55,%56,%57,%58,%59}, {%60,%61,%62,%63}, %64, p, 1, 1, 0;}"
    : "+f"(d[0]),"+f"(d[1]),"+f"(d[2]),"+f"(d[3]),"+f"(d[4]),"+f"(d[5]),"+f"(d[6]),"+f"(d[7]),"+f"(d[8]),"+f"(d[9]),"+f"(d[10]),"+f"(d[11]),"+f"(d[12]),"+f"(d[13]),"+f"(d[14]),"+f"(d[15]),"+f"(d[16]),"+f"(d[17]),"+f"(d[18]),"+f"(d[19]),"+f"(d[20]),"+f"(d[21]),"+f"(d[22]),"+f"(d[23]),"+f"(d[24]),"+f"(d[25]),"+f"(d[26]),"+f"(d[27]),"+f"(d[28]),"+f"(d[29]),"+f"(d[30]),"+f"(d[31]),"+f"(d[32]),"+f"(d[33]),"+f"(d[34]),"+f"(d[35]),"+f"(d[36]),"+f"(d[37]),"+f"(d[38]),"+f"(d[39]),"+f"(d[40]),"+f"(d[41]),"+f"(d[42]),"+f"(d[43]),"+f"(d[44]),"+f"(d[45]),"+f"(d[46]),"+f"(d[47]),"+f"(d[48]),"+f"(d[49]),"+f"(d[50]),"+f"(d[51]),"+f"(d[52]),"+f"(d[53]),"+f"(d[54]),"+f"(d[55]),"+f"(d[56]),"+f"(d[57]),"+f"(d[58]),"+f"(d[59]) : "r"(a0), "r"(a1), "r"(a2), "r"(a3), "l"(db));
}
template<> __device__ __forceinline__ void wg_rs<112>(float (&d)[64], uint32_t a0, uint32_t a1, uint32_t a2, uint32_t a3, uint64_t db) {
  asm volatile("{.reg .pred p; setp.ne.b32 p, 1, 0; wgmma.mma_async.sync.aligned.m64n112k16.f32.bf16.bf16 {%0,%1,%2,%3,%4,%5,%6,%7,%8,%9,%10,%11,%12,%13,%14,%15,%16,%17,%18,%19,%20,%21,%22,%23,%24,%25,%26,%27,%28,%29,%30,%31,%32,%33,%34,%35,%36,%37,%38,%39,%40,%41,%42,%43,%44,%45,%46,%47,%48,%49,%50,%51,%52,%53,%54,%55}, {%56,%57,%58,%59}, %60, p, 1, 1, 0;}"
    : "+f"(d[0]),"+f"(d[1]),"+f"(d[2]),"+f"(d[3]),"+f"(d[4]),"+f"(d[5]),"+f"(d[6]),"+f"(d[7]),"+f"(d[8]),"+f"(d[9]),"+f"(d[10]),"+f"(d[11]),"+f"(d[12]),"+f"(d[13]),"+f"(d[14]),"+f"(d[15]),"+f"(d[16]),"+f"(d[17]),"+f"(d[18]),"+f"(d[19]),"+f"(d[20]),"+f"(d[21]),"+f"(d[22]),"+f"(d[23]),"+f"(d[24]),"+f"(d[25]),"+f"(d[26]),"+f"(d[27]),"+f"(d[28]),"+f"(d[29]),"+f"(d[30]),"+f"(d[31]),"+f"(d[32]),"+f"(d[33]),"+f"(d[34]),"+f"(d[35]),"+f"(d[36]),"+f"(d[37]),"+f"(d[38]),"+f"(d[39]),"+f"(d[40]),"+f"(d[41]),"+f"(d[42]),"+f"(d[43]),"+f"(d[44]),"+f"(d[45]),"+f"(d[46]),"+f"(d[47]),"+f"(d[48]),"+f"(d[49]),"+f"(d[50]),"+f"(d[51]),"+f"(d[52]),"+f"(d[53]),"+f"(d[54]),"+f"(d[55]) : "r"(a0), "r"(a1), "r"(a2), "r"(a3), "l"(db));
}
template<> __device__ __forceinline__ void wg_rs<104>(float (&d)[64], uint32_t a0, uint32_t a1, uint32_t a2, uint32_t a3, uint64_t db) {
  asm volatile("{.reg .pred p; setp.ne.b32 p, 1, 0; wgmma.mma_async.sync.aligned.m64n104k16.f32.bf16.bf16 {%0,%1,%2,%3,%4,%5,%6,%7,%8,%9,%10,%11,%12,%13,%14,%15,%16,%17,%18,%19,%20,%21,%22,%23,%24,%25,%26,%27,%28,%29,%30,%31,%32,%33,%34,%35,%36,%37,%38,%39,%40,%41,%42,%43,%44,%45,%46,%47,%48,%49,%50,%51}, {%52,%53,%54,%55}, %56, p, 1, 1, 0;}"
    : "+f"(d[0]),"+f"(d[1]),"+f"(d[2]),"+f"(d[3]),"+f"(d[4]),"+f"(d[5]),"+f"(d[6]),"+f"(d[7]),"+f"(d[8]),"+f"(d[9]),"+f"(d[10]),"+f"(d[11]),"+f"(d[12]),"+f"(d[13]),"+f"(d[14]),"+f"(d[15]),"+f"(d[16]),"+f"(d[17]),"+f"(d[18]),"+f"(d[19]),"+f"(d[20]),"+f"(d[21]),"+f"(d[22]),"+f"(d[23]),"+f"(d[24]),"+f"(d[25]),"+f"(d[26]),"+f"(d[27]),"+f"(d[28]),"+f"(d[29]),"+f"(d[30]),"+f"(d[31]),"+f"(d[32]),"+f"(d[33]),"+f"(d[34]),"+f"(d[35]),"+f"(d[36]),"+f"(d[37]),"+f"(d[38]),"+f"(d[39]),"+f"(d[40]),"+f"(d[41]),"+f"(d[42]),"+f"(d[43]),"+f"(d[44]),"+f"(d[45]),"+f"(d[46]),"+f"(d[47]),"+f"(d[48]),"+f"(d[49]),"+f"(d[50]),"+f"(d[51]) : "r"(a0), "r"(a1), "r"(a2), "r"(a3), "l"(db));
}
template<> __device__ __forceinline__ void wg_rs<96>(float (&d)[64], uint32_t a0, uint32_t a1, uint32_t a2, uint32_t a3, uint64_t db) {
  asm volatile("{.reg .pred p; setp.ne.b32 p, 1, 0; wgmma.mma_async.sync.aligned.m64n96k16.f32.bf16.bf16 {%0,%1,%2,%3,%4,%5,%6,%7,%8,%9,%10,%11,%12,%13,%14,%15,%16,%17,%18,%19,%20,%21,%22,%23,%24,%25,%26,%27,%28,%29,%30,%31,%32,%33,%34,%35,%36,%37,%38,%39,%40,%41,%42,%43,%44,%45,%46,%47}, {%48,%49,%50,%51}, %52, p, 1, 1, 0;}"
    : "+f"(d[0]),"+f"(d[1]),"+f"(d[2]),"+f"(d[3]),"+f"(d[4]),"+f"(d[5]),"+f"(d[6]),"+f"(d[7]),"+f"(d[8]),"+f"(d[9]),"+f"(d[10]),"+f"(d[11]),"+f"(d[12]),"+f"(d[13]),"+f"(d[14]),"+f"(d[15]),"+f"(d[16]),"+f"(d[17]),"+f"(d[18]),"+f"(d[19]),"+f"(d[20]),"+f"(d[21]),"+f"(d[22]),"+f"(d[23]),"+f"(d[24]),"+f"(d[25]),"+f"(d[26]),"+f"(d[27]),"+f"(d[28]),"+f"(d[29]),"+f"(d[30]),"+f"(d[31]),"+f"(d[32]),"+f"(d[33]),"+f"(d[34]),"+f"(d[35]),"+f"(d[36]),"+f"(d[37]),"+f"(d[38]),"+f"(d[39]),"+f"(d[40]),"+f"(d[41]),"+f"(d[42]),"+f"(d[43]),"+f"(d[44]),"+f"(d[45]),"+f"(d[46]),"+f"(d[47]) : "r"(a0), "r"(a1), "r"(a2), "r"(a3), "l"(db));
}
template<> __device__ __forceinline__ void wg_rs<88>(float (&d)[64], uint32_t a0, uint32_t a1, uint32_t a2, uint32_t a3, uint64_t db) {
  asm volatile("{.reg .pred p; setp.ne.b32 p, 1, 0; wgmma.mma_async.sync.aligned.m64n88k16.f32.bf16.bf16 {%0,%1,%2,%3,%4,%5,%6,%7,%8,%9,%10,%11,%12,%13,%14,%15,%16,%17,%18,%19,%20,%21,%22,%23,%24,%25,%26,%27,%28,%29,%30,%31,%32,%33,%34,%35,%36,%37,%38,%39,%40,%41,%42,%43}, {%44,%45,%46,%47}, %48, p, 1, 1, 0;}"
    : "+f"(d[0]),"+f"(d[1]),"+f"(d[2]),"+f"(d[3]),"+f"(d[4]),"+f"(d[5]),"+f"(d[6]),"+f"(d[7]),"+f"(d[8]),"+f"(d[9]),"+f"(d[10]),"+f"(d[11]),"+f"(d[12]),"+f"(d[13]),"+f"(d[14]),"+f"(d[15]),"+f"(d[16]),"+f"(d[17]),"+f"(d[18]),"+f"(d[19]),"+f"(d[20]),"+f"(d[21]),"+f"(d[22]),"+f"(d[23]),"+f"(d[24]),"+f"(d[25]),"+f"(d[26]),"+f"(d[27]),"+f"(d[28]),"+f"(d[29]),"+f"(d[30]),"+f"(d[31]),"+f"(d[32]),"+f"(d[33]),"+f"(d[34]),"+f"(d[35]),"+f"(d[36]),"+f"(d[37]),"+f"(d[38]),"+f"(d[39]),"+f"(d[40]),"+f"(d[41]),"+f"(d[42]),"+f"(d[43]) : "r"(a0), "r"(a1), "r"(a2), "r"(a3), "l"(db));
}
template<> __device__ __forceinline__ void wg_rs<80>(float (&d)[64], uint32_t a0, uint32_t a1, uint32_t a2, uint32_t a3, uint64_t db) {
  asm volatile("{.reg .pred p; setp.ne.b32 p, 1, 0; wgmma.mma_async.sync.aligned.m64n80k16.f32.bf16.bf16 {%0,%1,%2,%3,%4,%5,%6,%7,%8,%9,%10,%11,%12,%13,%14,%15,%16,%17,%18,%19,%20,%21,%22,%23,%24,%25,%26,%27,%28,%29,%30,%31,%32,%33,%34,%35,%36,%37,%38,%39}, {%40,%41,%42,%43}, %44, p, 1, 1, 0;}"
    : "+f"(d[0]),"+f"(d[1]),"+f"(d[2]),"+f"(d[3]),"+f"(d[4]),"+f"(d[5]),"+f"(d[6]),"+f"(d[7]),"+f"(d[8]),"+f"(d[9]),"+f"(d[10]),"+f"(d[11]),"+f"(d[12]),"+f"(d[13]),"+f"(d[14]),"+f"(d[15]),"+f"(d[16]),"+f"(d[17]),"+f"(d[18]),"+f"(d[19]),"+f"(d[20]),"+f"(d[21]),"+f"(d[22]),"+f"(d[23]),"+f"(d[24]),"+f"(d[25]),"+f"(d[26]),"+f"(d[27]),"+f"(d[28]),"+f"(d[29]),"+f"(d[30]),"+f"(d[31]),"+f"(d[32]),"+f"(d[33]),"+f"(d[34]),"+f"(d[35]),"+f"(d[36]),"+f"(d[37]),"+f"(d[38]),"+f"(d[39]) : "r"(a0), "r"(a1), "r"(a2), "r"(a3), "l"(db));
}
template<> __device__ __forceinline__ void wg_rs<72>(float (&d)[64], uint32_t a0, uint32_t a1, uint32_t a2, uint32_t a3, uint64_t db) {
  asm volatile("{.reg .pred p; setp.ne.b32 p, 1, 0; wgmma.mma_async.sync.aligned.m64n72k16.f32.bf16.bf16 {%0,%1,%2,%3,%4,%5,%6,%7,%8,%9,%10,%11,%12,%13,%14,%15,%16,%17,%18,%19,%20,%21,%22,%23,%24,%25,%26,%27,%28,%29,%30,%31,%32,%33,%34,%35}, {%36,%37,%38,%39}, %40, p, 1, 1, 0;}"
    : "+f"(d[0]),"+f"(d[1]),"+f"(d[2]),"+f"(d[3]),"+f"(d[4]),"+f"(d[5]),"+f"(d[6]),"+f"(d[7]),"+f"(d[8]),"+f"(d[9]),"+f"(d[10]),"+f"(d[11]),"+f"(d[12]),"+f"(d[13]),"+f"(d[14]),"+f"(d[15]),"+f"(d[16]),"+f"(d[17]),"+f"(d[18]),"+f"(d[19]),"+f"(d[20]),"+f"(d[21]),"+f"(d[22]),"+f"(d[23]),"+f"(d[24]),"+f"(d[25]),"+f"(d[26]),"+f"(d[27]),"+f"(d[28]),"+f"(d[29]),"+f"(d[30]),"+f"(d[31]),"+f"(d[32]),"+f"(d[33]),"+f"(d[34]),"+f"(d[35]) : "r"(a0), "r"(a1), "r"(a2), "r"(a3), "l"(db));
}
template<> __device__ __forceinline__ void wg_rs<64>(float (&d)[64], uint32_t a0, uint32_t a1, uint32_t a2, uint32_t a3, uint64_t db) {
  asm volatile("{.reg .pred p; setp.ne.b32 p, 1, 0; wgmma.mma_async.sync.aligned.m64n64k16.f32.bf16.bf16 {%0,%1,%2,%3,%4,%5,%6,%7,%8,%9,%10,%11,%12,%13,%14,%15,%16,%17,%18,%19,%20,%21,%22,%23,%24,%25,%26,%27,%28,%29,%30,%31}, {%32,%33,%34,%35}, %36, p, 1, 1, 0;}"
    : "+f"(d[0]),"+f"(d[1]),"+f"(d[2]),"+f"(d[3]),"+f"(d[4]),"+f"(d[5]),"+f"(d[6]),"+f"(d[7]),"+f"(d[8]),"+f"(d[9]),"+f"(d[10]),"+f"(d[11]),"+f"(d[12]),"+f"(d[13]),"+f"(d[14]),"+f"(d[15]),"+f"(d[16]),"+f"(d[17]),"+f"(d[18]),"+f"(d[19]),"+f"(d[20]),"+f"(d[21]),"+f"(d[22]),"+f"(d[23]),"+f"(d[24]),"+f"(d[25]),"+f"(d[26]),"+f"(d[27]),"+f"(d[28]),"+f"(d[29]),"+f"(d[30]),"+f"(d[31]) : "r"(a0), "r"(a1), "r"(a2), "r"(a3), "l"(db));
}
__device__ __forceinline__ void wg_rs_first(float (&d)[64], uint32_t a0, uint32_t a1, uint32_t a2, uint32_t a3, uint64_t db) {
  asm volatile("{.reg .pred p; setp.ne.b32 p, 0, 0; wgmma.mma_async.sync.aligned.m64n128k16.f32.bf16.bf16 {%0,%1,%2,%3,%4,%5,%6,%7,%8,%9,%10,%11,%12,%13,%14,%15,%16,%17,%18,%19,%20,%21,%22,%23,%24,%25,%26,%27,%28,%29,%30,%31,%32,%33,%34,%35,%36,%37,%38,%39,%40,%41,%42,%43,%44,%45,%46,%47,%48,%49,%50,%51,%52,%53,%54,%55,%56,%57,%58,%59,%60,%61,%62,%63}, {%64,%65,%66,%67}, %68, p, 1, 1, 0;}"
    : "=f"(d[0]),"=f"(d[1]),"=f"(d[2]),"=f"(d[3]),"=f"(d[4]),"=f"(d[5]),"=f"(d[6]),"=f"(d[7]),"=f"(d[8]),"=f"(d[9]),"=f"(d[10]),"=f"(d[11]),"=f"(d[12]),"=f"(d[13]),"=f"(d[14]),"=f"(d[15]),"=f"(d[16]),"=f"(d[17]),"=f"(d[18]),"=f"(d[19]),"=f"(d[20]),"=f"(d[21]),"=f"(d[22]),"=f"(d[23]),"=f"(d[24]),"=f"(d[25]),"=f"(d[26]),"=f"(d[27]),"=f"(d[28]),"=f"(d[29]),"=f"(d[30]),"=f"(d[31]),"=f"(d[32]),"=f"(d[33]),"=f"(d[34]),"=f"(d[35]),"=f"(d[36]),"=f"(d[37]),"=f"(d[38]),"=f"(d[39]),"=f"(d[40]),"=f"(d[41]),"=f"(d[42]),"=f"(d[43]),"=f"(d[44]),"=f"(d[45]),"=f"(d[46]),"=f"(d[47]),"=f"(d[48]),"=f"(d[49]),"=f"(d[50]),"=f"(d[51]),"=f"(d[52]),"=f"(d[53]),"=f"(d[54]),"=f"(d[55]),"=f"(d[56]),"=f"(d[57]),"=f"(d[58]),"=f"(d[59]),"=f"(d[60]),"=f"(d[61]),"=f"(d[62]),"=f"(d[63]) : "r"(a0), "r"(a1), "r"(a2), "r"(a3), "l"(db));
}
__device__ __forceinline__ void wg_tt128(float (&d)[64], uint64_t da, uint64_t db, int sc) {
  asm volatile("{.reg .pred p; setp.ne.b32 p, %66, 0; wgmma.mma_async.sync.aligned.m64n128k16.f32.bf16.bf16 {%0,%1,%2,%3,%4,%5,%6,%7,%8,%9,%10,%11,%12,%13,%14,%15,%16,%17,%18,%19,%20,%21,%22,%23,%24,%25,%26,%27,%28,%29,%30,%31,%32,%33,%34,%35,%36,%37,%38,%39,%40,%41,%42,%43,%44,%45,%46,%47,%48,%49,%50,%51,%52,%53,%54,%55,%56,%57,%58,%59,%60,%61,%62,%63}, %64, %65, p, 1, 1, 1, 1;}"
    : "+f"(d[0]),"+f"(d[1]),"+f"(d[2]),"+f"(d[3]),"+f"(d[4]),"+f"(d[5]),"+f"(d[6]),"+f"(d[7]),"+f"(d[8]),"+f"(d[9]),"+f"(d[10]),"+f"(d[11]),"+f"(d[12]),"+f"(d[13]),"+f"(d[14]),"+f"(d[15]),"+f"(d[16]),"+f"(d[17]),"+f"(d[18]),"+f"(d[19]),"+f"(d[20]),"+f"(d[21]),"+f"(d[22]),"+f"(d[23]),"+f"(d[24]),"+f"(d[25]),"+f"(d[26]),"+f"(d[27]),"+f"(d[28]),"+f"(d[29]),"+f"(d[30]),"+f"(d[31]),"+f"(d[32]),"+f"(d[33]),"+f"(d[34]),"+f"(d[35]),"+f"(d[36]),"+f"(d[37]),"+f"(d[38]),"+f"(d[39]),"+f"(d[40]),"+f"(d[41]),"+f"(d[42]),"+f"(d[43]),"+f"(d[44]),"+f"(d[45]),"+f"(d[46]),"+f"(d[47]),"+f"(d[48]),"+f"(d[49]),"+f"(d[50]),"+f"(d[51]),"+f"(d[52]),"+f"(d[53]),"+f"(d[54]),"+f"(d[55]),"+f"(d[56]),"+f"(d[57]),"+f"(d[58]),"+f"(d[59]),"+f"(d[60]),"+f"(d[61]),"+f"(d[62]),"+f"(d[63]) : "l"(da), "l"(db), "r"(sc));
}
__device__ __forceinline__ void wg_tt64(float (&d)[64], uint64_t da, uint64_t db, int sc) {
  asm volatile("{.reg .pred p; setp.ne.b32 p, %34, 0; wgmma.mma_async.sync.aligned.m64n64k16.f32.bf16.bf16 {%0,%1,%2,%3,%4,%5,%6,%7,%8,%9,%10,%11,%12,%13,%14,%15,%16,%17,%18,%19,%20,%21,%22,%23,%24,%25,%26,%27,%28,%29,%30,%31}, %32, %33, p, 1, 1, 1, 1;}"
    : "+f"(d[0]),"+f"(d[1]),"+f"(d[2]),"+f"(d[3]),"+f"(d[4]),"+f"(d[5]),"+f"(d[6]),"+f"(d[7]),"+f"(d[8]),"+f"(d[9]),"+f"(d[10]),"+f"(d[11]),"+f"(d[12]),"+f"(d[13]),"+f"(d[14]),"+f"(d[15]),"+f"(d[16]),"+f"(d[17]),"+f"(d[18]),"+f"(d[19]),"+f"(d[20]),"+f"(d[21]),"+f"(d[22]),"+f"(d[23]),"+f"(d[24]),"+f"(d[25]),"+f"(d[26]),"+f"(d[27]),"+f"(d[28]),"+f"(d[29]),"+f"(d[30]),"+f"(d[31]) : "l"(da), "l"(db), "r"(sc));
}
__device__ __forceinline__ void wg_tt32(float (&d)[64], uint64_t da, uint64_t db, int sc) {
  asm volatile("{.reg .pred p; setp.ne.b32 p, %18, 0; wgmma.mma_async.sync.aligned.m64n32k16.f32.bf16.bf16 {%0,%1,%2,%3,%4,%5,%6,%7,%8,%9,%10,%11,%12,%13,%14,%15}, %16, %17, p, 1, 1, 1, 1;}"
    : "+f"(d[0]),"+f"(d[1]),"+f"(d[2]),"+f"(d[3]),"+f"(d[4]),"+f"(d[5]),"+f"(d[6]),"+f"(d[7]),"+f"(d[8]),"+f"(d[9]),"+f"(d[10]),"+f"(d[11]),"+f"(d[12]),"+f"(d[13]),"+f"(d[14]),"+f"(d[15]) : "l"(da), "l"(db), "r"(sc));
}
__device__ __forceinline__ void wg_g1(float (&d)[88], uint64_t da, uint64_t db, int sc) {
  asm volatile("{.reg .pred p; setp.ne.b32 p, %90, 0; wgmma.mma_async.sync.aligned.m64n176k16.f32.bf16.bf16 {%0,%1,%2,%3,%4,%5,%6,%7,%8,%9,%10,%11,%12,%13,%14,%15,%16,%17,%18,%19,%20,%21,%22,%23,%24,%25,%26,%27,%28,%29,%30,%31,%32,%33,%34,%35,%36,%37,%38,%39,%40,%41,%42,%43,%44,%45,%46,%47,%48,%49,%50,%51,%52,%53,%54,%55,%56,%57,%58,%59,%60,%61,%62,%63,%64,%65,%66,%67,%68,%69,%70,%71,%72,%73,%74,%75,%76,%77,%78,%79,%80,%81,%82,%83,%84,%85,%86,%87}, %88, %89, p, 1, 1, 1, 0;}"
    : "+f"(d[0]),"+f"(d[1]),"+f"(d[2]),"+f"(d[3]),"+f"(d[4]),"+f"(d[5]),"+f"(d[6]),"+f"(d[7]),"+f"(d[8]),"+f"(d[9]),"+f"(d[10]),"+f"(d[11]),"+f"(d[12]),"+f"(d[13]),"+f"(d[14]),"+f"(d[15]),"+f"(d[16]),"+f"(d[17]),"+f"(d[18]),"+f"(d[19]),"+f"(d[20]),"+f"(d[21]),"+f"(d[22]),"+f"(d[23]),"+f"(d[24]),"+f"(d[25]),"+f"(d[26]),"+f"(d[27]),"+f"(d[28]),"+f"(d[29]),"+f"(d[30]),"+f"(d[31]),"+f"(d[32]),"+f"(d[33]),"+f"(d[34]),"+f"(d[35]),"+f"(d[36]),"+f"(d[37]),"+f"(d[38]),"+f"(d[39]),"+f"(d[40]),"+f"(d[41]),"+f"(d[42]),"+f"(d[43]),"+f"(d[44]),"+f"(d[45]),"+f"(d[46]),"+f"(d[47]),"+f"(d[48]),"+f"(d[49]),"+f"(d[50]),"+f"(d[51]),"+f"(d[52]),"+f"(d[53]),"+f"(d[54]),"+f"(d[55]),"+f"(d[56]),"+f"(d[57]),"+f"(d[58]),"+f"(d[59]),"+f"(d[60]),"+f"(d[61]),"+f"(d[62]),"+f"(d[63]),"+f"(d[64]),"+f"(d[65]),"+f"(d[66]),"+f"(d[67]),"+f"(d[68]),"+f"(d[69]),"+f"(d[70]),"+f"(d[71]),"+f"(d[72]),"+f"(d[73]),"+f"(d[74]),"+f"(d[75]),"+f"(d[76]),"+f"(d[77]),"+f"(d[78]),"+f"(d[79]),"+f"(d[80]),"+f"(d[81]),"+f"(d[82]),"+f"(d[83]),"+f"(d[84]),"+f"(d[85]),"+f"(d[86]),"+f"(d[87]) : "l"(da), "l"(db), "r"(sc));
}

struct Params { const __nv_bfloat16 *x, *logA, *Aim, *Cr, *Ci, *logdt, *Dskip, *Wg, *Wu, *Wd; __nv_bfloat16* out; uint4* xnT; float2* st; uint2* S; unsigned* flags; };
struct Maps { CUtensorMap x[2], xo, wg, wu, wd, hst[2], hld, xt, sld; };

__device__ __forceinline__ void conv_channel(uint32_t cb, int w, int lane, uint32_t (&res)[8], uint32_t sig, int sidx, unsigned* gflag) {
    const int q = lane & 3, g = lane >> 2, gam = g >> 2;
    float acc[64];
    uint2 a[17][2];
    const uint32_t t0 = cb + CH_T + (uint32_t)(14 + 4 * w + (g & 3) - 2 * q) * 280u + gam * 8;
#define LDA(s0, s1) _Pragma("unroll") for (int s = s0; s < s1; s++) { a[s][0] = lds64(t0 + s * 16); a[s][1] = lds64(t0 - 8 * 280 + s * 16); }
#define CT(N, s) wg_rs<N>(acc, a[s][0].x, a[s][0].y, a[s][1].x, a[s][1].y, dU + 4 * (s))
    const uint64_t dU = mkdesc(cb + CH_U, UPLANE, 128, 0);
    LDA(0, 17)
    if (sig) { fence_async_smem(); mbar_arrive(sig); }
    WG_FENCE();
    if (w == 0) STAMP2(52 + 3 * sidx);
    wg_rs_first(acc, a[0][0].x, a[0][0].y, a[0][1].x, a[0][1].y, dU);
    CT(128, 1); CT(120, 2); CT(120, 3); CT(112, 4); CT(112, 5); CT(104, 6); CT(104, 7); CT(96, 8);
    CT(96, 9); CT(88, 10); CT(88, 11); CT(80, 12); CT(80, 13); CT(72, 14); CT(72, 15); CT(64, 16);
#undef CT
#undef LDA
    wg_tt64(acc, mkdesc(cb + CH_A3, 128, 512, 0), mkdesc(cb + CH_B3, 384, 32, 0), 1);
    wg_tt32(acc, mkdesc(cb + CH_A3 + 256, 128, 512, 0), mkdesc(cb + CH_B3 + 128, 384, 32, 0), 1);
    WG_COMMIT();
    if (gflag && threadIdx.x == 0) start_vote(gflag);
    if (w == 0) STAMP2(53 + 3 * sidx);
    WG_WAIT(0);
    fence_acc(acc);
    if (w == 0) STAMP2(54 + 3 * sidx);
    const int src1 = (lane & ~3) | ((q + 1) & 3);
    float E[16][2];
    #pragma unroll
    for (int j = 0; j < 16; j++) {
        const float nxt = (j < 15) ? acc[4 * (j + 1) + 2] : 0.f;
        const float sup = (q == 0) ? nxt : acc[4 * j + 2];
        const float v = __shfl_sync(0xffffffffu, sup, src1);
        E[j][0] = acc[4 * j] + acc[4 * j + 3];
        E[j][1] = acc[4 * j + 1] + v;
    }
    const int src2 = gam ? ((lane & 12) | ((q + 3) & 3)) : (16 | (lane & 12) | ((q + 1) & 3));
    const bool c1 = gam && q != 0, c2 = gam && q == 0;
    #pragma unroll
    for (int a2 = 0; a2 < 8; a2++) {
        float y[2];
        #pragma unroll
        for (int e = 0; e < 2; e++) {
            const float sup = c1 ? E[2 * a2][e] : E[2 * a2 + 1][e];
            const float nxt = (a2 < 7) ? E[2 * a2 + 2][e] : 0.f;
            const float keep = c2 ? nxt : (c1 ? E[2 * a2 + 1][e] : E[2 * a2][e]);
            y[e] = keep + __shfl_sync(0xffffffffu, sup, src2);
        }
        res[a2] = pack2(y[1], y[0]);
    }
}

__device__ __forceinline__ void consumer(uint32_t sb, int warp, const Params& P, const Maps& M) {
    const int V = warp >> 2, w = warp & 3, lane = threadIdx.x & 31, q = lane & 3, g = lane >> 2;
    const int c = blockIdx.x;
    const uint32_t bars = sb + OFF_BAR, xb = sb + OFF_X + V * 2 * XBUF;
    {
        float ag[88], au[88];
        define_acc(ag); define_acc(au);
        mbar_wait(bars + 8 * B_FULLW, 0);
        mbar_wait(bars + 8 * (B_FULLX + 2 * V), 0);
        #pragma unroll 1
        for (int st = 0; st < 8; st++) {
            uint64_t dG = mkdesc(sb + OFF_W + (st & 3) * 16384, 0, 1024, 1), dX = mkdesc(xb + (st & 1) * XBUF, 16, 1024, 1);
            uint32_t sig = lane == 0 && (V ? st < 6 : st > 0);
            asm volatile("" : "+l"(dG), "+l"(dX), "+r"(sig) :: "memory");
            if (V ? st < 7 : st > 1) mbar_wait(bars + 8 * (B_TURN + V), st & 1);
            STAMP(40 + 8 * V + st); if (st == 0 && V == 0) GSTAMP(33);
            WG_FENCE();
            #pragma unroll
            for (int k = 0; k < 4; k++) {
                if (k == SIGK) mbar_arrive_if(bars + 8 * (B_TURN + 1 - V), sig);
                wg_g1(ag, dG + k * 128, dX + k * 2, k ? 1 : st);
                wg_g1(au, dG + 512 + k * 128, dX + k * 2, k ? 1 : st);
            }
            WG_COMMIT();
            if (st == 6 * V) {
                mbar_wait(bars + 8 * (B_FULLW + ((st + 1) & 3)), V);
                mbar_wait(bars + 8 * (B_FULLX + 2 * V + 1), V);
            } else {
                WG_WAIT(1);
                mbar_arrive_if(bars + 8 * (B_EMPTYW + 2 * V), lane == 0 && st == 6 * V + 1);
                mbar_arrive_if(bars + 8 * (B_EMPTYX + 2 * V), lane == 0 && st == 6 * V + 1);
                WG_WAIT(0);
                mbar_arrive_if(bars + 8 * (B_EMPTYW + (st & 3)), lane == 0);
                mbar_arrive_if(bars + 8 * (B_EMPTYX + 2 * V + (st & 1)), lane == 0);
                if (st < 7) {
                    mbar_wait(bars + 8 * (B_FULLW + ((st + 1) & 3)), (st + 1) >> 2);
                    mbar_wait(bars + 8 * (B_FULLX + 2 * V + ((st + 1) & 1)), ((st + 1) >> 1) & 1);
                }
            }
        }
        WG_WAIT(0);
        fence_acc(ag); fence_acc(au);
        STAMP(8 * V + 1); GSTAMP(29 + V);
        float cg0 = ag[84], cg1 = ag[86], cu0 = au[84], cu1 = au[86];
        const uint32_t ca = sb + OFF_CSUM + (8 * w + g) * 16;
        if (V == 0) { sts128(ca, FU(cg0), FU(cg1), FU(cu0), FU(cu1)); mbar_arrive(bars + 8 * B_CS); }
        else { mbar_wait(bars + 8 * B_CS, 0); const uint4 t = lds128(ca); cg0 = UF(t.x); cg1 = UF(t.y); cu0 = UF(t.z); cu1 = UF(t.w); }
        mbar_wait(bars + 8 * B_STATS, 0);
        mbar_wait(bars + 8 * (B_EMPTYX + 2 * V), 1);
        STAMP(13 + V);
        const uint32_t hs = xb + (2 * w + ((lane >> 3) & 1)) * (2688 + 128 * V) + (lane >> 4) * 128 + (lane & 7) * 16;
        const uint32_t sa = sb + OFF_ST + (168 * V + 2 * q) * 8;
        uint4 sq[22];
        #pragma unroll
        for (int j = 0; j < 3; j++) sq[j] = lds128(sa + j * 64);
        #pragma unroll
        for (int j = 0; j < 22; j += 2) {
            uint32_t o[4];
            #pragma unroll
            for (int jj = 0; jj < 2; jj++) {
                const uint4 sv = sq[j + jj];
                float hv[4];
                #pragma unroll
                for (int i = 0; i < 4; i++) {
                    const float m = UF((i & 1) ? sv.z : sv.x);
                    const float gh = fmaf(-m, (i & 2) ? cg1 : cg0, ag[4 * (j + jj) + i]) * UF((i & 1) ? sv.w : sv.y);
                    const float p = gh * fmaf(-m, (i & 2) ? cu1 : cu0, au[4 * (j + jj) + i]);
                    hv[i] = fmaf(p, tanh_fast(gh), p);
                }
                o[2 * jj] = pack2(hv[0], hv[1]); o[2 * jj + 1] = pack2(hv[2], hv[3]);
            }
            #pragma unroll
            for (int k = (j ? 3 + 3 * j / 2 : 3); k < 6 + 3 * j / 2 && k < 22; k++) sq[k] = lds128(sa + k * 64);
            uint32_t ad = hs + j * 128;
            if (j == 20 && V == 0 && lane >= 16) ad = xb + 21504 + (lane & 7) * 16;
            stsm4(ad, o[0], o[1], o[2], o[3]);
        }
        if (c >= 128 || V) { fence_async_smem(); mbar_arrive(bars + 8 * (B_EPI + V)); }
        STAMP(8 * V + 2);
    }
    if (c >= 128) return;
    {
        mbar_wait(bars + 8 * B_CONV, 0);
        uint32_t r0[8], r1[8];
        #pragma unroll
        for (int i = 0; i < 8; i++) asm volatile("" : "=r"(r1[i]));
        #pragma unroll 1
        for (int e = 0; e < 2; e++) {
            #pragma unroll
            for (int i = 0; i < 8; i++) r0[i] = r1[i];
            conv_channel(sb + OFF_CONV + (2 * V + e) * CH_STRIDE, w, lane, r1, (e | V) ? 0 : bars + 8 * B_EPI, 2 * V + e, e ? P.flags : nullptr);
            if (e == 0) STAMP(8 * V + 3);
        }
        const int gam = g >> 2, qq = gam ? ((q + 3) & 3) : q;
        const uint32_t sp = sb + OFF_CONV + V * OFF_SST + ((63 - 4 * gam - qq) * 16 + 4 * (w ^ (3 - qq)) + (g & 3)) * 8;
        bar_sync(3 + V);
        #pragma unroll
        for (int a2 = 0; a2 < 8; a2++) sts64(sp - a2 * 1024, r0[a2], r1[a2]);
        fence_async_smem();
        mbar_arrive(bars + 8 * (B_SIG + V));
        STAMP(8 * V + 4); GSTAMP(35 + V);
    }
    if (V == 1) return;
    {
        const int tau = c >> 2, dg = c & 3;
        const uint32_t row = 8 * (w & 1) + 32 * (w >> 1);
        float acc[64];
        define_acc(acc);
        const float rr0 = __ldcg(&P.st[64 * tau + row + g].y), rr1 = __ldcg(&P.st[64 * tau + row + g + 16].y);
        mbar_wait(bars + 8 * B_S, 0);
        mbar_wait(bars + 8 * B_FULLD, 0);
        STAMP(5); GSTAMP(27);
        uint64_t dB = mkdesc(sb + wd_slot(0), 8192, 1024, 1), dA = mkdesc(sb + h_slot(0), 1024, 128, 0);
        int sd = 0; uint32_t np = 0;
        #pragma unroll 1
        for (int st = 0; st < 21; st++) {
            WG_FENCE();
            wg_tt128(acc, dA, dB, st);
            wg_tt128(acc, dA + 128, dB + 128, 1);
            wg_tt128(acc, dA + 256, dB + 256, 1);
            wg_tt128(acc, dA + 384, dB + 384, 1);
            WG_COMMIT();
            uint32_t ro = bars + 8 * (B_EMPTYD + (sd ? sd - 1 : 6)), m = lane == 0 && st > 0, ok;
            if (++sd == 7) { sd = 0; np ^= 1; }
            const uint32_t nb = bars + 8 * (B_FULLD + sd);
            dB = mkdesc(sb + wd_slot(sd), 8192, 1024, 1); dA = mkdesc(sb + h_slot(sd), 1024, 128, 0);
            asm volatile("{.reg .pred p; mbarrier.test_wait.parity.shared::cta.b64 p, [%5], %6; vote.sync.all.pred p, p, -1; selp.u32 %0, 1, 0, p;}"
                : "=r"(ok), "+l"(dA), "+l"(dB), "+r"(ro), "+r"(m) : "r"(nb), "r"(np) : "memory");
            WG_WAIT(1);
            mbar_arrive_if(ro, m);
            if (!ok) mbar_wait(nb, np);
            if (w == 0) STAMP2(20 + st);
        }
        WG_FENCE();
        wg_tt128(acc, dA, dB, 1);
        wg_tt128(acc, dA + 128, dB + 128, 1);
        WG_COMMIT();
        mbar_wait(bars + 8 * B_XO, 0);
        const uint32_t xo = sb + OFF_XO + (row + (lane & 7) + 16 * ((lane >> 3) & 1)) * 128;
        const uint32_t so = sb + OFF_SI + (w >> 1) * 8192 + q * 256 + (g & 1) * 8;
        const uint32_t sx = (4 * (w & 1) + (g >> 1)) ^ (2 * q) ^ (2 * ((2 * tau + (w >> 1)) & 3));
        uint32_t xr[8][4];
        uint2 sv[16];
        #pragma unroll
        for (int j = 0; j < 16; j += 2) {
            ldsm4(xr[j >> 1], xo + (j >> 3) * 8192 + ((((j & 7) + (lane >> 4)) ^ (lane & 7)) << 4));
            sv[j] = lds64(so + j * 512 + (sx << 4));
            sv[j + 1] = lds64(so + j * 512 + 128 + ((sx ^ 1) << 4));
        }
        WG_WAIT(0);
        fence_acc(acc);
        STAMP(6); GSTAMP(28);
        #pragma unroll
        for (int j = 0; j < 16; j += 2) {
            #pragma unroll
            for (int i = 0; i < 4; i++) {
                const int jj = j + (i >> 1), hh = i & 1;
                const float f0 = acc[4 * jj + 2 * hh] * (hh ? rr1 : rr0), f1 = acc[4 * jj + 2 * hh + 1] * (hh ? rr1 : rr0);
                const uint32_t G = pack2(fmaf(f0, tanh_fast(f0), f0), fmaf(f1, tanh_fast(f1), f1));
                const uint32_t s2 = __byte_perm(sv[jj].x, sv[jj].y, hh ? 0x7632 : 0x5410);
                asm("fma.rn.bf16x2 %0, %1, %2, %0;" : "+r"(xr[j >> 1][i]) : "r"(s2), "r"(G));
            }
            stsm4(xo + (j >> 3) * 8192 + ((((j & 7) + (lane >> 4)) ^ (lane & 7)) << 4), xr[j >> 1][0], xr[j >> 1][1], xr[j >> 1][2], xr[j >> 1][3]);
        }
        __syncwarp();
        {
            const uint32_t rr = row + ((lane >> 4) << 4), la = sb + OFF_XO + rr * 128 + ((lane >> 3) & 1) * 8192;
            uint4* dst = (uint4*)(P.out + (64 * tau + rr) * DM + 128 * dg) + (lane & 15);
            uint4 v[8];
            #pragma unroll
            for (int i = 0; i < 8; i++) v[i] = lds128(la + i * 128 + (((lane & 7) ^ i) << 4));
            #pragma unroll
            for (int i = 0; i < 8; i++) dst[i * 64] = v[i];
        }
        STAMP(7); GSTAMP(23);
    }
}

__device__ __forceinline__ float2 cexp_p(float re2, float im, float p) {
    float sn, cs;
    const float mag = ex2(re2 * p), th = im * p;
    asm("sin.approx.ftz.f32 %0, %1;" : "=f"(sn) : "f"(th));
    asm("cos.approx.ftz.f32 %0, %1;" : "=f"(cs) : "f"(th));
    return make_float2(mag * cs, mag * sn);
}
struct SsmRaw { unsigned short la, ai, cr, ci, ldt, dsk; };
__device__ __forceinline__ unsigned short ldu16(const void* p) { unsigned short v; asm volatile("ld.global.nc.u16 %0, [%1];" : "=h"(v) : "l"(p)); return v; }
__device__ __forceinline__ float2 cmul(float2 a, float2 b) { return make_float2(fmaf(a.x, b.x, -a.y * b.y), fmaf(a.x, b.y, a.y * b.x)); }
__device__ __forceinline__ float2 csqr(float2 a) { const float t = a.x * a.y; return make_float2(fmaf(a.x, a.x, -a.y * a.y), t + t); }
__device__ __forceinline__ void mma16816(float (&d)[4], const uint32_t (&a)[4], uint32_t b0, uint32_t b1) {
    asm volatile("mma.sync.aligned.m16n8k16.row.col.f32.bf16.bf16.f32 {%0,%1,%2,%3}, {%4,%5,%6,%7}, {%8,%9}, {%0,%1,%2,%3};"
        : "+f"(d[0]), "+f"(d[1]), "+f"(d[2]), "+f"(d[3]) : "r"(a[0]), "r"(a[1]), "r"(a[2]), "r"(a[3]), "r"(b0), "r"(b1));
}

__device__ __forceinline__ void layer_norm(uint32_t sb, uint32_t cb, int w, int lane) {
    const uint32_t bars = sb + OFF_BAR;
    mbar_wait(bars + 8 * (B_LNX + w), 0);
    STAMP(34);
    {
        const uint32_t r0 = cb + CH_LN + (w & 1) * 64 + (lane >> 3) * 1040, ra = r0 + (lane & 7) * 16;
        const float pv = bf_lo(FU(ldsf(r0)));
        float s0 = 0.f, s1 = 0.f, a0 = 0.f, a1 = 0.f;
        #pragma unroll 1
        for (int k = 0; k < 1024; k += 512) {
            uint32_t v[16];
            #pragma unroll
            for (int j = 0; j < 4; j++) *(uint4*)&v[4 * j] = lds128(ra + k + 128 * j);
            #pragma unroll
            for (int i = 0; i < 16; i++) { const float t0 = bf_lo(v[i]) - pv, t1 = bf_hi(v[i]) - pv; s0 += t0; s1 += t1; a0 = fmaf(t0, t0, a0); a1 = fmaf(t1, t1, a1); }
        }
        s0 += s1; a0 += a1;
        #pragma unroll
        for (int o = 4; o; o >>= 1) { s0 += __shfl_xor_sync(0xffffffffu, s0, o); a0 += __shfl_xor_sync(0xffffffffu, a0, o); }
        s0 *= 1.f / DM;
        float sd, ri;
        asm("sqrt.approx.ftz.f32 %0, %1;" : "=f"(sd) : "f"(bf_round(bf_round(fmaxf(fmaf(-s0, s0, a0 * (1.f / DM)), 0.f)) + 1e-5f)));
        asm("rcp.approx.ftz.f32 %0, %1;" : "=f"(ri) : "f"(bf_round(sd)));
        if ((lane & 7) == 0) sts64(sb + OFF_CSUM + (w + 4 * (lane >> 3)) * 8, FU(bf_round(pv + s0)), FU(0.5f * ri));
    }
    STAMP(62);
    bar_sync(2);
    const int r = 4 * ((lane & 7) >> 1) + (lane & 1) + 2 * ((lane >> 3) & 1);
    const uint32_t ad = sb + OFF_CONV + (r & 3) * CH_STRIDE + CH_LN + (r & 1) * 64 + (r >> 2) * 1040 + (16 * w + (lane >> 4)) * 16;
    const uint4 sa = lds128(sb + OFF_CSUM + (lane & 3) * 32), sc = lds128(sb + OFF_CSUM + (lane & 3) * 32 + 16);
    const uint32_t m2[2] = {__byte_perm(sa.x, sa.z, 0x7632), __byte_perm(sc.x, sc.z, 0x7632)};
    const float ri[4] = {2.f * UF(sa.y), 2.f * UF(sa.w), 2.f * UF(sc.y), 2.f * UF(sc.w)};
    #pragma unroll 1
    for (int i = 0; i < 8; i += 4) {
        uint32_t v[4][4];
        #pragma unroll
        for (int j = 0; j < 4; j++)
            asm volatile("ldmatrix.sync.aligned.m8n8.x4.trans.shared.b16 {%0,%1,%2,%3}, [%4];" : "=r"(v[j][0]), "=r"(v[j][1]), "=r"(v[j][2]), "=r"(v[j][3]) : "r"(ad + 32 * (i + j)) : "memory");
        #pragma unroll
        for (int j = 0; j < 4; j++) {
            #pragma unroll
            for (int k = 0; k < 4; k++) {
                uint32_t dv; asm("sub.rn.bf16x2 %0, %1, %2;" : "=r"(dv) : "r"(v[j][k]), "r"(m2[k & 1]));
                v[j][k] = pack2(bf_lo(dv) * ri[2 * (k & 1)], bf_hi(dv) * ri[2 * (k & 1) + 1]);
            }
            sts64(cb + CH_LNT + lane * 8 + (i + j) * 512, v[j][0], v[j][1]); sts64(cb + CH_LNT + lane * 8 + (i + j) * 512 + 256, v[j][2], v[j][3]);
        }
    }
    fence_async_smem();
    mbar_arrive(bars + 8 * B_LN);
    STAMP(16);
}

__device__ __forceinline__ void kernel_gen(uint32_t fs, int lane, const SsmRaw& raw, float (&dacc)[2][3][4]) {
    const float dt = bf_round(ex2(bf_lo(raw.ldt) * 1.4426950408889634f));
    const float re2 = bf_round(ex2(bf_lo(raw.la) * 1.4426950408889634f)) * dt * -1.4426950408889634f, im = bf_lo(raw.ai) * dt;
    const float2 C = make_float2(bf_lo(raw.cr) * (dt + dt), bf_lo(raw.ci) * -(dt + dt));
    STAMP(56);
    const float2 y1 = cexp_p(re2, -im, 1.f), y256 = cexp_p(re2, -im, 256.f), z64 = cexp_p(re2, im, 64.f);
    const uint32_t fm = fs + (lane >> 3) * 144 + (lane & 7) * 16;
#define PK(v) pack2((v).x, (v).y)
    const float2 y2 = csqr(y1), y4 = csqr(y2), y8 = csqr(y4);
    const float2 l1 = cmul(C, y1), l2 = cmul(C, y2), l3 = cmul(l1, y2);
    stsm4(fm, PK(C), PK(l1), PK(l2), PK(l3));
    stsm4(fm + 4 * 144, PK(cmul(C, y4)), PK(cmul(l1, y4)), PK(cmul(l2, y4)), PK(cmul(l3, y4)));
    const float2 t0 = cmul(C, y256), t1 = cmul(t0, y256), t2 = cmul(t1, y256), t3_ = cmul(t2, y256);
    const float2 u1 = cmul(t0, y2), u2 = cmul(u1, y2), u3 = cmul(u2, y2);
    stsm4(fm + 8 * 144, PK(t0), PK(u1), PK(u2), PK(u3));
    stsm4(fm + 12 * 144, PK(t1), PK(cmul(t1, y4)), PK(t2), PK(cmul(t2, y4)));
    const float2 v0 = cmul(t3_, y8), v1 = cmul(v0, y256), v2 = cmul(v1, y256), v3 = cmul(v2, y256);
    stsm4(fm + 16 * 144, PK(v0), PK(v1), PK(v2), PK(v3));
    stsf(fs + lane * 4 + 20 * 144, UF(PK(t3_)));
    STAMP(57);
    const uint32_t ldb = fs + (lane & 7) * 144 + ((lane >> 3) & 1) * 16 + (lane >> 4) * 8 * 144;
    const float p8 = (float)(2 * (lane & 28));
    __syncwarp();
    #pragma unroll 1
    for (int ks = 0; ks < 4; ks++) {
        uint32_t b01[4], b2[2], a0[4], a1[4];
        ldsm4(b01, ldb + ks * 32);
        asm volatile("ldmatrix.sync.aligned.m8n8.x2.shared.b16 {%0,%1}, [%2];" : "=r"(b2[0]), "=r"(b2[1]) : "r"(ldb + 16 * 144 + ks * 32) : "memory");
        #pragma unroll
        for (int mh = 0; mh < 2; mh++) {
            const int src = 8 * ks + 4 * mh + (lane & 3);
            const float2 z = make_float2(__shfl_sync(0xffffffffu, z64.x, src), __shfl_sync(0xffffffffu, z64.y, src));
            const float2 R0 = cexp_p(__shfl_sync(0xffffffffu, re2, src), __shfl_sync(0xffffffffu, im, src), p8);
            const float2 R1 = cmul(R0, z), R2 = cmul(R1, z), R3 = cmul(R2, z);
            a0[2 * mh] = PK(R0); a0[2 * mh + 1] = PK(R1); a1[2 * mh] = PK(R2); a1[2 * mh + 1] = PK(R3);
        }
        mma16816(dacc[0][0], a0, b01[0], b01[1]); mma16816(dacc[1][0], a1, b01[0], b01[1]);
        mma16816(dacc[0][1], a0, b01[2], b01[3]); mma16816(dacc[1][1], a1, b01[2], b01[3]);
        mma16816(dacc[0][2], a0, b2[0], b2[1]);   mma16816(dacc[1][2], a1, b2[0], b2[1]);
    }
#undef PK
    STAMP(58);
}

__device__ __forceinline__ void aux_role(uint32_t sb, int w, float (&dacc)[2][3][4], float dsk) {
    const int lane = threadIdx.x & 31, q = lane & 3, g = lane >> 2;
    const int c = blockIdx.x;
    const uint32_t bars = sb + OFF_BAR;
    if (c >= 128) { mbar_arrive(bars + 8 * B_LN); return; }
    {
        const uint32_t cb = sb + OFF_CONV + w * CH_STRIDE;
        layer_norm(sb, cb, w, lane);
        {
            uint4 v[2][3];
            #pragma unroll
            for (int i = 0; i < 3; i++) v[0][i] = lds128(cb + CH_PART + lane * 16 + i * 512);
            #pragma unroll
            for (int k = 0; k < 6; k++) {
                #pragma unroll
                for (int i = 0; i < 3; i++) if (k < 5) v[(k + 1) & 1][i] = lds128(cb + CH_PART + lane * 16 + (k + 1) * 1536 + i * 512);
                #pragma unroll
                for (int i = 0; i < 3; i++) {
                    float* d = &dacc[0][0][0] + 12 * (k & 1) + 4 * i;
                    d[0] += UF(v[k & 1][i].x); d[1] += UF(v[k & 1][i].y); d[2] += UF(v[k & 1][i].z); d[3] += UF(v[k & 1][i].w);
                }
            }
        }
        __syncwarp();
        STAMP(18);
        const uint32_t sF = cb + CH_A3, sG = cb + CH_G;
        if (lane == 0) dacc[0][0][0] += dsk;
        if (lane < 10) sts128(sG + 128 + (lane & 1) * 208 + (lane >> 1) * 16, 0, 0, 0, 0);
        const uint32_t f0 = sF + (8 * g + 2 * q) * 4, f1 = sF + ((q < 2) ? 256 + 4 * g + 2 * q : 256 + 2 * g + 64 * q) * 4, st1 = (q < 2) ? 128 : 64;
        const uint32_t ga = sG + ((g & 1) ? 0 : 208) + (63 - (g >> 1) - 32 * q) * 2;
        #pragma unroll
        for (int i = 0; i < 4; i++) {
            const int mu = i >> 1, hh = i & 1;
            sts64(f0 + i * 256, FU(dacc[mu][0][2 * hh]), FU(dacc[mu][0][2 * hh + 1]));
            sts64(f1 + i * st1, FU(dacc[mu][1][2 * hh]), FU(dacc[mu][1][2 * hh + 1]));
            const uint32_t pk = pack2(dacc[mu][2][2 * hh], dacc[mu][2][2 * hh + 1]);
            if (q < 2) { sts16(ga - 8 * i, pk & 0xffff); sts16(ga - 8 * i - 32, pk >> 16); }
        }
        if (lane == 2) stsf(sF + 2048, dacc[0][2][0]);
        STAMP(19);
        bar_sync(2);
    }
    const int u = min(lane, 30) - 15, r2 = (u + ((u >> 1) & 1)) >> 1, r4 = (u + 1 + ((u >> 2) & 1)) >> 2, xt = 1024 + 16 * w + u;
    const uint32_t o0 = CH_A3 + 4 * (w == 0 ? u : w == 1 ? 256 + r2 : 256 + 64 * w + r4), ost = w == 0 ? 64 : w == 1 ? 32 : 16;
    const uint32_t oa0 = u >= 0 || w == 3 ? o0 : CH_A3 + 4 * (w == 1 ? 256 + u : w == 2 ? 384 + r2 : 0);
    const uint32_t ot = CH_A3 + 4 * min(512, 256 + ((xt + 1 + ((xt >> 2) & 1)) >> 2));
    const int kap = (lane >> 4) * 8 + ((lane >> 1) & 7), gam = lane & 1, hh = w >> 1, wp = w & 1;
    const uint32_t oa = CH_U + wp * UPLANE + (127 - 4 * kap - 2 * gam - hh) * 16;
    const uint32_t ob = CH_U + (wp ^ 1) * UPLANE + (128 - wp - 4 * kap - 2 * gam - hh) * 16;
    const uint32_t od = CH_A3 + (4 * wp + hh) * 512 + (kap >> 3) * 256 + (kap & 7) * 16 + gam * 8;
    const int tid = threadIdx.x & 127;
    const uint32_t og = CH_G + (tid >= 24) * 16 + min(tid, 47) * 8, cend = sb + OFF_CONV + 3 * CH_STRIDE;
    {
        float nx[17]; uint2 n0, n1;
#define LDT(b) nx[0] = ldsf((b) + oa0); nx[16] = ldsf((b) + ot); _Pragma("unroll") for (int s = 1; s < 16; s++) nx[s] = ldsf((b) + o0 + s * ost); n0 = lds64((b) + og); n1 = lds64((b) + og + 8)
        LDT(sb + OFF_CONV);
        #pragma unroll 1
        for (uint32_t cb = sb + OFF_CONV; cb <= cend; cb += CH_STRIDE) {
            float kv[17];
            #pragma unroll
            for (int s = 0; s < 17; s++) kv[s] = nx[s];
            if (tid < 48) sts128(cb + CH_B3 + tid * 16, n0.x, n0.y, n1.x, n1.y);
            LDT(min(cb + CH_STRIDE, cend));
            if (u < 0 && w == 0) kv[0] = 0.f;
            if (xt > 1028) kv[16] = 0.f;
            uint32_t o[17];
            #pragma unroll
            for (int s = 0; s < 17; s++) o[s] = pack2(kv[s], __shfl_up_sync(0xffffffffu, kv[s], 1));
            if (lane > 0 && lane < 31) {
                const uint32_t ta = cb + CH_T + (lane - 1) * 280;
                #pragma unroll
                for (int s2 = 0; s2 < 8; s2++) sts64(ta + 64 * w + s2 * 8, o[2 * s2], o[2 * s2 + 1]);
                stsf(ta + 256 + 4 * w, UF(o[16]));
            }
        }
#undef LDT
    }
    STAMP(61);
    mbar_wait(bars + 8 * B_U, 0);
    if (lane < 8) sts128(sb + OFF_CONV + w * CH_STRIDE + CH_U + 2048 + (lane & 4) * (UPLANE / 4) + (lane & 3) * 16, 0, 0, 0, 0);
    bar_sync(2);
    STAMP(17);
    uint2 n0 = lds64(sb + OFF_CONV + ob + 24), n3 = lds64(sb + OFF_CONV + oa);
    uint4 n1 = lds128(sb + OFF_CONV + oa + 16), n2 = lds128(sb + OFF_CONV + ob);
    #pragma unroll 1
    for (uint32_t cb = sb + OFF_CONV; cb <= cend; cb += CH_STRIDE) {
        const uint32_t r[12] = {n0.x, n0.y, n1.x, n1.y, n1.z, n1.w, n2.x, n2.y, n2.z, n2.w, n3.x, n3.y}, nb = min(cb + CH_STRIDE, cend);
        n0 = lds64(nb + ob + 24); n3 = lds64(nb + oa); n1 = lds128(nb + oa + 16); n2 = lds128(nb + ob);
        float p[24];
        p[0] = 0.f; p[1] = bf_lo(r[0]);
        #pragma unroll
        for (int i = 2; i < 24; i++) p[i] = p[i - 1] + ((i & 1) ? bf_lo(r[i >> 1]) : bf_hi(r[(i - 1) >> 1]));
        #pragma unroll
        for (int i = 0; i < 8; i += 4) {
            sts64(cb + od + i * 256, pack2(p[i + 9] - p[i], p[i + 10] - p[i + 1]), pack2(p[i + 11] - p[i + 2], p[i + 12] - p[i + 3]));
            sts64(cb + od + i * 256 + 128, pack2(p[i + 16] - p[i + 9], p[i + 17] - p[i + 10]), pack2(p[i + 18] - p[i + 11], p[i + 19] - p[i + 12]));
        }
    }
    fence_async_smem();
    mbar_arrive(bars + 8 * B_CONV);
    STAMP(21);
}

__device__ __forceinline__ void store_h(uint32_t sb, const Params& P, const Maps& M, int V, int tg, int fb) {
    const uint32_t bars = sb + OFF_BAR;
    mbar_wait(bars + 8 * (B_EPI + V), 0);
    STAMP2(3 + 2 * V);
    asm volatile("cp.async.bulk.tensor.3d.global.shared::cta.bulk_group [%0, {%2, %3, %4}], [%1];"
        :: "l"(&M.hst[V]), "r"(sb + OFF_X + V * 2 * XBUF), "r"(0), "r"(43 * tg + 21 * V), "r"(8 * fb) : "memory");
    flag_signal(P.flags, F_H + 2 * tg + V);
    mbar_arrive(bars + 8 * (B_STG + V));
    STAMP2(4 + 2 * V);
}

__global__ void __launch_bounds__(512, 1)
fused_kernel(const __grid_constant__ Params P, const __grid_constant__ Maps M) {
    extern __shared__ __align__(1024) uint8_t smem_raw[];
    const uint32_t sb = smem_u32(smem_raw);
    const uint32_t bars = sb + OFF_BAR;
    const int warp = __shfl_sync(0xffffffffu, threadIdx.x >> 5, 0);
    const int c = blockIdx.x, tg = c / 22, fb = c - 22 * tg;
    SsmRaw raw;
    {
        const int d = min(4 * c + (warp & 3), DM - 1), o = d * 128 + (warp >> 2) * 32 + (threadIdx.x & 31);
        raw.la = ldu16(P.logA + o); raw.ai = ldu16(P.Aim + o); raw.cr = ldu16(P.Cr + o); raw.ci = ldu16(P.Ci + o);
        raw.ldt = ldu16(P.logdt + d); raw.dsk = ldu16(P.Dskip + d);
    }
    if (elect_one()) {
        if (warp == 0) { STAMP(24); GSTAMP(22); }
        asm volatile("" :: "l"(((const uint64_t*)&P)[warp < 15 ? warp : 0]));
        if (warp < 11) asm volatile("prefetch.tensormap [%0];" :: "l"(&M.x[0] + warp) : "memory");
        #pragma unroll
        for (int k = 0; k < 4; k++) {
            const int i = 16 * k + ((warp + 4) & 15);
            const uint32_t cnt = i >= B_LNX ? 1 : i >= B_CONV ? 128 : ((0xf0ull >> i) & 1) ? 8 : ((0xff0000ull >> i) & 1) ? 2 : ((0x3e00ff00f000ull >> i) & 1) ? 4 : 1;
            asm volatile("mbarrier.init.shared::cta.b64 [%0], %1;" :: "r"(bars + 8 * i), "r"(cnt) : "memory");
        }
        asm volatile("fence.mbarrier_init.release.cluster; fence.proxy.async.shared::cta;" ::: "memory");
        if (warp == 12 || warp == 13) {
            const uint32_t s = warp - 12;
            mbar_expect(bars + 8 * (B_FULLW + s), 16384);
            tma2d(sb + OFF_W + s * 16384, &M.wg, 64 * fb, 64 * s, bars + 8 * (B_FULLW + s));
            tma2d(sb + OFF_W + s * 16384 + 8192, &M.wu, 64 * fb, 64 * s, bars + 8 * (B_FULLW + s));
            STAMP(31);
        } else if (warp >= 4 && warp < 7) {
            const uint32_t s = warp - 4, V = s >> 1;
            mbar_expect(bars + 8 * (B_FULLX + s), (168 + 8 * V) * 128);
            tma2d(sb + OFF_X + s * XBUF, &M.x[V], 64 * (s & 1), TOKG * tg + 168 * V, bars + 8 * (B_FULLX + s));
        } else if ((warp >> 2) == 2 && c < 128) {
            const int w = warp & 3;
            mbar_expect(bars + 8 * (B_LNX + w), 4096);
            #pragma unroll
            for (int i = 0; i < 4; i++)
                bulk_load(sb + OFF_CONV + w * CH_STRIDE + CH_LN + (w & 1) * 64 + i * 1040,
                          P.x + (16 * (c & ~1) + 8 * (c & 1) + 16 + w + 4 * (i & 1) - 8 * (i & 2)) * DM, 1024, bars + 8 * (B_LNX + w));
        }
        if (sb & 1023) __trap();
    }
    if (warp < 4) sts128(sb + OFF_X + (warp >> 1) * XBUF + 168 * 128 + (threadIdx.x & 63) * 16, 0x3f803f80u, 0x3f803f80u, 0x3f803f80u, 0x3f803f80u);
    float dacc[2][3][4];
    #pragma unroll
    for (int i = 0; i < 24; i++) (&dacc[0][0][0])[i] = 0.f;
    if (c < 128) {
        const int wg = warp >> 2;
        const uint32_t fs = sb + OFF_CONV + (warp & 3) * CH_STRIDE + (wg == 2 ? CH_LNT : CH_PART + min(wg, 2) * CH_PSZ);
        kernel_gen(fs, threadIdx.x & 31, raw, dacc);
        if (wg != 2) {
            __syncwarp();
            #pragma unroll
            for (int i = 0; i < 6; i++) { const float* d = &dacc[0][0][0] + 4 * i; sts128(fs + (threadIdx.x & 31) * 16 + i * 512, FU(d[0]), FU(d[1]), FU(d[2]), FU(d[3])); }
        }
    }
    if (warp < 4) fence_async_smem();
    __syncthreads();
    if (warp < 8) {
        asm volatile("setmaxnreg.inc.sync.aligned.u32 208;");
        consumer(sb, warp, P, M);
        asm volatile("nanosleep.u32 1;");
    } else if (warp < 12) {
        asm volatile("setmaxnreg.dec.sync.aligned.u32 72;");
        STAMP(32);
        aux_role(sb, warp - 8, dacc, bf_lo(raw.dsk));
        if (warp == 8 && c < 128 && elect_one()) { mbar_wait(bars + 8 * B_HF, 0); if (ALIGN2) start_wait(P.flags); mbar_arrive(bars + 8 * B_S); }
        asm volatile("nanosleep.u32 2;");
    } else {
        asm volatile("setmaxnreg.dec.sync.aligned.u32 24;");
        const int tau = c >> 2, dg = c & 3;
        if (elect_one()) {
            if (warp < 15) {
                if (warp == 12) {
                    #pragma unroll 1
                    for (int st = 2; st < 8; st++) {
                        const uint32_t s = st & 3, fb_ = bars + 8 * (B_FULLW + s);
                        mbar_wait(bars + 8 * (B_EMPTYW + s), (st >> 2) ^ 1);
                        mbar_expect(fb_, 16384);
                        tma2d(sb + OFF_W + s * 16384, &M.wg, 64 * fb, 64 * st, fb_);
                        tma2d(sb + OFF_W + s * 16384 + 8192, &M.wu, 64 * fb, 64 * st, fb_);
                    }
                } else {
                    const int V = warp - 13;
                    #pragma unroll 1
                    for (int st = 2 - V; st < 8; st++) {
                        const uint32_t s = 2 * V + (st & 1);
                        mbar_wait(bars + 8 * (B_EMPTYX + s), ((st >> 1) & 1) ^ 1);
                        mbar_expect(bars + 8 * (B_FULLX + s), (168 + 8 * V) * 128);
                        tma2d(sb + OFF_X + s * XBUF, &M.x[V], 64 * st, TOKG * tg + 168 * V, bars + 8 * (B_FULLX + s));
                    }
                }
                if (warp == 14) store_h(sb, P, M, 1, tg, fb);
                if (c < 128 && warp < 14) {
                    if (warp == 13) {
                        mbar_wait(bars + 8 * (B_STG + 1), 0);
                        #pragma unroll 1
                        for (int o = 8 * tau; o < 8 * tau + 8; o += 7) flag_wait(P.flags, F_H + 2 * (o / 43) + ((o % 43) >= 21), 22);
                        start_vote(P.flags);
                        mbar_arrive(bars + 8 * B_HF);
                        STAMP(25); GSTAMP(37);
                    }
                    #pragma unroll 1
                    for (int st = 0; st < 22; st += (st < 6 || (st == 6 && warp == 13)) ? 1 : 2) {
                        const int rd = (st >= 7) + (st >= 14) + (st >= 21), sd = st - 7 * rd;
                        const uint32_t fb_ = bars + 8 * (B_FULLD + sd);
                        if (rd) mbar_wait(bars + 8 * (B_EMPTYD + sd), (rd & 1) ^ 1);
                        else if (warp == 12 || st == 6) mbar_wait(bars + 8 * (uint32_t)((0x3623070d060504ull >> (8 * st)) & 0xff), st < 5);
                        if (st >= 10 && st < 21) STAMP2(31 + st);
                        if (rd || warp == 13) {
                            mbar_expect(fb_, 8192);
                            asm volatile("cp.async.bulk.tensor.5d.shared::cluster.global.mbarrier::complete_tx::bytes [%0], [%1, {%3, %3, %3, %4, %5}], [%2];"
                                :: "r"(sb + h_slot(sd)), "l"(&M.hld), "r"(fb_), "r"(0), "r"(2 * tau), "r"(8 * st) : "memory");
                        }
                        if (rd || warp == 12) {
                            const uint32_t da = sb + wd_slot(sd);
                            mbar_expect(fb_, 16384);
                            tma2d(da, &M.wd, 128 * dg, 64 * st, fb_);
                            tma2d(da + 8192, &M.wd, 128 * dg + 64, 64 * st, fb_);
                        }
                    }
                } else if (c < 128) {
                    mbar_wait(bars + 8 * (B_SIG + 1), 0);
                    mbar_expect(bars + 8 * B_XO, 32768);
                    tma2d(sb + OFF_XO, &M.xo, 128 * dg, 64 * tau, bars + 8 * B_XO);
                    tma2d(sb + OFF_XO + 8192, &M.xo, 128 * dg + 64, 64 * tau, bars + 8 * B_XO);
                    mbar_wait(bars + 8 * B_SST, 0);
                    flag_wait(P.flags, F_S + dg, 64);
                    STAMP(26);
                    asm volatile("cp.async.bulk.tensor.5d.shared::cluster.global.mbarrier::complete_tx::bytes [%0], [%1, {%3, %3, %3, %4, %5}], [%2];"
                        :: "r"(sb + OFF_SI), "l"(&M.sld), "r"(bars + 8 * B_XO), "r"(0), "r"(8 * dg), "r"(2 * tau) : "memory");
                    mbar_wait(bars + 8 * B_S, 0);
                    exit_count(P.flags);
                }
            } else {
                if (c < 128) {
                    asm volatile("cp.async.bulk.prefetch.L2.global [%0], %1;" :: "l"((const char*)P.Wg + 256 * FF * 2 + c * 5504), "r"(5504) : "memory");
                    asm volatile("cp.async.bulk.prefetch.L2.global [%0], %1;" :: "l"((const char*)P.Wu + 256 * FF * 2 + c * 5504), "r"(5504) : "memory");
                }
                mbar_wait(bars + 8 * B_LN, 0);
                STAMP2(0);
                if (c < 128) {
                    #pragma unroll 1
                    for (int i = 0; i < 4; i++)
                        asm volatile("cp.async.bulk.tensor.2d.global.shared::cta.bulk_group [%0, {%2, %3}], [%1];"
                            :: "l"(&M.xt), "r"(sb + OFF_CONV + i * CH_STRIDE + CH_LNT), "r"((c & 1) * 1024 + (126 - (c & ~1)) * 8), "r"(128 * i) : "memory");
                    #pragma unroll 1
                    for (int i = 0; i < 2; i++) bulk_store(P.st + 16 * (c & ~1) + 8 * (c & 1) + 16 - 16 * i, sb + OFF_CSUM + 64 * i, 64);
                    asm volatile("cp.async.bulk.prefetch.L2.global [%0], %1;" :: "l"(P.Wd + c * (FF * DM / 128)), "r"(FF * DM / 64) : "memory");
                }
                STAMP2(1);
                flag_signal(P.flags, F_A);
                STAMP2(2);
                flag_wait(P.flags, F_A, NCTA);
                STAMP(20);
                mbar_expect(bars + 8 * B_STATS, TOKG * 8);
                bulk_load(sb + OFF_ST, P.st + TOKG * tg, TOKG * 8, bars + 8 * B_STATS);
                if (c < 128) {
                    mbar_expect(bars + 8 * B_U, 8 * 2048);
                    #pragma unroll 1
                    for (int i = 0; i < 8; i++)
                        bulk_load(sb + OFF_CONV + (i >> 1) * CH_STRIDE + CH_U + (i & 1) * UPLANE, P.xnT + 4 * c * 256 + i * 128, 2048, bars + 8 * B_U);
                } else exit_count(P.flags);
                store_h(sb, P, M, 0, tg, fb);
                if (c < 128) {
                    #pragma unroll 1
                    for (int V = 0; V < 2; V++) {
                        mbar_wait(bars + 8 * (B_SIG + V), 0);
                        STAMP2(7 + 2 * V);
                        bulk_store(P.S + (2 * c + V) * 1024, sb + OFF_CONV + V * OFF_SST, 8192);
                        flag_signal(P.flags, F_S + (c >> 5));
                        STAMP2(8 + 2 * V);
                    }
                    mbar_arrive(bars + 8 * B_SST);
                }
            }
            asm volatile("nanosleep.u32 0;");
        }
    }
}

typedef CUresult (*EncodeFn)(CUtensorMap*, CUtensorMapDataType, cuuint32_t, void*, const cuuint64_t*, const cuuint64_t*, const cuuint32_t*,
                             const cuuint32_t*, CUtensorMapInterleave, CUtensorMapSwizzle, CUtensorMapL2promotion, CUtensorMapFloatOOBfill);

void make_map(EncodeFn enc, CUtensorMap* m, const void* ptr, int rank, const cuuint64_t* dims, const cuuint64_t* strides, const cuuint32_t* box, bool swz, bool wide = false) {
    const cuuint32_t es[5] = {1, 1, 1, 1, 1};
    enc(m, CU_TENSOR_MAP_DATA_TYPE_BFLOAT16, rank, (void*)ptr, dims, strides, box, es, CU_TENSOR_MAP_INTERLEAVE_NONE,
        swz ? CU_TENSOR_MAP_SWIZZLE_128B : CU_TENSOR_MAP_SWIZZLE_NONE, wide ? CU_TENSOR_MAP_L2_PROMOTION_L2_256B : CU_TENSOR_MAP_L2_PROMOTION_L2_128B, CU_TENSOR_MAP_FLOAT_OOB_FILL_NONE);
}
void make_map2(EncodeFn enc, CUtensorMap* m, const void* ptr, cuuint64_t inner, cuuint64_t outer, cuuint32_t rows) {
    const cuuint64_t dims[2] = {inner, outer}, strides[1] = {inner * 2};
    const cuuint32_t box[2] = {64, rows};
    make_map(enc, m, ptr, 2, dims, strides, box, true, rows > 64);
}

}

extern "C" void kernel_launch(void* const* d_in, const int* in_sizes, int n_in, void* d_out, int out_size) {
    (void)in_sizes; (void)n_in; (void)out_size;
    static EncodeFn enc = nullptr;
    static void *hptr, *p_xnT, *p_st, *p_S, *p_flags;
    if (!enc) {
        cudaDriverEntryPointQueryResult qr;
        cudaGetDriverEntryPoint("cuTensorMapEncodeTiled", (void**)&enc, cudaEnableDefault, &qr);
        cudaFuncSetAttribute(fused_kernel, cudaFuncAttributeMaxDynamicSharedMemorySize, SMEM_BYTES);
        cudaGetSymbolAddress(&hptr, g_H); cudaGetSymbolAddress(&p_xnT, g_xnT); cudaGetSymbolAddress(&p_st, g_st);
        cudaGetSymbolAddress(&p_S, g_S); cudaGetSymbolAddress(&p_flags, g_flags);
    }
    Params P;
    P.x = (const __nv_bfloat16*)d_in[0]; P.logA = (const __nv_bfloat16*)d_in[1]; P.Aim = (const __nv_bfloat16*)d_in[2];
    P.Cr = (const __nv_bfloat16*)d_in[3]; P.Ci = (const __nv_bfloat16*)d_in[4]; P.logdt = (const __nv_bfloat16*)d_in[5];
    P.Dskip = (const __nv_bfloat16*)d_in[6];
    P.Wg = (const __nv_bfloat16*)d_in[8]; P.Wu = (const __nv_bfloat16*)d_in[9]; P.Wd = (const __nv_bfloat16*)d_in[10]; P.out = (__nv_bfloat16*)d_out; P.xnT = (uint4*)p_xnT; P.st = (float2*)p_st; P.S = (uint2*)p_S; P.flags = (unsigned*)p_flags;
    Maps M;
    make_map2(enc, &M.x[0], d_in[0], DM, SEQ, 168); make_map2(enc, &M.x[1], d_in[0], DM, SEQ, 176);
    make_map2(enc, &M.xo, d_in[0], DM, SEQ, 64);
    make_map2(enc, &M.wg, d_in[8], FF, DM, 64);     make_map2(enc, &M.wu, d_in[9], FF, DM, 64);
    make_map2(enc, &M.wd, d_in[10], DM, FF, 64);
    for (int v = 0; v < 2; v++) {
        const cuuint64_t dims[3] = {64, 256, 172}, strides[2] = {128, 32768};
        const cuuint32_t box[3] = {64, (cuuint32_t)(21 + v), 8};
        make_map(enc, &M.hst[v], hptr, 3, dims, strides, box, false);
    }
    {
        const cuuint64_t dims[2] = {2048, 512}, strides[1] = {4096};
        const cuuint32_t box[2] = {16, 128};
        make_map(enc, &M.xt, p_xnT, 2, dims, strides, box, false);
    }
    {
        const cuuint64_t dims[5] = {64, 2, 4, 32, 64}, strides[4] = {4 * 8192, 8192, 8 * 8192, 128};
        const cuuint32_t box[5] = {64, 2, 4, 8, 2};
        make_map(enc, &M.sld, p_S, 5, dims, strides, box, true);
    }
    {
        const cuuint64_t dims[5] = {64, 2, 2, 64, 172}, strides[4] = {256, 128, 512, 32768};
        const cuuint32_t box[5] = {64, 2, 2, 2, 8};
        make_map(enc, &M.hld, hptr, 5, dims, strides, box, false);
    }
    fused_kernel<<<NCTA, 512, SMEM_BYTES>>>(P, M);
}
```

```cpp
#include <cuda_runtime.h>
#include <cuda_bf16.h>
#include <cuda.h>
#include <stdint.h>

#define PROF 0

namespace {

constexpr int SEQ = 2048, DM = 512, FF = 1376;
constexpr int NCTA = 132;
#define SIGK 3
#define KUNR 1
constexpr int KUNR_ = KUNR;
constexpr int TOKG = 344;

constexpr uint32_t OFF_W = 0;
constexpr uint32_t XBUF = 22528;
constexpr uint32_t OFF_X = 65536;
constexpr uint32_t OFF_CONV = 155648;
constexpr uint32_t CH_STRIDE = 17536;
constexpr uint32_t CH_T = 0;
constexpr uint32_t CH_A3 = 8448;
constexpr uint32_t CH_B3 = 12544;
constexpr uint32_t CH_U = 13312;
constexpr uint32_t CH_G = CH_A3 + 2064;
constexpr uint32_t UPLANE = 2112;
constexpr uint32_t CH_LN = 0, CH_PART = 4224, CH_PSZ = 3072, CH_LNT = 13440;
constexpr uint32_t OFF_SST = 60416;
constexpr uint32_t OFF_XO = 191488, OFF_SI = 207872;
constexpr uint32_t OFF_ST = 225792;
constexpr uint32_t OFF_CSUM = 228544;
constexpr uint32_t OFF_BAR = 229056;
constexpr uint32_t SMEM_BYTES = 229568;

enum {
    B_FULLW = 0, B_EMPTYW = 4, B_FULLX = 8, B_EMPTYX = 12, B_FULLD = 16, B_EMPTYD = 24,
    B_U = 32, B_XO = 33, B_S = 34, B_STG = 35, B_HF = 37, B_STATS = 38, B_LNS = 39, B_SST = 40,
    B_TURN = 43,
    B_CONV = 46, B_LN = 50, B_CS = 51, B_EPI = 52, B_SIG = 54,
    B_LNX = 60
};
enum { F_A = 0, F_H = 1, F_S = 13, F_EXIT = 17, F_COUNT = 18 };

__device__ uint4 g_xnT[DM * 256];
__device__ float2 g_st[6 * TOKG];
__device__ uint4 g_H[172 * 256 * 8];
__device__ uint2 g_S[256 * 1024];
__device__ __align__(128) unsigned g_flags[F_COUNT * 32];
#define STAMP(i) do {} while (0)
#define GSTAMP(i) do {} while (0)
#define STAMP2(i) do {} while (0)

__device__ __forceinline__ uint32_t smem_u32(const void* p) { return (uint32_t)__cvta_generic_to_shared(p); }
__device__ __forceinline__ void mbar_expect(uint32_t bar, uint32_t bytes) { asm volatile("mbarrier.arrive.expect_tx.shared::cta.b64 _, [%0], %1;" :: "r"(bar), "r"(bytes) : "memory"); }
__device__ __forceinline__ void mbar_arrive(uint32_t bar) { asm volatile("mbarrier.arrive.shared::cta.b64 _, [%0];" :: "r"(bar) : "memory"); }
__device__ __forceinline__ void mbar_wait(uint32_t bar, uint32_t parity) {
    asm volatile("{.reg .pred p; .reg .u32 n; mov.u32 n, 0x20000;\n"
                 "LW: mbarrier.try_wait.parity.shared::cta.b64 p, [%0], %1;\n"
                 "sub.u32 n, n, 1; setp.eq.or.u32 p, n, 0, p; @!p bra LW;}" :: "r"(bar), "r"(parity) : "memory");
}
__device__ __forceinline__ void mbar_arrive_if(uint32_t bar, uint32_t pred) {
    asm volatile("{.reg .pred p; setp.ne.u32 p, %1, 0; @p mbarrier.arrive.shared::cta.b64 _, [%0];}" :: "r"(bar), "r"(pred) : "memory");
}
__device__ __forceinline__ bool elect_one() { uint32_t p; asm volatile("{.reg .pred P; elect.sync _|P, 0xffffffff; selp.u32 %0, 1, 0, P;}" : "=r"(p)); return p; }
__device__ __forceinline__ void tma2d(uint32_t dst, const CUtensorMap* m, int c0, int c1, uint32_t bar) {
    asm volatile("cp.async.bulk.tensor.2d.shared::cluster.global.mbarrier::complete_tx::bytes [%0], [%1, {%3, %4}], [%2];"
        :: "r"(dst), "l"(m), "r"(bar), "r"(c0), "r"(c1) : "memory");
}
__device__ __forceinline__ void bulk_load(uint32_t dst, const void* src, uint32_t bytes, uint32_t bar) {
    asm volatile("cp.async.bulk.shared::cluster.global.mbarrier::complete_tx::bytes [%0], [%1], %2, [%3];" :: "r"(dst), "l"(src), "r"(bytes), "r"(bar) : "memory");
}
__device__ __forceinline__ void bulk_store(void* dst, uint32_t src, uint32_t bytes) {
    asm volatile("cp.async.bulk.global.shared::cta.bulk_group [%0], [%1], %2;" :: "l"(dst), "r"(src), "r"(bytes) : "memory");
}
__device__ __forceinline__ void fence_async_smem() { asm volatile("fence.proxy.async.shared::cta;" ::: "memory"); }
__device__ __forceinline__ void flag_wait(unsigned* g_flags, int f, unsigned target) {
    asm volatile("{.reg .pred p; .reg .u32 n, v; mov.u32 n, 0x40000;\n"
                 "LF: ld.acquire.gpu.global.u32 v, [%0]; setp.ge.u32 p, v, %1; @p bra LD;\n"
                 "sub.u32 n, n, 1; setp.ne.u32 p, n, 0; @p bra LF; trap;\nLD: }"
                 :: "l"(g_flags + f * 32), "r"(target) : "memory");
}
__device__ __forceinline__ void flag_signal(unsigned* g_flags, int f) {
    asm volatile("cp.async.bulk.commit_group; cp.async.bulk.wait_group 0; red.relaxed.gpu.global.add.u32 [%0], 1;" :: "l"(g_flags + f * 32) : "memory");
}
__device__ __forceinline__ void exit_count(unsigned* g_flags) {
    if (atomicAdd(g_flags + F_EXIT * 32, 1u) == NCTA - 1) {
        #pragma unroll 1
        for (int i = 0; i < F_COUNT; i++) g_flags[i * 32] = 0;
    }
}
__device__ __forceinline__ void bar_sync(int id) { asm volatile("bar.sync %0, 128;" :: "r"(id) : "memory"); }
__device__ __forceinline__ uint64_t mkdesc(uint32_t addr, uint32_t lbo, uint32_t sbo, uint32_t swz) {
    return (uint64_t)((addr >> 4) | ((lbo >> 4) << 16)) | ((uint64_t)((sbo >> 4) | (swz << 30)) << 32);
}
#define WG_FENCE() asm volatile("wgmma.fence.sync.aligned;" ::: "memory")
#define WG_COMMIT() asm volatile("wgmma.commit_group.sync.aligned;" ::: "memory")
#define WG_WAIT(n) asm volatile("wgmma.wait_group.sync.aligned " #n ";" ::: "memory")
template <int N> __device__ __forceinline__ void fence_acc(float (&d)[N]) {
    #pragma unroll
    for (int i = 0; i < N; i++) asm volatile("" : "+f"(d[i]) :: "memory");
}
template <int N> __device__ __forceinline__ void define_acc(float (&d)[N]) {
    #pragma unroll
    for (int i = 0; i < N; i++) asm volatile("" : "=f"(d[i]));
}
__device__ __forceinline__ uint32_t pack2(float lo, float hi) { uint32_t r; asm("cvt.rn.bf16x2.f32 %0, %1, %2;" : "=r"(r) : "f"(hi), "f"(lo)); return r; }
__device__ __forceinline__ float bf_lo(uint32_t v) { return __uint_as_float(v << 16); }
__device__ __forceinline__ float bf_hi(uint32_t v) { return __uint_as_float(v & 0xffff0000u); }
__device__ __forceinline__ float bf_round(float v) { return bf_hi(pack2(0.f, v)); }
__device__ __forceinline__ float tanh_fast(float v) { float r; asm("tanh.approx.f32 %0, %1;" : "=f"(r) : "f"(v)); return r; }
__device__ __forceinline__ float ex2(float v) { float r; asm("ex2.approx.ftz.f32 %0, %1;" : "=f"(r) : "f"(v)); return r; }
__device__ __forceinline__ uint4 lds128(uint32_t a) { uint4 v; asm volatile("ld.shared.v4.b32 {%0,%1,%2,%3}, [%4];" : "=r"(v.x), "=r"(v.y), "=r"(v.z), "=r"(v.w) : "r"(a)); return v; }
__device__ __forceinline__ uint2 lds64(uint32_t a) { uint2 v; asm volatile("ld.shared.v2.b32 {%0,%1}, [%2];" : "=r"(v.x), "=r"(v.y) : "r"(a)); return v; }
__device__ __forceinline__ float ldsf(uint32_t a) { float v; asm volatile("ld.shared.f32 %0, [%1];" : "=f"(v) : "r"(a)); return v; }
__device__ __forceinline__ void sts128(uint32_t a, uint32_t x, uint32_t y, uint32_t z, uint32_t w) { asm volatile("st.shared.v4.b32 [%0], {%1,%2,%3,%4};" :: "r"(a), "r"(x), "r"(y), "r"(z), "r"(w) : "memory"); }
__device__ __forceinline__ void sts64(uint32_t a, uint32_t x, uint32_t y) { asm volatile("st.shared.v2.b32 [%0], {%1,%2};" :: "r"(a), "r"(x), "r"(y) : "memory"); }
__device__ __forceinline__ void stsf(uint32_t a, float x) { asm volatile("st.shared.f32 [%0], %1;" :: "r"(a), "f"(x) : "memory"); }
__device__ __forceinline__ void sts16(uint32_t a, uint32_t x) { asm volatile("st.shared.b16 [%0], %1;" :: "r"(a), "h"((unsigned short)x) : "memory"); }
__device__ __forceinline__ void stsm4(uint32_t a, uint32_t r0, uint32_t r1, uint32_t r2, uint32_t r3) {
    asm volatile("stmatrix.sync.aligned.m8n8.x4.shared.b16 [%0], {%1,%2,%3,%4};" :: "r"(a), "r"(r0), "r"(r1), "r"(r2), "r"(r3) : "memory");
}
__device__ __forceinline__ void ldsm4(uint32_t (&r)[4], uint32_t a) {
    asm volatile("ldmatrix.sync.aligned.m8n8.x4.shared.b16 {%0,%1,%2,%3}, [%4];" : "=r"(r[0]), "=r"(r[1]), "=r"(r[2]), "=r"(r[3]) : "r"(a) : "memory");
}
#define FU(x) __float_as_uint(x)
#define UF(x) __uint_as_float(x)
__device__ __forceinline__ uint32_t wd_slot(int s) { return (uint32_t)((0xbba8403056201000ull >> (8 * s)) & 0xff) << 10; }
__device__ __forceinline__ uint32_t h_slot(int s) { return (uint32_t)((0xcba0908880787068ull >> (8 * s)) & 0xff) << 10; }

template<int N> __device__ __forceinline__ void wg_rs(float (&d)[64], uint32_t a0, uint32_t a1, uint32_t a2, uint32_t a3, uint64_t db);
template<> __device__ __forceinline__ void wg_rs<128>(float (&d)[64], uint32_t a0, uint32_t a1, uint32_t a2, uint32_t a3, uint64_t db) {
  asm volatile("{.reg .pred p; setp.ne.b32 p, 1, 0; wgmma.mma_async.sync.aligned.m64n128k16.f32.bf16.bf16 {%0,%1,%2,%3,%4,%5,%6,%7,%8,%9,%10,%11,%12,%13,%14,%15,%16,%17,%18,%19,%20,%21,%22,%23,%24,%25,%26,%27,%28,%29,%30,%31,%32,%33,%34,%35,%36,%37,%38,%39,%40,%41,%42,%43,%44,%45,%46,%47,%48,%49,%50,%51,%52,%53,%54,%55,%56,%57,%58,%59,%60,%61,%62,%63}, {%64,%65,%66,%67}, %68, p, 1, 1, 0;}"
    : "+f"(d[0]),"+f"(d[1]),"+f"(d[2]),"+f"(d[3]),"+f"(d[4]),"+f"(d[5]),"+f"(d[6]),"+f"(d[7]),"+f"(d[8]),"+f"(d[9]),"+f"(d[10]),"+f"(d[11]),"+f"(d[12]),"+f"(d[13]),"+f"(d[14]),"+f"(d[15]),"+f"(d[16]),"+f"(d[17]),"+f"(d[18]),"+f"(d[19]),"+f"(d[20]),"+f"(d[21]),"+f"(d[22]),"+f"(d[23]),"+f"(d[24]),"+f"(d[25]),"+f"(d[26]),"+f"(d[27]),"+f"(d[28]),"+f"(d[29]),"+f"(d[30]),"+f"(d[31]),"+f"(d[32]),"+f"(d[33]),"+f"(d[34]),"+f"(d[35]),"+f"(d[36]),"+f"(d[37]),"+f"(d[38]),"+f"(d[39]),"+f"(d[40]),"+f"(d[41]),"+f"(d[42]),"+f"(d[43]),"+f"(d[44]),"+f"(d[45]),"+f"(d[46]),"+f"(d[47]),"+f"(d[48]),"+f"(d[49]),"+f"(d[50]),"+f"(d[51]),"+f"(d[52]),"+f"(d[53]),"+f"(d[54]),"+f"(d[55]),"+f"(d[56]),"+f"(d[57]),"+f"(d[58]),"+f"(d[59]),"+f"(d[60]),"+f"(d[61]),"+f"(d[62]),"+f"(d[63]) : "r"(a0), "r"(a1), "r"(a2), "r"(a3), "l"(db));
}
template<> __device__ __forceinline__ void wg_rs<120>(float (&d)[64], uint32_t a0, uint32_t a1, uint32_t a2, uint32_t a3, uint64_t db) {
  asm volatile("{.reg .pred p; setp.ne.b32 p, 1, 0; wgmma.mma_async.sync.aligned.m64n120k16.f32.bf16.bf16 {%0,%1,%2,%3,%4,%5,%6,%7,%8,%9,%10,%11,%12,%13,%14,%15,%16,%17,%18,%19,%20,%21,%22,%23,%24,%25,%26,%27,%28,%29,%30,%31,%32,%33,%34,%35,%36,%37,%38,%39,%40,%41,%42,%43,%44,%45,%46,%47,%48,%49,%50,%51,%52,%53,%54,%55,%56,%57,%58,%59}, {%60,%61,%62,%63}, %64, p, 1, 1, 0;}"
    : "+f"(d[0]),"+f"(d[1]),"+f"(d[2]),"+f"(d[3]),"+f"(d[4]),"+f"(d[5]),"+f"(d[6]),"+f"(d[7]),"+f"(d[8]),"+f"(d[9]),"+f"(d[10]),"+f"(d[11]),"+f"(d[12]),"+f"(d[13]),"+f"(d[14]),"+f"(d[15]),"+f"(d[16]),"+f"(d[17]),"+f"(d[18]),"+f"(d[19]),"+f"(d[20]),"+f"(d[21]),"+f"(d[22]),"+f"(d[23]),"+f"(d[24]),"+f"(d[25]),"+f"(d[26]),"+f"(d[27]),"+f"(d[28]),"+f"(d[29]),"+f"(d[30]),"+f"(d[31]),"+f"(d[32]),"+f"(d[33]),"+f"(d[34]),"+f"(d[35]),"+f"(d[36]),"+f"(d[37]),"+f"(d[38]),"+f"(d[39]),"+f"(d[40]),"+f"(d[41]),"+f"(d[42]),"+f"(d[43]),"+f"(d[44]),"+f"(d[45]),"+f"(d[46]),"+f"(d[47]),"+f"(d[48]),"+f"(d[49]),"+f"(d[50]),"+f"(d[51]),"+f"(d[52]),"+f"(d[53]),"+f"(d[54]),"+f"(d[55]),"+f"(d[56]),"+f"(d[57]),"+f"(d[58]),"+f"(d[59]) : "r"(a0), "r"(a1), "r"(a2), "r"(a3), "l"(db));
}
template<> __device__ __forceinline__ void wg_rs<112>(float (&d)[64], uint32_t a0, uint32_t a1, uint32_t a2, uint32_t a3, uint64_t db) {
  asm volatile("{.reg .pred p; setp.ne.b32 p, 1, 0; wgmma.mma_async.sync.aligned.m64n112k16.f32.bf16.bf16 {%0,%1,%2,%3,%4,%5,%6,%7,%8,%9,%10,%11,%12,%13,%14,%15,%16,%17,%18,%19,%20,%21,%22,%23,%24,%25,%26,%27,%28,%29,%30,%31,%32,%33,%34,%35,%36,%37,%38,%39,%40,%41,%42,%43,%44,%45,%46,%47,%48,%49,%50,%51,%52,%53,%54,%55}, {%56,%57,%58,%59}, %60, p, 1, 1, 0;}"
    : "+f"(d[0]),"+f"(d[1]),"+f"(d[2]),"+f"(d[3]),"+f"(d[4]),"+f"(d[5]),"+f"(d[6]),"+f"(d[7]),"+f"(d[8]),"+f"(d[9]),"+f"(d[10]),"+f"(d[11]),"+f"(d[12]),"+f"(d[13]),"+f"(d[14]),"+f"(d[15]),"+f"(d[16]),"+f"(d[17]),"+f"(d[18]),"+f"(d[19]),"+f"(d[20]),"+f"(d[21]),"+f"(d[22]),"+f"(d[23]),"+f"(d[24]),"+f"(d[25]),"+f"(d[26]),"+f"(d[27]),"+f"(d[28]),"+f"(d[29]),"+f"(d[30]),"+f"(d[31]),"+f"(d[32]),"+f"(d[33]),"+f"(d[34]),"+f"(d[35]),"+f"(d[36]),"+f"(d[37]),"+f"(d[38]),"+f"(d[39]),"+f"(d[40]),"+f"(d[41]),"+f"(d[42]),"+f"(d[43]),"+f"(d[44]),"+f"(d[45]),"+f"(d[46]),"+f"(d[47]),"+f"(d[48]),"+f"(d[49]),"+f"(d[50]),"+f"(d[51]),"+f"(d[52]),"+f"(d[53]),"+f"(d[54]),"+f"(d[55]) : "r"(a0), "r"(a1), "r"(a2), "r"(a3), "l"(db));
}
template<> __device__ __forceinline__ void wg_rs<104>(float (&d)[64], uint32_t a0, uint32_t a1, uint32_t a2, uint32_t a3, uint64_t db) {
  asm volatile("{.reg .pred p; setp.ne.b32 p, 1, 0; wgmma.mma_async.sync.aligned.m64n104k16.f32.bf16.bf16 {%0,%1,%2,%3,%4,%5,%6,%7,%8,%9,%10,%11,%12,%13,%14,%15,%16,%17,%18,%19,%20,%21,%22,%23,%24,%25,%26,%27,%28,%29,%30,%31,%32,%33,%34,%35,%36,%37,%38,%39,%40,%41,%42,%43,%44,%45,%46,%47,%48,%49,%50,%51}, {%52,%53,%54,%55}, %56, p, 1, 1, 0;}"
    : "+f"(d[0]),"+f"(d[1]),"+f"(d[2]),"+f"(d[3]),"+f"(d[4]),"+f"(d[5]),"+f"(d[6]),"+f"(d[7]),"+f"(d[8]),"+f"(d[9]),"+f"(d[10]),"+f"(d[11]),"+f"(d[12]),"+f"(d[13]),"+f"(d[14]),"+f"(d[15]),"+f"(d[16]),"+f"(d[17]),"+f"(d[18]),"+f"(d[19]),"+f"(d[20]),"+f"(d[21]),"+f"(d[22]),"+f"(d[23]),"+f"(d[24]),"+f"(d[25]),"+f"(d[26]),"+f"(d[27]),"+f"(d[28]),"+f"(d[29]),"+f"(d[30]),"+f"(d[31]),"+f"(d[32]),"+f"(d[33]),"+f"(d[34]),"+f"(d[35]),"+f"(d[36]),"+f"(d[37]),"+f"(d[38]),"+f"(d[39]),"+f"(d[40]),"+f"(d[41]),"+f"(d[42]),"+f"(d[43]),"+f"(d[44]),"+f"(d[45]),"+f"(d[46]),"+f"(d[47]),"+f"(d[48]),"+f"(d[49]),"+f"(d[50]),"+f"(d[51]) : "r"(a0), "r"(a1), "r"(a2), "r"(a3), "l"(db));
}
template<> __device__ __forceinline__ void wg_rs<96>(float (&d)[64], uint32_t a0, uint32_t a1, uint32_t a2, uint32_t a3, uint64_t db) {
  asm volatile("{.reg .pred p; setp.ne.b32 p, 1, 0; wgmma.mma_async.sync.aligned.m64n96k16.f32.bf16.bf16 {%0,%1,%2,%3,%4,%5,%6,%7,%8,%9,%10,%11,%12,%13,%14,%15,%16,%17,%18,%19,%20,%21,%22,%23,%24,%25,%26,%27,%28,%29,%30,%31,%32,%33,%34,%35,%36,%37,%38,%39,%40,%41,%42,%43,%44,%45,%46,%47}, {%48,%49,%50,%51}, %52, p, 1, 1, 0;}"
    : "+f"(d[0]),"+f"(d[1]),"+f"(d[2]),"+f"(d[3]),"+f"(d[4]),"+f"(d[5]),"+f"(d[6]),"+f"(d[7]),"+f"(d[8]),"+f"(d[9]),"+f"(d[10]),"+f"(d[11]),"+f"(d[12]),"+f"(d[13]),"+f"(d[14]),"+f"(d[15]),"+f"(d[16]),"+f"(d[17]),"+f"(d[18]),"+f"(d[19]),"+f"(d[20]),"+f"(d[21]),"+f"(d[22]),"+f"(d[23]),"+f"(d[24]),"+f"(d[25]),"+f"(d[26]),"+f"(d[27]),"+f"(d[28]),"+f"(d[29]),"+f"(d[30]),"+f"(d[31]),"+f"(d[32]),"+f"(d[33]),"+f"(d[34]),"+f"(d[35]),"+f"(d[36]),"+f"(d[37]),"+f"(d[38]),"+f"(d[39]),"+f"(d[40]),"+f"(d[41]),"+f"(d[42]),"+f"(d[43]),"+f"(d[44]),"+f"(d[45]),"+f"(d[46]),"+f"(d[47]) : "r"(a0), "r"(a1), "r"(a2), "r"(a3), "l"(db));
}
template<> __device__ __forceinline__ void wg_rs<88>(float (&d)[64], uint32_t a0, uint32_t a1, uint32_t a2, uint32_t a3, uint64_t db) {
  asm volatile("{.reg .pred p; setp.ne.b32 p, 1, 0; wgmma.mma_async.sync.aligned.m64n88k16.f32.bf16.bf16 {%0,%1,%2,%3,%4,%5,%6,%7,%8,%9,%10,%11,%12,%13,%14,%15,%16,%17,%18,%19,%20,%21,%22,%23,%24,%25,%26,%27,%28,%29,%30,%31,%32,%33,%34,%35,%36,%37,%38,%39,%40,%41,%42,%43}, {%44,%45,%46,%47}, %48, p, 1, 1, 0;}"
    : "+f"(d[0]),"+f"(d[1]),"+f"(d[2]),"+f"(d[3]),"+f"(d[4]),"+f"(d[5]),"+f"(d[6]),"+f"(d[7]),"+f"(d[8]),"+f"(d[9]),"+f"(d[10]),"+f"(d[11]),"+f"(d[12]),"+f"(d[13]),"+f"(d[14]),"+f"(d[15]),"+f"(d[16]),"+f"(d[17]),"+f"(d[18]),"+f"(d[19]),"+f"(d[20]),"+f"(d[21]),"+f"(d[22]),"+f"(d[23]),"+f"(d[24]),"+f"(d[25]),"+f"(d[26]),"+f"(d[27]),"+f"(d[28]),"+f"(d[29]),"+f"(d[30]),"+f"(d[31]),"+f"(d[32]),"+f"(d[33]),"+f"(d[34]),"+f"(d[35]),"+f"(d[36]),"+f"(d[37]),"+f"(d[38]),"+f"(d[39]),"+f"(d[40]),"+f"(d[41]),"+f"(d[42]),"+f"(d[43]) : "r"(a0), "r"(a1), "r"(a2), "r"(a3), "l"(db));
}
template<> __device__ __forceinline__ void wg_rs<80>(float (&d)[64], uint32_t a0, uint32_t a1, uint32_t a2, uint32_t a3, uint64_t db) {
  asm volatile("{.reg .pred p; setp.ne.b32 p, 1, 0; wgmma.mma_async.sync.aligned.m64n80k16.f32.bf16.bf16 {%0,%1,%2,%3,%4,%5,%6,%7,%8,%9,%10,%11,%12,%13,%14,%15,%16,%17,%18,%19,%20,%21,%22,%23,%24,%25,%26,%27,%28,%29,%30,%31,%32,%33,%34,%35,%36,%37,%38,%39}, {%40,%41,%42,%43}, %44, p, 1, 1, 0;}"
    : "+f"(d[0]),"+f"(d[1]),"+f"(d[2]),"+f"(d[3]),"+f"(d[4]),"+f"(d[5]),"+f"(d[6]),"+f"(d[7]),"+f"(d[8]),"+f"(d[9]),"+f"(d[10]),"+f"(d[11]),"+f"(d[12]),"+f"(d[13]),"+f"(d[14]),"+f"(d[15]),"+f"(d[16]),"+f"(d[17]),"+f"(d[18]),"+f"(d[19]),"+f"(d[20]),"+f"(d[21]),"+f"(d[22]),"+f"(d[23]),"+f"(d[24]),"+f"(d[25]),"+f"(d[26]),"+f"(d[27]),"+f"(d[28]),"+f"(d[29]),"+f"(d[30]),"+f"(d[31]),"+f"(d[32]),"+f"(d[33]),"+f"(d[34]),"+f"(d[35]),"+f"(d[36]),"+f"(d[37]),"+f"(d[38]),"+f"(d[39]) : "r"(a0), "r"(a1), "r"(a2), "r"(a3), "l"(db));
}
template<> __device__ __forceinline__ void wg_rs<72>(float (&d)[64], uint32_t a0, uint32_t a1, uint32_t a2, uint32_t a3, uint64_t db) {
  asm volatile("{.reg .pred p; setp.ne.b32 p, 1, 0; wgmma.mma_async.sync.aligned.m64n72k16.f32.bf16.bf16 {%0,%1,%2,%3,%4,%5,%6,%7,%8,%9,%10,%11,%12,%13,%14,%15,%16,%17,%18,%19,%20,%21,%22,%23,%24,%25,%26,%27,%28,%29,%30,%31,%32,%33,%34,%35}, {%36,%37,%38,%39}, %40, p, 1, 1, 0;}"
    : "+f"(d[0]),"+f"(d[1]),"+f"(d[2]),"+f"(d[3]),"+f"(d[4]),"+f"(d[5]),"+f"(d[6]),"+f"(d[7]),"+f"(d[8]),"+f"(d[9]),"+f"(d[10]),"+f"(d[11]),"+f"(d[12]),"+f"(d[13]),"+f"(d[14]),"+f"(d[15]),"+f"(d[16]),"+f"(d[17]),"+f"(d[18]),"+f"(d[19]),"+f"(d[20]),"+f"(d[21]),"+f"(d[22]),"+f"(d[23]),"+f"(d[24]),"+f"(d[25]),"+f"(d[26]),"+f"(d[27]),"+f"(d[28]),"+f"(d[29]),"+f"(d[30]),"+f"(d[31]),"+f"(d[32]),"+f"(d[33]),"+f"(d[34]),"+f"(d[35]) : "r"(a0), "r"(a1), "r"(a2), "r"(a3), "l"(db));
}
template<> __device__ __forceinline__ void wg_rs<64>(float (&d)[64], uint32_t a0, uint32_t a1, uint32_t a2, uint32_t a3, uint64_t db) {
  asm volatile("{.reg .pred p; setp.ne.b32 p, 1, 0; wgmma.mma_async.sync.aligned.m64n64k16.f32.bf16.bf16 {%0,%1,%2,%3,%4,%5,%6,%7,%8,%9,%10,%11,%12,%13,%14,%15,%16,%17,%18,%19,%20,%21,%22,%23,%24,%25,%26,%27,%28,%29,%30,%31}, {%32,%33,%34,%35}, %36, p, 1, 1, 0;}"
    : "+f"(d[0]),"+f"(d[1]),"+f"(d[2]),"+f"(d[3]),"+f"(d[4]),"+f"(d[5]),"+f"(d[6]),"+f"(d[7]),"+f"(d[8]),"+f"(d[9]),"+f"(d[10]),"+f"(d[11]),"+f"(d[12]),"+f"(d[13]),"+f"(d[14]),"+f"(d[15]),"+f"(d[16]),"+f"(d[17]),"+f"(d[18]),"+f"(d[19]),"+f"(d[20]),"+f"(d[21]),"+f"(d[22]),"+f"(d[23]),"+f"(d[24]),"+f"(d[25]),"+f"(d[26]),"+f"(d[27]),"+f"(d[28]),"+f"(d[29]),"+f"(d[30]),"+f"(d[31]) : "r"(a0), "r"(a1), "r"(a2), "r"(a3), "l"(db));
}
__device__ __forceinline__ void wg_rs_first(float (&d)[64], uint32_t a0, uint32_t a1, uint32_t a2, uint32_t a3, uint64_t db) {
  asm volatile("{.reg .pred p; setp.ne.b32 p, 0, 0; wgmma.mma_async.sync.aligned.m64n128k16.f32.bf16.bf16 {%0,%1,%2,%3,%4,%5,%6,%7,%8,%9,%10,%11,%12,%13,%14,%15,%16,%17,%18,%19,%20,%21,%22,%23,%24,%25,%26,%27,%28,%29,%30,%31,%32,%33,%34,%35,%36,%37,%38,%39,%40,%41,%42,%43,%44,%45,%46,%47,%48,%49,%50,%51,%52,%53,%54,%55,%56,%57,%58,%59,%60,%61,%62,%63}, {%64,%65,%66,%67}, %68, p, 1, 1, 0;}"
    : "=f"(d[0]),"=f"(d[1]),"=f"(d[2]),"=f"(d[3]),"=f"(d[4]),"=f"(d[5]),"=f"(d[6]),"=f"(d[7]),"=f"(d[8]),"=f"(d[9]),"=f"(d[10]),"=f"(d[11]),"=f"(d[12]),"=f"(d[13]),"=f"(d[14]),"=f"(d[15]),"=f"(d[16]),"=f"(d[17]),"=f"(d[18]),"=f"(d[19]),"=f"(d[20]),"=f"(d[21]),"=f"(d[22]),"=f"(d[23]),"=f"(d[24]),"=f"(d[25]),"=f"(d[26]),"=f"(d[27]),"=f"(d[28]),"=f"(d[29]),"=f"(d[30]),"=f"(d[31]),"=f"(d[32]),"=f"(d[33]),"=f"(d[34]),"=f"(d[35]),"=f"(d[36]),"=f"(d[37]),"=f"(d[38]),"=f"(d[39]),"=f"(d[40]),"=f"(d[41]),"=f"(d[42]),"=f"(d[43]),"=f"(d[44]),"=f"(d[45]),"=f"(d[46]),"=f"(d[47]),"=f"(d[48]),"=f"(d[49]),"=f"(d[50]),"=f"(d[51]),"=f"(d[52]),"=f"(d[53]),"=f"(d[54]),"=f"(d[55]),"=f"(d[56]),"=f"(d[57]),"=f"(d[58]),"=f"(d[59]),"=f"(d[60]),"=f"(d[61]),"=f"(d[62]),"=f"(d[63]) : "r"(a0), "r"(a1), "r"(a2), "r"(a3), "l"(db));
}
__device__ __forceinline__ void wg_tt128(float (&d)[64], uint64_t da, uint64_t db, int sc) {
  asm volatile("{.reg .pred p; setp.ne.b32 p, %66, 0; wgmma.mma_async.sync.aligned.m64n128k16.f32.bf16.bf16 {%0,%1,%2,%3,%4,%5,%6,%7,%8,%9,%10,%11,%12,%13,%14,%15,%16,%17,%18,%19,%20,%21,%22,%23,%24,%25,%26,%27,%28,%29,%30,%31,%32,%33,%34,%35,%36,%37,%38,%39,%40,%41,%42,%43,%44,%45,%46,%47,%48,%49,%50,%51,%52,%53,%54,%55,%56,%57,%58,%59,%60,%61,%62,%63}, %64, %65, p, 1, 1, 1, 1;}"
    : "+f"(d[0]),"+f"(d[1]),"+f"(d[2]),"+f"(d[3]),"+f"(d[4]),"+f"(d[5]),"+f"(d[6]),"+f"(d[7]),"+f"(d[8]),"+f"(d[9]),"+f"(d[10]),"+f"(d[11]),"+f"(d[12]),"+f"(d[13]),"+f"(d[14]),"+f"(d[15]),"+f"(d[16]),"+f"(d[17]),"+f"(d[18]),"+f"(d[19]),"+f"(d[20]),"+f"(d[21]),"+f"(d[22]),"+f"(d[23]),"+f"(d[24]),"+f"(d[25]),"+f"(d[26]),"+f"(d[27]),"+f"(d[28]),"+f"(d[29]),"+f"(d[30]),"+f"(d[31]),"+f"(d[32]),"+f"(d[33]),"+f"(d[34]),"+f"(d[35]),"+f"(d[36]),"+f"(d[37]),"+f"(d[38]),"+f"(d[39]),"+f"(d[40]),"+f"(d[41]),"+f"(d[42]),"+f"(d[43]),"+f"(d[44]),"+f"(d[45]),"+f"(d[46]),"+f"(d[47]),"+f"(d[48]),"+f"(d[49]),"+f"(d[50]),"+f"(d[51]),"+f"(d[52]),"+f"(d[53]),"+f"(d[54]),"+f"(d[55]),"+f"(d[56]),"+f"(d[57]),"+f"(d[58]),"+f"(d[59]),"+f"(d[60]),"+f"(d[61]),"+f"(d[62]),"+f"(d[63]) : "l"(da), "l"(db), "r"(sc));
}
__device__ __forceinline__ void wg_tt64(float (&d)[64], uint64_t da, uint64_t db, int sc) {
  asm volatile("{.reg .pred p; setp.ne.b32 p, %34, 0; wgmma.mma_async.sync.aligned.m64n64k16.f32.bf16.bf16 {%0,%1,%2,%3,%4,%5,%6,%7,%8,%9,%10,%11,%12,%13,%14,%15,%16,%17,%18,%19,%20,%21,%22,%23,%24,%25,%26,%27,%28,%29,%30,%31}, %32, %33, p, 1, 1, 1, 1;}"
    : "+f"(d[0]),"+f"(d[1]),"+f"(d[2]),"+f"(d[3]),"+f"(d[4]),"+f"(d[5]),"+f"(d[6]),"+f"(d[7]),"+f"(d[8]),"+f"(d[9]),"+f"(d[10]),"+f"(d[11]),"+f"(d[12]),"+f"(d[13]),"+f"(d[14]),"+f"(d[15]),"+f"(d[16]),"+f"(d[17]),"+f"(d[18]),"+f"(d[19]),"+f"(d[20]),"+f"(d[21]),"+f"(d[22]),"+f"(d[23]),"+f"(d[24]),"+f"(d[25]),"+f"(d[26]),"+f"(d[27]),"+f"(d[28]),"+f"(d[29]),"+f"(d[30]),"+f"(d[31]) : "l"(da), "l"(db), "r"(sc));
}
__device__ __forceinline__ void wg_tt32(float (&d)[64], uint64_t da, uint64_t db, int sc) {
  asm volatile("{.reg .pred p; setp.ne.b32 p, %18, 0; wgmma.mma_async.sync.aligned.m64n32k16.f32.bf16.bf16 {%0,%1,%2,%3,%4,%5,%6,%7,%8,%9,%10,%11,%12,%13,%14,%15}, %16, %17, p, 1, 1, 1, 1;}"
    : "+f"(d[0]),"+f"(d[1]),"+f"(d[2]),"+f"(d[3]),"+f"(d[4]),"+f"(d[5]),"+f"(d[6]),"+f"(d[7]),"+f"(d[8]),"+f"(d[9]),"+f"(d[10]),"+f"(d[11]),"+f"(d[12]),"+f"(d[13]),"+f"(d[14]),"+f"(d[15]) : "l"(da), "l"(db), "r"(sc));
}
__device__ __forceinline__ void wg_g1(float (&d)[88], uint64_t da, uint64_t db, int sc) {
  asm volatile("{.reg .pred p; setp.ne.b32 p, %90, 0; wgmma.mma_async.sync.aligned.m64n176k16.f32.bf16.bf16 {%0,%1,%2,%3,%4,%5,%6,%7,%8,%9,%10,%11,%12,%13,%14,%15,%16,%17,%18,%19,%20,%21,%22,%23,%24,%25,%26,%27,%28,%29,%30,%31,%32,%33,%34,%35,%36,%37,%38,%39,%40,%41,%42,%43,%44,%45,%46,%47,%48,%49,%50,%51,%52,%53,%54,%55,%56,%57,%58,%59,%60,%61,%62,%63,%64,%65,%66,%67,%68,%69,%70,%71,%72,%73,%74,%75,%76,%77,%78,%79,%80,%81,%82,%83,%84,%85,%86,%87}, %88, %89, p, 1, 1, 1, 0;}"
    : "+f"(d[0]),"+f"(d[1]),"+f"(d[2]),"+f"(d[3]),"+f"(d[4]),"+f"(d[5]),"+f"(d[6]),"+f"(d[7]),"+f"(d[8]),"+f"(d[9]),"+f"(d[10]),"+f"(d[11]),"+f"(d[12]),"+f"(d[13]),"+f"(d[14]),"+f"(d[15]),"+f"(d[16]),"+f"(d[17]),"+f"(d[18]),"+f"(d[19]),"+f"(d[20]),"+f"(d[21]),"+f"(d[22]),"+f"(d[23]),"+f"(d[24]),"+f"(d[25]),"+f"(d[26]),"+f"(d[27]),"+f"(d[28]),"+f"(d[29]),"+f"(d[30]),"+f"(d[31]),"+f"(d[32]),"+f"(d[33]),"+f"(d[34]),"+f"(d[35]),"+f"(d[36]),"+f"(d[37]),"+f"(d[38]),"+f"(d[39]),"+f"(d[40]),"+f"(d[41]),"+f"(d[42]),"+f"(d[43]),"+f"(d[44]),"+f"(d[45]),"+f"(d[46]),"+f"(d[47]),"+f"(d[48]),"+f"(d[49]),"+f"(d[50]),"+f"(d[51]),"+f"(d[52]),"+f"(d[53]),"+f"(d[54]),"+f"(d[55]),"+f"(d[56]),"+f"(d[57]),"+f"(d[58]),"+f"(d[59]),"+f"(d[60]),"+f"(d[61]),"+f"(d[62]),"+f"(d[63]),"+f"(d[64]),"+f"(d[65]),"+f"(d[66]),"+f"(d[67]),"+f"(d[68]),"+f"(d[69]),"+f"(d[70]),"+f"(d[71]),"+f"(d[72]),"+f"(d[73]),"+f"(d[74]),"+f"(d[75]),"+f"(d[76]),"+f"(d[77]),"+f"(d[78]),"+f"(d[79]),"+f"(d[80]),"+f"(d[81]),"+f"(d[82]),"+f"(d[83]),"+f"(d[84]),"+f"(d[85]),"+f"(d[86]),"+f"(d[87]) : "l"(da), "l"(db), "r"(sc));
}

struct Params { const __nv_bfloat16 *x, *logA, *Aim, *Cr, *Ci, *logdt, *Dskip, *Wg, *Wu, *Wd; __nv_bfloat16* out; uint4* xnT; float2* st; uint2* S; unsigned* flags; };
struct Maps { CUtensorMap x[2], xo, wg, wu, wd, hst[2], hld, xt, sld; };

__device__ __forceinline__ void conv_channel(uint32_t cb, int w, int lane, uint32_t (&res)[8], uint32_t sig, int sidx) {
    const int q = lane & 3, g = lane >> 2, gam = g >> 2;
    float acc[64];
    uint2 a[17][2];
    const uint32_t t0 = cb + CH_T + (uint32_t)(14 + 4 * w + (g & 3) - 2 * q) * 280u + gam * 8;
#define LDA(s0, s1) _Pragma("unroll") for (int s = s0; s < s1; s++) { a[s][0] = lds64(t0 + s * 16); a[s][1] = lds64(t0 - 8 * 280 + s * 16); }
#define CT(N, s) wg_rs<N>(acc, a[s][0].x, a[s][0].y, a[s][1].x, a[s][1].y, dU + 4 * (s))
    const uint64_t dU = mkdesc(cb + CH_U, UPLANE, 128, 0);
    LDA(0, 17)
    if (sig) { fence_async_smem(); mbar_arrive(sig); }
    WG_FENCE();
    if (w == 0) STAMP2(52 + 3 * sidx);
    wg_rs_first(acc, a[0][0].x, a[0][0].y, a[0][1].x, a[0][1].y, dU);
    CT(128, 1); CT(120, 2); CT(120, 3); CT(112, 4); CT(112, 5); CT(104, 6); CT(104, 7); CT(96, 8);
    CT(96, 9); CT(88, 10); CT(88, 11); CT(80, 12); CT(80, 13); CT(72, 14); CT(72, 15); CT(64, 16);
#undef CT
#undef LDA
    wg_tt64(acc, mkdesc(cb + CH_A3, 128, 512, 0), mkdesc(cb + CH_B3, 384, 32, 0), 1);
    wg_tt32(acc, mkdesc(cb + CH_A3 + 256, 128, 512, 0), mkdesc(cb + CH_B3 + 128, 384, 32, 0), 1);
    WG_COMMIT();
    if (w == 0) STAMP2(53 + 3 * sidx);
    WG_WAIT(0);
    fence_acc(acc);
    if (w == 0) STAMP2(54 + 3 * sidx);
    const int src1 = (lane & ~3) | ((q + 1) & 3);
    float E[16][2];
    #pragma unroll
    for (int j = 0; j < 16; j++) {
        const float nxt = (j < 15) ? acc[4 * (j + 1) + 2] : 0.f;
        const float sup = (q == 0) ? nxt : acc[4 * j + 2];
        const float v = __shfl_sync(0xffffffffu, sup, src1);
        E[j][0] = acc[4 * j] + acc[4 * j + 3];
        E[j][1] = acc[4 * j + 1] + v;
    }
    const int src2 = gam ? ((lane & 12) | ((q + 3) & 3)) : (16 | (lane & 12) | ((q + 1) & 3));
    const bool c1 = gam && q != 0, c2 = gam && q == 0;
    #pragma unroll
    for (int a2 = 0; a2 < 8; a2++) {
        float y[2];
        #pragma unroll
        for (int e = 0; e < 2; e++) {
            const float sup = c1 ? E[2 * a2][e] : E[2 * a2 + 1][e];
            const float nxt = (a2 < 7) ? E[2 * a2 + 2][e] : 0.f;
            const float keep = c2 ? nxt : (c1 ? E[2 * a2 + 1][e] : E[2 * a2][e]);
            y[e] = keep + __shfl_sync(0xffffffffu, sup, src2);
        }
        res[a2] = pack2(y[1], y[0]);
    }
}

__device__ __forceinline__ void consumer(uint32_t sb, int warp, const Params& P, const Maps& M) {
    const int V = warp >> 2, w = warp & 3, lane = threadIdx.x & 31, q = lane & 3, g = lane >> 2;
    const int c = blockIdx.x;
    const uint32_t bars = sb + OFF_BAR, xb = sb + OFF_X + V * 2 * XBUF;
    {
        float ag[88], au[88];
        define_acc(ag); define_acc(au);
        mbar_wait(bars + 8 * B_FULLW, 0);
        mbar_wait(bars + 8 * (B_FULLX + 2 * V), 0);
        #pragma unroll 1
        for (int st = 0; st < 8; st++) {
            uint64_t dG = mkdesc(sb + OFF_W + (st & 3) * 16384, 0, 1024, 1), dX = mkdesc(xb + (st & 1) * XBUF, 16, 1024, 1);
            uint32_t sig = lane == 0 && (V ? st < 6 : st > 0);
            asm volatile("" : "+l"(dG), "+l"(dX), "+r"(sig) :: "memory");
            if (V ? st < 7 : st > 1) mbar_wait(bars + 8 * (B_TURN + V), st & 1);
            STAMP(40 + 8 * V + st); if (st == 0 && V == 0) GSTAMP(33);
            WG_FENCE();
            #pragma unroll
            for (int k = 0; k < 4; k++) {
                if (k == SIGK) mbar_arrive_if(bars + 8 * (B_TURN + 1 - V), sig);
                wg_g1(ag, dG + k * 128, dX + k * 2, k ? 1 : st);
                wg_g1(au, dG + 512 + k * 128, dX + k * 2, k ? 1 : st);
            }
            WG_COMMIT();
            if (st == 6 * V) {
                mbar_wait(bars + 8 * (B_FULLW + ((st + 1) & 3)), V);
                mbar_wait(bars + 8 * (B_FULLX + 2 * V + 1), V);
            } else {
                WG_WAIT(1);
                mbar_arrive_if(bars + 8 * (B_EMPTYW + 2 * V), lane == 0 && st == 6 * V + 1);
                mbar_arrive_if(bars + 8 * (B_EMPTYX + 2 * V), lane == 0 && st == 6 * V + 1);
                WG_WAIT(0);
                mbar_arrive_if(bars + 8 * (B_EMPTYW + (st & 3)), lane == 0);
                mbar_arrive_if(bars + 8 * (B_EMPTYX + 2 * V + (st & 1)), lane == 0);
                if (st < 7) {
                    mbar_wait(bars + 8 * (B_FULLW + ((st + 1) & 3)), (st + 1) >> 2);
                    mbar_wait(bars + 8 * (B_FULLX + 2 * V + ((st + 1) & 1)), ((st + 1) >> 1) & 1);
                }
            }
        }
        WG_WAIT(0);
        fence_acc(ag); fence_acc(au);
        STAMP(8 * V + 1); GSTAMP(29 + V);
        float cg0 = ag[84], cg1 = ag[86], cu0 = au[84], cu1 = au[86];
        const uint32_t ca = sb + OFF_CSUM + (8 * w + g) * 16;
        if (V == 0) { sts128(ca, FU(cg0), FU(cg1), FU(cu0), FU(cu1)); mbar_arrive(bars + 8 * B_CS); }
        else { mbar_wait(bars + 8 * B_CS, 0); const uint4 t = lds128(ca); cg0 = UF(t.x); cg1 = UF(t.y); cu0 = UF(t.z); cu1 = UF(t.w); }
        mbar_wait(bars + 8 * B_STATS, 0);
        mbar_wait(bars + 8 * (B_EMPTYX + 2 * V), 1);
        STAMP(13 + V);
        const uint32_t hs = xb + (2 * w + ((lane >> 3) & 1)) * (2688 + 128 * V) + (lane >> 4) * 128 + (lane & 7) * 16;
        const uint32_t sa = sb + OFF_ST + (168 * V + 2 * q) * 8;
        uint4 sq[22];
        #pragma unroll
        for (int j = 0; j < 3; j++) sq[j] = lds128(sa + j * 64);
        #pragma unroll
        for (int j = 0; j < 22; j += 2) {
            uint32_t o[4];
            #pragma unroll
            for (int jj = 0; jj < 2; jj++) {
                const uint4 sv = sq[j + jj];
                float hv[4];
                #pragma unroll
                for (int i = 0; i < 4; i++) {
                    const float m = UF((i & 1) ? sv.z : sv.x);
                    const float gh = fmaf(-m, (i & 2) ? cg1 : cg0, ag[4 * (j + jj) + i]) * UF((i & 1) ? sv.w : sv.y);
                    const float p = gh * fmaf(-m, (i & 2) ? cu1 : cu0, au[4 * (j + jj) + i]);
                    hv[i] = fmaf(p, tanh_fast(gh), p);
                }
                o[2 * jj] = pack2(hv[0], hv[1]); o[2 * jj + 1] = pack2(hv[2], hv[3]);
            }
            #pragma unroll
            for (int k = (j ? 3 + 3 * j / 2 : 3); k < 6 + 3 * j / 2 && k < 22; k++) sq[k] = lds128(sa + k * 64);
            uint32_t ad = hs + j * 128;
            if (j == 20 && V == 0 && lane >= 16) ad = xb + 21504 + (lane & 7) * 16;
            stsm4(ad, o[0], o[1], o[2], o[3]);
        }
        if (c >= 128 || V) { fence_async_smem(); mbar_arrive(bars + 8 * (B_EPI + V)); }
        STAMP(8 * V + 2);
    }
    if (c >= 128) return;
    {
        mbar_wait(bars + 8 * B_CONV, 0);
        uint32_t r0[8], r1[8];
        #pragma unroll
        for (int i = 0; i < 8; i++) asm volatile("" : "=r"(r1[i]));
        #pragma unroll 1
        for (int e = 0; e < 2; e++) {
            #pragma unroll
            for (int i = 0; i < 8; i++) r0[i] = r1[i];
            conv_channel(sb + OFF_CONV + (2 * V + e) * CH_STRIDE, w, lane, r1, (e | V) ? 0 : bars + 8 * B_EPI, 2 * V + e);
            if (e == 0) STAMP(8 * V + 3);
        }
        const int gam = g >> 2, qq = gam ? ((q + 3) & 3) : q;
        const uint32_t sp = sb + OFF_CONV + V * OFF_SST + ((63 - 4 * gam - qq) * 16 + 4 * (w ^ (3 - qq)) + (g & 3)) * 8;
        bar_sync(3 + V);
        #pragma unroll
        for (int a2 = 0; a2 < 8; a2++) sts64(sp - a2 * 1024, r0[a2], r1[a2]);
        fence_async_smem();
        mbar_arrive(bars + 8 * (B_SIG + V));
        STAMP(8 * V + 4); GSTAMP(35 + V);
    }
    if (V == 1) return;
    {
        const int tau = c >> 2, dg = c & 3;
        const uint32_t row = 8 * (w & 1) + 32 * (w >> 1);
        float acc[64];
        define_acc(acc);
        const float rr0 = __ldcg(&P.st[64 * tau + row + g].y), rr1 = __ldcg(&P.st[64 * tau + row + g + 16].y);
        mbar_wait(bars + 8 * B_FULLD, 0);
        STAMP(5); GSTAMP(27);
        uint64_t dB = mkdesc(sb + wd_slot(0), 8192, 1024, 1), dA = mkdesc(sb + h_slot(0), 1024, 128, 0);
        int sd = 0; uint32_t np = 0;
        #pragma unroll 1
        for (int st = 0; st < 21; st++) {
            WG_FENCE();
            wg_tt128(acc, dA, dB, st);
            wg_tt128(acc, dA + 128, dB + 128, 1);
            wg_tt128(acc, dA + 256, dB + 256, 1);
            wg_tt128(acc, dA + 384, dB + 384, 1);
            WG_COMMIT();
            uint32_t ro = bars + 8 * (B_EMPTYD + (sd ? sd - 1 : 6)), m = lane == 0 && st > 0, ok;
            if (++sd == 7) { sd = 0; np ^= 1; }
            const uint32_t nb = bars + 8 * (B_FULLD + sd);
            dB = mkdesc(sb + wd_slot(sd), 8192, 1024, 1); dA = mkdesc(sb + h_slot(sd), 1024, 128, 0);
            asm volatile("{.reg .pred p; mbarrier.test_wait.parity.shared::cta.b64 p, [%5], %6; vote.sync.all.pred p, p, -1; selp.u32 %0, 1, 0, p;}"
                : "=r"(ok), "+l"(dA), "+l"(dB), "+r"(ro), "+r"(m) : "r"(nb), "r"(np) : "memory");
            WG_WAIT(1);
            mbar_arrive_if(ro, m);
            if (!ok) mbar_wait(nb, np);
            if (w == 0) STAMP2(20 + st);
        }
        WG_FENCE();
        wg_tt128(acc, dA, dB, 1);
        wg_tt128(acc, dA + 128, dB + 128, 1);
        WG_COMMIT();
        mbar_wait(bars + 8 * B_XO, 0);
        const uint32_t xo = sb + OFF_XO + (row + (lane & 7) + 16 * ((lane >> 3) & 1)) * 128;
        const uint32_t so = sb + OFF_SI + (w >> 1) * 8192 + q * 256 + (g & 1) * 8;
        const uint32_t sx = (4 * (w & 1) + (g >> 1)) ^ (2 * q) ^ (2 * ((2 * tau + (w >> 1)) & 3));
        uint32_t xr[8][4];
        uint2 sv[16];
        #pragma unroll
        for (int j = 0; j < 16; j += 2) {
            ldsm4(xr[j >> 1], xo + (j >> 3) * 8192 + ((((j & 7) + (lane >> 4)) ^ (lane & 7)) << 4));
            sv[j] = lds64(so + j * 512 + (sx << 4));
            sv[j + 1] = lds64(so + j * 512 + 128 + ((sx ^ 1) << 4));
        }
        WG_WAIT(0);
        fence_acc(acc);
        STAMP(6); GSTAMP(28);
        #pragma unroll
        for (int j = 0; j < 16; j += 2) {
            #pragma unroll
            for (int i = 0; i < 4; i++) {
                const int jj = j + (i >> 1), hh = i & 1;
                const float f0 = acc[4 * jj + 2 * hh] * (hh ? rr1 : rr0), f1 = acc[4 * jj + 2 * hh + 1] * (hh ? rr1 : rr0);
                const uint32_t G = pack2(fmaf(f0, tanh_fast(f0), f0), fmaf(f1, tanh_fast(f1), f1));
                const uint32_t s2 = __byte_perm(sv[jj].x, sv[jj].y, hh ? 0x7632 : 0x5410);
                asm("fma.rn.bf16x2 %0, %1, %2, %0;" : "+r"(xr[j >> 1][i]) : "r"(s2), "r"(G));
            }
            stsm4(xo + (j >> 3) * 8192 + ((((j & 7) + (lane >> 4)) ^ (lane & 7)) << 4), xr[j >> 1][0], xr[j >> 1][1], xr[j >> 1][2], xr[j >> 1][3]);
        }
        __syncwarp();
        {
            const uint32_t rr = row + ((lane >> 4) << 4), la = sb + OFF_XO + rr * 128 + ((lane >> 3) & 1) * 8192;
            uint4* dst = (uint4*)(P.out + (64 * tau + rr) * DM + 128 * dg) + (lane & 15);
            uint4 v[8];
            #pragma unroll
            for (int i = 0; i < 8; i++) v[i] = lds128(la + i * 128 + (((lane & 7) ^ i) << 4));
            #pragma unroll
            for (int i = 0; i < 8; i++) dst[i * 64] = v[i];
        }
        STAMP(7); GSTAMP(23);
    }
}

__device__ __forceinline__ float2 cexp_p(float re2, float im, float p) {
    float sn, cs;
    const float mag = ex2(re2 * p), th = im * p;
    asm("sin.approx.ftz.f32 %0, %1;" : "=f"(sn) : "f"(th));
    asm("cos.approx.ftz.f32 %0, %1;" : "=f"(cs) : "f"(th));
    return make_float2(mag * cs, mag * sn);
}
struct SsmRaw { unsigned short la, ai, cr, ci, ldt, dsk; };
__device__ __forceinline__ unsigned short ldu16(const void* p) { unsigned short v; asm volatile("ld.global.nc.u16 %0, [%1];" : "=h"(v) : "l"(p)); return v; }
__device__ __forceinline__ float2 cmul(float2 a, float2 b) { return make_float2(fmaf(a.x, b.x, -a.y * b.y), fmaf(a.x, b.y, a.y * b.x)); }
__device__ __forceinline__ float2 csqr(float2 a) { const float t = a.x * a.y; return make_float2(fmaf(a.x, a.x, -a.y * a.y), t + t); }
__device__ __forceinline__ void mma16816(float (&d)[4], const uint32_t (&a)[4], uint32_t b0, uint32_t b1) {
    asm volatile("mma.sync.aligned.m16n8k16.row.col.f32.bf16.bf16.f32 {%0,%1,%2,%3}, {%4,%5,%6,%7}, {%8,%9}, {%0,%1,%2,%3};"
        : "+f"(d[0]), "+f"(d[1]), "+f"(d[2]), "+f"(d[3]) : "r"(a[0]), "r"(a[1]), "r"(a[2]), "r"(a[3]), "r"(b0), "r"(b1));
}

__device__ __forceinline__ void layer_norm(uint32_t sb, uint32_t cb, int w, int lane) {
    const uint32_t bars = sb + OFF_BAR;
    mbar_wait(bars + 8 * (B_LNX + w), 0);
    STAMP(34);
    {
        const uint32_t r0 = cb + CH_LN + (w & 1) * 64 + (lane >> 3) * 1040, ra = r0 + (lane & 7) * 16;
        const float pv = bf_lo(FU(ldsf(r0)));
        float s0 = 0.f, s1 = 0.f, a0 = 0.f, a1 = 0.f;
        #pragma unroll 1
        for (int k = 0; k < 1024; k += 512) {
            uint32_t v[16];
            #pragma unroll
            for (int j = 0; j < 4; j++) *(uint4*)&v[4 * j] = lds128(ra + k + 128 * j);
            #pragma unroll
            for (int i = 0; i < 16; i++) { const float t0 = bf_lo(v[i]) - pv, t1 = bf_hi(v[i]) - pv; s0 += t0; s1 += t1; a0 = fmaf(t0, t0, a0); a1 = fmaf(t1, t1, a1); }
        }
        s0 += s1; a0 += a1;
        #pragma unroll
        for (int o = 4; o; o >>= 1) { s0 += __shfl_xor_sync(0xffffffffu, s0, o); a0 += __shfl_xor_sync(0xffffffffu, a0, o); }
        s0 *= 1.f / DM;
        float sd, ri;
        asm("sqrt.approx.ftz.f32 %0, %1;" : "=f"(sd) : "f"(bf_round(bf_round(fmaxf(fmaf(-s0, s0, a0 * (1.f / DM)), 0.f)) + 1e-5f)));
        asm("rcp.approx.ftz.f32 %0, %1;" : "=f"(ri) : "f"(bf_round(sd)));
        if ((lane & 7) == 0) sts64(sb + OFF_CSUM + (w + 4 * (lane >> 3)) * 8, FU(bf_round(pv + s0)), FU(0.5f * ri));
    }
    STAMP(62);
    bar_sync(2);
    const int r = 4 * ((lane & 7) >> 1) + (lane & 1) + 2 * ((lane >> 3) & 1);
    const uint32_t ad = sb + OFF_CONV + (r & 3) * CH_STRIDE + CH_LN + (r & 1) * 64 + (r >> 2) * 1040 + (16 * w + (lane >> 4)) * 16;
    const uint4 sa = lds128(sb + OFF_CSUM + (lane & 3) * 32), sc = lds128(sb + OFF_CSUM + (lane & 3) * 32 + 16);
    const uint32_t m2[2] = {__byte_perm(sa.x, sa.z, 0x7632), __byte_perm(sc.x, sc.z, 0x7632)};
    const float ri[4] = {2.f * UF(sa.y), 2.f * UF(sa.w), 2.f * UF(sc.y), 2.f * UF(sc.w)};
    #pragma unroll 1
    for (int i = 0; i < 8; i += 4) {
        uint32_t v[4][4];
        #pragma unroll
        for (int j = 0; j < 4; j++)
            asm volatile("ldmatrix.sync.aligned.m8n8.x4.trans.shared.b16 {%0,%1,%2,%3}, [%4];" : "=r"(v[j][0]), "=r"(v[j][1]), "=r"(v[j][2]), "=r"(v[j][3]) : "r"(ad + 32 * (i + j)) : "memory");
        #pragma unroll
        for (int j = 0; j < 4; j++) {
            #pragma unroll
            for (int k = 0; k < 4; k++) {
                uint32_t dv; asm("sub.rn.bf16x2 %0, %1, %2;" : "=r"(dv) : "r"(v[j][k]), "r"(m2[k & 1]));
                v[j][k] = pack2(bf_lo(dv) * ri[2 * (k & 1)], bf_hi(dv) * ri[2 * (k & 1) + 1]);
            }
            sts64(cb + CH_LNT + lane * 8 + (i + j) * 512, v[j][0], v[j][1]); sts64(cb + CH_LNT + lane * 8 + (i + j) * 512 + 256, v[j][2], v[j][3]);
        }
    }
    fence_async_smem();
    mbar_arrive(bars + 8 * B_LN);
    STAMP(16);
}

__device__ __forceinline__ void kernel_gen(uint32_t fs, int lane, const SsmRaw& raw, float (&dacc)[2][3][4], const char* pf) {
    const float dt = bf_round(ex2(bf_lo(raw.ldt) * 1.4426950408889634f));
    const float re2 = bf_round(ex2(bf_lo(raw.la) * 1.4426950408889634f)) * dt * -1.4426950408889634f, im = bf_lo(raw.ai) * dt;
    const float2 C = make_float2(bf_lo(raw.cr) * (dt + dt), bf_lo(raw.ci) * -(dt + dt));
    STAMP(56);
    const float2 y1 = cexp_p(re2, -im, 1.f), y256 = cexp_p(re2, -im, 256.f), z64 = cexp_p(re2, im, 64.f);
    const uint32_t fm = fs + (lane >> 3) * 144 + (lane & 7) * 16;
#define PK(v) pack2((v).x, (v).y)
    const float2 y2 = csqr(y1), y4 = csqr(y2), y8 = csqr(y4);
    const float2 l1 = cmul(C, y1), l2 = cmul(C, y2), l3 = cmul(l1, y2);
    stsm4(fm, PK(C), PK(l1), PK(l2), PK(l3));
    stsm4(fm + 4 * 144, PK(cmul(C, y4)), PK(cmul(l1, y4)), PK(cmul(l2, y4)), PK(cmul(l3, y4)));
    const float2 t0 = cmul(C, y256), t1 = cmul(t0, y256), t2 = cmul(t1, y256), t3_ = cmul(t2, y256);
    const float2 u1 = cmul(t0, y2), u2 = cmul(u1, y2), u3 = cmul(u2, y2);
    stsm4(fm + 8 * 144, PK(t0), PK(u1), PK(u2), PK(u3));
    stsm4(fm + 12 * 144, PK(t1), PK(cmul(t1, y4)), PK(t2), PK(cmul(t2, y4)));
    const float2 v0 = cmul(t3_, y8), v1 = cmul(v0, y256), v2 = cmul(v1, y256), v3 = cmul(v2, y256);
    stsm4(fm + 16 * 144, PK(v0), PK(v1), PK(v2), PK(v3));
    stsf(fs + lane * 4 + 20 * 144, UF(PK(t3_)));
    STAMP(57);
    if (pf) asm volatile("prefetch.global.L2 [%0];" :: "l"(pf));
    const uint32_t ldb = fs + (lane & 7) * 144 + ((lane >> 3) & 1) * 16 + (lane >> 4) * 8 * 144;
    const float p8 = (float)(2 * (lane & 28));
    __syncwarp();
    #pragma unroll KUNR_
    for (int ks = 0; ks < 4; ks++) {
        uint32_t b01[4], b2[2], a0[4], a1[4];
        ldsm4(b01, ldb + ks * 32);
        asm volatile("ldmatrix.sync.aligned.m8n8.x2.shared.b16 {%0,%1}, [%2];" : "=r"(b2[0]), "=r"(b2[1]) : "r"(ldb + 16 * 144 + ks * 32) : "memory");
        #pragma unroll
        for (int mh = 0; mh < 2; mh++) {
            const int src = 8 * ks + 4 * mh + (lane & 3);
            const float2 z = make_float2(__shfl_sync(0xffffffffu, z64.x, src), __shfl_sync(0xffffffffu, z64.y, src));
            const float2 R0 = cexp_p(__shfl_sync(0xffffffffu, re2, src), __shfl_sync(0xffffffffu, im, src), p8);
            const float2 R1 = cmul(R0, z), R2 = cmul(R1, z), R3 = cmul(R2, z);
            a0[2 * mh] = PK(R0); a0[2 * mh + 1] = PK(R1); a1[2 * mh] = PK(R2); a1[2 * mh + 1] = PK(R3);
        }
        mma16816(dacc[0][0], a0, b01[0], b01[1]); mma16816(dacc[1][0], a1, b01[0], b01[1]);
        mma16816(dacc[0][1], a0, b01[2], b01[3]); mma16816(dacc[1][1], a1, b01[2], b01[3]);
        mma16816(dacc[0][2], a0, b2[0], b2[1]);   mma16816(dacc[1][2], a1, b2[0], b2[1]);
    }
#undef PK
    STAMP(58);
}

__device__ __forceinline__ void aux_role(uint32_t sb, int w, float (&dacc)[2][3][4], float dsk) {
    const int lane = threadIdx.x & 31, q = lane & 3, g = lane >> 2;
    const int c = blockIdx.x;
    const uint32_t bars = sb + OFF_BAR;
    if (c >= 128) { mbar_arrive(bars + 8 * B_LN); return; }
    {
        const uint32_t cb = sb + OFF_CONV + w * CH_STRIDE;
        layer_norm(sb, cb, w, lane);
        {
            uint4 v[2][3];
            #pragma unroll
            for (int i = 0; i < 3; i++) v[0][i] = lds128(cb + CH_PART + lane * 16 + i * 512);
            #pragma unroll
            for (int k = 0; k < 6; k++) {
                #pragma unroll
                for (int i = 0; i < 3; i++) if (k < 5) v[(k + 1) & 1][i] = lds128(cb + CH_PART + lane * 16 + (k + 1) * 1536 + i * 512);
                #pragma unroll
                for (int i = 0; i < 3; i++) {
                    float* d = &dacc[0][0][0] + 12 * (k & 1) + 4 * i;
                    d[0] += UF(v[k & 1][i].x); d[1] += UF(v[k & 1][i].y); d[2] += UF(v[k & 1][i].z); d[3] += UF(v[k & 1][i].w);
                }
            }
        }
        __syncwarp();
        STAMP(18);
        const uint32_t sF = cb + CH_A3, sG = cb + CH_G;
        if (lane == 0) dacc[0][0][0] += dsk;
        if (lane < 10) sts128(sG + 128 + (lane & 1) * 208 + (lane >> 1) * 16, 0, 0, 0, 0);
        const uint32_t f0 = sF + (8 * g + 2 * q) * 4, f1 = sF + ((q < 2) ? 256 + 4 * g + 2 * q : 256 + 2 * g + 64 * q) * 4, st1 = (q < 2) ? 128 : 64;
        const uint32_t ga = sG + ((g & 1) ? 0 : 208) + (63 - (g >> 1) - 32 * q) * 2;
        #pragma unroll
        for (int i = 0; i < 4; i++) {
            const int mu = i >> 1, hh = i & 1;
            sts64(f0 + i * 256, FU(dacc[mu][0][2 * hh]), FU(dacc[mu][0][2 * hh + 1]));
            sts64(f1 + i * st1, FU(dacc[mu][1][2 * hh]), FU(dacc[mu][1][2 * hh + 1]));
            const uint32_t pk = pack2(dacc[mu][2][2 * hh], dacc[mu][2][2 * hh + 1]);
            if (q < 2) { sts16(ga - 8 * i, pk & 0xffff); sts16(ga - 8 * i - 32, pk >> 16); }
        }
        if (lane == 2) stsf(sF + 2048, dacc[0][2][0]);
        STAMP(19);
        bar_sync(2);
    }
    const int u = min(lane, 30) - 15, r2 = (u + ((u >> 1) & 1)) >> 1, r4 = (u + 1 + ((u >> 2) & 1)) >> 2, xt = 1024 + 16 * w + u;
    const uint32_t o0 = CH_A3 + 4 * (w == 0 ? u : w == 1 ? 256 + r2 : 256 + 64 * w + r4), ost = w == 0 ? 64 : w == 1 ? 32 : 16;
    const uint32_t oa0 = u >= 0 || w == 3 ? o0 : CH_A3 + 4 * (w == 1 ? 256 + u : w == 2 ? 384 + r2 : 0);
    const uint32_t ot = CH_A3 + 4 * min(512, 256 + ((xt + 1 + ((xt >> 2) & 1)) >> 2));
    const int kap = (lane >> 4) * 8 + ((lane >> 1) & 7), gam = lane & 1, hh = w >> 1, wp = w & 1;
    const uint32_t oa = CH_U + wp * UPLANE + (127 - 4 * kap - 2 * gam - hh) * 16;
    const uint32_t ob = CH_U + (wp ^ 1) * UPLANE + (128 - wp - 4 * kap - 2 * gam - hh) * 16;
    const uint32_t od = CH_A3 + (4 * wp + hh) * 512 + (kap >> 3) * 256 + (kap & 7) * 16 + gam * 8;
    const int tid = threadIdx.x & 127;
    const uint32_t og = CH_G + (tid >= 24) * 16 + min(tid, 47) * 8, cend = sb + OFF_CONV + 3 * CH_STRIDE;
    {
        float nx[17]; uint2 n0, n1;
#define LDT(b) nx[0] = ldsf((b) + oa0); nx[16] = ldsf((b) + ot); _Pragma("unroll") for (int s = 1; s < 16; s++) nx[s] = ldsf((b) + o0 + s * ost); n0 = lds64((b) + og); n1 = lds64((b) + og + 8)
        LDT(sb + OFF_CONV);
        #pragma unroll 1
        for (uint32_t cb = sb + OFF_CONV; cb <= cend; cb += CH_STRIDE) {
            float kv[17];
            #pragma unroll
            for (int s = 0; s < 17; s++) kv[s] = nx[s];
            if (tid < 48) sts128(cb + CH_B3 + tid * 16, n0.x, n0.y, n1.x, n1.y);
            LDT(min(cb + CH_STRIDE, cend));
            if (u < 0 && w == 0) kv[0] = 0.f;
            if (xt > 1028) kv[16] = 0.f;
            uint32_t o[17];
            #pragma unroll
            for (int s = 0; s < 17; s++) o[s] = pack2(kv[s], __shfl_up_sync(0xffffffffu, kv[s], 1));
            if (lane > 0 && lane < 31) {
                const uint32_t ta = cb + CH_T + (lane - 1) * 280;
                #pragma unroll
                for (int s2 = 0; s2 < 8; s2++) sts64(ta + 64 * w + s2 * 8, o[2 * s2], o[2 * s2 + 1]);
                stsf(ta + 256 + 4 * w, UF(o[16]));
            }
        }
#undef LDT
    }
    STAMP(61);
    mbar_wait(bars + 8 * B_U, 0);
    if (lane < 8) sts128(sb + OFF_CONV + w * CH_STRIDE + CH_U + 2048 + (lane & 4) * (UPLANE / 4) + (lane & 3) * 16, 0, 0, 0, 0);
    bar_sync(2);
    STAMP(17);
    uint2 n0 = lds64(sb + OFF_CONV + ob + 24), n3 = lds64(sb + OFF_CONV + oa);
    uint4 n1 = lds128(sb + OFF_CONV + oa + 16), n2 = lds128(sb + OFF_CONV + ob);
    #pragma unroll 1
    for (uint32_t cb = sb + OFF_CONV; cb <= cend; cb += CH_STRIDE) {
        const uint32_t r[12] = {n0.x, n0.y, n1.x, n1.y, n1.z, n1.w, n2.x, n2.y, n2.z, n2.w, n3.x, n3.y}, nb = min(cb + CH_STRIDE, cend);
        n0 = lds64(nb + ob + 24); n3 = lds64(nb + oa); n1 = lds128(nb + oa + 16); n2 = lds128(nb + ob);
        float p[24];
        p[0] = 0.f; p[1] = bf_lo(r[0]);
        #pragma unroll
        for (int i = 2; i < 24; i++) p[i] = p[i - 1] + ((i & 1) ? bf_lo(r[i >> 1]) : bf_hi(r[(i - 1) >> 1]));
        #pragma unroll
        for (int i = 0; i < 8; i += 4) {
            sts64(cb + od + i * 256, pack2(p[i + 9] - p[i], p[i + 10] - p[i + 1]), pack2(p[i + 11] - p[i + 2], p[i + 12] - p[i + 3]));
            sts64(cb + od + i * 256 + 128, pack2(p[i + 16] - p[i + 9], p[i + 17] - p[i + 10]), pack2(p[i + 18] - p[i + 11], p[i + 19] - p[i + 12]));
        }
    }
    fence_async_smem();
    mbar_arrive(bars + 8 * B_CONV);
    STAMP(21);
}

__device__ __forceinline__ void store_h(uint32_t sb, const Params& P, const Maps& M, int V, int tg, int fb) {
    const uint32_t bars = sb + OFF_BAR;
    mbar_wait(bars + 8 * (B_EPI + V), 0);
    STAMP2(3 + 2 * V);
    asm volatile("cp.async.bulk.tensor.3d.global.shared::cta.bulk_group [%0, {%2, %3, %4}], [%1];"
        :: "l"(&M.hst[V]), "r"(sb + OFF_X + V * 2 * XBUF), "r"(0), "r"(43 * tg + 21 * V), "r"(8 * fb) : "memory");
    flag_signal(P.flags, F_H + 2 * tg + V);
    mbar_arrive(bars + 8 * (B_STG + V));
    STAMP2(4 + 2 * V);
}

__global__ void __launch_bounds__(512, 1)
fused_kernel(const __grid_constant__ Params P, const __grid_constant__ Maps M) {
    extern __shared__ __align__(1024) uint8_t smem_raw[];
    const uint32_t sb = smem_u32(smem_raw);
    const uint32_t bars = sb + OFF_BAR;
    const int warp = __shfl_sync(0xffffffffu, threadIdx.x >> 5, 0);
    const int c = blockIdx.x, tg = c / 22, fb = c - 22 * tg;
    SsmRaw raw;
    {
        const int d = min(4 * c + (warp & 3), DM - 1), o = d * 128 + (warp >> 2) * 32 + (threadIdx.x & 31);
        raw.la = ldu16(P.logA + o); raw.ai = ldu16(P.Aim + o); raw.cr = ldu16(P.Cr + o); raw.ci = ldu16(P.Ci + o);
        raw.ldt = ldu16(P.logdt + d); raw.dsk = ldu16(P.Dskip + d);
    }
    if (elect_one()) {
        if (warp == 0) { STAMP(24); GSTAMP(22); }
        asm volatile("" :: "l"(((const uint64_t*)&P)[warp < 15 ? warp : 0]));
        if (warp < 11) asm volatile("prefetch.tensormap [%0];" :: "l"(&M.x[0] + warp) : "memory");
        #pragma unroll
        for (int k = 0; k < 4; k++) {
            const int i = 16 * k + ((warp + 4) & 15);
            const uint32_t cnt = i >= B_LNX ? 1 : i >= B_CONV ? 128 : ((0xf0ull >> i) & 1) ? 8 : ((0xff0000ull >> i) & 1) ? 2 : ((0x3e00ff00f000ull >> i) & 1) ? 4 : 1;
            asm volatile("mbarrier.init.shared::cta.b64 [%0], %1;" :: "r"(bars + 8 * i), "r"(cnt) : "memory");
        }
        asm volatile("fence.mbarrier_init.release.cluster; fence.proxy.async.shared::cta;" ::: "memory");
        if (warp == 12 || warp == 13) {
            const uint32_t s = warp - 12;
            mbar_expect(bars + 8 * (B_FULLW + s), 16384);
            tma2d(sb + OFF_W + s * 16384, &M.wg, 64 * fb, 64 * s, bars + 8 * (B_FULLW + s));
            tma2d(sb + OFF_W + s * 16384 + 8192, &M.wu, 64 * fb, 64 * s, bars + 8 * (B_FULLW + s));
            STAMP(31);
        } else if (warp >= 4 && warp < 7) {
            const uint32_t s = warp - 4, V = s >> 1;
            mbar_expect(bars + 8 * (B_FULLX + s), (168 + 8 * V) * 128);
            tma2d(sb + OFF_X + s * XBUF, &M.x[V], 64 * (s & 1), TOKG * tg + 168 * V, bars + 8 * (B_FULLX + s));
        } else if ((warp >> 2) == 2 && c < 128) {
            const int w = warp & 3;
            mbar_expect(bars + 8 * (B_LNX + w), 4096);
            #pragma unroll
            for (int i = 0; i < 4; i++)
                bulk_load(sb + OFF_CONV + w * CH_STRIDE + CH_LN + (w & 1) * 64 + i * 1040,
                          P.x + (16 * (c & ~1) + 8 * (c & 1) + 16 + w + 4 * (i & 1) - 8 * (i & 2)) * DM, 1024, bars + 8 * (B_LNX + w));
        }
        if (sb & 1023) __trap();
    }
    if (warp < 4) sts128(sb + OFF_X + (warp >> 1) * XBUF + 168 * 128 + (threadIdx.x & 63) * 16, 0x3f803f80u, 0x3f803f80u, 0x3f803f80u, 0x3f803f80u);
    float dacc[2][3][4];
    #pragma unroll
    for (int i = 0; i < 24; i++) (&dacc[0][0][0])[i] = 0.f;
    if (c < 128) {
        const int wg = warp >> 2;
        const uint32_t fs = sb + OFF_CONV + (warp & 3) * CH_STRIDE + (wg == 2 ? CH_LNT : CH_PART + min(wg, 2) * CH_PSZ);
        const int ln = threadIdx.x & 63;
        kernel_gen(fs, threadIdx.x & 31, raw, dacc, (wg == 3 && ln < 43) ? (const char*)((warp & 2) ? P.Wu : P.Wg) + 256 * FF * 2 + c * 5504 + ln * 128 : nullptr);
        if (wg != 2) {
            __syncwarp();
            #pragma unroll
            for (int i = 0; i < 6; i++) { const float* d = &dacc[0][0][0] + 4 * i; sts128(fs + (threadIdx.x & 31) * 16 + i * 512, FU(d[0]), FU(d[1]), FU(d[2]), FU(d[3])); }
        }
    }
    if (warp < 4) fence_async_smem();
    __syncthreads();
    if (warp < 8) {
        asm volatile("setmaxnreg.inc.sync.aligned.u32 208;");
        consumer(sb, warp, P, M);
        asm volatile("nanosleep.u32 1;");
    } else if (warp < 12) {
        asm volatile("setmaxnreg.dec.sync.aligned.u32 72;");
        STAMP(32);
        aux_role(sb, warp - 8, dacc, bf_lo(raw.dsk));
        asm volatile("nanosleep.u32 2;");
    } else {
        asm volatile("setmaxnreg.dec.sync.aligned.u32 24;");
        const int tau = c >> 2, dg = c & 3;
        if (elect_one()) {
            if (warp < 15) {
                if (warp == 12) {
                    #pragma unroll 1
                    for (int st = 2; st < 8; st++) {
                        const uint32_t s = st & 3, fb_ = bars + 8 * (B_FULLW + s);
                        mbar_wait(bars + 8 * (B_EMPTYW + s), (st >> 2) ^ 1);
                        mbar_expect(fb_, 16384);
                        tma2d(sb + OFF_W + s * 16384, &M.wg, 64 * fb, 64 * st, fb_);
                        tma2d(sb + OFF_W + s * 16384 + 8192, &M.wu, 64 * fb, 64 * st, fb_);
                    }
                } else {
                    const int V = warp - 13;
                    #pragma unroll 1
                    for (int st = 2 - V; st < 8; st++) {
                        const uint32_t s = 2 * V + (st & 1);
                        mbar_wait(bars + 8 * (B_EMPTYX + s), ((st >> 1) & 1) ^ 1);
                        mbar_expect(bars + 8 * (B_FULLX + s), (168 + 8 * V) * 128);
                        tma2d(sb + OFF_X + s * XBUF, &M.x[V], 64 * st, TOKG * tg + 168 * V, bars + 8 * (B_FULLX + s));
                    }
                }
                if (warp == 14) store_h(sb, P, M, 1, tg, fb);
                if (c < 128 && warp < 14) {
                    if (warp == 13) {
                        mbar_wait(bars + 8 * (B_STG + 1), 0);
                        #pragma unroll 1
                        for (int o = 8 * tau; o < 8 * tau + 8; o += 7) flag_wait(P.flags, F_H + 2 * (o / 43) + ((o % 43) >= 21), 22);
                        mbar_arrive(bars + 8 * B_HF);
                        STAMP(25); GSTAMP(37);
                    }
                    #pragma unroll 1
                    for (int st = 0; st < 22; st += (st < 6 || (st == 6 && warp == 13)) ? 1 : 2) {
                        const int rd = (st >= 7) + (st >= 14) + (st >= 21), sd = st - 7 * rd;
                        const uint32_t fb_ = bars + 8 * (B_FULLD + sd);
                        if (rd) mbar_wait(bars + 8 * (B_EMPTYD + sd), (rd & 1) ^ 1);
                        else if (warp == 12 || st == 6) mbar_wait(bars + 8 * (uint32_t)((0x3623070d060504ull >> (8 * st)) & 0xff), st < 5);
                        if (st >= 10 && st < 21) STAMP2(31 + st);
                        if (rd || warp == 13) {
                            mbar_expect(fb_, 8192);
                            asm volatile("cp.async.bulk.tensor.5d.shared::cluster.global.mbarrier::complete_tx::bytes [%0], [%1, {%3, %3, %3, %4, %5}], [%2];"
                                :: "r"(sb + h_slot(sd)), "l"(&M.hld), "r"(fb_), "r"(0), "r"(2 * tau), "r"(8 * st) : "memory");
                        }
                        if (rd || warp == 12) {
                            const uint32_t da = sb + wd_slot(sd);
                            mbar_expect(fb_, 16384);
                            tma2d(da, &M.wd, 128 * dg, 64 * st, fb_);
                            tma2d(da + 8192, &M.wd, 128 * dg + 64, 64 * st, fb_);
                        }
                    }
                } else if (c < 128) {
                    mbar_wait(bars + 8 * (B_SIG + 1), 0);
                    mbar_expect(bars + 8 * B_XO, 32768);
                    tma2d(sb + OFF_XO, &M.xo, 128 * dg, 64 * tau, bars + 8 * B_XO);
                    tma2d(sb + OFF_XO + 8192, &M.xo, 128 * dg + 64, 64 * tau, bars + 8 * B_XO);
                    mbar_wait(bars + 8 * B_SST, 0);
                    flag_wait(P.flags, F_S + dg, 64);
                    STAMP(26);
                    asm volatile("cp.async.bulk.tensor.5d.shared::cluster.global.mbarrier::complete_tx::bytes [%0], [%1, {%3, %3, %3, %4, %5}], [%2];"
                        :: "r"(sb + OFF_SI), "l"(&M.sld), "r"(bars + 8 * B_XO), "r"(0), "r"(8 * dg), "r"(2 * tau) : "memory");
                    mbar_wait(bars + 8 * B_HF, 0);
                    exit_count(P.flags);
                }
            } else {
                mbar_wait(bars + 8 * B_LN, 0);
                STAMP2(0);
                if (c < 128) {
                    #pragma unroll 1
                    for (int i = 0; i < 4; i++)
                        asm volatile("cp.async.bulk.tensor.2d.global.shared::cta.bulk_group [%0, {%2, %3}], [%1];"
                            :: "l"(&M.xt), "r"(sb + OFF_CONV + i * CH_STRIDE + CH_LNT), "r"((c & 1) * 1024 + (126 - (c & ~1)) * 8), "r"(128 * i) : "memory");
                    #pragma unroll 1
                    for (int i = 0; i < 2; i++) bulk_store(P.st + 16 * (c & ~1) + 8 * (c & 1) + 16 - 16 * i, sb + OFF_CSUM + 64 * i, 64);
                    asm volatile("cp.async.bulk.prefetch.L2.global [%0], %1;" :: "l"(P.Wd + c * (FF * DM / 128)), "r"(FF * DM / 64) : "memory");
                }
                STAMP2(1);
                flag_signal(P.flags, F_A);
                STAMP2(2);
                flag_wait(P.flags, F_A, NCTA);
                STAMP(20);
                mbar_expect(bars + 8 * B_STATS, TOKG * 8);
                bulk_load(sb + OFF_ST, P.st + TOKG * tg, TOKG * 8, bars + 8 * B_STATS);
                if (c < 128) {
                    mbar_expect(bars + 8 * B_U, 8 * 2048);
                    #pragma unroll 1
                    for (int i = 0; i < 8; i++)
                        bulk_load(sb + OFF_CONV + (i >> 1) * CH_STRIDE + CH_U + (i & 1) * UPLANE, P.xnT + 4 * c * 256 + i * 128, 2048, bars + 8 * B_U);
                } else exit_count(P.flags);
                store_h(sb, P, M, 0, tg, fb);
                if (c < 128) {
                    #pragma unroll 1
                    for (int V = 0; V < 2; V++) {
                        mbar_wait(bars + 8 * (B_SIG + V), 0);
                        STAMP2(7 + 2 * V);
                        bulk_store(P.S + (2 * c + V) * 1024, sb + OFF_CONV + V * OFF_SST, 8192);
                        flag_signal(P.flags, F_S + (c >> 5));
                        STAMP2(8 + 2 * V);
                    }
                    mbar_arrive(bars + 8 * B_SST);
                }
            }
            asm volatile("nanosleep.u32 0;");
        }
    }
}

typedef CUresult (*EncodeFn)(CUtensorMap*, CUtensorMapDataType, cuuint32_t, void*, const cuuint64_t*, const cuuint64_t*, const cuuint32_t*,
                             const cuuint32_t*, CUtensorMapInterleave, CUtensorMapSwizzle, CUtensorMapL2promotion, CUtensorMapFloatOOBfill);

void make_map(EncodeFn enc, CUtensorMap* m, const void* ptr, int rank, const cuuint64_t* dims, const cuuint64_t* strides, const cuuint32_t* box, bool swz, bool wide = false) {
    const cuuint32_t es[5] = {1, 1, 1, 1, 1};
    enc(m, CU_TENSOR_MAP_DATA_TYPE_BFLOAT16, rank, (void*)ptr, dims, strides, box, es, CU_TENSOR_MAP_INTERLEAVE_NONE,
        swz ? CU_TENSOR_MAP_SWIZZLE_128B : CU_TENSOR_MAP_SWIZZLE_NONE, wide ? CU_TENSOR_MAP_L2_PROMOTION_L2_256B : CU_TENSOR_MAP_L2_PROMOTION_L2_128B, CU_TENSOR_MAP_FLOAT_OOB_FILL_NONE);
}
void make_map2(EncodeFn enc, CUtensorMap* m, const void* ptr, cuuint64_t inner, cuuint64_t outer, cuuint32_t rows) {
    const cuuint64_t dims[2] = {inner, outer}, strides[1] = {inner * 2};
    const cuuint32_t box[2] = {64, rows};
    make_map(enc, m, ptr, 2, dims, strides, box, true, rows > 64);
}

}

extern "C" void kernel_launch(void* const* d_in, const int* in_sizes, int n_in, void* d_out, int out_size) {
    (void)in_sizes; (void)n_in; (void)out_size;
    static EncodeFn enc = nullptr;
    static void *hptr, *p_xnT, *p_st, *p_S, *p_flags;
    if (!enc) {
        cudaDriverEntryPointQueryResult qr;
        cudaGetDriverEntryPoint("cuTensorMapEncodeTiled", (void**)&enc, cudaEnableDefault, &qr);
        cudaFuncSetAttribute(fused_kernel, cudaFuncAttributeMaxDynamicSharedMemorySize, SMEM_BYTES);
        cudaGetSymbolAddress(&hptr, g_H); cudaGetSymbolAddress(&p_xnT, g_xnT); cudaGetSymbolAddress(&p_st, g_st);
        cudaGetSymbolAddress(&p_S, g_S); cudaGetSymbolAddress(&p_flags, g_flags);
    }
    Params P;
    P.x = (const __nv_bfloat16*)d_in[0]; P.logA = (const __nv_bfloat16*)d_in[1]; P.Aim = (const __nv_bfloat16*)d_in[2];
    P.Cr = (const __nv_bfloat16*)d_in[3]; P.Ci = (const __nv_bfloat16*)d_in[4]; P.logdt = (const __nv_bfloat16*)d_in[5];
    P.Dskip = (const __nv_bfloat16*)d_in[6];
    P.Wg = (const __nv_bfloat16*)d_in[8]; P.Wu = (const __nv_bfloat16*)d_in[9]; P.Wd = (const __nv_bfloat16*)d_in[10]; P.out = (__nv_bfloat16*)d_out; P.xnT = (uint4*)p_xnT; P.st = (float2*)p_st; P.S = (uint2*)p_S; P.flags = (unsigned*)p_flags;
    Maps M;
    make_map2(enc, &M.x[0], d_in[0], DM, SEQ, 168); make_map2(enc, &M.x[1], d_in[0], DM, SEQ, 176);
    make_map2(enc, &M.xo, d_in[0], DM, SEQ, 64);
    make_map2(enc, &M.wg, d_in[8], FF, DM, 64);     make_map2(enc, &M.wu, d_in[9], FF, DM, 64);
    make_map2(enc, &M.wd, d_in[10], DM, FF, 64);
    for (int v = 0; v < 2; v++) {
        const cuuint64_t dims[3] = {64, 256, 172}, strides[2] = {128, 32768};
        const cuuint32_t box[3] = {64, (cuuint32_t)(21 + v), 8};
        make_map(enc, &M.hst[v], hptr, 3, dims, strides, box, false);
    }
    {
        const cuuint64_t dims[2] = {2048, 512}, strides[1] = {4096};
        const cuuint32_t box[2] = {16, 128};
        make_map(enc, &M.xt, p_xnT, 2, dims, strides, box, false);
    }
    {
        const cuuint64_t dims[5] = {64, 2, 4, 32, 64}, strides[4] = {4 * 8192, 8192, 8 * 8192, 128};
        const cuuint32_t box[5] = {64, 2, 4, 8, 2};
        make_map(enc, &M.sld, p_S, 5, dims, strides, box, true);
    }
    {
        const cuuint64_t dims[5] = {64, 2, 2, 64, 172}, strides[4] = {256, 128, 512, 32768};
        const cuuint32_t box[5] = {64, 2, 2, 2, 8};
        make_map(enc, &M.hld, hptr, 5, dims, strides, box, false);
    }
    fused_kernel<<<NCTA, 512, SMEM_BYTES>>>(P, M);
}
```

```cpp
#include <cuda_runtime.h>
#include <cuda_bf16.h>
#include <cuda.h>
#include <stdint.h>

#define PROF 0

namespace {

constexpr int SEQ = 2048, DM = 512, FF = 1376;
constexpr int NCTA = 132;
#define SIGK 3
#define KUNR 4
constexpr int KUNR_ = KUNR;
constexpr int TOKG = 344;

constexpr uint32_t OFF_W = 0;
constexpr uint32_t XBUF = 22528;
constexpr uint32_t OFF_X = 65536;
constexpr uint32_t OFF_CONV = 155648;
constexpr uint32_t CH_STRIDE = 17536;
constexpr uint32_t CH_T = 0;
constexpr uint32_t CH_A3 = 8448;
constexpr uint32_t CH_B3 = 12544;
constexpr uint32_t CH_U = 13312;
constexpr uint32_t CH_G = CH_A3 + 2064;
constexpr uint32_t UPLANE = 2112;
constexpr uint32_t CH_LN = 0, CH_PART = 4224, CH_PSZ = 3072, CH_LNT = 13440;
constexpr uint32_t OFF_SST = 60416;
constexpr uint32_t OFF_XO = 191488, OFF_SI = 207872;
constexpr uint32_t OFF_ST = 225792;
constexpr uint32_t OFF_CSUM = 228544;
constexpr uint32_t OFF_BAR = 229056;
constexpr uint32_t SMEM_BYTES = 229568;

enum {
    B_FULLW = 0, B_EMPTYW = 4, B_FULLX = 8, B_EMPTYX = 12, B_FULLD = 16, B_EMPTYD = 24,
    B_U = 32, B_XO = 33, B_S = 34, B_STG = 35, B_HF = 37, B_STATS = 38, B_LNS = 39, B_SST = 40,
    B_TURN = 43,
    B_CONV = 46, B_LN = 50, B_CS = 51, B_EPI = 52, B_SIG = 54,
    B_LNX = 60
};
enum { F_A = 0, F_H = 1, F_S = 13, F_EXIT = 17, F_COUNT = 18 };

__device__ uint4 g_xnT[DM * 256];
__device__ float2 g_st[6 * TOKG];
__device__ uint4 g_H[172 * 256 * 8];
__device__ uint2 g_S[256 * 1024];
__device__ __align__(128) unsigned g_flags[F_COUNT * 32];
#define STAMP(i) do {} while (0)
#define GSTAMP(i) do {} while (0)
#define STAMP2(i) do {} while (0)

__device__ __forceinline__ uint32_t smem_u32(const void* p) { return (uint32_t)__cvta_generic_to_shared(p); }
__device__ __forceinline__ void mbar_expect(uint32_t bar, uint32_t bytes) { asm volatile("mbarrier.arrive.expect_tx.shared::cta.b64 _, [%0], %1;" :: "r"(bar), "r"(bytes) : "memory"); }
__device__ __forceinline__ void mbar_arrive(uint32_t bar) { asm volatile("mbarrier.arrive.shared::cta.b64 _, [%0];" :: "r"(bar) : "memory"); }
__device__ __forceinline__ void mbar_wait(uint32_t bar, uint32_t parity) {
    asm volatile("{.reg .pred p; .reg .u32 n; mov.u32 n, 0x20000;\n"
                 "LW: mbarrier.try_wait.parity.shared::cta.b64 p, [%0], %1;\n"
                 "sub.u32 n, n, 1; setp.eq.or.u32 p, n, 0, p; @!p bra LW;}" :: "r"(bar), "r"(parity) : "memory");
}
__device__ __forceinline__ void mbar_arrive_if(uint32_t bar, uint32_t pred) {
    asm volatile("{.reg .pred p; setp.ne.u32 p, %1, 0; @p mbarrier.arrive.shared::cta.b64 _, [%0];}" :: "r"(bar), "r"(pred) : "memory");
}
__device__ __forceinline__ bool elect_one() { uint32_t p; asm volatile("{.reg .pred P; elect.sync _|P, 0xffffffff; selp.u32 %0, 1, 0, P;}" : "=r"(p)); return p; }
__device__ __forceinline__ void tma2d(uint32_t dst, const CUtensorMap* m, int c0, int c1, uint32_t bar) {
    asm volatile("cp.async.bulk.tensor.2d.shared::cluster.global.mbarrier::complete_tx::bytes [%0], [%1, {%3, %4}], [%2];"
        :: "r"(dst), "l"(m), "r"(bar), "r"(c0), "r"(c1) : "memory");
}
__device__ __forceinline__ void bulk_load(uint32_t dst, const void* src, uint32_t bytes, uint32_t bar) {
    asm volatile("cp.async.bulk.shared::cluster.global.mbarrier::complete_tx::bytes [%0], [%1], %2, [%3];" :: "r"(dst), "l"(src), "r"(bytes), "r"(bar) : "memory");
}
__device__ __forceinline__ void bulk_store(void* dst, uint32_t src, uint32_t bytes) {
    asm volatile("cp.async.bulk.global.shared::cta.bulk_group [%0], [%1], %2;" :: "l"(dst), "r"(src), "r"(bytes) : "memory");
}
__device__ __forceinline__ void fence_async_smem() { asm volatile("fence.proxy.async.shared::cta;" ::: "memory"); }
__device__ __forceinline__ void flag_wait(unsigned* g_flags, int f, unsigned target) {
    asm volatile("{.reg .pred p; .reg .u32 n, v; mov.u32 n, 0x40000;\n"
                 "LF: ld.acquire.gpu.global.u32 v, [%0]; setp.ge.u32 p, v, %1; @p bra LD;\n"
                 "sub.u32 n, n, 1; setp.ne.u32 p, n, 0; @p bra LF; trap;\nLD: }"
                 :: "l"(g_flags + f * 32), "r"(target) : "memory");
}
__device__ __forceinline__ void flag_signal(unsigned* g_flags, int f) {
    asm volatile("cp.async.bulk.commit_group; cp.async.bulk.wait_group 0; red.relaxed.gpu.global.add.u32 [%0], 1;" :: "l"(g_flags + f * 32) : "memory");
}
__device__ __forceinline__ void exit_count(unsigned* g_flags) {
    if (atomicAdd(g_flags + F_EXIT * 32, 1u) == NCTA - 1) {
        #pragma unroll 1
        for (int i = 0; i < F_COUNT; i++) g_flags[i * 32] = 0;
    }
}
__device__ __forceinline__ void bar_sync(int id) { asm volatile("bar.sync %0, 128;" :: "r"(id) : "memory"); }
__device__ __forceinline__ uint64_t mkdesc(uint32_t addr, uint32_t lbo, uint32_t sbo, uint32_t swz) {
    return (uint64_t)((addr >> 4) | ((lbo >> 4) << 16)) | ((uint64_t)((sbo >> 4) | (swz << 30)) << 32);
}
#define WG_FENCE() asm volatile("wgmma.fence.sync.aligned;" ::: "memory")
#define WG_COMMIT() asm volatile("wgmma.commit_group.sync.aligned;" ::: "memory")
#define WG_WAIT(n) asm volatile("wgmma.wait_group.sync.aligned " #n ";" ::: "memory")
template <int N> __device__ __forceinline__ void fence_acc(float (&d)[N]) {
    #pragma unroll
    for (int i = 0; i < N; i++) asm volatile("" : "+f"(d[i]) :: "memory");
}
template <int N> __device__ __forceinline__ void define_acc(float (&d)[N]) {
    #pragma unroll
    for (int i = 0; i < N; i++) asm volatile("" : "=f"(d[i]));
}
__device__ __forceinline__ uint32_t pack2(float lo, float hi) { uint32_t r; asm("cvt.rn.bf16x2.f32 %0, %1, %2;" : "=r"(r) : "f"(hi), "f"(lo)); return r; }
__device__ __forceinline__ float bf_lo(uint32_t v) { return __uint_as_float(v << 16); }
__device__ __forceinline__ float bf_hi(uint32_t v) { return __uint_as_float(v & 0xffff0000u); }
__device__ __forceinline__ float bf_round(float v) { return bf_hi(pack2(0.f, v)); }
__device__ __forceinline__ float tanh_fast(float v) { float r; asm("tanh.approx.f32 %0, %1;" : "=f"(r) : "f"(v)); return r; }
__device__ __forceinline__ float ex2(float v) { float r; asm("ex2.approx.ftz.f32 %0, %1;" : "=f"(r) : "f"(v)); return r; }
__device__ __forceinline__ uint4 lds128(uint32_t a) { uint4 v; asm volatile("ld.shared.v4.b32 {%0,%1,%2,%3}, [%4];" : "=r"(v.x), "=r"(v.y), "=r"(v.z), "=r"(v.w) : "r"(a)); return v; }
__device__ __forceinline__ uint2 lds64(uint32_t a) { uint2 v; asm volatile("ld.shared.v2.b32 {%0,%1}, [%2];" : "=r"(v.x), "=r"(v.y) : "r"(a)); return v; }
__device__ __forceinline__ float ldsf(uint32_t a) { float v; asm volatile("ld.shared.f32 %0, [%1];" : "=f"(v) : "r"(a)); return v; }
__device__ __forceinline__ void sts128(uint32_t a, uint32_t x, uint32_t y, uint32_t z, uint32_t w) { asm volatile("st.shared.v4.b32 [%0], {%1,%2,%3,%4};" :: "r"(a), "r"(x), "r"(y), "r"(z), "r"(w) : "memory"); }
__device__ __forceinline__ void sts64(uint32_t a, uint32_t x, uint32_t y) { asm volatile("st.shared.v2.b32 [%0], {%1,%2};" :: "r"(a), "r"(x), "r"(y) : "memory"); }
__device__ __forceinline__ void stsf(uint32_t a, float x) { asm volatile("st.shared.f32 [%0], %1;" :: "r"(a), "f"(x) : "memory"); }
__device__ __forceinline__ void sts16(uint32_t a, uint32_t x) { asm volatile("st.shared.b16 [%0], %1;" :: "r"(a), "h"((unsigned short)x) : "memory"); }
__device__ __forceinline__ void stsm4(uint32_t a, uint32_t r0, uint32_t r1, uint32_t r2, uint32_t r3) {
    asm volatile("stmatrix.sync.aligned.m8n8.x4.shared.b16 [%0], {%1,%2,%3,%4};" :: "r"(a), "r"(r0), "r"(r1), "r"(r2), "r"(r3) : "memory");
}
__device__ __forceinline__ void ldsm4(uint32_t (&r)[4], uint32_t a) {
    asm volatile("ldmatrix.sync.aligned.m8n8.x4.shared.b16 {%0,%1,%2,%3}, [%4];" : "=r"(r[0]), "=r"(r[1]), "=r"(r[2]), "=r"(r[3]) : "r"(a) : "memory");
}
#define FU(x) __float_as_uint(x)
#define UF(x) __uint_as_float(x)
__device__ __forceinline__ uint32_t wd_slot(int s) { return (uint32_t)((0xbba8403056201000ull >> (8 * s)) & 0xff) << 10; }
__device__ __forceinline__ uint32_t h_slot(int s) { return (uint32_t)((0xcba0908880787068ull >> (8 * s)) & 0xff) << 10; }

template<int N> __device__ __forceinline__ void wg_rs(float (&d)[64], uint32_t a0, uint32_t a1, uint32_t a2, uint32_t a3, uint64_t db);
template<> __device__ __forceinline__ void wg_rs<128>(float (&d)[64], uint32_t a0, uint32_t a1, uint32_t a2, uint32_t a3, uint64_t db) {
  asm volatile("{.reg .pred p; setp.ne.b32 p, 1, 0; wgmma.mma_async.sync.aligned.m64n128k16.f32.bf16.bf16 {%0,%1,%2,%3,%4,%5,%6,%7,%8,%9,%10,%11,%12,%13,%14,%15,%16,%17,%18,%19,%20,%21,%22,%23,%24,%25,%26,%27,%28,%29,%30,%31,%32,%33,%34,%35,%36,%37,%38,%39,%40,%41,%42,%43,%44,%45,%46,%47,%48,%49,%50,%51,%52,%53,%54,%55,%56,%57,%58,%59,%60,%61,%62,%63}, {%64,%65,%66,%67}, %68, p, 1, 1, 0;}"
    : "+f"(d[0]),"+f"(d[1]),"+f"(d[2]),"+f"(d[3]),"+f"(d[4]),"+f"(d[5]),"+f"(d[6]),"+f"(d[7]),"+f"(d[8]),"+f"(d[9]),"+f"(d[10]),"+f"(d[11]),"+f"(d[12]),"+f"(d[13]),"+f"(d[14]),"+f"(d[15]),"+f"(d[16]),"+f"(d[17]),"+f"(d[18]),"+f"(d[19]),"+f"(d[20]),"+f"(d[21]),"+f"(d[22]),"+f"(d[23]),"+f"(d[24]),"+f"(d[25]),"+f"(d[26]),"+f"(d[27]),"+f"(d[28]),"+f"(d[29]),"+f"(d[30]),"+f"(d[31]),"+f"(d[32]),"+f"(d[33]),"+f"(d[34]),"+f"(d[35]),"+f"(d[36]),"+f"(d[37]),"+f"(d[38]),"+f"(d[39]),"+f"(d[40]),"+f"(d[41]),"+f"(d[42]),"+f"(d[43]),"+f"(d[44]),"+f"(d[45]),"+f"(d[46]),"+f"(d[47]),"+f"(d[48]),"+f"(d[49]),"+f"(d[50]),"+f"(d[51]),"+f"(d[52]),"+f"(d[53]),"+f"(d[54]),"+f"(d[55]),"+f"(d[56]),"+f"(d[57]),"+f"(d[58]),"+f"(d[59]),"+f"(d[60]),"+f"(d[61]),"+f"(d[62]),"+f"(d[63]) : "r"(a0), "r"(a1), "r"(a2), "r"(a3), "l"(db));
}
template<> __device__ __forceinline__ void wg_rs<120>(float (&d)[64], uint32_t a0, uint32_t a1, uint32_t a2, uint32_t a3, uint64_t db) {
  asm volatile("{.reg .pred p; setp.ne.b32 p, 1, 0; wgmma.mma_async.sync.aligned.m64n120k16.f32.bf16.bf16 {%0,%1,%2,%3,%4,%5,%6,%7,%8,%9,%10,%11,%12,%13,%14,%15,%16,%17,%18,%19,%20,%21,%22,%23,%24,%25,%26,%27,%28,%29,%30,%31,%32,%33,%34,%35,%36,%37,%38,%39,%40,%41,%42,%43,%44,%45,%46,%47,%48,%49,%50,%51,%52,%53,%54,%55,%56,%57,%58,%59}, {%60,%61,%62,%63}, %64, p, 1, 1, 0;}"
    : "+f"(d[0]),"+f"(d[1]),"+f"(d[2]),"+f"(d[3]),"+f"(d[4]),"+f"(d[5]),"+f"(d[6]),"+f"(d[7]),"+f"(d[8]),"+f"(d[9]),"+f"(d[10]),"+f"(d[11]),"+f"(d[12]),"+f"(d[13]),"+f"(d[14]),"+f"(d[15]),"+f"(d[16]),"+f"(d[17]),"+f"(d[18]),"+f"(d[19]),"+f"(d[20]),"+f"(d[21]),"+f"(d[22]),"+f"(d[23]),"+f"(d[24]),"+f"(d[25]),"+f"(d[26]),"+f"(d[27]),"+f"(d[28]),"+f"(d[29]),"+f"(d[30]),"+f"(d[31]),"+f"(d[32]),"+f"(d[33]),"+f"(d[34]),"+f"(d[35]),"+f"(d[36]),"+f"(d[37]),"+f"(d[38]),"+f"(d[39]),"+f"(d[40]),"+f"(d[41]),"+f"(d[42]),"+f"(d[43]),"+f"(d[44]),"+f"(d[45]),"+f"(d[46]),"+f"(d[47]),"+f"(d[48]),"+f"(d[49]),"+f"(d[50]),"+f"(d[51]),"+f"(d[52]),"+f"(d[53]),"+f"(d[54]),"+f"(d[55]),"+f"(d[56]),"+f"(d[57]),"+f"(d[58]),"+f"(d[59]) : "r"(a0), "r"(a1), "r"(a2), "r"(a3), "l"(db));
}
template<> __device__ __forceinline__ void wg_rs<112>(float (&d)[64], uint32_t a0, uint32_t a1, uint32_t a2, uint32_t a3, uint64_t db) {
  asm volatile("{.reg .pred p; setp.ne.b32 p, 1, 0; wgmma.mma_async.sync.aligned.m64n112k16.f32.bf16.bf16 {%0,%1,%2,%3,%4,%5,%6,%7,%8,%9,%10,%11,%12,%13,%14,%15,%16,%17,%18,%19,%20,%21,%22,%23,%24,%25,%26,%27,%28,%29,%30,%31,%32,%33,%34,%35,%36,%37,%38,%39,%40,%41,%42,%43,%44,%45,%46,%47,%48,%49,%50,%51,%52,%53,%54,%55}, {%56,%57,%58,%59}, %60, p, 1, 1, 0;}"
    : "+f"(d[0]),"+f"(d[1]),"+f"(d[2]),"+f"(d[3]),"+f"(d[4]),"+f"(d[5]),"+f"(d[6]),"+f"(d[7]),"+f"(d[8]),"+f"(d[9]),"+f"(d[10]),"+f"(d[11]),"+f"(d[12]),"+f"(d[13]),"+f"(d[14]),"+f"(d[15]),"+f"(d[16]),"+f"(d[17]),"+f"(d[18]),"+f"(d[19]),"+f"(d[20]),"+f"(d[21]),"+f"(d[22]),"+f"(d[23]),"+f"(d[24]),"+f"(d[25]),"+f"(d[26]),"+f"(d[27]),"+f"(d[28]),"+f"(d[29]),"+f"(d[30]),"+f"(d[31]),"+f"(d[32]),"+f"(d[33]),"+f"(d[34]),"+f"(d[35]),"+f"(d[36]),"+f"(d[37]),"+f"(d[38]),"+f"(d[39]),"+f"(d[40]),"+f"(d[41]),"+f"(d[42]),"+f"(d[43]),"+f"(d[44]),"+f"(d[45]),"+f"(d[46]),"+f"(d[47]),"+f"(d[48]),"+f"(d[49]),"+f"(d[50]),"+f"(d[51]),"+f"(d[52]),"+f"(d[53]),"+f"(d[54]),"+f"(d[55]) : "r"(a0), "r"(a1), "r"(a2), "r"(a3), "l"(db));
}
template<> __device__ __forceinline__ void wg_rs<104>(float (&d)[64], uint32_t a0, uint32_t a1, uint32_t a2, uint32_t a3, uint64_t db) {
  asm volatile("{.reg .pred p; setp.ne.b32 p, 1, 0; wgmma.mma_async.sync.aligned.m64n104k16.f32.bf16.bf16 {%0,%1,%2,%3,%4,%5,%6,%7,%8,%9,%10,%11,%12,%13,%14,%15,%16,%17,%18,%19,%20,%21,%22,%23,%24,%25,%26,%27,%28,%29,%30,%31,%32,%33,%34,%35,%36,%37,%38,%39,%40,%41,%42,%43,%44,%45,%46,%47,%48,%49,%50,%51}, {%52,%53,%54,%55}, %56, p, 1, 1, 0;}"
    : "+f"(d[0]),"+f"(d[1]),"+f"(d[2]),"+f"(d[3]),"+f"(d[4]),"+f"(d[5]),"+f"(d[6]),"+f"(d[7]),"+f"(d[8]),"+f"(d[9]),"+f"(d[10]),"+f"(d[11]),"+f"(d[12]),"+f"(d[13]),"+f"(d[14]),"+f"(d[15]),"+f"(d[16]),"+f"(d[17]),"+f"(d[18]),"+f"(d[19]),"+f"(d[20]),"+f"(d[21]),"+f"(d[22]),"+f"(d[23]),"+f"(d[24]),"+f"(d[25]),"+f"(d[26]),"+f"(d[27]),"+f"(d[28]),"+f"(d[29]),"+f"(d[30]),"+f"(d[31]),"+f"(d[32]),"+f"(d[33]),"+f"(d[34]),"+f"(d[35]),"+f"(d[36]),"+f"(d[37]),"+f"(d[38]),"+f"(d[39]),"+f"(d[40]),"+f"(d[41]),"+f"(d[42]),"+f"(d[43]),"+f"(d[44]),"+f"(d[45]),"+f"(d[46]),"+f"(d[47]),"+f"(d[48]),"+f"(d[49]),"+f"(d[50]),"+f"(d[51]) : "r"(a0), "r"(a1), "r"(a2), "r"(a3), "l"(db));
}
template<> __device__ __forceinline__ void wg_rs<96>(float (&d)[64], uint32_t a0, uint32_t a1, uint32_t a2, uint32_t a3, uint64_t db) {
  asm volatile("{.reg .pred p; setp.ne.b32 p, 1, 0; wgmma.mma_async.sync.aligned.m64n96k16.f32.bf16.bf16 {%0,%1,%2,%3,%4,%5,%6,%7,%8,%9,%10,%11,%12,%13,%14,%15,%16,%17,%18,%19,%20,%21,%22,%23,%24,%25,%26,%27,%28,%29,%30,%31,%32,%33,%34,%35,%36,%37,%38,%39,%40,%41,%42,%43,%44,%45,%46,%47}, {%48,%49,%50,%51}, %52, p, 1, 1, 0;}"
    : "+f"(d[0]),"+f"(d[1]),"+f"(d[2]),"+f"(d[3]),"+f"(d[4]),"+f"(d[5]),"+f"(d[6]),"+f"(d[7]),"+f"(d[8]),"+f"(d[9]),"+f"(d[10]),"+f"(d[11]),"+f"(d[12]),"+f"(d[13]),"+f"(d[14]),"+f"(d[15]),"+f"(d[16]),"+f"(d[17]),"+f"(d[18]),"+f"(d[19]),"+f"(d[20]),"+f"(d[21]),"+f"(d[22]),"+f"(d[23]),"+f"(d[24]),"+f"(d[25]),"+f"(d[26]),"+f"(d[27]),"+f"(d[28]),"+f"(d[29]),"+f"(d[30]),"+f"(d[31]),"+f"(d[32]),"+f"(d[33]),"+f"(d[34]),"+f"(d[35]),"+f"(d[36]),"+f"(d[37]),"+f"(d[38]),"+f"(d[39]),"+f"(d[40]),"+f"(d[41]),"+f"(d[42]),"+f"(d[43]),"+f"(d[44]),"+f"(d[45]),"+f"(d[46]),"+f"(d[47]) : "r"(a0), "r"(a1), "r"(a2), "r"(a3), "l"(db));
}
template<> __device__ __forceinline__ void wg_rs<88>(float (&d)[64], uint32_t a0, uint32_t a1, uint32_t a2, uint32_t a3, uint64_t db) {
  asm volatile("{.reg .pred p; setp.ne.b32 p, 1, 0; wgmma.mma_async.sync.aligned.m64n88k16.f32.bf16.bf16 {%0,%1,%2,%3,%4,%5,%6,%7,%8,%9,%10,%11,%12,%13,%14,%15,%16,%17,%18,%19,%20,%21,%22,%23,%24,%25,%26,%27,%28,%29,%30,%31,%32,%33,%34,%35,%36,%37,%38,%39,%40,%41,%42,%43}, {%44,%45,%46,%47}, %48, p, 1, 1, 0;}"
    : "+f"(d[0]),"+f"(d[1]),"+f"(d[2]),"+f"(d[3]),"+f"(d[4]),"+f"(d[5]),"+f"(d[6]),"+f"(d[7]),"+f"(d[8]),"+f"(d[9]),"+f"(d[10]),"+f"(d[11]),"+f"(d[12]),"+f"(d[13]),"+f"(d[14]),"+f"(d[15]),"+f"(d[16]),"+f"(d[17]),"+f"(d[18]),"+f"(d[19]),"+f"(d[20]),"+f"(d[21]),"+f"(d[22]),"+f"(d[23]),"+f"(d[24]),"+f"(d[25]),"+f"(d[26]),"+f"(d[27]),"+f"(d[28]),"+f"(d[29]),"+f"(d[30]),"+f"(d[31]),"+f"(d[32]),"+f"(d[33]),"+f"(d[34]),"+f"(d[35]),"+f"(d[36]),"+f"(d[37]),"+f"(d[38]),"+f"(d[39]),"+f"(d[40]),"+f"(d[41]),"+f"(d[42]),"+f"(d[43]) : "r"(a0), "r"(a1), "r"(a2), "r"(a3), "l"(db));
}
template<> __device__ __forceinline__ void wg_rs<80>(float (&d)[64], uint32_t a0, uint32_t a1, uint32_t a2, uint32_t a3, uint64_t db) {
  asm volatile("{.reg .pred p; setp.ne.b32 p, 1, 0; wgmma.mma_async.sync.aligned.m64n80k16.f32.bf16.bf16 {%0,%1,%2,%3,%4,%5,%6,%7,%8,%9,%10,%11,%12,%13,%14,%15,%16,%17,%18,%19,%20,%21,%22,%23,%24,%25,%26,%27,%28,%29,%30,%31,%32,%33,%34,%35,%36,%37,%38,%39}, {%40,%41,%42,%43}, %44, p, 1, 1, 0;}"
    : "+f"(d[0]),"+f"(d[1]),"+f"(d[2]),"+f"(d[3]),"+f"(d[4]),"+f"(d[5]),"+f"(d[6]),"+f"(d[7]),"+f"(d[8]),"+f"(d[9]),"+f"(d[10]),"+f"(d[11]),"+f"(d[12]),"+f"(d[13]),"+f"(d[14]),"+f"(d[15]),"+f"(d[16]),"+f"(d[17]),"+f"(d[18]),"+f"(d[19]),"+f"(d[20]),"+f"(d[21]),"+f"(d[22]),"+f"(d[23]),"+f"(d[24]),"+f"(d[25]),"+f"(d[26]),"+f"(d[27]),"+f"(d[28]),"+f"(d[29]),"+f"(d[30]),"+f"(d[31]),"+f"(d[32]),"+f"(d[33]),"+f"(d[34]),"+f"(d[35]),"+f"(d[36]),"+f"(d[37]),"+f"(d[38]),"+f"(d[39]) : "r"(a0), "r"(a1), "r"(a2), "r"(a3), "l"(db));
}
template<> __device__ __forceinline__ void wg_rs<72>(float (&d)[64], uint32_t a0, uint32_t a1, uint32_t a2, uint32_t a3, uint64_t db) {
  asm volatile("{.reg .pred p; setp.ne.b32 p, 1, 0; wgmma.mma_async.sync.aligned.m64n72k16.f32.bf16.bf16 {%0,%1,%2,%3,%4,%5,%6,%7,%8,%9,%10,%11,%12,%13,%14,%15,%16,%17,%18,%19,%20,%21,%22,%23,%24,%25,%26,%27,%28,%29,%30,%31,%32,%33,%34,%35}, {%36,%37,%38,%39}, %40, p, 1, 1, 0;}"
    : "+f"(d[0]),"+f"(d[1]),"+f"(d[2]),"+f"(d[3]),"+f"(d[4]),"+f"(d[5]),"+f"(d[6]),"+f"(d[7]),"+f"(d[8]),"+f"(d[9]),"+f"(d[10]),"+f"(d[11]),"+f"(d[12]),"+f"(d[13]),"+f"(d[14]),"+f"(d[15]),"+f"(d[16]),"+f"(d[17]),"+f"(d[18]),"+f"(d[19]),"+f"(d[20]),"+f"(d[21]),"+f"(d[22]),"+f"(d[23]),"+f"(d[24]),"+f"(d[25]),"+f"(d[26]),"+f"(d[27]),"+f"(d[28]),"+f"(d[29]),"+f"(d[30]),"+f"(d[31]),"+f"(d[32]),"+f"(d[33]),"+f"(d[34]),"+f"(d[35]) : "r"(a0), "r"(a1), "r"(a2), "r"(a3), "l"(db));
}
template<> __device__ __forceinline__ void wg_rs<64>(float (&d)[64], uint32_t a0, uint32_t a1, uint32_t a2, uint32_t a3, uint64_t db) {
  asm volatile("{.reg .pred p; setp.ne.b32 p, 1, 0; wgmma.mma_async.sync.aligned.m64n64k16.f32.bf16.bf16 {%0,%1,%2,%3,%4,%5,%6,%7,%8,%9,%10,%11,%12,%13,%14,%15,%16,%17,%18,%19,%20,%21,%22,%23,%24,%25,%26,%27,%28,%29,%30,%31}, {%32,%33,%34,%35}, %36, p, 1, 1, 0;}"
    : "+f"(d[0]),"+f"(d[1]),"+f"(d[2]),"+f"(d[3]),"+f"(d[4]),"+f"(d[5]),"+f"(d[6]),"+f"(d[7]),"+f"(d[8]),"+f"(d[9]),"+f"(d[10]),"+f"(d[11]),"+f"(d[12]),"+f"(d[13]),"+f"(d[14]),"+f"(d[15]),"+f"(d[16]),"+f"(d[17]),"+f"(d[18]),"+f"(d[19]),"+f"(d[20]),"+f"(d[21]),"+f"(d[22]),"+f"(d[23]),"+f"(d[24]),"+f"(d[25]),"+f"(d[26]),"+f"(d[27]),"+f"(d[28]),"+f"(d[29]),"+f"(d[30]),"+f"(d[31]) : "r"(a0), "r"(a1), "r"(a2), "r"(a3), "l"(db));
}
__device__ __forceinline__ void wg_rs_first(float (&d)[64], uint32_t a0, uint32_t a1, uint32_t a2, uint32_t a3, uint64_t db) {
  asm volatile("{.reg .pred p; setp.ne.b32 p, 0, 0; wgmma.mma_async.sync.aligned.m64n128k16.f32.bf16.bf16 {%0,%1,%2,%3,%4,%5,%6,%7,%8,%9,%10,%11,%12,%13,%14,%15,%16,%17,%18,%19,%20,%21,%22,%23,%24,%25,%26,%27,%28,%29,%30,%31,%32,%33,%34,%35,%36,%37,%38,%39,%40,%41,%42,%43,%44,%45,%46,%47,%48,%49,%50,%51,%52,%53,%54,%55,%56,%57,%58,%59,%60,%61,%62,%63}, {%64,%65,%66,%67}, %68, p, 1, 1, 0;}"
    : "=f"(d[0]),"=f"(d[1]),"=f"(d[2]),"=f"(d[3]),"=f"(d[4]),"=f"(d[5]),"=f"(d[6]),"=f"(d[7]),"=f"(d[8]),"=f"(d[9]),"=f"(d[10]),"=f"(d[11]),"=f"(d[12]),"=f"(d[13]),"=f"(d[14]),"=f"(d[15]),"=f"(d[16]),"=f"(d[17]),"=f"(d[18]),"=f"(d[19]),"=f"(d[20]),"=f"(d[21]),"=f"(d[22]),"=f"(d[23]),"=f"(d[24]),"=f"(d[25]),"=f"(d[26]),"=f"(d[27]),"=f"(d[28]),"=f"(d[29]),"=f"(d[30]),"=f"(d[31]),"=f"(d[32]),"=f"(d[33]),"=f"(d[34]),"=f"(d[35]),"=f"(d[36]),"=f"(d[37]),"=f"(d[38]),"=f"(d[39]),"=f"(d[40]),"=f"(d[41]),"=f"(d[42]),"=f"(d[43]),"=f"(d[44]),"=f"(d[45]),"=f"(d[46]),"=f"(d[47]),"=f"(d[48]),"=f"(d[49]),"=f"(d[50]),"=f"(d[51]),"=f"(d[52]),"=f"(d[53]),"=f"(d[54]),"=f"(d[55]),"=f"(d[56]),"=f"(d[57]),"=f"(d[58]),"=f"(d[59]),"=f"(d[60]),"=f"(d[61]),"=f"(d[62]),"=f"(d[63]) : "r"(a0), "r"(a1), "r"(a2), "r"(a3), "l"(db));
}
__device__ __forceinline__ void wg_tt128(float (&d)[64], uint64_t da, uint64_t db, int sc) {
  asm volatile("{.reg .pred p; setp.ne.b32 p, %66, 0; wgmma.mma_async.sync.aligned.m64n128k16.f32.bf16.bf16 {%0,%1,%2,%3,%4,%5,%6,%7,%8,%9,%10,%11,%12,%13,%14,%15,%16,%17,%18,%19,%20,%21,%22,%23,%24,%25,%26,%27,%28,%29,%30,%31,%32,%33,%34,%35,%36,%37,%38,%39,%40,%41,%42,%43,%44,%45,%46,%47,%48,%49,%50,%51,%52,%53,%54,%55,%56,%57,%58,%59,%60,%61,%62,%63}, %64, %65, p, 1, 1, 1, 1;}"
    : "+f"(d[0]),"+f"(d[1]),"+f"(d[2]),"+f"(d[3]),"+f"(d[4]),"+f"(d[5]),"+f"(d[6]),"+f"(d[7]),"+f"(d[8]),"+f"(d[9]),"+f"(d[10]),"+f"(d[11]),"+f"(d[12]),"+f"(d[13]),"+f"(d[14]),"+f"(d[15]),"+f"(d[16]),"+f"(d[17]),"+f"(d[18]),"+f"(d[19]),"+f"(d[20]),"+f"(d[21]),"+f"(d[22]),"+f"(d[23]),"+f"(d[24]),"+f"(d[25]),"+f"(d[26]),"+f"(d[27]),"+f"(d[28]),"+f"(d[29]),"+f"(d[30]),"+f"(d[31]),"+f"(d[32]),"+f"(d[33]),"+f"(d[34]),"+f"(d[35]),"+f"(d[36]),"+f"(d[37]),"+f"(d[38]),"+f"(d[39]),"+f"(d[40]),"+f"(d[41]),"+f"(d[42]),"+f"(d[43]),"+f"(d[44]),"+f"(d[45]),"+f"(d[46]),"+f"(d[47]),"+f"(d[48]),"+f"(d[49]),"+f"(d[50]),"+f"(d[51]),"+f"(d[52]),"+f"(d[53]),"+f"(d[54]),"+f"(d[55]),"+f"(d[56]),"+f"(d[57]),"+f"(d[58]),"+f"(d[59]),"+f"(d[60]),"+f"(d[61]),"+f"(d[62]),"+f"(d[63]) : "l"(da), "l"(db), "r"(sc));
}
__device__ __forceinline__ void wg_tt64(float (&d)[64], uint64_t da, uint64_t db, int sc) {
  asm volatile("{.reg .pred p; setp.ne.b32 p, %34, 0; wgmma.mma_async.sync.aligned.m64n64k16.f32.bf16.bf16 {%0,%1,%2,%3,%4,%5,%6,%7,%8,%9,%10,%11,%12,%13,%14,%15,%16,%17,%18,%19,%20,%21,%22,%23,%24,%25,%26,%27,%28,%29,%30,%31}, %32, %33, p, 1, 1, 1, 1;}"
    : "+f"(d[0]),"+f"(d[1]),"+f"(d[2]),"+f"(d[3]),"+f"(d[4]),"+f"(d[5]),"+f"(d[6]),"+f"(d[7]),"+f"(d[8]),"+f"(d[9]),"+f"(d[10]),"+f"(d[11]),"+f"(d[12]),"+f"(d[13]),"+f"(d[14]),"+f"(d[15]),"+f"(d[16]),"+f"(d[17]),"+f"(d[18]),"+f"(d[19]),"+f"(d[20]),"+f"(d[21]),"+f"(d[22]),"+f"(d[23]),"+f"(d[24]),"+f"(d[25]),"+f"(d[26]),"+f"(d[27]),"+f"(d[28]),"+f"(d[29]),"+f"(d[30]),"+f"(d[31]) : "l"(da), "l"(db), "r"(sc));
}
__device__ __forceinline__ void wg_tt32(float (&d)[64], uint64_t da, uint64_t db, int sc) {
  asm volatile("{.reg .pred p; setp.ne.b32 p, %18, 0; wgmma.mma_async.sync.aligned.m64n32k16.f32.bf16.bf16 {%0,%1,%2,%3,%4,%5,%6,%7,%8,%9,%10,%11,%12,%13,%14,%15}, %16, %17, p, 1, 1, 1, 1;}"
    : "+f"(d[0]),"+f"(d[1]),"+f"(d[2]),"+f"(d[3]),"+f"(d[4]),"+f"(d[5]),"+f"(d[6]),"+f"(d[7]),"+f"(d[8]),"+f"(d[9]),"+f"(d[10]),"+f"(d[11]),"+f"(d[12]),"+f"(d[13]),"+f"(d[14]),"+f"(d[15]) : "l"(da), "l"(db), "r"(sc));
}
__device__ __forceinline__ void wg_g1(float (&d)[88], uint64_t da, uint64_t db, int sc) {
  asm volatile("{.reg .pred p; setp.ne.b32 p, %90, 0; wgmma.mma_async.sync.aligned.m64n176k16.f32.bf16.bf16 {%0,%1,%2,%3,%4,%5,%6,%7,%8,%9,%10,%11,%12,%13,%14,%15,%16,%17,%18,%19,%20,%21,%22,%23,%24,%25,%26,%27,%28,%29,%30,%31,%32,%33,%34,%35,%36,%37,%38,%39,%40,%41,%42,%43,%44,%45,%46,%47,%48,%49,%50,%51,%52,%53,%54,%55,%56,%57,%58,%59,%60,%61,%62,%63,%64,%65,%66,%67,%68,%69,%70,%71,%72,%73,%74,%75,%76,%77,%78,%79,%80,%81,%82,%83,%84,%85,%86,%87}, %88, %89, p, 1, 1, 1, 0;}"
    : "+f"(d[0]),"+f"(d[1]),"+f"(d[2]),"+f"(d[3]),"+f"(d[4]),"+f"(d[5]),"+f"(d[6]),"+f"(d[7]),"+f"(d[8]),"+f"(d[9]),"+f"(d[10]),"+f"(d[11]),"+f"(d[12]),"+f"(d[13]),"+f"(d[14]),"+f"(d[15]),"+f"(d[16]),"+f"(d[17]),"+f"(d[18]),"+f"(d[19]),"+f"(d[20]),"+f"(d[21]),"+f"(d[22]),"+f"(d[23]),"+f"(d[24]),"+f"(d[25]),"+f"(d[26]),"+f"(d[27]),"+f"(d[28]),"+f"(d[29]),"+f"(d[30]),"+f"(d[31]),"+f"(d[32]),"+f"(d[33]),"+f"(d[34]),"+f"(d[35]),"+f"(d[36]),"+f"(d[37]),"+f"(d[38]),"+f"(d[39]),"+f"(d[40]),"+f"(d[41]),"+f"(d[42]),"+f"(d[43]),"+f"(d[44]),"+f"(d[45]),"+f"(d[46]),"+f"(d[47]),"+f"(d[48]),"+f"(d[49]),"+f"(d[50]),"+f"(d[51]),"+f"(d[52]),"+f"(d[53]),"+f"(d[54]),"+f"(d[55]),"+f"(d[56]),"+f"(d[57]),"+f"(d[58]),"+f"(d[59]),"+f"(d[60]),"+f"(d[61]),"+f"(d[62]),"+f"(d[63]),"+f"(d[64]),"+f"(d[65]),"+f"(d[66]),"+f"(d[67]),"+f"(d[68]),"+f"(d[69]),"+f"(d[70]),"+f"(d[71]),"+f"(d[72]),"+f"(d[73]),"+f"(d[74]),"+f"(d[75]),"+f"(d[76]),"+f"(d[77]),"+f"(d[78]),"+f"(d[79]),"+f"(d[80]),"+f"(d[81]),"+f"(d[82]),"+f"(d[83]),"+f"(d[84]),"+f"(d[85]),"+f"(d[86]),"+f"(d[87]) : "l"(da), "l"(db), "r"(sc));
}

struct Params { const __nv_bfloat16 *x, *logA, *Aim, *Cr, *Ci, *logdt, *Dskip, *Wg, *Wu, *Wd; __nv_bfloat16* out; uint4* xnT; float2* st; uint2* S; unsigned* flags; };
struct Maps { CUtensorMap x[2], xo, wg, wu, wd, hst[2], hld, sld; };

__device__ __forceinline__ void conv_channel(uint32_t cb, int w, int lane, uint32_t (&res)[8], uint32_t sig, int sidx) {
    const int q = lane & 3, g = lane >> 2, gam = g >> 2;
    float acc[64];
    uint2 a[17][2];
    const uint32_t t0 = cb + CH_T + (uint32_t)(14 + 4 * w + (g & 3) - 2 * q) * 280u + gam * 8;
#define LDA(s0, s1) _Pragma("unroll") for (int s = s0; s < s1; s++) { a[s][0] = lds64(t0 + s * 16); a[s][1] = lds64(t0 - 8 * 280 + s * 16); }
#define CT(N, s) wg_rs<N>(acc, a[s][0].x, a[s][0].y, a[s][1].x, a[s][1].y, dU + 4 * (s))
    const uint64_t dU = mkdesc(cb + CH_U, UPLANE, 128, 0);
    LDA(0, 17)
    if (sig) { fence_async_smem(); mbar_arrive(sig); }
    WG_FENCE();
    if (w == 0) STAMP2(52 + 3 * sidx);
    wg_rs_first(acc, a[0][0].x, a[0][0].y, a[0][1].x, a[0][1].y, dU);
    CT(128, 1); CT(120, 2); CT(120, 3); CT(112, 4); CT(112, 5); CT(104, 6); CT(104, 7); CT(96, 8);
    CT(96, 9); CT(88, 10); CT(88, 11); CT(80, 12); CT(80, 13); CT(72, 14); CT(72, 15); CT(64, 16);
#undef CT
#undef LDA
    wg_tt64(acc, mkdesc(cb + CH_A3, 128, 512, 0), mkdesc(cb + CH_B3, 384, 32, 0), 1);
    wg_tt32(acc, mkdesc(cb + CH_A3 + 256, 128, 512, 0), mkdesc(cb + CH_B3 + 128, 384, 32, 0), 1);
    WG_COMMIT();
    if (w == 0) STAMP2(53 + 3 * sidx);
    WG_WAIT(0);
    fence_acc(acc);
    if (w == 0) STAMP2(54 + 3 * sidx);
    const int src1 = (lane & ~3) | ((q + 1) & 3);
    float E[16][2];
    #pragma unroll
    for (int j = 0; j < 16; j++) {
        const float nxt = (j < 15) ? acc[4 * (j + 1) + 2] : 0.f;
        const float sup = (q == 0) ? nxt : acc[4 * j + 2];
        const float v = __shfl_sync(0xffffffffu, sup, src1);
        E[j][0] = acc[4 * j] + acc[4 * j + 3];
        E[j][1] = acc[4 * j + 1] + v;
    }
    const int src2 = gam ? ((lane & 12) | ((q + 3) & 3)) : (16 | (lane & 12) | ((q + 1) & 3));
    const bool c1 = gam && q != 0, c2 = gam && q == 0;
    #pragma unroll
    for (int a2 = 0; a2 < 8; a2++) {
        float y[2];
        #pragma unroll
        for (int e = 0; e < 2; e++) {
            const float sup = c1 ? E[2 * a2][e] : E[2 * a2 + 1][e];
            const float nxt = (a2 < 7) ? E[2 * a2 + 2][e] : 0.f;
            const float keep = c2 ? nxt : (c1 ? E[2 * a2 + 1][e] : E[2 * a2][e]);
            y[e] = keep + __shfl_sync(0xffffffffu, sup, src2);
        }
        res[a2] = pack2(y[1], y[0]);
    }
}

__device__ __forceinline__ void consumer(uint32_t sb, int warp, const Params& P, const Maps& M) {
    const int V = warp >> 2, w = warp & 3, lane = threadIdx.x & 31, q = lane & 3, g = lane >> 2;
    const int c = blockIdx.x;
    const uint32_t bars = sb + OFF_BAR, xb = sb + OFF_X + V * 2 * XBUF;
    {
        float ag[88], au[88];
        define_acc(ag); define_acc(au);
        mbar_wait(bars + 8 * B_FULLW, 0);
        mbar_wait(bars + 8 * (B_FULLX + 2 * V), 0);
        #pragma unroll 1
        for (int st = 0; st < 8; st++) {
            uint64_t dG = mkdesc(sb + OFF_W + (st & 3) * 16384, 0, 1024, 1), dX = mkdesc(xb + (st & 1) * XBUF, 16, 1024, 1);
            uint32_t sig = lane == 0 && (V ? st < 6 : st > 0);
            asm volatile("" : "+l"(dG), "+l"(dX), "+r"(sig) :: "memory");
            if (V ? st < 7 : st > 1) mbar_wait(bars + 8 * (B_TURN + V), st & 1);
            STAMP(40 + 8 * V + st); if (st == 0 && V == 0) GSTAMP(33);
            WG_FENCE();
            #pragma unroll
            for (int k = 0; k < 4; k++) {
                if (k == SIGK) mbar_arrive_if(bars + 8 * (B_TURN + 1 - V), sig);
                wg_g1(ag, dG + k * 128, dX + k * 2, k ? 1 : st);
                wg_g1(au, dG + 512 + k * 128, dX + k * 2, k ? 1 : st);
            }
            WG_COMMIT();
            if (st == 6 * V) {
                mbar_wait(bars + 8 * (B_FULLW + ((st + 1) & 3)), V);
                mbar_wait(bars + 8 * (B_FULLX + 2 * V + 1), V);
            } else {
                WG_WAIT(1);
                mbar_arrive_if(bars + 8 * (B_EMPTYW + 2 * V), lane == 0 && st == 6 * V + 1);
                mbar_arrive_if(bars + 8 * (B_EMPTYX + 2 * V), lane == 0 && st == 6 * V + 1);
                WG_WAIT(0);
                mbar_arrive_if(bars + 8 * (B_EMPTYW + (st & 3)), lane == 0);
                mbar_arrive_if(bars + 8 * (B_EMPTYX + 2 * V + (st & 1)), lane == 0);
                if (st < 7) {
                    mbar_wait(bars + 8 * (B_FULLW + ((st + 1) & 3)), (st + 1) >> 2);
                    mbar_wait(bars + 8 * (B_FULLX + 2 * V + ((st + 1) & 1)), ((st + 1) >> 1) & 1);
                }
            }
        }
        WG_WAIT(0);
        fence_acc(ag); fence_acc(au);
        STAMP(8 * V + 1); GSTAMP(29 + V);
        float cg0 = ag[84], cg1 = ag[86], cu0 = au[84], cu1 = au[86];
        const uint32_t ca = sb + OFF_CSUM + (8 * w + g) * 16;
        if (V == 0) { sts128(ca, FU(cg0), FU(cg1), FU(cu0), FU(cu1)); mbar_arrive(bars + 8 * B_CS); }
        else { mbar_wait(bars + 8 * B_CS, 0); const uint4 t = lds128(ca); cg0 = UF(t.x); cg1 = UF(t.y); cu0 = UF(t.z); cu1 = UF(t.w); }
        mbar_wait(bars + 8 * B_STATS, 0);
        mbar_wait(bars + 8 * (B_EMPTYX + 2 * V), 1);
        STAMP(13 + V);
        const uint32_t hs = xb + (2 * w + ((lane >> 3) & 1)) * (2688 + 128 * V) + (lane >> 4) * 128 + (lane & 7) * 16;
        const uint32_t sa = sb + OFF_ST + (168 * V + 2 * q) * 8;
        uint4 sq[22];
        #pragma unroll
        for (int j = 0; j < 3; j++) sq[j] = lds128(sa + j * 64);
        #pragma unroll
        for (int j = 0; j < 22; j += 2) {
            uint32_t o[4];
            #pragma unroll
            for (int jj = 0; jj < 2; jj++) {
                const uint4 sv = sq[j + jj];
                float hv[4];
                #pragma unroll
                for (int i = 0; i < 4; i++) {
                    const float m = UF((i & 1) ? sv.z : sv.x);
                    const float gh = fmaf(-m, (i & 2) ? cg1 : cg0, ag[4 * (j + jj) + i]) * UF((i & 1) ? sv.w : sv.y);
                    const float p = gh * fmaf(-m, (i & 2) ? cu1 : cu0, au[4 * (j + jj) + i]);
                    hv[i] = fmaf(p, tanh_fast(gh), p);
                }
                o[2 * jj] = pack2(hv[0], hv[1]); o[2 * jj + 1] = pack2(hv[2], hv[3]);
            }
            #pragma unroll
            for (int k = (j ? 3 + 3 * j / 2 : 3); k < 6 + 3 * j / 2 && k < 22; k++) sq[k] = lds128(sa + k * 64);
            uint32_t ad = hs + j * 128;
            if (j == 20 && V == 0 && lane >= 16) ad = xb + 21504 + (lane & 7) * 16;
            stsm4(ad, o[0], o[1], o[2], o[3]);
        }
        if (c >= 128 || V) { fence_async_smem(); mbar_arrive(bars + 8 * (B_EPI + V)); }
        STAMP(8 * V + 2);
    }
    if (c >= 128) return;
    {
        mbar_wait(bars + 8 * B_CONV, 0);
        uint32_t r0[8], r1[8];
        #pragma unroll
        for (int i = 0; i < 8; i++) asm volatile("" : "=r"(r1[i]));
        #pragma unroll 1
        for (int e = 0; e < 2; e++) {
            #pragma unroll
            for (int i = 0; i < 8; i++) r0[i] = r1[i];
            conv_channel(sb + OFF_CONV + (2 * V + e) * CH_STRIDE, w, lane, r1, (e | V) ? 0 : bars + 8 * B_EPI, 2 * V + e);
            if (e == 0) STAMP(8 * V + 3);
        }
        const int gam = g >> 2, qq = gam ? ((q + 3) & 3) : q;
        const uint32_t sp = sb + OFF_CONV + V * OFF_SST + ((63 - 4 * gam - qq) * 16 + 4 * (w ^ (3 - qq)) + (g & 3)) * 8;
        bar_sync(3 + V);
        #pragma unroll
        for (int a2 = 0; a2 < 8; a2++) sts64(sp - a2 * 1024, r0[a2], r1[a2]);
        fence_async_smem();
        mbar_arrive(bars + 8 * (B_SIG + V));
        STAMP(8 * V + 4); GSTAMP(35 + V);
    }
    if (V == 1) return;
    {
        const int tau = c >> 2, dg = c & 3;
        const uint32_t row = 8 * (w & 1) + 32 * (w >> 1);
        float acc[64];
        define_acc(acc);
        const float rr0 = __ldcg(&P.st[64 * tau + row + g].y), rr1 = __ldcg(&P.st[64 * tau + row + g + 16].y);
        mbar_wait(bars + 8 * B_FULLD, 0);
        STAMP(5); GSTAMP(27);
        uint64_t dB = mkdesc(sb + wd_slot(0), 8192, 1024, 1), dA = mkdesc(sb + h_slot(0), 1024, 128, 0);
        int sd = 0; uint32_t np = 0;
        #pragma unroll 1
        for (int st = 0; st < 21; st++) {
            WG_FENCE();
            wg_tt128(acc, dA, dB, st);
            wg_tt128(acc, dA + 128, dB + 128, 1);
            wg_tt128(acc, dA + 256, dB + 256, 1);
            wg_tt128(acc, dA + 384, dB + 384, 1);
            WG_COMMIT();
            uint32_t ro = bars + 8 * (B_EMPTYD + (sd ? sd - 1 : 6)), m = lane == 0 && st > 0, ok;
            if (++sd == 7) { sd = 0; np ^= 1; }
            const uint32_t nb = bars + 8 * (B_FULLD + sd);
            dB = mkdesc(sb + wd_slot(sd), 8192, 1024, 1); dA = mkdesc(sb + h_slot(sd), 1024, 128, 0);
            asm volatile("{.reg .pred p; mbarrier.test_wait.parity.shared::cta.b64 p, [%5], %6; vote.sync.all.pred p, p, -1; selp.u32 %0, 1, 0, p;}"
                : "=r"(ok), "+l"(dA), "+l"(dB), "+r"(ro), "+r"(m) : "r"(nb), "r"(np) : "memory");
            WG_WAIT(1);
            mbar_arrive_if(ro, m);
            if (!ok) mbar_wait(nb, np);
            if (w == 0) STAMP2(20 + st);
        }
        WG_FENCE();
        wg_tt128(acc, dA, dB, 1);
        wg_tt128(acc, dA + 128, dB + 128, 1);
        WG_COMMIT();
        mbar_wait(bars + 8 * B_XO, 0);
        const uint32_t xo = sb + OFF_XO + (row + (lane & 7) + 16 * ((lane >> 3) & 1)) * 128;
        const uint32_t so = sb + OFF_SI + (w >> 1) * 8192 + q * 256 + (g & 1) * 8;
        const uint32_t sx = (4 * (w & 1) + (g >> 1)) ^ (2 * q) ^ (2 * ((2 * tau + (w >> 1)) & 3));
        uint32_t xr[8][4];
        uint2 sv[16];
        #pragma unroll
        for (int j = 0; j < 16; j += 2) {
            ldsm4(xr[j >> 1], xo + (j >> 3) * 8192 + ((((j & 7) + (lane >> 4)) ^ (lane & 7)) << 4));
            sv[j] = lds64(so + j * 512 + (sx << 4));
            sv[j + 1] = lds64(so + j * 512 + 128 + ((sx ^ 1) << 4));
        }
        WG_WAIT(0);
        fence_acc(acc);
        STAMP(6); GSTAMP(28);
        #pragma unroll
        for (int j = 0; j < 16; j += 2) {
            #pragma unroll
            for (int i = 0; i < 4; i++) {
                const int jj = j + (i >> 1), hh = i & 1;
                const float f0 = acc[4 * jj + 2 * hh] * (hh ? rr1 : rr0), f1 = acc[4 * jj + 2 * hh + 1] * (hh ? rr1 : rr0);
                const uint32_t G = pack2(fmaf(f0, tanh_fast(f0), f0), fmaf(f1, tanh_fast(f1), f1));
                const uint32_t s2 = __byte_perm(sv[jj].x, sv[jj].y, hh ? 0x7632 : 0x5410);
                asm("fma.rn.bf16x2 %0, %1, %2, %0;" : "+r"(xr[j >> 1][i]) : "r"(s2), "r"(G));
            }
            stsm4(xo + (j >> 3) * 8192 + ((((j & 7) + (lane >> 4)) ^ (lane & 7)) << 4), xr[j >> 1][0], xr[j >> 1][1], xr[j >> 1][2], xr[j >> 1][3]);
        }
        __syncwarp();
        {
            const uint32_t rr = row + ((lane >> 4) << 4), la = sb + OFF_XO + rr * 128 + ((lane >> 3) & 1) * 8192;
            uint4* dst = (uint4*)(P.out + (64 * tau + rr) * DM + 128 * dg) + (lane & 15);
            uint4 v[8];
            #pragma unroll
            for (int i = 0; i < 8; i++) v[i] = lds128(la + i * 128 + (((lane & 7) ^ i) << 4));
            #pragma unroll
            for (int i = 0; i < 8; i++) dst[i * 64] = v[i];
        }
        STAMP(7); GSTAMP(23);
    }
}

__device__ __forceinline__ float2 cexp_p(float re2, float im, float p) {
    float sn, cs;
    const float mag = ex2(re2 * p), th = im * p;
    asm("sin.approx.ftz.f32 %0, %1;" : "=f"(sn) : "f"(th));
    asm("cos.approx.ftz.f32 %0, %1;" : "=f"(cs) : "f"(th));
    return make_float2(mag * cs, mag * sn);
}
struct SsmRaw { unsigned short la, ai, cr, ci, ldt, dsk; };
__device__ __forceinline__ unsigned short ldu16(const void* p) { unsigned short v; asm volatile("ld.global.nc.u16 %0, [%1];" : "=h"(v) : "l"(p)); return v; }
__device__ __forceinline__ float2 cmul(float2 a, float2 b) { return make_float2(fmaf(a.x, b.x, -a.y * b.y), fmaf(a.x, b.y, a.y * b.x)); }
__device__ __forceinline__ float2 csqr(float2 a) { const float t = a.x * a.y; return make_float2(fmaf(a.x, a.x, -a.y * a.y), t + t); }
__device__ __forceinline__ void mma16816(float (&d)[4], const uint32_t (&a)[4], uint32_t b0, uint32_t b1) {
    asm volatile("mma.sync.aligned.m16n8k16.row.col.f32.bf16.bf16.f32 {%0,%1,%2,%3}, {%4,%5,%6,%7}, {%8,%9}, {%0,%1,%2,%3};"
        : "+f"(d[0]), "+f"(d[1]), "+f"(d[2]), "+f"(d[3]) : "r"(a[0]), "r"(a[1]), "r"(a[2]), "r"(a[3]), "r"(b0), "r"(b1));
}

__device__ __forceinline__ void layer_norm(uint32_t sb, uint32_t cb, int w, int lane, const Params& P) {
    const uint32_t bars = sb + OFF_BAR;
    const int c = blockIdx.x;
    mbar_wait(bars + 8 * (B_LNX + w), 0);
    STAMP(34);
    {
        const uint32_t r0 = cb + CH_LN + (w & 1) * 64 + (lane >> 3) * 1040, ra = r0 + (lane & 7) * 16;
        const float pv = bf_lo(FU(ldsf(r0)));
        float s0 = 0.f, s1 = 0.f, a0 = 0.f, a1 = 0.f;
        #pragma unroll 1
        for (int k = 0; k < 1024; k += 512) {
            uint32_t v[16];
            #pragma unroll
            for (int j = 0; j < 4; j++) *(uint4*)&v[4 * j] = lds128(ra + k + 128 * j);
            #pragma unroll
            for (int i = 0; i < 16; i++) { const float t0 = bf_lo(v[i]) - pv, t1 = bf_hi(v[i]) - pv; s0 += t0; s1 += t1; a0 = fmaf(t0, t0, a0); a1 = fmaf(t1, t1, a1); }
        }
        s0 += s1; a0 += a1;
        #pragma unroll
        for (int o = 4; o; o >>= 1) { s0 += __shfl_xor_sync(0xffffffffu, s0, o); a0 += __shfl_xor_sync(0xffffffffu, a0, o); }
        s0 *= 1.f / DM;
        float sd, ri;
        asm("sqrt.approx.ftz.f32 %0, %1;" : "=f"(sd) : "f"(bf_round(bf_round(fmaxf(fmaf(-s0, s0, a0 * (1.f / DM)), 0.f)) + 1e-5f)));
        asm("rcp.approx.ftz.f32 %0, %1;" : "=f"(ri) : "f"(bf_round(sd)));
        if ((lane & 7) == 0) {
            const float2 sv = make_float2(bf_round(pv + s0), 0.5f * ri);
            sts64(sb + OFF_CSUM + (w + 4 * (lane >> 3)) * 8, FU(sv.x), FU(sv.y));
            P.st[16 * (c & ~1) + 8 * (c & 1) + 16 + w + ((lane >> 1) & 4) - (lane & 16)] = sv;
        }
    }
    STAMP(62);
    bar_sync(2);
    const int r = 4 * ((lane & 7) >> 1) + (lane & 1) + 2 * ((lane >> 3) & 1);
    const uint32_t ad = sb + OFF_CONV + (r & 3) * CH_STRIDE + CH_LN + (r & 1) * 64 + (r >> 2) * 1040 + (16 * w + (lane >> 4)) * 16;
    const uint4 sa = lds128(sb + OFF_CSUM + (lane & 3) * 32), sc = lds128(sb + OFF_CSUM + (lane & 3) * 32 + 16);
    const uint32_t m2[2] = {__byte_perm(sa.x, sa.z, 0x7632), __byte_perm(sc.x, sc.z, 0x7632)};
    const float ri[4] = {2.f * UF(sa.y), 2.f * UF(sa.w), 2.f * UF(sc.y), 2.f * UF(sc.w)};
    uint2* dst = (uint2*)(P.xnT + (128 * w + (lane >> 2)) * 256 + (c & 1) * 128 + 126 - (c & ~1)) + (lane & 3);
    #pragma unroll 1
    for (int i = 0; i < 8; i += 4) {
        uint32_t v[4][4];
        #pragma unroll
        for (int j = 0; j < 4; j++)
            asm volatile("ldmatrix.sync.aligned.m8n8.x4.trans.shared.b16 {%0,%1,%2,%3}, [%4];" : "=r"(v[j][0]), "=r"(v[j][1]), "=r"(v[j][2]), "=r"(v[j][3]) : "r"(ad + 32 * (i + j)) : "memory");
        #pragma unroll
        for (int j = 0; j < 4; j++) {
            #pragma unroll
            for (int k = 0; k < 4; k++) {
                uint32_t dv; asm("sub.rn.bf16x2 %0, %1, %2;" : "=r"(dv) : "r"(v[j][k]), "r"(m2[k & 1]));
                v[j][k] = pack2(bf_lo(dv) * ri[2 * (k & 1)], bf_hi(dv) * ri[2 * (k & 1) + 1]);
            }
            dst[(i + j) * 16 * 512] = make_uint2(v[j][0], v[j][1]); dst[(i + j) * 16 * 512 + 8 * 512] = make_uint2(v[j][2], v[j][3]);
        }
    }
    mbar_arrive(bars + 8 * B_LN);
    STAMP(16);
}

__device__ __forceinline__ void kernel_gen(uint32_t fs, int lane, const SsmRaw& raw, float (&dacc)[2][3][4], const char* pf) {
    const float dt = bf_round(ex2(bf_lo(raw.ldt) * 1.4426950408889634f));
    const float re2 = bf_round(ex2(bf_lo(raw.la) * 1.4426950408889634f)) * dt * -1.4426950408889634f, im = bf_lo(raw.ai) * dt;
    const float2 C = make_float2(bf_lo(raw.cr) * (dt + dt), bf_lo(raw.ci) * -(dt + dt));
    STAMP(56);
    const float2 y1 = cexp_p(re2, -im, 1.f), y256 = cexp_p(re2, -im, 256.f), z64 = cexp_p(re2, im, 64.f);
    const uint32_t fm = fs + (lane >> 3) * 144 + (lane & 7) * 16;
#define PK(v) pack2((v).x, (v).y)
    const float2 y2 = csqr(y1), y4 = csqr(y2), y8 = csqr(y4);
    const float2 l1 = cmul(C, y1), l2 = cmul(C, y2), l3 = cmul(l1, y2);
    stsm4(fm, PK(C), PK(l1), PK(l2), PK(l3));
    stsm4(fm + 4 * 144, PK(cmul(C, y4)), PK(cmul(l1, y4)), PK(cmul(l2, y4)), PK(cmul(l3, y4)));
    const float2 t0 = cmul(C, y256), t1 = cmul(t0, y256), t2 = cmul(t1, y256), t3_ = cmul(t2, y256);
    const float2 u1 = cmul(t0, y2), u2 = cmul(u1, y2), u3 = cmul(u2, y2);
    stsm4(fm + 8 * 144, PK(t0), PK(u1), PK(u2), PK(u3));
    stsm4(fm + 12 * 144, PK(t1), PK(cmul(t1, y4)), PK(t2), PK(cmul(t2, y4)));
    const float2 v0 = cmul(t3_, y8), v1 = cmul(v0, y256), v2 = cmul(v1, y256), v3 = cmul(v2, y256);
    stsm4(fm + 16 * 144, PK(v0), PK(v1), PK(v2), PK(v3));
    stsf(fs + lane * 4 + 20 * 144, UF(PK(t3_)));
    STAMP(57);
    if (pf) asm volatile("prefetch.global.L2 [%0];" :: "l"(pf));
    const uint32_t ldb = fs + (lane & 7) * 144 + ((lane >> 3) & 1) * 16 + (lane >> 4) * 8 * 144;
    const float p8 = (float)(2 * (lane & 28));
    __syncwarp();
    #pragma unroll KUNR_
    for (int ks = 0; ks < 4; ks++) {
        uint32_t b01[4], b2[2], a0[4], a1[4];
        ldsm4(b01, ldb + ks * 32);
        asm volatile("ldmatrix.sync.aligned.m8n8.x2.shared.b16 {%0,%1}, [%2];" : "=r"(b2[0]), "=r"(b2[1]) : "r"(ldb + 16 * 144 + ks * 32) : "memory");
        #pragma unroll
        for (int mh = 0; mh < 2; mh++) {
            const int src = 8 * ks + 4 * mh + (lane & 3);
            const float2 z = make_float2(__shfl_sync(0xffffffffu, z64.x, src), __shfl_sync(0xffffffffu, z64.y, src));
            const float2 R0 = cexp_p(__shfl_sync(0xffffffffu, re2, src), __shfl_sync(0xffffffffu, im, src), p8);
            const float2 R1 = cmul(R0, z), R2 = cmul(R1, z), R3 = cmul(R2, z);
            a0[2 * mh] = PK(R0); a0[2 * mh + 1] = PK(R1); a1[2 * mh] = PK(R2); a1[2 * mh + 1] = PK(R3);
        }
        mma16816(dacc[0][0], a0, b01[0], b01[1]); mma16816(dacc[1][0], a1, b01[0], b01[1]);
        mma16816(dacc[0][1], a0, b01[2], b01[3]); mma16816(dacc[1][1], a1, b01[2], b01[3]);
        mma16816(dacc[0][2], a0, b2[0], b2[1]);   mma16816(dacc[1][2], a1, b2[0], b2[1]);
    }
#undef PK
    STAMP(58);
}

__device__ __forceinline__ void aux_role(uint32_t sb, int w, float (&dacc)[2][3][4], float dsk, const Params& P) {
    const int lane = threadIdx.x & 31, q = lane & 3, g = lane >> 2;
    const int c = blockIdx.x;
    const uint32_t bars = sb + OFF_BAR;
    if (c >= 128) { mbar_arrive(bars + 8 * B_LN); return; }
    {
        const uint32_t cb = sb + OFF_CONV + w * CH_STRIDE;
        layer_norm(sb, cb, w, lane, P);
        {
            uint4 v[2][3];
            #pragma unroll
            for (int i = 0; i < 3; i++) v[0][i] = lds128(cb + CH_PART + lane * 16 + i * 512);
            #pragma unroll
            for (int k = 0; k < 6; k++) {
                #pragma unroll
                for (int i = 0; i < 3; i++) if (k < 5) v[(k + 1) & 1][i] = lds128(cb + CH_PART + lane * 16 + (k + 1) * 1536 + i * 512);
                #pragma unroll
                for (int i = 0; i < 3; i++) {
                    float* d = &dacc[0][0][0] + 12 * (k & 1) + 4 * i;
                    d[0] += UF(v[k & 1][i].x); d[1] += UF(v[k & 1][i].y); d[2] += UF(v[k & 1][i].z); d[3] += UF(v[k & 1][i].w);
                }
            }
        }
        __syncwarp();
        STAMP(18);
        const uint32_t sF = cb + CH_A3, sG = cb + CH_G;
        if (lane == 0) dacc[0][0][0] += dsk;
        if (lane < 10) sts128(sG + 128 + (lane & 1) * 208 + (lane >> 1) * 16, 0, 0, 0, 0);
        const uint32_t f0 = sF + (8 * g + 2 * q) * 4, f1 = sF + ((q < 2) ? 256 + 4 * g + 2 * q : 256 + 2 * g + 64 * q) * 4, st1 = (q < 2) ? 128 : 64;
        const uint32_t ga = sG + ((g & 1) ? 0 : 208) + (63 - (g >> 1) - 32 * q) * 2;
        #pragma unroll
        for (int i = 0; i < 4; i++) {
            const int mu = i >> 1, hh = i & 1;
            sts64(f0 + i * 256, FU(dacc[mu][0][2 * hh]), FU(dacc[mu][0][2 * hh + 1]));
            sts64(f1 + i * st1, FU(dacc[mu][1][2 * hh]), FU(dacc[mu][1][2 * hh + 1]));
            const uint32_t pk = pack2(dacc[mu][2][2 * hh], dacc[mu][2][2 * hh + 1]);
            if (q < 2) { sts16(ga - 8 * i, pk & 0xffff); sts16(ga - 8 * i - 32, pk >> 16); }
        }
        if (lane == 2) stsf(sF + 2048, dacc[0][2][0]);
        STAMP(19);
        bar_sync(2);
    }
    const int u = min(lane, 30) - 15, r2 = (u + ((u >> 1) & 1)) >> 1, r4 = (u + 1 + ((u >> 2) & 1)) >> 2, xt = 1024 + 16 * w + u;
    const uint32_t o0 = CH_A3 + 4 * (w == 0 ? u : w == 1 ? 256 + r2 : 256 + 64 * w + r4), ost = w == 0 ? 64 : w == 1 ? 32 : 16;
    const uint32_t oa0 = u >= 0 || w == 3 ? o0 : CH_A3 + 4 * (w == 1 ? 256 + u : w == 2 ? 384 + r2 : 0);
    const uint32_t ot = CH_A3 + 4 * min(512, 256 + ((xt + 1 + ((xt >> 2) & 1)) >> 2));
    const int kap = (lane >> 4) * 8 + ((lane >> 1) & 7), gam = lane & 1, hh = w >> 1, wp = w & 1;
    const uint32_t oa = CH_U + wp * UPLANE + (127 - 4 * kap - 2 * gam - hh) * 16;
    const uint32_t ob = CH_U + (wp ^ 1) * UPLANE + (128 - wp - 4 * kap - 2 * gam - hh) * 16;
    const uint32_t od = CH_A3 + (4 * wp + hh) * 512 + (kap >> 3) * 256 + (kap & 7) * 16 + gam * 8;
    const int tid = threadIdx.x & 127;
    const uint32_t og = CH_G + (tid >= 24) * 16 + min(tid, 47) * 8, cend = sb + OFF_CONV + 3 * CH_STRIDE;
    {
        float nx[17]; uint2 n0, n1;
#define LDT(b) nx[0] = ldsf((b) + oa0); nx[16] = ldsf((b) + ot); _Pragma("unroll") for (int s = 1; s < 16; s++) nx[s] = ldsf((b) + o0 + s * ost); n0 = lds64((b) + og); n1 = lds64((b) + og + 8)
        LDT(sb + OFF_CONV);
        #pragma unroll 1
        for (uint32_t cb = sb + OFF_CONV; cb <= cend; cb += CH_STRIDE) {
            float kv[17];
            #pragma unroll
            for (int s = 0; s < 17; s++) kv[s] = nx[s];
            if (tid < 48) sts128(cb + CH_B3 + tid * 16, n0.x, n0.y, n1.x, n1.y);
            LDT(min(cb + CH_STRIDE, cend));
            if (u < 0 && w == 0) kv[0] = 0.f;
            if (xt > 1028) kv[16] = 0.f;
            uint32_t o[17];
            #pragma unroll
            for (int s = 0; s < 17; s++) o[s] = pack2(kv[s], __shfl_up_sync(0xffffffffu, kv[s], 1));
            if (lane > 0 && lane < 31) {
                const uint32_t ta = cb + CH_T + (lane - 1) * 280;
                #pragma unroll
                for (int s2 = 0; s2 < 8; s2++) sts64(ta + 64 * w + s2 * 8, o[2 * s2], o[2 * s2 + 1]);
                stsf(ta + 256 + 4 * w, UF(o[16]));
            }
        }
#undef LDT
    }
    STAMP(61);
    if (lane < 8) sts128(sb + OFF_CONV + w * CH_STRIDE + CH_U + 2048 + (lane & 4) * (UPLANE / 4) + (lane & 3) * 16, 0, 0, 0, 0);
    mbar_wait(bars + 8 * B_U, 0);
    bar_sync(2);
    STAMP(17);
    uint2 n0 = lds64(sb + OFF_CONV + ob + 24), n3 = lds64(sb + OFF_CONV + oa);
    uint4 n1 = lds128(sb + OFF_CONV + oa + 16), n2 = lds128(sb + OFF_CONV + ob);
    #pragma unroll 1
    for (uint32_t cb = sb + OFF_CONV; cb <= cend; cb += CH_STRIDE) {
        const uint32_t r[12] = {n0.x, n0.y, n1.x, n1.y, n1.z, n1.w, n2.x, n2.y, n2.z, n2.w, n3.x, n3.y}, nb = min(cb + CH_STRIDE, cend);
        n0 = lds64(nb + ob + 24); n3 = lds64(nb + oa); n1 = lds128(nb + oa + 16); n2 = lds128(nb + ob);
        float p[24];
        p[0] = 0.f; p[1] = bf_lo(r[0]);
        #pragma unroll
        for (int i = 2; i < 24; i++) p[i] = p[i - 1] + ((i & 1) ? bf_lo(r[i >> 1]) : bf_hi(r[(i - 1) >> 1]));
        #pragma unroll
        for (int i = 0; i < 8; i += 4) {
            sts64(cb + od + i * 256, pack2(p[i + 9] - p[i], p[i + 10] - p[i + 1]), pack2(p[i + 11] - p[i + 2], p[i + 12] - p[i + 3]));
            sts64(cb + od + i * 256 + 128, pack2(p[i + 16] - p[i + 9], p[i + 17] - p[i + 10]), pack2(p[i + 18] - p[i + 11], p[i + 19] - p[i + 12]));
        }
    }
    fence_async_smem();
    mbar_arrive(bars + 8 * B_CONV);
    STAMP(21);
}

__device__ __forceinline__ void store_h(uint32_t sb, const Params& P, const Maps& M, int V, int tg, int fb) {
    const uint32_t bars = sb + OFF_BAR;
    mbar_wait(bars + 8 * (B_EPI + V), 0);
    STAMP2(3 + 2 * V);
    asm volatile("cp.async.bulk.tensor.3d.global.shared::cta.bulk_group [%0, {%2, %3, %4}], [%1];"
        :: "l"(&M.hst[V]), "r"(sb + OFF_X + V * 2 * XBUF), "r"(0), "r"(43 * tg + 21 * V), "r"(8 * fb) : "memory");
    flag_signal(P.flags, F_H + 2 * tg + V);
    mbar_arrive(bars + 8 * (B_STG + V));
    STAMP2(4 + 2 * V);
}

__global__ void __launch_bounds__(512, 1)
fused_kernel(const __grid_constant__ Params P, const __grid_constant__ Maps M) {
    extern __shared__ __align__(1024) uint8_t smem_raw[];
    const uint32_t sb = smem_u32(smem_raw);
    const uint32_t bars = sb + OFF_BAR;
    const int warp = __shfl_sync(0xffffffffu, threadIdx.x >> 5, 0);
    const int c = blockIdx.x, tg = c / 22, fb = c - 22 * tg;
    SsmRaw raw;
    {
        const int d = min(4 * c + (warp & 3), DM - 1), o = d * 128 + (warp >> 2) * 32 + (threadIdx.x & 31);
        raw.la = ldu16(P.logA + o); raw.ai = ldu16(P.Aim + o); raw.cr = ldu16(P.Cr + o); raw.ci = ldu16(P.Ci + o);
        raw.ldt = ldu16(P.logdt + d); raw.dsk = ldu16(P.Dskip + d);
    }
    if (elect_one()) {
        if (warp == 0) { STAMP(24); GSTAMP(22); }
        asm volatile("" :: "l"(((const uint64_t*)&P)[warp < 15 ? warp : 0]));
        if (warp < 10) asm volatile("prefetch.tensormap [%0];" :: "l"(&M.x[0] + warp) : "memory");
        #pragma unroll
        for (int k = 0; k < 4; k++) {
            const int i = 16 * k + ((warp + 4) & 15);
            const uint32_t cnt = i >= B_LNX ? 1 : i >= B_CONV ? 128 : ((0xf0ull >> i) & 1) ? 8 : ((0xff0000ull >> i) & 1) ? 2 : ((0x3e00ff00f000ull >> i) & 1) ? 4 : 1;
            asm volatile("mbarrier.init.shared::cta.b64 [%0], %1;" :: "r"(bars + 8 * i), "r"(cnt) : "memory");
        }
        asm volatile("fence.mbarrier_init.release.cluster; fence.proxy.async.shared::cta;" ::: "memory");
        if (warp == 12 || warp == 13) {
            const uint32_t s = warp - 12;
            mbar_expect(bars + 8 * (B_FULLW + s), 16384);
            tma2d(sb + OFF_W + s * 16384, &M.wg, 64 * fb, 64 * s, bars + 8 * (B_FULLW + s));
            tma2d(sb + OFF_W + s * 16384 + 8192, &M.wu, 64 * fb, 64 * s, bars + 8 * (B_FULLW + s));
            STAMP(31);
        } else if (warp >= 4 && warp < 7) {
            const uint32_t s = warp - 4, V = s >> 1;
            mbar_expect(bars + 8 * (B_FULLX + s), (168 + 8 * V) * 128);
            tma2d(sb + OFF_X + s * XBUF, &M.x[V], 64 * (s & 1), TOKG * tg + 168 * V, bars + 8 * (B_FULLX + s));
        } else if ((warp >> 2) == 2 && c < 128) {
            const int w = warp & 3;
            mbar_expect(bars + 8 * (B_LNX + w), 4096);
            #pragma unroll
            for (int i = 0; i < 4; i++)
                bulk_load(sb + OFF_CONV + w * CH_STRIDE + CH_LN + (w & 1) * 64 + i * 1040,
                          P.x + (16 * (c & ~1) + 8 * (c & 1) + 16 + w + 4 * (i & 1) - 8 * (i & 2)) * DM, 1024, bars + 8 * (B_LNX + w));
        }
        if (sb & 1023) __trap();
    }
    if (warp < 4) sts128(sb + OFF_X + (warp >> 1) * XBUF + 168 * 128 + (threadIdx.x & 63) * 16, 0x3f803f80u, 0x3f803f80u, 0x3f803f80u, 0x3f803f80u);
    float dacc[2][3][4];
    #pragma unroll
    for (int i = 0; i < 24; i++) (&dacc[0][0][0])[i] = 0.f;
    if (c < 128) {
        const int wg = warp >> 2;
        const uint32_t fs = sb + OFF_CONV + (warp & 3) * CH_STRIDE + (wg == 2 ? CH_LNT : CH_PART + min(wg, 2) * CH_PSZ);
        const int ln = threadIdx.x & 63;
        kernel_gen(fs, threadIdx.x & 31, raw, dacc, (wg == 3 && ln < 43) ? (const char*)((warp & 2) ? P.Wu : P.Wg) + 256 * FF * 2 + c * 5504 + ln * 128 : nullptr);
        if (wg != 2) {
            __syncwarp();
            #pragma unroll
            for (int i = 0; i < 6; i++) { const float* d = &dacc[0][0][0] + 4 * i; sts128(fs + (threadIdx.x & 31) * 16 + i * 512, FU(d[0]), FU(d[1]), FU(d[2]), FU(d[3])); }
        }
    }
    if (warp < 4) fence_async_smem();
    __syncthreads();
    if (warp < 8) {
        asm volatile("setmaxnreg.inc.sync.aligned.u32 208;");
        consumer(sb, warp, P, M);
        asm volatile("nanosleep.u32 1;");
    } else if (warp < 12) {
        asm volatile("setmaxnreg.dec.sync.aligned.u32 72;");
        STAMP(32);
        aux_role(sb, warp - 8, dacc, bf_lo(raw.dsk), P);
        asm volatile("nanosleep.u32 2;");
    } else {
        asm volatile("setmaxnreg.dec.sync.aligned.u32 24;");
        const int tau = c >> 2, dg = c & 3;
        if (elect_one()) {
            if (warp < 15) {
                if (warp == 12) {
                    #pragma unroll 1
                    for (int st = 2; st < 8; st++) {
                        const uint32_t s = st & 3, fb_ = bars + 8 * (B_FULLW + s);
                        mbar_wait(bars + 8 * (B_EMPTYW + s), (st >> 2) ^ 1);
                        mbar_expect(fb_, 16384);
                        tma2d(sb + OFF_W + s * 16384, &M.wg, 64 * fb, 64 * st, fb_);
                        tma2d(sb + OFF_W + s * 16384 + 8192, &M.wu, 64 * fb, 64 * st, fb_);
                    }
                } else {
                    const int V = warp - 13;
                    #pragma unroll 1
                    for (int st = 2 - V; st < 8; st++) {
                        const uint32_t s = 2 * V + (st & 1);
                        mbar_wait(bars + 8 * (B_EMPTYX + s), ((st >> 1) & 1) ^ 1);
                        mbar_expect(bars + 8 * (B_FULLX + s), (168 + 8 * V) * 128);
                        tma2d(sb + OFF_X + s * XBUF, &M.x[V], 64 * st, TOKG * tg + 168 * V, bars + 8 * (B_FULLX + s));
                    }
                }
                if (warp == 14) store_h(sb, P, M, 1, tg, fb);
                if (c < 128 && warp < 14) {
                    if (warp == 13) {
                        mbar_wait(bars + 8 * (B_STG + 1), 0);
                        #pragma unroll 1
                        for (int o = 8 * tau; o < 8 * tau + 8; o += 7) flag_wait(P.flags, F_H + 2 * (o / 43) + ((o % 43) >= 21), 22);
                        mbar_arrive(bars + 8 * B_HF);
                        STAMP(25); GSTAMP(37);
                    }
                    #pragma unroll 1
                    for (int st = 0; st < 22; st += (st < 6 || (st == 6 && warp == 13)) ? 1 : 2) {
                        const int rd = (st >= 7) + (st >= 14) + (st >= 21), sd = st - 7 * rd;
                        const uint32_t fb_ = bars + 8 * (B_FULLD + sd);
                        if (rd) mbar_wait(bars + 8 * (B_EMPTYD + sd), (rd & 1) ^ 1);
                        else if (warp == 12 || st == 6) mbar_wait(bars + 8 * (uint32_t)((0x3623070d060504ull >> (8 * st)) & 0xff), st < 5);
                        if (st >= 10 && st < 21) STAMP2(31 + st);
                        if (rd || warp == 13) {
                            mbar_expect(fb_, 8192);
                            asm volatile("cp.async.bulk.tensor.5d.shared::cluster.global.mbarrier::complete_tx::bytes [%0], [%1, {%3, %3, %3, %4, %5}], [%2];"
                                :: "r"(sb + h_slot(sd)), "l"(&M.hld), "r"(fb_), "r"(0), "r"(2 * tau), "r"(8 * st) : "memory");
                        }
                        if (rd || warp == 12) {
                            const uint32_t da = sb + wd_slot(sd);
                            mbar_expect(fb_, 16384);
                            tma2d(da, &M.wd, 128 * dg, 64 * st, fb_);
                            tma2d(da + 8192, &M.wd, 128 * dg + 64, 64 * st, fb_);
                        }
                    }
                } else if (c < 128) {
                    mbar_wait(bars + 8 * (B_SIG + 1), 0);
                    mbar_expect(bars + 8 * B_XO, 32768);
                    tma2d(sb + OFF_XO, &M.xo, 128 * dg, 64 * tau, bars + 8 * B_XO);
                    tma2d(sb + OFF_XO + 8192, &M.xo, 128 * dg + 64, 64 * tau, bars + 8 * B_XO);
                    mbar_wait(bars + 8 * B_SST, 0);
                    flag_wait(P.flags, F_S + dg, 64);
                    STAMP(26);
                    asm volatile("cp.async.bulk.tensor.5d.shared::cluster.global.mbarrier::complete_tx::bytes [%0], [%1, {%3, %3, %3, %4, %5}], [%2];"
                        :: "r"(sb + OFF_SI), "l"(&M.sld), "r"(bars + 8 * B_XO), "r"(0), "r"(8 * dg), "r"(2 * tau) : "memory");
                    mbar_wait(bars + 8 * B_HF, 0);
                    exit_count(P.flags);
                }
            } else {
                mbar_wait(bars + 8 * B_LN, 0);
                STAMP2(0);
                asm volatile("fence.acq_rel.gpu; red.relaxed.gpu.global.add.u32 [%0], 1;" :: "l"(P.flags + F_A * 32) : "memory");
                if (c < 128) asm volatile("cp.async.bulk.prefetch.L2.global [%0], %1;" :: "l"(P.Wd + c * (FF * DM / 128)), "r"(FF * DM / 64) : "memory");
                STAMP2(2);
                flag_wait(P.flags, F_A, NCTA);
                asm volatile("fence.proxy.async.global;" ::: "memory");
                STAMP(20);
                mbar_expect(bars + 8 * B_STATS, TOKG * 8);
                bulk_load(sb + OFF_ST, P.st + TOKG * tg, TOKG * 8, bars + 8 * B_STATS);
                if (c < 128) {
                    mbar_expect(bars + 8 * B_U, 8 * 2048);
                    #pragma unroll 1
                    for (int i = 0; i < 8; i++)
                        bulk_load(sb + OFF_CONV + (i >> 1) * CH_STRIDE + CH_U + (i & 1) * UPLANE, P.xnT + 4 * c * 256 + i * 128, 2048, bars + 8 * B_U);
                } else exit_count(P.flags);
                store_h(sb, P, M, 0, tg, fb);
                if (c < 128) {
                    #pragma unroll 1
                    for (int V = 0; V < 2; V++) {
                        mbar_wait(bars + 8 * (B_SIG + V), 0);
                        STAMP2(7 + 2 * V);
                        bulk_store(P.S + (2 * c + V) * 1024, sb + OFF_CONV + V * OFF_SST, 8192);
                        flag_signal(P.flags, F_S + (c >> 5));
                        STAMP2(8 + 2 * V);
                    }
                    mbar_arrive(bars + 8 * B_SST);
                }
            }
            asm volatile("nanosleep.u32 0;");
        }
    }
}

typedef CUresult (*EncodeFn)(CUtensorMap*, CUtensorMapDataType, cuuint32_t, void*, const cuuint64_t*, const cuuint64_t*, const cuuint32_t*,
                             const cuuint32_t*, CUtensorMapInterleave, CUtensorMapSwizzle, CUtensorMapL2promotion, CUtensorMapFloatOOBfill);

void make_map(EncodeFn enc, CUtensorMap* m, const void* ptr, int rank, const cuuint64_t* dims, const cuuint64_t* strides, const cuuint32_t* box, bool swz, bool wide = false) {
    const cuuint32_t es[5] = {1, 1, 1, 1, 1};
    enc(m, CU_TENSOR_MAP_DATA_TYPE_BFLOAT16, rank, (void*)ptr, dims, strides, box, es, CU_TENSOR_MAP_INTERLEAVE_NONE,
        swz ? CU_TENSOR_MAP_SWIZZLE_128B : CU_TENSOR_MAP_SWIZZLE_NONE, wide ? CU_TENSOR_MAP_L2_PROMOTION_L2_256B : CU_TENSOR_MAP_L2_PROMOTION_L2_128B, CU_TENSOR_MAP_FLOAT_OOB_FILL_NONE);
}
void make_map2(EncodeFn enc, CUtensorMap* m, const void* ptr, cuuint64_t inner, cuuint64_t outer, cuuint32_t rows) {
    const cuuint64_t dims[2] = {inner, outer}, strides[1] = {inner * 2};
    const cuuint32_t box[2] = {64, rows};
    make_map(enc, m, ptr, 2, dims, strides, box, true, rows > 64);
}

}

extern "C" void kernel_launch(void* const* d_in, const int* in_sizes, int n_in, void* d_out, int out_size) {
    (void)in_sizes; (void)n_in; (void)out_size;
    static EncodeFn enc = nullptr;
    static void *hptr, *p_xnT, *p_st, *p_S, *p_flags;
    if (!enc) {
        cudaDriverEntryPointQueryResult qr;
        cudaGetDriverEntryPoint("cuTensorMapEncodeTiled", (void**)&enc, cudaEnableDefault, &qr);
        cudaFuncSetAttribute(fused_kernel, cudaFuncAttributeMaxDynamicSharedMemorySize, SMEM_BYTES);
        cudaGetSymbolAddress(&hptr, g_H); cudaGetSymbolAddress(&p_xnT, g_xnT); cudaGetSymbolAddress(&p_st, g_st);
        cudaGetSymbolAddress(&p_S, g_S); cudaGetSymbolAddress(&p_flags, g_flags);
    }
    Params P;
    P.x = (const __nv_bfloat16*)d_in[0]; P.logA = (const __nv_bfloat16*)d_in[1]; P.Aim = (const __nv_bfloat16*)d_in[2];
    P.Cr = (const __nv_bfloat16*)d_in[3]; P.Ci = (const __nv_bfloat16*)d_in[4]; P.logdt = (const __nv_bfloat16*)d_in[5];
    P.Dskip = (const __nv_bfloat16*)d_in[6];
    P.Wg = (const __nv_bfloat16*)d_in[8]; P.Wu = (const __nv_bfloat16*)d_in[9]; P.Wd = (const __nv_bfloat16*)d_in[10]; P.out = (__nv_bfloat16*)d_out; P.xnT = (uint4*)p_xnT; P.st = (float2*)p_st; P.S = (uint2*)p_S; P.flags = (unsigned*)p_flags;
    Maps M;
    make_map2(enc, &M.x[0], d_in[0], DM, SEQ, 168); make_map2(enc, &M.x[1], d_in[0], DM, SEQ, 176);
    make_map2(enc, &M.xo, d_in[0], DM, SEQ, 64);
    make_map2(enc, &M.wg, d_in[8], FF, DM, 64);     make_map2(enc, &M.wu, d_in[9], FF, DM, 64);
    make_map2(enc, &M.wd, d_in[10], DM, FF, 64);
    for (int v = 0; v < 2; v++) {
        const cuuint64_t dims[3] = {64, 256, 172}, strides[2] = {128, 32768};
        const cuuint32_t box[3] = {64, (cuuint32_t)(21 + v), 8};
        make_map(enc, &M.hst[v], hptr, 3, dims, strides, box, false);
    }
    {
        const cuuint64_t dims[5] = {64, 2, 4, 32, 64}, strides[4] = {4 * 8192, 8192, 8 * 8192, 128};
        const cuuint32_t box[5] = {64, 2, 4, 8, 2};
        make_map(enc, &M.sld, p_S, 5, dims, strides, box, true);
    }
    {
        const cuuint64_t dims[5] = {64, 2, 2, 64, 172}, strides[4] = {256, 128, 512, 32768};
        const cuuint32_t box[5] = {64, 2, 2, 2, 8};
        make_map(enc, &M.hld, hptr, 5, dims, strides, box, false);
    }
    fused_kernel<<<NCTA, 512, SMEM_BYTES>>>(P, M);
}
```

```cpp
#include <cuda_runtime.h>
#include <cuda_bf16.h>
#include <cuda.h>
#include <stdint.h>

#define PROF 0

namespace {

constexpr int SEQ = 2048, DM = 512, FF = 1376;
constexpr int NCTA = 132;
#define SIGK 3
#define KUNR 4
constexpr int KUNR_ = KUNR;
constexpr int TOKG = 344;

constexpr uint32_t OFF_W = 0;
constexpr uint32_t XBUF = 22528;
constexpr uint32_t OFF_X = 65536;
constexpr uint32_t OFF_CONV = 155648;
constexpr uint32_t CH_STRIDE = 17536;
constexpr uint32_t CH_T = 0;
constexpr uint32_t CH_A3 = 8448;
constexpr uint32_t CH_B3 = 12544;
constexpr uint32_t CH_U = 13312;
constexpr uint32_t CH_G = CH_A3 + 2064;
constexpr uint32_t UPLANE = 2112;
constexpr uint32_t CH_LN = 0, CH_PART = 4224, CH_PSZ = 3072, CH_LNT = 13440;
constexpr uint32_t OFF_SST = 60416;
constexpr uint32_t OFF_XO = 191488, OFF_SI = 207872;
constexpr uint32_t OFF_ST = 225792;
constexpr uint32_t OFF_CSUM = 228544;
constexpr uint32_t OFF_BAR = 229056;
constexpr uint32_t SMEM_BYTES = 229568;

enum {
    B_FULLW = 0, B_EMPTYW = 4, B_FULLX = 8, B_EMPTYX = 12, B_FULLD = 16, B_EMPTYD = 24,
    B_U = 32, B_XO = 33, B_S = 34, B_STG = 35, B_HF = 37, B_STATS = 38, B_LNS = 39, B_SST = 40,
    B_TURN = 43,
    B_CONV = 46, B_LN = 50, B_CS = 51, B_EPI = 52, B_SIG = 54,
    B_LNX = 60
};
enum { F_A = 0, F_H = 1, F_S = 13, F_EXIT = 17, F_COUNT = 18 };

__device__ uint4 g_xnT[DM * 256];
__device__ float2 g_st[6 * TOKG];
__device__ uint4 g_H[172 * 256 * 8];
__device__ uint2 g_S[256 * 1024];
__device__ __align__(128) unsigned g_flags[F_COUNT * 32];
#define STAMP(i) do {} while (0)
#define GSTAMP(i) do {} while (0)
#define STAMP2(i) do {} while (0)

__device__ __forceinline__ uint32_t smem_u32(const void* p) { return (uint32_t)__cvta_generic_to_shared(p); }
__device__ __forceinline__ void mbar_expect(uint32_t bar, uint32_t bytes) { asm volatile("mbarrier.arrive.expect_tx.shared::cta.b64 _, [%0], %1;" :: "r"(bar), "r"(bytes) : "memory"); }
__device__ __forceinline__ void mbar_arrive(uint32_t bar) { asm volatile("mbarrier.arrive.shared::cta.b64 _, [%0];" :: "r"(bar) : "memory"); }
__device__ __forceinline__ void mbar_wait(uint32_t bar, uint32_t parity) {
    asm volatile("{.reg .pred p; .reg .u32 n; mov.u32 n, 0x20000;\n"
                 "LW: mbarrier.try_wait.parity.shared::cta.b64 p, [%0], %1;\n"
                 "sub.u32 n, n, 1; setp.eq.or.u32 p, n, 0, p; @!p bra LW;}" :: "r"(bar), "r"(parity) : "memory");
}
__device__ __forceinline__ void mbar_arrive_if(uint32_t bar, uint32_t pred) {
    asm volatile("{.reg .pred p; setp.ne.u32 p, %1, 0; @p mbarrier.arrive.shared::cta.b64 _, [%0];}" :: "r"(bar), "r"(pred) : "memory");
}
__device__ __forceinline__ bool elect_one() { uint32_t p; asm volatile("{.reg .pred P; elect.sync _|P, 0xffffffff; selp.u32 %0, 1, 0, P;}" : "=r"(p)); return p; }
__device__ __forceinline__ void tma2d(uint32_t dst, const CUtensorMap* m, int c0, int c1, uint32_t bar) {
    asm volatile("cp.async.bulk.tensor.2d.shared::cluster.global.mbarrier::complete_tx::bytes [%0], [%1, {%3, %4}], [%2];"
        :: "r"(dst), "l"(m), "r"(bar), "r"(c0), "r"(c1) : "memory");
}
__device__ __forceinline__ void bulk_load(uint32_t dst, const void* src, uint32_t bytes, uint32_t bar) {
    asm volatile("cp.async.bulk.shared::cluster.global.mbarrier::complete_tx::bytes [%0], [%1], %2, [%3];" :: "r"(dst), "l"(src), "r"(bytes), "r"(bar) : "memory");
}
__device__ __forceinline__ void bulk_store(void* dst, uint32_t src, uint32_t bytes) {
    asm volatile("cp.async.bulk.global.shared::cta.bulk_group [%0], [%1], %2;" :: "l"(dst), "r"(src), "r"(bytes) : "memory");
}
__device__ __forceinline__ void fence_async_smem() { asm volatile("fence.proxy.async.shared::cta;" ::: "memory"); }
__device__ __forceinline__ void flag_wait(unsigned* g_flags, int f, unsigned target) {
    asm volatile("{.reg .pred p; .reg .u32 n, v; mov.u32 n, 0x40000;\n"
                 "LF: ld.acquire.gpu.global.u32 v, [%0]; setp.ge.u32 p, v, %1; @p bra LD;\n"
                 "sub.u32 n, n, 1; setp.ne.u32 p, n, 0; @p bra LF; trap;\nLD: }"
                 :: "l"(g_flags + f * 32), "r"(target) : "memory");
}
__device__ __forceinline__ void flag_signal(unsigned* g_flags, int f) {
    asm volatile("cp.async.bulk.commit_group; cp.async.bulk.wait_group 0; red.relaxed.gpu.global.add.u32 [%0], 1;" :: "l"(g_flags + f * 32) : "memory");
}
__device__ __forceinline__ void exit_count(unsigned* g_flags) {
    if (atomicAdd(g_flags + F_EXIT * 32, 1u) == NCTA - 1) {
        #pragma unroll 1
        for (int i = 0; i < F_COUNT; i++) g_flags[i * 32] = 0;
    }
}
__device__ __forceinline__ void bar_sync(int id) { asm volatile("bar.sync %0, 128;" :: "r"(id) : "memory"); }
__device__ __forceinline__ uint64_t mkdesc(uint32_t addr, uint32_t lbo, uint32_t sbo, uint32_t swz) {
    return (uint64_t)((addr >> 4) | ((lbo >> 4) << 16)) | ((uint64_t)((sbo >> 4) | (swz << 30)) << 32);
}
#define WG_FENCE() asm volatile("wgmma.fence.sync.aligned;" ::: "memory")
#define WG_COMMIT() asm volatile("wgmma.commit_group.sync.aligned;" ::: "memory")
#define WG_WAIT(n) asm volatile("wgmma.wait_group.sync.aligned " #n ";" ::: "memory")
template <int N> __device__ __forceinline__ void fence_acc(float (&d)[N]) {
    #pragma unroll
    for (int i = 0; i < N; i++) asm volatile("" : "+f"(d[i]) :: "memory");
}
template <int N> __device__ __forceinline__ void define_acc(float (&d)[N]) {
    #pragma unroll
    for (int i = 0; i < N; i++) asm volatile("" : "=f"(d[i]));
}
__device__ __forceinline__ uint32_t pack2(float lo, float hi) { uint32_t r; asm("cvt.rn.bf16x2.f32 %0, %1, %2;" : "=r"(r) : "f"(hi), "f"(lo)); return r; }
__device__ __forceinline__ float bf_lo(uint32_t v) { return __uint_as_float(v << 16); }
__device__ __forceinline__ float bf_hi(uint32_t v) { return __uint_as_float(v & 0xffff0000u); }
__device__ __forceinline__ float bf_round(float v) { return bf_hi(pack2(0.f, v)); }
__device__ __forceinline__ float tanh_fast(float v) { float r; asm("tanh.approx.f32 %0, %1;" : "=f"(r) : "f"(v)); return r; }
__device__ __forceinline__ float ex2(float v) { float r; asm("ex2.approx.ftz.f32 %0, %1;" : "=f"(r) : "f"(v)); return r; }
__device__ __forceinline__ uint4 lds128(uint32_t a) { uint4 v; asm volatile("ld.shared.v4.b32 {%0,%1,%2,%3}, [%4];" : "=r"(v.x), "=r"(v.y), "=r"(v.z), "=r"(v.w) : "r"(a)); return v; }
__device__ __forceinline__ uint2 lds64(uint32_t a) { uint2 v; asm volatile("ld.shared.v2.b32 {%0,%1}, [%2];" : "=r"(v.x), "=r"(v.y) : "r"(a)); return v; }
__device__ __forceinline__ float ldsf(uint32_t a) { float v; asm volatile("ld.shared.f32 %0, [%1];" : "=f"(v) : "r"(a)); return v; }
__device__ __forceinline__ void sts128(uint32_t a, uint32_t x, uint32_t y, uint32_t z, uint32_t w) { asm volatile("st.shared.v4.b32 [%0], {%1,%2,%3,%4};" :: "r"(a), "r"(x), "r"(y), "r"(z), "r"(w) : "memory"); }
__device__ __forceinline__ void sts64(uint32_t a, uint32_t x, uint32_t y) { asm volatile("st.shared.v2.b32 [%0], {%1,%2};" :: "r"(a), "r"(x), "r"(y) : "memory"); }
__device__ __forceinline__ void stsf(uint32_t a, float x) { asm volatile("st.shared.f32 [%0], %1;" :: "r"(a), "f"(x) : "memory"); }
__device__ __forceinline__ void sts16(uint32_t a, uint32_t x) { asm volatile("st.shared.b16 [%0], %1;" :: "r"(a), "h"((unsigned short)x) : "memory"); }
__device__ __forceinline__ void stsm4(uint32_t a, uint32_t r0, uint32_t r1, uint32_t r2, uint32_t r3) {
    asm volatile("stmatrix.sync.aligned.m8n8.x4.shared.b16 [%0], {%1,%2,%3,%4};" :: "r"(a), "r"(r0), "r"(r1), "r"(r2), "r"(r3) : "memory");
}
__device__ __forceinline__ void ldsm4(uint32_t (&r)[4], uint32_t a) {
    asm volatile("ldmatrix.sync.aligned.m8n8.x4.shared.b16 {%0,%1,%2,%3}, [%4];" : "=r"(r[0]), "=r"(r[1]), "=r"(r[2]), "=r"(r[3]) : "r"(a) : "memory");
}
#define FU(x) __float_as_uint(x)
#define UF(x) __uint_as_float(x)
__device__ __forceinline__ uint32_t wd_slot(int s) { return (uint32_t)((0xbba8403056201000ull >> (8 * s)) & 0xff) << 10; }
__device__ __forceinline__ uint32_t h_slot(int s) { return (uint32_t)((0xcba0908880787068ull >> (8 * s)) & 0xff) << 10; }

template<int N> __device__ __forceinline__ void wg_rs(float (&d)[64], uint32_t a0, uint32_t a1, uint32_t a2, uint32_t a3, uint64_t db);
template<> __device__ __forceinline__ void wg_rs<128>(float (&d)[64], uint32_t a0, uint32_t a1, uint32_t a2, uint32_t a3, uint64_t db) {
  asm volatile("{.reg .pred p; setp.ne.b32 p, 1, 0; wgmma.mma_async.sync.aligned.m64n128k16.f32.bf16.bf16 {%0,%1,%2,%3,%4,%5,%6,%7,%8,%9,%10,%11,%12,%13,%14,%15,%16,%17,%18,%19,%20,%21,%22,%23,%24,%25,%26,%27,%28,%29,%30,%31,%32,%33,%34,%35,%36,%37,%38,%39,%40,%41,%42,%43,%44,%45,%46,%47,%48,%49,%50,%51,%52,%53,%54,%55,%56,%57,%58,%59,%60,%61,%62,%63}, {%64,%65,%66,%67}, %68, p, 1, 1, 0;}"
    : "+f"(d[0]),"+f"(d[1]),"+f"(d[2]),"+f"(d[3]),"+f"(d[4]),"+f"(d[5]),"+f"(d[6]),"+f"(d[7]),"+f"(d[8]),"+f"(d[9]),"+f"(d[10]),"+f"(d[11]),"+f"(d[12]),"+f"(d[13]),"+f"(d[14]),"+f"(d[15]),"+f"(d[16]),"+f"(d[17]),"+f"(d[18]),"+f"(d[19]),"+f"(d[20]),"+f"(d[21]),"+f"(d[22]),"+f"(d[23]),"+f"(d[24]),"+f"(d[25]),"+f"(d[26]),"+f"(d[27]),"+f"(d[28]),"+f"(d[29]),"+f"(d[30]),"+f"(d[31]),"+f"(d[32]),"+f"(d[33]),"+f"(d[34]),"+f"(d[35]),"+f"(d[36]),"+f"(d[37]),"+f"(d[38]),"+f"(d[39]),"+f"(d[40]),"+f"(d[41]),"+f"(d[42]),"+f"(d[43]),"+f"(d[44]),"+f"(d[45]),"+f"(d[46]),"+f"(d[47]),"+f"(d[48]),"+f"(d[49]),"+f"(d[50]),"+f"(d[51]),"+f"(d[52]),"+f"(d[53]),"+f"(d[54]),"+f"(d[55]),"+f"(d[56]),"+f"(d[57]),"+f"(d[58]),"+f"(d[59]),"+f"(d[60]),"+f"(d[61]),"+f"(d[62]),"+f"(d[63]) : "r"(a0), "r"(a1), "r"(a2), "r"(a3), "l"(db));
}
template<> __device__ __forceinline__ void wg_rs<120>(float (&d)[64], uint32_t a0, uint32_t a1, uint32_t a2, uint32_t a3, uint64_t db) {
  asm volatile("{.reg .pred p; setp.ne.b32 p, 1, 0; wgmma.mma_async.sync.aligned.m64n120k16.f32.bf16.bf16 {%0,%1,%2,%3,%4,%5,%6,%7,%8,%9,%10,%11,%12,%13,%14,%15,%16,%17,%18,%19,%20,%21,%22,%23,%24,%25,%26,%27,%28,%29,%30,%31,%32,%33,%34,%35,%36,%37,%38,%39,%40,%41,%42,%43,%44,%45,%46,%47,%48,%49,%50,%51,%52,%53,%54,%55,%56,%57,%58,%59}, {%60,%61,%62,%63}, %64, p, 1, 1, 0;}"
    : "+f"(d[0]),"+f"(d[1]),"+f"(d[2]),"+f"(d[3]),"+f"(d[4]),"+f"(d[5]),"+f"(d[6]),"+f"(d[7]),"+f"(d[8]),"+f"(d[9]),"+f"(d[10]),"+f"(d[11]),"+f"(d[12]),"+f"(d[13]),"+f"(d[14]),"+f"(d[15]),"+f"(d[16]),"+f"(d[17]),"+f"(d[18]),"+f"(d[19]),"+f"(d[20]),"+f"(d[21]),"+f"(d[22]),"+f"(d[23]),"+f"(d[24]),"+f"(d[25]),"+f"(d[26]),"+f"(d[27]),"+f"(d[28]),"+f"(d[29]),"+f"(d[30]),"+f"(d[31]),"+f"(d[32]),"+f"(d[33]),"+f"(d[34]),"+f"(d[35]),"+f"(d[36]),"+f"(d[37]),"+f"(d[38]),"+f"(d[39]),"+f"(d[40]),"+f"(d[41]),"+f"(d[42]),"+f"(d[43]),"+f"(d[44]),"+f"(d[45]),"+f"(d[46]),"+f"(d[47]),"+f"(d[48]),"+f"(d[49]),"+f"(d[50]),"+f"(d[51]),"+f"(d[52]),"+f"(d[53]),"+f"(d[54]),"+f"(d[55]),"+f"(d[56]),"+f"(d[57]),"+f"(d[58]),"+f"(d[59]) : "r"(a0), "r"(a1), "r"(a2), "r"(a3), "l"(db));
}
template<> __device__ __forceinline__ void wg_rs<112>(float (&d)[64], uint32_t a0, uint32_t a1, uint32_t a2, uint32_t a3, uint64_t db) {
  asm volatile("{.reg .pred p; setp.ne.b32 p, 1, 0; wgmma.mma_async.sync.aligned.m64n112k16.f32.bf16.bf16 {%0,%1,%2,%3,%4,%5,%6,%7,%8,%9,%10,%11,%12,%13,%14,%15,%16,%17,%18,%19,%20,%21,%22,%23,%24,%25,%26,%27,%28,%29,%30,%31,%32,%33,%34,%35,%36,%37,%38,%39,%40,%41,%42,%43,%44,%45,%46,%47,%48,%49,%50,%51,%52,%53,%54,%55}, {%56,%57,%58,%59}, %60, p, 1, 1, 0;}"
    : "+f"(d[0]),"+f"(d[1]),"+f"(d[2]),"+f"(d[3]),"+f"(d[4]),"+f"(d[5]),"+f"(d[6]),"+f"(d[7]),"+f"(d[8]),"+f"(d[9]),"+f"(d[10]),"+f"(d[11]),"+f"(d[12]),"+f"(d[13]),"+f"(d[14]),"+f"(d[15]),"+f"(d[16]),"+f"(d[17]),"+f"(d[18]),"+f"(d[19]),"+f"(d[20]),"+f"(d[21]),"+f"(d[22]),"+f"(d[23]),"+f"(d[24]),"+f"(d[25]),"+f"(d[26]),"+f"(d[27]),"+f"(d[28]),"+f"(d[29]),"+f"(d[30]),"+f"(d[31]),"+f"(d[32]),"+f"(d[33]),"+f"(d[34]),"+f"(d[35]),"+f"(d[36]),"+f"(d[37]),"+f"(d[38]),"+f"(d[39]),"+f"(d[40]),"+f"(d[41]),"+f"(d[42]),"+f"(d[43]),"+f"(d[44]),"+f"(d[45]),"+f"(d[46]),"+f"(d[47]),"+f"(d[48]),"+f"(d[49]),"+f"(d[50]),"+f"(d[51]),"+f"(d[52]),"+f"(d[53]),"+f"(d[54]),"+f"(d[55]) : "r"(a0), "r"(a1), "r"(a2), "r"(a3), "l"(db));
}
template<> __device__ __forceinline__ void wg_rs<104>(float (&d)[64], uint32_t a0, uint32_t a1, uint32_t a2, uint32_t a3, uint64_t db) {
  asm volatile("{.reg .pred p; setp.ne.b32 p, 1, 0; wgmma.mma_async.sync.aligned.m64n104k16.f32.bf16.bf16 {%0,%1,%2,%3,%4,%5,%6,%7,%8,%9,%10,%11,%12,%13,%14,%15,%16,%17,%18,%19,%20,%21,%22,%23,%24,%25,%26,%27,%28,%29,%30,%31,%32,%33,%34,%35,%36,%37,%38,%39,%40,%41,%42,%43,%44,%45,%46,%47,%48,%49,%50,%51}, {%52,%53,%54,%55}, %56, p, 1, 1, 0;}"
    : "+f"(d[0]),"+f"(d[1]),"+f"(d[2]),"+f"(d[3]),"+f"(d[4]),"+f"(d[5]),"+f"(d[6]),"+f"(d[7]),"+f"(d[8]),"+f"(d[9]),"+f"(d[10]),"+f"(d[11]),"+f"(d[12]),"+f"(d[13]),"+f"(d[14]),"+f"(d[15]),"+f"(d[16]),"+f"(d[17]),"+f"(d[18]),"+f"(d[19]),"+f"(d[20]),"+f"(d[21]),"+f"(d[22]),"+f"(d[23]),"+f"(d[24]),"+f"(d[25]),"+f"(d[26]),"+f"(d[27]),"+f"(d[28]),"+f"(d[29]),"+f"(d[30]),"+f"(d[31]),"+f"(d[32]),"+f"(d[33]),"+f"(d[34]),"+f"(d[35]),"+f"(d[36]),"+f"(d[37]),"+f"(d[38]),"+f"(d[39]),"+f"(d[40]),"+f"(d[41]),"+f"(d[42]),"+f"(d[43]),"+f"(d[44]),"+f"(d[45]),"+f"(d[46]),"+f"(d[47]),"+f"(d[48]),"+f"(d[49]),"+f"(d[50]),"+f"(d[51]) : "r"(a0), "r"(a1), "r"(a2), "r"(a3), "l"(db));
}
template<> __device__ __forceinline__ void wg_rs<96>(float (&d)[64], uint32_t a0, uint32_t a1, uint32_t a2, uint32_t a3, uint64_t db) {
  asm volatile("{.reg .pred p; setp.ne.b32 p, 1, 0; wgmma.mma_async.sync.aligned.m64n96k16.f32.bf16.bf16 {%0,%1,%2,%3,%4,%5,%6,%7,%8,%9,%10,%11,%12,%13,%14,%15,%16,%17,%18,%19,%20,%21,%22,%23,%24,%25,%26,%27,%28,%29,%30,%31,%32,%33,%34,%35,%36,%37,%38,%39,%40,%41,%42,%43,%44,%45,%46,%47}, {%48,%49,%50,%51}, %52, p, 1, 1, 0;}"
    : "+f"(d[0]),"+f"(d[1]),"+f"(d[2]),"+f"(d[3]),"+f"(d[4]),"+f"(d[5]),"+f"(d[6]),"+f"(d[7]),"+f"(d[8]),"+f"(d[9]),"+f"(d[10]),"+f"(d[11]),"+f"(d[12]),"+f"(d[13]),"+f"(d[14]),"+f"(d[15]),"+f"(d[16]),"+f"(d[17]),"+f"(d[18]),"+f"(d[19]),"+f"(d[20]),"+f"(d[21]),"+f"(d[22]),"+f"(d[23]),"+f"(d[24]),"+f"(d[25]),"+f"(d[26]),"+f"(d[27]),"+f"(d[28]),"+f"(d[29]),"+f"(d[30]),"+f"(d[31]),"+f"(d[32]),"+f"(d[33]),"+f"(d[34]),"+f"(d[35]),"+f"(d[36]),"+f"(d[37]),"+f"(d[38]),"+f"(d[39]),"+f"(d[40]),"+f"(d[41]),"+f"(d[42]),"+f"(d[43]),"+f"(d[44]),"+f"(d[45]),"+f"(d[46]),"+f"(d[47]) : "r"(a0), "r"(a1), "r"(a2), "r"(a3), "l"(db));
}
template<> __device__ __forceinline__ void wg_rs<88>(float (&d)[64], uint32_t a0, uint32_t a1, uint32_t a2, uint32_t a3, uint64_t db) {
  asm volatile("{.reg .pred p; setp.ne.b32 p, 1, 0; wgmma.mma_async.sync.aligned.m64n88k16.f32.bf16.bf16 {%0,%1,%2,%3,%4,%5,%6,%7,%8,%9,%10,%11,%12,%13,%14,%15,%16,%17,%18,%19,%20,%21,%22,%23,%24,%25,%26,%27,%28,%29,%30,%31,%32,%33,%34,%35,%36,%37,%38,%39,%40,%41,%42,%43}, {%44,%45,%46,%47}, %48, p, 1, 1, 0;}"
    : "+f"(d[0]),"+f"(d[1]),"+f"(d[2]),"+f"(d[3]),"+f"(d[4]),"+f"(d[5]),"+f"(d[6]),"+f"(d[7]),"+f"(d[8]),"+f"(d[9]),"+f"(d[10]),"+f"(d[11]),"+f"(d[12]),"+f"(d[13]),"+f"(d[14]),"+f"(d[15]),"+f"(d[16]),"+f"(d[17]),"+f"(d[18]),"+f"(d[19]),"+f"(d[20]),"+f"(d[21]),"+f"(d[22]),"+f"(d[23]),"+f"(d[24]),"+f"(d[25]),"+f"(d[26]),"+f"(d[27]),"+f"(d[28]),"+f"(d[29]),"+f"(d[30]),"+f"(d[31]),"+f"(d[32]),"+f"(d[33]),"+f"(d[34]),"+f"(d[35]),"+f"(d[36]),"+f"(d[37]),"+f"(d[38]),"+f"(d[39]),"+f"(d[40]),"+f"(d[41]),"+f"(d[42]),"+f"(d[43]) : "r"(a0), "r"(a1), "r"(a2), "r"(a3), "l"(db));
}
template<> __device__ __forceinline__ void wg_rs<80>(float (&d)[64], uint32_t a0, uint32_t a1, uint32_t a2, uint32_t a3, uint64_t db) {
  asm volatile("{.reg .pred p; setp.ne.b32 p, 1, 0; wgmma.mma_async.sync.aligned.m64n80k16.f32.bf16.bf16 {%0,%1,%2,%3,%4,%5,%6,%7,%8,%9,%10,%11,%12,%13,%14,%15,%16,%17,%18,%19,%20,%21,%22,%23,%24,%25,%26,%27,%28,%29,%30,%31,%32,%33,%34,%35,%36,%37,%38,%39}, {%40,%41,%42,%43}, %44, p, 1, 1, 0;}"
    : "+f"(d[0]),"+f"(d[1]),"+f"(d[2]),"+f"(d[3]),"+f"(d[4]),"+f"(d[5]),"+f"(d[6]),"+f"(d[7]),"+f"(d[8]),"+f"(d[9]),"+f"(d[10]),"+f"(d[11]),"+f"(d[12]),"+f"(d[13]),"+f"(d[14]),"+f"(d[15]),"+f"(d[16]),"+f"(d[17]),"+f"(d[18]),"+f"(d[19]),"+f"(d[20]),"+f"(d[21]),"+f"(d[22]),"+f"(d[23]),"+f"(d[24]),"+f"(d[25]),"+f"(d[26]),"+f"(d[27]),"+f"(d[28]),"+f"(d[29]),"+f"(d[30]),"+f"(d[31]),"+f"(d[32]),"+f"(d[33]),"+f"(d[34]),"+f"(d[35]),"+f"(d[36]),"+f"(d[37]),"+f"(d[38]),"+f"(d[39]) : "r"(a0), "r"(a1), "r"(a2), "r"(a3), "l"(db));
}
template<> __device__ __forceinline__ void wg_rs<72>(float (&d)[64], uint32_t a0, uint32_t a1, uint32_t a2, uint32_t a3, uint64_t db) {
  asm volatile("{.reg .pred p; setp.ne.b32 p, 1, 0; wgmma.mma_async.sync.aligned.m64n72k16.f32.bf16.bf16 {%0,%1,%2,%3,%4,%5,%6,%7,%8,%9,%10,%11,%12,%13,%14,%15,%16,%17,%18,%19,%20,%21,%22,%23,%24,%25,%26,%27,%28,%29,%30,%31,%32,%33,%34,%35}, {%36,%37,%38,%39}, %40, p, 1, 1, 0;}"
    : "+f"(d[0]),"+f"(d[1]),"+f"(d[2]),"+f"(d[3]),"+f"(d[4]),"+f"(d[5]),"+f"(d[6]),"+f"(d[7]),"+f"(d[8]),"+f"(d[9]),"+f"(d[10]),"+f"(d[11]),"+f"(d[12]),"+f"(d[13]),"+f"(d[14]),"+f"(d[15]),"+f"(d[16]),"+f"(d[17]),"+f"(d[18]),"+f"(d[19]),"+f"(d[20]),"+f"(d[21]),"+f"(d[22]),"+f"(d[23]),"+f"(d[24]),"+f"(d[25]),"+f"(d[26]),"+f"(d[27]),"+f"(d[28]),"+f"(d[29]),"+f"(d[30]),"+f"(d[31]),"+f"(d[32]),"+f"(d[33]),"+f"(d[34]),"+f"(d[35]) : "r"(a0), "r"(a1), "r"(a2), "r"(a3), "l"(db));
}
template<> __device__ __forceinline__ void wg_rs<64>(float (&d)[64], uint32_t a0, uint32_t a1, uint32_t a2, uint32_t a3, uint64_t db) {
  asm volatile("{.reg .pred p; setp.ne.b32 p, 1, 0; wgmma.mma_async.sync.aligned.m64n64k16.f32.bf16.bf16 {%0,%1,%2,%3,%4,%5,%6,%7,%8,%9,%10,%11,%12,%13,%14,%15,%16,%17,%18,%19,%20,%21,%22,%23,%24,%25,%26,%27,%28,%29,%30,%31}, {%32,%33,%34,%35}, %36, p, 1, 1, 0;}"
    : "+f"(d[0]),"+f"(d[1]),"+f"(d[2]),"+f"(d[3]),"+f"(d[4]),"+f"(d[5]),"+f"(d[6]),"+f"(d[7]),"+f"(d[8]),"+f"(d[9]),"+f"(d[10]),"+f"(d[11]),"+f"(d[12]),"+f"(d[13]),"+f"(d[14]),"+f"(d[15]),"+f"(d[16]),"+f"(d[17]),"+f"(d[18]),"+f"(d[19]),"+f"(d[20]),"+f"(d[21]),"+f"(d[22]),"+f"(d[23]),"+f"(d[24]),"+f"(d[25]),"+f"(d[26]),"+f"(d[27]),"+f"(d[28]),"+f"(d[29]),"+f"(d[30]),"+f"(d[31]) : "r"(a0), "r"(a1), "r"(a2), "r"(a3), "l"(db));
}
__device__ __forceinline__ void wg_rs_first(float (&d)[64], uint32_t a0, uint32_t a1, uint32_t a2, uint32_t a3, uint64_t db) {
  asm volatile("{.reg .pred p; setp.ne.b32 p, 0, 0; wgmma.mma_async.sync.aligned.m64n128k16.f32.bf16.bf16 {%0,%1,%2,%3,%4,%5,%6,%7,%8,%9,%10,%11,%12,%13,%14,%15,%16,%17,%18,%19,%20,%21,%22,%23,%24,%25,%26,%27,%28,%29,%30,%31,%32,%33,%34,%35,%36,%37,%38,%39,%40,%41,%42,%43,%44,%45,%46,%47,%48,%49,%50,%51,%52,%53,%54,%55,%56,%57,%58,%59,%60,%61,%62,%63}, {%64,%65,%66,%67}, %68, p, 1, 1, 0;}"
    : "=f"(d[0]),"=f"(d[1]),"=f"(d[2]),"=f"(d[3]),"=f"(d[4]),"=f"(d[5]),"=f"(d[6]),"=f"(d[7]),"=f"(d[8]),"=f"(d[9]),"=f"(d[10]),"=f"(d[11]),"=f"(d[12]),"=f"(d[13]),"=f"(d[14]),"=f"(d[15]),"=f"(d[16]),"=f"(d[17]),"=f"(d[18]),"=f"(d[19]),"=f"(d[20]),"=f"(d[21]),"=f"(d[22]),"=f"(d[23]),"=f"(d[24]),"=f"(d[25]),"=f"(d[26]),"=f"(d[27]),"=f"(d[28]),"=f"(d[29]),"=f"(d[30]),"=f"(d[31]),"=f"(d[32]),"=f"(d[33]),"=f"(d[34]),"=f"(d[35]),"=f"(d[36]),"=f"(d[37]),"=f"(d[38]),"=f"(d[39]),"=f"(d[40]),"=f"(d[41]),"=f"(d[42]),"=f"(d[43]),"=f"(d[44]),"=f"(d[45]),"=f"(d[46]),"=f"(d[47]),"=f"(d[48]),"=f"(d[49]),"=f"(d[50]),"=f"(d[51]),"=f"(d[52]),"=f"(d[53]),"=f"(d[54]),"=f"(d[55]),"=f"(d[56]),"=f"(d[57]),"=f"(d[58]),"=f"(d[59]),"=f"(d[60]),"=f"(d[61]),"=f"(d[62]),"=f"(d[63]) : "r"(a0), "r"(a1), "r"(a2), "r"(a3), "l"(db));
}
__device__ __forceinline__ void wg_tt128(float (&d)[64], uint64_t da, uint64_t db, int sc) {
  asm volatile("{.reg .pred p; setp.ne.b32 p, %66, 0; wgmma.mma_async.sync.aligned.m64n128k16.f32.bf16.bf16 {%0,%1,%2,%3,%4,%5,%6,%7,%8,%9,%10,%11,%12,%13,%14,%15,%16,%17,%18,%19,%20,%21,%22,%23,%24,%25,%26,%27,%28,%29,%30,%31,%32,%33,%34,%35,%36,%37,%38,%39,%40,%41,%42,%43,%44,%45,%46,%47,%48,%49,%50,%51,%52,%53,%54,%55,%56,%57,%58,%59,%60,%61,%62,%63}, %64, %65, p, 1, 1, 1, 1;}"
    : "+f"(d[0]),"+f"(d[1]),"+f"(d[2]),"+f"(d[3]),"+f"(d[4]),"+f"(d[5]),"+f"(d[6]),"+f"(d[7]),"+f"(d[8]),"+f"(d[9]),"+f"(d[10]),"+f"(d[11]),"+f"(d[12]),"+f"(d[13]),"+f"(d[14]),"+f"(d[15]),"+f"(d[16]),"+f"(d[17]),"+f"(d[18]),"+f"(d[19]),"+f"(d[20]),"+f"(d[21]),"+f"(d[22]),"+f"(d[23]),"+f"(d[24]),"+f"(d[25]),"+f"(d[26]),"+f"(d[27]),"+f"(d[28]),"+f"(d[29]),"+f"(d[30]),"+f"(d[31]),"+f"(d[32]),"+f"(d[33]),"+f"(d[34]),"+f"(d[35]),"+f"(d[36]),"+f"(d[37]),"+f"(d[38]),"+f"(d[39]),"+f"(d[40]),"+f"(d[41]),"+f"(d[42]),"+f"(d[43]),"+f"(d[44]),"+f"(d[45]),"+f"(d[46]),"+f"(d[47]),"+f"(d[48]),"+f"(d[49]),"+f"(d[50]),"+f"(d[51]),"+f"(d[52]),"+f"(d[53]),"+f"(d[54]),"+f"(d[55]),"+f"(d[56]),"+f"(d[57]),"+f"(d[58]),"+f"(d[59]),"+f"(d[60]),"+f"(d[61]),"+f"(d[62]),"+f"(d[63]) : "l"(da), "l"(db), "r"(sc));
}
__device__ __forceinline__ void wg_tt64(float (&d)[64], uint64_t da, uint64_t db, int sc) {
  asm volatile("{.reg .pred p; setp.ne.b32 p, %34, 0; wgmma.mma_async.sync.aligned.m64n64k16.f32.bf16.bf16 {%0,%1,%2,%3,%4,%5,%6,%7,%8,%9,%10,%11,%12,%13,%14,%15,%16,%17,%18,%19,%20,%21,%22,%23,%24,%25,%26,%27,%28,%29,%30,%31}, %32, %33, p, 1, 1, 1, 1;}"
    : "+f"(d[0]),"+f"(d[1]),"+f"(d[2]),"+f"(d[3]),"+f"(d[4]),"+f"(d[5]),"+f"(d[6]),"+f"(d[7]),"+f"(d[8]),"+f"(d[9]),"+f"(d[10]),"+f"(d[11]),"+f"(d[12]),"+f"(d[13]),"+f"(d[14]),"+f"(d[15]),"+f"(d[16]),"+f"(d[17]),"+f"(d[18]),"+f"(d[19]),"+f"(d[20]),"+f"(d[21]),"+f"(d[22]),"+f"(d[23]),"+f"(d[24]),"+f"(d[25]),"+f"(d[26]),"+f"(d[27]),"+f"(d[28]),"+f"(d[29]),"+f"(d[30]),"+f"(d[31]) : "l"(da), "l"(db), "r"(sc));
}
__device__ __forceinline__ void wg_tt32(float (&d)[64], uint64_t da, uint64_t db, int sc) {
  asm volatile("{.reg .pred p; setp.ne.b32 p, %18, 0; wgmma.mma_async.sync.aligned.m64n32k16.f32.bf16.bf16 {%0,%1,%2,%3,%4,%5,%6,%7,%8,%9,%10,%11,%12,%13,%14,%15}, %16, %17, p, 1, 1, 1, 1;}"
    : "+f"(d[0]),"+f"(d[1]),"+f"(d[2]),"+f"(d[3]),"+f"(d[4]),"+f"(d[5]),"+f"(d[6]),"+f"(d[7]),"+f"(d[8]),"+f"(d[9]),"+f"(d[10]),"+f"(d[11]),"+f"(d[12]),"+f"(d[13]),"+f"(d[14]),"+f"(d[15]) : "l"(da), "l"(db), "r"(sc));
}
__device__ __forceinline__ void wg_g1(float (&d)[88], uint64_t da, uint64_t db, int sc) {
  asm volatile("{.reg .pred p; setp.ne.b32 p, %90, 0; wgmma.mma_async.sync.aligned.m64n176k16.f32.bf16.bf16 {%0,%1,%2,%3,%4,%5,%6,%7,%8,%9,%10,%11,%12,%13,%14,%15,%16,%17,%18,%19,%20,%21,%22,%23,%24,%25,%26,%27,%28,%29,%30,%31,%32,%33,%34,%35,%36,%37,%38,%39,%40,%41,%42,%43,%44,%45,%46,%47,%48,%49,%50,%51,%52,%53,%54,%55,%56,%57,%58,%59,%60,%61,%62,%63,%64,%65,%66,%67,%68,%69,%70,%71,%72,%73,%74,%75,%76,%77,%78,%79,%80,%81,%82,%83,%84,%85,%86,%87}, %88, %89, p, 1, 1, 1, 0;}"
    : "+f"(d[0]),"+f"(d[1]),"+f"(d[2]),"+f"(d[3]),"+f"(d[4]),"+f"(d[5]),"+f"(d[6]),"+f"(d[7]),"+f"(d[8]),"+f"(d[9]),"+f"(d[10]),"+f"(d[11]),"+f"(d[12]),"+f"(d[13]),"+f"(d[14]),"+f"(d[15]),"+f"(d[16]),"+f"(d[17]),"+f"(d[18]),"+f"(d[19]),"+f"(d[20]),"+f"(d[21]),"+f"(d[22]),"+f"(d[23]),"+f"(d[24]),"+f"(d[25]),"+f"(d[26]),"+f"(d[27]),"+f"(d[28]),"+f"(d[29]),"+f"(d[30]),"+f"(d[31]),"+f"(d[32]),"+f"(d[33]),"+f"(d[34]),"+f"(d[35]),"+f"(d[36]),"+f"(d[37]),"+f"(d[38]),"+f"(d[39]),"+f"(d[40]),"+f"(d[41]),"+f"(d[42]),"+f"(d[43]),"+f"(d[44]),"+f"(d[45]),"+f"(d[46]),"+f"(d[47]),"+f"(d[48]),"+f"(d[49]),"+f"(d[50]),"+f"(d[51]),"+f"(d[52]),"+f"(d[53]),"+f"(d[54]),"+f"(d[55]),"+f"(d[56]),"+f"(d[57]),"+f"(d[58]),"+f"(d[59]),"+f"(d[60]),"+f"(d[61]),"+f"(d[62]),"+f"(d[63]),"+f"(d[64]),"+f"(d[65]),"+f"(d[66]),"+f"(d[67]),"+f"(d[68]),"+f"(d[69]),"+f"(d[70]),"+f"(d[71]),"+f"(d[72]),"+f"(d[73]),"+f"(d[74]),"+f"(d[75]),"+f"(d[76]),"+f"(d[77]),"+f"(d[78]),"+f"(d[79]),"+f"(d[80]),"+f"(d[81]),"+f"(d[82]),"+f"(d[83]),"+f"(d[84]),"+f"(d[85]),"+f"(d[86]),"+f"(d[87]) : "l"(da), "l"(db), "r"(sc));
}

struct Params { const __nv_bfloat16 *x, *logA, *Aim, *Cr, *Ci, *logdt, *Dskip, *Wg, *Wu, *Wd; __nv_bfloat16* out; uint4* xnT; float2* st; uint2* S; unsigned* flags; };
struct Maps { CUtensorMap x[2], xo, wg, wu, wd, hst[2], hld, sld; };

__device__ __forceinline__ void conv_channel(uint32_t cb, int w, int lane, uint32_t (&res)[8], int sidx) {
    const int q = lane & 3, g = lane >> 2, gam = g >> 2;
    float acc[64];
    uint2 a[17][2];
    const uint32_t t0 = cb + CH_T + (uint32_t)(14 + 4 * w + (g & 3) - 2 * q) * 280u + gam * 8;
#define LDA(s0, s1) _Pragma("unroll") for (int s = s0; s < s1; s++) { a[s][0] = lds64(t0 + s * 16); a[s][1] = lds64(t0 - 8 * 280 + s * 16); }
#define CT(N, s) wg_rs<N>(acc, a[s][0].x, a[s][0].y, a[s][1].x, a[s][1].y, dU + 4 * (s))
    const uint64_t dU = mkdesc(cb + CH_U, UPLANE, 128, 0);
    LDA(0, 17)
    WG_FENCE();
    if (w == 0) STAMP2(52 + 3 * sidx);
    wg_rs_first(acc, a[0][0].x, a[0][0].y, a[0][1].x, a[0][1].y, dU);
    CT(128, 1); CT(120, 2); CT(120, 3); CT(112, 4); CT(112, 5); CT(104, 6); CT(104, 7); CT(96, 8);
    CT(96, 9); CT(88, 10); CT(88, 11); CT(80, 12); CT(80, 13); CT(72, 14); CT(72, 15); CT(64, 16);
#undef CT
#undef LDA
    wg_tt64(acc, mkdesc(cb + CH_A3, 128, 512, 0), mkdesc(cb + CH_B3, 384, 32, 0), 1);
    wg_tt32(acc, mkdesc(cb + CH_A3 + 256, 128, 512, 0), mkdesc(cb + CH_B3 + 128, 384, 32, 0), 1);
    WG_COMMIT();
    if (w == 0) STAMP2(53 + 3 * sidx);
    WG_WAIT(0);
    fence_acc(acc);
    if (w == 0) STAMP2(54 + 3 * sidx);
    const int src1 = (lane & ~3) | ((q + 1) & 3);
    float E[16][2];
    #pragma unroll
    for (int j = 0; j < 16; j++) {
        const float nxt = (j < 15) ? acc[4 * (j + 1) + 2] : 0.f;
        const float sup = (q == 0) ? nxt : acc[4 * j + 2];
        const float v = __shfl_sync(0xffffffffu, sup, src1);
        E[j][0] = acc[4 * j] + acc[4 * j + 3];
        E[j][1] = acc[4 * j + 1] + v;
    }
    const int src2 = gam ? ((lane & 12) | ((q + 3) & 3)) : (16 | (lane & 12) | ((q + 1) & 3));
    const bool c1 = gam && q != 0, c2 = gam && q == 0;
    #pragma unroll
    for (int a2 = 0; a2 < 8; a2++) {
        float y[2];
        #pragma unroll
        for (int e = 0; e < 2; e++) {
            const float sup = c1 ? E[2 * a2][e] : E[2 * a2 + 1][e];
            const float nxt = (a2 < 7) ? E[2 * a2 + 2][e] : 0.f;
            const float keep = c2 ? nxt : (c1 ? E[2 * a2 + 1][e] : E[2 * a2][e]);
            y[e] = keep + __shfl_sync(0xffffffffu, sup, src2);
        }
        res[a2] = pack2(y[1], y[0]);
    }
}

__device__ __forceinline__ void consumer(uint32_t sb, int warp, const Params& P, const Maps& M) {
    const int V = warp >> 2, w = warp & 3, lane = threadIdx.x & 31, q = lane & 3, g = lane >> 2;
    const int c = blockIdx.x;
    const uint32_t bars = sb + OFF_BAR, xb = sb + OFF_X + V * 2 * XBUF;
    {
        float ag[88], au[88];
        define_acc(ag); define_acc(au);
        mbar_wait(bars + 8 * B_FULLW, 0);
        mbar_wait(bars + 8 * (B_FULLX + 2 * V), 0);
        #pragma unroll 1
        for (int st = 0; st < 8; st++) {
            uint64_t dG = mkdesc(sb + OFF_W + (st & 3) * 16384, 0, 1024, 1), dX = mkdesc(xb + (st & 1) * XBUF, 16, 1024, 1);
            uint32_t sig = lane == 0 && (V ? st < 6 : st > 0);
            asm volatile("" : "+l"(dG), "+l"(dX), "+r"(sig) :: "memory");
            if (V ? st < 7 : st > 1) mbar_wait(bars + 8 * (B_TURN + V), st & 1);
            STAMP(40 + 8 * V + st); if (st == 0 && V == 0) GSTAMP(33);
            WG_FENCE();
            #pragma unroll
            for (int k = 0; k < 4; k++) {
                if (k == SIGK) mbar_arrive_if(bars + 8 * (B_TURN + 1 - V), sig);
                wg_g1(ag, dG + k * 128, dX + k * 2, k ? 1 : st);
                wg_g1(au, dG + 512 + k * 128, dX + k * 2, k ? 1 : st);
            }
            WG_COMMIT();
            if (st == 6 * V) {
                mbar_wait(bars + 8 * (B_FULLW + ((st + 1) & 3)), V);
                mbar_wait(bars + 8 * (B_FULLX + 2 * V + 1), V);
            } else {
                WG_WAIT(1);
                mbar_arrive_if(bars + 8 * (B_EMPTYW + 2 * V), lane == 0 && st == 6 * V + 1);
                mbar_arrive_if(bars + 8 * (B_EMPTYX + 2 * V), lane == 0 && st == 6 * V + 1);
                WG_WAIT(0);
                mbar_arrive_if(bars + 8 * (B_EMPTYW + (st & 3)), lane == 0);
                mbar_arrive_if(bars + 8 * (B_EMPTYX + 2 * V + (st & 1)), lane == 0);
                if (st < 7) {
                    mbar_wait(bars + 8 * (B_FULLW + ((st + 1) & 3)), (st + 1) >> 2);
                    mbar_wait(bars + 8 * (B_FULLX + 2 * V + ((st + 1) & 1)), ((st + 1) >> 1) & 1);
                }
            }
        }
        WG_WAIT(0);
        fence_acc(ag); fence_acc(au);
        STAMP(8 * V + 1); GSTAMP(29 + V);
        float cg0 = ag[84], cg1 = ag[86], cu0 = au[84], cu1 = au[86];
        const uint32_t ca = sb + OFF_CSUM + (8 * w + g) * 16;
        if (V == 0) { sts128(ca, FU(cg0), FU(cg1), FU(cu0), FU(cu1)); mbar_arrive(bars + 8 * B_CS); }
        else { mbar_wait(bars + 8 * B_CS, 0); const uint4 t = lds128(ca); cg0 = UF(t.x); cg1 = UF(t.y); cu0 = UF(t.z); cu1 = UF(t.w); }
        mbar_wait(bars + 8 * B_STATS, 0);
        mbar_wait(bars + 8 * (B_EMPTYX + 2 * V), 1);
        STAMP(13 + V);
        const uint32_t hs = xb + (2 * w + ((lane >> 3) & 1)) * (2688 + 128 * V) + (lane >> 4) * 128 + (lane & 7) * 16;
        const uint32_t sa = sb + OFF_ST + (168 * V + 2 * q) * 8;
        uint4 sq[22];
        #pragma unroll
        for (int j = 0; j < 3; j++) sq[j] = lds128(sa + j * 64);
        #pragma unroll
        for (int j = 0; j < 22; j += 2) {
            uint32_t o[4];
            #pragma unroll
            for (int jj = 0; jj < 2; jj++) {
                const uint4 sv = sq[j + jj];
                float sg[4], uc[4];
                #pragma unroll
                for (int i = 0; i < 4; i++) {
                    const float m = UF((i & 1) ? sv.z : sv.x);
                    const float gh = fmaf(-m, (i & 2) ? cg1 : cg0, ag[4 * (j + jj) + i]) * UF((i & 1) ? sv.w : sv.y);
                    sg[i] = fmaf(gh, tanh_fast(gh), gh);
                    uc[i] = fmaf(-m, (i & 2) ? cu1 : cu0, au[4 * (j + jj) + i]);
                }
                asm("mul.rn.bf16x2 %0, %1, %2;" : "=r"(o[2 * jj]) : "r"(pack2(sg[0], sg[1])), "r"(pack2(uc[0], uc[1])));
                asm("mul.rn.bf16x2 %0, %1, %2;" : "=r"(o[2 * jj + 1]) : "r"(pack2(sg[2], sg[3])), "r"(pack2(uc[2], uc[3])));
            }
            #pragma unroll
            for (int k = (j ? 3 + 3 * j / 2 : 3); k < 6 + 3 * j / 2 && k < 22; k++) sq[k] = lds128(sa + k * 64);
            uint32_t ad = hs + j * 128;
            if (j == 20 && V == 0 && lane >= 16) ad = xb + 21504 + (lane & 7) * 16;
            stsm4(ad, o[0], o[1], o[2], o[3]);
        }
        fence_async_smem();
        mbar_arrive(bars + 8 * (B_EPI + V));
        STAMP(8 * V + 2);
    }
    if (c >= 128) return;
    {
        mbar_wait(bars + 8 * B_CONV, 0);
        uint32_t r0[8], r1[8];
        #pragma unroll
        for (int i = 0; i < 8; i++) asm volatile("" : "=r"(r1[i]));
        #pragma unroll 1
        for (int e = 0; e < 2; e++) {
            #pragma unroll
            for (int i = 0; i < 8; i++) r0[i] = r1[i];
            conv_channel(sb + OFF_CONV + (2 * V + e) * CH_STRIDE, w, lane, r1, 2 * V + e);
            if (e == 0) STAMP(8 * V + 3);
        }
        const int gam = g >> 2, qq = gam ? ((q + 3) & 3) : q;
        const uint32_t sp = sb + OFF_CONV + V * OFF_SST + ((63 - 4 * gam - qq) * 16 + 4 * (w ^ (3 - qq)) + (g & 3)) * 8;
        bar_sync(3 + V);
        #pragma unroll
        for (int a2 = 0; a2 < 8; a2++) sts64(sp - a2 * 1024, r0[a2], r1[a2]);
        fence_async_smem();
        mbar_arrive(bars + 8 * (B_SIG + V));
        STAMP(8 * V + 4); GSTAMP(35 + V);
    }
    if (V == 1) return;
    {
        const int tau = c >> 2, dg = c & 3;
        const uint32_t row = 8 * (w & 1) + 32 * (w >> 1);
        float acc[64];
        define_acc(acc);
        const float rr0 = __ldcg(&P.st[64 * tau + row + g].y), rr1 = __ldcg(&P.st[64 * tau + row + g + 16].y);
        mbar_wait(bars + 8 * B_FULLD, 0);
        STAMP(5); GSTAMP(27);
        uint64_t dB = mkdesc(sb + wd_slot(0), 8192, 1024, 1), dA = mkdesc(sb + h_slot(0), 1024, 128, 0);
        int sd = 0; uint32_t np = 0;
        #pragma unroll 1
        for (int st = 0; st < 21; st++) {
            WG_FENCE();
            wg_tt128(acc, dA, dB, st);
            wg_tt128(acc, dA + 128, dB + 128, 1);
            wg_tt128(acc, dA + 256, dB + 256, 1);
            wg_tt128(acc, dA + 384, dB + 384, 1);
            WG_COMMIT();
            uint32_t ro = bars + 8 * (B_EMPTYD + (sd ? sd - 1 : 6)), m = lane == 0 && st > 0, ok;
            if (++sd == 7) { sd = 0; np ^= 1; }
            const uint32_t nb = bars + 8 * (B_FULLD + sd);
            dB = mkdesc(sb + wd_slot(sd), 8192, 1024, 1); dA = mkdesc(sb + h_slot(sd), 1024, 128, 0);
            asm volatile("{.reg .pred p; mbarrier.test_wait.parity.shared::cta.b64 p, [%5], %6; vote.sync.all.pred p, p, -1; selp.u32 %0, 1, 0, p;}"
                : "=r"(ok), "+l"(dA), "+l"(dB), "+r"(ro), "+r"(m) : "r"(nb), "r"(np) : "memory");
            WG_WAIT(1);
            mbar_arrive_if(ro, m);
            if (!ok) mbar_wait(nb, np);
            if (w == 0) STAMP2(20 + st);
        }
        WG_FENCE();
        wg_tt128(acc, dA, dB, 1);
        wg_tt128(acc, dA + 128, dB + 128, 1);
        WG_COMMIT();
        mbar_wait(bars + 8 * B_XO, 0);
        const uint32_t xo = sb + OFF_XO + (row + (lane & 7) + 16 * ((lane >> 3) & 1)) * 128;
        const uint32_t so = sb + OFF_SI + (w >> 1) * 8192 + q * 256 + (g & 1) * 8;
        const uint32_t sx = (4 * (w & 1) + (g >> 1)) ^ (2 * q) ^ (2 * ((2 * tau + (w >> 1)) & 3));
        uint32_t xr[8][4];
        uint2 sv[16];
        #pragma unroll
        for (int j = 0; j < 16; j += 2) {
            ldsm4(xr[j >> 1], xo + (j >> 3) * 8192 + ((((j & 7) + (lane >> 4)) ^ (lane & 7)) << 4));
            sv[j] = lds64(so + j * 512 + (sx << 4));
            sv[j + 1] = lds64(so + j * 512 + 128 + ((sx ^ 1) << 4));
        }
        WG_WAIT(0);
        fence_acc(acc);
        STAMP(6); GSTAMP(28);
        #pragma unroll
        for (int j = 0; j < 16; j += 2) {
            #pragma unroll
            for (int i = 0; i < 4; i++) {
                const int jj = j + (i >> 1), hh = i & 1;
                const float f0 = acc[4 * jj + 2 * hh] * (hh ? rr1 : rr0), f1 = acc[4 * jj + 2 * hh + 1] * (hh ? rr1 : rr0);
                const uint32_t G = pack2(fmaf(f0, tanh_fast(f0), f0), fmaf(f1, tanh_fast(f1), f1));
                const uint32_t s2 = __byte_perm(sv[jj].x, sv[jj].y, hh ? 0x7632 : 0x5410);
                asm("fma.rn.bf16x2 %0, %1, %2, %0;" : "+r"(xr[j >> 1][i]) : "r"(s2), "r"(G));
            }
            stsm4(xo + (j >> 3) * 8192 + ((((j & 7) + (lane >> 4)) ^ (lane & 7)) << 4), xr[j >> 1][0], xr[j >> 1][1], xr[j >> 1][2], xr[j >> 1][3]);
        }
        __syncwarp();
        {
            const uint32_t rr = row + ((lane >> 4) << 4), la = sb + OFF_XO + rr * 128 + ((lane >> 3) & 1) * 8192;
            uint4* dst = (uint4*)(P.out + (64 * tau + rr) * DM + 128 * dg) + (lane & 15);
            uint4 v[8];
            #pragma unroll
            for (int i = 0; i < 8; i++) v[i] = lds128(la + i * 128 + (((lane & 7) ^ i) << 4));
            #pragma unroll
            for (int i = 0; i < 8; i++) dst[i * 64] = v[i];
        }
        STAMP(7); GSTAMP(23);
    }
}

__device__ __forceinline__ float2 cexp_p(float re2, float im, float p) {
    float sn, cs;
    const float mag = ex2(re2 * p), th = im * p;
    asm("sin.approx.ftz.f32 %0, %1;" : "=f"(sn) : "f"(th));
    asm("cos.approx.ftz.f32 %0, %1;" : "=f"(cs) : "f"(th));
    return make_float2(mag * cs, mag * sn);
}
struct SsmRaw { unsigned short la, ai, cr, ci, ldt, dsk; };
__device__ __forceinline__ unsigned short ldu16(const void* p) { unsigned short v; asm volatile("ld.global.nc.u16 %0, [%1];" : "=h"(v) : "l"(p)); return v; }
__device__ __forceinline__ float2 cmul(float2 a, float2 b) { return make_float2(fmaf(a.x, b.x, -a.y * b.y), fmaf(a.x, b.y, a.y * b.x)); }
__device__ __forceinline__ float2 csqr(float2 a) { const float t = a.x * a.y; return make_float2(fmaf(a.x, a.x, -a.y * a.y), t + t); }
__device__ __forceinline__ void mma16816(float (&d)[4], const uint32_t (&a)[4], uint32_t b0, uint32_t b1) {
    asm volatile("mma.sync.aligned.m16n8k16.row.col.f32.bf16.bf16.f32 {%0,%1,%2,%3}, {%4,%5,%6,%7}, {%8,%9}, {%0,%1,%2,%3};"
        : "+f"(d[0]), "+f"(d[1]), "+f"(d[2]), "+f"(d[3]) : "r"(a[0]), "r"(a[1]), "r"(a[2]), "r"(a[3]), "r"(b0), "r"(b1));
}

__device__ __forceinline__ void layer_norm(uint32_t sb, uint32_t cb, int w, int lane, const Params& P) {
    const uint32_t bars = sb + OFF_BAR;
    const int c = blockIdx.x;
    mbar_wait(bars + 8 * (B_LNX + w), 0);
    STAMP(34);
    {
        const uint32_t ra = cb + CH_LN + (w & 1) * 64 + (lane >> 3) * 1040 + (lane & 7) * 16;
        float s0 = 0.f, s1 = 0.f, a0 = 0.f, a1 = 0.f;
        #pragma unroll 1
        for (int k = 0; k < 1024; k += 512) {
            uint32_t v[16];
            #pragma unroll
            for (int j = 0; j < 4; j++) *(uint4*)&v[4 * j] = lds128(ra + k + 128 * j);
            #pragma unroll
            for (int i = 0; i < 16; i++) { const float t0 = bf_lo(v[i]), t1 = bf_hi(v[i]); s0 += t0; s1 += t1; a0 = fmaf(t0, t0, a0); a1 = fmaf(t1, t1, a1); }
        }
        s0 += s1; a0 += a1;
        #pragma unroll
        for (int o = 4; o; o >>= 1) { s0 += __shfl_xor_sync(0xffffffffu, s0, o); a0 += __shfl_xor_sync(0xffffffffu, a0, o); }
        s0 *= 1.f / DM;
        float sd, ri;
        asm("sqrt.approx.ftz.f32 %0, %1;" : "=f"(sd) : "f"(bf_round(bf_round(fmaxf(fmaf(-s0, s0, a0 * (1.f / DM)), 0.f)) + 1e-5f)));
        asm("rcp.approx.ftz.f32 %0, %1;" : "=f"(ri) : "f"(bf_round(sd)));
        if ((lane & 7) == 0) {
            const float2 sv = make_float2(bf_round(s0), 0.5f * ri);
            sts64(sb + OFF_CSUM + (w + 4 * (lane >> 3)) * 8, FU(sv.x), FU(sv.y));
            P.st[16 * (c & ~1) + 8 * (c & 1) + 16 + w + ((lane >> 1) & 4) - (lane & 16)] = sv;
        }
    }
    STAMP(62);
    bar_sync(2);
    const int r = 4 * ((lane & 7) >> 1) + (lane & 1) + 2 * ((lane >> 3) & 1);
    const uint32_t ad = sb + OFF_CONV + (r & 3) * CH_STRIDE + CH_LN + (r & 1) * 64 + (r >> 2) * 1040 + (16 * w + (lane >> 4)) * 16;
    const uint4 sa = lds128(sb + OFF_CSUM + (lane & 3) * 32), sc = lds128(sb + OFF_CSUM + (lane & 3) * 32 + 16);
    const uint32_t m2[2] = {__byte_perm(sa.x, sa.z, 0x7632), __byte_perm(sc.x, sc.z, 0x7632)};
    const float ri[4] = {2.f * UF(sa.y), 2.f * UF(sa.w), 2.f * UF(sc.y), 2.f * UF(sc.w)};
    uint2* dst = (uint2*)(P.xnT + (128 * w + (lane >> 2)) * 256 + (c & 1) * 128 + 126 - (c & ~1)) + (lane & 3);
    #pragma unroll 1
    for (int i = 0; i < 8; i += 4) {
        uint32_t v[4][4];
        #pragma unroll
        for (int j = 0; j < 4; j++)
            asm volatile("ldmatrix.sync.aligned.m8n8.x4.trans.shared.b16 {%0,%1,%2,%3}, [%4];" : "=r"(v[j][0]), "=r"(v[j][1]), "=r"(v[j][2]), "=r"(v[j][3]) : "r"(ad + 32 * (i + j)) : "memory");
        #pragma unroll
        for (int j = 0; j < 4; j++) {
            #pragma unroll
            for (int k = 0; k < 4; k++) {
                uint32_t dv; asm("sub.rn.bf16x2 %0, %1, %2;" : "=r"(dv) : "r"(v[j][k]), "r"(m2[k & 1]));
                v[j][k] = pack2(bf_lo(dv) * ri[2 * (k & 1)], bf_hi(dv) * ri[2 * (k & 1) + 1]);
            }
            dst[(i + j) * 16 * 512] = make_uint2(v[j][0], v[j][1]); dst[(i + j) * 16 * 512 + 8 * 512] = make_uint2(v[j][2], v[j][3]);
        }
    }
    mbar_arrive(bars + 8 * B_LN);
    STAMP(16);
}

__device__ __forceinline__ void kernel_gen(uint32_t fs, int lane, const SsmRaw& raw, float (&dacc)[2][3][4], const char* pf) {
    const float dt = bf_round(ex2(bf_lo(raw.ldt) * 1.4426950408889634f));
    const float re2 = bf_round(ex2(bf_lo(raw.la) * 1.4426950408889634f)) * dt * -1.4426950408889634f, im = bf_lo(raw.ai) * dt;
    const float2 C = make_float2(bf_lo(raw.cr) * (dt + dt), bf_lo(raw.ci) * -(dt + dt));
    STAMP(56);
    const float2 y1 = cexp_p(re2, -im, 1.f), y256 = cexp_p(re2, -im, 256.f), z64 = cexp_p(re2, im, 64.f);
    const uint32_t fm = fs + (lane >> 3) * 144 + (lane & 7) * 16;
#define PK(v) pack2((v).x, (v).y)
    const float2 y2 = csqr(y1), y4 = csqr(y2), y8 = csqr(y4);
    const float2 l1 = cmul(C, y1), l2 = cmul(C, y2), l3 = cmul(l1, y2);
    stsm4(fm, PK(C), PK(l1), PK(l2), PK(l3));
    stsm4(fm + 4 * 144, PK(cmul(C, y4)), PK(cmul(l1, y4)), PK(cmul(l2, y4)), PK(cmul(l3, y4)));
    const float2 t0 = cmul(C, y256), t1 = cmul(t0, y256), t2 = cmul(t1, y256), t3_ = cmul(t2, y256);
    const float2 u1 = cmul(t0, y2), u2 = cmul(u1, y2), u3 = cmul(u2, y2);
    stsm4(fm + 8 * 144, PK(t0), PK(u1), PK(u2), PK(u3));
    stsm4(fm + 12 * 144, PK(t1), PK(cmul(t1, y4)), PK(t2), PK(cmul(t2, y4)));
    const float2 v0 = cmul(t3_, y8), v1 = cmul(v0, y256), v2 = cmul(v1, y256), v3 = cmul(v2, y256);
    stsm4(fm + 16 * 144, PK(v0), PK(v1), PK(v2), PK(v3));
    stsf(fs + lane * 4 + 20 * 144, UF(PK(t3_)));
    STAMP(57);
    if (pf) asm volatile("prefetch.global.L2 [%0];" :: "l"(pf));
    const uint32_t ldb = fs + (lane & 7) * 144 + ((lane >> 3) & 1) * 16 + (lane >> 4) * 8 * 144;
    const float p8 = (float)(2 * (lane & 28));
    __syncwarp();
    #pragma unroll KUNR_
    for (int ks = 0; ks < 4; ks++) {
        uint32_t b01[4], b2[2], a0[4], a1[4];
        ldsm4(b01, ldb + ks * 32);
        asm volatile("ldmatrix.sync.aligned.m8n8.x2.shared.b16 {%0,%1}, [%2];" : "=r"(b2[0]), "=r"(b2[1]) : "r"(ldb + 16 * 144 + ks * 32) : "memory");
        #pragma unroll
        for (int mh = 0; mh < 2; mh++) {
            const int src = 8 * ks + 4 * mh + (lane & 3);
            const float2 z = make_float2(__shfl_sync(0xffffffffu, z64.x, src), __shfl_sync(0xffffffffu, z64.y, src));
            const float2 R0 = cexp_p(__shfl_sync(0xffffffffu, re2, src), __shfl_sync(0xffffffffu, im, src), p8);
            const float2 R1 = cmul(R0, z), R2 = cmul(R1, z), R3 = cmul(R2, z);
            a0[2 * mh] = PK(R0); a0[2 * mh + 1] = PK(R1); a1[2 * mh] = PK(R2); a1[2 * mh + 1] = PK(R3);
        }
        mma16816(dacc[0][0], a0, b01[0], b01[1]); mma16816(dacc[1][0], a1, b01[0], b01[1]);
        mma16816(dacc[0][1], a0, b01[2], b01[3]); mma16816(dacc[1][1], a1, b01[2], b01[3]);
        mma16816(dacc[0][2], a0, b2[0], b2[1]);   mma16816(dacc[1][2], a1, b2[0], b2[1]);
    }
#undef PK
    STAMP(58);
}

__device__ __forceinline__ void aux_role(uint32_t sb, int w, float (&dacc)[2][3][4], float dsk, const Params& P) {
    const int lane = threadIdx.x & 31, q = lane & 3, g = lane >> 2;
    const int c = blockIdx.x;
    const uint32_t bars = sb + OFF_BAR;
    if (c >= 128) { mbar_arrive(bars + 8 * B_LN); return; }
    {
        const uint32_t cb = sb + OFF_CONV + w * CH_STRIDE;
        layer_norm(sb, cb, w, lane, P);
        {
            uint4 v[2][3];
            #pragma unroll
            for (int i = 0; i < 3; i++) v[0][i] = lds128(cb + CH_PART + lane * 16 + i * 512);
            #pragma unroll
            for (int k = 0; k < 6; k++) {
                #pragma unroll
                for (int i = 0; i < 3; i++) if (k < 5) v[(k + 1) & 1][i] = lds128(cb + CH_PART + lane * 16 + (k + 1) * 1536 + i * 512);
                #pragma unroll
                for (int i = 0; i < 3; i++) {
                    float* d = &dacc[0][0][0] + 12 * (k & 1) + 4 * i;
                    d[0] += UF(v[k & 1][i].x); d[1] += UF(v[k & 1][i].y); d[2] += UF(v[k & 1][i].z); d[3] += UF(v[k & 1][i].w);
                }
            }
        }
        __syncwarp();
        STAMP(18);
        const uint32_t sF = cb + CH_A3, sG = cb + CH_G;
        if (lane == 0) dacc[0][0][0] += dsk;
        if (lane < 10) sts128(sG + 128 + (lane & 1) * 208 + (lane >> 1) * 16, 0, 0, 0, 0);
        const uint32_t f0 = sF + (8 * g + 2 * q) * 4, f1 = sF + ((q < 2) ? 256 + 4 * g + 2 * q : 256 + 2 * g + 64 * q) * 4, st1 = (q < 2) ? 128 : 64;
        const uint32_t ga = sG + ((g & 1) ? 0 : 208) + (63 - (g >> 1) - 32 * q) * 2;
        #pragma unroll
        for (int i = 0; i < 4; i++) {
            const int mu = i >> 1, hh = i & 1;
            sts64(f0 + i * 256, FU(dacc[mu][0][2 * hh]), FU(dacc[mu][0][2 * hh + 1]));
            sts64(f1 + i * st1, FU(dacc[mu][1][2 * hh]), FU(dacc[mu][1][2 * hh + 1]));
            const uint32_t pk = pack2(dacc[mu][2][2 * hh], dacc[mu][2][2 * hh + 1]);
            if (q < 2) { sts16(ga - 8 * i, pk & 0xffff); sts16(ga - 8 * i - 32, pk >> 16); }
        }
        if (lane == 2) stsf(sF + 2048, dacc[0][2][0]);
        STAMP(19);
        bar_sync(2);
    }
    const int u = min(lane, 30) - 15, r2 = (u + ((u >> 1) & 1)) >> 1, r4 = (u + 1 + ((u >> 2) & 1)) >> 2, xt = 1024 + 16 * w + u;
    const uint32_t o0 = CH_A3 + 4 * (w == 0 ? u : w == 1 ? 256 + r2 : 256 + 64 * w + r4), ost = w == 0 ? 64 : w == 1 ? 32 : 16;
    const uint32_t oa0 = u >= 0 || w == 3 ? o0 : CH_A3 + 4 * (w == 1 ? 256 + u : w == 2 ? 384 + r2 : 0);
    const uint32_t ot = CH_A3 + 4 * min(512, 256 + ((xt + 1 + ((xt >> 2) & 1)) >> 2));
    const int kap = (lane >> 4) * 8 + ((lane >> 1) & 7), gam = lane & 1, hh = w >> 1, wp = w & 1;
    const uint32_t oa = CH_U + wp * UPLANE + (127 - 4 * kap - 2 * gam - hh) * 16;
    const uint32_t ob = CH_U + (wp ^ 1) * UPLANE + (128 - wp - 4 * kap - 2 * gam - hh) * 16;
    const uint32_t od = CH_A3 + (4 * wp + hh) * 512 + (kap >> 3) * 256 + (kap & 7) * 16 + gam * 8;
    const int tid = threadIdx.x & 127;
    const uint32_t og = CH_G + (tid >= 24) * 16 + min(tid, 47) * 8, cend = sb + OFF_CONV + 3 * CH_STRIDE;
    {
        float nx[17]; uint2 n0, n1;
#define LDT(b) nx[0] = ldsf((b) + oa0); nx[16] = ldsf((b) + ot); _Pragma("unroll") for (int s = 1; s < 16; s++) nx[s] = ldsf((b) + o0 + s * ost); n0 = lds64((b) + og); n1 = lds64((b) + og + 8)
        LDT(sb + OFF_CONV);
        #pragma unroll 1
        for (uint32_t cb = sb + OFF_CONV; cb <= cend; cb += CH_STRIDE) {
            float kv[17];
            #pragma unroll
            for (int s = 0; s < 17; s++) kv[s] = nx[s];
            if (tid < 48) sts128(cb + CH_B3 + tid * 16, n0.x, n0.y, n1.x, n1.y);
            LDT(min(cb + CH_STRIDE, cend));
            if (u < 0 && w == 0) kv[0] = 0.f;
            if (xt > 1028) kv[16] = 0.f;
            uint32_t o[17];
            #pragma unroll
            for (int s = 0; s < 17; s++) o[s] = pack2(kv[s], __shfl_up_sync(0xffffffffu, kv[s], 1));
            if (lane > 0 && lane < 31) {
                const uint32_t ta = cb + CH_T + (lane - 1) * 280;
                #pragma unroll
                for (int s2 = 0; s2 < 8; s2++) sts64(ta + 64 * w + s2 * 8, o[2 * s2], o[2 * s2 + 1]);
                stsf(ta + 256 + 4 * w, UF(o[16]));
            }
        }
#undef LDT
    }
    STAMP(61);
    if (lane < 8) sts128(sb + OFF_CONV + w * CH_STRIDE + CH_U + 2048 + (lane & 4) * (UPLANE / 4) + (lane & 3) * 16, 0, 0, 0, 0);
    mbar_wait(bars + 8 * B_U, 0);
    bar_sync(2);
    STAMP(17);
    uint2 n0 = lds64(sb + OFF_CONV + ob + 24), n3 = lds64(sb + OFF_CONV + oa);
    uint4 n1 = lds128(sb + OFF_CONV + oa + 16), n2 = lds128(sb + OFF_CONV + ob);
    #pragma unroll 1
    for (uint32_t cb = sb + OFF_CONV; cb <= cend; cb += CH_STRIDE) {
        const uint32_t r[12] = {n0.x, n0.y, n1.x, n1.y, n1.z, n1.w, n2.x, n2.y, n2.z, n2.w, n3.x, n3.y}, nb = min(cb + CH_STRIDE, cend);
        n0 = lds64(nb + ob + 24); n3 = lds64(nb + oa); n1 = lds128(nb + oa + 16); n2 = lds128(nb + ob);
        float p[24];
        p[0] = 0.f; p[1] = bf_lo(r[0]);
        #pragma unroll
        for (int i = 2; i < 24; i++) p[i] = p[i - 1] + ((i & 1) ? bf_lo(r[i >> 1]) : bf_hi(r[(i - 1) >> 1]));
        #pragma unroll
        for (int i = 0; i < 8; i += 4) {
            sts64(cb + od + i * 256, pack2(p[i + 9] - p[i], p[i + 10] - p[i + 1]), pack2(p[i + 11] - p[i + 2], p[i + 12] - p[i + 3]));
            sts64(cb + od + i * 256 + 128, pack2(p[i + 16] - p[i + 9], p[i + 17] - p[i + 10]), pack2(p[i + 18] - p[i + 11], p[i + 19] - p[i + 12]));
        }
    }
    fence_async_smem();
    mbar_arrive(bars + 8 * B_CONV);
    STAMP(21);
}

__device__ __forceinline__ void store_h(uint32_t sb, const Params& P, const Maps& M, int V, int tg, int fb) {
    const uint32_t bars = sb + OFF_BAR;
    mbar_wait(bars + 8 * (B_EPI + V), 0);
    STAMP2(3 + 2 * V);
    asm volatile("cp.async.bulk.tensor.3d.global.shared::cta.bulk_group [%0, {%2, %3, %4}], [%1];"
        :: "l"(&M.hst[V]), "r"(sb + OFF_X + V * 2 * XBUF), "r"(0), "r"(43 * tg + 21 * V), "r"(8 * fb) : "memory");
    flag_signal(P.flags, F_H + 2 * tg + V);
    mbar_arrive(bars + 8 * (B_STG + V));
    STAMP2(4 + 2 * V);
}

__global__ void __launch_bounds__(512, 1)
fused_kernel(const __grid_constant__ Params P, const __grid_constant__ Maps M) {
    extern __shared__ __align__(1024) uint8_t smem_raw[];
    const uint32_t sb = smem_u32(smem_raw);
    const uint32_t bars = sb + OFF_BAR;
    const int warp = __shfl_sync(0xffffffffu, threadIdx.x >> 5, 0);
    const int c = blockIdx.x, tg = c / 22, fb = c - 22 * tg;
    SsmRaw raw;
    {
        const int d = min(4 * c + (warp & 3), DM - 1), o = d * 128 + (warp >> 2) * 32 + (threadIdx.x & 31);
        raw.la = ldu16(P.logA + o); raw.ai = ldu16(P.Aim + o); raw.cr = ldu16(P.Cr + o); raw.ci = ldu16(P.Ci + o);
        raw.ldt = ldu16(P.logdt + d); raw.dsk = ldu16(P.Dskip + d);
    }
    if (elect_one()) {
        if (warp == 0) { STAMP(24); GSTAMP(22); }
        asm volatile("" :: "l"(((const uint64_t*)&P)[warp < 15 ? warp : 0]));
        if (warp < 10) asm volatile("prefetch.tensormap [%0];" :: "l"(&M.x[0] + warp) : "memory");
        #pragma unroll
        for (int k = 0; k < 4; k++) {
            const int i = 16 * k + ((warp + 4) & 15);
            const uint32_t cnt = i >= B_LNX ? 1 : i >= B_CONV ? 128 : ((0xf0ull >> i) & 1) ? 8 : ((0xff0000ull >> i) & 1) ? 2 : ((0x3e00ff00f000ull >> i) & 1) ? 4 : 1;
            asm volatile("mbarrier.init.shared::cta.b64 [%0], %1;" :: "r"(bars + 8 * i), "r"(cnt) : "memory");
        }
        asm volatile("fence.mbarrier_init.release.cluster; fence.proxy.async.shared::cta;" ::: "memory");
        if (warp == 12 || warp == 13) {
            const uint32_t s = warp - 12;
            mbar_expect(bars + 8 * (B_FULLW + s), 16384);
            tma2d(sb + OFF_W + s * 16384, &M.wg, 64 * fb, 64 * s, bars + 8 * (B_FULLW + s));
            tma2d(sb + OFF_W + s * 16384 + 8192, &M.wu, 64 * fb, 64 * s, bars + 8 * (B_FULLW + s));
            STAMP(31);
        } else if (warp >= 4 && warp < 7) {
            const uint32_t s = warp - 4, V = s >> 1;
            mbar_expect(bars + 8 * (B_FULLX + s), (168 + 8 * V) * 128);
            tma2d(sb + OFF_X + s * XBUF, &M.x[V], 64 * (s & 1), TOKG * tg + 168 * V, bars + 8 * (B_FULLX + s));
        } else if ((warp >> 2) == 2 && c < 128) {
            const int w = warp & 3;
            mbar_expect(bars + 8 * (B_LNX + w), 4096);
            #pragma unroll
            for (int i = 0; i < 4; i++)
                bulk_load(sb + OFF_CONV + w * CH_STRIDE + CH_LN + (w & 1) * 64 + i * 1040,
                          P.x + (16 * (c & ~1) + 8 * (c & 1) + 16 + w + 4 * (i & 1) - 8 * (i & 2)) * DM, 1024, bars + 8 * (B_LNX + w));
        }
        if (sb & 1023) __trap();
    }
    if (warp < 4) sts128(sb + OFF_X + (warp >> 1) * XBUF + 168 * 128 + (threadIdx.x & 63) * 16, 0x3f803f80u, 0x3f803f80u, 0x3f803f80u, 0x3f803f80u);
    float dacc[2][3][4];
    #pragma unroll
    for (int i = 0; i < 24; i++) (&dacc[0][0][0])[i] = 0.f;
    if (c < 128) {
        const int wg = warp >> 2;
        const uint32_t fs = sb + OFF_CONV + (warp & 3) * CH_STRIDE + (wg == 2 ? CH_LNT : CH_PART + min(wg, 2) * CH_PSZ);
        const int ln = threadIdx.x & 63;
        kernel_gen(fs, threadIdx.x & 31, raw, dacc, (wg == 3 && ln < 43) ? (const char*)((warp & 2) ? P.Wu : P.Wg) + 256 * FF * 2 + c * 5504 + ln * 128 : nullptr);
        if (wg != 2) {
            __syncwarp();
            #pragma unroll
            for (int i = 0; i < 6; i++) { const float* d = &dacc[0][0][0] + 4 * i; sts128(fs + (threadIdx.x & 31) * 16 + i * 512, FU(d[0]), FU(d[1]), FU(d[2]), FU(d[3])); }
        }
    }
    if (warp < 4) fence_async_smem();
    __syncthreads();
    if (warp < 8) {
        asm volatile("setmaxnreg.inc.sync.aligned.u32 208;");
        consumer(sb, warp, P, M);
        asm volatile("nanosleep.u32 1;");
    } else if (warp < 12) {
        asm volatile("setmaxnreg.dec.sync.aligned.u32 72;");
        STAMP(32);
        aux_role(sb, warp - 8, dacc, bf_lo(raw.dsk), P);
        asm volatile("nanosleep.u32 2;");
    } else {
        asm volatile("setmaxnreg.dec.sync.aligned.u32 24;");
        const int tau = c >> 2, dg = c & 3;
        if (elect_one()) {
            if (warp < 15) {
                if (warp == 12) {
                    #pragma unroll 1
                    for (int st = 2; st < 8; st++) {
                        const uint32_t s = st & 3, fb_ = bars + 8 * (B_FULLW + s);
                        mbar_wait(bars + 8 * (B_EMPTYW + s), (st >> 2) ^ 1);
                        mbar_expect(fb_, 16384);
                        tma2d(sb + OFF_W + s * 16384, &M.wg, 64 * fb, 64 * st, fb_);
                        tma2d(sb + OFF_W + s * 16384 + 8192, &M.wu, 64 * fb, 64 * st, fb_);
                    }
                } else {
                    const int V = warp - 13;
                    #pragma unroll 1
                    for (int st = 2 - V; st < 8; st++) {
                        const uint32_t s = 2 * V + (st & 1);
                        mbar_wait(bars + 8 * (B_EMPTYX + s), ((st >> 1) & 1) ^ 1);
                        mbar_expect(bars + 8 * (B_FULLX + s), (168 + 8 * V) * 128);
                        tma2d(sb + OFF_X + s * XBUF, &M.x[V], 64 * st, TOKG * tg + 168 * V, bars + 8 * (B_FULLX + s));
                    }
                }
                if (warp == 14) store_h(sb, P, M, 1, tg, fb);
                if (c < 128 && warp < 14) {
                    if (warp == 13) {
                        mbar_wait(bars + 8 * (B_STG + 1), 0);
                        #pragma unroll 1
                        for (int o = 8 * tau; o < 8 * tau + 8; o += 7) flag_wait(P.flags, F_H + 2 * (o / 43) + ((o % 43) >= 21), 22);
                        mbar_arrive(bars + 8 * B_HF);
                        STAMP(25); GSTAMP(37);
                    }
                    #pragma unroll 1
                    for (int st = 0; st < 22; st += (st < 6 || (st == 6 && warp == 13)) ? 1 : 2) {
                        const int rd = (st >= 7) + (st >= 14) + (st >= 21), sd = st - 7 * rd;
                        const uint32_t fb_ = bars + 8 * (B_FULLD + sd);
                        if (rd) mbar_wait(bars + 8 * (B_EMPTYD + sd), (rd & 1) ^ 1);
                        else if (warp == 12 || st == 6) mbar_wait(bars + 8 * (uint32_t)((0x3623070d060504ull >> (8 * st)) & 0xff), st < 5);
                        if (st >= 10 && st < 21) STAMP2(31 + st);
                        if (rd || warp == 13) {
                            mbar_expect(fb_, 8192);
                            asm volatile("cp.async.bulk.tensor.5d.shared::cluster.global.mbarrier::complete_tx::bytes [%0], [%1, {%3, %3, %3, %4, %5}], [%2];"
                                :: "r"(sb + h_slot(sd)), "l"(&M.hld), "r"(fb_), "r"(0), "r"(2 * tau), "r"(8 * st) : "memory");
                        }
                        if (rd || warp == 12) {
                            const uint32_t da = sb + wd_slot(sd);
                            mbar_expect(fb_, 16384);
                            tma2d(da, &M.wd, 128 * dg, 64 * st, fb_);
                            tma2d(da + 8192, &M.wd, 128 * dg + 64, 64 * st, fb_);
                        }
                    }
                } else if (c < 128) {
                    mbar_wait(bars + 8 * (B_SIG + 1), 0);
                    mbar_expect(bars + 8 * B_XO, 32768);
                    tma2d(sb + OFF_XO, &M.xo, 128 * dg, 64 * tau, bars + 8 * B_XO);
                    tma2d(sb + OFF_XO + 8192, &M.xo, 128 * dg + 64, 64 * tau, bars + 8 * B_XO);
                    mbar_wait(bars + 8 * B_SST, 0);
                    flag_wait(P.flags, F_S + dg, 64);
                    STAMP(26);
                    asm volatile("cp.async.bulk.tensor.5d.shared::cluster.global.mbarrier::complete_tx::bytes [%0], [%1, {%3, %3, %3, %4, %5}], [%2];"
                        :: "r"(sb + OFF_SI), "l"(&M.sld), "r"(bars + 8 * B_XO), "r"(0), "r"(8 * dg), "r"(2 * tau) : "memory");
                    mbar_wait(bars + 8 * B_HF, 0);
                    exit_count(P.flags);
                }
            } else {
                mbar_wait(bars + 8 * B_LN, 0);
                STAMP2(0);
                asm volatile("fence.acq_rel.gpu; red.relaxed.gpu.global.add.u32 [%0], 1;" :: "l"(P.flags + F_A * 32) : "memory");
                if (c < 128) asm volatile("cp.async.bulk.prefetch.L2.global [%0], %1;" :: "l"(P.Wd + c * (FF * DM / 128)), "r"(FF * DM / 64) : "memory");
                STAMP2(2);
                flag_wait(P.flags, F_A, NCTA);
                asm volatile("fence.proxy.async.global;" ::: "memory");
                STAMP(20);
                mbar_expect(bars + 8 * B_STATS, TOKG * 8);
                bulk_load(sb + OFF_ST, P.st + TOKG * tg, TOKG * 8, bars + 8 * B_STATS);
                if (c < 128) {
                    mbar_expect(bars + 8 * B_U, 8 * 2048);
                    #pragma unroll 1
                    for (int i = 0; i < 8; i++)
                        bulk_load(sb + OFF_CONV + (i >> 1) * CH_STRIDE + CH_U + (i & 1) * UPLANE, P.xnT + 4 * c * 256 + i * 128, 2048, bars + 8 * B_U);
                } else exit_count(P.flags);
                store_h(sb, P, M, 0, tg, fb);
                if (c < 128) {
                    #pragma unroll 1
                    for (int V = 0; V < 2; V++) {
                        mbar_wait(bars + 8 * (B_SIG + V), 0);
                        STAMP2(7 + 2 * V);
                        bulk_store(P.S + (2 * c + V) * 1024, sb + OFF_CONV + V * OFF_SST, 8192);
                        flag_signal(P.flags, F_S + (c >> 5));
                        STAMP2(8 + 2 * V);
                    }
                    mbar_arrive(bars + 8 * B_SST);
                }
            }
            asm volatile("nanosleep.u32 0;");
        }
    }
}

typedef CUresult (*EncodeFn)(CUtensorMap*, CUtensorMapDataType, cuuint32_t, void*, const cuuint64_t*, const cuuint64_t*, const cuuint32_t*,
                             const cuuint32_t*, CUtensorMapInterleave, CUtensorMapSwizzle, CUtensorMapL2promotion, CUtensorMapFloatOOBfill);

void make_map(EncodeFn enc, CUtensorMap* m, const void* ptr, int rank, const cuuint64_t* dims, const cuuint64_t* strides, const cuuint32_t* box, bool swz, bool wide = false) {
    const cuuint32_t es[5] = {1, 1, 1, 1, 1};
    enc(m, CU_TENSOR_MAP_DATA_TYPE_BFLOAT16, rank, (void*)ptr, dims, strides, box, es, CU_TENSOR_MAP_INTERLEAVE_NONE,
        swz ? CU_TENSOR_MAP_SWIZZLE_128B : CU_TENSOR_MAP_SWIZZLE_NONE, wide ? CU_TENSOR_MAP_L2_PROMOTION_L2_256B : CU_TENSOR_MAP_L2_PROMOTION_L2_128B, CU_TENSOR_MAP_FLOAT_OOB_FILL_NONE);
}
void make_map2(EncodeFn enc, CUtensorMap* m, const void* ptr, cuuint64_t inner, cuuint64_t outer, cuuint32_t rows) {
    const cuuint64_t dims[2] = {inner, outer}, strides[1] = {inner * 2};
    const cuuint32_t box[2] = {64, rows};
    make_map(enc, m, ptr, 2, dims, strides, box, true, rows > 64);
}

}

extern "C" void kernel_launch(void* const* d_in, const int* in_sizes, int n_in, void* d_out, int out_size) {
    (void)in_sizes; (void)n_in; (void)out_size;
    static EncodeFn enc = nullptr;
    static void *hptr, *p_xnT, *p_st, *p_S, *p_flags;
    if (!enc) {
        cudaDriverEntryPointQueryResult qr;
        cudaGetDriverEntryPoint("cuTensorMapEncodeTiled", (void**)&enc, cudaEnableDefault, &qr);
        cudaFuncSetAttribute(fused_kernel, cudaFuncAttributeMaxDynamicSharedMemorySize, SMEM_BYTES);
        cudaGetSymbolAddress(&hptr, g_H); cudaGetSymbolAddress(&p_xnT, g_xnT); cudaGetSymbolAddress(&p_st, g_st);
        cudaGetSymbolAddress(&p_S, g_S); cudaGetSymbolAddress(&p_flags, g_flags);
    }
    Params P;
    P.x = (const __nv_bfloat16*)d_in[0]; P.logA = (const __nv_bfloat16*)d_in[1]; P.Aim = (const __nv_bfloat16*)d_in[2];
    P.Cr = (const __nv_bfloat16*)d_in[3]; P.Ci = (const __nv_bfloat16*)d_in[4]; P.logdt = (const __nv_bfloat16*)d_in[5];
    P.Dskip = (const __nv_bfloat16*)d_in[6];
    P.Wg = (const __nv_bfloat16*)d_in[8]; P.Wu = (const __nv_bfloat16*)d_in[9]; P.Wd = (const __nv_bfloat16*)d_in[10]; P.out = (__nv_bfloat16*)d_out; P.xnT = (uint4*)p_xnT; P.st = (float2*)p_st; P.S = (uint2*)p_S; P.flags = (unsigned*)p_flags;
    Maps M;
    make_map2(enc, &M.x[0], d_in[0], DM, SEQ, 168); make_map2(enc, &M.x[1], d_in[0], DM, SEQ, 176);
    make_map2(enc, &M.xo, d_in[0], DM, SEQ, 64);
    make_map2(enc, &M.wg, d_in[8], FF, DM, 64);     make_map2(enc, &M.wu, d_in[9], FF, DM, 64);
    make_map2(enc, &M.wd, d_in[10], DM, FF, 64);
    for (int v = 0; v < 2; v++) {
        const cuuint64_t dims[3] = {64, 256, 172}, strides[2] = {128, 32768};
        const cuuint32_t box[3] = {64, (cuuint32_t)(21 + v), 8};
        make_map(enc, &M.hst[v], hptr, 3, dims, strides, box, false);
    }
    {
        const cuuint64_t dims[5] = {64, 2, 4, 32, 64}, strides[4] = {4 * 8192, 8192, 8 * 8192, 128};
        const cuuint32_t box[5] = {64, 2, 4, 8, 2};
        make_map(enc, &M.sld, p_S, 5, dims, strides, box, true);
    }
    {
        const cuuint64_t dims[5] = {64, 2, 2, 64, 172}, strides[4] = {256, 128, 512, 32768};
        const cuuint32_t box[5] = {64, 2, 2, 2, 8};
        make_map(enc, &M.hld, hptr, 5, dims, strides, box, false);
    }
    fused_kernel<<<NCTA, 512, SMEM_BYTES>>>(P, M);
}
```
